```python
import torch

def _softmax(x, axis=-1):
    return torch.softmax(x, dim=axis)

def _gelu(x):
    return torch.nn.functional.gelu(x, approximate='tanh')

def _silu(x):
    return torch.nn.functional.silu(x)

def _sigmoid(x):
    return torch.sigmoid(x)

def _layernorm(x, axis=-1, eps=1e-05):
    m = x.mean(dim=axis, keepdim=True)
    v = x.var(dim=axis, keepdim=True, unbiased=False)
    return (x - m) / torch.sqrt(v + eps)

def _scatter_add(tgt, idx, src, axis=0):
    return tgt.clone().index_add_(axis, idx, src)

def _segment_sum(src, seg, n):
    out = torch.zeros((n,) + src.shape[1:], dtype=src.dtype)
    return out.index_add_(0, seg, src)

def _pad(x, pw):
    flat = tuple((v for pair in reversed(pw) for v in pair))
    return torch.nn.functional.pad(x, flat)
kernel_name = 'adaLN_cond__ssm_conv_s4d__moe_arch_mod__prompt'

def setup_inputs():

    _w = lambda a: (lambda t: t.to(torch.bfloat16) if t.is_floating_point() else t)(torch.as_tensor(a))

    def _A_setup():
        Bsz, L, D, N = (1, 2048, 576, 128)
        return {'u': _w((lambda *s: torch.randn(*s, dtype=torch.bfloat16) * 0.1)(Bsz, L, D)), 'log_A_real': _w((lambda *s: torch.randn(*s, dtype=torch.bfloat16) * 3.2)(D, N) * 0.5), 'A_imag': _w((lambda *s: torch.randn(*s, dtype=torch.bfloat16) * 0.4)(D, N) * 3.14), 'C_real': _w((lambda *s: torch.randn(*s, dtype=torch.bfloat16) * 0.8)(D, N) / N ** 0.5), 'C_imag': _w((lambda *s: torch.randn(*s, dtype=torch.bfloat16) * 0.8)(D, N) / N ** 0.5), 'log_dt': _w((lambda *s: torch.randn(*s, dtype=torch.bfloat16) * 0.4)(D) * 0.5 - 4.0), 'D_skip': _w((lambda *s: torch.randn(*s, dtype=torch.bfloat16) * 0.4)(D))}
    _A_in = _A_setup()

    def _B_setup():
        B, S, D, F, C = (1, 2048, 576, 4608, 8)
        return {'x': _w((lambda *s: torch.randn(*s, dtype=torch.bfloat16) * 0.1)(B, S, D)), 'w_r': _w((lambda *s: torch.randn(*s, dtype=torch.bfloat16) * 0.4)(D)), 'w_gate': _w((lambda *s: torch.randn(*s, dtype=torch.bfloat16) * 0.4)(D, F)), 'w_up': _w((lambda *s: torch.randn(*s, dtype=torch.bfloat16) * 0.4)(D, F)), 'w_down': _w((lambda *s: torch.randn(*s, dtype=torch.bfloat16) * 0.4)(F, D))}
    _B_in = _B_setup()
    return {'A_u': _A_in['u'], 'A_log_A_real': _A_in['log_A_real'], 'A_A_imag': _A_in['A_imag'], 'A_C_real': _A_in['C_real'], 'A_C_imag': _A_in['C_imag'], 'A_log_dt': _A_in['log_dt'], 'A_D_skip': _A_in['D_skip'], 'B_x': _B_in['x'], 'B_w_r': _B_in['w_r'], 'B_w_gate': _B_in['w_gate'], 'B_w_up': _B_in['w_up'], 'B_w_down': _B_in['w_down'], 'c': _w((lambda *s: torch.randn(*s, dtype=torch.bfloat16) * 0.2)(1, 576) * 8.0), 'w_mod': _w((lambda *s: torch.randn(*s, dtype=torch.bfloat16) * 0.2)(576, 6 * 576) * 576 ** (-0.5) * 8.0)}

def reference(A_u, A_log_A_real, A_A_imag, A_C_real, A_C_imag, A_log_dt, A_D_skip, B_x, B_w_r, B_w_gate, B_w_up, B_w_down, c, w_mod):

    def _A_ref(u, log_A_real, A_imag, C_real, C_imag, log_dt, D_skip):
        L = u.shape[1]
        dt = torch.exp(log_dt)
        A = -torch.exp(log_A_real) + 1j * A_imag
        C = (C_real + 1j * C_imag) * dt[:, None]
        pos = (lambda x, dt: x.to(dt))(torch.arange(L), log_dt.dtype)
        P = torch.exp((A * dt[:, None])[:, :, None] * pos[None, None, :])
        K = 2.0 * torch.einsum('dn,dnl->dl', C, P).real
        L2 = 2 * L
        u_t = (lambda x, *d: x.permute(*d))(u, 0, 2, 1)
        Kf = (lambda x, *a, **k: torch.fft.rfft(x.float(), *a, **k))(K, L2)
        Uf = (lambda x, *a, **k: torch.fft.rfft(x.float(), *a, **k))(u_t, L2)
        y = (lambda x, *a, **k: torch.fft.irfft(x, *a, **k).to(torch.bfloat16))(Uf * Kf[None, :, :], L2)[:, :, :L]
        y = (lambda x, *d: x.permute(*d))(y, 0, 2, 1)
        return y + u * D_skip[None, None, :]

    def _B_ref(x, w_r, w_gate, w_up, w_down):
        B, S, D = x.shape
        C = 8
        r = x @ w_r
        idx = torch.argsort(-r, axis=-1)[:, :C]
        idx_e = (lambda x, n, axis: torch.repeat_interleave(x, n, dim=axis))(idx.reshape(B, C, 1), D, axis=2)
        x_sel = (lambda x, i, axis: torch.take_along_dim(x, i, dim=axis))(x, idx_e, axis=1)
        g = _silu(x_sel @ w_gate)
        u = x_sel @ w_up
        y = g * u @ w_down
        r_sel = _sigmoid((lambda x, i, axis: torch.take_along_dim(x, i, dim=axis))(r, idx, axis=1))
        y = y * r_sel.reshape(B, C, 1)
        b_off = (torch.arange(B) * S).reshape(B, 1)
        flat_idx = (idx + b_off).reshape(B * C)
        zero = (x * 0.0).reshape(B * S, D)
        upd = _scatter_add(zero, flat_idx, y.reshape(B * C, D), axis=0)
        return x + upd.reshape(B, S, D)
    x = A_u
    mod = (_silu(c) @ w_mod).reshape(c.shape[0], 6, 1, -1)
    sa, ca, ga, sb, cb, gb = (mod[:, 0].clone(), mod[:, 1].clone(), mod[:, 2].clone(), mod[:, 3].clone(), mod[:, 4].clone(), mod[:, 5].clone())
    h = _layernorm(x, axis=-1) * (1 + ca) + sa
    x = x + ga * _A_ref(h, A_log_A_real, A_A_imag, A_C_real, A_C_imag, A_log_dt, A_D_skip)
    h = _layernorm(x, axis=-1) * (1 + cb) + sb
    x = x + gb * _B_ref(h, B_w_r, B_w_gate, B_w_up, B_w_down)
    return x
```

```cpp
#include <cuda_runtime.h>
#include <cuda_bf16.h>
#include <stdint.h>
typedef __nv_bfloat16 bf16;
#define L_ 2048
#define D_ 576
#define N_ 128
#define F_ 4608
__device__ float g_mod[6*D_];
__device__ float g_hT[D_*L_];
__device__ float g_K[D_*L_];
__device__ float g_yT[D_*L_];
__device__ float g_h2[L_*D_];
__device__ float g_x1[L_*D_];
__device__ float g_r[L_];
__device__ int   g_sel[8];
__device__ float g_act[8*F_];
__device__ __forceinline__ float rb(float x){ return __bfloat162float(__float2bfloat16_rn(x)); }
__device__ __forceinline__ float b2f(bf16 x){ return __bfloat162float(x); }

__global__ void k_mod(const bf16* c,const bf16* w){
  int col=blockIdx.x*32+(threadIdx.x&31), kq=threadIdx.x>>5; __shared__ float red[8][32];
  float s=0; for(int k=kq;k<D_;k+=8){ float v=b2f(c[k]); float sl=rb(v/(1.f+expf(-v))); s+=sl*b2f(w[(size_t)k*6*D_+col]); }
  red[kq][threadIdx.x&31]=s; __syncthreads();
  if(kq==0){ float t=0; for(int i=0;i<8;i++) t+=red[i][threadIdx.x]; g_mod[col]=rb(t); }
}
__device__ __forceinline__ void ln_stats(const float* v,int n,float&m,float&s){
  float a=0; for(int i=0;i<n;i++) a+=v[i]; for(int o=16;o;o>>=1) a+=__shfl_xor_sync(~0u,a,o);
  float mu=a/D_; float q=0; for(int i=0;i<n;i++){float d=v[i]-mu; q+=d*d;} for(int o=16;o;o>>=1) q+=__shfl_xor_sync(~0u,q,o);
  m=rb(mu); s=rb(sqrtf(rb(rb(q/D_)+1e-5f)));
}
__global__ void k_ln1(const bf16* x){
  int t=blockIdx.x*8+(threadIdx.x>>5), l=threadIdx.x&31; float v[18];
  for(int i=0;i<18;i++) v[i]=b2f(x[(size_t)t*D_+l+32*i]);
  float m,s; ln_stats(v,18,m,s);
  for(int i=0;i<18;i++){ int d=l+32*i; float z=rb(rb(v[i]-m)/s); g_hT[(size_t)d*L_+t]=rb(rb(z*rb(1.f+g_mod[D_+d]))+g_mod[d]); }
}
__global__ void k_K(const bf16* la,const bf16* ai,const bf16* cr,const bf16* ci,const bf16* ldt){
  int d=blockIdx.x; __shared__ float sar[N_],sai[N_],scr[N_],sci[N_];
  float dt=rb(expf(b2f(ldt[d])));
  if(threadIdx.x<N_){int n=threadIdx.x; sar[n]=-rb(expf(b2f(la[d*N_+n])))*dt; sai[n]=b2f(ai[d*N_+n])*dt; scr[n]=b2f(cr[d*N_+n])*dt; sci[n]=b2f(ci[d*N_+n])*dt;}
  __syncthreads();
  for(int l=threadIdx.x;l<L_;l+=blockDim.x){ float p=rb((float)l); float s=0;
    for(int n=0;n<N_;n++){ float e=expf(sar[n]*p); float sn,cs; sincosf(sai[n]*p,&sn,&cs); s+=e*(scr[n]*cs-sci[n]*sn); }
    g_K[(size_t)d*L_+l]=2.f*s; }
}
__global__ void k_conv(){
  int d=blockIdx.x; __shared__ float sk[L_],sh[L_];
  for(int i=threadIdx.x;i<L_;i+=blockDim.x){sk[i]=g_K[(size_t)d*L_+i]; sh[i]=g_hT[(size_t)d*L_+i];}
  __syncthreads();
  for(int t=threadIdx.x;t<L_;t+=blockDim.x){ float s=0; for(int l=0;l<=t;l++) s+=sk[l]*sh[t-l]; g_yT[(size_t)d*L_+t]=rb(s); }
}
__global__ void k_tok2(const bf16* x,const bf16* dsk,const bf16* wr,bf16* out){
  int t=blockIdx.x*8+(threadIdx.x>>5), l=threadIdx.x&31; float v[18];
  for(int i=0;i<18;i++){ int d=l+32*i; float h=g_hT[(size_t)d*L_+t]; float a=rb(g_yT[(size_t)d*L_+t]+rb(h*b2f(dsk[d]))); v[i]=rb(b2f(x[(size_t)t*D_+d])+rb(g_mod[2*D_+d]*a)); }
  float m,s; ln_stats(v,18,m,s); float r=0;
  for(int i=0;i<18;i++){ int d=l+32*i; float z=rb(rb(v[i]-m)/s); float h2=rb(rb(z*rb(1.f+g_mod[4*D_+d]))+g_mod[3*D_+d]);
    g_h2[(size_t)t*D_+d]=h2; g_x1[(size_t)t*D_+d]=v[i]; r+=h2*b2f(wr[d]); out[(size_t)t*D_+d]=__float2bfloat16_rn(v[i]+rb(g_mod[5*D_+d]*h2)); }
  for(int o=16;o;o>>=1) r+=__shfl_xor_sync(~0u,r,o);
  if(l==0) g_r[t]=rb(r);
}
__global__ void k_top(){
  __shared__ float sr[L_]; for(int i=threadIdx.x;i<L_;i+=blockDim.x) sr[i]=g_r[i]; __syncthreads();
  for(int t=threadIdx.x;t<L_;t+=blockDim.x){ float r=sr[t]; int rank=0; for(int j=0;j<L_;j++){ float o=sr[j]; rank+=(o>r)||(o==r&&j<t);} if(rank<8) g_sel[rank]=t; }
}
__global__ void k_gu(const bf16* wg,const bf16* wu){
  int f=blockIdx.x*32+(threadIdx.x&31), s=threadIdx.x>>5; const float* xs=g_h2+(size_t)g_sel[s]*D_;
  float g=0,u=0; for(int k=0;k<D_;k++){ float xv=xs[k]; g+=xv*b2f(wg[(size_t)k*F_+f]); u+=xv*b2f(wu[(size_t)k*F_+f]); }
  g=rb(g);u=rb(u); float sg=rb(g/(1.f+expf(-g))); g_act[s*F_+f]=rb(sg*u);
}
__global__ void k_down(const bf16* wd,bf16* out){
  int d=blockIdx.x*32+(threadIdx.x&31), s=blockIdx.y, kq=threadIdx.x>>5; __shared__ float red[8][32];
  float a=0; for(int k=kq;k<F_;k+=8) a+=g_act[s*F_+k]*b2f(wd[(size_t)k*D_+d]);
  red[kq][threadIdx.x&31]=a; __syncthreads();
  if(kq==0){ float y=0; for(int i=0;i<8;i++) y+=red[i][threadIdx.x]; int t=g_sel[s]; float r=g_r[t]; float sg=rb(1.f/(1.f+expf(-r)));
    y=rb(rb(y)*sg); float b=rb(g_h2[(size_t)t*D_+d]+y); out[(size_t)t*D_+d]=__float2bfloat16_rn(g_x1[(size_t)t*D_+d]+rb(g_mod[5*D_+d]*b)); }
}
extern "C" void kernel_launch(void* const* d_in, const int* in_sizes, int n_in, void* d_out, int out_size) {
  const bf16* x=(const bf16*)d_in[0]; bf16* out=(bf16*)d_out;
  k_mod<<<108,256>>>((const bf16*)d_in[12],(const bf16*)d_in[13]);
  k_ln1<<<256,256>>>(x);
  k_K<<<D_,256>>>((const bf16*)d_in[1],(const bf16*)d_in[2],(const bf16*)d_in[3],(const bf16*)d_in[4],(const bf16*)d_in[5]);
  k_conv<<<D_,256>>>();
  k_tok2<<<256,256>>>(x,(const bf16*)d_in[6],(const bf16*)d_in[8],out);
  k_top<<<1,1024>>>();
  k_gu<<<F_/32,256>>>((const bf16*)d_in[9],(const bf16*)d_in[10]);
  k_down<<<dim3(18,8),256>>>((const bf16*)d_in[11],out);
}
```

```cpp
#include <cuda_runtime.h>
#include <cuda.h>
#include <cuda_bf16.h>
#include <cuda_fp16.h>
#include <stdint.h>
#define FUSED 1
#define DEV __device__ __forceinline__
typedef uint32_t u32;

__device__ __align__(128) uint4 g_Z[128 * 576 * 2];
__device__ __align__(128) uint4 g_Y[128 * 576 * 2];
__device__ __align__(128) uint4 g_MOD[216 * 8];
__device__ __align__(128) uint4 g_KEY[512];
__device__ __align__(128) uint4 g_HX[128 * 2 * 2 * 72];
__device__ __align__(128) uint4 g_HX2[8 * 2 * 72];
__device__ __align__(128) u32 g_FLG[8 * 32];
__device__ __align__(128) uint4 g_ACT[576 * 8];
__device__ __align__(128) uint2 g_PART[16 * 72 * 32];
__device__ u32 g_epoch;
__device__ u32 g_err;
#define TS(i)
#define TSW(ww, i)

constexpr int SM_GATE = 0, SM_UP = 46080, SM_ZS = 92160, SM_TAP = 114816, TAPS = 3264;
constexpr int SM_SP = 131136;
constexpr int SM_MB = 136896;
constexpr int SM_ZERO = SM_MB + 64;
constexpr int SM_CNT = SM_MB + 80;
constexpr int SM_ST = SM_MB + 128;
constexpr int SM_SC = SM_MB + 256;
constexpr int SM_KV = SM_MB + 352;
constexpr int SM_RC = SM_MB + 384;
constexpr int SM_GP = SM_MB + 448;
constexpr int SM_GM = SM_MB + 576;
constexpr int SM_SEL = SM_MB + 640;
constexpr int SM_SIL = SM_MB + 768;
constexpr int SM_R = 139264;
constexpr int KTAB = 9216, WSL = 12320;
constexpr int W5O = 0, W3O = 3088, W9O = 6176, W7O = 8224, V2O = 10272;
constexpr int SM_WD = SM_R, SM_XS = SM_R + 41600, SM_AC = SM_XS + 9344, SM_RED = SM_AC + 4608, SM_LIST = SM_RED + 10240;
constexpr int SM_TOTAL = SM_R + 92160;
constexpr int TE = 4, TO = 272 + 4, T5 = 544 - 25, T3 = 592 - 25, TE9 = 640 - 25, TO9 = 688 - 25, TE7 = 728 - 25, TO7 = 776 - 25;
constexpr int SPIN = 1 << 16;
constexpr u32 TAGM = 0x40004000u, INVAL = 0x00004000u;

DEV u32 s2u(const void* p) { return (u32)__cvta_generic_to_shared(p); }
DEV void mma_bf(float (&c)[4], u32 a0, u32 a1, u32 a2, u32 a3, u32 b0, u32 b1) {
  asm("mma.sync.aligned.m16n8k16.row.col.f32.bf16.bf16.f32 {%0,%1,%2,%3},{%4,%5,%6,%7},{%8,%9},{%0,%1,%2,%3};"
      : "+f"(c[0]), "+f"(c[1]), "+f"(c[2]), "+f"(c[3]) : "r"(a0), "r"(a1), "r"(a2), "r"(a3), "r"(b0), "r"(b1));
}
DEV void mma_hf(float (&c)[4], u32 a0, u32 a1, u32 a2, u32 a3, u32 b0, u32 b1) {
  asm("mma.sync.aligned.m16n8k16.row.col.f32.f16.f16.f32 {%0,%1,%2,%3},{%4,%5,%6,%7},{%8,%9},{%0,%1,%2,%3};"
      : "+f"(c[0]), "+f"(c[1]), "+f"(c[2]), "+f"(c[3]) : "r"(a0), "r"(a1), "r"(a2), "r"(a3), "r"(b0), "r"(b1));
}
DEV void mma8_bf(float (&c)[4], u32 a0, u32 a1, u32 b0) {
  asm("mma.sync.aligned.m16n8k8.row.col.f32.bf16.bf16.f32 {%0,%1,%2,%3},{%4,%5},{%6},{%0,%1,%2,%3};"
      : "+f"(c[0]), "+f"(c[1]), "+f"(c[2]), "+f"(c[3]) : "r"(a0), "r"(a1), "r"(b0));
}
DEV void mma8_hf(float (&c)[4], u32 a0, u32 a1, u32 b0) {
  asm("mma.sync.aligned.m16n8k8.row.col.f32.f16.f16.f32 {%0,%1,%2,%3},{%4,%5},{%6},{%0,%1,%2,%3};"
      : "+f"(c[0]), "+f"(c[1]), "+f"(c[2]), "+f"(c[3]) : "r"(a0), "r"(a1), "r"(b0));
}
DEV u32 movm(u32 x) { u32 r; asm("movmatrix.sync.aligned.m8n8.trans.b16 %0,%1;" : "=r"(r) : "r"(x)); return r; }
DEV uint4 ldsm4(u32 a) { uint4 r; asm volatile("ldmatrix.sync.aligned.m8n8.x4.shared.b16 {%0,%1,%2,%3},[%4];" : "=r"(r.x), "=r"(r.y), "=r"(r.z), "=r"(r.w) : "r"(a)); return r; }
DEV uint2 ldsm2(u32 a) { uint2 r; asm volatile("ldmatrix.sync.aligned.m8n8.x2.shared.b16 {%0,%1},[%2];" : "=r"(r.x), "=r"(r.y) : "r"(a)); return r; }
DEV uint4 ldsm4t(u32 a) { uint4 r; asm volatile("ldmatrix.sync.aligned.m8n8.x4.trans.shared.b16 {%0,%1,%2,%3},[%4];" : "=r"(r.x), "=r"(r.y), "=r"(r.z), "=r"(r.w) : "r"(a)); return r; }
DEV u32 lds32(u32 a) { u32 r; asm volatile("ld.volatile.shared.u32 %0,[%1];" : "=r"(r) : "r"(a)); return r; }
DEV uint2 lds64(u32 a) { uint2 r; asm volatile("ld.shared.v2.u32 {%0,%1},[%2];" : "=r"(r.x), "=r"(r.y) : "r"(a)); return r; }
DEV uint4 lds128(u32 a) { uint4 r; asm volatile("ld.shared.v4.u32 {%0,%1,%2,%3},[%4];" : "=r"(r.x), "=r"(r.y), "=r"(r.z), "=r"(r.w) : "r"(a)); return r; }
DEV void sts16(u32 a, u32 v) { asm volatile("st.shared.u16 [%0],%1;" ::"r"(a), "h"((unsigned short)v) : "memory"); }
DEV void sts32(u32 a, u32 v) { asm volatile("st.shared.u32 [%0],%1;" ::"r"(a), "r"(v) : "memory"); }
DEV void sts64(u32 a, u32 x, u32 y) { asm volatile("st.shared.v2.u32 [%0],{%1,%2};" ::"r"(a), "r"(x), "r"(y) : "memory"); }
DEV void sts128(u32 a, u32 x, u32 y, u32 z, u32 w) { asm volatile("st.shared.v4.u32 [%0],{%1,%2,%3,%4};" ::"r"(a), "r"(x), "r"(y), "r"(z), "r"(w) : "memory"); }
DEV uint4 ldr128(const void* p) { uint4 v; asm volatile("ld.relaxed.gpu.global.v4.u32 {%0,%1,%2,%3},[%4];" : "=r"(v.x), "=r"(v.y), "=r"(v.z), "=r"(v.w) : "l"(p) : "memory"); return v; }
DEV uint2 ldr64(const void* p) { uint2 v; asm volatile("ld.relaxed.gpu.global.v2.u32 {%0,%1},[%2];" : "=r"(v.x), "=r"(v.y) : "l"(p) : "memory"); return v; }
DEV u32 ldr32(const void* p) { u32 v; asm volatile("ld.relaxed.gpu.global.u32 %0,[%1];" : "=r"(v) : "l"(p) : "memory"); return v; }
DEV void str128(void* p, u32 x, u32 y, u32 z, u32 w) { asm volatile("st.relaxed.gpu.global.v4.u32 [%0],{%1,%2,%3,%4};" ::"l"(p), "r"(x), "r"(y), "r"(z), "r"(w) : "memory"); }
DEV void str64(void* p, u32 x, u32 y) { asm volatile("st.relaxed.gpu.global.v2.u32 [%0],{%1,%2};" ::"l"(p), "r"(x), "r"(y) : "memory"); }
DEV void str32(void* p, u32 x) { asm volatile("st.relaxed.gpu.global.u32 [%0],%1;" ::"l"(p), "r"(x) : "memory"); }
DEV void str16(void* p, u32 x) { asm volatile("st.relaxed.gpu.global.u16 [%0],%1;" ::"l"(p), "h"((unsigned short)x) : "memory"); }
DEV uint4 ldg128(const void* p) { uint4 v; asm volatile("ld.global.nc.v4.u32 {%0,%1,%2,%3},[%4];" : "=r"(v.x), "=r"(v.y), "=r"(v.z), "=r"(v.w) : "l"(p)); return v; }
DEV uint2 ldg64(const void* p) { uint2 v; asm volatile("ld.global.nc.v2.u32 {%0,%1},[%2];" : "=r"(v.x), "=r"(v.y) : "l"(p)); return v; }
DEV u32 ldg32(const void* p) { u32 v; asm volatile("ld.global.nc.u32 %0,[%1];" : "=r"(v) : "l"(p)); return v; }
DEV u32 ldg16(const void* p) { unsigned short v; asm volatile("ld.global.nc.u16 %0,[%1];" : "=h"(v) : "l"(p)); return v; }
DEV void bsync(int id, int n) { asm volatile("bar.sync %0,%1;" ::"r"(id), "r"(n) : "memory"); }
DEV void barrive(int id, int n) { asm volatile("bar.arrive %0,%1;" ::"r"(id), "r"(n) : "memory"); }
DEV void mb_init(u32 a) { asm volatile("mbarrier.init.shared.b64 [%0],1;" ::"r"(a) : "memory"); }
DEV void mb_expect(u32 a, u32 bytes) { asm volatile("mbarrier.arrive.expect_tx.shared.b64 _,[%0],%1;" ::"r"(a), "r"(bytes) : "memory"); }
DEV void mb_wait(u32 a) {
  u32 ok = 0; int it = 0;
  do { asm volatile("{.reg .pred p; mbarrier.try_wait.parity.shared.b64 p,[%1],0; selp.u32 %0,1,0,p;}" : "=r"(ok) : "r"(a) : "memory"); } while (!ok && ++it < SPIN);
  if (!ok) g_err = 0x100;
}
DEV void tma2d(u32 dst, const CUtensorMap* tm, u32 mb, int c0, int c1) {
  asm volatile("cp.async.bulk.tensor.2d.shared::cluster.global.mbarrier::complete_tx::bytes [%0],[%1,{%3,%4}],[%2];"
               ::"r"(dst), "l"((uint64_t)tm), "r"(mb), "r"(c0), "r"(c1) : "memory");
}
DEV float blo(u32 w) { return __uint_as_float(w << 16); }
DEV float bhi(u32 w) { return __uint_as_float(w & 0xffff0000u); }
DEV u32 pk_bf(float lo, float hi) { u32 r; asm("cvt.rn.bf16x2.f32 %0,%1,%2;" : "=r"(r) : "f"(hi), "f"(lo)); return r; }
DEV u32 pk_hf(float lo, float hi) { u32 r; asm("cvt.rn.f16x2.f32 %0,%1,%2;" : "=r"(r) : "f"(hi), "f"(lo)); return r; }
DEV float rbf(float x) { return __uint_as_float(pk_bf(0.f, x) & 0xffff0000u); }
DEV u32 bfma(u32 a, u32 b, u32 c) { u32 r; asm("fma.rn.bf16x2 %0,%1,%2,%3;" : "=r"(r) : "r"(a), "r"(b), "r"(c)); return r; }
DEV u32 bmul(u32 a, u32 b) { u32 r; asm("mul.rn.bf16x2 %0,%1,%2;" : "=r"(r) : "r"(a), "r"(b)); return r; }
DEV u32 badd(u32 a, u32 b) { u32 r; asm("add.rn.bf16x2 %0,%1,%2;" : "=r"(r) : "r"(a), "r"(b)); return r; }
DEV u32 hadd(u32 a, u32 b) { u32 r; asm("add.rn.f16x2 %0,%1,%2;" : "=r"(r) : "r"(a), "r"(b)); return r; }
DEV u32 hfma(u32 a, u32 b, u32 c) { u32 r; asm("fma.rn.f16x2 %0,%1,%2,%3;" : "=r"(r) : "r"(a), "r"(b), "r"(c)); return r; }
DEV u32 hcm(u32 s, u32 m, u32 mp) {
  __half2 S = *reinterpret_cast<__half2*>(&s), M = *reinterpret_cast<__half2*>(&m), P = *reinterpret_cast<__half2*>(&mp);
  __half2 r = __hfma2(__high2half2(S), P, __hmul2(__low2half2(S), M));
  return *reinterpret_cast<u32*>(&r);
}
DEV float ex2(float x) { float r; asm("ex2.approx.ftz.f32 %0,%1;" : "=f"(r) : "f"(x)); return r; }
DEV float rcpf(float x) { float r; asm("rcp.approx.ftz.f32 %0,%1;" : "=f"(r) : "f"(x)); return r; }
DEV float2 cmul(float2 a, float2 b) { return make_float2(fmaf(a.x, b.x, -a.y * b.y), fmaf(a.x, b.y, a.y * b.x)); }
DEV float2 csq(float2 a) { return make_float2(fmaf(a.x, a.x, -a.y * a.y), (a.x + a.x) * a.y); }
DEV float2 cexp(float lr2, float th) {
  float k = rintf(th * 0.15915494309189535f);
  float r = fmaf(k, -6.2831854820251465f, th); r = fmaf(k, 1.7484555e-7f, r);
  float m = ex2(lr2);
  return make_float2(m * __cosf(r), m * __sinf(r));
}
DEV float silu_f(float v) { return v * rcpf(1.f + ex2(-1.4426950408889634f * v)); }
constexpr u32 B2P64 = 0x5F805F80u, B2M64 = 0x1F801F80u, BONE = 0x3F803F80u;
DEV int chan_of(int P) { int r = P & 63; return (P & ~63) + 32 * (r & 1) + 8 * ((r >> 2) & 3) + 2 * (r >> 4) + ((r >> 1) & 1); }
DEV const uint4* mod_chunk(int idx) { return g_MOD + (idx >> 4) * 8 + ((idx >> 3) & 1); }

struct Prm {
  const uint16_t *x, *la, *ai, *cr, *ci, *ldt, *dsk, *wr, *c;
  uint16_t* out;
};

DEV void mod_gemv(u32 sb, int w, int lane, int slot, int slice, u32 pm) {
  const int g = lane >> 2, q = lane & 3, kh = w - 8;
  mb_wait(sb + SM_MB + 8 * slot);
  float c[2][4] = {};
  const int row = 288 * kh + (lane & 7) + 8 * (lane >> 4);
  const u32 aa = sb + SM_UP + slot * 18432 + row * 32 + ((((lane >> 3) & 1) ^ ((row >> 2) & 1)) << 4);
  const u32 ba = sb + SM_SIL + 576 * kh + 4 * q;
#pragma unroll
  for (int s = 0; s < 18; s++) {
    uint4 a = ldsm4t(aa + s * 512);
    mma_bf(c[s & 1], a.x, a.y, a.z, a.w, lds32(ba + 32 * s), lds32(ba + 32 * s + 16));
  }
  float v = (q & 1) ? c[0][2] + c[1][2] : c[0][0] + c[1][0];
  if (kh) sts32(sb + SM_GP + lane * 4, __float_as_uint(v));
  bsync(7, 64);
  if (!kh) {
    v += __uint_as_float(lds32(sb + SM_GP + lane * 4));
    u32 o = pk_bf(rbf(v) * 5.421010862427522e-20f, 0.f) | (g < 2 ? (pm & 0xffff) : 0);
    if (q < 2) str16((uint16_t*)(g_MOD + slice * 8) + g + 8 * q, o);
  }
  bsync(7, 64);
}

DEV void y_store(const float (&c)[4], float F, u32 pml, char* yp, int u) {
  str32(yp + (size_t)u * 8 * 18432, pk_bf(c[0] * F, c[2] * F) | pml);
  str32(yp + (size_t)u * 8 * 18432 + 18432, pk_bf(c[1] * F, c[3] * F) | pml);
}

__global__ void __launch_bounds__(384, 1)
fused_kernel(const Prm p, const __grid_constant__ CUtensorMap tm_mod, const __grid_constant__ CUtensorMap tm_gate,
             const __grid_constant__ CUtensorMap tm_up, const __grid_constant__ CUtensorMap tm_down) {
  extern __shared__ __align__(1024) unsigned char smem[];
  const u32 sb = s2u(smem);
  const int tid = threadIdx.x, w = tid >> 5, lane = tid & 31, b = blockIdx.x;
  const int g = lane >> 2, q = lane & 3, e = g >> 2, h = (g >> 1) & 1, hi = g & 1;
  const int rho = b & 1, Pb = 9 * (b >> 1) + 4 * rho;
  TSW(0, 0);
  const bool kw = (w < 8) || (w >= 10);
  const int ksig = w < 8 ? (w & 3) : 4, khf = w < 8 ? (w >> 2) : (w & 1);
  const int kP = ksig < 4 ? Pb + ksig + rho : Pb + (rho ? 0 : 4);
  u32 la = 0, ai = 0, ldt = 0; uint2 cr = {0, 0}, ci = {0, 0};
  if (kw) {
    const int d = chan_of(kP), o = d * 128 + 4 * lane;
    la = ldg32(p.la + o + 2 * khf); ai = ldg32(p.ai + o + 2 * khf);
    cr = ldg64(p.cr + o); ci = ldg64(p.ci + o); ldt = ldg16(p.ldt + d);
  }
  uint4 xv[4];
  const uint16_t* xrow = p.x + (size_t)(16 * b) * 576 + 64 * w + 8 * (4 * e + q);
  if (w < 9) {
#pragma unroll
    for (int k = 0; k < 4; k++) xv[k] = ldg128(xrow + (4 * h + 2 * (k >> 1) + 8 * (k & 1) + hi) * 576);
  }
  const u32 ep = ldr32(&g_epoch);
  u32 cw[5];
  if (w == 8 || w == 9) {
#pragma unroll
    for (int j = 0; j < 5; j++) { int i = lane + 32 * j; cw[j] = i < 144 ? ldg32(p.c + 288 * (w - 8) + 2 * i) : 0; }
  }
  if (w == 9 && lane == 0) {
    for (int i = 0; i < 5; i++) mb_init(sb + SM_MB + 8 * i);
    asm volatile("fence.mbarrier_init.release.cluster;" ::: "memory");
    mb_expect(sb + SM_MB, 18432);
    for (int i = 0; i < 3; i++) tma2d(sb + SM_UP + i * 6144, &tm_mod, sb + SM_MB, 16 * b, 192 * i);
    if (b < 88) {
      mb_expect(sb + SM_MB + 8, 18432);
      for (int i = 0; i < 3; i++) tma2d(sb + SM_UP + 18432 + i * 6144, &tm_mod, sb + SM_MB + 8, 16 * (128 + b), 192 * i);
    }
    mb_expect(sb + SM_MB + 16, 46080);
    for (int i = 0; i < 3; i++) tma2d(sb + SM_GATE + i * 15360, &tm_gate, sb + SM_MB + 16, 72 * (b >> 1) + 40 * rho, 192 * i);
  }
  for (int i = tid; i < 5 * TAPS / 16; i += 384) sts128(sb + SM_TAP + i * 16, 0, 0, 0, 0);
  if (tid < 64) sts128(sb + SM_ZS + (tid >> 4) * 4384 + (tid & 15) * 16, 0, 0, 0, 0);
  else if (tid < 128) sts128(sb + SM_ZS + 17536 + (tid - 64) * 16, 0, 0, 0, 0);
  else if (tid < 130) sts128(sb + SM_ZERO + (tid - 128) * 16, 0, 0, 0, 0);
  char* const zdst = (char*)g_Z + (size_t)b * 18432 + w * 2048 + lane * 16;
  if (w < 9) {
#pragma unroll
    for (int v = 0; v < 4; v++) str128(zdst + 512 * v, INVAL, 0, 0, 0);
  } else if (w == 9) {
    if (lane < 2) { str128(g_MOD + b * 8 + lane, INVAL, 0, 0, 0); if (b < 88) str128(g_MOD + (128 + b) * 8 + lane, INVAL, 0, 0, 0); }
    if (lane < 4) str128(g_KEY + b * 4 + lane, 0x800, 0x800, 0x800, 0x800);
    for (int i = lane; i < 8 * (5 - rho); i += 32) str128(g_ACT + (9 * (b >> 1) + 5 * rho) * 8 + i, INVAL, 0, 0, 0);
    for (int i = lane; i < 144; i += 32) str128((uint4*)(g_PART + ((b >> 3) * 72 + 9 * (b & 7)) * 32) + i, 1, 0, 1, 0);
  }
  if (w < 8) {
    const int P = w < 4 ? Pb + w + rho : Pb + (rho ? 0 : 4);
    const int tb = 96 + (lane >> 1) + (w < 4 ? 0 : 16 * rho);
    if (w < 5) str128((char*)g_Y + (size_t)tb * 18432 + P * 32 + (lane & 1) * 16, INVAL, 0, 0, 0);
    if (w < 4) str128((char*)g_Y + (size_t)(tb + 16) * 18432 + P * 32 + (lane & 1) * 16, INVAL, 0, 0, 0);
  }
  __syncthreads();
  const u32 par = (ep + 1) & 1, pm = par ? TAGM : 0;
  TSW(0, 1);
  const u32 ktab = sb + SM_R + (w < 8 ? w : w - 2) * KTAB;
  float FK = 0.f, k2048 = 0.f;
  if (kw) {
    u32 mx = __vmaxu2(__vmaxu2(cr.x & 0x7fff7fff, cr.y & 0x7fff7fff), __vmaxu2(ci.x & 0x7fff7fff, ci.y & 0x7fff7fff));
    mx = max(mx & 0xffff, mx >> 16);
    int E = max((int)(__reduce_max_sync(~0u, mx) >> 7), 8);
    const float dt = rbf(ex2(blo(ldt) * 1.4426950408889634f));
    const float csc = __uint_as_float((258 - E) << 23);
    FK = 2.f * dt * __uint_as_float(max(E - 4, 1) << 23);
    const u32 crw = khf ? cr.y : cr.x, ciw = khf ? ci.y : ci.x;
    u32 B0[2][8], B1[2][8], B2[2][8], S[2][8], M[2][4];
#pragma unroll
    for (int m = 0; m < 2; m++) {
      const float lr = -rbf(ex2((m ? bhi(la) : blo(la)) * 1.4426950408889634f)) * dt, th = (m ? bhi(ai) : blo(ai)) * dt;
      const float lr2 = lr * 1.4426950408889634f;
      const float2 C = make_float2((m ? bhi(crw) : blo(crw)) * csc, (m ? bhi(ciw) : blo(ciw)) * csc);
      const float2 w1 = cexp(lr2, th), w64 = cexp(64.f * lr2, 64.f * th);
      const float2 w2 = csq(w1), w4 = csq(w2), w8 = csq(w4), w16 = csq(w8), w32 = csq(w16);
      const float2 w128 = csq(w64), w256 = csq(w128), w512 = csq(w256), w1024 = csq(w512), w768 = cmul(w512, w256);
      float2 a[8];
      a[0] = C; a[1] = cmul(C, w1); a[2] = cmul(C, w2); a[3] = cmul(a[1], w2);
#pragma unroll
      for (int i = 0; i < 4; i++) a[4 + i] = cmul(a[i], w4);
#pragma unroll
      for (int i = 0; i < 8; i++) B0[m][i] = pk_hf(a[i].x, a[i].y);
      float2 t;
#pragma unroll
      for (int i = 0; i < 4; i++) { t = cmul(a[2 * i], w256); B1[m][i] = pk_hf(t.x, t.y); }
      t = cmul(a[0], w512); B1[m][4] = pk_hf(t.x, t.y);
      t = cmul(a[4], w512); B1[m][5] = pk_hf(t.x, t.y);
      t = cmul(a[0], w768); B1[m][6] = pk_hf(t.x, t.y);
      t = cmul(a[4], w768); B1[m][7] = pk_hf(t.x, t.y);
      a[0] = cmul(C, w1024); a[1] = cmul(a[0], w128); a[2] = cmul(a[0], w256); a[3] = cmul(a[1], w256);
#pragma unroll
      for (int i = 0; i < 4; i++) a[4 + i] = cmul(a[i], w512);
#pragma unroll
      for (int i = 0; i < 8; i++) B2[m][i] = pk_hf(a[i].x, a[i].y);
      k2048 += fmaf(a[0].x, w1024.x, -a[0].y * w1024.y);
      a[1] = w8; a[2] = w16; a[3] = cmul(w8, w16); a[4] = w32;
#pragma unroll
      for (int i = 1; i < 4; i++) a[4 + i] = cmul(a[i], w32);
      S[m][0] = 0x00003C00u;
#pragma unroll
      for (int i = 1; i < 8; i++) S[m][i] = pk_hf(a[i].x, -a[i].y);
      M[m][0] = pk_hf(w64.x, -w64.y); M[m][1] = pk_hf(w64.y, w64.x);
      M[m][2] = pk_hf(w128.x, -w128.y); M[m][3] = pk_hf(w128.y, w128.x);
    }
    const u32 f = (lane & 1) | ((lane & 2) << 1) | ((lane & 4) >> 1);
    const u32 ta = ktab + lane * 256;
#pragma unroll
    for (int i = 0; i < 8; i++) {
      sts128(ta + (((2 * i) ^ f) << 4), B0[0][i], B0[1][i], B1[0][i], B1[1][i]);
      sts128(ta + (((2 * i + 1) ^ f) << 4), B2[0][i], B2[1][i], S[0][i], S[1][i]);
    }
    sts128(ktab + 8192 + lane * 32, M[0][0], M[0][1], M[0][2], M[0][3]);
    sts128(ktab + 8192 + lane * 32 + 16, M[1][0], M[1][1], M[1][2], M[1][3]);
    __syncwarp();
  } else {
#pragma unroll
    for (int j = 0; j < 5; j++) { int i = lane + 32 * j; if (i < 144) sts32(sb + SM_SIL + 576 * (w - 8) + 4 * i, pk_bf(silu_f(blo(cw[j])), silu_f(bhi(cw[j])))); }
    __syncwarp();
  }
  TSW(0, 2); TSW(10, 3);
  const u32 spw = sb + SM_SP + (2 * w + e) * 320 + (g & 3) * 16;
  const u32 spr = sb + SM_SP + (lane >> 4) * 9 * 320 + (lane & 15) * 16;
  if (w < 9) {
#pragma unroll
    for (int k = 0; k < 4; k++) {
      float s[4] = {}, X[4] = {}, Y[4] = {};
      mma_bf(s, xv[k].x, xv[k].y, xv[k].z, xv[k].w, BONE, BONE);
      mma8_bf(X, xv[k].x, xv[k].y, xv[k].x); mma8_bf(Y, xv[k].x, xv[k].y, xv[k].y);
      mma8_bf(X, xv[k].z, xv[k].w, xv[k].z); mma8_bf(Y, xv[k].z, xv[k].w, xv[k].w);
      const bool sq = (q & 1) == h;
      float v = sq ? (hi ? X[1] + Y[3] : X[0] + Y[2]) : s[0] + s[2];
      if ((q >> 1) == e) sts32(spw + k * 64 + (sq ? 4 : 0), __float_as_uint(v));
    }
    TSW(0, 4);
    bsync(1, 288);
    float S1 = 0.f, S2 = 0.f;
#pragma unroll
    for (int i = 0; i < 9; i++) { uint2 t = lds64(spr + i * 320); S1 += __uint_as_float(t.x); S2 += __uint_as_float(t.y); }
    S1 += __shfl_xor_sync(~0u, S1, 16); S2 += __shfl_xor_sync(~0u, S2, 16);
    const float mu = S1 * (1.f / 576.f), var = fmaxf(fmaf(-mu, mu, S2 * (1.f / 576.f)), 0.f);
    const float m = rbf(mu), sd = rbf(sqrtf(rbf(rbf(var) + 1e-5f)));
    const float rs = __frcp_rn(sd), ra = rs * 0.0625f, rc = -m * ra;
    if (w == 8 && lane < 16) { const int k = lane >> 2; sts64(sb + SM_ST + 8 * (4 * ((lane >> 1) & 1) + 2 * (k >> 1) + 8 * (k & 1) + (lane & 1)), __float_as_uint(m), __float_as_uint(rs)); }
    u32 zt[4][4];
#pragma unroll
    for (int k = 0; k < 4; k++) {
      const float a = __shfl_sync(~0u, ra, 4 * k + (g & 3)), c = __shfl_sync(~0u, rc, 4 * k + (g & 3));
      const u32 xx[4] = {xv[k].x, xv[k].y, xv[k].z, xv[k].w};
#pragma unroll
      for (int v = 0; v < 4; v++) zt[v][k] = movm(pk_hf(fmaf(blo(xx[v]), a, c), fmaf(bhi(xx[v]), a, c)));
    }
#pragma unroll
    for (int v = 0; v < 4; v++) str128(zdst + 512 * v, zt[v][0] | pm, zt[v][1], zt[v][2], zt[v][3]);
  }
  TSW(0, 5);
  if (kw) {
    float D0[2][4] = {}, D1[2][4] = {}, D2[4] = {};
    const u32 f0 = (q & 1) | ((q & 2) << 1);
#pragma unroll
    for (int s = 0; s < 8; s++) {
      const u32 ta = ktab + (4 * s + q) * 256, f = f0 | ((s & 1) << 1);
      const uint4 c0 = lds128(ta + (((2 * g) ^ f) << 4)), c1 = lds128(ta + (((2 * g + 1) ^ f) << 4));
      const uint4 ma = lds128(ktab + 8192 + (4 * s + q) * 32), mb = lds128(ktab + 8192 + (4 * s + q) * 32 + 16);
      const u32 a1 = hcm(c1.z, ma.x, ma.y), b1 = hcm(c1.w, mb.x, mb.y);
      const u32 a2 = hcm(c1.z, ma.z, ma.w), b2 = hcm(c1.w, mb.z, mb.w);
      const u32 a3 = hcm(a1, ma.z, ma.w), b3 = hcm(b1, mb.z, mb.w);
      mma_hf(D0[0], c1.z, a1, c1.w, b1, c0.x, c0.y);
      mma_hf(D1[0], c1.z, a1, c1.w, b1, c0.z, c0.w);
      mma_hf(D2, c1.z, a1, c1.w, b1, c1.x, c1.y);
      mma_hf(D0[1], a2, a3, b2, b3, c0.x, c0.y);
      mma_hf(D1[1], a2, a3, b2, b3, c0.z, c0.w);
    }
    const u32 xa = sb + SM_R + (ksig < 4 ? 4 + ksig : 9) * KTAB + lane * 16;
    if (khf) {
      __syncwarp();
      sts128(xa, __float_as_uint(D0[0][0]), __float_as_uint(D0[0][1]), __float_as_uint(D0[0][2]), __float_as_uint(D0[0][3]));
      sts128(xa + 512, __float_as_uint(D0[1][0]), __float_as_uint(D0[1][1]), __float_as_uint(D0[1][2]), __float_as_uint(D0[1][3]));
      sts128(xa + 1024, __float_as_uint(D1[0][0]), __float_as_uint(D1[0][1]), __float_as_uint(D1[0][2]), __float_as_uint(D1[0][3]));
      sts128(xa + 1536, __float_as_uint(D1[1][0]), __float_as_uint(D1[1][1]), __float_as_uint(D1[1][2]), __float_as_uint(D1[1][3]));
      sts128(xa + 2048, __float_as_uint(D2[0]), __float_as_uint(D2[1]), __float_as_uint(D2[2]), __float_as_uint(D2[3]));
      sts32(xa + 2560, __float_as_uint(k2048));
      barrive(2 + ksig, 64);
    } else {
      bsync(2 + ksig, 64);
      uint4 t;
#pragma unroll
      for (int j = 0; j < 2; j++) {
        t = lds128(xa + 512 * j); D0[j][0] += __uint_as_float(t.x); D0[j][1] += __uint_as_float(t.y); D0[j][2] += __uint_as_float(t.z); D0[j][3] += __uint_as_float(t.w);
        t = lds128(xa + 1024 + 512 * j); D1[j][0] += __uint_as_float(t.x); D1[j][1] += __uint_as_float(t.y); D1[j][2] += __uint_as_float(t.z); D1[j][3] += __uint_as_float(t.w);
      }
      t = lds128(xa + 2048); D2[0] += __uint_as_float(t.x); D2[1] += __uint_as_float(t.y); D2[2] += __uint_as_float(t.z); D2[3] += __uint_as_float(t.w);
      k2048 += __uint_as_float(lds32(xa + 2560));
#pragma unroll
      for (int o = 16; o; o >>= 1) k2048 += __shfl_xor_sync(~0u, k2048, o);
      const float kv512 = __shfl_sync(~0u, D1[0][0], 2);
      if (lane == 29) D1[1][3] -= kv512;
      const u32 tp = sb + SM_TAP + ksig * TAPS;
#pragma unroll
      for (int r = 0; r < 4; r++) {
        const u32 v = pk_hf(D1[r >> 1][2 * (r & 1)], D1[r >> 1][2 * (r & 1) + 1]), v0 = v & 0xffff, v1 = v >> 16;
        if (q < 2) {
          const int n = 128 + 32 * r + 4 * g + 2 * q;
          const u32 vv = v0 | (v0 << 16);
          sts32(tp + (TO + n) * 4, vv); sts16(tp + (TO + n + 1) * 4 + 2, v1); sts16(tp + (TO + n - 1) * 4, v0);
          sts32(tp + (TE + n) * 4, vv); sts32(tp + (TE + n + 1) * 4, v1 | (v0 << 16));
        } else {
          const int a = 63 + 32 * (q - 2) + 8 * r + g, ix = a + 2 * (a & 1);
          sts16(tp + T5 * 4 + ix * 2, v0); sts16(tp + T3 * 4 + ix * 2, v1);
        }
      }
#pragma unroll
      for (int r = 0; r < 2; r++) {
        const u32 v = pk_hf(D2[2 * r], D2[2 * r + 1]);
#pragma unroll
        for (int j = 0; j < 2; j++) {
          const u32 vj = j ? v >> 16 : v & 0xffff;
          const int x = 63 + hi + 8 * (2 * q + j) + 4 * r + (g >> 1);
          if (r == 0 && j == 0 && lane == 0) { sts16(tp + T5 * 4 + 129 * 2, vj); sts32(sb + SM_KV + 4 * ksig, vj); }
          else { sts16(tp + (hi ? TE7 : TE9) * 4 + (x + 2 * (x & 1)) * 2, vj); sts16(tp + (hi ? TO7 : TO9) * 4 + (x ^ 1) * 2, vj); }
        }
      }
      if (lane == 0) { sts16(tp + TO9 * 4 + 126 * 2, pk_hf(k2048, 0.f)); sts32(sb + SM_SC + 16 * ksig + 12, __float_as_uint(FK)); }
      __syncwarp();
#pragma unroll
      for (int r = 0; r < 4; r++) {
        const u32 v = pk_hf(D0[r >> 1][2 * (r & 1) + 1], D0[r >> 1][2 * (r & 1)]);
        const int n = 32 * r + lane;
        sts32(tp + (TO + n) * 4, v); sts16(tp + (TE + n) * 4, v >> 16); sts16(tp + (TE + n + 1) * 4 + 2, v & 0xffff);
      }
    }
  } else if (b < 72) {
    mod_gemv(sb, w, lane, 0, b, pm);
  }
  TSW(0, 6); TSW(10, 7); TSW(8, 8);
  if (w < 10) {
    const int c = tid % 10, t0 = tid / 10, s = c >> 1, sig = rho ? (s ? s - 1 : 4) : s;
    const char* src = (const char*)g_Z + (size_t)t0 * 18432 + Pb * 32 + c * 16;
    uint4 v[4]; int it = 0; u32 bad;
#pragma unroll
    for (int j = 0; j < 4; j++) v[j] = ldr128(src + (size_t)j * 32 * 18432);
    while (true) {
      bad = ((v[0].x ^ pm) | (v[1].x ^ pm) | (v[2].x ^ pm) | (v[3].x ^ pm)) & TAGM;
      if (!__any_sync(~0u, bad) || ++it > SPIN) break;
#pragma unroll
      for (int j = 0; j < 4; j++) if ((v[j].x ^ pm) & TAGM) v[j] = ldr128(src + (size_t)j * 32 * 18432);
    }
    if (bad) g_err = 1;
    TSW(0, 9);
    bsync(8, 352);
    const uint2 cc = lds64(sb + SM_SC + 16 * sig);
    const u32 dst = sb + SM_ZS + (sig < 4 ? sig * 4384 + 256 : 18560) + t0 * 32 + (c & 1) * 16;
#pragma unroll
    for (int j = 0; j < 4; j++)
      sts128(dst + j * 1024, hfma(v[j].x & ~TAGM, cc.x, cc.y), hfma(v[j].y, cc.x, cc.y), hfma(v[j].z, cc.x, cc.y), hfma(v[j].w, cc.x, cc.y));
  } else if (w == 11) {
    if (lane < 5) {
      const int d = chan_of(lane < 4 ? Pb + lane + rho : Pb + (rho ? 0 : 4));
      uint4 a, c; int it = 0; u32 bad;
      do { a = ldr128(mod_chunk(d)); c = ldr128(mod_chunk(576 + d)); bad = ((a.x ^ pm) | (c.x ^ pm)) & TAGM; } while (bad && ++it < SPIN);
      if (bad) g_err = 2;
      a.x &= ~TAGM; c.x &= ~TAGM;
      const int j = (d >> 1) & 3;
      u32 aw = j == 0 ? a.x : j == 1 ? a.y : j == 2 ? a.z : a.w, cw_ = j == 0 ? c.x : j == 1 ? c.y : j == 2 ? c.z : c.w;
      const float sa = ((d & 1) ? bhi(aw) : blo(aw)) * 1.8446744073709552e19f;
      const float c1 = rbf(fmaf((d & 1) ? bhi(cw_) : blo(cw_), 1.8446744073709552e19f, 1.f));
      const int EM = min(max((int)(__float_as_uint(fmaxf(32.f * fabsf(c1), fabsf(sa))) >> 23), 80), 250);
      const float inv = __uint_as_float((264 - EM) << 23);
      const u32 h1 = pk_hf(16.f * c1 * inv, 16.f * c1 * inv), h0 = pk_hf(sa * inv, sa * inv);
      sts64(sb + SM_SC + 16 * lane, h1, h0);
      sts32(sb + SM_SC + 16 * lane + 8, (EM - 74) << 23);
    }
    __syncwarp();
    TS(10);
    barrive(8, 352);
  }
  __syncthreads();
  TSW(0, 11);
  const u32 pml = (g & 3) ? 0 : pm;
  if (w < 4) {
    asm volatile("setmaxnreg.inc.sync.aligned.u32 232;");
    const u32 tp = sb + SM_TAP + w * TAPS;
    const u32 tr = tp + ((hi ? TO : TE) + (g >> 1) - q) * 4;
    const uint2* zb = (const uint2*)(smem + SM_ZS + w * 4384 + 256) + lane;
    const u32 wb = sb + SM_R + w * WSL;
    char* yp = (char*)g_Y + (size_t)(2 * q) * 18432 + (Pb + w + rho) * 32 + 4 * g;
    const uint2 fc = lds64(sb + SM_SC + 16 * w + 8);
    const float F = __uint_as_float(fc.x) * __uint_as_float(fc.y);
    u32 T[33][4];
#pragma unroll
    for (int j = 0; j < 33; j++) {
      const int d = j < 32 ? (7 - (j >> 2)) + 8 * (j & 3) : 32;
      T[d][0] = lds32(tr + 32 * d); T[d][3] = lds32(tr + 32 * d);
      T[d][1] = d < 32 ? lds32(tr + 32 * d + 16) : 0u; T[d][2] = d ? lds32(tr + 32 * d - 16) : 0u;
    }
    float acc[16][4] = {};
#define DENSE(E_) { const uint2 bf_ = zb[(E_) * 4]; _Pragma("unroll") for (int u = 0; u < 16; u++) { const int d = 8 * u - (E_); if (d >= 0 && d <= 32) mma_hf(acc[u], T[d][0], T[d][1], T[d][2], T[d][3], bf_.x, bf_.y); } }
#pragma unroll
    for (int ee = -7; ee <= 16; ee++) {
      DENSE(ee);
      if (ee >= 0 && (ee & 7) == 0) y_store(acc[ee >> 3], F, pml, yp, ee >> 3);
    }
    TSW(0, 12);
    bsync(10, 384);
    TSW(0, 13);
    const int rl = (lane & 7) + ((lane >> 3) & 1) + 8 * (lane >> 4);
#pragma unroll
    for (int ty = 0; ty < 2; ty++) {
      u32 B[5][2];
      const u32 bt = tp + ((ty ? T3 : T5) + g - q) * 4;
#pragma unroll
      for (int d = 4; d <= 8; d++) { B[d - 4][0] = lds32(bt + 32 * d); B[d - 4][1] = lds32(bt + 32 * d - 16); }
      const u32 wa = wb + (ty ? W3O : W5O) + rl * 16;
#pragma unroll
      for (int j = 0; j < 13; j++) {
        const int ord[13] = {-1, 11, 0, 10, 1, 9, 2, 8, 3, 7, 4, 6, 5};
        const int bb = ord[j];
        if (ty && bb < 0) continue;
        const uint4 a = ldsm4t(bb < 0 ? (rl == 16 ? wa - 256 : sb + SM_ZERO) : wa + bb * 256);
#pragma unroll
        for (int d = 4; d <= 8; d++) if (bb + d <= 15) mma_hf(acc[bb + d], a.x, a.y, a.z, a.w, B[d - 4][0], B[d - 4][1]);
      }
    }
#pragma unroll
    for (int ty = 0; ty < 2; ty++) {
      uint4 a[4];
      const u32 wa = wb + (ty ? W7O : W9O) + ((lane >> 3) & 1) * 1024 + ((lane & 7) + 8 * (lane >> 4)) * 16;
#pragma unroll
      for (int be = 0; be < 4; be++) a[be] = ldsm4t(wa + be * 256);
      const u32 bt = tp + ((ty ? (hi ? TO7 : TE7) : (hi ? TO9 : TE9)) + (g >> 1) - q) * 4;
#pragma unroll
      for (int d = 8; d <= 15; d++) {
        const u32 b0 = lds32(bt + 16 * d), b1 = lds32(bt + 16 * d - 16);
#pragma unroll
        for (int be = 0; be < 4; be++) if (d + 2 * be <= 15) mma_hf(acc[d + 2 * be], a[be].x, a[be].y, a[be].z, a[be].w, b0, b1);
      }
    }
    {
      const u32 kv = lds32(sb + SM_KV + 4 * w), bi = (g >> 1) == q ? (hi ? kv << 16 : kv) : 0u;
      const u32 wa = wb + V2O + ((lane >> 3) & 1) * 1024 + ((lane & 7) + 8 * (lane >> 4)) * 16;
#pragma unroll
      for (int j = 0; j < 4; j++) { const uint4 a = ldsm4t(wa + j * 256); mma8_hf(acc[8 + 2 * j], a.x, a.y, bi); mma8_hf(acc[9 + 2 * j], a.z, a.w, bi); }
    }
    barrive(11, 288);
    TSW(0, 14);
#pragma unroll
    for (int ee = 17; ee <= 96; ee++) {
      DENSE(ee);
      if (ee >= 49 && ee <= 72) DENSE(ee + 48);
      if ((ee & 7) == 0) y_store(acc[ee >> 3], F, pml, yp, ee >> 3);
    }
    y_store(acc[13], F, pml, yp, 13); y_store(acc[14], F, pml, yp, 14); y_store(acc[15], F, pml, yp, 15);
    asm volatile("setmaxnreg.dec.sync.aligned.u32 168;");
    TSW(0, 15);
  } else {
    if (w >= 8) asm volatile("setmaxnreg.dec.sync.aligned.u32 104;");
#pragma unroll 1
    for (int tk = tid - 128; tk < 485; tk += 256) {
      const int sig = tk / 97, i = tk - 97 * sig;
      const u32 za = sb + SM_ZS + (sig < 4 ? sig * 4384 + 256 : 18560) + i * 32;
      const uint4 c2 = lds128(za - 48), a1 = lds128(za - 32), b1 = lds128(za - 16), a0 = lds128(za), b0 = lds128(za + 16);
      const u32 P[17] = {c2.y, c2.w, a1.x, a1.z, b1.x, b1.z, a1.y, a1.w, b1.y, b1.w, a0.x, a0.z, b0.x, b0.z, a0.y, a0.w, b0.y};
      u32 Q[17], D1[15], F4[15], W5[13], D2[17];
#pragma unroll
      for (int j = 1; j < 17; j++) Q[j] = __byte_perm(P[j - 1], P[j], 0x5432);
#pragma unroll
      for (int j = 1; j < 15; j++) D1[j] = hadd(P[j], Q[j]);
#pragma unroll
      for (int j = 2; j < 15; j++) F4[j] = hadd(D1[j], D1[j - 1]);
#pragma unroll
      for (int n = 0; n < 13; n++) W5[n] = hadd(F4[n + 2], P[n]);
#pragma unroll
      for (int j = 5; j < 17; j++) D2[j] = hadd(Q[j], P[j - 1]);
      const u32 wa = sb + SM_R + sig * WSL;
      u32 o[8];
      sts128(wa + W5O + i * 32, W5[5], W5[6], W5[7], W5[8]);
      if (i < 96) sts128(wa + W5O + i * 32 + 16, W5[9], W5[10], W5[11], W5[12]);
#pragma unroll
      for (int n = 0; n < 8; n++) o[n] = hadd(D2[n + 5], Q[n + 4]);
      sts128(wa + W3O + i * 32, o[0], o[1], o[2], o[3]);
      if (i < 96) sts128(wa + W3O + i * 32 + 16, o[4], o[5], o[6], o[7]);
      if (i < 64) {
#pragma unroll
        for (int n = 0; n < 8; n++) o[n] = hadd(F4[n + 4], W5[n]);
        sts128(wa + W9O + i * 16, o[0], o[1], o[2], o[3]); sts128(wa + W9O + 1024 + i * 16, o[4], o[5], o[6], o[7]);
#pragma unroll
        for (int n = 0; n < 8; n++) o[n] = hadd(hadd(Q[n + 8], Q[n + 5]), W5[n + 5]);
        sts128(wa + W7O + i * 16, o[0], o[1], o[2], o[3]); sts128(wa + W7O + 1024 + i * 16, o[4], o[5], o[6], o[7]);
        sts128(wa + V2O + i * 16, D2[9], D2[10], D2[11], D2[12]); sts128(wa + V2O + 1024 + i * 16, D2[13], D2[14], D2[15], D2[16]);
      }
    }
    if (w < 8) {
      const int u0 = 4 * (w - 4) + 2 * rho;
      const u32 tp = sb + SM_TAP + 4 * TAPS;
      const u32 tr = tp + ((hi ? TO : TE) + (g >> 1) - q) * 4;
      const u32 zb = sb + SM_ZS + 18560 + (8 * u0 + 8) * 32 + lane * 8;
      const u32 wb = sb + SM_R + 4 * WSL;
      float acc[4][4] = {};
      barrive(10, 384);
      uint2 Fr[41];
#pragma unroll
      for (int j = 0; j < 8; j++) Fr[j] = lds64(zb - 32 * j);
      u32 prev = 0;
#pragma unroll
      for (int d = 0; d <= 32; d++) {
        Fr[d + 8] = lds64(zb - 32 * (d + 8));
        const u32 t0 = lds32(tr + 32 * d), t1 = d < 32 ? lds32(tr + 32 * d + 16) : 0u;
        mma_hf(acc[2 + (d & 1)], t0, t1, prev, t0, Fr[d].x, Fr[d].y);
        mma_hf(acc[d & 1], t0, t1, prev, t0, Fr[d + 8].x, Fr[d + 8].y);
        prev = t1;
      }
      bsync(12, 256);
      const int rl = (lane & 7) + ((lane >> 3) & 1) + 8 * (lane >> 4);
#pragma unroll
      for (int j = 0; j < 6; j++) {
        const int bb = u0 - 8 + j;
        if (bb >= -1) {
          const int row = 16 * bb + rl;
#pragma unroll
          for (int ty = 0; ty < 2; ty++) {
            const uint4 a = ldsm4t(row < 0 ? sb + SM_ZERO : wb + (ty ? W3O : W5O) + row * 16);
            const u32 bt = tp + ((ty ? T3 : T5) + g - q) * 4;
            if (j <= 4) mma_hf(acc[ty], a.x, a.y, a.z, a.w, lds32(bt + 32 * (8 - j)), lds32(bt + 32 * (8 - j) - 16));
            if (j >= 1) mma_hf(acc[2 + ty], a.x, a.y, a.z, a.w, lds32(bt + 32 * (9 - j)), lds32(bt + 32 * (9 - j) - 16));
          }
        }
      }
      if (u0 >= 8) {
        const u32 lo_ = ((lane >> 3) & 1) * 1024 + ((lane & 7) + 8 * (lane >> 4)) * 16;
#pragma unroll 1
        for (int be = 0; u0 - 2 * be >= 8; be++) {
          const int d = u0 - 2 * be;
#pragma unroll
          for (int ty = 0; ty < 2; ty++) {
            const uint4 a = ldsm4t(wb + (ty ? W7O : W9O) + lo_ + be * 256);
            const u32 bt = tp + ((ty ? (hi ? TO7 : TE7) : (hi ? TO9 : TE9)) + (g >> 1) - q) * 4 + 16 * d;
            const u32 r0 = lds32(bt - 16), r1 = lds32(bt), r2 = lds32(bt + 16);
            mma_hf(acc[ty], a.x, a.y, a.z, a.w, r1, r0);
            mma_hf(acc[2 + ty], a.x, a.y, a.z, a.w, r2, r1);
          }
        }
        const u32 kv = lds32(sb + SM_KV + 16), bi = (g >> 1) == q ? (hi ? kv << 16 : kv) : 0u;
        const uint4 a = ldsm4t(wb + V2O + lo_ + (u0 - 8) * 128);
        mma8_hf(acc[0], a.x, a.y, bi); mma8_hf(acc[2], a.z, a.w, bi);
      }
      barrive(11, 288);
      const uint2 fc = lds64(sb + SM_SC + 16 * 4 + 8);
      const float F = __uint_as_float(fc.x) * __uint_as_float(fc.y);
#pragma unroll
      for (int i = 0; i < 4; i++) { acc[0][i] += acc[1][i]; acc[2][i] += acc[3][i]; }
      char* yp = (char*)g_Y + (size_t)(8 * u0 + 2 * q) * 18432 + (Pb + (rho ? 0 : 4)) * 32 + 4 * g;
      y_store(acc[0], F, pml, yp, 0); y_store(acc[2], F, pml, yp, 1);
      TSW(7, 16);
    } else {
      barrive(10, 384);
      barrive(12, 256);
      if (w < 10) {
        if (b >= 72) mod_gemv(sb, w, lane, 0, b, pm);
        if (b < 88) mod_gemv(sb, w, lane, 1, 128 + b, pm);
        if (w == 9) {
          if (lane == 0) {
            mb_expect(sb + SM_MB + 24, 46080);
            for (int i = 0; i < 3; i++) tma2d(sb + SM_UP + i * 15360, &tm_up, sb + SM_MB + 24, 72 * (b >> 1) + 40 * rho, 192 * i);
          }
          __syncwarp();
          TS(17);
          bsync(11, 288);
          if (lane == 0) {
            asm volatile("fence.proxy.async.shared::cta;" ::: "memory");
            mb_expect(sb + SM_MB + 32, 41472);
            for (int i = 0; i < 2; i++) tma2d(sb + SM_WD + i * 20736, &tm_down, sb + SM_MB + 32, 72 * (b & 7), 288 * (b >> 3) + 144 * i);
          }
          __syncwarp();
        }
      } else if (w == 10) {
        float s1 = 0.f, s2 = 0.f;
#pragma unroll 1
        for (int j = lane; j < 72; j += 32) {
          uint4 a, c; int it = 0; u32 bad;
          const uint4 r = ldg128(p.wr + 8 * j);
          do { a = ldr128(mod_chunk(3 * 576 + 8 * j)); c = ldr128(mod_chunk(4 * 576 + 8 * j)); bad = ((a.x ^ pm) | (c.x ^ pm)) & TAGM; } while (bad && ++it < SPIN);
          if (bad) g_err = 3;
          const u32 aw[4] = {a.x & ~TAGM, a.y, a.z, a.w}, cw_[4] = {c.x & ~TAGM, c.y, c.z, c.w}, rw[4] = {r.x, r.y, r.z, r.w};
#pragma unroll
          for (int i = 0; i < 4; i++) {
            const u32 c1 = bfma(cw_[i], B2P64, BONE), s = bmul(aw[i], B2P64);
            s1 = fmaf(blo(c1), blo(rw[i]), s1); s1 = fmaf(bhi(c1), bhi(rw[i]), s1);
            s2 = fmaf(blo(s), blo(rw[i]), s2); s2 = fmaf(bhi(s), bhi(rw[i]), s2);
          }
        }
#pragma unroll
        for (int o = 16; o; o >>= 1) { s1 += __shfl_xor_sync(~0u, s1, o); s2 += __shfl_xor_sync(~0u, s2, o); }
        if (lane == 0) sts64(sb + SM_RC, __float_as_uint(s1), __float_as_uint(s2));
        __syncwarp();
        barrive(1, 320);
      }
      asm volatile("setmaxnreg.inc.sync.aligned.u32 168;");
    }
  }
  u32 x1[4][4], h2[4][4], gbw[4];
  float rsel_dummy = 0.f; (void)rsel_dummy;
  if (w < 9) {
    const int ch = 64 * w + 8 * (4 * e + q);
#pragma unroll
    for (int k = 0; k < 4; k++) xv[k] = ldg128(xrow + (4 * h + k + 8 * hi) * 576);
    const uint4 dk = ldg128(p.dsk + ch), wr = ldg128(p.wr + ch);
    uint4 md[6]; int it = 0; u32 bad;
    do {
      bad = 0;
#pragma unroll
      for (int j = 0; j < 6; j++) { md[j] = ldr128(mod_chunk(576 * j + ch)); bad |= md[j].x ^ pm; }
      bad &= TAGM;
    } while (__any_sync(~0u, bad) && ++it < SPIN);
    if (bad) g_err = 4;
    const char* ysrc = (const char*)g_Y + (size_t)b * 18432 + w * 2048 + lane * 16;
    uint4 yv[4];
#pragma unroll
    for (int v = 0; v < 4; v++) yv[v] = ldr128(ysrc + 512 * v);
    const u32 saw[4] = {md[0].x & ~TAGM, md[0].y, md[0].z, md[0].w}, caw[4] = {md[1].x & ~TAGM, md[1].y, md[1].z, md[1].w};
    const u32 gaw[4] = {md[2].x & ~TAGM, md[2].y, md[2].z, md[2].w}, sbw[4] = {md[3].x & ~TAGM, md[3].y, md[3].z, md[3].w};
    const u32 cbr[4] = {md[4].x & ~TAGM, md[4].y, md[4].z, md[4].w}, dw[4] = {dk.x, dk.y, dk.z, dk.w};
    gbw[0] = md[5].x & ~TAGM; gbw[1] = md[5].y; gbw[2] = md[5].z; gbw[3] = md[5].w;
    u32 hD[4][4], cb1[4];
#pragma unroll
    for (int v = 0; v < 4; v++) cb1[v] = bfma(cbr[v], B2P64, BONE);
#pragma unroll
    for (int k = 0; k < 4; k++) {
      const uint2 st = lds64(sb + SM_ST + 8 * (4 * h + k + 8 * hi));
      const float rs = __uint_as_float(st.y), rh = rbf(rs);
      const u32 nm = pk_bf(-__uint_as_float(st.x), -__uint_as_float(st.x)), rH = pk_bf(rh, rh), rL = pk_bf(rs - rh, rs - rh);
      const u32 xx[4] = {xv[k].x, xv[k].y, xv[k].z, xv[k].w};
#pragma unroll
      for (int v = 0; v < 4; v++) {
        const u32 d = badd(xx[v], nm), z = bfma(d, rH, bmul(d, rL));
        const u32 hh = bfma(saw[v], B2P64, bmul(z, bfma(caw[v], B2P64, BONE)));
        hD[k][v] = bmul(hh, dw[v]);
      }
    }
    u32 rb0, rb1;
    {
      const u32 c0 = hi ? cb1[1] : cb1[0], c2 = hi ? cb1[3] : cb1[2], w0 = hi ? wr.y : wr.x, w2 = hi ? wr.w : wr.z;
      const float q0 = blo(c0) * blo(w0), q1 = bhi(c0) * bhi(w0), q2 = blo(c2) * blo(w2), q3 = bhi(c2) * bhi(w2);
      const u32 H0 = pk_bf(q0, q1), H1 = pk_bf(q2, q3);
      const u32 L0 = pk_bf(q0 - blo(H0), q1 - bhi(H0)), L1 = pk_bf(q2 - blo(H1), q3 - bhi(H1));
      const int src = (lane ^ 16);
      rb0 = __shfl_sync(~0u, h ? L0 : H0, src); rb1 = __shfl_sync(~0u, h ? L1 : H1, src);
    }
    TSW(0, 18);
    it = 0;
    while (true) {
      bad = ((yv[0].x ^ pm) | (yv[1].x ^ pm) | (yv[2].x ^ pm) | (yv[3].x ^ pm)) & TAGM;
      if (!__any_sync(~0u, bad) || ++it > SPIN) break;
#pragma unroll
      for (int v = 0; v < 4; v++) if ((yv[v].x ^ pm) & TAGM) yv[v] = ldr128(ysrc + 512 * v);
    }
    if (bad) g_err = 5;
    TSW(0, 19);
#pragma unroll
    for (int k = 0; k < 4; k++) {
      const u32 xx[4] = {xv[k].x, xv[k].y, xv[k].z, xv[k].w};
#pragma unroll
      for (int v = 0; v < 4; v++) {
        const u32 yw = k == 0 ? yv[v].x & ~TAGM : k == 1 ? yv[v].y : k == 2 ? yv[v].z : yv[v].w;
        const u32 a = bfma(movm(yw), B2P64, hD[k][v]);
        x1[k][v] = bfma(bmul(gaw[v], a), B2P64, xx[v]);
      }
      float s[4] = {}, X[4] = {}, Y[4] = {}, R[4] = {};
      mma_bf(s, x1[k][0], x1[k][1], x1[k][2], x1[k][3], BONE, BONE);
      mma_bf(R, x1[k][0], x1[k][1], x1[k][2], x1[k][3], rb0, rb1);
      mma8_bf(X, x1[k][0], x1[k][1], x1[k][0]); mma8_bf(Y, x1[k][0], x1[k][1], x1[k][1]);
      mma8_bf(X, x1[k][2], x1[k][3], x1[k][2]); mma8_bf(Y, x1[k][2], x1[k][3], x1[k][3]);
      const bool own = (q >> 1) == e, sq = (q & 1) == h;
      const float v = own ? (sq ? (hi ? X[1] + Y[3] : X[0] + Y[2]) : s[0] + s[2]) : R[0] + R[3];
      sts32(spw + k * 64 + (own ? (sq ? 4 : 0) : 8 + 4 * (q & 1)), __float_as_uint(v));
    }
    bsync(1, 320);
    float S1 = 0.f, S2 = 0.f, S3 = 0.f;
#pragma unroll
    for (int i = 0; i < 9; i++) { uint4 t = lds128(spr + i * 320); S1 += __uint_as_float(t.x); S2 += __uint_as_float(t.y); S3 += __uint_as_float(t.z) + __uint_as_float(t.w); }
    const uint2 rc = lds64(sb + SM_RC);
    S1 += __shfl_xor_sync(~0u, S1, 16); S2 += __shfl_xor_sync(~0u, S2, 16); S3 += __shfl_xor_sync(~0u, S3, 16);
    const float mu = S1 * (1.f / 576.f), var = fmaxf(fmaf(-mu, mu, S2 * (1.f / 576.f)), 0.f);
    const float m = rbf(mu), sd = rbf(sqrtf(rbf(rbf(var) + 1e-5f)));
    const float rs = __frcp_rn(sd);
    const float r = fmaf(fmaf(-m, __uint_as_float(rc.x), S3), rs, __uint_as_float(rc.y));
    u32 rbits = pk_bf(r, 0.f) & 0xffff;
    if (rbits == 0x8000) rbits = 0;
    rbits = (rbits & 0x8000) ? (~rbits & 0xffff) : (rbits | 0x8000);
    const int tl = 4 * ((lane >> 1) & 1) + ((lane >> 2) & 3) + 8 * (lane & 1);
    const u32 key = (rbits << 16) | (par ? 0x1800u : 0u) | (u32)(2047 - 16 * b - tl);
    if (w == 8 && lane < 16) str32((u32*)g_KEY + 16 * b + tl, key);
    TSW(8, 20);
    const float rh = rbf(rs);
    const u32 nm_ = pk_bf(-m, rh), rL_ = pk_bf(rs - rh, rs - rh);
#pragma unroll
    for (int k = 0; k < 4; k++) {
      const u32 t = __shfl_sync(~0u, nm_, 4 * k + (g & 3)), rL = __shfl_sync(~0u, rL_, 4 * k + (g & 3));
      const u32 nm = __byte_perm(t, t, 0x1010), rH = __byte_perm(t, t, 0x3232);
#pragma unroll
      for (int v = 0; v < 4; v++) {
        const u32 d = badd(x1[k][v], nm), z = bfma(d, rH, bmul(d, rL));
        h2[k][v] = bfma(sbw[v], B2P64, bmul(z, cb1[v]));
      }
    }
    const u32 k1 = __reduce_max_sync(~0u, key), k2 = __reduce_max_sync(~0u, key == k1 ? 0u : key);
#pragma unroll
    for (int j = 0; j < 2; j++) {
      const int t = (2047 - ((j ? k2 : k1) & 2047)) & 15, k = t & 3;
      u32 a[4], c[4];
#pragma unroll
      for (int v = 0; v < 4; v++) {
        a[v] = k == 0 ? h2[0][v] : k == 1 ? h2[1][v] : k == 2 ? h2[2][v] : h2[3][v];
        c[v] = k == 0 ? x1[0][v] : k == 1 ? x1[1][v] : k == 2 ? x1[2][v] : x1[3][v];
      }
      if ((t >> 2) == (h + 2 * hi)) {
        uint4* dst = g_HX + (b * 2 + j) * 144 + 8 * w + 4 * e + q;
        str128(dst, bmul(a[0], B2M64) | pm, a[1], a[2], a[3]);
        str128(dst + 72, bmul(c[0], B2M64) | pm, c[1], c[2], c[3]);
      }
    }
    TSW(0, 21);
  }
  const int nun = 5 - rho, kq = w & 3, tg = w >> 2;
  uint4 A[2][9];
  mb_wait(sb + SM_MB + 16); mb_wait(sb + SM_MB + 24);
  {
    const u32 aa = sb + (((lane >> 3) & 1) ? SM_UP : SM_GATE) + (144 * kq + 8 * (lane >> 4) + (lane & 7)) * 80 + tg * 32;
#pragma unroll
    for (int s = 0; s < 9; s++) { A[0][s] = ldsm4t(aa + s * 1280); if (tg < 2) A[1][s] = ldsm4t(aa + s * 1280 + 16); }
  }
  TSW(0, 22);
  if (w < 8) {
    const uint4* ks = g_KEY + (8 * (lane >> 2) + w) * 4 + q;
    const u32 kt = par ? 0x1800u : 0u;
    uint4 a, c; int it = 0; u32 bad;
    do {
      a = ldr128(ks); c = ldr128(ks + 256);
      bad = ((a.x ^ kt) | (c.x ^ kt)) & 0x1800u;
    } while (__any_sync(~0u, bad) && ++it < SPIN);
    if (bad) g_err = 6;
    TSW(0, 23);
    const u32 kk[8] = {a.x, a.y, a.z, a.w, c.x, c.y, c.z, c.w};
    const u32 mx = __reduce_max_sync(~0u, max(max(max(a.x, a.y), max(a.z, a.w)), max(max(c.x, c.y), max(c.z, c.w))));
    if (lane == 0) sts32(sb + SM_GM + 4 * w, mx);
    bsync(13, 256);
    const uint4 m0 = lds128(sb + SM_GM), m1 = lds128(sb + SM_GM + 16);
    const u32 th = min(min(min(m0.x, m0.y), min(m0.z, m0.w)), min(min(m1.x, m1.y), min(m1.z, m1.w)));
#pragma unroll
    for (int j = 0; j < 8; j++)
      if (kk[j] >= th) { u32 pos; asm volatile("atom.shared.add.u32 %0,[%1],1;" : "=r"(pos) : "r"(sb + SM_CNT) : "memory"); sts32(sb + SM_LIST + 4 * pos, kk[j]); }
    bsync(13, 256);
    const int n = lds32(sb + SM_CNT);
    for (int i = tid; i < n; i += 256) {
      const u32 me = lds32(sb + SM_LIST + 4 * i);
      int rank = 0;
      for (int j = 0; j < n; j++) rank += lds32(sb + SM_LIST + 4 * j) > me;
      if (rank < 8) sts32(sb + SM_SEL + 4 * rank, me);
    }
  }
  __syncthreads();
  TSW(0, 24);
  u32 sel[8];
  { const uint4 s0 = lds128(sb + SM_SEL), s1 = lds128(sb + SM_SEL + 16);
    sel[0] = s0.x; sel[1] = s0.y; sel[2] = s0.z; sel[3] = s0.w; sel[4] = s1.x; sel[5] = s1.y; sel[6] = s1.z; sel[7] = s1.w; }
  int blk[8], lr[8]; u32 slow = 0, mine = 0;
#pragma unroll
  for (int j = 0; j < 8; j++) {
    const int t = 2047 - (sel[j] & 2047);
    blk[j] = t >> 4; lr[j] = 0;
#pragma unroll
    for (int i = 0; i < j; i++) lr[j] += blk[i] == blk[j];
    if (lr[j] >= 2) slow |= 1u << j;
    if (blk[j] == b) mine |= 1u << (t & 15);
  }
  if (slow) {
    if (w < 9) {
#pragma unroll
      for (int j = 2; j < 8; j++) if (((slow >> j) & 1) && blk[j] == b) {
        const int t = (2047 - (sel[j] & 2047)) & 15;
#pragma unroll
        for (int k = 0; k < 4; k++) if (t == 4 * h + k + 8 * hi) {
          uint4* dst = g_HX2 + j * 144 + 8 * w + 4 * e + q;
          str128(dst, bmul(h2[k][0], B2M64) | pm, h2[k][1], h2[k][2], h2[k][3]);
          str128(dst + 72, bmul(x1[k][0], B2M64) | pm, x1[k][1], x1[k][2], x1[k][3]);
        }
      }
      __threadfence();
    }
    __syncthreads();
    if (tid < 8 && ((slow >> tid) & 1)) {
      int bj = 0;
#pragma unroll
      for (int j = 0; j < 8; j++) if (j == tid) bj = blk[j];
      if (bj == b) { __threadfence(); str32(g_FLG + 32 * tid, ep + 1); }
      int it = 0;
      while (ldr32(g_FLG + 32 * tid) != ep + 1 && ++it < SPIN) {}
      if (it >= SPIN) g_err = 7;
      __threadfence();
    }
    __syncthreads();
  }
  if (w < 9) {
    const int c = tid % 72, j0 = tid / 72;
    int o0 = 0, o1 = 0;
#pragma unroll
    for (int j = 0; j < 4; j++) if (j == j0) { o0 = lr[j] < 2 ? (blk[j] * 2 + lr[j]) * 144 : -1 - j; o1 = lr[j + 4] < 2 ? (blk[j + 4] * 2 + lr[j + 4]) * 144 : -5 - j; }
    const uint4* s0 = (o0 >= 0 ? g_HX + o0 : g_HX2 + (-1 - o0) * 144) + c;
    const uint4* s1 = (o1 >= 0 ? g_HX + o1 : g_HX2 + (-1 - o1) * 144) + c;
    uint4 a, d; int it = 0; u32 bad;
    do { a = ldr128(s0); d = ldr128(s1); bad = ((a.x ^ pm) | (d.x ^ pm)) & TAGM; } while (__any_sync(~0u, bad) && ++it < SPIN);
    if (bad) g_err = 8;
    sts128(sb + SM_XS + j0 * 1168 + c * 16, bmul(a.x & ~TAGM, B2P64), a.y, a.z, a.w);
    sts128(sb + SM_XS + (j0 + 4) * 1168 + c * 16, bmul(d.x & ~TAGM, B2P64), d.y, d.z, d.w);
  }
  __syncthreads();
  TSW(0, 25);
  if (2 * tg < nun) {
    float c0[2][4] = {}, c1[2][4] = {};
    const u32 ba = sb + SM_XS + (lane & 7) * 1168 + (18 * kq + (lane >> 3)) * 16;
#pragma unroll
    for (int s = 0; s < 9; s += 2) {
      uint4 bb;
      if (s < 8) bb = ldsm4(ba + s * 32); else { uint2 t = ldsm2(ba + s * 32); bb.x = t.x; bb.y = t.y; }
      mma_bf(c0[0], A[0][s].x, A[0][s].y, A[0][s].z, A[0][s].w, bb.x, bb.y);
      if (tg < 2) mma_bf(c1[0], A[1][s].x, A[1][s].y, A[1][s].z, A[1][s].w, bb.x, bb.y);
      if (s < 8) {
        mma_bf(c0[1], A[0][s + 1].x, A[0][s + 1].y, A[0][s + 1].z, A[0][s + 1].w, bb.z, bb.w);
        if (tg < 2) mma_bf(c1[1], A[1][s + 1].x, A[1][s + 1].y, A[1][s + 1].z, A[1][s + 1].w, bb.z, bb.w);
      }
    }
    const u32 ra = sb + SM_RED + (2 * tg * 4 + kq) * 512 + lane * 16;
    sts128(ra, __float_as_uint(c0[0][0] + c0[1][0]), __float_as_uint(c0[0][1] + c0[1][1]), __float_as_uint(c0[0][2] + c0[1][2]), __float_as_uint(c0[0][3] + c0[1][3]));
    if (tg < 2) sts128(ra + 2048, __float_as_uint(c1[0][0] + c1[1][0]), __float_as_uint(c1[0][1] + c1[1][1]), __float_as_uint(c1[0][2] + c1[1][2]), __float_as_uint(c1[0][3] + c1[1][3]));
  }
  __syncthreads();
  if (w < nun) {
    float s[4] = {};
#pragma unroll
    for (int i = 0; i < 4; i++) { const uint4 t = lds128(sb + SM_RED + (w * 4 + i) * 512 + lane * 16); s[0] += __uint_as_float(t.x); s[1] += __uint_as_float(t.y); s[2] += __uint_as_float(t.z); s[3] += __uint_as_float(t.w); }
    const u32 sg = pk_bf(silu_f(rbf(s[0])), silu_f(rbf(s[1])));
    const u32 act = movm(bmul(bmul(sg, pk_bf(s[2], s[3])), B2M64));
    str32((u32*)(g_ACT + (9 * (b >> 1) + 5 * rho + w) * 8) + lane, act | (q ? 0 : pm));
  }
  TSW(0, 26);
  if (w < 9) {
    uint16_t* orow = p.out + (size_t)(16 * b) * 576 + 64 * w + 8 * (4 * e + q);
#pragma unroll
    for (int k = 0; k < 4; k++) {
      const int t = 4 * h + k + 8 * hi;
      uint4 o;
      o.x = bfma(bmul(gbw[0], h2[k][0]), B2P64, x1[k][0]); o.y = bfma(bmul(gbw[1], h2[k][1]), B2P64, x1[k][1]);
      o.z = bfma(bmul(gbw[2], h2[k][2]), B2P64, x1[k][2]); o.w = bfma(bmul(gbw[3], h2[k][3]), B2P64, x1[k][3]);
      if (!((mine >> t) & 1)) *(uint4*)(orow + t * 576) = o;
    }
    const uint4* src = g_ACT + (b >> 3) * 288 + tid;
    uint4 a; int it = 0; u32 bad;
    do { a = ldr128(src); bad = (a.x ^ pm) & TAGM; } while (__any_sync(~0u, bad) && ++it < SPIN);
    if (bad) g_err = 9;
    sts128(sb + SM_AC + tid * 16, a.x & ~TAGM, a.y, a.z, a.w);
  }
  TSW(0, 27);
  mb_wait(sb + SM_MB + 32);
  __syncthreads();
  TSW(0, 28);
  if (w < 5) {
    float c[3][4] = {};
    const u32 aa = sb + SM_WD + (8 * (lane >> 4) + (lane & 7)) * 144 + (2 * w + ((lane >> 3) & 1)) * 16;
    const u32 ba = sb + SM_AC + lane * 16;
#pragma unroll
    for (int s = 0; s < 18; s += 2) {
      const uint4 bb = ldsm4(ba + s * 256);
      const uint4 a0 = ldsm4t(aa + s * 2304), a1 = ldsm4t(aa + (s + 1) * 2304);
      mma_bf(c[s % 3], a0.x, a0.y, a0.z, a0.w, bb.x, bb.y);
      mma_bf(c[(s + 1) % 3], a1.x, a1.y, a1.z, a1.w, bb.z, bb.w);
    }
    uint2* dst = g_PART + ((b >> 3) * 72 + 9 * (b & 7) + 2 * w) * 32 + lane;
    u32 o[4];
#pragma unroll
    for (int i = 0; i < 4; i++) o[i] = (__float_as_uint((c[0][i] + c[1][i] + c[2][i]) * 1.8446744073709552e19f) & ~1u) | par;
    str64(dst, o[0], o[1]);
    if (w < 4) str64(dst + 32, o[2], o[3]);
    TSW(0, 29);
  } else if (w == 8 && b < 72) {
    int og = 0; u32 kg = 0;
#pragma unroll
    for (int j = 0; j < 8; j++) if (j == g) { og = lr[j] < 2 ? (blk[j] * 2 + lr[j]) * 144 : -1 - j; kg = sel[j]; }
    const uint4* xs = (og >= 0 ? g_HX + og : g_HX2 + (-1 - og) * 144) + 72 + b;
    uint4 xq, gq; int it = 0; u32 bad;
    do { xq = ldr128(xs); gq = ldr128(mod_chunk(5 * 576 + 8 * b)); bad = ((xq.x ^ pm) | (gq.x ^ pm)) & TAGM; } while (__any_sync(~0u, bad) && ++it < SPIN);
    if (bad) g_err = 10;
    const u32 x1w = q == 0 ? bmul(xq.x & ~TAGM, B2P64) : q == 1 ? xq.y : q == 2 ? xq.z : xq.w;
    const u32 gw = q == 0 ? gq.x & ~TAGM : q == 1 ? gq.y : q == 2 ? gq.z : gq.w;
    const u32 hw = lds32(sb + SM_XS + g * 1168 + b * 16 + q * 4);
    u32 rb_ = kg >> 16; rb_ = (rb_ & 0x8000) ? (rb_ ^ 0x8000) : (~rb_ & 0xffff);
    const float sgm = rcpf(1.f + ex2(-1.4426950408889634f * blo(rb_)));
    const u32 sg = pk_bf(sgm, sgm);
    const uint2* src = g_PART + b * 32 + lane;
    uint2 v[16]; it = 0;
#pragma unroll
    for (int j = 0; j < 16; j++) v[j] = ldr64(src + j * 72 * 32);
    while (true) {
      bad = 0;
#pragma unroll
      for (int j = 0; j < 16; j++) bad |= (v[j].x ^ par) | (v[j].y ^ par);
      bad &= 1;
      if (!__any_sync(~0u, bad) || ++it > SPIN) break;
#pragma unroll
      for (int j = 0; j < 16; j++) if (((v[j].x ^ par) | (v[j].y ^ par)) & 1) v[j] = ldr64(src + j * 72 * 32);
    }
    if (bad) g_err = 11;
    float s0 = 0.f, s1 = 0.f, s2 = 0.f, s3 = 0.f;
#pragma unroll
    for (int j = 0; j < 16; j += 2) { s0 += __uint_as_float(v[j].x); s1 += __uint_as_float(v[j].y); s2 += __uint_as_float(v[j + 1].x); s3 += __uint_as_float(v[j + 1].y); }
    const u32 yw = movm(pk_bf(s0 + s2, s1 + s3));
    const u32 o = bfma(bmul(gw, badd(hw, bmul(yw, sg))), B2P64, x1w);
    *(u32*)(p.out + (size_t)(2047 - (kg & 2047)) * 576 + 8 * b + 2 * q) = o;
    if (b == 0 && lane == 0) g_epoch = ep + 1;
    TS(30);
  }
}

typedef CUresult (*EncFn)(CUtensorMap*, CUtensorMapDataType, cuuint32_t, void*, const cuuint64_t*, const cuuint64_t*, const cuuint32_t*, const cuuint32_t*,
                          CUtensorMapInterleave, CUtensorMapSwizzle, CUtensorMapL2promotion, CUtensorMapFloatOOBfill);
static void make_map(EncFn enc, CUtensorMap* tm, void* ptr, int cols, int rows, int bw, int br, CUtensorMapSwizzle sw) {
  cuuint64_t gd[2] = {(cuuint64_t)cols, (cuuint64_t)rows}, gs[1] = {(cuuint64_t)cols * 2};
  cuuint32_t bd[2] = {(cuuint32_t)bw, (cuuint32_t)br}, es[2] = {1, 1};
  enc(tm, CU_TENSOR_MAP_DATA_TYPE_BFLOAT16, 2, ptr, gd, gs, bd, es, CU_TENSOR_MAP_INTERLEAVE_NONE, sw, CU_TENSOR_MAP_L2_PROMOTION_NONE, CU_TENSOR_MAP_FLOAT_OOB_FILL_NONE);
}
extern "C" void kernel_launch(void* const* d_in, const int* in_sizes, int n_in, void* d_out, int out_size) {
  static EncFn enc = nullptr;
  if (!enc) {
    cudaDriverEntryPointQueryResult qr;
    cudaGetDriverEntryPoint("cuTensorMapEncodeTiled", (void**)&enc, cudaEnableDefault, &qr);
    cudaFuncSetAttribute(fused_kernel, cudaFuncAttributeMaxDynamicSharedMemorySize, SM_TOTAL);
  }
  CUtensorMap tm_mod, tm_gate, tm_up, tm_down;
  make_map(enc, &tm_mod, d_in[13], 3456, 576, 16, 192, CU_TENSOR_MAP_SWIZZLE_32B);
  make_map(enc, &tm_gate, d_in[9], 4608, 576, 40, 192, CU_TENSOR_MAP_SWIZZLE_NONE);
  make_map(enc, &tm_up, d_in[10], 4608, 576, 40, 192, CU_TENSOR_MAP_SWIZZLE_NONE);
  make_map(enc, &tm_down, d_in[11], 576, 4608, 72, 144, CU_TENSOR_MAP_SWIZZLE_NONE);
  Prm p;
  p.x = (const uint16_t*)d_in[0]; p.la = (const uint16_t*)d_in[1]; p.ai = (const uint16_t*)d_in[2]; p.cr = (const uint16_t*)d_in[3];
  p.ci = (const uint16_t*)d_in[4]; p.ldt = (const uint16_t*)d_in[5]; p.dsk = (const uint16_t*)d_in[6]; p.wr = (const uint16_t*)d_in[8];
  p.c = (const uint16_t*)d_in[12]; p.out = (uint16_t*)d_out;
  fused_kernel<<<128, 384, SM_TOTAL>>>(p, tm_mod, tm_gate, tm_up, tm_down);
}
```

```cpp
#include <cuda_runtime.h>
#include <cuda.h>
#include <cuda_bf16.h>
#include <cuda_fp16.h>
#include <stdint.h>
#define FUSED 1
#define DEV __device__ __forceinline__
typedef uint32_t u32;

constexpr u32 OB_KEY = 0, OB_ACT = 128, OB_PART = 768, OB = 3072;
constexpr u32 G_Z = 0, G_Y = 128 * 18432, G_H2 = 2 * G_Y, G_X1 = 3 * G_Y, G_MOD = G_X1 + 8 * 1152, G_OB = G_MOD + 216 * 128, G_END = G_OB + 128 * OB;
__device__ __align__(128) unsigned char g_s[G_END];
__device__ u32 g_epoch;
__device__ u32 g_err;
#define TS(i)
#define TSW(ww, i)

constexpr int SM_GATE = 0, SM_UP = 46080, SM_ZS = 92160, SM_TAP = 114816, TAPS = 3392;
constexpr int SM_CNT = SM_TAP + 5 * TAPS;
constexpr int SM_FLG = SM_CNT + 16;
constexpr int SM_MB = SM_FLG + 16;
constexpr int SM_ST = SM_MB + 48;
constexpr int SM_SC = SM_ST + 256;
constexpr int SM_KV = SM_SC + 80;
constexpr int SM_RC = SM_KV + 32;
constexpr int SM_GM = SM_RC + 16;
constexpr int SM_SEL = SM_GM + 32;
constexpr int SM_GP = SM_SEL + 32;
constexpr int SM_SIL = SM_GP + 128;
constexpr int SM_SP = SM_SIL + 1152;
constexpr int SM_R = 139520;
static_assert(SM_SP + 5760 <= SM_R && SM_SP % 16 == 0 && SM_SEL % 16 == 0 && SM_ST % 16 == 0, "smem map");
constexpr int KTAB = 9216, WSL = 12832, W5O = 256, W3O = 3600, W9O = 6688, W7O = 8736, V2O = 10784;
constexpr int SM_S3 = SM_R + 5 * WSL;
constexpr int SM_WD = SM_R, SM_XS = SM_R + 41600, SM_AC = SM_XS + 9344, SM_RED = SM_AC + 4608, SM_LIST = SM_RED + 10240;
constexpr int SM_TOTAL = SM_R + 92160;
constexpr int TE = 4, TO = 272 + 4, T5 = 544 - 17, T3 = 608 - 17, TE9 = 672 - 25, TE7 = 760 - 25, TEO = 48;
constexpr int SPIN = 1 << 16;
constexpr u32 TAGM = 0x40004000u, INVAL = 0x00004801u;

DEV u32 s2u(const void* p) { return (u32)__cvta_generic_to_shared(p); }
DEV void mma_bf(float (&c)[4], u32 a0, u32 a1, u32 a2, u32 a3, u32 b0, u32 b1) {
  asm("mma.sync.aligned.m16n8k16.row.col.f32.bf16.bf16.f32 {%0,%1,%2,%3},{%4,%5,%6,%7},{%8,%9},{%0,%1,%2,%3};"
      : "+f"(c[0]), "+f"(c[1]), "+f"(c[2]), "+f"(c[3]) : "r"(a0), "r"(a1), "r"(a2), "r"(a3), "r"(b0), "r"(b1));
}
DEV void mma_hf(float (&c)[4], u32 a0, u32 a1, u32 a2, u32 a3, u32 b0, u32 b1) {
  asm("mma.sync.aligned.m16n8k16.row.col.f32.f16.f16.f32 {%0,%1,%2,%3},{%4,%5,%6,%7},{%8,%9},{%0,%1,%2,%3};"
      : "+f"(c[0]), "+f"(c[1]), "+f"(c[2]), "+f"(c[3]) : "r"(a0), "r"(a1), "r"(a2), "r"(a3), "r"(b0), "r"(b1));
}
DEV void mma8_bf(float (&c)[4], u32 a0, u32 a1, u32 b0) {
  asm("mma.sync.aligned.m16n8k8.row.col.f32.bf16.bf16.f32 {%0,%1,%2,%3},{%4,%5},{%6},{%0,%1,%2,%3};"
      : "+f"(c[0]), "+f"(c[1]), "+f"(c[2]), "+f"(c[3]) : "r"(a0), "r"(a1), "r"(b0));
}
DEV void mma8_hf(float (&c)[4], u32 a0, u32 a1, u32 b0) {
  asm("mma.sync.aligned.m16n8k8.row.col.f32.f16.f16.f32 {%0,%1,%2,%3},{%4,%5},{%6},{%0,%1,%2,%3};"
      : "+f"(c[0]), "+f"(c[1]), "+f"(c[2]), "+f"(c[3]) : "r"(a0), "r"(a1), "r"(b0));
}
DEV u32 movm(u32 x) { u32 r; asm("movmatrix.sync.aligned.m8n8.trans.b16 %0,%1;" : "=r"(r) : "r"(x)); return r; }
DEV uint4 ldsm4(u32 a) { uint4 r; asm volatile("ldmatrix.sync.aligned.m8n8.x4.shared.b16 {%0,%1,%2,%3},[%4];" : "=r"(r.x), "=r"(r.y), "=r"(r.z), "=r"(r.w) : "r"(a)); return r; }
DEV uint2 ldsm2(u32 a) { uint2 r; asm volatile("ldmatrix.sync.aligned.m8n8.x2.shared.b16 {%0,%1},[%2];" : "=r"(r.x), "=r"(r.y) : "r"(a)); return r; }
DEV uint4 ldsm4t(u32 a) { uint4 r; asm volatile("ldmatrix.sync.aligned.m8n8.x4.trans.shared.b16 {%0,%1,%2,%3},[%4];" : "=r"(r.x), "=r"(r.y), "=r"(r.z), "=r"(r.w) : "r"(a)); return r; }
DEV u32 lds32(u32 a) { u32 r; asm volatile("ld.volatile.shared.u32 %0,[%1];" : "=r"(r) : "r"(a)); return r; }
DEV uint2 lds64(u32 a) { uint2 r; asm volatile("ld.shared.v2.u32 {%0,%1},[%2];" : "=r"(r.x), "=r"(r.y) : "r"(a)); return r; }
DEV uint4 lds128(u32 a) { uint4 r; asm volatile("ld.shared.v4.u32 {%0,%1,%2,%3},[%4];" : "=r"(r.x), "=r"(r.y), "=r"(r.z), "=r"(r.w) : "r"(a)); return r; }
DEV void sts16(u32 a, u32 v) { asm volatile("st.shared.u16 [%0],%1;" ::"r"(a), "h"((unsigned short)v) : "memory"); }
DEV void sts32(u32 a, u32 v) { asm volatile("st.shared.u32 [%0],%1;" ::"r"(a), "r"(v) : "memory"); }
DEV void sts64(u32 a, u32 x, u32 y) { asm volatile("st.shared.v2.u32 [%0],{%1,%2};" ::"r"(a), "r"(x), "r"(y) : "memory"); }
DEV void sts128(u32 a, u32 x, u32 y, u32 z, u32 w) { asm volatile("st.shared.v4.u32 [%0],{%1,%2,%3,%4};" ::"r"(a), "r"(x), "r"(y), "r"(z), "r"(w) : "memory"); }
DEV uint4 ldr128(const void* p) { uint4 v; asm volatile("ld.relaxed.gpu.global.v4.u32 {%0,%1,%2,%3},[%4];" : "=r"(v.x), "=r"(v.y), "=r"(v.z), "=r"(v.w) : "l"(p) : "memory"); return v; }
DEV uint2 ldr64(const void* p) { uint2 v; asm volatile("ld.relaxed.gpu.global.v2.u32 {%0,%1},[%2];" : "=r"(v.x), "=r"(v.y) : "l"(p) : "memory"); return v; }
DEV u32 ldr32(const void* p) { u32 v; asm volatile("ld.relaxed.gpu.global.u32 %0,[%1];" : "=r"(v) : "l"(p) : "memory"); return v; }
DEV void str128(void* p, u32 x, u32 y, u32 z, u32 w) { asm volatile("st.relaxed.gpu.global.v4.u32 [%0],{%1,%2,%3,%4};" ::"l"(p), "r"(x), "r"(y), "r"(z), "r"(w) : "memory"); }
DEV void str64(void* p, u32 x, u32 y) { asm volatile("st.relaxed.gpu.global.v2.u32 [%0],{%1,%2};" ::"l"(p), "r"(x), "r"(y) : "memory"); }
DEV void str32(void* p, u32 x) { asm volatile("st.relaxed.gpu.global.u32 [%0],%1;" ::"l"(p), "r"(x) : "memory"); }
DEV void str16(void* p, u32 x) { asm volatile("st.relaxed.gpu.global.u16 [%0],%1;" ::"l"(p), "h"((unsigned short)x) : "memory"); }
DEV uint4 ldg128(const void* p) { uint4 v; asm volatile("ld.global.nc.v4.u32 {%0,%1,%2,%3},[%4];" : "=r"(v.x), "=r"(v.y), "=r"(v.z), "=r"(v.w) : "l"(p)); return v; }
DEV uint2 ldg64(const void* p) { uint2 v; asm volatile("ld.global.nc.v2.u32 {%0,%1},[%2];" : "=r"(v.x), "=r"(v.y) : "l"(p)); return v; }
DEV u32 ldg32(const void* p) { u32 v; asm volatile("ld.global.nc.u32 %0,[%1];" : "=r"(v) : "l"(p)); return v; }
DEV u32 ldg16(const void* p) { unsigned short v; asm volatile("ld.global.nc.u16 %0,[%1];" : "=h"(v) : "l"(p)); return v; }
#define bsync(id, n) asm volatile("bar.sync %0,%1;" ::"n"(id), "n"(n) : "memory")
#define barrive(id, n) asm volatile("bar.arrive %0,%1;" ::"n"(id), "n"(n) : "memory")
DEV void mb_init(u32 a) { asm volatile("mbarrier.init.shared.b64 [%0],1;" ::"r"(a) : "memory"); }
DEV void mb_expect(u32 a, u32 bytes) { asm volatile("mbarrier.arrive.expect_tx.shared.b64 _,[%0],%1;" ::"r"(a), "r"(bytes) : "memory"); }
DEV void mb_wait(u32 a) {
  u32 ok = 0; int it = 0;
  do { asm volatile("{.reg .pred p; mbarrier.try_wait.parity.shared.b64 p,[%1],0; selp.u32 %0,1,0,p;}" : "=r"(ok) : "r"(a) : "memory"); } while (!ok && ++it < SPIN);
  if (!ok) g_err = 0x100;
}
DEV void tma3d(u32 dst, const CUtensorMap* tm, u32 mb, u32 bytes, int c0, int c2) {
  mb_expect(mb, bytes);
  asm volatile("cp.async.bulk.tensor.3d.shared::cluster.global.mbarrier::complete_tx::bytes [%0],[%1,{%3,0,%4}],[%2];"
               ::"r"(dst), "l"((uint64_t)tm), "r"(mb), "r"(c0), "r"(c2) : "memory");
}
DEV float blo(u32 w) { return __uint_as_float(w << 16); }
DEV float bhi(u32 w) { return __uint_as_float(w & 0xffff0000u); }
DEV u32 pk_bf(float lo, float hi) { u32 r; asm("cvt.rn.bf16x2.f32 %0,%1,%2;" : "=r"(r) : "f"(hi), "f"(lo)); return r; }
DEV u32 pk_hf(float lo, float hi) { u32 r; asm("cvt.rn.f16x2.f32 %0,%1,%2;" : "=r"(r) : "f"(hi), "f"(lo)); return r; }
DEV float rbf(float x) { return __uint_as_float(pk_bf(0.f, x) & 0xffff0000u); }
DEV u32 bfma(u32 a, u32 b, u32 c) { u32 r; asm("fma.rn.bf16x2 %0,%1,%2,%3;" : "=r"(r) : "r"(a), "r"(b), "r"(c)); return r; }
DEV u32 bmul(u32 a, u32 b) { u32 r; asm("mul.rn.bf16x2 %0,%1,%2;" : "=r"(r) : "r"(a), "r"(b)); return r; }
DEV u32 badd(u32 a, u32 b) { u32 r; asm("add.rn.bf16x2 %0,%1,%2;" : "=r"(r) : "r"(a), "r"(b)); return r; }
DEV u32 hadd(u32 a, u32 b) { u32 r; asm("add.rn.f16x2 %0,%1,%2;" : "=r"(r) : "r"(a), "r"(b)); return r; }
DEV u32 hfma(u32 a, u32 b, u32 c) { u32 r; asm("fma.rn.f16x2 %0,%1,%2,%3;" : "=r"(r) : "r"(a), "r"(b), "r"(c)); return r; }
DEV u32 hcm(u32 s, u32 m, u32 mp) {
  __half2 S = *reinterpret_cast<__half2*>(&s), M = *reinterpret_cast<__half2*>(&m), P = *reinterpret_cast<__half2*>(&mp);
  __half2 r = __hfma2(__high2half2(S), P, __hmul2(__low2half2(S), M));
  return *reinterpret_cast<u32*>(&r);
}
DEV float ex2(float x) { float r; asm("ex2.approx.ftz.f32 %0,%1;" : "=f"(r) : "f"(x)); return r; }
DEV float rcpf(float x) { float r; asm("rcp.approx.ftz.f32 %0,%1;" : "=f"(r) : "f"(x)); return r; }
DEV float2 cmul(float2 a, float2 b) { return make_float2(fmaf(a.x, b.x, -a.y * b.y), fmaf(a.x, b.y, a.y * b.x)); }
DEV float2 csq(float2 a) { return make_float2(fmaf(a.x, a.x, -a.y * a.y), (a.x + a.x) * a.y); }
DEV float2 cexp(float lr2, float th) {
  float k = rintf(th * 0.15915494309189535f);
  float r = fmaf(k, -6.2831854820251465f, th); r = fmaf(k, 1.7484555e-7f, r);
  float m = ex2(lr2);
  return make_float2(m * __cosf(r), m * __sinf(r));
}
DEV float silu_f(float v) { return v * rcpf(1.f + ex2(-1.4426950408889634f * v)); }
constexpr u32 B2P64 = 0x5F805F80u, B2M64 = 0x1F801F80u, BONE = 0x3F803F80u;
DEV u32 chan_of(u32 P) { u32 r = P & 63; return (P & ~63) + 32 * (r & 1) + 8 * ((r >> 2) & 3) + 2 * (r >> 4) + ((r >> 1) & 1); }
DEV u32 mod_off(u32 idx) { return G_MOD + (idx >> 4) * 128 + (idx & 8) * 2; }
constexpr u32 MODJ = 36 * 128;
DEV float sqrta(float x) { float r; asm("sqrt.approx.ftz.f32 %0,%1;" : "=f"(r) : "f"(x)); return r; }
DEV u32 fu(float x) { return __float_as_uint(x); }
DEV float uf(u32 x) { return __uint_as_float(x); }
DEV void mma_hf_o(float (&d)[4], const float (&c)[4], const u32 (&a)[4], u32 b0, u32 b1) {
  asm("mma.sync.aligned.m16n8k16.row.col.f32.f16.f16.f32 {%0,%1,%2,%3},{%4,%5,%6,%7},{%8,%9},{%10,%11,%12,%13};"
      : "=f"(d[0]), "=f"(d[1]), "=f"(d[2]), "=f"(d[3]) : "r"(a[0]), "r"(a[1]), "r"(a[2]), "r"(a[3]), "r"(b0), "r"(b1), "f"(c[0]), "f"(c[1]), "f"(c[2]), "f"(c[3]));
}

struct Prm {
  const char *x, *la, *ai, *cr, *ci, *ldt, *dsk, *wr, *c;
  char* out;
};
constexpr float LOG2E = 1.4426950408889634f, F2P64 = 1.8446744073709552e19f, F2M64 = 5.421010862427522e-20f;

DEV void y_store(float c0, float c1, float c2, float c3, float F, u32 pml, char* yp) {
  str32(yp, pk_bf(c0 * F, c2 * F) | pml);
  str32(yp + 18432, pk_bf(c1 * F, c3 * F) | pml);
}
#define POLL(cond_bad, reload, code) { int it_ = 0; while (__any_sync(~0u, (cond_bad))) { if (++it_ > SPIN) { g_err = code; break; } reload; } }

__global__ void __launch_bounds__(384, 1)
fused_kernel(const Prm p, const __grid_constant__ CUtensorMap tm_mod, const __grid_constant__ CUtensorMap tm_gate,
             const __grid_constant__ CUtensorMap tm_up, const __grid_constant__ CUtensorMap tm_down) {
  extern __shared__ __align__(1024) unsigned char smem[];
  const u32 sb = s2u(smem);
  const u32 tid = threadIdx.x, w = tid >> 5, lane = tid & 31, b = blockIdx.x;
  const u32 g = lane >> 2, q = lane & 3, e = g >> 2, h = (g >> 1) & 1, hi = g & 1;
  const u32 rho = b & 1, Pm = 9 * (b >> 1) + 5 * rho, Ps = 9 * (b >> 1) + 4;
  char* const gs = (char*)g_s;
  TSW(0, 0);
  const u32 cho = 128 * w + 64 * e + 16 * q;
  uint4 xv[4];
  if (w < 9) {
    const char* xp = p.x + (b * 18432 + cho + (4 * h + hi) * 1152);
#pragma unroll
    for (int k = 0; k < 4; k++) xv[k] = ldg128(xp + (2 * (k >> 1) + 8 * (k & 1)) * 1152);
  }
  const bool kw = (w >> 1) != 4;
  const u32 ksig = w < 8 ? (w & 3) : 4, khf = w < 8 ? (w >> 2) : (w & 1);
  u32 la, ai, ldt; uint2 cr, ci;
  if (kw) {
    const u32 d = chan_of(w < 8 ? Pm + ksig : Ps), o = d * 256 + 8 * lane;
    la = ldg32(p.la + (o + 4 * khf)); ai = ldg32(p.ai + (o + 4 * khf));
    cr = ldg64(p.cr + o); ci = ldg64(p.ci + o); ldt = ldg16(p.ldt + 2 * d);
  } else {
    const char* cp = p.c + (576 * (w & 1) + 4 * lane);
    la = ldg32(cp); ai = ldg32(cp + 128); cr.x = ldg32(cp + 256); cr.y = ldg32(cp + 384); ci.x = lane < 16 ? ldg32(cp + 512) : 0;
  }
  const u32 ep = ldr32(&g_epoch);
  if (tid == 288) {
#pragma unroll
    for (int i = 0; i < 5; i++) mb_init(sb + SM_MB + 8 * i);
    asm volatile("fence.mbarrier_init.release.cluster;" ::: "memory");
    tma3d(sb + SM_UP, &tm_mod, sb + SM_MB, 18432, 16 * b, 0);
    if (b < 88) tma3d(sb + SM_UP + 18432, &tm_mod, sb + SM_MB + 8, 18432, 16 * b + 2048, 0);
    tma3d(sb + SM_GATE, &tm_gate, sb + SM_MB + 16, 46080, 8 * Pm, 0);
  }
#pragma unroll 1
  for (u32 i = SM_ZS + tid * 16; i < SM_MB; i += 384 * 16) sts128(sb + i, 0, 0, 0, 0);
  char* const zdst = gs + (b * 18432 + tid * 16 + (w * 2048 - w * 512));
  if (w < 9) {
#pragma unroll
    for (int v = 0; v < 4; v++) str128(zdst + 512 * v, INVAL, 0, 1, 0);
    str128(gs + (G_Y + 96 * 18432 + (w < 8 ? (tid >> 3) * 18432 + Pm * 32 + (tid & 7) * 16 : (16 * rho + (lane >> 1)) * 18432 + Ps * 32 + (lane & 1) * 16)), INVAL, 0, 1, 0);
  }
  if (tid < (b < 88 ? 196 : 194)) str128(gs + (tid < 192 ? G_OB + b * OB + tid * 16 : G_MOD + b * 128 + (tid & 2) * 8192 + (tid & 1) * 16), INVAL, 0, 1, 0);
  __syncthreads();
  const u32 par = (ep + 1) & 1, pm = par ? TAGM : 0;
  TSW(0, 1);
  const u32 ktab = sb + SM_R + (w < 8 ? w : w - 2) * KTAB;
  float FK, k2048 = 0.f;
  if (kw) {
    u32 mx = __vmaxu2(__vmaxu2(cr.x & 0x7fff7fff, cr.y & 0x7fff7fff), __vmaxu2(ci.x & 0x7fff7fff, ci.y & 0x7fff7fff));
    const u32 E = max(__reduce_max_sync(~0u, max(mx & 0xffff, mx >> 16)) >> 7, 8u);
    const float dt = rbf(ex2(blo(ldt) * LOG2E)), csc = uf((258 - E) << 23);
    FK = 2.f * dt * uf((E - 4) << 23);
    u32 crw = khf ? cr.y : cr.x, ciw = khf ? ci.y : ci.x;
    u32 ta = ktab + lane * 128;
    const u32 f = ((lane & 3) << 5) | ((lane & 4) << 2);
#pragma unroll 1
    for (int m = 0; m < 2; m++) {
      const float lr2 = rbf(ex2(blo(la) * LOG2E)) * dt * -LOG2E, th = blo(ai) * dt;
      const float2 C = make_float2(blo(crw) * csc, blo(ciw) * csc);
      la >>= 16; ai >>= 16; crw >>= 16; ciw >>= 16;
      const float2 w1 = cexp(lr2, th), w64 = cexp(64.f * lr2, 64.f * th);
      const float2 w2 = csq(w1), w4 = csq(w2), w8 = csq(w4), w16 = csq(w8), w32 = csq(w16);
      const float2 w128 = csq(w64), w256 = csq(w128), w512 = csq(w256), w1024 = csq(w512);
      u32 B0[8], B1[8], B2[8], S[8];
      const float2 a1 = cmul(C, w1), a2 = cmul(C, w2), a3 = cmul(a1, w2);
      B0[0] = pk_hf(C.x, C.y); B0[1] = pk_hf(a1.x, a1.y); B0[2] = pk_hf(a2.x, a2.y); B0[3] = pk_hf(a3.x, a3.y);
      const u32 h4 = pk_hf(w4.x, w4.y), h4p = pk_hf(-w4.y, w4.x), h256 = pk_hf(w256.x, w256.y), h256p = pk_hf(-w256.y, w256.x);
      const u32 h512 = pk_hf(w512.x, w512.y), h512p = pk_hf(-w512.y, w512.x);
#pragma unroll
      for (int i = 0; i < 4; i++) B0[4 + i] = hcm(B0[i], h4, h4p);
#pragma unroll
      for (int i = 0; i < 4; i++) B1[i] = hcm(B0[2 * i], h256, h256p);
      B1[4] = hcm(B0[0], h512, h512p); B1[5] = hcm(B0[4], h512, h512p);
      B1[6] = hcm(B1[4], h256, h256p); B1[7] = hcm(B1[5], h256, h256p);
      const float2 t0 = cmul(C, w1024), t1 = cmul(t0, w128), s3 = cmul(w8, w16);
      k2048 += fmaf(t0.x, w1024.x, -t0.y * w1024.y);
      B2[0] = pk_hf(t0.x, t0.y); B2[1] = pk_hf(t1.x, t1.y);
      B2[2] = hcm(B2[0], h256, h256p); B2[3] = hcm(B2[1], h256, h256p);
#pragma unroll
      for (int i = 0; i < 4; i++) B2[4 + i] = hcm(B2[i], h512, h512p);
      S[0] = 0x00003C00u; S[1] = pk_hf(w8.x, -w8.y); S[2] = pk_hf(w16.x, -w16.y); S[3] = pk_hf(s3.x, -s3.y); S[4] = pk_hf(w32.x, -w32.y);
      const u32 h32p = pk_hf(w32.y, w32.x);
#pragma unroll
      for (int i = 1; i < 4; i++) S[4 + i] = hcm(S[i], S[4], h32p);
#pragma unroll
      for (int i = 0; i < 8; i++) sts128(ta + ((i << 4) ^ f), B0[i], B1[i], B2[i], S[i]);
      sts128(ktab + 8192 + m * 512 + lane * 16, pk_hf(w64.x, -w64.y), pk_hf(w64.y, w64.x), pk_hf(w128.x, -w128.y), pk_hf(w128.y, w128.x));
      ta += 4096;
    }
  } else {
    u32 sa = sb + SM_SIL + 576 * (w & 1) + 4 * lane;
#pragma unroll 1
    for (int j = 0; j < 5; j++) {
      if (j < 4 || lane < 16) sts32(sa, pk_bf(silu_f(blo(la)), silu_f(bhi(la))));
      la = ai; ai = cr.x; cr.x = cr.y; cr.y = ci.x; sa += 128;
    }
  }
  __syncwarp();
  TSW(0, 2); TSW(10, 3);
  const u32 spw = sb + SM_SP + (2 * w + e) * 320 + (g & 3) * 16;
  const u32 spr = sb + SM_SP + (lane >> 4) * 9 * 320 + (lane & 15) * 16;
  const bool own = (q >> 1) == e, sq = (q & 1) == h;
  const u32 ssrc = g & 3;
  if (w < 9) {
#pragma unroll
    for (int k = 0; k < 4; k++) {
      float s[4] = {}, X[4] = {}, Y[4] = {};
      mma_bf(s, xv[k].x, xv[k].y, xv[k].z, xv[k].w, BONE, BONE);
      mma8_bf(X, xv[k].x, xv[k].y, xv[k].x); mma8_bf(Y, xv[k].x, xv[k].y, xv[k].y);
      mma8_bf(X, xv[k].z, xv[k].w, xv[k].z); mma8_bf(Y, xv[k].z, xv[k].w, xv[k].w);
      const float v = sq ? (hi ? X[1] + Y[3] : X[0] + Y[2]) : s[0] + s[2];
      if (own) sts32(spw + k * 64 + (sq ? 4 : 0), fu(v));
    }
    TSW(0, 4);
    bsync(1, 288);
    float S1 = 0.f, S2 = 0.f;
#pragma unroll
    for (int i = 0; i < 9; i++) { uint2 t = lds64(spr + i * 320); S1 += uf(t.x); S2 += uf(t.y); }
    S1 += __shfl_xor_sync(~0u, S1, 16); S2 += __shfl_xor_sync(~0u, S2, 16);
    const float mu = S1 * (1.f / 576.f), var = fmaxf(fmaf(-mu, mu, S2 * (1.f / 576.f)), 0.f);
    const float m = rbf(mu), rs = rcpf(rbf(sqrta(rbf(rbf(var) + 1e-5f))));
    const float ra = rs * 0.0625f, rc = -m * ra;
    u32 zt[4][4];
#pragma unroll
    for (int k = 0; k < 4; k++) {
      const float a = __shfl_sync(~0u, ra, 4 * k + ssrc), c = __shfl_sync(~0u, rc, 4 * k + ssrc);
      const u32 xx[4] = {xv[k].x, xv[k].y, xv[k].z, xv[k].w};
#pragma unroll
      for (int v = 0; v < 4; v++) zt[v][k] = movm(pk_hf(fmaf(blo(xx[v]), a, c), fmaf(bhi(xx[v]), a, c)));
    }
#pragma unroll
    for (int v = 0; v < 4; v++) str128(zdst + 512 * v, zt[v][0] | pm, zt[v][1], zt[v][2], zt[v][3]);
    if (w == 8) {
      const float rh = rbf(rs);
      sts128(sb + SM_ST + 16 * (4 * ((lane >> 1) & 1) + ((lane >> 2) & 2) + 2 * (lane & 4) + (lane & 1)), pk_bf(-m, -m), pk_bf(rh, rh), pk_bf(rs - rh, rs - rh), 0);
    }
  }
  TSW(0, 5);
  if (kw) {
    float D[5][4] = {};
    u32 ta = ktab + q * 128 + ((g ^ (q << 1)) << 4), tm = ktab + 8192 + q * 16;
#pragma unroll 1
    for (int s = 0; s < 8; s++) {
      const uint4 ca = lds128(ta), cb = lds128(ta + 4096), ma = lds128(tm), mb = lds128(tm + 512);
      ta = (ta + 512) ^ 16; tm += 64;
      const u32 a1 = hcm(ca.w, ma.x, ma.y), b1 = hcm(cb.w, mb.x, mb.y);
      const u32 a2 = hcm(ca.w, ma.z, ma.w), b2 = hcm(cb.w, mb.z, mb.w);
      const u32 a3 = hcm(a1, ma.z, ma.w), b3 = hcm(b1, mb.z, mb.w);
      mma_hf(D[0], ca.w, a1, cb.w, b1, ca.x, cb.x);
      mma_hf(D[2], ca.w, a1, cb.w, b1, ca.y, cb.y);
      mma_hf(D[4], ca.w, a1, cb.w, b1, ca.z, cb.z);
      mma_hf(D[1], a2, a3, b2, b3, ca.x, cb.x);
      mma_hf(D[3], a2, a3, b2, b3, ca.y, cb.y);
    }
    const u32 xa = sb + SM_R + (w < 8 ? 4 + ksig : 9) * KTAB + lane * 16;
    if (khf) {
      __syncwarp();
#pragma unroll
      for (int j = 0; j < 5; j++) sts128(xa + 512 * j, fu(D[j][0]), fu(D[j][1]), fu(D[j][2]), fu(D[j][3]));
      sts32(xa + 2560, fu(k2048));
      asm volatile("bar.arrive %0,64;" ::"r"(2 + ksig) : "memory");
    } else {
      asm volatile("bar.sync %0,64;" ::"r"(2 + ksig) : "memory");
#pragma unroll
      for (int j = 0; j < 5; j++) { const uint4 t = lds128(xa + 512 * j); D[j][0] += uf(t.x); D[j][1] += uf(t.y); D[j][2] += uf(t.z); D[j][3] += uf(t.w); }
      k2048 += uf(lds32(xa + 2560));
#pragma unroll
      for (int o = 16; o; o >>= 1) k2048 += __shfl_xor_sync(~0u, k2048, o);
      const float kv512 = __shfl_sync(~0u, D[2][0], 2);
      if (lane == 29) D[3][3] -= kv512;
      const u32 tp = sb + SM_TAP + ksig * TAPS;
      {
        const u32 a = 63 + 32 * q + g;
        const u32 t1 = tp + (q < 2 ? (128 + 4 * g + 2 * q) * 4 : T5 * 4 + (a - 64 + 2 * (a & 1)) * 2);
#pragma unroll
        for (int r = 0; r < 4; r++) {
          const u32 v = pk_hf(D[2 + (r >> 1)][2 * (r & 1)], D[2 + (r >> 1)][2 * (r & 1) + 1]);
          if (q < 2) {
            const u32 vv = __byte_perm(v, v, 0x1010);
            sts32(t1 + (TO + 32 * r) * 4, vv); sts16(t1 + (TO + 32 * r + 1) * 4 + 2, v >> 16); sts16(t1 + (TO + 32 * r - 1) * 4, v);
            sts64(t1 + (TE + 32 * r) * 4, vv, __byte_perm(v, v, 0x1032));
          } else {
            sts16(t1 + 16 * r, v); sts16(t1 + 16 * r + (T3 - T5) * 4, v >> 16);
          }
        }
      }
      {
        const u32 x = 63 + hi + 16 * q + (g >> 1), tb = tp + (hi ? TE7 : TE9) * 4;
        const u32 te = tb + (x + 2 * (x & 1)) * 2, to = tb + TEO * 4 + (x ^ 1) * 2;
#pragma unroll
        for (int r = 0; r < 2; r++) {
          const u32 v = pk_hf(D[4][2 * r], D[4][2 * r + 1]);
          if (r == 0 && lane == 0) { sts16(tp + T5 * 4 + 129 * 2, v); sts32(sb + SM_KV + 4 * ksig, v & 0xffff); sts16(tb + TEO * 4 + 126 * 2, pk_hf(k2048, 0.f)); sts32(sb + SM_SC + 16 * ksig + 12, fu(FK)); }
          else { sts16(te + 8 * r, v); sts16(to + 8 * r, v); }
          sts16(te + 8 * r + 16, v >> 16); sts16(to + 8 * r + 16, v >> 16);
        }
      }
      __syncwarp();
#pragma unroll
      for (int r = 0; r < 4; r++) {
        const u32 v = pk_hf(D[r >> 1][2 * (r & 1) + 1], D[r >> 1][2 * (r & 1)]), t1 = tp + lane * 4 + 128 * r;
        sts32(t1 + TO * 4, v); sts16(t1 + TE * 4, v >> 16); sts16(t1 + (TE + 1) * 4 + 2, v);
      }
      __syncwarp();
    }
  }
  TSW(0, 6); TSW(10, 7);
  const u32 pml = ssrc ? 0 : pm;
  const u32 rl16 = ((lane & 7) + ((lane >> 3) & 1) + 8 * (lane >> 4)) * 16;
  if (w < 4) {
    asm volatile("setmaxnreg.inc.sync.aligned.u32 232;");
    const u32 tp = sb + SM_TAP + w * TAPS;
    const u32 tr = tp + ((hi ? TO : TE) + (g >> 1) - q) * 4;
    u32 T[33][4], B5[5][2], B3[5][2];
#pragma unroll
    for (int d = 0; d < 33; d++) { T[d][0] = lds32(tr + 32 * d); T[d][1] = lds32(tr + 32 * d + 16); T[d][2] = d ? lds32(tr + 32 * d - 16) : 0u; T[d][3] = lds32(tr + 32 * d); }
    const u32 bt = tp + (T5 + g - q) * 4;
#pragma unroll
    for (int d = 0; d < 5; d++) {
      B5[d][0] = lds32(bt + 32 * d + 128); B5[d][1] = lds32(bt + 32 * d + 112);
      B3[d][0] = lds32(bt + 32 * d + 128 + (T3 - T5) * 4); B3[d][1] = lds32(bt + 32 * d + 112 + (T3 - T5) * 4);
    }
    u32 za = sb + SM_ZS + w * 4384 + 32 + lane * 8;
    u32 wa = sb + SM_R + w * WSL + W5O + rl16 - 768;
    u32 sa = sb + SM_S3 + w * 4096 + lane * 16 - 4096;
    char* yp = gs + (G_Y + 2 * q * 18432 + (Pm + w) * 32 + 4 * g);
    TSW(0, 8);
    bsync(9, 384);
    TSW(0, 11);
    const uint2 fc = lds64(sb + SM_SC + 16 * w + 8);
    const float F = uf(fc.x) * uf(fc.y);
    float A[5][4] = {};
    uint2 ring[4];
#pragma unroll
    for (int s = 0; s < 3; s++) ring[s] = lds64(za + 32 * s);
#pragma unroll 1
    for (int j = 0; j < 13; j++) {
#pragma unroll
      for (int s = 0; s < 7; s++) {
        ring[(s + 3) & 3] = lds64(za + 32 * (s + 3));
#pragma unroll
        for (int i = 0; i < 4; i++) mma_hf_o(A[i], A[i], T[8 * i + 7 - s], ring[s & 3].x, ring[s & 3].y);
      }
      ring[2] = lds64(za + 320);
      float O[4];
      mma_hf_o(O, A[0], T[0], ring[3].x, ring[3].y);
#pragma unroll
      for (int i = 0; i < 4; i++) mma_hf_o(A[i], A[i + 1], T[8 * i + 8], ring[3].x, ring[3].y);
      A[4][0] = A[4][1] = A[4][2] = A[4][3] = 0.f;
      if (j == 2) bsync(10, 384);
      if (j == 8) bsync(11, 256);
      const uint4 a5 = ldsm4t(wa), a3 = ldsm4t(wa + (W3O - W5O));
      uint4 s3 = {0, 0, 0, 0};
      if (j >= 8) s3 = lds128(sa);
      if (j >= 2) {
#pragma unroll
        for (int i = 4; i >= 0; i--) mma_hf(A[i], a5.x, a5.y, a5.z, a5.w, B5[i][0], B5[i][1]);
#pragma unroll
        for (int i = 4; i >= 0; i--) mma_hf(A[i], a3.x, a3.y, a3.z, a3.w, B3[i][0], B3[i][1]);
      }
      y_store(O[0] + uf(s3.x), O[1] + uf(s3.y), O[2] + uf(s3.z), O[3] + uf(s3.w), F, pml, yp);
      za += 256; wa += 256; sa += 512; yp += 8 * 18432;
    }
    TSW(0, 14);
    {
      float X[3][4] = {};
#pragma unroll
      for (int ty = 0; ty < 2; ty++) {
        const uint4 a = ldsm4t(wa + ty * (W3O - W5O)), c = ldsm4t(wa + 256 + ty * (W3O - W5O));
        mma_hf(X[0], a.x, a.y, a.z, a.w, ty ? B3[0][0] : B5[0][0], ty ? B3[0][1] : B5[0][1]);
        mma_hf(X[1], a.x, a.y, a.z, a.w, ty ? B3[1][0] : B5[1][0], ty ? B3[1][1] : B5[1][1]);
        mma_hf(X[2], c.x, c.y, c.z, c.w, ty ? B3[0][0] : B5[0][0], ty ? B3[0][1] : B5[0][1]);
      }
      barrive(12, 288);
#pragma unroll
      for (int s = 0; s < 8; s++) {
        const uint2 f0 = s < 3 ? ring[s] : lds64(za + 32 * s), f1 = lds64(za + 32 * s + 256), f2 = lds64(za + 32 * s + 512);
#pragma unroll
        for (int i = 0; i < 3; i++) mma_hf_o(A[i], A[i], T[8 * i + 7 - s], f0.x, f0.y);
        mma_hf_o(X[0], X[0], T[7 - s], f1.x, f1.y); mma_hf_o(X[1], X[1], T[15 - s], f1.x, f1.y);
        mma_hf_o(X[2], X[2], T[7 - s], f2.x, f2.y);
      }
      const uint4 s0 = lds128(sa), s1 = lds128(sa + 512), s2 = lds128(sa + 1024);
      y_store(A[0][0] + uf(s0.x), A[0][1] + uf(s0.y), A[0][2] + uf(s0.z), A[0][3] + uf(s0.w), F, pml, yp);
      y_store(A[1][0] + X[0][0] + uf(s1.x), A[1][1] + X[0][1] + uf(s1.y), A[1][2] + X[0][2] + uf(s1.z), A[1][3] + X[0][3] + uf(s1.w), F, pml, yp + 8 * 18432);
      y_store(A[2][0] + X[1][0] + (X[2][0] + uf(s2.x)), A[2][1] + X[1][1] + (X[2][1] + uf(s2.y)), A[2][2] + X[1][2] + (X[2][2] + uf(s2.z)), A[2][3] + X[1][3] + (X[2][3] + uf(s2.w)), F, pml, yp + 16 * 18432);
    }
    barrive(13, 288);
    TSW(0, 15);
  } else {
    asm volatile("setmaxnreg.dec.sync.aligned.u32 136;");
    const u32 t8 = tid - 128;
#pragma unroll 1
    for (int ph = 0; ph < 2; ph++) {
      if (!kw) {
        const u32 urg = b < 72;
#pragma unroll 1
        for (u32 slot = ph ? urg : 0; slot < (ph ? (b < 88 ? 2 : 1) : urg); slot++) {
          mb_wait(sb + SM_MB + 8 * slot);
          float c[2][4] = {};
          const u32 row = 288 * (w & 1) + (lane & 7) + 8 * (lane >> 4);
          u32 aa = sb + SM_UP + slot * 18432 + row * 32 + ((((lane >> 3) ^ (row >> 2)) & 1) << 4);
          u32 ba = sb + SM_SIL + 576 * (w & 1) + 4 * q;
#pragma unroll 1
          for (int s = 0; s < 3; s++) {
#pragma unroll
            for (int i = 0; i < 6; i++) { const uint4 a = ldsm4t(aa + i * 512); mma_bf(c[i & 1], a.x, a.y, a.z, a.w, lds32(ba + 32 * i), lds32(ba + 32 * i + 16)); }
            aa += 3072; ba += 192;
          }
          float v = (q & 1) ? c[0][2] + c[1][2] : c[0][0] + c[1][0];
          if (w & 1) sts32(sb + SM_GP + lane * 4, fu(v));
          bsync(7, 64);
          v += uf(lds32(sb + SM_GP + lane * 4));
          if (!(w & 1) && q < 2) str16(gs + (G_MOD + (b + 128 * slot) * 128 + 2 * g + 16 * q), pk_bf(rbf(v) * F2M64, 0.f) | (g < 2 ? pm : 0));
          bsync(7, 64);
        }
      }
      if (ph) break;
      TSW(8, 12);
      const char* zs = gs + ((t8 >> 3) * 18432 + Pm * 32 + (t8 & 7) * 16);
      const char* zs4 = gs + ((t8 >> 1) * 18432 + Ps * 32 + (t8 & 1) * 16);
      uint4 v[5];
#pragma unroll
      for (int j = 0; j < 5; j++) v[j].x = INVAL;
      POLL(((v[0].x ^ pm) | (v[1].x ^ pm) | (v[2].x ^ pm) | (v[3].x ^ pm) | (v[4].x ^ pm)) & TAGM,
           _Pragma("unroll") for (int j = 0; j < 5; j++) if ((v[j].x ^ pm) & TAGM) v[j] = ldr128(j < 4 ? zs + j * 32 * 18432 : zs4), 1);
      TSW(4, 9);
      if (w == 11) {
        const u32 d = chan_of(lane < 4 ? Pm + lane : Ps);
        const char* mp = gs + mod_off(d);
        u32 ta = INVAL, tc = INVAL, aw, cw;
        POLL(((ta ^ pm) | (tc ^ pm)) & TAGM, { ta = ldr32(mp); tc = ldr32(mp + MODJ); aw = ldr32(mp + (d & 6) * 2); cw = ldr32(mp + MODJ + (d & 6) * 2); }, 2);
        if (((aw ^ ta) | (cw ^ tc)) & ((d & 6) ? 0 : TAGM)) g_err = 12;
        aw = ldr32(mp + (d & 6) * 2) & ~TAGM; cw = ldr32(mp + MODJ + (d & 6) * 2) & ~TAGM;
        const float sa = ((d & 1) ? bhi(aw) : blo(aw)) * F2P64, c1 = rbf(fmaf((d & 1) ? bhi(cw) : blo(cw), F2P64, 1.f));
        const u32 EM = min(max(fu(fmaxf(32.f * fabsf(c1), fabsf(sa))) >> 23, 80u), 250u);
        const float inv = uf((264 - EM) << 23);
        if (lane < 5) { sts64(sb + SM_SC + 16 * lane, pk_hf(16.f * c1 * inv, 16.f * c1 * inv), pk_hf(sa * inv, sa * inv)); sts32(sb + SM_SC + 16 * lane + 8, (EM - 74) << 23); }
        TS(10);
      }
      bsync(8, 256);
      const uint2 cc = lds64(sb + SM_SC + 8 * (t8 & 6)), c4 = lds64(sb + SM_SC + 64);
      const u32 dst = sb + SM_ZS + 256 + (t8 & 6) * 2192 + (t8 >> 3) * 32 + (t8 & 1) * 16;
#pragma unroll
      for (int j = 0; j < 5; j++) {
        const uint2 c = j < 4 ? cc : c4;
        sts128(j < 4 ? dst + j * 1024 : sb + SM_ZS + 18560 + t8 * 16, hfma(v[j].x & ~TAGM, c.x, c.y), hfma(v[j].y, c.x, c.y), hfma(v[j].z, c.x, c.y), hfma(v[j].w, c.x, c.y));
      }
      bsync(9, 384);
#pragma unroll 1
      for (u32 tk = t8; tk < 485; tk += 256) {
        const u32 sig = tk / 97, i = tk - 97 * sig;
        const u32 za = sb + SM_ZS + 256 + sig * 4384 + (sig >> 2) * 768 + i * 32;
        const uint4 c2 = lds128(za - 48), a1 = lds128(za - 32), b1 = lds128(za - 16), a0 = lds128(za), b0 = lds128(za + 16);
        const u32 P[17] = {c2.y, c2.w, a1.x, a1.z, b1.x, b1.z, a1.y, a1.w, b1.y, b1.w, a0.x, a0.z, b0.x, b0.z, a0.y, a0.w, b0.y};
        u32 Q[17], D1[15], F4[15], W5[13], D2[17];
#pragma unroll
        for (int j = 1; j < 17; j++) Q[j] = __byte_perm(P[j - 1], P[j], 0x5432);
#pragma unroll
        for (int j = 1; j < 15; j++) D1[j] = hadd(P[j], Q[j]);
#pragma unroll
        for (int j = 2; j < 15; j++) F4[j] = hadd(D1[j], D1[j - 1]);
#pragma unroll
        for (int n = 0; n < 13; n++) W5[n] = hadd(F4[n + 2], P[n]);
#pragma unroll
        for (int j = 5; j < 17; j++) D2[j] = hadd(Q[j], P[j - 1]);
        const u32 wa = sb + SM_R + sig * WSL + i * 16, wb = wa + i * 16;
        u32 o[8];
#pragma unroll
        for (int n = 0; n < 8; n++) o[n] = hadd(D2[n + 5], Q[n + 4]);
        sts128(wb + W5O, W5[5], W5[6], W5[7], W5[8]); sts128(wb + W3O, o[0], o[1], o[2], o[3]);
        if (i < 96) { sts128(wb + W5O + 16, W5[9], W5[10], W5[11], W5[12]); sts128(wb + W3O + 16, o[4], o[5], o[6], o[7]); }
        if (i < 16) { sts128(wa, 0, 0, 0, 0); sts128(wa + W3O - 256, 0, 0, 0, 0); }
        if (i < 64) {
#pragma unroll
          for (int n = 0; n < 8; n++) o[n] = hadd(F4[n + 4], W5[n]);
          sts128(wa + W9O, o[0], o[1], o[2], o[3]); sts128(wa + W9O + 1024, o[4], o[5], o[6], o[7]);
#pragma unroll
          for (int n = 0; n < 8; n++) o[n] = hadd(hadd(Q[n + 8], Q[n + 5]), W5[n + 5]);
          sts128(wa + W7O, o[0], o[1], o[2], o[3]); sts128(wa + W7O + 1024, o[4], o[5], o[6], o[7]);
          sts128(wa + V2O, D2[9], D2[10], D2[11], D2[12]); sts128(wa + V2O + 1024, D2[13], D2[14], D2[15], D2[16]);
        }
      }
      if (w >= 8) barrive(10, 384);
    }
    if (w < 8) {
      bsync(10, 384);
      TSW(4, 13);
#pragma unroll 1
      for (u32 sl = w - 4;; sl = 4) {
        const u32 wa = sb + SM_R + sl * WSL + ((lane >> 3) & 1) * 1024 + ((lane & 7) + 8 * (lane >> 4)) * 16;
        const u32 kv = lds32(sb + SM_KV + 4 * sl), bi = (g >> 1) == q ? (hi ? kv << 16 : kv) : 0u;
        float acc[8][4] = {};
#pragma unroll
        for (int j = 0; j < 4; j++) { const uint4 a = ldsm4t(wa + V2O + j * 256); mma8_hf(acc[2 * j], a.x, a.y, bi); mma8_hf(acc[2 * j + 1], a.z, a.w, bi); }
        u32 bt = sb + SM_TAP + sl * TAPS + (TE9 + hi * TEO + (g >> 1) - q) * 4, wt = wa + W9O;
#pragma unroll 1
        for (int ty = 0; ty < 2; ty++) {
          uint4 a[4];
#pragma unroll
          for (int be = 0; be < 4; be++) a[be] = ldsm4t(wt + be * 256);
#pragma unroll
          for (int d = 0; d < 8; d++) {
            const u32 b0 = lds32(bt + 16 * d + 128), b1 = lds32(bt + 16 * d + 112);
#pragma unroll
            for (int be = 0; be < 4; be++) if (d + 2 * be < 8) mma_hf(acc[d + 2 * be], a[be].x, a[be].y, a[be].z, a[be].w, b0, b1);
          }
          bt += (TE7 - TE9) * 4; wt += W7O - W9O;
        }
#pragma unroll
        for (int j = 0; j < 8; j++) sts128(sb + SM_S3 + sl * 4096 + j * 512 + lane * 16, fu(acc[j][0]), fu(acc[j][1]), fu(acc[j][2]), fu(acc[j][3]));
        if (w != 4 || sl == 4) break;
      }
      barrive(11, 256);
      const int u0 = 4 * (w - 4) + 2 * rho;
      const u32 tp = sb + SM_TAP + 4 * TAPS;
      u32 tr = tp + ((hi ? TO : TE) + (g >> 1) - q) * 4;
      u32 zb = sb + SM_ZS + 18560 + u0 * 256 + lane * 8;
      float acc[4][4] = {};
      uint2 R[8];
#pragma unroll
      for (int j = 0; j < 8; j++) R[j] = lds64(zb + 256 - 32 * j);
      u32 prev = 0;
#pragma unroll 1
      for (int it = 0; it < 4; it++) {
#pragma unroll
        for (int s = 0; s < 8; s++) {
          const uint2 nw = lds64(zb - 32 * s);
          const u32 t0 = lds32(tr + 32 * s), t1 = lds32(tr + 32 * s + 16);
          mma_hf(acc[2 + (s & 1)], t0, t1, prev, t0, R[s].x, R[s].y);
          mma_hf(acc[s & 1], t0, t1, prev, t0, nw.x, nw.y);
          R[s] = nw; prev = t1;
        }
        zb -= 256; tr += 256;
      }
      { const uint2 nw = lds64(zb); const u32 t0 = lds32(tr); mma_hf(acc[2], t0, 0, prev, t0, R[0].x, R[0].y); mma_hf(acc[0], t0, 0, prev, t0, nw.x, nw.y); }
#pragma unroll 1
      for (int d = min(u0 + 1, 8); d >= 3; d--) {
        const u32 wa = sb + SM_R + 4 * WSL + W5O + rl16 + (u0 - d) * 256, bt = tp + (T5 + g - q) * 4 + 32 * d;
#pragma unroll
        for (int ty = 0; ty < 2; ty++) {
          const uint4 a = ldsm4t(wa + ty * (W3O - W5O));
          const u32 bb = bt + ty * (T3 - T5) * 4;
          mma_hf(acc[ty], a.x, a.y, a.z, a.w, lds32(bb), lds32(bb - 16));
          mma_hf(acc[2 + ty], a.x, a.y, a.z, a.w, lds32(bb + 32), lds32(bb + 16));
        }
      }
      barrive(12, 288);
      bsync(14, 128);
      const uint2 fc = lds64(sb + SM_SC + 16 * 4 + 8);
      const float F = uf(fc.x) * uf(fc.y);
      char* yp = gs + (G_Y + (8 * u0 + 2 * q) * 18432 + Ps * 32 + 4 * g);
#pragma unroll
      for (int j = 0; j < 2; j++) {
        uint4 s3 = {0, 0, 0, 0};
        if (u0 >= 8) s3 = lds128(sb + SM_S3 + 4 * 4096 + (u0 - 8 + j) * 512 + lane * 16);
        y_store(acc[2 * j][0] + acc[2 * j + 1][0] + uf(s3.x), acc[2 * j][1] + acc[2 * j + 1][1] + uf(s3.y), acc[2 * j][2] + acc[2 * j + 1][2] + uf(s3.z),
                acc[2 * j][3] + acc[2 * j + 1][3] + uf(s3.w), F, pml, yp + j * 8 * 18432);
      }
      TSW(7, 16);
    } else if (w == 9) {
      if (lane == 0) tma3d(sb + SM_UP, &tm_up, sb + SM_MB + 24, 46080, 8 * Pm, 0);
      TS(17);
      bsync(12, 288);
      if (lane == 0) {
        asm volatile("fence.proxy.async.shared::cta;" ::: "memory");
        tma3d(sb + SM_WD, &tm_down, sb + SM_MB + 32, 41472, 72 * (b & 7), 2 * (b >> 3));
      }
    } else if (w == 10) {
      float s1 = 0.f, s2 = 0.f;
#pragma unroll 1
      for (u32 j = lane; j < 96; j += 32) {
        const u32 jj = min(j, 71u);
        const char* mp = gs + mod_off(8 * jj);
        uint4 a, c, r = ldg128(p.wr + 16 * jj);
        a.x = INVAL;
        POLL(((a.x ^ pm) | (c.x ^ pm)) & TAGM, { a = ldr128(mp + 3 * MODJ); c = ldr128(mp + 4 * MODJ); }, 3);
        a.x &= ~TAGM; c.x &= ~TAGM;
#pragma unroll 1
        for (int i = j < 72 ? 0 : 4; i < 4; i++) {
          const u32 c1 = bfma(c.x, B2P64, BONE), s = bmul(a.x, B2P64);
          s1 = fmaf(blo(c1), blo(r.x), s1); s1 = fmaf(bhi(c1), bhi(r.x), s1);
          s2 = fmaf(blo(s), blo(r.x), s2); s2 = fmaf(bhi(s), bhi(r.x), s2);
          a.x = a.y; a.y = a.z; a.z = a.w; c.x = c.y; c.y = c.z; c.z = c.w; r.x = r.y; r.y = r.z; r.z = r.w;
        }
      }
#pragma unroll 1
      for (int o = 16; o; o >>= 1) { s1 += __shfl_xor_sync(~0u, s1, o); s2 += __shfl_xor_sync(~0u, s2, o); }
      sts64(sb + SM_RC, fu(s1), fu(s2));
      barrive(1, 320);
    }
  }
  u32 x1[4][4], h2[4][4], gbw[4];
  const u32 tko = (4 * h + 8 * hi) * 1152 + cho + b * 18432;
  if (w < 9) {
#pragma unroll
    for (int k = 0; k < 4; k++) xv[k] = ldg128(p.x + tko + k * 1152);
    const uint4 dk = ldg128(p.dsk + cho), wr = ldg128(p.wr + cho);
    const char* mp = gs + mod_off(cho >> 1);
    uint4 md[6];
    md[0].x = INVAL;
    POLL(((md[0].x ^ pm) | (md[1].x ^ pm) | (md[2].x ^ pm) | (md[3].x ^ pm) | (md[4].x ^ pm) | (md[5].x ^ pm)) & TAGM,
         _Pragma("unroll") for (int j = 0; j < 6; j++) md[j] = ldr128(mp + j * MODJ), 4);
    const u32 saw[4] = {md[0].x & ~TAGM, md[0].y, md[0].z, md[0].w}, caw[4] = {md[1].x & ~TAGM, md[1].y, md[1].z, md[1].w};
    const u32 gaw[4] = {md[2].x & ~TAGM, md[2].y, md[2].z, md[2].w}, sbw[4] = {md[3].x & ~TAGM, md[3].y, md[3].z, md[3].w};
    const u32 cbr[4] = {md[4].x & ~TAGM, md[4].y, md[4].z, md[4].w}, dw[4] = {dk.x, dk.y, dk.z, dk.w};
    gbw[0] = md[5].x & ~TAGM; gbw[1] = md[5].y; gbw[2] = md[5].z; gbw[3] = md[5].w;
    u32 hD[4][4], cb1[4], ca1[4];
#pragma unroll
    for (int v = 0; v < 4; v++) { cb1[v] = bfma(cbr[v], B2P64, BONE); ca1[v] = bfma(caw[v], B2P64, BONE); }
#pragma unroll
    for (int k = 0; k < 4; k++) {
      const uint4 st = lds128(sb + SM_ST + 16 * (4 * h + k + 8 * hi));
      const u32 xx[4] = {xv[k].x, xv[k].y, xv[k].z, xv[k].w};
#pragma unroll
      for (int v = 0; v < 4; v++) {
        const u32 d = badd(xx[v], st.x), z = bfma(d, st.y, bmul(d, st.z));
        hD[k][v] = bmul(bfma(saw[v], B2P64, bmul(z, ca1[v])), dw[v]);
      }
    }
    u32 rb0, rb1;
    {
      const u32 c0 = hi ? cb1[1] : cb1[0], c2 = hi ? cb1[3] : cb1[2], w0 = hi ? wr.y : wr.x, w2 = hi ? wr.w : wr.z;
      const u32 H0 = bmul(c0, w0), H1 = bmul(c2, w2);
      const u32 L0 = bfma(c0, w0, H0 ^ 0x80008000u), L1 = bfma(c2, w2, H1 ^ 0x80008000u);
      rb0 = __shfl_xor_sync(~0u, h ? L0 : H0, 16); rb1 = __shfl_xor_sync(~0u, h ? L1 : H1, 16);
    }
    TSW(0, 18);
    if (w >= 4) bsync(13, 288);
    const char* ysrc = zdst + G_Y;
    uint4 yv[4];
#pragma unroll
    for (int v = 0; v < 4; v++) yv[v].x = INVAL;
    POLL(((yv[0].x ^ pm) | (yv[1].x ^ pm) | (yv[2].x ^ pm) | (yv[3].x ^ pm)) & TAGM,
         _Pragma("unroll") for (int v = 0; v < 4; v++) if ((yv[v].x ^ pm) & TAGM) yv[v] = ldr128(ysrc + 512 * v), 5);
    TSW(0, 19);
#pragma unroll
    for (int k = 0; k < 4; k++) {
      const u32 xx[4] = {xv[k].x, xv[k].y, xv[k].z, xv[k].w};
#pragma unroll
      for (int v = 0; v < 4; v++) {
        const u32 yw = k == 0 ? yv[v].x & ~TAGM : k == 1 ? yv[v].y : k == 2 ? yv[v].z : yv[v].w;
        x1[k][v] = bfma(bmul(gaw[v], bfma(movm(yw), B2P64, hD[k][v])), B2P64, xx[v]);
      }
      float s[4] = {}, X[4] = {}, Y[4] = {}, R[4] = {};
      mma_bf(s, x1[k][0], x1[k][1], x1[k][2], x1[k][3], BONE, BONE);
      mma_bf(R, x1[k][0], x1[k][1], x1[k][2], x1[k][3], rb0, rb1);
      mma8_bf(X, x1[k][0], x1[k][1], x1[k][0]); mma8_bf(Y, x1[k][0], x1[k][1], x1[k][1]);
      mma8_bf(X, x1[k][2], x1[k][3], x1[k][2]); mma8_bf(Y, x1[k][2], x1[k][3], x1[k][3]);
      const float v = own ? (sq ? (hi ? X[1] + Y[3] : X[0] + Y[2]) : s[0] + s[2]) : R[0] + R[3];
      sts32(spw + k * 64 + (own ? (sq ? 4 : 0) : 8 + 4 * (q & 1)), fu(v));
    }
    bsync(1, 320);
    float S1 = 0.f, S2 = 0.f, S3 = 0.f, S4 = 0.f;
#pragma unroll
    for (int i = 0; i < 9; i++) { uint4 t = lds128(spr + i * 320); S1 += uf(t.x); S2 += uf(t.y); S3 += uf(t.z); S4 += uf(t.w); }
    const uint2 rc = lds64(sb + SM_RC);
    S3 += S4;
    S1 += __shfl_xor_sync(~0u, S1, 16); S2 += __shfl_xor_sync(~0u, S2, 16); S3 += __shfl_xor_sync(~0u, S3, 16);
    const float mu = S1 * (1.f / 576.f), var = fmaxf(fmaf(-mu, mu, S2 * (1.f / 576.f)), 0.f);
    const float m = rbf(mu), rs = rcpf(rbf(sqrta(rbf(rbf(var) + 1e-5f))));
    if (w == 8) {
      const int rb_ = (int)pk_bf(0.f, fmaf(fmaf(-m, uf(rc.x), S3), rs, uf(rc.y)) + 0.f);
      const u32 tl = 4 * ((lane >> 1) & 1) + ((lane >> 2) & 3) + 8 * (lane & 1);
      const u32 key = ((rb_ ^ ((rb_ >> 31) | 0x80000000)) & 0xffff0000u) | (par * 0x1800u + 2047 - 16 * b - tl);
      if (lane < 16) str32(gs + (G_OB + b * OB + OB_KEY + 4 * tl), key);
      TS(20);
    }
    const float rh = rbf(rs);
    const u32 nm_ = pk_bf(-m, rh), rL_ = pk_bf(rs - rh, rs - rh);
#pragma unroll
    for (int k = 0; k < 4; k++) {
      const u32 t = __shfl_sync(~0u, nm_, 4 * k + ssrc), rL = __shfl_sync(~0u, rL_, 4 * k + ssrc);
      const u32 nm = __byte_perm(t, t, 0x1010), rH = __byte_perm(t, t, 0x3232);
#pragma unroll
      for (int v = 0; v < 4; v++) {
        const u32 d = badd(x1[k][v], nm), z = bfma(d, rH, bmul(d, rL));
        h2[k][v] = bfma(sbw[v], B2P64, bmul(z, cb1[v]));
      }
      str128(gs + (G_H2 + tko + k * 1152), bmul(h2[k][0], B2M64) | pm, h2[k][1], h2[k][2], h2[k][3]);
    }
    TSW(0, 21);
  }
  const u32 kq = w & 3, tg = w >> 2;
  uint4 A[2][9];
  mb_wait(sb + SM_MB + 16); mb_wait(sb + SM_MB + 24);
  {
    const u32 aa = sb + ((lane & 8) ? SM_UP : SM_GATE) + (144 * kq + 8 * (lane >> 4) + (lane & 7)) * 80 + tg * 32;
#pragma unroll
    for (int s = 0; s < 9; s++) { A[0][s] = ldsm4t(aa + s * 1280); A[1][s] = ldsm4t(aa + s * 1280 + (tg < 2 ? 16 : 0)); }
  }
  TSW(0, 22);
  if (w < 8) {
    const char* ks = gs + (G_OB + OB_KEY + (8 * g + w) * OB + q * 16);
    const u32 kt = par * 0x1800u;
    uint4 a, c;
    a.x = INVAL;
    POLL(((a.x ^ kt) | (c.x ^ kt)) & 0x1800u, { a = ldr128(ks); c = ldr128(ks + 64 * OB); }, 6);
    TSW(0, 23);
    const u32 mx = __reduce_max_sync(~0u, max(max(max(a.x, a.y), max(a.z, a.w)), max(max(c.x, c.y), max(c.z, c.w))));
    sts32(sb + SM_GM + 4 * w, mx);
    bsync(2, 256);
    const u32 th = __reduce_min_sync(~0u, lds32(sb + SM_GM + 4 * (lane & 7)));
#pragma unroll 1
    for (int j = 0; j < 8; j++) {
      if (a.x >= th) { u32 pos; asm volatile("atom.shared.add.u32 %0,[%1],4;" : "=r"(pos) : "r"(sb + SM_CNT) : "memory"); sts32(sb + SM_LIST + pos, a.x); }
      a.x = a.y; a.y = a.z; a.z = a.w; a.w = c.x; c.x = c.y; c.y = c.z; c.z = c.w;
    }
    bsync(2, 256);
    const u32 n = lds32(sb + SM_CNT);
#pragma unroll 1
    for (u32 i = 4 * tid; i < n; i += 1024) {
      const u32 me = lds32(sb + SM_LIST + i);
      u32 rank = 0;
#pragma unroll 4
      for (u32 j = 0; j < n; j += 4) rank += lds32(sb + SM_LIST + j) > me;
      if (rank < 8) {
        sts32(sb + SM_SEL + 4 * rank, me);
        const u32 t = 2047 - (me & 2047);
        if ((t >> 4) == b) asm volatile("st.shared.u8 [%0],%1;" ::"r"(sb + SM_FLG + (t & 15)), "r"(rank + 1) : "memory");
      }
    }
  }
  __syncthreads();
  TSW(0, 24);
  if (w < 9) {
    const u32 j0 = tid / 72, c = 16 * (tid - 72 * j0);
    const char* s0 = gs + (G_H2 + 2047 * 1152 + c - (lds32(sb + SM_SEL + 4 * j0) & 2047) * 1152);
    const char* s1 = gs + (G_H2 + 2047 * 1152 + c - (lds32(sb + SM_SEL + 4 * j0 + 16) & 2047) * 1152);
    uint4 a, d;
    a.x = INVAL;
    POLL(((a.x ^ pm) | (d.x ^ pm)) & TAGM, { a = ldr128(s0); d = ldr128(s1); }, 8);
    sts128(sb + SM_XS + j0 * 1168 + c, bmul(a.x & ~TAGM, B2P64), a.y, a.z, a.w);
    sts128(sb + SM_XS + (j0 + 4) * 1168 + c, bmul(d.x & ~TAGM, B2P64), d.y, d.z, d.w);
  }
  __syncthreads();
  TSW(0, 25);
  {
    float c0[2][4] = {}, c1[2][4] = {};
    const u32 ba = sb + SM_XS + (lane & 7) * 1168 + (18 * kq + (lane >> 3)) * 16;
#pragma unroll
    for (int s = 0; s < 9; s += 2) {
      const uint4 bb = ldsm4(ba + s * 32);
      mma_bf(c0[0], A[0][s].x, A[0][s].y, A[0][s].z, A[0][s].w, bb.x, bb.y);
      if (tg < 2) mma_bf(c1[0], A[1][s].x, A[1][s].y, A[1][s].z, A[1][s].w, bb.x, bb.y);
      if (s < 8) {
        mma_bf(c0[1], A[0][s + 1].x, A[0][s + 1].y, A[0][s + 1].z, A[0][s + 1].w, bb.z, bb.w);
        if (tg < 2) mma_bf(c1[1], A[1][s + 1].x, A[1][s + 1].y, A[1][s + 1].z, A[1][s + 1].w, bb.z, bb.w);
      }
    }
    const u32 ra = sb + SM_RED + (8 * tg + kq) * 512 + lane * 16;
    sts128(ra, fu(c0[0][0] + c0[1][0]), fu(c0[0][1] + c0[1][1]), fu(c0[0][2] + c0[1][2]), fu(c0[0][3] + c0[1][3]));
    if (tg < 2) sts128(ra + 2048, fu(c1[0][0] + c1[1][0]), fu(c1[0][1] + c1[1][1]), fu(c1[0][2] + c1[1][2]), fu(c1[0][3] + c1[1][3]));
  }
  __syncthreads();
  if (w < 5 - rho) {
    float s[4] = {};
#pragma unroll
    for (int i = 0; i < 4; i++) { const uint4 t = lds128(sb + SM_RED + (w * 4 + i) * 512 + lane * 16); s[0] += uf(t.x); s[1] += uf(t.y); s[2] += uf(t.z); s[3] += uf(t.w); }
    const u32 sg = pk_bf(silu_f(rbf(s[0])), silu_f(rbf(s[1])));
    const u32 act = movm(bmul(bmul(sg, pk_bf(s[2], s[3])), B2M64));
    str32(gs + (G_OB + OB_ACT + b * OB + tid * 4), act | (q ? 0 : pm));
  }
  TSW(0, 26);
  if (w < 9) {
    const u32 ul = tid >> 3, pr = ul / 9, r9 = ul - 9 * pr;
    const char* src = gs + (G_OB + OB_ACT + ((b & ~7u) + 2 * pr) * OB + (r9 < 5 ? r9 * 128 : OB + (r9 - 5) * 128) + (tid & 7) * 16);
    uint4 a = ldr128(src);
    const u32 fl = lds32(sb + SM_FLG + 4 * h + 8 * hi);
#pragma unroll
    for (int k = 0; k < 4; k++) {
      const u32 f = (fl >> (8 * k)) & 255;
      if (f) str128(gs + (G_X1 - 1152 + f * 1152 + cho), bmul(x1[k][0], B2M64) | pm, x1[k][1], x1[k][2], x1[k][3]);
      else *(uint4*)(p.out + tko + k * 1152) = make_uint4(bfma(bmul(gbw[0], h2[k][0]), B2P64, x1[k][0]), bfma(bmul(gbw[1], h2[k][1]), B2P64, x1[k][1]),
                                                          bfma(bmul(gbw[2], h2[k][2]), B2P64, x1[k][2]), bfma(bmul(gbw[3], h2[k][3]), B2P64, x1[k][3]));
    }
    POLL((a.x ^ pm) & TAGM, a = ldr128(src), 9);
    sts128(sb + SM_AC + tid * 16, a.x & ~TAGM, a.y, a.z, a.w);
  }
  TSW(0, 27);
  mb_wait(sb + SM_MB + 32);
  __syncthreads();
  TSW(0, 28);
  if (w < 5) {
    float c[2][4] = {};
    u32 aa = sb + SM_WD + (8 * (lane >> 4) + (lane & 7)) * 144 + (2 * w + ((lane >> 3) & 1)) * 16, ba = sb + SM_AC + lane * 16;
#pragma unroll 3
    for (int s = 0; s < 9; s++) {
      const uint4 bb = ldsm4(ba), a0 = ldsm4t(aa), a1 = ldsm4t(aa + 2304);
      mma_bf(c[0], a0.x, a0.y, a0.z, a0.w, bb.x, bb.y);
      mma_bf(c[1], a1.x, a1.y, a1.z, a1.w, bb.z, bb.w);
      ba += 512; aa += 4608;
    }
    char* dst = gs + (G_OB + OB_PART + b * OB + w * 512 + lane * 8);
    u32 o[4];
#pragma unroll
    for (int i = 0; i < 4; i++) o[i] = (fu((c[0][i] + c[1][i]) * F2P64) & ~1u) | par;
    str64(dst, o[0], o[1]);
    if (w < 4) str64(dst + 256, o[2], o[3]);
    TSW(0, 29);
  } else if (w == 8 && b < 72) {
    const u32 kg = lds32(sb + SM_SEL + 4 * g), cg = b / 9;
    const char* src = gs + (G_OB + OB_PART + cg * OB + (b - 9 * cg) * 256 + lane * 8);
    const char* xs = gs + (G_X1 + g * 1152 + b * 16);
    u32 xt = INVAL;
    POLL((xt ^ pm) & TAGM, xt = ldr32(xs), 10);
    u32 x1w = ldr32(xs + 4 * q);
    const u32 gw = ldr32(gs + (mod_off(8 * b) + 5 * MODJ + 4 * q)) & ~TAGM;
    const u32 hw = lds32(sb + SM_XS + g * 1168 + b * 16 + q * 4);
    const float sgm = rcpf(1.f + ex2(-LOG2E * uf((kg ^ (((int)~kg >> 31) | 0x80000000)) & 0xffff0000u)));
    float s0 = 0.f, s1 = 0.f;
#pragma unroll 1
    for (int hf = 0; hf < 1; hf++) {
      uint2 v[16];
#pragma unroll
      for (int j = 0; j < 16; j++) v[j] = make_uint2(1, 0);
      u32 bad = 1;
      POLL(bad, { bad = 0; _Pragma("unroll") for (int j = 0; j < 16; j++) { if (((v[j].x ^ par) | (v[j].y ^ par)) & 1) v[j] = ldr64(src + j * 8 * OB); }
                  _Pragma("unroll") for (int j = 0; j < 16; j++) bad |= (v[j].x ^ par) | (v[j].y ^ par); bad &= 1; }, 11);
#pragma unroll
      for (int j = 0; j < 16; j++) { s0 += uf(v[j].x); s1 += uf(v[j].y); }
    }
    if (q == 0) x1w = bmul(x1w & ~TAGM, B2P64);
    const u32 o = bfma(bmul(gw, badd(hw, bmul(movm(pk_bf(s0, s1)), pk_bf(sgm, sgm)))), B2P64, x1w);
    *(u32*)(p.out + ((2047 - (kg & 2047)) * 1152 + 16 * b + 4 * q)) = o;
    if (b == 0 && lane == 0) g_epoch = ep + 1;
    TS(30);
  }
}

typedef CUresult (*EncFn)(CUtensorMap*, CUtensorMapDataType, cuuint32_t, void*, const cuuint64_t*, const cuuint64_t*, const cuuint32_t*, const cuuint32_t*,
                          CUtensorMapInterleave, CUtensorMapSwizzle, CUtensorMapL2promotion, CUtensorMapFloatOOBfill);
static void make_map(EncFn enc, CUtensorMap* tm, void* ptr, int cols, int rows, int bw, int br, int nb, CUtensorMapSwizzle sw) {
  cuuint64_t gd[3] = {(cuuint64_t)cols, (cuuint64_t)br, (cuuint64_t)(rows / br)}, gs[2] = {(cuuint64_t)cols * 2, (cuuint64_t)cols * 2 * br};
  cuuint32_t bd[3] = {(cuuint32_t)bw, (cuuint32_t)br, (cuuint32_t)nb}, es[3] = {1, 1, 1};
  enc(tm, CU_TENSOR_MAP_DATA_TYPE_BFLOAT16, 3, ptr, gd, gs, bd, es, CU_TENSOR_MAP_INTERLEAVE_NONE, sw, CU_TENSOR_MAP_L2_PROMOTION_NONE, CU_TENSOR_MAP_FLOAT_OOB_FILL_NONE);
}
extern "C" void kernel_launch(void* const* d_in, const int* in_sizes, int n_in, void* d_out, int out_size) {
  static EncFn enc = nullptr;
  if (!enc) {
    cudaDriverEntryPointQueryResult qr;
    cudaGetDriverEntryPoint("cuTensorMapEncodeTiled", (void**)&enc, cudaEnableDefault, &qr);
    cudaFuncSetAttribute(fused_kernel, cudaFuncAttributeMaxDynamicSharedMemorySize, SM_TOTAL);
  }
  CUtensorMap tm_mod, tm_gate, tm_up, tm_down;
  make_map(enc, &tm_mod, d_in[13], 3456, 576, 16, 192, 3, CU_TENSOR_MAP_SWIZZLE_32B);
  make_map(enc, &tm_gate, d_in[9], 4608, 576, 40, 192, 3, CU_TENSOR_MAP_SWIZZLE_NONE);
  make_map(enc, &tm_up, d_in[10], 4608, 576, 40, 192, 3, CU_TENSOR_MAP_SWIZZLE_NONE);
  make_map(enc, &tm_down, d_in[11], 576, 4608, 72, 144, 2, CU_TENSOR_MAP_SWIZZLE_NONE);
  Prm p;
  p.x = (const char*)d_in[0]; p.la = (const char*)d_in[1]; p.ai = (const char*)d_in[2]; p.cr = (const char*)d_in[3];
  p.ci = (const char*)d_in[4]; p.ldt = (const char*)d_in[5]; p.dsk = (const char*)d_in[6]; p.wr = (const char*)d_in[8];
  p.c = (const char*)d_in[12]; p.out = (char*)d_out;
  fused_kernel<<<128, 384, SM_TOTAL>>>(p, tm_mod, tm_gate, tm_up, tm_down);
}
```

```cpp
#include <cuda_runtime.h>
#include <cuda.h>
#include <cuda_bf16.h>
#include <cuda_fp16.h>
#include <stdint.h>
#define FUSED 1
#define DEV __device__ __forceinline__
typedef uint32_t u32;

constexpr u32 OB_KEY = 0, OB_ACT = 128, OB_PART = 768, OB = 3072, ROW = 1168;
constexpr u32 G_Z = 0, G_Y = 128 * 18432, G_XS = 2 * G_Y, G_X1 = G_XS + 8 * ROW, G_MOD = G_X1 + 8 * ROW, G_OB = G_MOD + 216 * 128;
constexpr u32 G_EP = G_OB + 128 * OB, G_END = G_EP + 128;
__device__ __align__(128) unsigned char g_s[G_END];
#define TS(i)
#define TSW(ww, i)
#define ERRF(code)

constexpr int SM0 = 1024;
constexpr int ZPS = 2240, ZSS = 4496, ZP4 = 2624;
constexpr int SM_GATE = SM0, SM_UP = SM_GATE + 46080, SM_ZS = SM_UP + 46080, SM_Z4 = SM_ZS + 4 * ZSS + 512;
constexpr int SM_TAP = SM_Z4 + ZP4 + 2048, TAPS = 3392;
constexpr int SM_MB = SM_TAP + 5 * TAPS;
constexpr int SM_ST = SM_MB + 48;
constexpr int SM_SC = SM_ST + 256;
constexpr int SM_KV = SM_SC + 80;
constexpr int SM_RC = SM_KV + 32;
constexpr int SM_THR = SM_RC + 16;
constexpr int SM_KEY = SM_THR + 48;
constexpr int SM_TOK = SM_KEY + 64;
constexpr int SM_CNT = SM_TOK + 128;
constexpr int SM_GP = SM_CNT + 128;
constexpr int SM_SIL = SM_GP + 128;
constexpr int SM_SP = SM_SIL + 1152;
constexpr int SM_R = (SM_SP + 5760 + 127) / 128 * 128;
static_assert(SM_SP % 16 == 0 && SM_THR % 16 == 0 && SM_ST % 16 == 0 && SM_TAP % 16 == 0 && SM_CNT % 16 == 0, "smem map");
constexpr int KTAB = 9216, WSL = 12832, W5O = 256, W3O = 3600, W9O = 6688, W7O = 8736, V2O = 10784;
constexpr int SM_S3 = SM_R + 5 * WSL;
constexpr int SM_WD = SM_R, SM_XS = SM_R + 41600, SM_AC = SM_XS + 9344, SM_RED = SM_AC + 4608, SM_OS = SM_RED + 10240;
constexpr int STASH = 16 * ROW + 64, SM_HS = SM_ZS, SM_X1S = SM_HS + STASH;
constexpr int SM_TOTAL = SM_R + 92160 - SM0;
static_assert(SM_X1S + STASH <= SM_MB && SM_OS + STASH <= SM_R + 92160 && SM_TOTAL <= 232448, "smem map");
constexpr int TE = 4, TO = 272 + 4, T5 = 544 - 17, T3 = 608 - 17, TE9 = 672 - 25, TE7 = 760 - 25, TEO = 48;
constexpr int SPIN = 1 << 16;
constexpr u32 TAGM = 0x40004000u, INVAL = 0x00004801u;

DEV u32 s2u(const void* p) { return (u32)__cvta_generic_to_shared(p); }
DEV void mma_bf(float (&c)[4], u32 a0, u32 a1, u32 a2, u32 a3, u32 b0, u32 b1) {
  asm("mma.sync.aligned.m16n8k16.row.col.f32.bf16.bf16.f32 {%0,%1,%2,%3},{%4,%5,%6,%7},{%8,%9},{%0,%1,%2,%3};"
      : "+f"(c[0]), "+f"(c[1]), "+f"(c[2]), "+f"(c[3]) : "r"(a0), "r"(a1), "r"(a2), "r"(a3), "r"(b0), "r"(b1));
}
DEV void mma_hf(float (&c)[4], u32 a0, u32 a1, u32 a2, u32 a3, u32 b0, u32 b1) {
  asm("mma.sync.aligned.m16n8k16.row.col.f32.f16.f16.f32 {%0,%1,%2,%3},{%4,%5,%6,%7},{%8,%9},{%0,%1,%2,%3};"
      : "+f"(c[0]), "+f"(c[1]), "+f"(c[2]), "+f"(c[3]) : "r"(a0), "r"(a1), "r"(a2), "r"(a3), "r"(b0), "r"(b1));
}
DEV void mma8_bf(float (&c)[4], u32 a0, u32 a1, u32 b0) {
  asm("mma.sync.aligned.m16n8k8.row.col.f32.bf16.bf16.f32 {%0,%1,%2,%3},{%4,%5},{%6},{%0,%1,%2,%3};"
      : "+f"(c[0]), "+f"(c[1]), "+f"(c[2]), "+f"(c[3]) : "r"(a0), "r"(a1), "r"(b0));
}
DEV void mma8_hf(float (&c)[4], u32 a0, u32 a1, u32 b0) {
  asm("mma.sync.aligned.m16n8k8.row.col.f32.f16.f16.f32 {%0,%1,%2,%3},{%4,%5},{%6},{%0,%1,%2,%3};"
      : "+f"(c[0]), "+f"(c[1]), "+f"(c[2]), "+f"(c[3]) : "r"(a0), "r"(a1), "r"(b0));
}
DEV u32 movm(u32 x) { u32 r; asm("movmatrix.sync.aligned.m8n8.trans.b16 %0,%1;" : "=r"(r) : "r"(x)); return r; }
DEV uint4 ldsm4(u32 a) { uint4 r; asm volatile("ldmatrix.sync.aligned.m8n8.x4.shared.b16 {%0,%1,%2,%3},[%4];" : "=r"(r.x), "=r"(r.y), "=r"(r.z), "=r"(r.w) : "r"(a)); return r; }
DEV uint2 ldsm2(u32 a) { uint2 r; asm volatile("ldmatrix.sync.aligned.m8n8.x2.shared.b16 {%0,%1},[%2];" : "=r"(r.x), "=r"(r.y) : "r"(a)); return r; }
DEV uint4 ldsm4t(u32 a) { uint4 r; asm volatile("ldmatrix.sync.aligned.m8n8.x4.trans.shared.b16 {%0,%1,%2,%3},[%4];" : "=r"(r.x), "=r"(r.y), "=r"(r.z), "=r"(r.w) : "r"(a)); return r; }
DEV u32 lds32(u32 a) { u32 r; asm volatile("ld.volatile.shared.u32 %0,[%1];" : "=r"(r) : "r"(a)); return r; }
DEV uint2 lds64(u32 a) { uint2 r; asm volatile("ld.shared.v2.u32 {%0,%1},[%2];" : "=r"(r.x), "=r"(r.y) : "r"(a)); return r; }
DEV uint4 lds128(u32 a) { uint4 r; asm volatile("ld.shared.v4.u32 {%0,%1,%2,%3},[%4];" : "=r"(r.x), "=r"(r.y), "=r"(r.z), "=r"(r.w) : "r"(a)); return r; }
DEV void sts16(u32 a, u32 v) { asm volatile("st.shared.u16 [%0],%1;" ::"r"(a), "h"((unsigned short)v) : "memory"); }
DEV void sts32(u32 a, u32 v) { asm volatile("st.shared.u32 [%0],%1;" ::"r"(a), "r"(v) : "memory"); }
DEV void sts64(u32 a, u32 x, u32 y) { asm volatile("st.shared.v2.u32 [%0],{%1,%2};" ::"r"(a), "r"(x), "r"(y) : "memory"); }
DEV void sts128(u32 a, u32 x, u32 y, u32 z, u32 w) { asm volatile("st.shared.v4.u32 [%0],{%1,%2,%3,%4};" ::"r"(a), "r"(x), "r"(y), "r"(z), "r"(w) : "memory"); }
DEV uint4 ldr128(const void* p) { uint4 v; asm volatile("ld.relaxed.gpu.global.v4.u32 {%0,%1,%2,%3},[%4];" : "=r"(v.x), "=r"(v.y), "=r"(v.z), "=r"(v.w) : "l"(p) : "memory"); return v; }
DEV uint2 ldr64(const void* p) { uint2 v; asm volatile("ld.relaxed.gpu.global.v2.u32 {%0,%1},[%2];" : "=r"(v.x), "=r"(v.y) : "l"(p) : "memory"); return v; }
DEV u32 ldr32(const void* p) { u32 v; asm volatile("ld.relaxed.gpu.global.u32 %0,[%1];" : "=r"(v) : "l"(p) : "memory"); return v; }
DEV void str128(void* p, u32 x, u32 y, u32 z, u32 w) { asm volatile("st.relaxed.gpu.global.v4.u32 [%0],{%1,%2,%3,%4};" ::"l"(p), "r"(x), "r"(y), "r"(z), "r"(w) : "memory"); }
DEV void str64(void* p, u32 x, u32 y) { asm volatile("st.relaxed.gpu.global.v2.u32 [%0],{%1,%2};" ::"l"(p), "r"(x), "r"(y) : "memory"); }
DEV void str32(void* p, u32 x) { asm volatile("st.relaxed.gpu.global.u32 [%0],%1;" ::"l"(p), "r"(x) : "memory"); }
DEV void str16(void* p, u32 x) { asm volatile("st.relaxed.gpu.global.u16 [%0],%1;" ::"l"(p), "h"((unsigned short)x) : "memory"); }
DEV uint4 ldg128(const void* p) { uint4 v; asm volatile("ld.global.nc.v4.u32 {%0,%1,%2,%3},[%4];" : "=r"(v.x), "=r"(v.y), "=r"(v.z), "=r"(v.w) : "l"(p)); return v; }
DEV uint2 ldg64(const void* p) { uint2 v; asm volatile("ld.global.nc.v2.u32 {%0,%1},[%2];" : "=r"(v.x), "=r"(v.y) : "l"(p)); return v; }
DEV u32 ldg32(const void* p) { u32 v; asm volatile("ld.global.nc.u32 %0,[%1];" : "=r"(v) : "l"(p)); return v; }
DEV u32 ldg16(const void* p) { unsigned short v; asm volatile("ld.global.nc.u16 %0,[%1];" : "=h"(v) : "l"(p)); return v; }
#define bsync(id, n) asm volatile("bar.sync %0,%1;" ::"n"(id), "n"(n) : "memory")
#define barrive(id, n) asm volatile("bar.arrive %0,%1;" ::"n"(id), "n"(n) : "memory")
DEV void mb_init(u32 a) { asm volatile("mbarrier.init.shared.b64 [%0],1;" ::"r"(a) : "memory"); }
DEV void mb_expect(u32 a, u32 bytes) { asm volatile("mbarrier.arrive.expect_tx.shared.b64 _,[%0],%1;" ::"r"(a), "r"(bytes) : "memory"); }
DEV void mb_wait(u32 a) {
  u32 ok; int it = 0;
  do { asm volatile("{.reg .pred p; mbarrier.try_wait.parity.shared.b64 p,[%1],0; selp.u32 %0,1,0,p;}" : "=r"(ok) : "r"(a) : "memory"); } while (!ok && ++it < SPIN);
}
DEV void bulk_out(void* dst, u32 src) { asm volatile("cp.async.bulk.global.shared::cta.bulk_group [%0],[%1],1152;" ::"l"(dst), "r"(src) : "memory"); }
DEV void tma3d(u32 dst, const CUtensorMap* tm, u32 mb, u32 bytes, int c0, int c2) {
  mb_expect(mb, bytes);
  asm volatile("cp.async.bulk.tensor.3d.shared::cluster.global.mbarrier::complete_tx::bytes [%0],[%1,{%3,0,%4}],[%2];"
               ::"r"(dst), "l"((uint64_t)tm), "r"(mb), "r"(c0), "r"(c2) : "memory");
}
DEV float blo(u32 w) { return __uint_as_float(w << 16); }
DEV float bhi(u32 w) { return __uint_as_float(w & 0xffff0000u); }
DEV u32 pk_bf(float lo, float hi) { u32 r; asm("cvt.rn.bf16x2.f32 %0,%1,%2;" : "=r"(r) : "f"(hi), "f"(lo)); return r; }
DEV u32 pk_hf(float lo, float hi) { u32 r; asm("cvt.rn.f16x2.f32 %0,%1,%2;" : "=r"(r) : "f"(hi), "f"(lo)); return r; }
DEV float rbf(float x) { return __uint_as_float(pk_bf(0.f, x) & 0xffff0000u); }
DEV u32 bfma(u32 a, u32 b, u32 c) { u32 r; asm("fma.rn.bf16x2 %0,%1,%2,%3;" : "=r"(r) : "r"(a), "r"(b), "r"(c)); return r; }
DEV u32 bmul(u32 a, u32 b) { u32 r; asm("mul.rn.bf16x2 %0,%1,%2;" : "=r"(r) : "r"(a), "r"(b)); return r; }
DEV u32 badd(u32 a, u32 b) { u32 r; asm("add.rn.bf16x2 %0,%1,%2;" : "=r"(r) : "r"(a), "r"(b)); return r; }
DEV u32 hadd(u32 a, u32 b) { u32 r; asm("add.rn.f16x2 %0,%1,%2;" : "=r"(r) : "r"(a), "r"(b)); return r; }
DEV u32 hfma(u32 a, u32 b, u32 c) { u32 r; asm("fma.rn.f16x2 %0,%1,%2,%3;" : "=r"(r) : "r"(a), "r"(b), "r"(c)); return r; }
struct C2 { u32 re, im; };
DEV C2 cm2(C2 a, C2 b) {
  const __half2 ar = *reinterpret_cast<__half2*>(&a.re), ai = *reinterpret_cast<__half2*>(&a.im), br = *reinterpret_cast<__half2*>(&b.re), bi = *reinterpret_cast<__half2*>(&b.im);
  __half2 re = __hfma2(ar, br, __hneg2(__hmul2(ai, bi))), im = __hfma2(ar, bi, __hmul2(ai, br));
  return {*reinterpret_cast<u32*>(&re), *reinterpret_cast<u32*>(&im)};
}
DEV C2 pk2(const float2 (&a)[2]) { return {pk_hf(a[0].x, a[1].x), pk_hf(a[0].y, a[1].y)}; }
DEV C2 pk2c(const float2 (&a)[2]) { return {pk_hf(a[0].x, a[1].x), pk_hf(-a[0].y, -a[1].y)}; }
DEV u32 cpy(u32 x, u32 zr, int alt) {
  u32 r;
  if (alt) asm volatile("xor.b32 %0,%1,%2;" : "=r"(r) : "r"(x), "r"(zr)); else asm volatile("mad.lo.u32 %0,%2,%2,%1;" : "=r"(r) : "r"(x), "r"(zr));
  return r;
}
DEV u32 bsetgt(u32 a, u32 b) { u32 r; asm("set.gt.bf16x2.bf16x2 %0,%1,%2;" : "=r"(r) : "r"(a), "r"(b)); return r; }
DEV float ex2(float x) { float r; asm("ex2.approx.ftz.f32 %0,%1;" : "=f"(r) : "f"(x)); return r; }
DEV float rcpf(float x) { float r; asm("rcp.approx.ftz.f32 %0,%1;" : "=f"(r) : "f"(x)); return r; }
DEV float2 cmul(float2 a, float2 b) { return make_float2(fmaf(a.x, b.x, -a.y * b.y), fmaf(a.x, b.y, a.y * b.x)); }
DEV float2 csq(float2 a) { return make_float2(fmaf(a.x, a.x, -a.y * a.y), (a.x + a.x) * a.y); }
DEV float2 cexp(float lr2, float th) {
  float k = rintf(th * 0.15915494309189535f);
  float r = fmaf(k, -6.2831854820251465f, th); r = fmaf(k, 1.7484555e-7f, r);
  float m = ex2(lr2);
  return make_float2(m * __cosf(r), m * __sinf(r));
}
DEV float silu_f(float v) { return v * rcpf(1.f + ex2(-1.4426950408889634f * v)); }
constexpr u32 B2P64 = 0x5F805F80u, B2M64 = 0x1F801F80u, BONE = 0x3F803F80u;
DEV u32 chan_of(u32 P) { u32 r = P & 63; return (P & ~63) + 32 * (r & 1) + 8 * ((r >> 2) & 3) + 2 * (r >> 4) + ((r >> 1) & 1); }
DEV u32 mod_off(u32 idx) { return G_MOD + (idx >> 4) * 128 + (idx & 8) * 2; }
constexpr u32 MODJ = 36 * 128;
DEV float sqrta(float x) { float r; asm("sqrt.approx.ftz.f32 %0,%1;" : "=f"(r) : "f"(x)); return r; }
DEV u32 fu(float x) { return __float_as_uint(x); }
DEV float uf(u32 x) { return __uint_as_float(x); }
DEV void mma_hf_o(float (&d)[4], const float (&c)[4], const u32 (&a)[4], u32 b0, u32 b1) {
  asm("mma.sync.aligned.m16n8k16.row.col.f32.f16.f16.f32 {%0,%1,%2,%3},{%4,%5,%6,%7},{%8,%9},{%10,%11,%12,%13};"
      : "=f"(d[0]), "=f"(d[1]), "=f"(d[2]), "=f"(d[3]) : "r"(a[0]), "r"(a[1]), "r"(a[2]), "r"(a[3]), "r"(b0), "r"(b1), "f"(c[0]), "f"(c[1]), "f"(c[2]), "f"(c[3]));
}

struct Prm {
  const char *x, *la, *ai, *cr, *ci, *ldt, *c;
  char* gs;
  const char *dsk, *wr;
  char* out;
  u32 zero;
};
constexpr float LOG2E = 1.4426950408889634f, F2P64 = 1.8446744073709552e19f, F2M64 = 5.421010862427522e-20f;

DEV void y_store(float c0, float c1, float c2, float c3, float F, u32 pml, char* yp) {
  str32(yp, pk_bf(c0 * F, c2 * F) | pml);
  str32(yp + 18432, pk_bf(c1 * F, c3 * F) | pml);
}
#define POLL(load, cond_bad, code) { int it_ = 0; do { load; if (++it_ > SPIN) { ERRF(code); break; } } while (__any_sync(~0u, (cond_bad))); }
#define POLLW(load, cond_bad, code) { int it_ = 0; while (__any_sync(~0u, (cond_bad))) { if (++it_ > SPIN) { ERRF(code); break; } load; } }

DEV void post_conv(const Prm& p, const u32 tid, const u32 b, const u32 ep, const uint4 (&xv)[4], const uint4 dk, const uint4 wr, uint4 (&md)[6]) {
  const u32 w = tid >> 5, lane = tid & 31;
  const u32 g = lane >> 2, q = lane & 3, e = g >> 2, h = (g >> 1) & 1, hi = g & 1;
  const u32 rho = b & 1, par = (ep + 1) & 1, pm = par ? TAGM : 0;
  char* const gs = p.gs;
  const u32 cho = 128 * w + 64 * e + 16 * q, ssrc = g & 3;
  const bool own = (q >> 1) == e, sq = (q & 1) == h;
  uint4 ka, kc;
  const char* ks = gs + (G_OB + OB_KEY + (8 * g + w) * OB + q * 16);
  if (w < 9) {
    {
      const char* mp = gs + mod_off(cho >> 1);
      POLLW(_Pragma("unroll") for (int j = 0; j < 6; j++) md[j] = ldr128(mp + j * MODJ),
            ((md[0].x ^ pm) | (md[1].x ^ pm) | (md[2].x ^ pm) | (md[3].x ^ pm) | (md[4].x ^ pm) | (md[5].x ^ pm)) & TAGM, 4);
    }
    const u32 saw[4] = {md[0].x & ~TAGM, md[0].y, md[0].z, md[0].w}, caw[4] = {md[1].x & ~TAGM, md[1].y, md[1].z, md[1].w};
    const u32 gaw[4] = {md[2].x & ~TAGM, md[2].y, md[2].z, md[2].w}, sbw[4] = {md[3].x & ~TAGM, md[3].y, md[3].z, md[3].w};
    const u32 cbr[4] = {md[4].x & ~TAGM, md[4].y, md[4].z, md[4].w}, dw[4] = {dk.x, dk.y, dk.z, dk.w};
    const u32 gbw[4] = {md[5].x & ~TAGM, md[5].y, md[5].z, md[5].w};
    const char* ysrc = gs + (G_Y + b * 18432 + tid * 16 + w * 1536);
    uint4 yv[4];
    if (w < 4) {
#pragma unroll
      for (int v = 0; v < 4; v++) yv[v] = ldr128(ysrc + 512 * v);
    } else {
#pragma unroll
      for (int v = 0; v < 4; v++) yv[v].x = INVAL;
    }
    u32 hD[4][4], cb1[4], ca1[4], x1[4][4];
#pragma unroll
    for (int v = 0; v < 4; v++) { cb1[v] = bfma(cbr[v], B2P64, BONE); ca1[v] = bfma(caw[v], B2P64, BONE); }
#pragma unroll
    for (int k = 0; k < 4; k++) {
      const uint4 st = lds128(SM_ST + 16 * (4 * h + k + 8 * hi));
      const u32 xx[4] = {xv[k].x, xv[k].y, xv[k].z, xv[k].w};
#pragma unroll
      for (int v = 0; v < 4; v++) {
        const u32 d = badd(xx[v], st.x), z = bfma(d, st.y, bmul(d, st.z));
        hD[k][v] = bmul(bfma(saw[v], B2P64, bmul(z, ca1[v])), dw[v]);
      }
    }
    u32 rb0, rb1;
    {
      const u32 c0 = hi ? cb1[1] : cb1[0], c2 = hi ? cb1[3] : cb1[2], w0 = hi ? wr.y : wr.x, w2 = hi ? wr.w : wr.z;
      const u32 H0 = bmul(c0, w0), H1 = bmul(c2, w2);
      const u32 L0 = bfma(c0, w0, H0 ^ 0x80008000u), L1 = bfma(c2, w2, H1 ^ 0x80008000u);
      rb0 = __shfl_xor_sync(~0u, h ? L0 : H0, 16); rb1 = __shfl_xor_sync(~0u, h ? L1 : H1, 16);
    }
    const u32 spw = SM_SP + (2 * w + e) * 320 + ssrc * 16 + (own ? (sq ? 4 : 0) : 8 + 4 * (q & 1));
    TSW(0, 18);
    if (w >= 4) bsync(13, 288);
    POLLW(_Pragma("unroll") for (int v = 0; v < 4; v++) if ((yv[v].x ^ pm) & TAGM) yv[v] = ldr128(ysrc + 512 * v),
          ((yv[0].x ^ pm) | (yv[1].x ^ pm) | (yv[2].x ^ pm) | (yv[3].x ^ pm)) & TAGM, 5);
    TSW(0, 19);
#pragma unroll
    for (int k = 0; k < 4; k++) {
      const u32 xx[4] = {xv[k].x, xv[k].y, xv[k].z, xv[k].w};
#pragma unroll
      for (int v = 0; v < 4; v++) {
        const u32 yw = k == 0 ? yv[v].x & ~TAGM : k == 1 ? yv[v].y : k == 2 ? yv[v].z : yv[v].w;
        x1[k][v] = bfma(bmul(gaw[v], bfma(movm(yw), B2P64, hD[k][v])), B2P64, xx[v]);
      }
      float s[4] = {}, X[4] = {}, Y[4] = {}, R[4] = {};
      mma8_bf(X, x1[k][0], x1[k][1], x1[k][0]); mma8_bf(Y, x1[k][0], x1[k][1], x1[k][1]);
      mma_bf(s, x1[k][0], x1[k][1], x1[k][2], x1[k][3], BONE, BONE);
      mma_bf(R, x1[k][0], x1[k][1], x1[k][2], x1[k][3], rb0, rb1);
      mma8_bf(X, x1[k][2], x1[k][3], x1[k][2]); mma8_bf(Y, x1[k][2], x1[k][3], x1[k][3]);
      const float u0 = hi ? X[1] : X[0], u1 = hi ? Y[3] : Y[2], u2 = own ? s[0] : R[0], u3 = own ? s[2] : R[3];
      const bool dg = own && sq;
      sts32(spw + k * 64, fu((dg ? u0 : u2) + (dg ? u1 : u3)));
    }
    bsync(1, 320);
    float S1 = 0.f, S2 = 0.f, S3 = 0.f, S4 = 0.f;
    const u32 spr = SM_SP + (lane >> 4) * 9 * 320 + (lane & 15) * 16;
#pragma unroll
    for (int i = 0; i < 9; i++) { uint4 t = lds128(spr + i * 320); S1 += uf(t.x); S2 += uf(t.y); S3 += uf(t.z); S4 += uf(t.w); }
    const uint2 rc = lds64(SM_RC);
    if (w < 8) { ka = ldr128(ks); kc = ldr128(ks + 64 * OB); }
    S3 += S4;
    S1 += __shfl_xor_sync(~0u, S1, 16); S2 += __shfl_xor_sync(~0u, S2, 16); S3 += __shfl_xor_sync(~0u, S3, 16);
    const float mu = S1 * (1.f / 576.f), var = fmaxf(fmaf(-mu, mu, S2 * (1.f / 576.f)), 0.f);
    const float m = rbf(mu), rs = rcpf(rbf(sqrta(rbf(rbf(var) + 1e-5f))));
    if (w == 8) {
      const u32 rb_ = pk_bf(0.f, fmaf(fmaf(-m, uf(rc.x), S3), rs, uf(rc.y)) + 0.f) & 0xffff0000u;
      const u32 tl = 4 * ((lane >> 1) & 1) + ((lane >> 2) & 3) + 8 * (lane & 1);
      if (lane < 16) str32(gs + (G_OB + b * OB + OB_KEY + 4 * tl), rb_ | (par * 0x1800u));
      TS(20);
      const u32 ok = ((rb_ ^ (((int)rb_ >> 31) | 0x80000000)) & 0xffff0000u) | (15 - tl);
      sts32(SM_KEY + 4 * (lane & 15), ok);
      sts128(SM_THR + 32, ~0u, ~0u, ~0u, ~0u);
      __syncwarp();
      const uint4 o0 = lds128(SM_KEY + 2 * (lane & 16)), o1 = lds128(SM_KEY + 2 * (lane & 16) + 16);
      u32 lr = (o0.x > ok) + (o0.y > ok) + (o0.z > ok) + (o0.w > ok) + (o1.x > ok) + (o1.y > ok) + (o1.z > ok) + (o1.w > ok);
      lr += __shfl_xor_sync(~0u, lr, 16);
      const u32 so = tl * ROW + (tl >> 3) * 64;
      sts64(SM_TOK + 8 * lr, tl * 1152, so);
      sts128(SM_HS + 1152 + so, pm, rb_ | (16 * b + tl), 0, 0);
      const u32 below = (int)rb_ > 0 ? rb_ - 0x10000u : (rb_ + 0x10000u) | 0x80000000u;
      if (lr < 8) sts16(SM_THR + (lane & 16) + 2 * lr, (lane & 16 ? below : rb_) >> 16);
    }
    const float rh = rbf(rs);
    const u32 nm_ = pk_bf(-m, rh), rL_ = pk_bf(rs - rh, rs - rh);
    const u32 so = (4 * h + 8 * hi) * ROW + 64 * hi + cho;
#pragma unroll
    for (int k = 0; k < 4; k++) {
      const u32 t = __shfl_sync(~0u, nm_, 4 * k + ssrc), rL = __shfl_sync(~0u, rL_, 4 * k + ssrc);
      const u32 nm = __byte_perm(t, t, 0x1010), rH = __byte_perm(t, t, 0x3232);
      u32 h2[4], o[4];
#pragma unroll
      for (int v = 0; v < 4; v++) {
        const u32 d = badd(x1[k][v], nm), z = bfma(d, rH, bmul(d, rL));
        h2[v] = bfma(sbw[v], B2P64, bmul(z, cb1[v]));
        o[v] = bfma(bmul(gbw[v], h2[v]), B2P64, x1[k][v]);
      }
      sts128(SM_HS + so + k * ROW, bmul(h2[0], B2M64) | pm, h2[1], h2[2], h2[3]);
      sts128(SM_X1S + so + k * ROW, bmul(x1[k][0], B2M64) | pm, x1[k][1], x1[k][2], x1[k][3]);
      sts128(SM_OS + so + k * ROW, o[0], o[1], o[2], o[3]);
    }
    asm volatile("fence.proxy.async.shared::cta;" ::: "memory");
    bsync(2, 288);
    TSW(0, 21);
  }
  if (w < 8) {
    const uint2 tk = lds64(SM_TOK + 8 * w), tk8 = lds64(SM_TOK + 64 + 8 * w);
    const u32 ba = 8 * g + w;
    const uint4 ta = lds128(SM_THR + (ba < b ? 16 : ba == b ? 32 : 0)), tc = lds128(SM_THR + (ba + 64 < b ? 16 : ba + 64 == b ? 32 : 0));
    const u32 l2 = lane < 9 ? lane * 16 + 1024 : 0;
    const uint4 h0 = lds128(SM_HS + tk.y + lane * 16), h1 = lds128(SM_HS + 512 + tk.y + lane * 16), h2 = lds128(SM_HS + tk.y + l2);
    char* const ob = p.out + b * 18432;
    if (lane == 0) bulk_out(ob + tk8.x, SM_OS + tk8.y);
    const u32 kt = par * 0x1800u;
    POLLW({ ka = ldr128(ks); kc = ldr128(ks + 64 * OB); }, ((ka.x ^ kt) | (kc.x ^ kt)) & 0x1800u, 6);
    TSW(0, 23);
    u32 n[4] = {0x43004300u, 0x43004300u, 0x43004300u, 0x43004300u};
    const u32 kk[8] = {ka.x, ka.y, ka.z, ka.w, kc.x, kc.y, kc.z, kc.w};
#pragma unroll
    for (int j = 0; j < 8; j++) {
      const u32 s = __byte_perm(kk[j], kk[j], 0x3232);
      const uint4 t = j < 4 ? ta : tc;
      n[0] = badd(n[0], bsetgt(s, t.x)); n[1] = badd(n[1], bsetgt(s, t.y)); n[2] = badd(n[2], bsetgt(s, t.z)); n[3] = badd(n[3], bsetgt(s, t.w));
    }
    sts128(SM_CNT + 16 * w, __reduce_add_sync(~0u, n[0]), __reduce_add_sync(~0u, n[1]), __reduce_add_sync(~0u, n[2]), __reduce_add_sync(~0u, n[3]));
    bsync(3, 256);
    const u32 cw = lds32(SM_CNT + 16 * (lane & 7) + 2 * (w & 6));
    const u32 tot = __reduce_add_sync(~0u, lane < 8 ? cw : 0) - 0x00430000u;
    const u32 rank = w + ((w & 1) ? tot >> 16 : tot & 0xffff);
    if (rank < 8) {
      char* dst = gs + (G_XS + rank * ROW + lane * 16);
      str128(dst, h0.x, h0.y, h0.z, h0.w); str128(dst + 512, h1.x, h1.y, h1.z, h1.w);
      if (lane < 9) str128(dst + 1024, h2.x, h2.y, h2.z, h2.w);
      const uint4 x0 = lds128(SM_X1S + tk.y + lane * 16), x1 = lds128(SM_X1S + 512 + tk.y + lane * 16), x2 = lds128(SM_X1S + tk.y + l2);
      str128(dst + 8 * ROW, x0.x, x0.y, x0.z, x0.w); str128(dst + (8 * ROW + 512), x1.x, x1.y, x1.z, x1.w);
      if (lane < 8) str128(dst + (8 * ROW + 1024), x2.x, x2.y, x2.z, x2.w);
    } else if (lane == 0) bulk_out(ob + tk.x, SM_OS + tk.y);
    if (w == 0) barrive(6, 160);
    TSW(0, 24);
    bsync(5, 288);
  } else {
    mb_wait(SM_MB + 16); mb_wait(SM_MB + 24);
    if (w == 9) barrive(5, 288);
  }
  const u32 kq = w & 3, tg = 2 - (w >> 2);
  uint4 A[2][9];
  {
    const u32 aa = ((lane & 8) ? SM_UP : SM_GATE) + (144 * kq + 8 * (lane >> 4) + (lane & 7)) * 80 + tg * 32;
#pragma unroll
    for (int s = 0; s < 9; s++) A[0][s] = ldsm4t(aa + s * 1280);
    if (tg < 2) {
#pragma unroll
      for (int s = 0; s < 9; s++) A[1][s] = ldsm4t(aa + s * 1280 + 16);
    }
  }
  TSW(0, 22);
  if (w >= 8) {
    const u32 t = (tid - 256) * 16;
    const char* xs = gs + (G_XS + t);
    uint4 v[5];
#pragma unroll
    for (int j = 0; j < 5; j++) v[j].x = INVAL;
    if (t >= 72 * 16) v[4].x = pm;
    bsync(6, 160);
    POLL(_Pragma("unroll") for (int j = 0; j < 5; j++) if ((v[j].x ^ pm) & TAGM) v[j] = ldr128(xs + j * 2048),
         ((v[0].x ^ pm) | (v[1].x ^ pm) | (v[2].x ^ pm) | (v[3].x ^ pm) | (v[4].x ^ pm)) & TAGM, 8);
#pragma unroll
    for (int j = 0; j < 5; j++) if (j < 4 || t < 72 * 16) sts128(SM_XS + t + j * 2048, bmul(v[j].x & ~TAGM, B2P64), v[j].y, v[j].z, v[j].w);
  }
  __syncthreads();
  TSW(0, 25);
  {
    float c0[2][4] = {}, c1[2][4] = {};
    const u32 ba = SM_XS + (lane & 7) * ROW + (18 * kq + (lane >> 3)) * 16;
    uint4 bb[5];
#pragma unroll
    for (int s = 0; s < 5; s++) bb[s] = ldsm4(ba + s * 64);
#pragma unroll
    for (int s = 0; s < 9; s++) mma_bf(c0[s & 1], A[0][s].x, A[0][s].y, A[0][s].z, A[0][s].w, s & 1 ? bb[s >> 1].z : bb[s >> 1].x, s & 1 ? bb[s >> 1].w : bb[s >> 1].y);
    const u32 ra = SM_RED + (8 * tg + kq) * 512 + lane * 16;
    if (tg < 2) {
#pragma unroll
      for (int s = 0; s < 9; s++) mma_bf(c1[s & 1], A[1][s].x, A[1][s].y, A[1][s].z, A[1][s].w, s & 1 ? bb[s >> 1].z : bb[s >> 1].x, s & 1 ? bb[s >> 1].w : bb[s >> 1].y);
      sts128(ra + 2048, fu(c1[0][0] + c1[1][0]), fu(c1[0][1] + c1[1][1]), fu(c1[0][2] + c1[1][2]), fu(c1[0][3] + c1[1][3]));
    }
    sts128(ra, fu(c0[0][0] + c0[1][0]), fu(c0[0][1] + c0[1][1]), fu(c0[0][2] + c0[1][2]), fu(c0[0][3] + c0[1][3]));
  }
  __syncthreads();
  if (w < 5 - rho) {
    float s[4] = {};
#pragma unroll
    for (int i = 0; i < 4; i++) { const uint4 t = lds128(SM_RED + (w * 4 + i) * 512 + lane * 16); s[0] += uf(t.x); s[1] += uf(t.y); s[2] += uf(t.z); s[3] += uf(t.w); }
    const u32 sg = pk_bf(silu_f(rbf(s[0])), silu_f(rbf(s[1])));
    const u32 act = movm(bmul(bmul(sg, pk_bf(s[2], s[3])), B2M64));
    str32(gs + (G_OB + OB_ACT + b * OB + tid * 4), act | (q ? 0 : pm));
  }
  TSW(0, 26);
  if (w >= 9) {
    if (w == 9) { mb_wait(SM_MB + 32); barrive(7, 192); }
    return;
  }
  {
    const u32 ul = tid >> 3, pr = ul / 9, r9 = ul - 9 * pr;
    const char* src = gs + (G_OB + OB_ACT + ((b & ~7u) + 2 * pr) * OB + (r9 < 5 ? r9 * 128 : OB + (r9 - 5) * 128) + (tid & 7) * 16);
    uint4 a = ldr128(src);
    if (w < 5) {
      const u32 aa = SM_WD + (8 * (lane >> 4) + (lane & 7)) * 144 + (2 * w + ((lane >> 3) & 1)) * 16;
      bsync(7, 192);
#pragma unroll
      for (int s = 0; s < 9; s++) { A[0][s] = ldsm4t(aa + s * 4608); A[1][s] = ldsm4t(aa + s * 4608 + 2304); }
    }
    TSW(0, 28);
    POLLW(a = ldr128(src), (a.x ^ pm) & TAGM, 9);
    sts128(SM_AC + tid * 16, a.x & ~TAGM, a.y, a.z, a.w);
  }
  TSW(0, 27);
  if (w < 5) {
    bsync(8, 288);
    float c[4][4] = {};
#pragma unroll
    for (int s = 0; s < 9; s++) {
      const uint4 bb = ldsm4(SM_AC + lane * 16 + s * 512);
      mma_bf(c[2 * (s & 1)], A[0][s].x, A[0][s].y, A[0][s].z, A[0][s].w, bb.x, bb.y);
      mma_bf(c[2 * (s & 1) + 1], A[1][s].x, A[1][s].y, A[1][s].z, A[1][s].w, bb.z, bb.w);
    }
    char* dst = gs + (G_OB + OB_PART + b * OB + w * 512 + lane * 8);
    u32 o[4];
#pragma unroll
    for (int i = 0; i < 4; i++) o[i] = (fu(((c[0][i] + c[1][i]) + (c[2][i] + c[3][i])) * F2P64) & ~1u) | par;
    str64(dst, o[0], o[1]);
    if (w < 4) str64(dst + 256, o[2], o[3]);
    TSW(0, 29);
  } else {
    barrive(8, 288);
    if (w == 8 && b < 72) {
      const u32 kg = lds32(SM_XS + 1156 + g * ROW), cg = b / 9;
      const char* src = gs + (G_OB + OB_PART + cg * OB + (b - 9 * cg) * 256 + lane * 8);
      const char* xs = gs + (G_X1 + g * ROW + b * 16);
      uint4 xt;
      POLL(xt = ldr128(xs), (xt.x ^ pm) & TAGM, 10);
      const u32 x1w = (q & 2) ? ((q & 1) ? xt.w : xt.z) : ((q & 1) ? xt.y : bmul(xt.x & ~TAGM, B2P64));
      const u32 gw = ldr32(gs + (mod_off(8 * b) + 5 * MODJ + 4 * q)) & ~TAGM;
      const u32 hw = lds32(SM_XS + g * ROW + b * 16 + q * 4);
      const float sgm = rcpf(1.f + ex2(-LOG2E * bhi(kg)));
      char* const dst = p.out + ((kg & 2047) * 1152 + 16 * b + 4 * q);
      uint2 v[16];
#pragma unroll
      for (int j = 0; j < 16; j++) v[j] = make_uint2(1, 0);
      u32 bad;
      POLL({ bad = 0; _Pragma("unroll") for (int j = 0; j < 16; j++) { if (((v[j].x ^ par) | (v[j].y ^ par)) & 1) v[j] = ldr64(src + j * 8 * OB); }
             _Pragma("unroll") for (int j = 0; j < 16; j++) bad |= (v[j].x ^ par) | (v[j].y ^ par); }, bad & 1, 11);
      float s0[4] = {}, s1[4] = {};
#pragma unroll
      for (int j = 0; j < 16; j++) { s0[j & 3] += uf(v[j].x); s1[j & 3] += uf(v[j].y); }
      const u32 y = movm(pk_bf((s0[0] + s0[1]) + (s0[2] + s0[3]), (s1[0] + s1[1]) + (s1[2] + s1[3])));
      *(u32*)dst = bfma(bmul(gw, badd(hw, bmul(y, pk_bf(sgm, sgm)))), B2P64, x1w);
      if (b == 0 && lane == 0) str32(gs + G_EP, ep + 1);
      TS(30);
    }
  }
  if (lane == 0) {
    asm volatile("cp.async.bulk.commit_group;" ::: "memory");
    asm volatile("cp.async.bulk.wait_group.read 0;" ::: "memory");
  }
}

__global__ void __launch_bounds__(384, 1)
fused_kernel(const Prm p, const __grid_constant__ CUtensorMap tm_mod, const __grid_constant__ CUtensorMap tm_gate,
             const __grid_constant__ CUtensorMap tm_up, const __grid_constant__ CUtensorMap tm_down) {
  extern __shared__ __align__(1024) unsigned char smem[];
  uint4 xv[4];
  {
    const u32 t = threadIdx.x;
    if (t < 288) {
      const char* xp = p.x + (blockIdx.x * 18432 + (t >> 5) * 128 + (t & 16) * 4 + (t & 3) * 16 + ((t & 8) * 576 + (t & 4) * 288));
#pragma unroll
      for (int k = 0; k < 4; k++) xv[k] = ldg128(xp + (2 * (k >> 1) + 8 * (k & 1)) * 1152);
    }
  }
  const u32 tid = __shfl_sync(~0u, threadIdx.x, threadIdx.x & 31), b = __shfl_sync(~0u, blockIdx.x, 0);
  const u32 w = tid >> 5, lane = tid & 31;
  const u32 g = lane >> 2, q = lane & 3, e = g >> 2, h = (g >> 1) & 1, hi = g & 1;
  const u32 rho = b & 1, Pm = 9 * (b >> 1) + 5 * rho, Ps = 9 * (b >> 1) + 4;
  char* const gs = p.gs;
  TSW(0, 0);
  const u32 cho = 128 * w + 64 * e + 16 * q;
  const bool kw = (w >> 1) != 4;
  const u32 ksig = w < 8 ? (w & 3) : 4, khf = w < 8 ? (w >> 2) : (w & 1);
  u32 la, ai, ldt; uint2 cr, ci;
  {
    const u32 d = chan_of(w < 8 ? Pm + ksig : Ps), o = d * 256 + 8 * lane;
    const char* cp = p.c + (576 * (w & 1) + 24 * min(lane, 23u));
    la = ldg32(kw ? p.la + (o + 4 * khf) : cp); ai = ldg32(kw ? p.ai + (o + 4 * khf) : cp + 4);
    cr = ldg64(kw ? p.cr + o : cp + 8); ci = ldg64(kw ? p.ci + o : cp + 16); ldt = ldg16(p.ldt + 2 * d);
  }
  const u32 zr = tid >> 16;
  const u32 epv = ldr32(gs + (G_EP + zr));
  if (tid == 288) {
#pragma unroll
    for (int i = 0; i < 5; i++) mb_init(SM_MB + 8 * i);
    asm volatile("fence.mbarrier_init.release.cluster;" ::: "memory");
    tma3d(SM_UP, &tm_mod, SM_MB, 18432, 16 * b, 0);
    if (b < 88) tma3d(SM_UP + 18432, &tm_mod, SM_MB + 8, 18432, 16 * b + 2048, 0);
    tma3d(SM_GATE, &tm_gate, SM_MB + 16, 46080, 8 * Pm, 0);
    asm volatile("prefetch.tensormap [%0];" ::"l"((uint64_t)&tm_up) : "memory");
    asm volatile("prefetch.tensormap [%0];" ::"l"((uint64_t)&tm_down) : "memory");
  }
#pragma unroll 1
  for (u32 i = SM_ZS + tid * 16; i < SM_MB; i += 384 * 16) sts128(i, 0, 0, 0, 0);
  __syncthreads();
  TSW(0, 1);
  char* const zdst = gs + (b * 18432 + tid * 16 + w * 1536);
  if (w < 9) {
#pragma unroll
    for (int v = 0; v < 4; v++) str128(zdst + 512 * v, INVAL, 0, 1, 0);
    str128(gs + (G_Y + 96 * 18432 + (w < 8 ? (tid >> 3) * 18432 + Pm * 32 + (tid & 7) * 16 : (16 * rho + (lane >> 1)) * 18432 + Ps * 32 + (lane & 1) * 16)), INVAL, 0, 1, 0);
  }
  {
    const u32 t = 383 - tid;
    if (t < 192 || (t < 208 && b < 73) || (t >= 224 && t < (b < 88 ? 228 : 226)))
      str128(gs + (t < 192 ? G_OB + b * OB + t * 16 : t < 208 ? G_XS + b * 256 + (t & 15) * 16 : G_MOD + b * 128 + (t & 2) * 8192 + (t & 1) * 16), INVAL, 0, 1, 0);
  }
  const u32 ep = __reduce_or_sync(~0u, epv), par = (ep + 1) & 1, pm = par ? TAGM : 0;
  const bool own = (q >> 1) == e, sq = (q & 1) == h;
  const u32 ssrc = g & 3;
  if (w < 9) {
    const u32 spw = SM_SP + (2 * w + e) * 160 + ssrc * 8 + (sq ? 4 : 0);
#pragma unroll
    for (int k = 0; k < 4; k++) {
      float s[4] = {}, X[4] = {}, Y[4] = {};
      mma8_bf(X, xv[k].x, xv[k].y, xv[k].x); mma8_bf(Y, xv[k].x, xv[k].y, xv[k].y);
      mma_bf(s, xv[k].x, xv[k].y, xv[k].z, xv[k].w, BONE, BONE);
      mma8_bf(X, xv[k].z, xv[k].w, xv[k].z); mma8_bf(Y, xv[k].z, xv[k].w, xv[k].w);
      const float u0 = hi ? X[1] : X[0], u1 = hi ? Y[3] : Y[2];
      const float v = (sq ? u0 : s[0]) + (sq ? u1 : s[2]);
      if (own) sts32(spw + k * 32, fu(v));
    }
    TSW(0, 4);
    bsync(1, 288);
    float S1 = 0.f, S2 = 0.f;
    const u32 spr = SM_SP + (lane >> 4) * 9 * 160 + (lane & 15) * 8;
#pragma unroll
    for (int i = 0; i < 9; i++) { uint2 t = lds64(spr + i * 160); S1 += uf(t.x); S2 += uf(t.y); }
    S1 += __shfl_xor_sync(~0u, S1, 16); S2 += __shfl_xor_sync(~0u, S2, 16);
    const float mu = S1 * (1.f / 576.f), var = fmaxf(fmaf(-mu, mu, S2 * (1.f / 576.f)), 0.f);
    const float m = rbf(mu), rs = rcpf(rbf(sqrta(rbf(rbf(var) + 1e-5f))));
    const float ra = rs * 0.0625f, rc = -m * ra;
    u32 zt[4][4];
#pragma unroll
    for (int k = 0; k < 4; k++) {
      const float a = __shfl_sync(~0u, ra, 4 * k + ssrc), c = __shfl_sync(~0u, rc, 4 * k + ssrc);
      const u32 xx[4] = {xv[k].x, xv[k].y, xv[k].z, xv[k].w};
#pragma unroll
      for (int v = 0; v < 4; v++) zt[v][k] = movm(pk_hf(fmaf(blo(xx[v]), a, c), fmaf(bhi(xx[v]), a, c)));
    }
#pragma unroll
    for (int v = 0; v < 4; v++) str128(zdst + 512 * v, zt[v][0] | pm, zt[v][1], zt[v][2], zt[v][3]);
    if (w == 8) {
      const float rh = rbf(rs);
      sts128(SM_ST + 16 * (4 * ((lane >> 1) & 1) + ((lane >> 2) & 2) + 2 * (lane & 4) + (lane & 1)), pk_bf(-m, -m), pk_bf(rh, rh), pk_bf(rs - rh, rs - rh), 0);
    }
  }
  TSW(0, 5);
  if (kw) {
    const u32 ktab = SM_R + (w < 8 ? w : w - 2) * KTAB;
    u32 mx = __vmaxu2(__vmaxu2(cr.x & 0x7fff7fff, cr.y & 0x7fff7fff), __vmaxu2(ci.x & 0x7fff7fff, ci.y & 0x7fff7fff));
    const u32 E = max(__reduce_max_sync(~0u, max(mx & 0xffff, mx >> 16)) >> 7, 8u);
    const float dt = rbf(ex2(blo(ldt) * LOG2E)), csc = uf((258 - E) << 23);
    const float FK = 2.f * dt * uf((E - 4) << 23);
    const u32 crw = khf ? cr.y : cr.x, ciw = khf ? ci.y : ci.x;
    float k2048 = 0.f;
    {
      float2 C[2], w4[2], w8[2], w16[2], w32[2], w64[2], w128[2], w256[2], w512[2], a1[2], a2[2], a3[2], t0[2], t1[2], s3[2];
#pragma unroll
      for (int m = 0; m < 2; m++) {
        const float lr2 = rbf(ex2((m ? bhi(la) : blo(la)) * LOG2E)) * dt * -LOG2E, th = (m ? bhi(ai) : blo(ai)) * dt;
        C[m] = make_float2((m ? bhi(crw) : blo(crw)) * csc, (m ? bhi(ciw) : blo(ciw)) * csc);
        const float2 w1 = cexp(lr2, th), w2 = csq(w1);
        w64[m] = cexp(64.f * lr2, 64.f * th);
        w4[m] = csq(w2); w8[m] = csq(w4[m]); w16[m] = csq(w8[m]); w32[m] = csq(w16[m]);
        w128[m] = csq(w64[m]); w256[m] = csq(w128[m]); w512[m] = csq(w256[m]);
        const float2 w1024 = csq(w512[m]);
        a1[m] = cmul(C[m], w1); a2[m] = cmul(C[m], w2); a3[m] = cmul(a1[m], w2);
        t0[m] = cmul(C[m], w1024); t1[m] = cmul(t0[m], w128[m]); s3[m] = cmul(w8[m], w16[m]);
        k2048 += fmaf(t0[m].x, w1024.x, -t0[m].y * w1024.y);
      }
      C2 B0[8], B1[8], B2[8], S[8];
      B0[0] = pk2(C); B0[1] = pk2(a1); B0[2] = pk2(a2); B0[3] = pk2(a3);
      const C2 h4 = pk2(w4), h256 = pk2(w256), h512 = pk2(w512);
#pragma unroll
      for (int i = 0; i < 4; i++) B0[4 + i] = cm2(B0[i], h4);
#pragma unroll
      for (int i = 0; i < 4; i++) B1[i] = cm2(B0[2 * i], h256);
      B1[4] = cm2(B0[0], h512); B1[5] = cm2(B0[4], h512);
      B1[6] = cm2(B1[4], h256); B1[7] = cm2(B1[5], h256);
      const u32 ta = ktab + lane * 128, f = ((lane & 3) << 5) | ((lane & 4) << 2);
#pragma unroll
      for (int i = 0; i < 8; i++) sts128(ta + ((i << 4) ^ f), B0[i].re, B0[i].im, B1[i].re, B1[i].im);
      B2[0] = pk2(t0); B2[1] = pk2(t1);
      B2[2] = cm2(B2[0], h256); B2[3] = cm2(B2[1], h256);
#pragma unroll
      for (int i = 0; i < 4; i++) B2[4 + i] = cm2(B2[i], h512);
      S[0] = {0x3C003C00u, 0u}; S[1] = pk2c(w8); S[2] = pk2c(w16); S[3] = pk2c(s3); S[4] = pk2c(w32);
#pragma unroll
      for (int i = 1; i < 4; i++) S[4 + i] = cm2(S[i], S[4]);
#pragma unroll
      for (int i = 0; i < 8; i++) sts128(ta + 4096 + ((i << 4) ^ f), B2[i].re, B2[i].im, S[i].re, S[i].im);
      const C2 m64 = pk2c(w64), m128 = pk2c(w128);
      sts128(ktab + 8192 + lane * 16, m64.re, m64.im, m128.re, m128.im);
    }
    __syncwarp();
    TSW(0, 2); TSW(10, 3);
    float D[5][4] = {};
    u32 ta = ktab + q * 128 + ((g ^ (q << 1)) << 4), tm = ktab + 8192 + q * 16;
#pragma unroll 2
    for (int s = 0; s < 8; s++) {
      const uint4 ca = lds128(ta), cb = lds128(ta + 4096), ma = lds128(tm);
      ta = (ta + 512) ^ 16; tm += 64;
      k2048 += __shfl_xor_sync(~0u, k2048, 16 >> s);
      const C2 s0 = {cb.z, cb.w}, s1 = cm2(s0, {ma.x, ma.y}), s2 = cm2(s0, {ma.z, ma.w}), s3 = cm2(s1, {ma.z, ma.w});
      mma_hf(D[0], s0.re, s1.re, s0.im, s1.im, ca.x, ca.y);
      mma_hf(D[2], s0.re, s1.re, s0.im, s1.im, ca.z, ca.w);
      mma_hf(D[4], s0.re, s1.re, s0.im, s1.im, cb.x, cb.y);
      mma_hf(D[1], s2.re, s3.re, s2.im, s3.im, ca.x, ca.y);
      mma_hf(D[3], s2.re, s3.re, s2.im, s3.im, ca.z, ca.w);
    }
    const u32 xa = SM_R + (w < 8 ? 4 + ksig : 9) * KTAB + lane * 16;
    if (khf) {
      __syncwarp();
#pragma unroll
      for (int j = 0; j < 5; j++) sts128(xa + 512 * j, fu(D[j][0]), fu(D[j][1]), fu(D[j][2]), fu(D[j][3]));
      if (lane == 0) sts32(xa + 2560, fu(k2048));
      asm volatile("bar.arrive %0,64;" ::"r"(2 + ksig) : "memory");
    } else {
      const u32 tp = SM_TAP + ksig * TAPS;
      const u32 a = 63 + 32 * q + g;
      const u32 t1 = tp + (q < 2 ? (128 + 4 * g + 2 * q) * 4 : T5 * 4 + (a - 64 + 2 * (a & 1)) * 2);
      const u32 x = 63 + hi + 16 * q + (g >> 1), tb = tp + (hi ? TE7 : TE9) * 4;
      const u32 te = tb + (x + 2 * (x & 1)) * 2, to = tb + TEO * 4 + (x ^ 1) * 2;
      asm volatile("bar.sync %0,64;" ::"r"(2 + ksig) : "memory");
#pragma unroll
      for (int j = 0; j < 5; j++) { const uint4 t = lds128(xa + 512 * j); D[j][0] += uf(t.x); D[j][1] += uf(t.y); D[j][2] += uf(t.z); D[j][3] += uf(t.w); }
      k2048 = (k2048 + uf(lds32(xa + 2560))) * 0.125f;
      const float kv512 = __shfl_sync(~0u, D[2][0], 2);
      if (lane == 29) D[3][3] -= kv512;
#pragma unroll
      for (int r = 0; r < 4; r++) {
        const u32 v = pk_hf(D[2 + (r >> 1)][2 * (r & 1)], D[2 + (r >> 1)][2 * (r & 1) + 1]);
        if (q < 2) {
          const u32 vv = __byte_perm(v, v, 0x1010);
          sts32(t1 + (TO + 32 * r) * 4, vv); sts16(t1 + (TO + 32 * r + 1) * 4 + 2, v >> 16); sts16(t1 + (TO + 32 * r - 1) * 4, v);
          sts64(t1 + (TE + 32 * r) * 4, vv, __byte_perm(v, v, 0x1032));
        } else {
          sts16(t1 + 16 * r, v); sts16(t1 + 16 * r + (T3 - T5) * 4, v >> 16);
        }
      }
#pragma unroll
      for (int r = 0; r < 2; r++) {
        const u32 v = pk_hf(D[4][2 * r], D[4][2 * r + 1]);
        if (r == 0 && lane == 0) { sts16(tp + T5 * 4 + 129 * 2, v); sts32(SM_KV + 4 * ksig, v & 0xffff); sts16(tb + TEO * 4 + 126 * 2, pk_hf(k2048, 0.f)); sts32(SM_SC + 16 * ksig + 12, fu(FK)); }
        else { sts16(te + 8 * r, v); sts16(to + 8 * r, v); }
        sts16(te + 8 * r + 16, v >> 16); sts16(to + 8 * r + 16, v >> 16);
      }
      __syncwarp();
#pragma unroll
      for (int r = 0; r < 4; r++) {
        const u32 v = pk_hf(D[r >> 1][2 * (r & 1) + 1], D[r >> 1][2 * (r & 1)]), t2 = tp + lane * 4 + 128 * r;
        sts32(t2 + TO * 4, v); sts16(t2 + TE * 4, v >> 16); sts16(t2 + (TE + 1) * 4 + 2, v);
      }
      __syncwarp();
    }
  } else {
    u32 sa = SM_SIL + 576 * (w & 1) + 24 * min(lane, 23u);
#pragma unroll 1
    for (int j = 0; j < 6; j++) {
      sts32(sa, pk_bf(silu_f(blo(la)), silu_f(bhi(la))));
      la = ai; ai = cr.x; cr.x = cr.y; cr.y = ci.x; ci.x = ci.y; sa += 4;
    }
    __syncwarp();
  }
  TSW(0, 6); TSW(10, 7);
  const u32 rl16 = ((lane & 7) + ((lane >> 3) & 1) + 8 * (lane >> 4)) * 16;
  const u32 zl = g * 16 + (q & 1) * 8;
  const u32 tko = (4 * h + 8 * hi) * 1152 + cho + b * 18432;
  uint4 dk, wr, md[6];
#define P2LOAD() { \
    const char* mp_ = gs + mod_off(cho >> 1); \
    _Pragma("unroll") for (int j = 0; j < 6; j++) md[j] = ldr128(mp_ + j * MODJ); \
    _Pragma("unroll") for (int k = 0; k < 4; k++) xv[k] = ldg128(p.x + tko + k * 1152); \
    dk = ldg128(p.dsk + cho); wr = ldg128(p.wr + cho); }
  if (w < 4) {
    asm volatile("setmaxnreg.inc.sync.aligned.u32 232;");
    const u32 tp = SM_TAP + w * TAPS;
    const u32 tr = tp + ((hi ? TO : TE) + (g >> 1) - q) * 4;
    u32 T[33][4], B5[5][2], B3[5][2];
    const u32 pml = (ssrc | zr) ? 0 : pm;
#pragma unroll
    for (int d = 0; d < 33; d++) {
      T[d][0] = lds32(tr + 32 * d); T[d][1] = lds32(tr + 32 * d + 16);
      T[d][2] = d ? cpy(T[d - 1][1], zr, 0) : zr; T[d][3] = cpy(T[d][0], zr, 1);
    }
    const u32 bt = tp + (T5 + g - q) * 4;
#pragma unroll
    for (int d = 0; d < 5; d++) {
      B5[d][0] = lds32(bt + 32 * d + 128); B5[d][1] = lds32(bt + 32 * d + 112);
      B3[d][0] = lds32(bt + 32 * d + 128 + (T3 - T5) * 4); B3[d][1] = lds32(bt + 32 * d + 112 + (T3 - T5) * 4);
    }
    u32 za = SM_ZS + 16 + w * ZSS + (q >> 1) * ZPS + zl;
    u32 wa = SM_R + W5O - 256 + w * WSL + rl16;
    u32 sa = SM_S3 - 2560 + w * 4096 + lane * 16;
    char* yp = gs + (G_Y + 2 * q * 18432 + (Pm + w) * 32 + 4 * g);
    TSW(0, 8);
    lds32(za);
    bsync(9, 384);
    TSW(0, 11);
    float A[4][4] = {};
    uint2 ring[4];
#pragma unroll
    for (int s = 0; s < 3; s++) ring[s] = lds64(za + 16 * s);
    const uint2 fc = lds64(SM_SC + 16 * w + 8);
    const float F = uf(fc.x) * uf(fc.y);
    const float ZERO[4] = {};
#define DENSE(s) { ring[(s + 3) & 3] = lds64(za + 16 * (s + 3)); \
    _Pragma("unroll") for (int i = 0; i < 4; i++) mma_hf_o(A[i], A[i], T[8 * i + 7 - s], ring[s & 3].x, ring[s & 3].y); }
#define LAST(N) ring[2] = lds64(za + 160); float O[4]; mma_hf_o(O, A[0], T[0], ring[3].x, ring[3].y); \
    _Pragma("unroll") for (int i = 0; i < 3; i++) mma_hf_o(A[i], A[i + 1], T[8 * i + 8], ring[3].x, ring[3].y); \
    mma_hf_o(A[3], N, T[32], ring[3].x, ring[3].y);
#pragma unroll 1
    for (int j = 0; j < 3; j++) {
#pragma unroll
      for (int s = 0; s < 7; s++) DENSE(s);
      LAST(ZERO);
      y_store(O[0], O[1], O[2], O[3], F, pml, yp);
      za += 128; yp += 8 * 18432;
    }
#pragma unroll 1
    for (int j = 3; j < 13; j++) {
#pragma unroll
      for (int s = 0; s < 5; s++) DENSE(s);
      if (j == 3) bsync(10, 384);
      if (j == 8) bsync(11, 256);
      const uint4 a5 = ldsm4t(wa), a3 = ldsm4t(wa + (W3O - W5O));
      uint4 s3 = {0, 0, 0, 0};
      if (j >= 8) s3 = lds128(sa);
      DENSE(5); DENSE(6);
      float N[4] = {};
      mma_hf(N, a5.x, a5.y, a5.z, a5.w, B5[4][0], B5[4][1]);
#pragma unroll
      for (int i = 0; i < 4; i++) mma_hf(A[i], a5.x, a5.y, a5.z, a5.w, B5[i][0], B5[i][1]);
      mma_hf(N, a3.x, a3.y, a3.z, a3.w, B3[4][0], B3[4][1]);
#pragma unroll
      for (int i = 0; i < 4; i++) mma_hf(A[i], a3.x, a3.y, a3.z, a3.w, B3[i][0], B3[i][1]);
      LAST(N);
      y_store(O[0] + uf(s3.x), O[1] + uf(s3.y), O[2] + uf(s3.z), O[3] + uf(s3.w), F, pml, yp);
      za += 128; wa += 256; sa += 512; yp += 8 * 18432;
    }
    TSW(0, 14);
    P2LOAD();
    {
      float X[3][4] = {};
#pragma unroll
      for (int ty = 0; ty < 2; ty++) {
        const uint4 a = ldsm4t(wa + ty * (W3O - W5O)), c = ldsm4t(wa + 256 + ty * (W3O - W5O)), d = ldsm4t(wa + 512 + ty * (W3O - W5O));
#pragma unroll
        for (int i = 0; i < 3; i++) mma_hf(A[i], a.x, a.y, a.z, a.w, ty ? B3[i][0] : B5[i][0], ty ? B3[i][1] : B5[i][1]);
#pragma unroll
        for (int i = 0; i < 2; i++) mma_hf(X[i], c.x, c.y, c.z, c.w, ty ? B3[i][0] : B5[i][0], ty ? B3[i][1] : B5[i][1]);
        mma_hf(X[2], d.x, d.y, d.z, d.w, ty ? B3[0][0] : B5[0][0], ty ? B3[0][1] : B5[0][1]);
      }
      barrive(12, 288);
#pragma unroll
      for (int s = 0; s < 8; s++) {
        const uint2 f0 = s < 3 ? ring[s] : lds64(za + 16 * s), f1 = lds64(za + 16 * s + 128), f2 = lds64(za + 16 * s + 256);
#pragma unroll
        for (int i = 0; i < 3; i++) mma_hf_o(A[i], A[i], T[8 * i + 7 - s], f0.x, f0.y);
        mma_hf_o(X[0], X[0], T[7 - s], f1.x, f1.y); mma_hf_o(X[1], X[1], T[15 - s], f1.x, f1.y);
        mma_hf_o(X[2], X[2], T[7 - s], f2.x, f2.y);
      }
      const uint4 s0 = lds128(sa), s1 = lds128(sa + 512), s2 = lds128(sa + 1024);
      y_store(A[0][0] + uf(s0.x), A[0][1] + uf(s0.y), A[0][2] + uf(s0.z), A[0][3] + uf(s0.w), F, pml, yp);
      y_store(A[1][0] + X[0][0] + uf(s1.x), A[1][1] + X[0][1] + uf(s1.y), A[1][2] + X[0][2] + uf(s1.z), A[1][3] + X[0][3] + uf(s1.w), F, pml, yp + 8 * 18432);
      y_store(A[2][0] + X[1][0] + (X[2][0] + uf(s2.x)), A[2][1] + X[1][1] + (X[2][1] + uf(s2.y)), A[2][2] + X[1][2] + (X[2][2] + uf(s2.z)), A[2][3] + X[1][3] + (X[2][3] + uf(s2.w)), F, pml, yp + 16 * 18432);
    }
    barrive(13, 288);
    TSW(0, 15);
  } else {
    asm volatile("setmaxnreg.dec.sync.aligned.u32 136;");
    const u32 t8 = tid - 128;
#pragma unroll 1
    for (int ph = 0; ph < 2; ph++) {
      if (!kw) {
        const u32 urg = b < 72;
#pragma unroll 1
        for (u32 slot = ph ? urg : 0; slot < (ph ? (b < 88 ? 2 : 1) : urg); slot++) {
          float c[2][4] = {};
          const u32 row = 288 * (w & 1) + (lane & 7) + 8 * (lane >> 4);
          u32 aa = SM_UP + slot * 18432 + row * 32 + ((((lane >> 3) ^ (row >> 2)) & 1) << 4);
          u32 ba = SM_SIL + 576 * (w & 1) + 4 * q;
          mb_wait(SM_MB + 8 * slot);
#pragma unroll 1
          for (int s = 0; s < 3; s++) {
#pragma unroll
            for (int i = 0; i < 6; i++) { const uint4 a = ldsm4t(aa + i * 512); mma_bf(c[i & 1], a.x, a.y, a.z, a.w, lds32(ba + 32 * i), lds32(ba + 32 * i + 16)); }
            aa += 3072; ba += 192;
          }
          float v = (q & 1) ? c[0][2] + c[1][2] : c[0][0] + c[1][0];
          if (w & 1) sts32(SM_GP + lane * 4, fu(v));
          bsync(7, 64);
          v += uf(lds32(SM_GP + lane * 4));
          if (!(w & 1) && q < 2) str16(gs + (G_MOD + (b + 128 * slot) * 128 + 2 * g + 16 * q), pk_bf(rbf(v) * F2M64, 0.f) | (g < 2 ? pm : 0));
          bsync(7, 64);
        }
      }
      if (ph) break;
      TSW(8, 12);
      const char* zs = gs + ((t8 >> 3) * 18432 + Pm * 32 + (t8 & 7) * 16);
      const char* zs4 = gs + ((t8 >> 1) * 18432 + Ps * 32 + (t8 & 1) * 16);
      uint4 v[5];
#pragma unroll
      for (int j = 0; j < 5; j++) v[j].x = INVAL;
      POLL(_Pragma("unroll") for (int j = 0; j < 5; j++) if ((v[j].x ^ pm) & TAGM) v[j] = ldr128(j < 4 ? zs + j * 32 * 18432 : zs4),
           ((v[0].x ^ pm) | (v[1].x ^ pm) | (v[2].x ^ pm) | (v[3].x ^ pm) | (v[4].x ^ pm)) & TAGM, 1);
      TSW(4, 9);
      if (w == 11) {
        const u32 d = chan_of(lane < 4 ? Pm + lane : Ps);
        const char* mp = gs + mod_off(d);
        uint4 ta, tc;
        POLL({ ta = ldr128(mp); tc = ldr128(mp + MODJ); }, ((ta.x ^ pm) | (tc.x ^ pm)) & TAGM, 2);
        const u32 aw = (d & 4) ? ((d & 2) ? ta.w : ta.z) : ((d & 2) ? ta.y : ta.x & ~TAGM);
        const u32 cw = (d & 4) ? ((d & 2) ? tc.w : tc.z) : ((d & 2) ? tc.y : tc.x & ~TAGM);
        const float sa = ((d & 1) ? bhi(aw) : blo(aw)) * F2P64, c1 = rbf(fmaf((d & 1) ? bhi(cw) : blo(cw), F2P64, 1.f));
        const u32 EM = min(max(fu(fmaxf(32.f * fabsf(c1), fabsf(sa))) >> 23, 80u), 250u);
        const float inv = uf((264 - EM) << 23);
        if (lane < 5) { sts64(SM_SC + 16 * lane, pk_hf(16.f * c1 * inv, 16.f * c1 * inv), pk_hf(sa * inv, sa * inv)); sts32(SM_SC + 16 * lane + 8, (EM - 74) << 23); }
        TS(10);
      }
      const u32 dst = SM_ZS + 128 + (t8 & 6) * (ZSS / 2) + (t8 & 1) * ZPS + (t8 >> 3) * 16;
      const u32 sig = t8 / 51, i0 = t8 - 51 * sig;
      bsync(8, 256);
      const uint2 cc = lds64(SM_SC + 8 * (t8 & 6)), c4 = lds64(SM_SC + 64);
#pragma unroll
      for (int j = 0; j < 5; j++) {
        const uint2 c = j < 4 ? cc : c4;
        sts128(j < 4 ? dst + j * 512 : SM_Z4 + (t8 & 1) * ZP4 + (t8 >> 1) * 16, hfma(v[j].x & ~TAGM, c.x, c.y), hfma(v[j].y, c.x, c.y), hfma(v[j].z, c.x, c.y), hfma(v[j].w, c.x, c.y));
      }
      bsync(9, 384);
#pragma unroll 1
      for (int rd = 0; rd < 2; rd++) {
        const u32 i = i0 + 51 * rd;
        if (sig < 5 && i < 97) {
          const u32 za = (sig < 4 ? SM_ZS + 128 + sig * ZSS : SM_Z4) + i * 16, zb = za + (sig < 4 ? ZPS : ZP4);
          const uint4 c2 = lds128(zb - 32), a1 = lds128(za - 16), b1 = lds128(zb - 16), a0 = lds128(za), b0 = lds128(zb);
          const u32 P[17] = {c2.y, c2.w, a1.x, a1.z, b1.x, b1.z, a1.y, a1.w, b1.y, b1.w, a0.x, a0.z, b0.x, b0.z, a0.y, a0.w, b0.y};
          u32 Q[17], D1[15], F4[15], W5[13], D2[17];
#pragma unroll
          for (int j = 1; j < 17; j++) Q[j] = __byte_perm(P[j - 1], P[j], 0x5432);
#pragma unroll
          for (int j = 1; j < 15; j++) D1[j] = hadd(P[j], Q[j]);
#pragma unroll
          for (int j = 2; j < 15; j++) F4[j] = hadd(D1[j], D1[j - 1]);
#pragma unroll
          for (int n = 0; n < 13; n++) W5[n] = hadd(F4[n + 2], P[n]);
#pragma unroll
          for (int j = 5; j < 17; j++) D2[j] = hadd(Q[j], P[j - 1]);
          const u32 wa = SM_R + sig * WSL + i * 16, wb = wa + i * 16;
          u32 o[8];
#pragma unroll
          for (int n = 0; n < 8; n++) o[n] = hadd(D2[n + 5], Q[n + 4]);
          sts128(wb + W5O, W5[5], W5[6], W5[7], W5[8]); sts128(wb + W3O, o[0], o[1], o[2], o[3]);
          if (i < 96) { sts128(wb + W5O + 16, W5[9], W5[10], W5[11], W5[12]); sts128(wb + W3O + 16, o[4], o[5], o[6], o[7]); }
          if (i < 16) { sts128(wa, 0, 0, 0, 0); sts128(wa + W3O - 256, 0, 0, 0, 0); }
          if (i < 64) {
#pragma unroll
            for (int n = 0; n < 8; n++) o[n] = hadd(F4[n + 4], W5[n]);
            sts128(wa + W9O, o[0], o[1], o[2], o[3]); sts128(wa + W9O + 1024, o[4], o[5], o[6], o[7]);
#pragma unroll
            for (int n = 0; n < 8; n++) o[n] = hadd(hadd(Q[n + 8], Q[n + 5]), W5[n + 5]);
            sts128(wa + W7O, o[0], o[1], o[2], o[3]); sts128(wa + W7O + 1024, o[4], o[5], o[6], o[7]);
            sts128(wa + V2O, D2[9], D2[10], D2[11], D2[12]); sts128(wa + V2O + 1024, D2[13], D2[14], D2[15], D2[16]);
          }
        }
        __syncwarp();
        if (rd == 0) barrive(10, 384);
      }
      if (w >= 8) barrive(15, 256);
    }
    if (w < 8) {
      bsync(15, 256);
      TSW(4, 13);
#pragma unroll 1
      for (u32 sl = w - 4;; sl = 4) {
        const u32 wa = SM_R + sl * WSL + ((lane >> 3) & 1) * 1024 + ((lane & 7) + 8 * (lane >> 4)) * 16;
        const u32 kv = lds32(SM_KV + 4 * sl), bi = (g >> 1) == q ? (hi ? kv << 16 : kv) : 0u;
        float acc[8][4] = {};
#pragma unroll
        for (int j = 0; j < 4; j++) { const uint4 a = ldsm4t(wa + V2O + j * 256); mma8_hf(acc[2 * j], a.x, a.y, bi); mma8_hf(acc[2 * j + 1], a.z, a.w, bi); }
        u32 bt = SM_TAP + sl * TAPS + (TE9 + hi * TEO + (g >> 1) - q) * 4, wt = wa + W9O;
#pragma unroll 1
        for (int ty = 0; ty < 2; ty++) {
          uint4 a[4];
#pragma unroll
          for (int be = 0; be < 4; be++) a[be] = ldsm4t(wt + be * 256);
          u32 b1 = lds32(bt + 112);
#pragma unroll
          for (int d = 0; d < 8; d++) {
            const u32 b0 = lds32(bt + 16 * d + 128);
#pragma unroll
            for (int be = 0; be < 4; be++) if (d + 2 * be < 8) mma_hf(acc[d + 2 * be], a[be].x, a[be].y, a[be].z, a[be].w, b0, b1);
            b1 = b0;
          }
          bt += (TE7 - TE9) * 4; wt += W7O - W9O;
        }
#pragma unroll
        for (int j = 0; j < 8; j++) sts128(SM_S3 + sl * 4096 + j * 512 + lane * 16, fu(acc[j][0]), fu(acc[j][1]), fu(acc[j][2]), fu(acc[j][3]));
        if (w != 4 || sl == 4) break;
      }
      barrive(11, 256);
      const int u0 = 4 * (w - 4) + 2 * rho;
      const u32 tp = SM_TAP + 4 * TAPS;
      u32 tr = tp + ((hi ? TO : TE) + (g >> 1) - q) * 4;
      u32 zb = SM_Z4 + (q >> 1) * ZP4 + u0 * 128 + zl;
      float acc[4][4] = {};
      uint2 R[8];
#pragma unroll
      for (int j = 0; j < 8; j++) R[j] = lds64(zb + 128 - 16 * j);
      u32 prev = 0;
#pragma unroll 1
      for (int it = 0; it < 4; it++) {
#pragma unroll
        for (int s = 0; s < 8; s++) {
          const uint2 nw = lds64(zb - 16 * s);
          const u32 t0 = lds32(tr + 32 * s), t1 = lds32(tr + 32 * s + 16);
          mma_hf(acc[2 + (s & 1)], t0, t1, prev, t0, R[s].x, R[s].y);
          mma_hf(acc[s & 1], t0, t1, prev, t0, nw.x, nw.y);
          R[s] = nw; prev = t1;
        }
        zb -= 128; tr += 256;
      }
      { const uint2 nw = lds64(zb); const u32 t0 = lds32(tr); mma_hf(acc[2], t0, 0, prev, t0, R[0].x, R[0].y); mma_hf(acc[0], t0, 0, prev, t0, nw.x, nw.y); }
#pragma unroll 1
      for (int d = min(u0 + 1, 8); d >= 3; d--) {
        const u32 wa = SM_R + 4 * WSL + W5O + rl16 + (u0 - d) * 256, bt = tp + (T5 + g - q) * 4 + 32 * d;
#pragma unroll
        for (int ty = 0; ty < 2; ty++) {
          const uint4 a = ldsm4t(wa + ty * (W3O - W5O));
          const u32 bb = bt + ty * (T3 - T5) * 4;
          mma_hf(acc[ty], a.x, a.y, a.z, a.w, lds32(bb), lds32(bb - 16));
          mma_hf(acc[2 + ty], a.x, a.y, a.z, a.w, lds32(bb + 32), lds32(bb + 16));
        }
      }
      barrive(12, 288);
      bsync(14, 128);
      const uint2 fc = lds64(SM_SC + 16 * 4 + 8);
      const float F = uf(fc.x) * uf(fc.y);
      char* yp = gs + (G_Y + (8 * u0 + 2 * q) * 18432 + Ps * 32 + 4 * g);
      const u32 pml = ssrc ? 0 : pm;
#pragma unroll
      for (int j = 0; j < 2; j++) {
        uint4 s3 = {0, 0, 0, 0};
        if (u0 >= 8) s3 = lds128(SM_S3 + 4 * 4096 + (u0 - 8 + j) * 512 + lane * 16);
        y_store(acc[2 * j][0] + acc[2 * j + 1][0] + uf(s3.x), acc[2 * j][1] + acc[2 * j + 1][1] + uf(s3.y), acc[2 * j][2] + acc[2 * j + 1][2] + uf(s3.z),
                acc[2 * j][3] + acc[2 * j + 1][3] + uf(s3.w), F, pml, yp + j * 8 * 18432);
      }
      TSW(7, 16);
    } else if (w == 9) {
      if (lane == 0) tma3d(SM_UP, &tm_up, SM_MB + 24, 46080, 8 * Pm, 0);
      TS(17);
      bsync(12, 288);
      if (lane == 0) {
        asm volatile("fence.proxy.async.shared::cta;" ::: "memory");
        tma3d(SM_WD, &tm_down, SM_MB + 32, 41472, 72 * (b & 7), 2 * (b >> 3));
      }
    } else if (w == 10) {
      float s1 = 0.f, s2 = 0.f;
#pragma unroll 1
      for (u32 j = lane; j < 96; j += 32) {
        const u32 jj = min(j, 71u);
        const char* mp = gs + mod_off(8 * jj);
        uint4 a, c, r = ldg128(p.wr + 16 * jj);
        POLL({ a = ldr128(mp + 3 * MODJ); c = ldr128(mp + 4 * MODJ); }, ((a.x ^ pm) | (c.x ^ pm)) & TAGM, 3);
        a.x &= ~TAGM; c.x &= ~TAGM;
#pragma unroll 1
        for (int i = j < 72 ? 0 : 4; i < 4; i++) {
          const u32 c1 = bfma(c.x, B2P64, BONE), s = bmul(a.x, B2P64);
          s1 = fmaf(blo(c1), blo(r.x), s1); s1 = fmaf(bhi(c1), bhi(r.x), s1);
          s2 = fmaf(blo(s), blo(r.x), s2); s2 = fmaf(bhi(s), bhi(r.x), s2);
          a.x = a.y; a.y = a.z; a.z = a.w; c.x = c.y; c.y = c.z; c.z = c.w; r.x = r.y; r.y = r.z; r.z = r.w;
        }
      }
#pragma unroll 1
      for (int o = 16; o; o >>= 1) { s1 += __shfl_xor_sync(~0u, s1, o); s2 += __shfl_xor_sync(~0u, s2, o); }
      sts64(SM_RC, fu(s1), fu(s2));
      TS(31);
      barrive(1, 320);
    }
    if (w < 9) P2LOAD();
  }
  post_conv(p, tid + p.zero, b, ep, xv, dk, wr, md);
  if (tid == 352 && s2u(smem) != SM0) __trap();
}

typedef CUresult (*EncFn)(CUtensorMap*, CUtensorMapDataType, cuuint32_t, void*, const cuuint64_t*, const cuuint64_t*, const cuuint32_t*, const cuuint32_t*,
                          CUtensorMapInterleave, CUtensorMapSwizzle, CUtensorMapL2promotion, CUtensorMapFloatOOBfill);
static void make_map(EncFn enc, CUtensorMap* tm, void* ptr, int cols, int rows, int bw, int br, int nb, CUtensorMapSwizzle sw) {
  cuuint64_t gd[3] = {(cuuint64_t)cols, (cuuint64_t)br, (cuuint64_t)(rows / br)}, gs[2] = {(cuuint64_t)cols * 2, (cuuint64_t)cols * 2 * br};
  cuuint32_t bd[3] = {(cuuint32_t)bw, (cuuint32_t)br, (cuuint32_t)nb}, es[3] = {1, 1, 1};
  enc(tm, CU_TENSOR_MAP_DATA_TYPE_BFLOAT16, 3, ptr, gd, gs, bd, es, CU_TENSOR_MAP_INTERLEAVE_NONE, sw, CU_TENSOR_MAP_L2_PROMOTION_NONE, CU_TENSOR_MAP_FLOAT_OOB_FILL_NONE);
}
extern "C" void kernel_launch(void* const* d_in, const int* in_sizes, int n_in, void* d_out, int out_size) {
  static EncFn enc = nullptr;
  static void* scratch = nullptr;
  if (!enc) {
    cudaGetSymbolAddress(&scratch, g_s);
    cudaDriverEntryPointQueryResult qr;
    cudaGetDriverEntryPoint("cuTensorMapEncodeTiled", (void**)&enc, cudaEnableDefault, &qr);
    cudaFuncSetAttribute(fused_kernel, cudaFuncAttributeMaxDynamicSharedMemorySize, SM_TOTAL);
  }
  CUtensorMap tm_mod, tm_gate, tm_up, tm_down;
  make_map(enc, &tm_mod, d_in[13], 3456, 576, 16, 192, 3, CU_TENSOR_MAP_SWIZZLE_32B);
  make_map(enc, &tm_gate, d_in[9], 4608, 576, 40, 192, 3, CU_TENSOR_MAP_SWIZZLE_NONE);
  make_map(enc, &tm_up, d_in[10], 4608, 576, 40, 192, 3, CU_TENSOR_MAP_SWIZZLE_NONE);
  make_map(enc, &tm_down, d_in[11], 576, 4608, 72, 144, 2, CU_TENSOR_MAP_SWIZZLE_NONE);
  Prm p;
  p.x = (const char*)d_in[0]; p.la = (const char*)d_in[1]; p.ai = (const char*)d_in[2]; p.cr = (const char*)d_in[3];
  p.ci = (const char*)d_in[4]; p.ldt = (const char*)d_in[5]; p.dsk = (const char*)d_in[6]; p.wr = (const char*)d_in[8];
  p.c = (const char*)d_in[12]; p.out = (char*)d_out; p.zero = 0; p.gs = (char*)scratch;
  fused_kernel<<<128, 384, SM_TOTAL>>>(p, tm_mod, tm_gate, tm_up, tm_down);
}
```

```cpp
#include <cuda_runtime.h>
#include <cuda.h>
#include <cuda_bf16.h>
#include <cuda_fp16.h>
#include <stdint.h>
#define FUSED 1
#define DEV __device__ __forceinline__
typedef uint32_t u32;

constexpr u32 OB_KEY = 0, OB_ACT = 128, OB_PART = 768, OB = 3072, ROW = 1168;
constexpr u32 G_Z = 0, G_Y = 128 * 18432, G_XS = 2 * G_Y, G_X1 = G_XS + 8 * ROW, G_MOD = G_X1 + 8 * ROW, G_OB = G_MOD + 216 * 128;
constexpr u32 G_EP = G_OB + 128 * OB, G_END = G_EP + 128;
__device__ __align__(128) unsigned char g_s[G_END];
#define TS(i)
#define TS0()
#define ERRF(code)

constexpr int SM0 = 1024;
constexpr int ZPS = 2240, ZSS = 4496, ZP4 = 2624;
constexpr int SM_GATE = SM0, SM_UP = SM_GATE + 46080, SM_ZS = SM_UP + 46080, SM_Z4 = SM_ZS + 4 * ZSS + 512;
constexpr int SM_TAP = SM_Z4 + ZP4 + 2048, TAPS = 3392;
constexpr int SM_MB = SM_TAP + 5 * TAPS;
constexpr int SM_ST = SM_MB + 48;
constexpr int SM_SC = SM_ST + 256;
constexpr int SM_KV = SM_SC + 80;
constexpr int SM_RC = SM_KV + 32;
constexpr int SM_THR = SM_RC + 16;
constexpr int SM_KEY = SM_THR + 48;
constexpr int SM_TOK = SM_KEY + 64;
constexpr int SM_CNT = SM_TOK + 128;
constexpr int SM_GP = SM_CNT + 128;
constexpr int SM_SIL = SM_GP + 128;
constexpr int SM_SP = SM_SIL + 1152;
constexpr int SM_R = (SM_SP + 5760 + 127) / 128 * 128;
static_assert(SM_SP % 16 == 0 && SM_THR % 16 == 0 && SM_ST % 16 == 0 && SM_TAP % 16 == 0 && SM_CNT % 16 == 0, "smem map");
constexpr int KTAB = 9216, WSL = 12832, W5O = 256, W3O = 3600, W9O = 6688, W7O = 8736, V2O = 10784;
constexpr int SM_S3 = SM_R + 5 * WSL;
constexpr int SM_WD = SM_R, SM_XS = SM_R + 41600, SM_AC = SM_XS + 9344, SM_RED = SM_AC + 4608, SM_OS = SM_RED + 10240;
constexpr int STASH = 16 * ROW + 64, SM_HS = SM_ZS, SM_X1S = SM_HS + STASH;
constexpr int SM_TOTAL = SM_R + 92160 - SM0;
static_assert(SM_X1S + STASH <= SM_MB && SM_OS + STASH <= SM_R + 92160 && SM_TOTAL <= 232448, "smem map");
constexpr int TE = 4, TO = 272 + 4, T5 = 544 - 17, T3 = 608 - 17, TE9 = 672 - 25, TE7 = 760 - 25, TEO = 48;
constexpr int SPIN = 1 << 16;
constexpr u32 TAGM = 0x40004000u, INVAL = 0x00004801u;

DEV u32 s2u(const void* p) { return (u32)__cvta_generic_to_shared(p); }
DEV void mma_bf(float (&c)[4], u32 a0, u32 a1, u32 a2, u32 a3, u32 b0, u32 b1) {
  asm("mma.sync.aligned.m16n8k16.row.col.f32.bf16.bf16.f32 {%0,%1,%2,%3},{%4,%5,%6,%7},{%8,%9},{%0,%1,%2,%3};"
      : "+f"(c[0]), "+f"(c[1]), "+f"(c[2]), "+f"(c[3]) : "r"(a0), "r"(a1), "r"(a2), "r"(a3), "r"(b0), "r"(b1));
}
DEV void mma_hf(float (&c)[4], u32 a0, u32 a1, u32 a2, u32 a3, u32 b0, u32 b1) {
  asm("mma.sync.aligned.m16n8k16.row.col.f32.f16.f16.f32 {%0,%1,%2,%3},{%4,%5,%6,%7},{%8,%9},{%0,%1,%2,%3};"
      : "+f"(c[0]), "+f"(c[1]), "+f"(c[2]), "+f"(c[3]) : "r"(a0), "r"(a1), "r"(a2), "r"(a3), "r"(b0), "r"(b1));
}
DEV void mma8_bf(float (&c)[4], u32 a0, u32 a1, u32 b0) {
  asm("mma.sync.aligned.m16n8k8.row.col.f32.bf16.bf16.f32 {%0,%1,%2,%3},{%4,%5},{%6},{%0,%1,%2,%3};"
      : "+f"(c[0]), "+f"(c[1]), "+f"(c[2]), "+f"(c[3]) : "r"(a0), "r"(a1), "r"(b0));
}
DEV void mma8_hf(float (&c)[4], u32 a0, u32 a1, u32 b0) {
  asm("mma.sync.aligned.m16n8k8.row.col.f32.f16.f16.f32 {%0,%1,%2,%3},{%4,%5},{%6},{%0,%1,%2,%3};"
      : "+f"(c[0]), "+f"(c[1]), "+f"(c[2]), "+f"(c[3]) : "r"(a0), "r"(a1), "r"(b0));
}
DEV u32 movm(u32 x) { u32 r; asm("movmatrix.sync.aligned.m8n8.trans.b16 %0,%1;" : "=r"(r) : "r"(x)); return r; }
DEV uint4 ldsm4(u32 a) { uint4 r; asm volatile("ldmatrix.sync.aligned.m8n8.x4.shared.b16 {%0,%1,%2,%3},[%4];" : "=r"(r.x), "=r"(r.y), "=r"(r.z), "=r"(r.w) : "r"(a)); return r; }
DEV uint2 ldsm2(u32 a) { uint2 r; asm volatile("ldmatrix.sync.aligned.m8n8.x2.shared.b16 {%0,%1},[%2];" : "=r"(r.x), "=r"(r.y) : "r"(a)); return r; }
DEV uint4 ldsm4t(u32 a) { uint4 r; asm volatile("ldmatrix.sync.aligned.m8n8.x4.trans.shared.b16 {%0,%1,%2,%3},[%4];" : "=r"(r.x), "=r"(r.y), "=r"(r.z), "=r"(r.w) : "r"(a)); return r; }
DEV u32 lds32(u32 a) { u32 r; asm volatile("ld.volatile.shared.u32 %0,[%1];" : "=r"(r) : "r"(a)); return r; }
DEV uint2 lds64(u32 a) { uint2 r; asm volatile("ld.shared.v2.u32 {%0,%1},[%2];" : "=r"(r.x), "=r"(r.y) : "r"(a)); return r; }
DEV uint4 lds128(u32 a) { uint4 r; asm volatile("ld.shared.v4.u32 {%0,%1,%2,%3},[%4];" : "=r"(r.x), "=r"(r.y), "=r"(r.z), "=r"(r.w) : "r"(a)); return r; }
DEV void sts16(u32 a, u32 v) { asm volatile("st.shared.u16 [%0],%1;" ::"r"(a), "h"((unsigned short)v) : "memory"); }
DEV void sts32(u32 a, u32 v) { asm volatile("st.shared.u32 [%0],%1;" ::"r"(a), "r"(v) : "memory"); }
DEV void sts64(u32 a, u32 x, u32 y) { asm volatile("st.shared.v2.u32 [%0],{%1,%2};" ::"r"(a), "r"(x), "r"(y) : "memory"); }
DEV void sts128(u32 a, u32 x, u32 y, u32 z, u32 w) { asm volatile("st.shared.v4.u32 [%0],{%1,%2,%3,%4};" ::"r"(a), "r"(x), "r"(y), "r"(z), "r"(w) : "memory"); }
DEV uint4 ldr128(const void* p) { uint4 v; asm volatile("ld.relaxed.gpu.global.v4.u32 {%0,%1,%2,%3},[%4];" : "=r"(v.x), "=r"(v.y), "=r"(v.z), "=r"(v.w) : "l"(p) : "memory"); return v; }
DEV uint2 ldr64(const void* p) { uint2 v; asm volatile("ld.relaxed.gpu.global.v2.u32 {%0,%1},[%2];" : "=r"(v.x), "=r"(v.y) : "l"(p) : "memory"); return v; }
DEV u32 ldr32(const void* p) { u32 v; asm volatile("ld.relaxed.gpu.global.u32 %0,[%1];" : "=r"(v) : "l"(p) : "memory"); return v; }
DEV void str128(void* p, u32 x, u32 y, u32 z, u32 w) { asm volatile("st.relaxed.gpu.global.v4.u32 [%0],{%1,%2,%3,%4};" ::"l"(p), "r"(x), "r"(y), "r"(z), "r"(w) : "memory"); }
DEV void str64(void* p, u32 x, u32 y) { asm volatile("st.relaxed.gpu.global.v2.u32 [%0],{%1,%2};" ::"l"(p), "r"(x), "r"(y) : "memory"); }
DEV void str32(void* p, u32 x) { asm volatile("st.relaxed.gpu.global.u32 [%0],%1;" ::"l"(p), "r"(x) : "memory"); }
DEV void str16(void* p, u32 x) { asm volatile("st.relaxed.gpu.global.u16 [%0],%1;" ::"l"(p), "h"((unsigned short)x) : "memory"); }
DEV uint4 ldg128(const void* p) { uint4 v; asm volatile("ld.global.nc.v4.u32 {%0,%1,%2,%3},[%4];" : "=r"(v.x), "=r"(v.y), "=r"(v.z), "=r"(v.w) : "l"(p)); return v; }
DEV uint2 ldg64(const void* p) { uint2 v; asm volatile("ld.global.nc.v2.u32 {%0,%1},[%2];" : "=r"(v.x), "=r"(v.y) : "l"(p)); return v; }
DEV u32 ldg32(const void* p) { u32 v; asm volatile("ld.global.nc.u32 %0,[%1];" : "=r"(v) : "l"(p)); return v; }
DEV u32 ldg16(const void* p) { unsigned short v; asm volatile("ld.global.nc.u16 %0,[%1];" : "=h"(v) : "l"(p)); return v; }
#define bsync(id, n) asm volatile("bar.sync %0,%1;" ::"n"(id), "n"(n) : "memory")
#define barrive(id, n) asm volatile("bar.arrive %0,%1;" ::"n"(id), "n"(n) : "memory")
DEV void mb_init(u32 a) { asm volatile("mbarrier.init.shared.b64 [%0],1;" ::"r"(a) : "memory"); }
DEV void mb_expect(u32 a, u32 bytes) { asm volatile("mbarrier.arrive.expect_tx.shared.b64 _,[%0],%1;" ::"r"(a), "r"(bytes) : "memory"); }
DEV void mb_wait(u32 a) {
  u32 ok; int it = 0;
  do { asm volatile("{.reg .pred p; mbarrier.try_wait.parity.shared.b64 p,[%1],0; selp.u32 %0,1,0,p;}" : "=r"(ok) : "r"(a) : "memory"); } while (!ok && ++it < SPIN);
}
DEV void bulk_out(void* dst, u32 src) { asm volatile("cp.async.bulk.global.shared::cta.bulk_group [%0],[%1],1152;" ::"l"(dst), "r"(src) : "memory"); }
DEV void tma3d(u32 dst, const CUtensorMap* tm, u32 mb, u32 bytes, int c0, int c2) {
  mb_expect(mb, bytes);
  asm volatile("cp.async.bulk.tensor.3d.shared::cluster.global.mbarrier::complete_tx::bytes [%0],[%1,{%3,0,%4}],[%2];"
               ::"r"(dst), "l"((uint64_t)tm), "r"(mb), "r"(c0), "r"(c2) : "memory");
}
DEV float blo(u32 w) { return __uint_as_float(w << 16); }
DEV float bhi(u32 w) { return __uint_as_float(w & 0xffff0000u); }
DEV u32 pk_bf(float lo, float hi) { u32 r; asm("cvt.rn.bf16x2.f32 %0,%1,%2;" : "=r"(r) : "f"(hi), "f"(lo)); return r; }
DEV u32 pk_hf(float lo, float hi) { u32 r; asm("cvt.rn.f16x2.f32 %0,%1,%2;" : "=r"(r) : "f"(hi), "f"(lo)); return r; }
DEV float rbf(float x) { return __uint_as_float(pk_bf(0.f, x) & 0xffff0000u); }
DEV u32 bfma(u32 a, u32 b, u32 c) { u32 r; asm("fma.rn.bf16x2 %0,%1,%2,%3;" : "=r"(r) : "r"(a), "r"(b), "r"(c)); return r; }
DEV u32 bmul(u32 a, u32 b) { u32 r; asm("mul.rn.bf16x2 %0,%1,%2;" : "=r"(r) : "r"(a), "r"(b)); return r; }
DEV u32 badd(u32 a, u32 b) { u32 r; asm("add.rn.bf16x2 %0,%1,%2;" : "=r"(r) : "r"(a), "r"(b)); return r; }
DEV u32 hadd(u32 a, u32 b) { u32 r; asm("add.rn.f16x2 %0,%1,%2;" : "=r"(r) : "r"(a), "r"(b)); return r; }
DEV u32 hfma(u32 a, u32 b, u32 c) { u32 r; asm("fma.rn.f16x2 %0,%1,%2,%3;" : "=r"(r) : "r"(a), "r"(b), "r"(c)); return r; }
struct C2 { u32 re, im; };
DEV C2 cm2(C2 a, C2 b) {
  const __half2 ar = *reinterpret_cast<__half2*>(&a.re), ai = *reinterpret_cast<__half2*>(&a.im), br = *reinterpret_cast<__half2*>(&b.re), bi = *reinterpret_cast<__half2*>(&b.im);
  __half2 re = __hfma2(ar, br, __hneg2(__hmul2(ai, bi))), im = __hfma2(ar, bi, __hmul2(ai, br));
  return {*reinterpret_cast<u32*>(&re), *reinterpret_cast<u32*>(&im)};
}
DEV C2 pk2(const float2 (&a)[2]) { return {pk_hf(a[0].x, a[1].x), pk_hf(a[0].y, a[1].y)}; }
DEV C2 pk2c(const float2 (&a)[2]) { return {pk_hf(a[0].x, a[1].x), pk_hf(-a[0].y, -a[1].y)}; }
DEV u32 cpy(u32 x, u32 zr, int alt) {
  u32 r;
  if (alt) asm volatile("xor.b32 %0,%1,%2;" : "=r"(r) : "r"(x), "r"(zr)); else asm volatile("mad.lo.u32 %0,%2,%2,%1;" : "=r"(r) : "r"(x), "r"(zr));
  return r;
}
DEV u32 bsetgt(u32 a, u32 b) { u32 r; asm("set.gt.bf16x2.bf16x2 %0,%1,%2;" : "=r"(r) : "r"(a), "r"(b)); return r; }
DEV float ex2(float x) { float r; asm("ex2.approx.ftz.f32 %0,%1;" : "=f"(r) : "f"(x)); return r; }
DEV float rcpf(float x) { float r; asm("rcp.approx.ftz.f32 %0,%1;" : "=f"(r) : "f"(x)); return r; }
DEV float2 cmul(float2 a, float2 b) { return make_float2(fmaf(a.x, b.x, -a.y * b.y), fmaf(a.x, b.y, a.y * b.x)); }
DEV float2 csq(float2 a) { return make_float2(fmaf(a.x, a.x, -a.y * a.y), (a.x + a.x) * a.y); }
DEV float2 cexp(float lr2, float th) {
  float k = rintf(th * 0.15915494309189535f);
  float r = fmaf(k, -6.2831854820251465f, th); r = fmaf(k, 1.7484555e-7f, r);
  float m = ex2(lr2);
  return make_float2(m * __cosf(r), m * __sinf(r));
}
DEV float silu_f(float v) { return v * rcpf(1.f + ex2(-1.4426950408889634f * v)); }
constexpr u32 B2P64 = 0x5F805F80u, B2M64 = 0x1F801F80u, BONE = 0x3F803F80u;
DEV u32 chan_of(u32 P) { u32 r = P & 63; return (P & ~63) + 32 * (r & 1) + 8 * ((r >> 2) & 3) + 2 * (r >> 4) + ((r >> 1) & 1); }
DEV u32 mod_off(u32 idx) { return G_MOD + (idx >> 4) * 128 + (idx & 8) * 2; }
constexpr u32 MODJ = 36 * 128;
DEV float sqrta(float x) { float r; asm("sqrt.approx.ftz.f32 %0,%1;" : "=f"(r) : "f"(x)); return r; }
DEV u32 fu(float x) { return __float_as_uint(x); }
DEV float uf(u32 x) { return __uint_as_float(x); }
DEV void mma_hf_o(float (&d)[4], const float (&c)[4], const u32 (&a)[4], u32 b0, u32 b1) {
  asm("mma.sync.aligned.m16n8k16.row.col.f32.f16.f16.f32 {%0,%1,%2,%3},{%4,%5,%6,%7},{%8,%9},{%10,%11,%12,%13};"
      : "=f"(d[0]), "=f"(d[1]), "=f"(d[2]), "=f"(d[3]) : "r"(a[0]), "r"(a[1]), "r"(a[2]), "r"(a[3]), "r"(b0), "r"(b1), "f"(c[0]), "f"(c[1]), "f"(c[2]), "f"(c[3]));
}

struct Prm {
  const char *x, *la, *ai, *cr, *ci, *ldt, *c;
  char* gs;
  const char *dsk, *wr;
  char* out;
  u32 zero;
};
constexpr float LOG2E = 1.4426950408889634f, F2P64 = 1.8446744073709552e19f, F2M64 = 5.421010862427522e-20f;

DEV void y_store(float c0, float c1, float c2, float c3, float F, u32 pml, char* yp) {
  str32(yp, pk_bf(c0 * F, c2 * F) | pml);
  str32(yp + 18432, pk_bf(c1 * F, c3 * F) | pml);
}
#define POLL(load, cond_bad, code) { int it_ = 0; do { load; if (++it_ > SPIN) { ERRF(code); break; } } while (__any_sync(~0u, (cond_bad))); }
#define POLLW(load, cond_bad, code) { int it_ = 0; while (__any_sync(~0u, (cond_bad))) { if (++it_ > SPIN) { ERRF(code); break; } load; } }

DEV void post_conv(const Prm& p, const u32 tid, const u32 b, const u32 ep, const uint4 (&xv)[4], const uint4 dk, const uint4 wr, uint4 (&md)[6]) {
  const u32 w = tid >> 5, lane = tid & 31;
  const u32 g = lane >> 2, q = lane & 3, e = g >> 2, h = (g >> 1) & 1, hi = g & 1;
  const u32 rho = b & 1, par = (ep + 1) & 1, pm = par ? TAGM : 0;
  char* const gs = p.gs;
  const u32 cho = 128 * w + 64 * e + 16 * q, ssrc = g & 3;
  const bool own = (q >> 1) == e, sq = (q & 1) == h;
  uint4 ka, kc;
  const char* ks = gs + (G_OB + OB_KEY + (8 * g + w) * OB + q * 16);
  if (w < 9) {
    {
      const char* mp = gs + mod_off(cho >> 1);
      POLLW(_Pragma("unroll") for (int j = 0; j < 6; j++) md[j] = ldr128(mp + j * MODJ),
            ((md[0].x ^ pm) | (md[1].x ^ pm) | (md[2].x ^ pm) | (md[3].x ^ pm) | (md[4].x ^ pm) | (md[5].x ^ pm)) & TAGM, 4);
    }
    const u32 saw[4] = {md[0].x & ~TAGM, md[0].y, md[0].z, md[0].w}, caw[4] = {md[1].x & ~TAGM, md[1].y, md[1].z, md[1].w};
    const u32 gaw[4] = {md[2].x & ~TAGM, md[2].y, md[2].z, md[2].w}, sbw[4] = {md[3].x & ~TAGM, md[3].y, md[3].z, md[3].w};
    const u32 cbr[4] = {md[4].x & ~TAGM, md[4].y, md[4].z, md[4].w}, dw[4] = {dk.x, dk.y, dk.z, dk.w};
    const u32 gbw[4] = {md[5].x & ~TAGM, md[5].y, md[5].z, md[5].w};
    const char* ysrc = gs + (G_Y + b * 18432 + tid * 16 + w * 1536);
    uint4 yv[4];
    if (w < 4) {
#pragma unroll
      for (int v = 0; v < 4; v++) yv[v] = ldr128(ysrc + 512 * v);
    } else {
#pragma unroll
      for (int v = 0; v < 4; v++) yv[v].x = INVAL;
    }
    u32 hD[4][4], cb1[4], ca1[4], x1[4][4];
#pragma unroll
    for (int v = 0; v < 4; v++) { cb1[v] = bfma(cbr[v], B2P64, BONE); ca1[v] = bfma(caw[v], B2P64, BONE); }
#pragma unroll
    for (int k = 0; k < 4; k++) {
      const uint4 st = lds128(SM_ST + 16 * (4 * h + k + 8 * hi));
      const u32 xx[4] = {xv[k].x, xv[k].y, xv[k].z, xv[k].w};
#pragma unroll
      for (int v = 0; v < 4; v++) {
        const u32 d = badd(xx[v], st.x), z = bfma(d, st.y, bmul(d, st.z));
        hD[k][v] = bmul(bfma(saw[v], B2P64, bmul(z, ca1[v])), dw[v]);
      }
    }
    u32 rb0, rb1;
    {
      const u32 c0 = hi ? cb1[1] : cb1[0], c2 = hi ? cb1[3] : cb1[2], w0 = hi ? wr.y : wr.x, w2 = hi ? wr.w : wr.z;
      const u32 H0 = bmul(c0, w0), H1 = bmul(c2, w2);
      const u32 L0 = bfma(c0, w0, H0 ^ 0x80008000u), L1 = bfma(c2, w2, H1 ^ 0x80008000u);
      rb0 = __shfl_xor_sync(~0u, h ? L0 : H0, 16); rb1 = __shfl_xor_sync(~0u, h ? L1 : H1, 16);
    }
    const u32 spw = SM_SP + (2 * w + e) * 320 + ssrc * 16 + (own ? (sq ? 4 : 0) : 8 + 4 * (q & 1));
    TS(18);
    if (w >= 4) bsync(13, 288);
    POLLW(_Pragma("unroll") for (int v = 0; v < 4; v++) if ((yv[v].x ^ pm) & TAGM) yv[v] = ldr128(ysrc + 512 * v),
          ((yv[0].x ^ pm) | (yv[1].x ^ pm) | (yv[2].x ^ pm) | (yv[3].x ^ pm)) & TAGM, 5);
    TS(19);
#pragma unroll
    for (int k = 0; k < 4; k++) {
      const u32 xx[4] = {xv[k].x, xv[k].y, xv[k].z, xv[k].w};
#pragma unroll
      for (int v = 0; v < 4; v++) {
        const u32 yw = k == 0 ? yv[v].x & ~TAGM : k == 1 ? yv[v].y : k == 2 ? yv[v].z : yv[v].w;
        x1[k][v] = bfma(bmul(gaw[v], bfma(movm(yw), B2P64, hD[k][v])), B2P64, xx[v]);
      }
      float s[4] = {}, X[4] = {}, Y[4] = {}, R[4] = {};
      mma8_bf(X, x1[k][0], x1[k][1], x1[k][0]); mma8_bf(Y, x1[k][0], x1[k][1], x1[k][1]);
      mma_bf(s, x1[k][0], x1[k][1], x1[k][2], x1[k][3], BONE, BONE);
      mma_bf(R, x1[k][0], x1[k][1], x1[k][2], x1[k][3], rb0, rb1);
      mma8_bf(X, x1[k][2], x1[k][3], x1[k][2]); mma8_bf(Y, x1[k][2], x1[k][3], x1[k][3]);
      const float u0 = hi ? X[1] : X[0], u1 = hi ? Y[3] : Y[2], u2 = own ? s[0] : R[0], u3 = own ? s[2] : R[3];
      const bool dg = own && sq;
      sts32(spw + k * 64, fu((dg ? u0 : u2) + (dg ? u1 : u3)));
    }
    TS(36);
    bsync(1, 320);
    TS(37);
    float S1 = 0.f, S2 = 0.f, S3 = 0.f, S4 = 0.f;
    const u32 spr = SM_SP + (lane >> 4) * 9 * 320 + (lane & 15) * 16;
#pragma unroll
    for (int i = 0; i < 9; i++) { uint4 t = lds128(spr + i * 320); S1 += uf(t.x); S2 += uf(t.y); S3 += uf(t.z); S4 += uf(t.w); }
    const uint2 rc = lds64(SM_RC);
    if (w < 8) { ka = ldr128(ks); kc = ldr128(ks + 64 * OB); }
    S3 += S4;
    S1 += __shfl_xor_sync(~0u, S1, 16); S2 += __shfl_xor_sync(~0u, S2, 16); S3 += __shfl_xor_sync(~0u, S3, 16);
    const float mu = S1 * (1.f / 576.f), var = fmaxf(fmaf(-mu, mu, S2 * (1.f / 576.f)), 0.f);
    const float m = rbf(mu), rs = rcpf(rbf(sqrta(rbf(rbf(var) + 1e-5f))));
    if (w == 8) {
      const u32 rb_ = pk_bf(0.f, fmaf(fmaf(-m, uf(rc.x), S3), rs, uf(rc.y)) + 0.f) & 0xffff0000u;
      const u32 tl = 4 * ((lane >> 1) & 1) + ((lane >> 2) & 3) + 8 * (lane & 1);
      if (lane < 16) str32(gs + (G_OB + b * OB + OB_KEY + 4 * tl), rb_ | (par * 0x1800u));
      TS(20);
      const u32 ok = ((rb_ ^ (((int)rb_ >> 31) | 0x80000000)) & 0xffff0000u) | (15 - tl);
      sts32(SM_KEY + 4 * (lane & 15), ok);
      sts128(SM_THR + 32, ~0u, ~0u, ~0u, ~0u);
      __syncwarp();
      const uint4 o0 = lds128(SM_KEY + 2 * (lane & 16)), o1 = lds128(SM_KEY + 2 * (lane & 16) + 16);
      u32 lr = (o0.x > ok) + (o0.y > ok) + (o0.z > ok) + (o0.w > ok) + (o1.x > ok) + (o1.y > ok) + (o1.z > ok) + (o1.w > ok);
      lr += __shfl_xor_sync(~0u, lr, 16);
      const u32 so = tl * ROW + (tl >> 3) * 64;
      sts64(SM_TOK + 8 * lr, tl * 1152, so);
      sts128(SM_HS + 1152 + so, pm, rb_ | (16 * b + tl), 0, 0);
      const u32 below = (int)rb_ > 0 ? rb_ - 0x10000u : (rb_ + 0x10000u) | 0x80000000u;
      if (lr < 8) sts16(SM_THR + (lane & 16) + 2 * lr, (lane & 16 ? below : rb_) >> 16);
    }
    const float rh = rbf(rs);
    const u32 nm_ = pk_bf(-m, rh), rL_ = pk_bf(rs - rh, rs - rh);
    const u32 so = (4 * h + 8 * hi) * ROW + 64 * hi + cho;
#pragma unroll
    for (int k = 0; k < 4; k++) {
      const u32 t = __shfl_sync(~0u, nm_, 4 * k + ssrc), rL = __shfl_sync(~0u, rL_, 4 * k + ssrc);
      const u32 nm = __byte_perm(t, t, 0x1010), rH = __byte_perm(t, t, 0x3232);
      u32 h2[4], o[4];
#pragma unroll
      for (int v = 0; v < 4; v++) {
        const u32 d = badd(x1[k][v], nm), z = bfma(d, rH, bmul(d, rL));
        h2[v] = bfma(sbw[v], B2P64, bmul(z, cb1[v]));
        o[v] = bfma(bmul(gbw[v], h2[v]), B2P64, x1[k][v]);
      }
      sts128(SM_HS + so + k * ROW, bmul(h2[0], B2M64) | pm, h2[1], h2[2], h2[3]);
      sts128(SM_X1S + so + k * ROW, bmul(x1[k][0], B2M64) | pm, x1[k][1], x1[k][2], x1[k][3]);
      sts128(SM_OS + so + k * ROW, o[0], o[1], o[2], o[3]);
    }
    asm volatile("fence.proxy.async.shared::cta;" ::: "memory");
    bsync(2, 288);
    TS(21);
  }
  if (w < 8) {
    const uint2 tk = lds64(SM_TOK + 8 * w), tk8 = lds64(SM_TOK + 64 + 8 * w);
    const u32 ba = 8 * g + w;
    const uint4 ta = lds128(SM_THR + (ba < b ? 16 : ba == b ? 32 : 0)), tc = lds128(SM_THR + (ba + 64 < b ? 16 : ba + 64 == b ? 32 : 0));
    const u32 l2 = lane < 9 ? lane * 16 + 1024 : 0;
    const uint4 h0 = lds128(SM_HS + tk.y + lane * 16), h1 = lds128(SM_HS + 512 + tk.y + lane * 16), h2 = lds128(SM_HS + tk.y + l2);
    char* const ob = p.out + b * 18432;
    if (lane == 0) bulk_out(ob + tk8.x, SM_OS + tk8.y);
    const u32 kt = par * 0x1800u;
    POLLW({ ka = ldr128(ks); kc = ldr128(ks + 64 * OB); }, ((ka.x ^ kt) | (kc.x ^ kt)) & 0x1800u, 6);
    TS(23);
    u32 n[4] = {0x43004300u, 0x43004300u, 0x43004300u, 0x43004300u};
    const u32 kk[8] = {ka.x, ka.y, ka.z, ka.w, kc.x, kc.y, kc.z, kc.w};
#pragma unroll
    for (int j = 0; j < 8; j++) {
      const u32 s = __byte_perm(kk[j], kk[j], 0x3232);
      const uint4 t = j < 4 ? ta : tc;
      n[0] = badd(n[0], bsetgt(s, t.x)); n[1] = badd(n[1], bsetgt(s, t.y)); n[2] = badd(n[2], bsetgt(s, t.z)); n[3] = badd(n[3], bsetgt(s, t.w));
    }
    sts128(SM_CNT + 16 * w, __reduce_add_sync(~0u, n[0]), __reduce_add_sync(~0u, n[1]), __reduce_add_sync(~0u, n[2]), __reduce_add_sync(~0u, n[3]));
    TS(38);
    bsync(3, 256);
    const u32 cw = lds32(SM_CNT + 16 * (lane & 7) + 2 * (w & 6));
    const u32 tot = __reduce_add_sync(~0u, lane < 8 ? cw : 0) - 0x00430000u;
    const u32 rank = w + ((w & 1) ? tot >> 16 : tot & 0xffff);
    if (rank < 8) {
      char* dst = gs + (G_XS + rank * ROW + lane * 16);
      str128(dst, h0.x, h0.y, h0.z, h0.w); str128(dst + 512, h1.x, h1.y, h1.z, h1.w);
      if (lane < 9) str128(dst + 1024, h2.x, h2.y, h2.z, h2.w);
      const uint4 x0 = lds128(SM_X1S + tk.y + lane * 16), x1 = lds128(SM_X1S + 512 + tk.y + lane * 16), x2 = lds128(SM_X1S + tk.y + l2);
      str128(dst + 8 * ROW, x0.x, x0.y, x0.z, x0.w); str128(dst + (8 * ROW + 512), x1.x, x1.y, x1.z, x1.w);
      if (lane < 8) str128(dst + (8 * ROW + 1024), x2.x, x2.y, x2.z, x2.w);
    } else if (lane == 0) bulk_out(ob + tk.x, SM_OS + tk.y);
    if (w == 0) barrive(6, 160);
    TS(24);
    bsync(5, 288);
  } else {
    mb_wait(SM_MB + 16); mb_wait(SM_MB + 24);
    if (w == 9) barrive(5, 288);
  }
  const u32 kq = w & 3, tg = 2 - (w >> 2);
  uint4 A[2][9];
  {
    const u32 aa = ((lane & 8) ? SM_UP : SM_GATE) + (144 * kq + 8 * (lane >> 4) + (lane & 7)) * 80 + tg * 32;
#pragma unroll
    for (int s = 0; s < 9; s++) A[0][s] = ldsm4t(aa + s * 1280);
    if (tg < 2) {
#pragma unroll
      for (int s = 0; s < 9; s++) A[1][s] = ldsm4t(aa + s * 1280 + 16);
    }
  }
  TS(22);
  if (w >= 8) {
    const u32 t = (tid - 256) * 16;
    const char* xs = gs + (G_XS + t);
    uint4 v[5];
#pragma unroll
    for (int j = 0; j < 5; j++) v[j].x = INVAL;
    if (t >= 72 * 16) v[4].x = pm;
    bsync(6, 160);
    POLL(_Pragma("unroll") for (int j = 0; j < 5; j++) if ((v[j].x ^ pm) & TAGM) v[j] = ldr128(xs + j * 2048),
         ((v[0].x ^ pm) | (v[1].x ^ pm) | (v[2].x ^ pm) | (v[3].x ^ pm) | (v[4].x ^ pm)) & TAGM, 8);
#pragma unroll
    for (int j = 0; j < 5; j++) if (j < 4 || t < 72 * 16) sts128(SM_XS + t + j * 2048, bmul(v[j].x & ~TAGM, B2P64), v[j].y, v[j].z, v[j].w);
  }
  __syncthreads();
  TS(25);
  {
    float c0[2][4] = {}, c1[2][4] = {};
    const u32 ba = SM_XS + (lane & 7) * ROW + (18 * kq + (lane >> 3)) * 16;
    uint4 bb[5];
#pragma unroll
    for (int s = 0; s < 5; s++) bb[s] = ldsm4(ba + s * 64);
#pragma unroll
    for (int s = 0; s < 9; s++) mma_bf(c0[s & 1], A[0][s].x, A[0][s].y, A[0][s].z, A[0][s].w, s & 1 ? bb[s >> 1].z : bb[s >> 1].x, s & 1 ? bb[s >> 1].w : bb[s >> 1].y);
    const u32 ra = SM_RED + (8 * tg + kq) * 512 + lane * 16;
    if (tg < 2) {
#pragma unroll
      for (int s = 0; s < 9; s++) mma_bf(c1[s & 1], A[1][s].x, A[1][s].y, A[1][s].z, A[1][s].w, s & 1 ? bb[s >> 1].z : bb[s >> 1].x, s & 1 ? bb[s >> 1].w : bb[s >> 1].y);
      sts128(ra + 2048, fu(c1[0][0] + c1[1][0]), fu(c1[0][1] + c1[1][1]), fu(c1[0][2] + c1[1][2]), fu(c1[0][3] + c1[1][3]));
    }
    sts128(ra, fu(c0[0][0] + c0[1][0]), fu(c0[0][1] + c0[1][1]), fu(c0[0][2] + c0[1][2]), fu(c0[0][3] + c0[1][3]));
  }
  TS(39);
  __syncthreads();
  if (w < 5 - rho) {
    float s[4] = {};
#pragma unroll
    for (int i = 0; i < 4; i++) { const uint4 t = lds128(SM_RED + (w * 4 + i) * 512 + lane * 16); s[0] += uf(t.x); s[1] += uf(t.y); s[2] += uf(t.z); s[3] += uf(t.w); }
    const u32 sg = pk_bf(silu_f(rbf(s[0])), silu_f(rbf(s[1])));
    const u32 act = movm(bmul(bmul(sg, pk_bf(s[2], s[3])), B2M64));
    str32(gs + (G_OB + OB_ACT + b * OB + tid * 4), act | (q ? 0 : pm));
  }
  TS(26);
  if (w >= 9) {
    if (w == 9) { mb_wait(SM_MB + 32); barrive(7, 192); }
    return;
  }
  {
    const u32 ul = tid >> 3, pr = ul / 9, r9 = ul - 9 * pr;
    const char* src = gs + (G_OB + OB_ACT + ((b & ~7u) + 2 * pr) * OB + (r9 < 5 ? r9 * 128 : OB + (r9 - 5) * 128) + (tid & 7) * 16);
    uint4 a = ldr128(src);
    if (w < 5) {
      const u32 aa = SM_WD + (8 * (lane >> 4) + (lane & 7)) * 144 + (2 * w + ((lane >> 3) & 1)) * 16;
      bsync(7, 192);
#pragma unroll
      for (int s = 0; s < 9; s++) { A[0][s] = ldsm4t(aa + s * 4608); A[1][s] = ldsm4t(aa + s * 4608 + 2304); }
    }
    TS(28);
    POLLW(a = ldr128(src), (a.x ^ pm) & TAGM, 9);
    sts128(SM_AC + tid * 16, a.x & ~TAGM, a.y, a.z, a.w);
  }
  TS(27);
  if (w < 5) {
    bsync(8, 288);
    float c[4][4] = {};
#pragma unroll
    for (int s = 0; s < 9; s++) {
      const uint4 bb = ldsm4(SM_AC + lane * 16 + s * 512);
      mma_bf(c[2 * (s & 1)], A[0][s].x, A[0][s].y, A[0][s].z, A[0][s].w, bb.x, bb.y);
      mma_bf(c[2 * (s & 1) + 1], A[1][s].x, A[1][s].y, A[1][s].z, A[1][s].w, bb.z, bb.w);
    }
    char* dst = gs + (G_OB + OB_PART + b * OB + w * 512 + lane * 8);
    u32 o[4];
#pragma unroll
    for (int i = 0; i < 4; i++) o[i] = (fu(((c[0][i] + c[1][i]) + (c[2][i] + c[3][i])) * F2P64) & ~1u) | par;
    str64(dst, o[0], o[1]);
    if (w < 4) str64(dst + 256, o[2], o[3]);
    TS(29);
  } else {
    barrive(8, 288);
    if (w == 8 && b < 72) {
      const u32 kg = lds32(SM_XS + 1156 + g * ROW), cg = b / 9;
      const char* src = gs + (G_OB + OB_PART + cg * OB + (b - 9 * cg) * 256 + lane * 8);
      const char* xs = gs + (G_X1 + g * ROW + b * 16);
      uint4 xt;
      POLL(xt = ldr128(xs), (xt.x ^ pm) & TAGM, 10);
      const u32 x1w = (q & 2) ? ((q & 1) ? xt.w : xt.z) : ((q & 1) ? xt.y : bmul(xt.x & ~TAGM, B2P64));
      const u32 gw = ldr32(gs + (mod_off(8 * b) + 5 * MODJ + 4 * q)) & ~TAGM;
      const u32 hw = lds32(SM_XS + g * ROW + b * 16 + q * 4);
      const float sgm = rcpf(1.f + ex2(-LOG2E * bhi(kg)));
      char* const dst = p.out + ((kg & 2047) * 1152 + 16 * b + 4 * q);
      uint2 v[16];
#pragma unroll
      for (int j = 0; j < 16; j++) v[j] = make_uint2(1, 0);
      u32 bad;
      POLL({ bad = 0; _Pragma("unroll") for (int j = 0; j < 16; j++) { if (((v[j].x ^ par) | (v[j].y ^ par)) & 1) v[j] = ldr64(src + j * 8 * OB); }
             _Pragma("unroll") for (int j = 0; j < 16; j++) bad |= (v[j].x ^ par) | (v[j].y ^ par); }, bad & 1, 11);
      float s0[4] = {}, s1[4] = {};
#pragma unroll
      for (int j = 0; j < 16; j++) { s0[j & 3] += uf(v[j].x); s1[j & 3] += uf(v[j].y); }
      const u32 y = movm(pk_bf((s0[0] + s0[1]) + (s0[2] + s0[3]), (s1[0] + s1[1]) + (s1[2] + s1[3])));
      *(u32*)dst = bfma(bmul(gw, badd(hw, bmul(y, pk_bf(sgm, sgm)))), B2P64, x1w);
      if (b == 0 && lane == 0) str32(gs + G_EP, ep + 1);
      TS(30);
    }
  }
  if (lane == 0) {
    asm volatile("cp.async.bulk.commit_group;" ::: "memory");
    asm volatile("cp.async.bulk.wait_group.read 0;" ::: "memory");
  }
}

__global__ void __launch_bounds__(384, 1)
fused_kernel(const Prm p, const __grid_constant__ CUtensorMap tm_mod, const __grid_constant__ CUtensorMap tm_gate,
             const __grid_constant__ CUtensorMap tm_up, const __grid_constant__ CUtensorMap tm_down) {
  extern __shared__ __align__(1024) unsigned char smem[];
  uint4 xv[4];
  {
    const u32 t = threadIdx.x;
    if (t < 288) {
      const char* xp = p.x + (blockIdx.x * 18432 + (t >> 5) * 128 + (t & 16) * 4 + (t & 3) * 16 + ((t & 8) * 576 + (t & 4) * 288));
#pragma unroll
      for (int k = 0; k < 4; k++) xv[k] = ldg128(xp + (2 * (k >> 1) + 8 * (k & 1)) * 1152);
    }
  }
  const u32 tid = __shfl_sync(~0u, threadIdx.x, threadIdx.x & 31), b = __shfl_sync(~0u, blockIdx.x, 0);
  const u32 w = tid >> 5, lane = tid & 31;
  const u32 g = lane >> 2, q = lane & 3, e = g >> 2, h = (g >> 1) & 1, hi = g & 1;
  const u32 rho = b & 1, Pm = 9 * (b >> 1) + 5 * rho, Ps = 9 * (b >> 1) + 4;
  char* const gs = p.gs;
  TS0();
  const u32 cho = 128 * w + 64 * e + 16 * q;
  const bool kw = (w >> 1) != 4;
  const u32 ksig = w < 8 ? (w & 3) : 4, khf = w < 8 ? (w >> 2) : (w & 1);
  u32 la, ai, ldt; uint2 cr, ci;
  {
    const u32 d = chan_of(w < 8 ? Pm + ksig : Ps), o = d * 256 + 8 * lane;
    const char* cp = p.c + (576 * (w & 1) + 24 * min(lane, 23u));
    la = ldg32(kw ? p.la + (o + 4 * khf) : cp); ai = ldg32(kw ? p.ai + (o + 4 * khf) : cp + 4);
    cr = ldg64(kw ? p.cr + o : cp + 8); ci = ldg64(kw ? p.ci + o : cp + 16); ldt = ldg16(p.ldt + 2 * d);
  }
  const u32 zr = tid >> 16;
  const u32 epv = ldr32(gs + (G_EP + zr));
  if (tid == 288) {
#pragma unroll
    for (int i = 0; i < 5; i++) mb_init(SM_MB + 8 * i);
    asm volatile("fence.mbarrier_init.release.cluster;" ::: "memory");
    tma3d(SM_UP, &tm_mod, SM_MB, 18432, 16 * b, 0);
    if (b < 88) tma3d(SM_UP + 18432, &tm_mod, SM_MB + 8, 18432, 16 * b + 2048, 0);
    tma3d(SM_GATE, &tm_gate, SM_MB + 16, 46080, 8 * Pm, 0);
    asm volatile("prefetch.tensormap [%0];" ::"l"((uint64_t)&tm_up) : "memory");
    asm volatile("prefetch.tensormap [%0];" ::"l"((uint64_t)&tm_down) : "memory");
  }
#pragma unroll 1
  for (u32 i = SM_ZS + tid * 16; i < SM_MB; i += 384 * 16) sts128(i, 0, 0, 0, 0);
  __syncthreads();
  TS(1);
  char* const zdst = gs + (b * 18432 + tid * 16 + w * 1536);
  if (w < 9) {
#pragma unroll
    for (int v = 0; v < 4; v++) str128(zdst + 512 * v, INVAL, 0, 1, 0);
    str128(gs + (G_Y + 96 * 18432 + (w < 8 ? (tid >> 3) * 18432 + Pm * 32 + (tid & 7) * 16 : (16 * rho + (lane >> 1)) * 18432 + Ps * 32 + (lane & 1) * 16)), INVAL, 0, 1, 0);
  }
  {
    const u32 t = 383 - tid;
    if (t < 192 || (t < 208 && b < 73) || (t >= 224 && t < (b < 88 ? 228 : 226)))
      str128(gs + (t < 192 ? G_OB + b * OB + t * 16 : t < 208 ? G_XS + b * 256 + (t & 15) * 16 : G_MOD + b * 128 + (t & 2) * 8192 + (t & 1) * 16), INVAL, 0, 1, 0);
  }
  const u32 ep = __reduce_or_sync(~0u, epv), par = (ep + 1) & 1, pm = par ? TAGM : 0;
  const bool own = (q >> 1) == e, sq = (q & 1) == h;
  const u32 ssrc = g & 3;
  if (w < 9) {
    const u32 spw = SM_SP + (2 * w + e) * 160 + ssrc * 8 + (sq ? 4 : 0);
#pragma unroll
    for (int k = 0; k < 4; k++) {
      float s[4] = {}, X[4] = {}, Y[4] = {};
      mma8_bf(X, xv[k].x, xv[k].y, xv[k].x); mma8_bf(Y, xv[k].x, xv[k].y, xv[k].y);
      mma_bf(s, xv[k].x, xv[k].y, xv[k].z, xv[k].w, BONE, BONE);
      mma8_bf(X, xv[k].z, xv[k].w, xv[k].z); mma8_bf(Y, xv[k].z, xv[k].w, xv[k].w);
      const float u0 = hi ? X[1] : X[0], u1 = hi ? Y[3] : Y[2];
      const float v = (sq ? u0 : s[0]) + (sq ? u1 : s[2]);
      if (own) sts32(spw + k * 32, fu(v));
    }
    TS(4);
    bsync(1, 288);
    TS(7);
    float S1 = 0.f, S2 = 0.f;
    const u32 spr = SM_SP + (lane >> 4) * 9 * 160 + (lane & 15) * 8;
#pragma unroll
    for (int i = 0; i < 9; i++) { uint2 t = lds64(spr + i * 160); S1 += uf(t.x); S2 += uf(t.y); }
    S1 += __shfl_xor_sync(~0u, S1, 16); S2 += __shfl_xor_sync(~0u, S2, 16);
    const float mu = S1 * (1.f / 576.f), var = fmaxf(fmaf(-mu, mu, S2 * (1.f / 576.f)), 0.f);
    const float m = rbf(mu), rs = rcpf(rbf(sqrta(rbf(rbf(var) + 1e-5f))));
    const float ra = rs * 0.0625f, rc = -m * ra;
    u32 zt[4][4];
#pragma unroll
    for (int k = 0; k < 4; k++) {
      const float a = __shfl_sync(~0u, ra, 4 * k + ssrc), c = __shfl_sync(~0u, rc, 4 * k + ssrc);
      const u32 xx[4] = {xv[k].x, xv[k].y, xv[k].z, xv[k].w};
#pragma unroll
      for (int v = 0; v < 4; v++) zt[v][k] = movm(pk_hf(fmaf(blo(xx[v]), a, c), fmaf(bhi(xx[v]), a, c)));
    }
#pragma unroll
    for (int v = 0; v < 4; v++) str128(zdst + 512 * v, zt[v][0] | pm, zt[v][1], zt[v][2], zt[v][3]);
    if (w == 8) {
      const float rh = rbf(rs);
      sts128(SM_ST + 16 * (4 * ((lane >> 1) & 1) + ((lane >> 2) & 2) + 2 * (lane & 4) + (lane & 1)), pk_bf(-m, -m), pk_bf(rh, rh), pk_bf(rs - rh, rs - rh), 0);
    }
  }
  TS(5);
  if (kw) {
    const u32 ktab = SM_R + (w < 8 ? w : w - 2) * KTAB;
    u32 mx = __vmaxu2(__vmaxu2(cr.x & 0x7fff7fff, cr.y & 0x7fff7fff), __vmaxu2(ci.x & 0x7fff7fff, ci.y & 0x7fff7fff));
    const u32 E = max(__reduce_max_sync(~0u, max(mx & 0xffff, mx >> 16)) >> 7, 8u);
    const float dt = rbf(ex2(blo(ldt) * LOG2E)), csc = uf((258 - E) << 23);
    const float FK = 2.f * dt * uf((E - 4) << 23);
    const u32 crw = khf ? cr.y : cr.x, ciw = khf ? ci.y : ci.x;
    float k2048 = 0.f;
    {
      float2 C[2], w4[2], w8[2], w16[2], w32[2], w64[2], w128[2], w256[2], w512[2], a1[2], a2[2], a3[2], t0[2], t1[2], s3[2];
#pragma unroll
      for (int m = 0; m < 2; m++) {
        const float lr2 = rbf(ex2((m ? bhi(la) : blo(la)) * LOG2E)) * dt * -LOG2E, th = (m ? bhi(ai) : blo(ai)) * dt;
        C[m] = make_float2((m ? bhi(crw) : blo(crw)) * csc, (m ? bhi(ciw) : blo(ciw)) * csc);
        const float2 w1 = cexp(lr2, th), w2 = csq(w1);
        w64[m] = cexp(64.f * lr2, 64.f * th);
        w4[m] = csq(w2); w8[m] = csq(w4[m]); w16[m] = csq(w8[m]); w32[m] = csq(w16[m]);
        w128[m] = csq(w64[m]); w256[m] = csq(w128[m]); w512[m] = csq(w256[m]);
        const float2 w1024 = csq(w512[m]);
        a1[m] = cmul(C[m], w1); a2[m] = cmul(C[m], w2); a3[m] = cmul(a1[m], w2);
        t0[m] = cmul(C[m], w1024); t1[m] = cmul(t0[m], w128[m]); s3[m] = cmul(w8[m], w16[m]);
        k2048 += fmaf(t0[m].x, w1024.x, -t0[m].y * w1024.y);
      }
      C2 B0[8], B1[8], B2[8], S[8];
      B0[0] = pk2(C); B0[1] = pk2(a1); B0[2] = pk2(a2); B0[3] = pk2(a3);
      const C2 h4 = pk2(w4), h256 = pk2(w256), h512 = pk2(w512);
#pragma unroll
      for (int i = 0; i < 4; i++) B0[4 + i] = cm2(B0[i], h4);
#pragma unroll
      for (int i = 0; i < 4; i++) B1[i] = cm2(B0[2 * i], h256);
      B1[4] = cm2(B0[0], h512); B1[5] = cm2(B0[4], h512);
      B1[6] = cm2(B1[4], h256); B1[7] = cm2(B1[5], h256);
      const u32 ta = ktab + lane * 128, f = ((lane & 3) << 5) | ((lane & 4) << 2);
#pragma unroll
      for (int i = 0; i < 8; i++) sts128(ta + ((i << 4) ^ f), B0[i].re, B0[i].im, B1[i].re, B1[i].im);
      B2[0] = pk2(t0); B2[1] = pk2(t1);
      B2[2] = cm2(B2[0], h256); B2[3] = cm2(B2[1], h256);
#pragma unroll
      for (int i = 0; i < 4; i++) B2[4 + i] = cm2(B2[i], h512);
      S[0] = {0x3C003C00u, 0u}; S[1] = pk2c(w8); S[2] = pk2c(w16); S[3] = pk2c(s3); S[4] = pk2c(w32);
#pragma unroll
      for (int i = 1; i < 4; i++) S[4 + i] = cm2(S[i], S[4]);
#pragma unroll
      for (int i = 0; i < 8; i++) sts128(ta + 4096 + ((i << 4) ^ f), B2[i].re, B2[i].im, S[i].re, S[i].im);
      const C2 m64 = pk2c(w64), m128 = pk2c(w128);
      sts128(ktab + 8192 + lane * 16, m64.re, m64.im, m128.re, m128.im);
    }
    __syncwarp();
    TS(2);
    float D[5][4] = {};
    u32 ta = ktab + q * 128 + ((g ^ (q << 1)) << 4), tm = ktab + 8192 + q * 16;
#pragma unroll 2
    for (int s = 0; s < 8; s++) {
      const uint4 ca = lds128(ta), cb = lds128(ta + 4096), ma = lds128(tm);
      ta = (ta + 512) ^ 16; tm += 64;
      k2048 += __shfl_xor_sync(~0u, k2048, 16 >> s);
      const C2 s0 = {cb.z, cb.w}, s1 = cm2(s0, {ma.x, ma.y}), s2 = cm2(s0, {ma.z, ma.w}), s3 = cm2(s1, {ma.z, ma.w});
      mma_hf(D[0], s0.re, s1.re, s0.im, s1.im, ca.x, ca.y);
      mma_hf(D[2], s0.re, s1.re, s0.im, s1.im, ca.z, ca.w);
      mma_hf(D[4], s0.re, s1.re, s0.im, s1.im, cb.x, cb.y);
      mma_hf(D[1], s2.re, s3.re, s2.im, s3.im, ca.x, ca.y);
      mma_hf(D[3], s2.re, s3.re, s2.im, s3.im, ca.z, ca.w);
    }
    TS(3);
    const u32 xa = SM_R + (w < 8 ? 4 + ksig : 9) * KTAB + lane * 16;
    if (khf) {
      __syncwarp();
#pragma unroll
      for (int j = 0; j < 5; j++) sts128(xa + 512 * j, fu(D[j][0]), fu(D[j][1]), fu(D[j][2]), fu(D[j][3]));
      if (lane == 0) sts32(xa + 2560, fu(k2048));
      asm volatile("bar.arrive %0,64;" ::"r"(2 + ksig) : "memory");
    } else {
      const u32 tp = SM_TAP + ksig * TAPS;
      const u32 a = 63 + 32 * q + g;
      const u32 t1 = tp + (q < 2 ? (128 + 4 * g + 2 * q) * 4 : T5 * 4 + (a - 64 + 2 * (a & 1)) * 2);
      const u32 x = 63 + hi + 16 * q + (g >> 1), tb = tp + (hi ? TE7 : TE9) * 4;
      const u32 te = tb + (x + 2 * (x & 1)) * 2, to = tb + TEO * 4 + (x ^ 1) * 2;
      asm volatile("bar.sync %0,64;" ::"r"(2 + ksig) : "memory");
#pragma unroll
      for (int j = 0; j < 5; j++) { const uint4 t = lds128(xa + 512 * j); D[j][0] += uf(t.x); D[j][1] += uf(t.y); D[j][2] += uf(t.z); D[j][3] += uf(t.w); }
      k2048 = (k2048 + uf(lds32(xa + 2560))) * 0.125f;
      const float kv512 = __shfl_sync(~0u, D[2][0], 2);
      if (lane == 29) D[3][3] -= kv512;
#pragma unroll
      for (int r = 0; r < 4; r++) {
        const u32 v = pk_hf(D[2 + (r >> 1)][2 * (r & 1)], D[2 + (r >> 1)][2 * (r & 1) + 1]);
        if (q < 2) {
          const u32 vv = __byte_perm(v, v, 0x1010);
          sts32(t1 + (TO + 32 * r) * 4, vv); sts16(t1 + (TO + 32 * r + 1) * 4 + 2, v >> 16); sts16(t1 + (TO + 32 * r - 1) * 4, v);
          sts64(t1 + (TE + 32 * r) * 4, vv, __byte_perm(v, v, 0x1032));
        } else {
          sts16(t1 + 16 * r, v); sts16(t1 + 16 * r + (T3 - T5) * 4, v >> 16);
        }
      }
#pragma unroll
      for (int r = 0; r < 2; r++) {
        const u32 v = pk_hf(D[4][2 * r], D[4][2 * r + 1]);
        if (r == 0 && lane == 0) { sts16(tp + T5 * 4 + 129 * 2, v); sts32(SM_KV + 4 * ksig, v & 0xffff); sts16(tb + TEO * 4 + 126 * 2, pk_hf(k2048, 0.f)); sts32(SM_SC + 16 * ksig + 12, fu(FK)); }
        else { sts16(te + 8 * r, v); sts16(to + 8 * r, v); }
        sts16(te + 8 * r + 16, v >> 16); sts16(to + 8 * r + 16, v >> 16);
      }
      __syncwarp();
#pragma unroll
      for (int r = 0; r < 4; r++) {
        const u32 v = pk_hf(D[r >> 1][2 * (r & 1) + 1], D[r >> 1][2 * (r & 1)]), t2 = tp + lane * 4 + 128 * r;
        sts32(t2 + TO * 4, v); sts16(t2 + TE * 4, v >> 16); sts16(t2 + (TE + 1) * 4 + 2, v);
      }
      __syncwarp();
    }
  } else {
    u32 sa = SM_SIL + 576 * (w & 1) + 24 * min(lane, 23u);
#pragma unroll 1
    for (int j = 0; j < 6; j++) {
      sts32(sa, pk_bf(silu_f(blo(la)), silu_f(bhi(la))));
      la = ai; ai = cr.x; cr.x = cr.y; cr.y = ci.x; ci.x = ci.y; sa += 4;
    }
    __syncwarp();
  }
  TS(6);
  const u32 rl16 = ((lane & 7) + ((lane >> 3) & 1) + 8 * (lane >> 4)) * 16;
  const u32 zl = g * 16 + (q & 1) * 8;
  const u32 tko = (4 * h + 8 * hi) * 1152 + cho + b * 18432;
  uint4 dk, wr, md[6];
#define P2LOAD() { \
    const char* mp_ = gs + mod_off(cho >> 1); \
    _Pragma("unroll") for (int j = 0; j < 6; j++) md[j] = ldr128(mp_ + j * MODJ); \
    _Pragma("unroll") for (int k = 0; k < 4; k++) xv[k] = ldg128(p.x + tko + k * 1152); \
    dk = ldg128(p.dsk + cho); wr = ldg128(p.wr + cho); }
  if (w < 4) {
    asm volatile("setmaxnreg.inc.sync.aligned.u32 232;");
    const u32 tp = SM_TAP + w * TAPS;
    const u32 tr = tp + ((hi ? TO : TE) + (g >> 1) - q) * 4;
    u32 T[33][4], B5[5][2], B3[5][2];
    const u32 pml = (ssrc | zr) ? 0 : pm;
#pragma unroll
    for (int d = 0; d < 33; d++) {
      T[d][0] = lds32(tr + 32 * d); T[d][1] = lds32(tr + 32 * d + 16);
      T[d][2] = d ? cpy(T[d - 1][1], zr, 0) : zr; T[d][3] = cpy(T[d][0], zr, 1);
    }
    const u32 bt = tp + (T5 + g - q) * 4;
#pragma unroll
    for (int d = 0; d < 5; d++) {
      B5[d][0] = lds32(bt + 32 * d + 128); B5[d][1] = lds32(bt + 32 * d + 112);
      B3[d][0] = lds32(bt + 32 * d + 128 + (T3 - T5) * 4); B3[d][1] = lds32(bt + 32 * d + 112 + (T3 - T5) * 4);
    }
    u32 za = SM_ZS + 16 + w * ZSS + (q >> 1) * ZPS + zl;
    u32 wa = SM_R + W5O - 256 + w * WSL + rl16;
    u32 sa = SM_S3 - 2560 + w * 4096 + lane * 16;
    char* yp = gs + (G_Y + 2 * q * 18432 + (Pm + w) * 32 + 4 * g);
    TS(8);
    lds32(za);
    bsync(9, 384);
    TS(11);
    float A[4][4] = {};
    uint2 ring[4];
#pragma unroll
    for (int s = 0; s < 3; s++) ring[s] = lds64(za + 16 * s);
    const uint2 fc = lds64(SM_SC + 16 * w + 8);
    const float F = uf(fc.x) * uf(fc.y);
    const float ZERO[4] = {};
#define DENSE(s) { ring[(s + 3) & 3] = lds64(za + 16 * (s + 3)); \
    _Pragma("unroll") for (int i = 0; i < 4; i++) mma_hf_o(A[i], A[i], T[8 * i + 7 - s], ring[s & 3].x, ring[s & 3].y); }
#define LAST(N) ring[2] = lds64(za + 160); float O[4]; mma_hf_o(O, A[0], T[0], ring[3].x, ring[3].y); \
    _Pragma("unroll") for (int i = 0; i < 3; i++) mma_hf_o(A[i], A[i + 1], T[8 * i + 8], ring[3].x, ring[3].y); \
    mma_hf_o(A[3], N, T[32], ring[3].x, ring[3].y);
#pragma unroll 1
    for (int j = 0; j < 3; j++) {
#pragma unroll
      for (int s = 0; s < 7; s++) DENSE(s);
      LAST(ZERO);
      y_store(O[0], O[1], O[2], O[3], F, pml, yp);
      za += 128; yp += 8 * 18432;
      TS(40 + j);
    }
#pragma unroll 1
    for (int j = 3; j < 13; j++) {
#pragma unroll
      for (int s = 0; s < 5; s++) DENSE(s);
      if (j == 3) bsync(10, 384);
      if (j == 8) bsync(11, 256);
      const uint4 a5 = ldsm4t(wa), a3 = ldsm4t(wa + (W3O - W5O));
      uint4 s3 = {0, 0, 0, 0};
      if (j >= 8) s3 = lds128(sa);
      DENSE(5); DENSE(6);
      float N[4] = {};
      mma_hf(N, a5.x, a5.y, a5.z, a5.w, B5[4][0], B5[4][1]);
#pragma unroll
      for (int i = 0; i < 4; i++) mma_hf(A[i], a5.x, a5.y, a5.z, a5.w, B5[i][0], B5[i][1]);
      mma_hf(N, a3.x, a3.y, a3.z, a3.w, B3[4][0], B3[4][1]);
#pragma unroll
      for (int i = 0; i < 4; i++) mma_hf(A[i], a3.x, a3.y, a3.z, a3.w, B3[i][0], B3[i][1]);
      LAST(N);
      y_store(O[0] + uf(s3.x), O[1] + uf(s3.y), O[2] + uf(s3.z), O[3] + uf(s3.w), F, pml, yp);
      za += 128; wa += 256; sa += 512; yp += 8 * 18432;
      TS(40 + j);
    }
    TS(14);
    P2LOAD();
    {
      float X[3][4] = {};
#pragma unroll
      for (int ty = 0; ty < 2; ty++) {
        const uint4 a = ldsm4t(wa + ty * (W3O - W5O)), c = ldsm4t(wa + 256 + ty * (W3O - W5O)), d = ldsm4t(wa + 512 + ty * (W3O - W5O));
#pragma unroll
        for (int i = 0; i < 3; i++) mma_hf(A[i], a.x, a.y, a.z, a.w, ty ? B3[i][0] : B5[i][0], ty ? B3[i][1] : B5[i][1]);
#pragma unroll
        for (int i = 0; i < 2; i++) mma_hf(X[i], c.x, c.y, c.z, c.w, ty ? B3[i][0] : B5[i][0], ty ? B3[i][1] : B5[i][1]);
        mma_hf(X[2], d.x, d.y, d.z, d.w, ty ? B3[0][0] : B5[0][0], ty ? B3[0][1] : B5[0][1]);
      }
      barrive(12, 288);
#pragma unroll
      for (int s = 0; s < 8; s++) {
        const uint2 f0 = s < 3 ? ring[s] : lds64(za + 16 * s), f1 = lds64(za + 16 * s + 128), f2 = lds64(za + 16 * s + 256);
#pragma unroll
        for (int i = 0; i < 3; i++) mma_hf_o(A[i], A[i], T[8 * i + 7 - s], f0.x, f0.y);
        mma_hf_o(X[0], X[0], T[7 - s], f1.x, f1.y); mma_hf_o(X[1], X[1], T[15 - s], f1.x, f1.y);
        mma_hf_o(X[2], X[2], T[7 - s], f2.x, f2.y);
      }
      const uint4 s0 = lds128(sa), s1 = lds128(sa + 512), s2 = lds128(sa + 1024);
      y_store(A[0][0] + uf(s0.x), A[0][1] + uf(s0.y), A[0][2] + uf(s0.z), A[0][3] + uf(s0.w), F, pml, yp);
      y_store(A[1][0] + X[0][0] + uf(s1.x), A[1][1] + X[0][1] + uf(s1.y), A[1][2] + X[0][2] + uf(s1.z), A[1][3] + X[0][3] + uf(s1.w), F, pml, yp + 8 * 18432);
      y_store(A[2][0] + X[1][0] + (X[2][0] + uf(s2.x)), A[2][1] + X[1][1] + (X[2][1] + uf(s2.y)), A[2][2] + X[1][2] + (X[2][2] + uf(s2.z)), A[2][3] + X[1][3] + (X[2][3] + uf(s2.w)), F, pml, yp + 16 * 18432);
    }
    barrive(13, 288);
    TS(15);
  } else {
    asm volatile("setmaxnreg.dec.sync.aligned.u32 136;");
    const u32 t8 = tid - 128;
#pragma unroll 1
    for (int ph = 0; ph < 2; ph++) {
      if (!kw) {
        const u32 urg = b < 72;
#pragma unroll 1
        for (u32 slot = ph ? urg : 0; slot < (ph ? (b < 88 ? 2 : 1) : urg); slot++) {
          float c[2][4] = {};
          const u32 row = 288 * (w & 1) + (lane & 7) + 8 * (lane >> 4);
          u32 aa = SM_UP + slot * 18432 + row * 32 + ((((lane >> 3) ^ (row >> 2)) & 1) << 4);
          u32 ba = SM_SIL + 576 * (w & 1) + 4 * q;
          mb_wait(SM_MB + 8 * slot);
#pragma unroll 1
          for (int s = 0; s < 3; s++) {
#pragma unroll
            for (int i = 0; i < 6; i++) { const uint4 a = ldsm4t(aa + i * 512); mma_bf(c[i & 1], a.x, a.y, a.z, a.w, lds32(ba + 32 * i), lds32(ba + 32 * i + 16)); }
            aa += 3072; ba += 192;
          }
          float v = (q & 1) ? c[0][2] + c[1][2] : c[0][0] + c[1][0];
          if (w & 1) sts32(SM_GP + lane * 4, fu(v));
          bsync(7, 64);
          v += uf(lds32(SM_GP + lane * 4));
          if (!(w & 1) && q < 2) str16(gs + (G_MOD + (b + 128 * slot) * 128 + 2 * g + 16 * q), pk_bf(rbf(v) * F2M64, 0.f) | (g < 2 ? pm : 0));
          bsync(7, 64);
        }
      }
      if (ph) break;
      TS(12);
      const char* zs = gs + ((t8 >> 3) * 18432 + Pm * 32 + (t8 & 7) * 16);
      const char* zs4 = gs + ((t8 >> 1) * 18432 + Ps * 32 + (t8 & 1) * 16);
      uint4 v[5];
#pragma unroll
      for (int j = 0; j < 5; j++) v[j].x = INVAL;
      POLL(_Pragma("unroll") for (int j = 0; j < 5; j++) if ((v[j].x ^ pm) & TAGM) v[j] = ldr128(j < 4 ? zs + j * 32 * 18432 : zs4),
           ((v[0].x ^ pm) | (v[1].x ^ pm) | (v[2].x ^ pm) | (v[3].x ^ pm) | (v[4].x ^ pm)) & TAGM, 1);
      TS(9);
      if (w == 11) {
        const u32 d = chan_of(lane < 4 ? Pm + lane : Ps);
        const char* mp = gs + mod_off(d);
        uint4 ta, tc;
        POLL({ ta = ldr128(mp); tc = ldr128(mp + MODJ); }, ((ta.x ^ pm) | (tc.x ^ pm)) & TAGM, 2);
        const u32 aw = (d & 4) ? ((d & 2) ? ta.w : ta.z) : ((d & 2) ? ta.y : ta.x & ~TAGM);
        const u32 cw = (d & 4) ? ((d & 2) ? tc.w : tc.z) : ((d & 2) ? tc.y : tc.x & ~TAGM);
        const float sa = ((d & 1) ? bhi(aw) : blo(aw)) * F2P64, c1 = rbf(fmaf((d & 1) ? bhi(cw) : blo(cw), F2P64, 1.f));
        const u32 EM = min(max(fu(fmaxf(32.f * fabsf(c1), fabsf(sa))) >> 23, 80u), 250u);
        const float inv = uf((264 - EM) << 23);
        if (lane < 5) { sts64(SM_SC + 16 * lane, pk_hf(16.f * c1 * inv, 16.f * c1 * inv), pk_hf(sa * inv, sa * inv)); sts32(SM_SC + 16 * lane + 8, (EM - 74) << 23); }
        TS(10);
      }
      const u32 dst = SM_ZS + 128 + (t8 & 6) * (ZSS / 2) + (t8 & 1) * ZPS + (t8 >> 3) * 16;
      const u32 sig = t8 / 51, i0 = t8 - 51 * sig;
      bsync(8, 256);
      const uint2 cc = lds64(SM_SC + 8 * (t8 & 6)), c4 = lds64(SM_SC + 64);
#pragma unroll
      for (int j = 0; j < 5; j++) {
        const uint2 c = j < 4 ? cc : c4;
        sts128(j < 4 ? dst + j * 512 : SM_Z4 + (t8 & 1) * ZP4 + (t8 >> 1) * 16, hfma(v[j].x & ~TAGM, c.x, c.y), hfma(v[j].y, c.x, c.y), hfma(v[j].z, c.x, c.y), hfma(v[j].w, c.x, c.y));
      }
      bsync(9, 384);
      TS(11);
#pragma unroll 1
      for (int rd = 0; rd < 2; rd++) {
        const u32 i = i0 + 51 * rd;
        if (sig < 5 && i < 97) {
          const u32 za = (sig < 4 ? SM_ZS + 128 + sig * ZSS : SM_Z4) + i * 16, zb = za + (sig < 4 ? ZPS : ZP4);
          const uint4 c2 = lds128(zb - 32), a1 = lds128(za - 16), b1 = lds128(zb - 16), a0 = lds128(za), b0 = lds128(zb);
          const u32 P[17] = {c2.y, c2.w, a1.x, a1.z, b1.x, b1.z, a1.y, a1.w, b1.y, b1.w, a0.x, a0.z, b0.x, b0.z, a0.y, a0.w, b0.y};
          u32 Q[17], D1[15], F4[15], W5[13], D2[17];
#pragma unroll
          for (int j = 1; j < 17; j++) Q[j] = __byte_perm(P[j - 1], P[j], 0x5432);
#pragma unroll
          for (int j = 1; j < 15; j++) D1[j] = hadd(P[j], Q[j]);
#pragma unroll
          for (int j = 2; j < 15; j++) F4[j] = hadd(D1[j], D1[j - 1]);
#pragma unroll
          for (int n = 0; n < 13; n++) W5[n] = hadd(F4[n + 2], P[n]);
#pragma unroll
          for (int j = 5; j < 17; j++) D2[j] = hadd(Q[j], P[j - 1]);
          const u32 wa = SM_R + sig * WSL + i * 16, wb = wa + i * 16;
          u32 o[8];
#pragma unroll
          for (int n = 0; n < 8; n++) o[n] = hadd(D2[n + 5], Q[n + 4]);
          sts128(wb + W5O, W5[5], W5[6], W5[7], W5[8]); sts128(wb + W3O, o[0], o[1], o[2], o[3]);
          if (i < 96) { sts128(wb + W5O + 16, W5[9], W5[10], W5[11], W5[12]); sts128(wb + W3O + 16, o[4], o[5], o[6], o[7]); }
          if (i < 16) { sts128(wa, 0, 0, 0, 0); sts128(wa + W3O - 256, 0, 0, 0, 0); }
          if (i < 64) {
#pragma unroll
            for (int n = 0; n < 8; n++) o[n] = hadd(F4[n + 4], W5[n]);
            sts128(wa + W9O, o[0], o[1], o[2], o[3]); sts128(wa + W9O + 1024, o[4], o[5], o[6], o[7]);
#pragma unroll
            for (int n = 0; n < 8; n++) o[n] = hadd(hadd(Q[n + 8], Q[n + 5]), W5[n + 5]);
            sts128(wa + W7O, o[0], o[1], o[2], o[3]); sts128(wa + W7O + 1024, o[4], o[5], o[6], o[7]);
            sts128(wa + V2O, D2[9], D2[10], D2[11], D2[12]); sts128(wa + V2O + 1024, D2[13], D2[14], D2[15], D2[16]);
          }
        }
        __syncwarp();
        TS(32 + rd);
        if (rd == 0) barrive(10, 384);
      }
      if (w >= 8) barrive(15, 256);
    }
    if (w < 8) {
      bsync(15, 256);
      TS(13);
#pragma unroll 1
      for (u32 sl = w - 4;; sl = 4) {
        const u32 wa = SM_R + sl * WSL + ((lane >> 3) & 1) * 1024 + ((lane & 7) + 8 * (lane >> 4)) * 16;
        const u32 kv = lds32(SM_KV + 4 * sl), bi = (g >> 1) == q ? (hi ? kv << 16 : kv) : 0u;
        float acc[8][4] = {};
#pragma unroll
        for (int j = 0; j < 4; j++) { const uint4 a = ldsm4t(wa + V2O + j * 256); mma8_hf(acc[2 * j], a.x, a.y, bi); mma8_hf(acc[2 * j + 1], a.z, a.w, bi); }
        u32 bt = SM_TAP + sl * TAPS + (TE9 + hi * TEO + (g >> 1) - q) * 4, wt = wa + W9O;
#pragma unroll 1
        for (int ty = 0; ty < 2; ty++) {
          uint4 a[4];
#pragma unroll
          for (int be = 0; be < 4; be++) a[be] = ldsm4t(wt + be * 256);
          u32 b1 = lds32(bt + 112);
#pragma unroll
          for (int d = 0; d < 8; d++) {
            const u32 b0 = lds32(bt + 16 * d + 128);
#pragma unroll
            for (int be = 0; be < 4; be++) if (d + 2 * be < 8) mma_hf(acc[d + 2 * be], a[be].x, a[be].y, a[be].z, a[be].w, b0, b1);
            b1 = b0;
          }
          bt += (TE7 - TE9) * 4; wt += W7O - W9O;
        }
#pragma unroll
        for (int j = 0; j < 8; j++) sts128(SM_S3 + sl * 4096 + j * 512 + lane * 16, fu(acc[j][0]), fu(acc[j][1]), fu(acc[j][2]), fu(acc[j][3]));
        if (w != 4 || sl == 4) break;
      }
      TS(34);
      barrive(11, 256);
      const int u0 = 4 * (w - 4) + 2 * rho;
      const u32 tp = SM_TAP + 4 * TAPS;
      u32 tr = tp + ((hi ? TO : TE) + (g >> 1) - q) * 4;
      u32 zb = SM_Z4 + (q >> 1) * ZP4 + u0 * 128 + zl;
      float acc[4][4] = {};
      uint2 R[8];
#pragma unroll
      for (int j = 0; j < 8; j++) R[j] = lds64(zb + 128 - 16 * j);
      u32 prev = 0;
#pragma unroll 1
      for (int it = 0; it < 4; it++) {
#pragma unroll
        for (int s = 0; s < 8; s++) {
          const uint2 nw = lds64(zb - 16 * s);
          const u32 t0 = lds32(tr + 32 * s), t1 = lds32(tr + 32 * s + 16);
          mma_hf(acc[2 + (s & 1)], t0, t1, prev, t0, R[s].x, R[s].y);
          mma_hf(acc[s & 1], t0, t1, prev, t0, nw.x, nw.y);
          R[s] = nw; prev = t1;
        }
        zb -= 128; tr += 256;
      }
      { const uint2 nw = lds64(zb); const u32 t0 = lds32(tr); mma_hf(acc[2], t0, 0, prev, t0, R[0].x, R[0].y); mma_hf(acc[0], t0, 0, prev, t0, nw.x, nw.y); }
#pragma unroll 1
      for (int d = min(u0 + 1, 8); d >= 3; d--) {
        const u32 wa = SM_R + 4 * WSL + W5O + rl16 + (u0 - d) * 256, bt = tp + (T5 + g - q) * 4 + 32 * d;
#pragma unroll
        for (int ty = 0; ty < 2; ty++) {
          const uint4 a = ldsm4t(wa + ty * (W3O - W5O));
          const u32 bb = bt + ty * (T3 - T5) * 4;
          mma_hf(acc[ty], a.x, a.y, a.z, a.w, lds32(bb), lds32(bb - 16));
          mma_hf(acc[2 + ty], a.x, a.y, a.z, a.w, lds32(bb + 32), lds32(bb + 16));
        }
      }
      TS(35);
      barrive(12, 288);
      bsync(14, 128);
      const uint2 fc = lds64(SM_SC + 16 * 4 + 8);
      const float F = uf(fc.x) * uf(fc.y);
      char* yp = gs + (G_Y + (8 * u0 + 2 * q) * 18432 + Ps * 32 + 4 * g);
      const u32 pml = ssrc ? 0 : pm;
#pragma unroll
      for (int j = 0; j < 2; j++) {
        uint4 s3 = {0, 0, 0, 0};
        if (u0 >= 8) s3 = lds128(SM_S3 + 4 * 4096 + (u0 - 8 + j) * 512 + lane * 16);
        y_store(acc[2 * j][0] + acc[2 * j + 1][0] + uf(s3.x), acc[2 * j][1] + acc[2 * j + 1][1] + uf(s3.y), acc[2 * j][2] + acc[2 * j + 1][2] + uf(s3.z),
                acc[2 * j][3] + acc[2 * j + 1][3] + uf(s3.w), F, pml, yp + j * 8 * 18432);
      }
      TS(16);
    } else if (w == 9) {
      if (lane == 0) tma3d(SM_UP, &tm_up, SM_MB + 24, 46080, 8 * Pm, 0);
      TS(17);
      bsync(12, 288);
      if (lane == 0) {
        asm volatile("fence.proxy.async.shared::cta;" ::: "memory");
        tma3d(SM_WD, &tm_down, SM_MB + 32, 41472, 72 * (b & 7), 2 * (b >> 3));
      }
    } else if (w == 10) {
      float s1 = 0.f, s2 = 0.f;
#pragma unroll 1
      for (u32 j = lane; j < 96; j += 32) {
        const u32 jj = min(j, 71u);
        const char* mp = gs + mod_off(8 * jj);
        uint4 a, c, r = ldg128(p.wr + 16 * jj);
        POLL({ a = ldr128(mp + 3 * MODJ); c = ldr128(mp + 4 * MODJ); }, ((a.x ^ pm) | (c.x ^ pm)) & TAGM, 3);
        a.x &= ~TAGM; c.x &= ~TAGM;
#pragma unroll 1
        for (int i = j < 72 ? 0 : 4; i < 4; i++) {
          const u32 c1 = bfma(c.x, B2P64, BONE), s = bmul(a.x, B2P64);
          s1 = fmaf(blo(c1), blo(r.x), s1); s1 = fmaf(bhi(c1), bhi(r.x), s1);
          s2 = fmaf(blo(s), blo(r.x), s2); s2 = fmaf(bhi(s), bhi(r.x), s2);
          a.x = a.y; a.y = a.z; a.z = a.w; c.x = c.y; c.y = c.z; c.z = c.w; r.x = r.y; r.y = r.z; r.z = r.w;
        }
      }
#pragma unroll 1
      for (int o = 16; o; o >>= 1) { s1 += __shfl_xor_sync(~0u, s1, o); s2 += __shfl_xor_sync(~0u, s2, o); }
      sts64(SM_RC, fu(s1), fu(s2));
      TS(31);
      barrive(1, 320);
    }
    if (w < 9) P2LOAD();
  }
  post_conv(p, tid + p.zero, b, ep, xv, dk, wr, md);
  if (tid == 352 && s2u(smem) != SM0) __trap();
}

typedef CUresult (*EncFn)(CUtensorMap*, CUtensorMapDataType, cuuint32_t, void*, const cuuint64_t*, const cuuint64_t*, const cuuint32_t*, const cuuint32_t*,
                          CUtensorMapInterleave, CUtensorMapSwizzle, CUtensorMapL2promotion, CUtensorMapFloatOOBfill);
static void make_map(EncFn enc, CUtensorMap* tm, void* ptr, int cols, int rows, int bw, int br, int nb, CUtensorMapSwizzle sw) {
  cuuint64_t gd[3] = {(cuuint64_t)cols, (cuuint64_t)br, (cuuint64_t)(rows / br)}, gs[2] = {(cuuint64_t)cols * 2, (cuuint64_t)cols * 2 * br};
  cuuint32_t bd[3] = {(cuuint32_t)bw, (cuuint32_t)br, (cuuint32_t)nb}, es[3] = {1, 1, 1};
  enc(tm, CU_TENSOR_MAP_DATA_TYPE_BFLOAT16, 3, ptr, gd, gs, bd, es, CU_TENSOR_MAP_INTERLEAVE_NONE, sw, CU_TENSOR_MAP_L2_PROMOTION_NONE, CU_TENSOR_MAP_FLOAT_OOB_FILL_NONE);
}
extern "C" void kernel_launch(void* const* d_in, const int* in_sizes, int n_in, void* d_out, int out_size) {
  static EncFn enc = nullptr;
  static void* scratch = nullptr;
  if (!enc) {
    cudaGetSymbolAddress(&scratch, g_s);
    cudaDriverEntryPointQueryResult qr;
    cudaGetDriverEntryPoint("cuTensorMapEncodeTiled", (void**)&enc, cudaEnableDefault, &qr);
    cudaFuncSetAttribute(fused_kernel, cudaFuncAttributeMaxDynamicSharedMemorySize, SM_TOTAL);
  }
  CUtensorMap tm_mod, tm_gate, tm_up, tm_down;
  make_map(enc, &tm_mod, d_in[13], 3456, 576, 16, 192, 3, CU_TENSOR_MAP_SWIZZLE_32B);
  make_map(enc, &tm_gate, d_in[9], 4608, 576, 40, 192, 3, CU_TENSOR_MAP_SWIZZLE_NONE);
  make_map(enc, &tm_up, d_in[10], 4608, 576, 40, 192, 3, CU_TENSOR_MAP_SWIZZLE_NONE);
  make_map(enc, &tm_down, d_in[11], 576, 4608, 72, 144, 2, CU_TENSOR_MAP_SWIZZLE_NONE);
  Prm p;
  p.x = (const char*)d_in[0]; p.la = (const char*)d_in[1]; p.ai = (const char*)d_in[2]; p.cr = (const char*)d_in[3];
  p.ci = (const char*)d_in[4]; p.ldt = (const char*)d_in[5]; p.dsk = (const char*)d_in[6]; p.wr = (const char*)d_in[8];
  p.c = (const char*)d_in[12]; p.out = (char*)d_out; p.zero = 0; p.gs = (char*)scratch;
  fused_kernel<<<128, 384, SM_TOTAL>>>(p, tm_mod, tm_gate, tm_up, tm_down);
}
```

```cpp
#include <cuda_runtime.h>
#include <cuda.h>
#include <cuda_bf16.h>
#include <cuda_fp16.h>
#include <stdint.h>
#define FUSED 1
#define X_NOWPREP 0
#define X_NOSEG3 0
#define X_NOSH 0
#define DEV __device__ __forceinline__
typedef uint32_t u32;

constexpr u32 OB_KEY = 0, OB_ACT = 128, OB_PART = 768, OB = 3072, ROW = 1168;
constexpr u32 G_Z = 0, G_Y = 128 * 18432, G_XS = 2 * G_Y, G_X1 = G_XS + 8 * ROW, G_MOD = G_X1 + 8 * ROW, G_OB = G_MOD + 216 * 128;
constexpr u32 G_EP = G_OB + 128 * OB, G_END = G_EP + 128;
__device__ __align__(128) unsigned char g_s[G_END];
#define TS(i)
#define TS0()
#define TSE()
#define ERRF(code)

constexpr int SM0 = 1024;
constexpr int ZPS = 2240, ZSS = 4496, ZP4 = 2624;
constexpr int SM_GATE = SM0, SM_UP = SM_GATE + 46080, SM_ZS = SM_UP + 46080, SM_Z4 = SM_ZS + 4 * ZSS + 512;
constexpr int SM_TAP = SM_Z4 + ZP4 + 2048, TAPS = 3392;
constexpr int SM_MB = SM_TAP + 5 * TAPS;
constexpr int SM_ST = SM_MB + 48;
constexpr int SM_SC = SM_ST + 256;
constexpr int SM_KV = SM_SC + 80;
constexpr int SM_RC = SM_KV + 32;
constexpr int SM_THR = SM_RC + 16;
constexpr int SM_KEY = SM_THR + 48;
constexpr int SM_TOK = SM_KEY + 64;
constexpr int SM_CNT = SM_TOK + 128;
constexpr int SM_GP = SM_CNT + 128;
constexpr int SM_SIL = SM_GP + 128;
constexpr int SM_SP = SM_SIL + 1152;
constexpr int SM_R = (SM_SP + 5760 + 127) / 128 * 128;
static_assert(SM_SP % 16 == 0 && SM_THR % 16 == 0 && SM_ST % 16 == 0 && SM_TAP % 16 == 0 && SM_CNT % 16 == 0, "smem map");
constexpr int KTAB = 9216, WSL = 12832, W5O = 256, W3O = 3600, W9O = 6688, W7O = 8736, V2O = 10784;
constexpr int SM_S3 = SM_R + 5 * WSL;
constexpr int SM_WD = SM_R, SM_XS = SM_R + 41600, SM_AC = SM_XS + 9344, SM_RED = SM_AC + 4608, SM_OS = SM_RED + 10240;
constexpr int STASH = 16 * ROW + 64, SM_HS = SM_ZS, SM_X1S = SM_HS + STASH;
constexpr int SM_TOTAL = SM_R + 92160 - SM0;
static_assert(SM_X1S + STASH <= SM_MB && SM_OS + STASH <= SM_R + 92160 && SM_TOTAL <= 232448, "smem map");
constexpr int TE = 4, TO = 272 + 4, T5 = 544 - 17, T3 = 608 - 17, TE9 = 672 - 25, TE7 = 760 - 25, TEO = 48;
constexpr int SPIN = 1 << 16;
constexpr u32 TAGM = 0x40004000u, INVAL = 0x00004801u;

DEV u32 s2u(const void* p) { return (u32)__cvta_generic_to_shared(p); }
DEV void mma_bf(float (&c)[4], u32 a0, u32 a1, u32 a2, u32 a3, u32 b0, u32 b1) {
  asm("mma.sync.aligned.m16n8k16.row.col.f32.bf16.bf16.f32 {%0,%1,%2,%3},{%4,%5,%6,%7},{%8,%9},{%0,%1,%2,%3};"
      : "+f"(c[0]), "+f"(c[1]), "+f"(c[2]), "+f"(c[3]) : "r"(a0), "r"(a1), "r"(a2), "r"(a3), "r"(b0), "r"(b1));
}
DEV void mma_hf(float (&c)[4], u32 a0, u32 a1, u32 a2, u32 a3, u32 b0, u32 b1) {
  asm("mma.sync.aligned.m16n8k16.row.col.f32.f16.f16.f32 {%0,%1,%2,%3},{%4,%5,%6,%7},{%8,%9},{%0,%1,%2,%3};"
      : "+f"(c[0]), "+f"(c[1]), "+f"(c[2]), "+f"(c[3]) : "r"(a0), "r"(a1), "r"(a2), "r"(a3), "r"(b0), "r"(b1));
}
DEV void mma8_bf(float (&c)[4], u32 a0, u32 a1, u32 b0) {
  asm("mma.sync.aligned.m16n8k8.row.col.f32.bf16.bf16.f32 {%0,%1,%2,%3},{%4,%5},{%6},{%0,%1,%2,%3};"
      : "+f"(c[0]), "+f"(c[1]), "+f"(c[2]), "+f"(c[3]) : "r"(a0), "r"(a1), "r"(b0));
}
DEV void mma8_hf(float (&c)[4], u32 a0, u32 a1, u32 b0) {
  asm("mma.sync.aligned.m16n8k8.row.col.f32.f16.f16.f32 {%0,%1,%2,%3},{%4,%5},{%6},{%0,%1,%2,%3};"
      : "+f"(c[0]), "+f"(c[1]), "+f"(c[2]), "+f"(c[3]) : "r"(a0), "r"(a1), "r"(b0));
}
DEV u32 movm(u32 x) { u32 r; asm("movmatrix.sync.aligned.m8n8.trans.b16 %0,%1;" : "=r"(r) : "r"(x)); return r; }
DEV uint4 ldsm4(u32 a) { uint4 r; asm volatile("ldmatrix.sync.aligned.m8n8.x4.shared.b16 {%0,%1,%2,%3},[%4];" : "=r"(r.x), "=r"(r.y), "=r"(r.z), "=r"(r.w) : "r"(a)); return r; }
DEV uint2 ldsm2(u32 a) { uint2 r; asm volatile("ldmatrix.sync.aligned.m8n8.x2.shared.b16 {%0,%1},[%2];" : "=r"(r.x), "=r"(r.y) : "r"(a)); return r; }
DEV uint4 ldsm4t(u32 a) { uint4 r; asm volatile("ldmatrix.sync.aligned.m8n8.x4.trans.shared.b16 {%0,%1,%2,%3},[%4];" : "=r"(r.x), "=r"(r.y), "=r"(r.z), "=r"(r.w) : "r"(a)); return r; }
DEV u32 lds32(u32 a) { u32 r; asm volatile("ld.volatile.shared.u32 %0,[%1];" : "=r"(r) : "r"(a)); return r; }
DEV uint2 lds64(u32 a) { uint2 r; asm volatile("ld.shared.v2.u32 {%0,%1},[%2];" : "=r"(r.x), "=r"(r.y) : "r"(a)); return r; }
DEV uint4 lds128(u32 a) { uint4 r; asm volatile("ld.shared.v4.u32 {%0,%1,%2,%3},[%4];" : "=r"(r.x), "=r"(r.y), "=r"(r.z), "=r"(r.w) : "r"(a)); return r; }
DEV void sts16(u32 a, u32 v) { asm volatile("st.shared.u16 [%0],%1;" ::"r"(a), "h"((unsigned short)v) : "memory"); }
DEV void sts32(u32 a, u32 v) { asm volatile("st.shared.u32 [%0],%1;" ::"r"(a), "r"(v) : "memory"); }
DEV void sts64(u32 a, u32 x, u32 y) { asm volatile("st.shared.v2.u32 [%0],{%1,%2};" ::"r"(a), "r"(x), "r"(y) : "memory"); }
DEV void sts128(u32 a, u32 x, u32 y, u32 z, u32 w) { asm volatile("st.shared.v4.u32 [%0],{%1,%2,%3,%4};" ::"r"(a), "r"(x), "r"(y), "r"(z), "r"(w) : "memory"); }
DEV uint4 ldr128(const void* p) { uint4 v; asm volatile("ld.relaxed.gpu.global.v4.u32 {%0,%1,%2,%3},[%4];" : "=r"(v.x), "=r"(v.y), "=r"(v.z), "=r"(v.w) : "l"(p) : "memory"); return v; }
DEV uint2 ldr64(const void* p) { uint2 v; asm volatile("ld.relaxed.gpu.global.v2.u32 {%0,%1},[%2];" : "=r"(v.x), "=r"(v.y) : "l"(p) : "memory"); return v; }
DEV u32 ldr32(const void* p) { u32 v; asm volatile("ld.relaxed.gpu.global.u32 %0,[%1];" : "=r"(v) : "l"(p) : "memory"); return v; }
DEV void str128(void* p, u32 x, u32 y, u32 z, u32 w) { asm volatile("st.relaxed.gpu.global.v4.u32 [%0],{%1,%2,%3,%4};" ::"l"(p), "r"(x), "r"(y), "r"(z), "r"(w) : "memory"); }
DEV void str64(void* p, u32 x, u32 y) { asm volatile("st.relaxed.gpu.global.v2.u32 [%0],{%1,%2};" ::"l"(p), "r"(x), "r"(y) : "memory"); }
DEV void str32(void* p, u32 x) { asm volatile("st.relaxed.gpu.global.u32 [%0],%1;" ::"l"(p), "r"(x) : "memory"); }
DEV void str16(void* p, u32 x) { asm volatile("st.relaxed.gpu.global.u16 [%0],%1;" ::"l"(p), "h"((unsigned short)x) : "memory"); }
DEV uint4 ldg128(const void* p) { uint4 v; asm volatile("ld.global.nc.v4.u32 {%0,%1,%2,%3},[%4];" : "=r"(v.x), "=r"(v.y), "=r"(v.z), "=r"(v.w) : "l"(p)); return v; }
DEV uint2 ldg64(const void* p) { uint2 v; asm volatile("ld.global.nc.v2.u32 {%0,%1},[%2];" : "=r"(v.x), "=r"(v.y) : "l"(p)); return v; }
DEV u32 ldg32(const void* p) { u32 v; asm volatile("ld.global.nc.u32 %0,[%1];" : "=r"(v) : "l"(p)); return v; }
DEV u32 ldg16(const void* p) { unsigned short v; asm volatile("ld.global.nc.u16 %0,[%1];" : "=h"(v) : "l"(p)); return v; }
#define bsync(id, n) asm volatile("bar.sync %0,%1;" ::"n"(id), "n"(n) : "memory")
#define barrive(id, n) asm volatile("bar.arrive %0,%1;" ::"n"(id), "n"(n) : "memory")
DEV void mb_init(u32 a) { asm volatile("mbarrier.init.shared.b64 [%0],1;" ::"r"(a) : "memory"); }
DEV void mb_expect(u32 a, u32 bytes) { asm volatile("mbarrier.arrive.expect_tx.shared.b64 _,[%0],%1;" ::"r"(a), "r"(bytes) : "memory"); }
DEV void mb_wait(u32 a) {
  u32 ok; int it = 0;
  do { asm volatile("{.reg .pred p; mbarrier.try_wait.parity.shared.b64 p,[%1],0; selp.u32 %0,1,0,p;}" : "=r"(ok) : "r"(a) : "memory"); } while (!ok && ++it < SPIN);
}
DEV void bulk_out(void* dst, u32 src) { asm volatile("cp.async.bulk.global.shared::cta.bulk_group [%0],[%1],1152;" ::"l"(dst), "r"(src) : "memory"); }
DEV void tma3d(u32 dst, const CUtensorMap* tm, u32 mb, u32 bytes, int c0, int c2) {
  mb_expect(mb, bytes);
  asm volatile("cp.async.bulk.tensor.3d.shared::cluster.global.mbarrier::complete_tx::bytes [%0],[%1,{%3,0,%4}],[%2];"
               ::"r"(dst), "l"((uint64_t)tm), "r"(mb), "r"(c0), "r"(c2) : "memory");
}
DEV float blo(u32 w) { return __uint_as_float(w << 16); }
DEV float bhi(u32 w) { return __uint_as_float(w & 0xffff0000u); }
DEV u32 pk_bf(float lo, float hi) { u32 r; asm("cvt.rn.bf16x2.f32 %0,%1,%2;" : "=r"(r) : "f"(hi), "f"(lo)); return r; }
DEV u32 pk_hf(float lo, float hi) { u32 r; asm("cvt.rn.f16x2.f32 %0,%1,%2;" : "=r"(r) : "f"(hi), "f"(lo)); return r; }
DEV float rbf(float x) { return __uint_as_float(pk_bf(0.f, x) & 0xffff0000u); }
DEV u32 bfma(u32 a, u32 b, u32 c) { u32 r; asm("fma.rn.bf16x2 %0,%1,%2,%3;" : "=r"(r) : "r"(a), "r"(b), "r"(c)); return r; }
DEV u32 bmul(u32 a, u32 b) { u32 r; asm("mul.rn.bf16x2 %0,%1,%2;" : "=r"(r) : "r"(a), "r"(b)); return r; }
DEV u32 badd(u32 a, u32 b) { u32 r; asm("add.rn.bf16x2 %0,%1,%2;" : "=r"(r) : "r"(a), "r"(b)); return r; }
DEV u32 hadd(u32 a, u32 b) { u32 r; asm("add.rn.f16x2 %0,%1,%2;" : "=r"(r) : "r"(a), "r"(b)); return r; }
DEV u32 hfma(u32 a, u32 b, u32 c) { u32 r; asm("fma.rn.f16x2 %0,%1,%2,%3;" : "=r"(r) : "r"(a), "r"(b), "r"(c)); return r; }
struct C2 { u32 re, im; };
DEV C2 cm2(C2 a, C2 b) {
  const __half2 ar = *reinterpret_cast<__half2*>(&a.re), ai = *reinterpret_cast<__half2*>(&a.im), br = *reinterpret_cast<__half2*>(&b.re), bi = *reinterpret_cast<__half2*>(&b.im);
  __half2 re = __hfma2(ar, br, __hneg2(__hmul2(ai, bi))), im = __hfma2(ar, bi, __hmul2(ai, br));
  return {*reinterpret_cast<u32*>(&re), *reinterpret_cast<u32*>(&im)};
}
DEV C2 pk2(const float2 (&a)[2]) { return {pk_hf(a[0].x, a[1].x), pk_hf(a[0].y, a[1].y)}; }
DEV C2 pk2c(const float2 (&a)[2]) { return {pk_hf(a[0].x, a[1].x), pk_hf(-a[0].y, -a[1].y)}; }
DEV u32 cpy(u32 x, u32 zr, int alt) {
  u32 r;
  if (alt) asm volatile("xor.b32 %0,%1,%2;" : "=r"(r) : "r"(x), "r"(zr)); else asm volatile("mad.lo.u32 %0,%2,%2,%1;" : "=r"(r) : "r"(x), "r"(zr));
  return r;
}
DEV u32 bsetgt(u32 a, u32 b) { u32 r; asm("set.gt.bf16x2.bf16x2 %0,%1,%2;" : "=r"(r) : "r"(a), "r"(b)); return r; }
DEV float ex2(float x) { float r; asm("ex2.approx.ftz.f32 %0,%1;" : "=f"(r) : "f"(x)); return r; }
DEV float rcpf(float x) { float r; asm("rcp.approx.ftz.f32 %0,%1;" : "=f"(r) : "f"(x)); return r; }
DEV float2 cmul(float2 a, float2 b) { return make_float2(fmaf(a.x, b.x, -a.y * b.y), fmaf(a.x, b.y, a.y * b.x)); }
DEV float2 csq(float2 a) { return make_float2(fmaf(a.x, a.x, -a.y * a.y), (a.x + a.x) * a.y); }
DEV float2 cexp(float lr2, float th) {
  float k = rintf(th * 0.15915494309189535f);
  float r = fmaf(k, -6.2831854820251465f, th); r = fmaf(k, 1.7484555e-7f, r);
  float m = ex2(lr2);
  return make_float2(m * __cosf(r), m * __sinf(r));
}
DEV float silu_f(float v) { return v * rcpf(1.f + ex2(-1.4426950408889634f * v)); }
constexpr u32 B2P64 = 0x5F805F80u, B2M64 = 0x1F801F80u, BONE = 0x3F803F80u;
DEV u32 chan_of(u32 P) { u32 r = P & 63; return (P & ~63) + 32 * (r & 1) + 8 * ((r >> 2) & 3) + 2 * (r >> 4) + ((r >> 1) & 1); }
DEV u32 mod_off(u32 idx) { return G_MOD + (idx >> 4) * 128 + (idx & 8) * 2; }
constexpr u32 MODJ = 36 * 128;
DEV float sqrta(float x) { float r; asm("sqrt.approx.ftz.f32 %0,%1;" : "=f"(r) : "f"(x)); return r; }
DEV u32 fu(float x) { return __float_as_uint(x); }
DEV float uf(u32 x) { return __uint_as_float(x); }
DEV void mma_hf_o(float (&d)[4], const float (&c)[4], const u32 (&a)[4], u32 b0, u32 b1) {
  asm("mma.sync.aligned.m16n8k16.row.col.f32.f16.f16.f32 {%0,%1,%2,%3},{%4,%5,%6,%7},{%8,%9},{%10,%11,%12,%13};"
      : "=f"(d[0]), "=f"(d[1]), "=f"(d[2]), "=f"(d[3]) : "r"(a[0]), "r"(a[1]), "r"(a[2]), "r"(a[3]), "r"(b0), "r"(b1), "f"(c[0]), "f"(c[1]), "f"(c[2]), "f"(c[3]));
}

struct Prm {
  const char *x, *la, *ai, *cr, *ci, *ldt, *c;
  char* gs;
  const char *dsk, *wr;
  char* out;
  u32 zero;
};
constexpr float LOG2E = 1.4426950408889634f, F2P64 = 1.8446744073709552e19f, F2M64 = 5.421010862427522e-20f;

DEV void y_store(float c0, float c1, float c2, float c3, float F, u32 pml, char* yp) {
  str32(yp, pk_bf(c0 * F, c2 * F) | pml);
  str32(yp + 18432, pk_bf(c1 * F, c3 * F) | pml);
}
#define POLL(load, cond_bad, code) { int it_ = 0; do { load; if (++it_ > SPIN) { ERRF(code); break; } } while (__any_sync(~0u, (cond_bad))); }
#define POLLW(load, cond_bad, code) { int it_ = 0; while (__any_sync(~0u, (cond_bad))) { if (++it_ > SPIN) { ERRF(code); break; } load; } }

DEV void post_conv(const Prm& p, const u32 tid, const u32 b, const u32 ep, const uint4 (&xv)[4], const uint4 dk, const uint4 wr, uint4 (&md)[6]) {
  const u32 w = tid >> 5, lane = tid & 31;
  const u32 g = lane >> 2, q = lane & 3, e = g >> 2, h = (g >> 1) & 1, hi = g & 1;
  const u32 rho = b & 1, par = (ep + 1) & 1, pm = par ? TAGM : 0;
  char* const gs = p.gs;
  const u32 cho = 128 * w + 64 * e + 16 * q, ssrc = g & 3;
  const bool own = (q >> 1) == e, sq = (q & 1) == h;
  uint4 ka, kc;
  const char* ks = gs + (G_OB + OB_KEY + (8 * g + w) * OB + q * 16);
  if (w < 9) {
    {
      const char* mp = gs + mod_off(cho >> 1);
      POLLW(_Pragma("unroll") for (int j = 0; j < 6; j++) md[j] = ldr128(mp + j * MODJ),
            ((md[0].x ^ pm) | (md[1].x ^ pm) | (md[2].x ^ pm) | (md[3].x ^ pm) | (md[4].x ^ pm) | (md[5].x ^ pm)) & TAGM, 4);
    }
    const u32 saw[4] = {md[0].x & ~TAGM, md[0].y, md[0].z, md[0].w}, caw[4] = {md[1].x & ~TAGM, md[1].y, md[1].z, md[1].w};
    const u32 gaw[4] = {md[2].x & ~TAGM, md[2].y, md[2].z, md[2].w}, sbw[4] = {md[3].x & ~TAGM, md[3].y, md[3].z, md[3].w};
    const u32 cbr[4] = {md[4].x & ~TAGM, md[4].y, md[4].z, md[4].w}, dw[4] = {dk.x, dk.y, dk.z, dk.w};
    const u32 gbw[4] = {md[5].x & ~TAGM, md[5].y, md[5].z, md[5].w};
    const char* ysrc = gs + (G_Y + b * 18432 + tid * 16 + w * 1536);
    uint4 yv[4];
    if (w < 4) {
#pragma unroll
      for (int v = 0; v < 4; v++) yv[v] = ldr128(ysrc + 512 * v);
    } else {
#pragma unroll
      for (int v = 0; v < 4; v++) yv[v].x = INVAL;
    }
    u32 hD[4][4], cb1[4], ca1[4], x1[4][4];
#pragma unroll
    for (int v = 0; v < 4; v++) { cb1[v] = bfma(cbr[v], B2P64, BONE); ca1[v] = bfma(caw[v], B2P64, BONE); }
#pragma unroll
    for (int k = 0; k < 4; k++) {
      const uint4 st = lds128(SM_ST + 16 * (4 * h + k + 8 * hi));
      const u32 xx[4] = {xv[k].x, xv[k].y, xv[k].z, xv[k].w};
#pragma unroll
      for (int v = 0; v < 4; v++) {
        const u32 d = badd(xx[v], st.x), z = bfma(d, st.y, bmul(d, st.z));
        hD[k][v] = bmul(bfma(saw[v], B2P64, bmul(z, ca1[v])), dw[v]);
      }
    }
    u32 rb0, rb1;
    {
      const u32 c0 = hi ? cb1[1] : cb1[0], c2 = hi ? cb1[3] : cb1[2], w0 = hi ? wr.y : wr.x, w2 = hi ? wr.w : wr.z;
      const u32 H0 = bmul(c0, w0), H1 = bmul(c2, w2);
      const u32 L0 = bfma(c0, w0, H0 ^ 0x80008000u), L1 = bfma(c2, w2, H1 ^ 0x80008000u);
      rb0 = __shfl_xor_sync(~0u, h ? L0 : H0, 16); rb1 = __shfl_xor_sync(~0u, h ? L1 : H1, 16);
    }
    const u32 spw = SM_SP + (2 * w + e) * 320 + ssrc * 16 + (own ? (sq ? 4 : 0) : 8 + 4 * (q & 1));
    TS(18);
    if (w >= 4) bsync(13, 288);
    POLLW(_Pragma("unroll") for (int v = 0; v < 4; v++) if ((yv[v].x ^ pm) & TAGM) yv[v] = ldr128(ysrc + 512 * v),
          ((yv[0].x ^ pm) | (yv[1].x ^ pm) | (yv[2].x ^ pm) | (yv[3].x ^ pm)) & TAGM, 5);
    TS(19);
#pragma unroll
    for (int k = 0; k < 4; k++) {
      const u32 xx[4] = {xv[k].x, xv[k].y, xv[k].z, xv[k].w};
#pragma unroll
      for (int v = 0; v < 4; v++) {
        const u32 yw = k == 0 ? yv[v].x & ~TAGM : k == 1 ? yv[v].y : k == 2 ? yv[v].z : yv[v].w;
        x1[k][v] = bfma(bmul(gaw[v], bfma(movm(yw), B2P64, hD[k][v])), B2P64, xx[v]);
      }
      float s[4] = {}, X[4] = {}, Y[4] = {}, R[4] = {};
      mma8_bf(X, x1[k][0], x1[k][1], x1[k][0]); mma8_bf(Y, x1[k][0], x1[k][1], x1[k][1]);
      mma_bf(s, x1[k][0], x1[k][1], x1[k][2], x1[k][3], BONE, BONE);
      mma_bf(R, x1[k][0], x1[k][1], x1[k][2], x1[k][3], rb0, rb1);
      mma8_bf(X, x1[k][2], x1[k][3], x1[k][2]); mma8_bf(Y, x1[k][2], x1[k][3], x1[k][3]);
      const float u0 = hi ? X[1] : X[0], u1 = hi ? Y[3] : Y[2], u2 = own ? s[0] : R[0], u3 = own ? s[2] : R[3];
      const bool dg = own && sq;
      sts32(spw + k * 64, fu((dg ? u0 : u2) + (dg ? u1 : u3)));
    }
    TS(36);
    bsync(1, 320);
    TS(37);
    float S1 = 0.f, S2 = 0.f, S3 = 0.f, S4 = 0.f;
    const u32 spr = SM_SP + (lane >> 4) * 9 * 320 + (lane & 15) * 16;
#pragma unroll
    for (int i = 0; i < 9; i++) { uint4 t = lds128(spr + i * 320); S1 += uf(t.x); S2 += uf(t.y); S3 += uf(t.z); S4 += uf(t.w); }
    const uint2 rc = lds64(SM_RC);
    if (w < 8) { ka = ldr128(ks); kc = ldr128(ks + 64 * OB); }
    S3 += S4;
    S1 += __shfl_xor_sync(~0u, S1, 16); S2 += __shfl_xor_sync(~0u, S2, 16); S3 += __shfl_xor_sync(~0u, S3, 16);
    const float mu = S1 * (1.f / 576.f), var = fmaxf(fmaf(-mu, mu, S2 * (1.f / 576.f)), 0.f);
    const float m = rbf(mu), rs = rcpf(rbf(sqrta(rbf(rbf(var) + 1e-5f))));
    if (w == 8) {
      const u32 rb_ = pk_bf(0.f, fmaf(fmaf(-m, uf(rc.x), S3), rs, uf(rc.y)) + 0.f) & 0xffff0000u;
      const u32 tl = 4 * ((lane >> 1) & 1) + ((lane >> 2) & 3) + 8 * (lane & 1);
      if (lane < 16) str32(gs + (G_OB + b * OB + OB_KEY + 4 * tl), rb_ | (par * 0x1800u));
      TS(20);
      const u32 ok = ((rb_ ^ (((int)rb_ >> 31) | 0x80000000)) & 0xffff0000u) | (15 - tl);
      sts32(SM_KEY + 4 * (lane & 15), ok);
      sts128(SM_THR + 32, ~0u, ~0u, ~0u, ~0u);
      __syncwarp();
      const uint4 o0 = lds128(SM_KEY + 2 * (lane & 16)), o1 = lds128(SM_KEY + 2 * (lane & 16) + 16);
      u32 lr = (o0.x > ok) + (o0.y > ok) + (o0.z > ok) + (o0.w > ok) + (o1.x > ok) + (o1.y > ok) + (o1.z > ok) + (o1.w > ok);
      lr += __shfl_xor_sync(~0u, lr, 16);
      const u32 so = tl * ROW + (tl >> 3) * 64;
      sts64(SM_TOK + 8 * lr, tl * 1152, so);
      sts128(SM_HS + 1152 + so, pm, rb_ | (16 * b + tl), 0, 0);
      const u32 below = (int)rb_ > 0 ? rb_ - 0x10000u : (rb_ + 0x10000u) | 0x80000000u;
      if (lr < 8) sts16(SM_THR + (lane & 16) + 2 * lr, (lane & 16 ? below : rb_) >> 16);
    }
    const float rh = rbf(rs);
    const u32 nm_ = pk_bf(-m, rh), rL_ = pk_bf(rs - rh, rs - rh);
    const u32 so = (4 * h + 8 * hi) * ROW + 64 * hi + cho;
#pragma unroll
    for (int k = 0; k < 4; k++) {
      const u32 t = __shfl_sync(~0u, nm_, 4 * k + ssrc), rL = __shfl_sync(~0u, rL_, 4 * k + ssrc);
      const u32 nm = __byte_perm(t, t, 0x1010), rH = __byte_perm(t, t, 0x3232);
      u32 h2[4], o[4];
#pragma unroll
      for (int v = 0; v < 4; v++) {
        const u32 d = badd(x1[k][v], nm), z = bfma(d, rH, bmul(d, rL));
        h2[v] = bfma(sbw[v], B2P64, bmul(z, cb1[v]));
        o[v] = bfma(bmul(gbw[v], h2[v]), B2P64, x1[k][v]);
      }
      sts128(SM_HS + so + k * ROW, bmul(h2[0], B2M64) | pm, h2[1], h2[2], h2[3]);
      sts128(SM_X1S + so + k * ROW, bmul(x1[k][0], B2M64) | pm, x1[k][1], x1[k][2], x1[k][3]);
      sts128(SM_OS + so + k * ROW, o[0], o[1], o[2], o[3]);
    }
    asm volatile("fence.proxy.async.shared::cta;" ::: "memory");
    bsync(2, 288);
    TS(21);
  }
  if (w < 8) {
    const uint2 tk = lds64(SM_TOK + 8 * w), tk8 = lds64(SM_TOK + 64 + 8 * w);
    const u32 ba = 8 * g + w;
    const uint4 ta = lds128(SM_THR + (ba < b ? 16 : ba == b ? 32 : 0)), tc = lds128(SM_THR + (ba + 64 < b ? 16 : ba + 64 == b ? 32 : 0));
    const u32 l2 = lane < 9 ? lane * 16 + 1024 : 0;
    const uint4 h0 = lds128(SM_HS + tk.y + lane * 16), h1 = lds128(SM_HS + 512 + tk.y + lane * 16), h2 = lds128(SM_HS + tk.y + l2);
    char* const ob = p.out + b * 18432;
    if (lane == 0) bulk_out(ob + tk8.x, SM_OS + tk8.y);
    const u32 kt = par * 0x1800u;
    POLLW({ ka = ldr128(ks); kc = ldr128(ks + 64 * OB); }, ((ka.x ^ kt) | (kc.x ^ kt)) & 0x1800u, 6);
    TS(23);
    u32 n[4] = {0x43004300u, 0x43004300u, 0x43004300u, 0x43004300u};
    const u32 kk[8] = {ka.x, ka.y, ka.z, ka.w, kc.x, kc.y, kc.z, kc.w};
#pragma unroll
    for (int j = 0; j < 8; j++) {
      const u32 s = __byte_perm(kk[j], kk[j], 0x3232);
      const uint4 t = j < 4 ? ta : tc;
      n[0] = badd(n[0], bsetgt(s, t.x)); n[1] = badd(n[1], bsetgt(s, t.y)); n[2] = badd(n[2], bsetgt(s, t.z)); n[3] = badd(n[3], bsetgt(s, t.w));
    }
    sts128(SM_CNT + 16 * w, __reduce_add_sync(~0u, n[0]), __reduce_add_sync(~0u, n[1]), __reduce_add_sync(~0u, n[2]), __reduce_add_sync(~0u, n[3]));
    TS(38);
    bsync(3, 256);
    const u32 cw = lds32(SM_CNT + 16 * (lane & 7) + 2 * (w & 6));
    const u32 tot = __reduce_add_sync(~0u, lane < 8 ? cw : 0) - 0x00430000u;
    const u32 rank = w + ((w & 1) ? tot >> 16 : tot & 0xffff);
    if (rank < 8) {
      char* dst = gs + (G_XS + rank * ROW + lane * 16);
      str128(dst, h0.x, h0.y, h0.z, h0.w); str128(dst + 512, h1.x, h1.y, h1.z, h1.w);
      if (lane < 9) str128(dst + 1024, h2.x, h2.y, h2.z, h2.w);
      const uint4 x0 = lds128(SM_X1S + tk.y + lane * 16), x1 = lds128(SM_X1S + 512 + tk.y + lane * 16), x2 = lds128(SM_X1S + tk.y + l2);
      str128(dst + 8 * ROW, x0.x, x0.y, x0.z, x0.w); str128(dst + (8 * ROW + 512), x1.x, x1.y, x1.z, x1.w);
      if (lane < 8) str128(dst + (8 * ROW + 1024), x2.x, x2.y, x2.z, x2.w);
    } else if (lane == 0) bulk_out(ob + tk.x, SM_OS + tk.y);
    if (w == 0) barrive(6, 160);
    TS(24);
    bsync(5, 288);
  } else {
    mb_wait(SM_MB + 16); mb_wait(SM_MB + 24);
    if (w == 9) barrive(5, 288);
  }
  const u32 kq = w & 3, tg = 2 - (w >> 2);
  uint4 A[2][9];
  {
    const u32 aa = ((lane & 8) ? SM_UP : SM_GATE) + (144 * kq + 8 * (lane >> 4) + (lane & 7)) * 80 + tg * 32;
#pragma unroll
    for (int s = 0; s < 9; s++) A[0][s] = ldsm4t(aa + s * 1280);
    if (tg < 2) {
#pragma unroll
      for (int s = 0; s < 9; s++) A[1][s] = ldsm4t(aa + s * 1280 + 16);
    }
  }
  TS(22);
  if (w >= 8) {
    const u32 t = (tid - 256) * 16;
    const char* xs = gs + (G_XS + t);
    uint4 v[5];
#pragma unroll
    for (int j = 0; j < 5; j++) v[j].x = INVAL;
    if (t >= 72 * 16) v[4].x = pm;
    bsync(6, 160);
    POLL(_Pragma("unroll") for (int j = 0; j < 5; j++) if ((v[j].x ^ pm) & TAGM) v[j] = ldr128(xs + j * 2048),
         ((v[0].x ^ pm) | (v[1].x ^ pm) | (v[2].x ^ pm) | (v[3].x ^ pm) | (v[4].x ^ pm)) & TAGM, 8);
#pragma unroll
    for (int j = 0; j < 5; j++) if (j < 4 || t < 72 * 16) sts128(SM_XS + t + j * 2048, bmul(v[j].x & ~TAGM, B2P64), v[j].y, v[j].z, v[j].w);
  }
  __syncthreads();
  TS(25);
  {
    float c0[2][4] = {}, c1[2][4] = {};
    const u32 ba = SM_XS + (lane & 7) * ROW + (18 * kq + (lane >> 3)) * 16;
    uint4 bb[5];
#pragma unroll
    for (int s = 0; s < 5; s++) bb[s] = ldsm4(ba + s * 64);
#pragma unroll
    for (int s = 0; s < 9; s++) mma_bf(c0[s & 1], A[0][s].x, A[0][s].y, A[0][s].z, A[0][s].w, s & 1 ? bb[s >> 1].z : bb[s >> 1].x, s & 1 ? bb[s >> 1].w : bb[s >> 1].y);
    const u32 ra = SM_RED + (8 * tg + kq) * 512 + lane * 16;
    if (tg < 2) {
#pragma unroll
      for (int s = 0; s < 9; s++) mma_bf(c1[s & 1], A[1][s].x, A[1][s].y, A[1][s].z, A[1][s].w, s & 1 ? bb[s >> 1].z : bb[s >> 1].x, s & 1 ? bb[s >> 1].w : bb[s >> 1].y);
      sts128(ra + 2048, fu(c1[0][0] + c1[1][0]), fu(c1[0][1] + c1[1][1]), fu(c1[0][2] + c1[1][2]), fu(c1[0][3] + c1[1][3]));
    }
    sts128(ra, fu(c0[0][0] + c0[1][0]), fu(c0[0][1] + c0[1][1]), fu(c0[0][2] + c0[1][2]), fu(c0[0][3] + c0[1][3]));
  }
  TS(39);
  __syncthreads();
  if (w < 5 - rho) {
    float s[4] = {};
#pragma unroll
    for (int i = 0; i < 4; i++) { const uint4 t = lds128(SM_RED + (w * 4 + i) * 512 + lane * 16); s[0] += uf(t.x); s[1] += uf(t.y); s[2] += uf(t.z); s[3] += uf(t.w); }
    const u32 sg = pk_bf(silu_f(rbf(s[0])), silu_f(rbf(s[1])));
    const u32 act = movm(bmul(bmul(sg, pk_bf(s[2], s[3])), B2M64));
    str32(gs + (G_OB + OB_ACT + b * OB + tid * 4), act | (q ? 0 : pm));
  }
  TS(26);
  if (w >= 9) {
    if (w == 9) { mb_wait(SM_MB + 32); barrive(7, 192); }
    return;
  }
  {
    const u32 ul = tid >> 3, pr = ul / 9, r9 = ul - 9 * pr;
    const char* src = gs + (G_OB + OB_ACT + ((b & ~7u) + 2 * pr) * OB + (r9 < 5 ? r9 * 128 : OB + (r9 - 5) * 128) + (tid & 7) * 16);
    uint4 a = ldr128(src);
    if (w < 5) {
      const u32 aa = SM_WD + (8 * (lane >> 4) + (lane & 7)) * 144 + (2 * w + ((lane >> 3) & 1)) * 16;
      bsync(7, 192);
#pragma unroll
      for (int s = 0; s < 9; s++) { A[0][s] = ldsm4t(aa + s * 4608); A[1][s] = ldsm4t(aa + s * 4608 + 2304); }
    }
    TS(28);
    POLLW(a = ldr128(src), (a.x ^ pm) & TAGM, 9);
    sts128(SM_AC + tid * 16, a.x & ~TAGM, a.y, a.z, a.w);
  }
  TS(27);
  if (w < 5) {
    bsync(8, 288);
    float c[4][4] = {};
#pragma unroll
    for (int s = 0; s < 9; s++) {
      const uint4 bb = ldsm4(SM_AC + lane * 16 + s * 512);
      mma_bf(c[2 * (s & 1)], A[0][s].x, A[0][s].y, A[0][s].z, A[0][s].w, bb.x, bb.y);
      mma_bf(c[2 * (s & 1) + 1], A[1][s].x, A[1][s].y, A[1][s].z, A[1][s].w, bb.z, bb.w);
    }
    char* dst = gs + (G_OB + OB_PART + b * OB + w * 512 + lane * 8);
    u32 o[4];
#pragma unroll
    for (int i = 0; i < 4; i++) o[i] = (fu(((c[0][i] + c[1][i]) + (c[2][i] + c[3][i])) * F2P64) & ~1u) | par;
    str64(dst, o[0], o[1]);
    if (w < 4) str64(dst + 256, o[2], o[3]);
    TS(29);
  } else {
    barrive(8, 288);
    if (w == 8 && b < 72) {
      const u32 kg = lds32(SM_XS + 1156 + g * ROW), cg = b / 9;
      const char* src = gs + (G_OB + OB_PART + cg * OB + (b - 9 * cg) * 256 + lane * 8);
      const char* xs = gs + (G_X1 + g * ROW + b * 16);
      uint4 xt;
      POLL(xt = ldr128(xs), (xt.x ^ pm) & TAGM, 10);
      const u32 x1w = (q & 2) ? ((q & 1) ? xt.w : xt.z) : ((q & 1) ? xt.y : bmul(xt.x & ~TAGM, B2P64));
      const u32 gw = ldr32(gs + (mod_off(8 * b) + 5 * MODJ + 4 * q)) & ~TAGM;
      const u32 hw = lds32(SM_XS + g * ROW + b * 16 + q * 4);
      const float sgm = rcpf(1.f + ex2(-LOG2E * bhi(kg)));
      char* const dst = p.out + ((kg & 2047) * 1152 + 16 * b + 4 * q);
      uint2 v[16];
#pragma unroll
      for (int j = 0; j < 16; j++) v[j] = make_uint2(1, 0);
      u32 bad;
      POLL({ bad = 0; _Pragma("unroll") for (int j = 0; j < 16; j++) { if (((v[j].x ^ par) | (v[j].y ^ par)) & 1) v[j] = ldr64(src + j * 8 * OB); }
             _Pragma("unroll") for (int j = 0; j < 16; j++) bad |= (v[j].x ^ par) | (v[j].y ^ par); }, bad & 1, 11);
      float s0[4] = {}, s1[4] = {};
#pragma unroll
      for (int j = 0; j < 16; j++) { s0[j & 3] += uf(v[j].x); s1[j & 3] += uf(v[j].y); }
      const u32 y = movm(pk_bf((s0[0] + s0[1]) + (s0[2] + s0[3]), (s1[0] + s1[1]) + (s1[2] + s1[3])));
      *(u32*)dst = bfma(bmul(gw, badd(hw, bmul(y, pk_bf(sgm, sgm)))), B2P64, x1w);
      if (b == 0 && lane == 0) str32(gs + G_EP, ep + 1);
      TS(30); TSE();
    }
  }
  if (lane == 0) {
    asm volatile("cp.async.bulk.commit_group;" ::: "memory");
    asm volatile("cp.async.bulk.wait_group.read 0;" ::: "memory");
  }
}

__global__ void __launch_bounds__(384, 1)
fused_kernel(const Prm p, const __grid_constant__ CUtensorMap tm_mod, const __grid_constant__ CUtensorMap tm_gate,
             const __grid_constant__ CUtensorMap tm_up, const __grid_constant__ CUtensorMap tm_down) {
  extern __shared__ __align__(1024) unsigned char smem[];
  uint4 xv[4];
  {
    const u32 t = threadIdx.x;
    if (t < 288) {
      const char* xp = p.x + (blockIdx.x * 18432 + (t >> 5) * 128 + (t & 16) * 4 + (t & 3) * 16 + ((t & 8) * 576 + (t & 4) * 288));
#pragma unroll
      for (int k = 0; k < 4; k++) xv[k] = ldg128(xp + (2 * (k >> 1) + 8 * (k & 1)) * 1152);
    }
  }
  const u32 tid = __shfl_sync(~0u, threadIdx.x, threadIdx.x & 31), b = __shfl_sync(~0u, blockIdx.x, 0);
  const u32 w = tid >> 5, lane = tid & 31;
  const u32 g = lane >> 2, q = lane & 3, e = g >> 2, h = (g >> 1) & 1, hi = g & 1;
  const u32 rho = b & 1, Pm = 9 * (b >> 1) + 5 * rho, Ps = 9 * (b >> 1) + 4;
  char* const gs = p.gs;
  TS0();
  const u32 cho = 128 * w + 64 * e + 16 * q;
  const bool kw = (w >> 1) != 4;
  const u32 ksig = w < 8 ? (w & 3) : 4, khf = w < 8 ? (w >> 2) : (w & 1);
  u32 la, ai, ldt; uint2 cr, ci;
  {
    const u32 d = chan_of(w < 8 ? Pm + ksig : Ps), o = d * 256 + 8 * lane;
    const char* cp = p.c + (576 * (w & 1) + 24 * min(lane, 23u));
    la = ldg32(kw ? p.la + (o + 4 * khf) : cp); ai = ldg32(kw ? p.ai + (o + 4 * khf) : cp + 4);
    cr = ldg64(kw ? p.cr + o : cp + 8); ci = ldg64(kw ? p.ci + o : cp + 16); ldt = ldg16(p.ldt + 2 * d);
  }
  const u32 zr = tid >> 16;
  const u32 epv = ldr32(gs + (G_EP + zr));
  if (tid == 288) {
#pragma unroll
    for (int i = 0; i < 5; i++) mb_init(SM_MB + 8 * i);
    asm volatile("fence.mbarrier_init.release.cluster;" ::: "memory");
    tma3d(SM_UP, &tm_mod, SM_MB, 18432, 16 * b, 0);
    if (b < 88) tma3d(SM_UP + 18432, &tm_mod, SM_MB + 8, 18432, 16 * b + 2048, 0);
    tma3d(SM_GATE, &tm_gate, SM_MB + 16, 46080, 8 * Pm, 0);
    asm volatile("prefetch.tensormap [%0];" ::"l"((uint64_t)&tm_up) : "memory");
    asm volatile("prefetch.tensormap [%0];" ::"l"((uint64_t)&tm_down) : "memory");
  }
#pragma unroll 1
  for (u32 i = SM_ZS + tid * 16; i < SM_MB; i += 384 * 16) sts128(i, 0, 0, 0, 0);
  __syncthreads();
  TS(1);
  char* const zdst = gs + (b * 18432 + tid * 16 + w * 1536);
  if (w < 9) {
#pragma unroll
    for (int v = 0; v < 4; v++) str128(zdst + 512 * v, INVAL, 0, 1, 0);
    str128(gs + (G_Y + 96 * 18432 + (w < 8 ? (tid >> 3) * 18432 + Pm * 32 + (tid & 7) * 16 : (16 * rho + (lane >> 1)) * 18432 + Ps * 32 + (lane & 1) * 16)), INVAL, 0, 1, 0);
  }
  {
    const u32 t = 383 - tid;
    if (t < 192 || (t < 208 && b < 73) || (t >= 224 && t < (b < 88 ? 228 : 226)))
      str128(gs + (t < 192 ? G_OB + b * OB + t * 16 : t < 208 ? G_XS + b * 256 + (t & 15) * 16 : G_MOD + b * 128 + (t & 2) * 8192 + (t & 1) * 16), INVAL, 0, 1, 0);
  }
  const u32 ep = __reduce_or_sync(~0u, epv), par = (ep + 1) & 1, pm = par ? TAGM : 0;
  const bool own = (q >> 1) == e, sq = (q & 1) == h;
  const u32 ssrc = g & 3;
  if (w < 9) {
    const u32 spw = SM_SP + (2 * w + e) * 160 + ssrc * 8 + (sq ? 4 : 0);
#pragma unroll
    for (int k = 0; k < 4; k++) {
      float s[4] = {}, X[4] = {}, Y[4] = {};
      mma8_bf(X, xv[k].x, xv[k].y, xv[k].x); mma8_bf(Y, xv[k].x, xv[k].y, xv[k].y);
      mma_bf(s, xv[k].x, xv[k].y, xv[k].z, xv[k].w, BONE, BONE);
      mma8_bf(X, xv[k].z, xv[k].w, xv[k].z); mma8_bf(Y, xv[k].z, xv[k].w, xv[k].w);
      const float u0 = hi ? X[1] : X[0], u1 = hi ? Y[3] : Y[2];
      const float v = (sq ? u0 : s[0]) + (sq ? u1 : s[2]);
      if (own) sts32(spw + k * 32, fu(v));
    }
    TS(4);
    bsync(1, 288);
    TS(7);
    float S1 = 0.f, S2 = 0.f;
    const u32 spr = SM_SP + (lane >> 4) * 9 * 160 + (lane & 15) * 8;
#pragma unroll
    for (int i = 0; i < 9; i++) { uint2 t = lds64(spr + i * 160); S1 += uf(t.x); S2 += uf(t.y); }
    S1 += __shfl_xor_sync(~0u, S1, 16); S2 += __shfl_xor_sync(~0u, S2, 16);
    const float mu = S1 * (1.f / 576.f), var = fmaxf(fmaf(-mu, mu, S2 * (1.f / 576.f)), 0.f);
    const float m = rbf(mu), rs = rcpf(rbf(sqrta(rbf(rbf(var) + 1e-5f))));
    const float ra = rs * 0.0625f, rc = -m * ra;
    u32 zt[4][4];
#pragma unroll
    for (int k = 0; k < 4; k++) {
      const float a = __shfl_sync(~0u, ra, 4 * k + ssrc), c = __shfl_sync(~0u, rc, 4 * k + ssrc);
      const u32 xx[4] = {xv[k].x, xv[k].y, xv[k].z, xv[k].w};
#pragma unroll
      for (int v = 0; v < 4; v++) zt[v][k] = movm(pk_hf(fmaf(blo(xx[v]), a, c), fmaf(bhi(xx[v]), a, c)));
    }
#pragma unroll
    for (int v = 0; v < 4; v++) str128(zdst + 512 * v, zt[v][0] | pm, zt[v][1], zt[v][2], zt[v][3]);
    if (w == 8) {
      const float rh = rbf(rs);
      sts128(SM_ST + 16 * (4 * ((lane >> 1) & 1) + ((lane >> 2) & 2) + 2 * (lane & 4) + (lane & 1)), pk_bf(-m, -m), pk_bf(rh, rh), pk_bf(rs - rh, rs - rh), 0);
    }
  }
  TS(5);
  if (kw) {
    const u32 ktab = SM_R + (w < 8 ? w : w - 2) * KTAB;
    u32 mx = __vmaxu2(__vmaxu2(cr.x & 0x7fff7fff, cr.y & 0x7fff7fff), __vmaxu2(ci.x & 0x7fff7fff, ci.y & 0x7fff7fff));
    const u32 E = max(__reduce_max_sync(~0u, max(mx & 0xffff, mx >> 16)) >> 7, 8u);
    const float dt = rbf(ex2(blo(ldt) * LOG2E)), csc = uf((258 - E) << 23);
    const float FK = 2.f * dt * uf((E - 4) << 23);
    const u32 crw = khf ? cr.y : cr.x, ciw = khf ? ci.y : ci.x;
    float k2048 = 0.f;
    {
      float2 C[2], w4[2], w8[2], w16[2], w32[2], w64[2], w128[2], w256[2], w512[2], a1[2], a2[2], a3[2], t0[2], t1[2], s3[2];
#pragma unroll
      for (int m = 0; m < 2; m++) {
        const float lr2 = rbf(ex2((m ? bhi(la) : blo(la)) * LOG2E)) * dt * -LOG2E, th = (m ? bhi(ai) : blo(ai)) * dt;
        C[m] = make_float2((m ? bhi(crw) : blo(crw)) * csc, (m ? bhi(ciw) : blo(ciw)) * csc);
        const float2 w1 = cexp(lr2, th), w2 = csq(w1);
        w64[m] = cexp(64.f * lr2, 64.f * th);
        w4[m] = csq(w2); w8[m] = csq(w4[m]); w16[m] = csq(w8[m]); w32[m] = csq(w16[m]);
        w128[m] = csq(w64[m]); w256[m] = csq(w128[m]); w512[m] = csq(w256[m]);
        const float2 w1024 = csq(w512[m]);
        a1[m] = cmul(C[m], w1); a2[m] = cmul(C[m], w2); a3[m] = cmul(a1[m], w2);
        t0[m] = cmul(C[m], w1024); t1[m] = cmul(t0[m], w128[m]); s3[m] = cmul(w8[m], w16[m]);
        k2048 += fmaf(t0[m].x, w1024.x, -t0[m].y * w1024.y);
      }
      C2 B0[8], B1[8], B2[8], S[8];
      B0[0] = pk2(C); B0[1] = pk2(a1); B0[2] = pk2(a2); B0[3] = pk2(a3);
      const C2 h4 = pk2(w4), h256 = pk2(w256), h512 = pk2(w512);
#pragma unroll
      for (int i = 0; i < 4; i++) B0[4 + i] = cm2(B0[i], h4);
#pragma unroll
      for (int i = 0; i < 4; i++) B1[i] = cm2(B0[2 * i], h256);
      B1[4] = cm2(B0[0], h512); B1[5] = cm2(B0[4], h512);
      B1[6] = cm2(B1[4], h256); B1[7] = cm2(B1[5], h256);
      const u32 ta = ktab + lane * 128, f = ((lane & 3) << 5) | ((lane & 4) << 2);
#pragma unroll
      for (int i = 0; i < 8; i++) sts128(ta + ((i << 4) ^ f), B0[i].re, B0[i].im, B1[i].re, B1[i].im);
      B2[0] = pk2(t0); B2[1] = pk2(t1);
      B2[2] = cm2(B2[0], h256); B2[3] = cm2(B2[1], h256);
#pragma unroll
      for (int i = 0; i < 4; i++) B2[4 + i] = cm2(B2[i], h512);
      S[0] = {0x3C003C00u, 0u}; S[1] = pk2c(w8); S[2] = pk2c(w16); S[3] = pk2c(s3); S[4] = pk2c(w32);
#pragma unroll
      for (int i = 1; i < 4; i++) S[4 + i] = cm2(S[i], S[4]);
#pragma unroll
      for (int i = 0; i < 8; i++) sts128(ta + 4096 + ((i << 4) ^ f), B2[i].re, B2[i].im, S[i].re, S[i].im);
      const C2 m64 = pk2c(w64), m128 = pk2c(w128);
      sts128(ktab + 8192 + lane * 16, m64.re, m64.im, m128.re, m128.im);
    }
    __syncwarp();
    TS(2);
    float D[5][4] = {};
    u32 ta = ktab + q * 128 + ((g ^ (q << 1)) << 4), tm = ktab + 8192 + q * 16;
#pragma unroll 2
    for (int s = 0; s < 8; s++) {
      const uint4 ca = lds128(ta), cb = lds128(ta + 4096), ma = lds128(tm);
      ta = (ta + 512) ^ 16; tm += 64;
      k2048 += __shfl_xor_sync(~0u, k2048, 16 >> s);
      const C2 s0 = {cb.z, cb.w}, s1 = cm2(s0, {ma.x, ma.y}), s2 = cm2(s0, {ma.z, ma.w}), s3 = cm2(s1, {ma.z, ma.w});
      mma_hf(D[0], s0.re, s1.re, s0.im, s1.im, ca.x, ca.y);
      mma_hf(D[2], s0.re, s1.re, s0.im, s1.im, ca.z, ca.w);
      mma_hf(D[4], s0.re, s1.re, s0.im, s1.im, cb.x, cb.y);
      mma_hf(D[1], s2.re, s3.re, s2.im, s3.im, ca.x, ca.y);
      mma_hf(D[3], s2.re, s3.re, s2.im, s3.im, ca.z, ca.w);
    }
    TS(3);
    const u32 xa = SM_R + (w < 8 ? 4 + ksig : 9) * KTAB + lane * 16;
    if (khf) {
      __syncwarp();
#pragma unroll
      for (int j = 0; j < 5; j++) sts128(xa + 512 * j, fu(D[j][0]), fu(D[j][1]), fu(D[j][2]), fu(D[j][3]));
      if (lane == 0) sts32(xa + 2560, fu(k2048));
      asm volatile("bar.arrive %0,64;" ::"r"(2 + ksig) : "memory");
    } else {
      const u32 tp = SM_TAP + ksig * TAPS;
      const u32 a = 63 + 32 * q + g;
      const u32 t1 = tp + (q < 2 ? (128 + 4 * g + 2 * q) * 4 : T5 * 4 + (a - 64 + 2 * (a & 1)) * 2);
      const u32 x = 63 + hi + 16 * q + (g >> 1), tb = tp + (hi ? TE7 : TE9) * 4;
      const u32 te = tb + (x + 2 * (x & 1)) * 2, to = tb + TEO * 4 + (x ^ 1) * 2;
      asm volatile("bar.sync %0,64;" ::"r"(2 + ksig) : "memory");
#pragma unroll
      for (int j = 0; j < 5; j++) { const uint4 t = lds128(xa + 512 * j); D[j][0] += uf(t.x); D[j][1] += uf(t.y); D[j][2] += uf(t.z); D[j][3] += uf(t.w); }
      k2048 = (k2048 + uf(lds32(xa + 2560))) * 0.125f;
      const float kv512 = __shfl_sync(~0u, D[2][0], 2);
      if (lane == 29) D[3][3] -= kv512;
#pragma unroll
      for (int r = 0; r < 4; r++) {
        const u32 v = pk_hf(D[2 + (r >> 1)][2 * (r & 1)], D[2 + (r >> 1)][2 * (r & 1) + 1]);
        if (q < 2) {
          const u32 vv = __byte_perm(v, v, 0x1010);
          sts32(t1 + (TO + 32 * r) * 4, vv); sts16(t1 + (TO + 32 * r + 1) * 4 + 2, v >> 16); sts16(t1 + (TO + 32 * r - 1) * 4, v);
          sts64(t1 + (TE + 32 * r) * 4, vv, __byte_perm(v, v, 0x1032));
        } else {
          sts16(t1 + 16 * r, v); sts16(t1 + 16 * r + (T3 - T5) * 4, v >> 16);
        }
      }
#pragma unroll
      for (int r = 0; r < 2; r++) {
        const u32 v = pk_hf(D[4][2 * r], D[4][2 * r + 1]);
        if (r == 0 && lane == 0) { sts16(tp + T5 * 4 + 129 * 2, v); sts32(SM_KV + 4 * ksig, v & 0xffff); sts16(tb + TEO * 4 + 126 * 2, pk_hf(k2048, 0.f)); sts32(SM_SC + 16 * ksig + 12, fu(FK)); }
        else { sts16(te + 8 * r, v); sts16(to + 8 * r, v); }
        sts16(te + 8 * r + 16, v >> 16); sts16(to + 8 * r + 16, v >> 16);
      }
      __syncwarp();
#pragma unroll
      for (int r = 0; r < 4; r++) {
        const u32 v = pk_hf(D[r >> 1][2 * (r & 1) + 1], D[r >> 1][2 * (r & 1)]), t2 = tp + lane * 4 + 128 * r;
        sts32(t2 + TO * 4, v); sts16(t2 + TE * 4, v >> 16); sts16(t2 + (TE + 1) * 4 + 2, v);
      }
      __syncwarp();
    }
  } else {
    u32 sa = SM_SIL + 576 * (w & 1) + 24 * min(lane, 23u);
#pragma unroll 1
    for (int j = 0; j < 6; j++) {
      sts32(sa, pk_bf(silu_f(blo(la)), silu_f(bhi(la))));
      la = ai; ai = cr.x; cr.x = cr.y; cr.y = ci.x; ci.x = ci.y; sa += 4;
    }
    __syncwarp();
  }
  TS(6);
  const u32 rl16 = ((lane & 7) + ((lane >> 3) & 1) + 8 * (lane >> 4)) * 16;
  const u32 zl = g * 16 + (q & 1) * 8;
  const u32 tko = (4 * h + 8 * hi) * 1152 + cho + b * 18432;
  uint4 dk, wr, md[6];
#define P2LOAD() { \
    const char* mp_ = gs + mod_off(cho >> 1); \
    _Pragma("unroll") for (int j = 0; j < 6; j++) md[j] = ldr128(mp_ + j * MODJ); \
    _Pragma("unroll") for (int k = 0; k < 4; k++) xv[k] = ldg128(p.x + tko + k * 1152); \
    dk = ldg128(p.dsk + cho); wr = ldg128(p.wr + cho); }
  if (w < 4) {
    asm volatile("setmaxnreg.inc.sync.aligned.u32 232;");
    const u32 tp = SM_TAP + w * TAPS;
    const u32 tr = tp + ((hi ? TO : TE) + (g >> 1) - q) * 4;
    u32 T[33][4], B5[5][2], B3[5][2];
    const u32 pml = (ssrc | zr) ? 0 : pm;
#pragma unroll
    for (int d = 0; d < 33; d++) {
      T[d][0] = lds32(tr + 32 * d); T[d][1] = lds32(tr + 32 * d + 16);
      T[d][2] = d ? cpy(T[d - 1][1], zr, 0) : zr; T[d][3] = cpy(T[d][0], zr, 1);
    }
    const u32 bt = tp + (T5 + g - q) * 4;
#pragma unroll
    for (int d = 0; d < 5; d++) {
      B5[d][0] = lds32(bt + 32 * d + 128); B5[d][1] = lds32(bt + 32 * d + 112);
      B3[d][0] = lds32(bt + 32 * d + 128 + (T3 - T5) * 4); B3[d][1] = lds32(bt + 32 * d + 112 + (T3 - T5) * 4);
    }
    u32 za = SM_ZS + 16 + w * ZSS + (q >> 1) * ZPS + zl;
    u32 wa = SM_R + W5O - 256 + w * WSL + rl16;
    u32 sa = SM_S3 - 2560 + w * 4096 + lane * 16;
    char* yp = gs + (G_Y + 2 * q * 18432 + (Pm + w) * 32 + 4 * g);
    TS(8);
    lds32(za);
    bsync(9, 384);
    TS(11);
    float A[4][4] = {};
    uint2 ring[4];
#pragma unroll
    for (int s = 0; s < 3; s++) ring[s] = lds64(za + 16 * s);
    const uint2 fc = lds64(SM_SC + 16 * w + 8);
    const float F = uf(fc.x) * uf(fc.y);
    const float ZERO[4] = {};
#define DENSE(s) { ring[(s + 3) & 3] = lds64(za + 16 * (s + 3)); \
    _Pragma("unroll") for (int i = 0; i < 4; i++) mma_hf_o(A[i], A[i], T[8 * i + 7 - s], ring[s & 3].x, ring[s & 3].y); }
#define LAST(N) ring[2] = lds64(za + 160); float O[4]; mma_hf_o(O, A[0], T[0], ring[3].x, ring[3].y); \
    _Pragma("unroll") for (int i = 0; i < 3; i++) mma_hf_o(A[i], A[i + 1], T[8 * i + 8], ring[3].x, ring[3].y); \
    mma_hf_o(A[3], N, T[32], ring[3].x, ring[3].y);
#pragma unroll 1
    for (int j = 0; j < 3; j++) {
#pragma unroll
      for (int s = 0; s < 7; s++) DENSE(s);
      LAST(ZERO);
      y_store(O[0], O[1], O[2], O[3], F, pml, yp);
      za += 128; yp += 8 * 18432;
      TS(40 + j);
    }
#pragma unroll 1
    for (int j = 3; j < 13; j++) {
#pragma unroll
      for (int s = 0; s < 5; s++) DENSE(s);
      if (j == 3) bsync(10, 384);
      if (j == 8) bsync(11, 256);
      const uint4 a5 = ldsm4t(wa), a3 = ldsm4t(wa + (W3O - W5O));
      uint4 s3 = {0, 0, 0, 0};
      if (j >= 8) s3 = lds128(sa);
      DENSE(5); DENSE(6);
      float N[4] = {};
      mma_hf(N, a5.x, a5.y, a5.z, a5.w, B5[4][0], B5[4][1]);
#pragma unroll
      for (int i = 0; i < 4; i++) mma_hf(A[i], a5.x, a5.y, a5.z, a5.w, B5[i][0], B5[i][1]);
      mma_hf(N, a3.x, a3.y, a3.z, a3.w, B3[4][0], B3[4][1]);
#pragma unroll
      for (int i = 0; i < 4; i++) mma_hf(A[i], a3.x, a3.y, a3.z, a3.w, B3[i][0], B3[i][1]);
      LAST(N);
      y_store(O[0] + uf(s3.x), O[1] + uf(s3.y), O[2] + uf(s3.z), O[3] + uf(s3.w), F, pml, yp);
      za += 128; wa += 256; sa += 512; yp += 8 * 18432;
      TS(40 + j);
    }
    TS(14);
    P2LOAD();
    {
      float X[3][4] = {};
#pragma unroll
      for (int ty = 0; ty < 2; ty++) {
        const uint4 a = ldsm4t(wa + ty * (W3O - W5O)), c = ldsm4t(wa + 256 + ty * (W3O - W5O)), d = ldsm4t(wa + 512 + ty * (W3O - W5O));
#pragma unroll
        for (int i = 0; i < 3; i++) mma_hf(A[i], a.x, a.y, a.z, a.w, ty ? B3[i][0] : B5[i][0], ty ? B3[i][1] : B5[i][1]);
#pragma unroll
        for (int i = 0; i < 2; i++) mma_hf(X[i], c.x, c.y, c.z, c.w, ty ? B3[i][0] : B5[i][0], ty ? B3[i][1] : B5[i][1]);
        mma_hf(X[2], d.x, d.y, d.z, d.w, ty ? B3[0][0] : B5[0][0], ty ? B3[0][1] : B5[0][1]);
      }
      barrive(12, 288);
#pragma unroll
      for (int s = 0; s < 8; s++) {
        const uint2 f0 = s < 3 ? ring[s] : lds64(za + 16 * s), f1 = lds64(za + 16 * s + 128), f2 = lds64(za + 16 * s + 256);
#pragma unroll
        for (int i = 0; i < 3; i++) mma_hf_o(A[i], A[i], T[8 * i + 7 - s], f0.x, f0.y);
        mma_hf_o(X[0], X[0], T[7 - s], f1.x, f1.y); mma_hf_o(X[1], X[1], T[15 - s], f1.x, f1.y);
        mma_hf_o(X[2], X[2], T[7 - s], f2.x, f2.y);
      }
      const uint4 s0 = lds128(sa), s1 = lds128(sa + 512), s2 = lds128(sa + 1024);
      y_store(A[0][0] + uf(s0.x), A[0][1] + uf(s0.y), A[0][2] + uf(s0.z), A[0][3] + uf(s0.w), F, pml, yp);
      y_store(A[1][0] + X[0][0] + uf(s1.x), A[1][1] + X[0][1] + uf(s1.y), A[1][2] + X[0][2] + uf(s1.z), A[1][3] + X[0][3] + uf(s1.w), F, pml, yp + 8 * 18432);
      y_store(A[2][0] + X[1][0] + (X[2][0] + uf(s2.x)), A[2][1] + X[1][1] + (X[2][1] + uf(s2.y)), A[2][2] + X[1][2] + (X[2][2] + uf(s2.z)), A[2][3] + X[1][3] + (X[2][3] + uf(s2.w)), F, pml, yp + 16 * 18432);
    }
    barrive(13, 288);
    TS(15);
  } else {
    asm volatile("setmaxnreg.dec.sync.aligned.u32 136;");
    const u32 t8 = tid - 128;
#pragma unroll 1
    for (int ph = 0; ph < 2; ph++) {
      if (!kw) {
        const u32 urg = b < 72;
#pragma unroll 1
        for (u32 slot = ph ? urg : 0; slot < (ph ? (b < 88 ? 2 : 1) : urg); slot++) {
          float c[2][4] = {};
          const u32 row = 288 * (w & 1) + (lane & 7) + 8 * (lane >> 4);
          u32 aa = SM_UP + slot * 18432 + row * 32 + ((((lane >> 3) ^ (row >> 2)) & 1) << 4);
          u32 ba = SM_SIL + 576 * (w & 1) + 4 * q;
          mb_wait(SM_MB + 8 * slot);
#pragma unroll 1
          for (int s = 0; s < 3; s++) {
#pragma unroll
            for (int i = 0; i < 6; i++) { const uint4 a = ldsm4t(aa + i * 512); mma_bf(c[i & 1], a.x, a.y, a.z, a.w, lds32(ba + 32 * i), lds32(ba + 32 * i + 16)); }
            aa += 3072; ba += 192;
          }
          float v = (q & 1) ? c[0][2] + c[1][2] : c[0][0] + c[1][0];
          if (w & 1) sts32(SM_GP + lane * 4, fu(v));
          bsync(7, 64);
          v += uf(lds32(SM_GP + lane * 4));
          if (!(w & 1) && q < 2) str16(gs + (G_MOD + (b + 128 * slot) * 128 + 2 * g + 16 * q), pk_bf(rbf(v) * F2M64, 0.f) | (g < 2 ? pm : 0));
          bsync(7, 64);
        }
      }
      if (ph) break;
      TS(12);
      const char* zs = gs + ((t8 >> 3) * 18432 + Pm * 32 + (t8 & 7) * 16);
      const char* zs4 = gs + ((t8 >> 1) * 18432 + Ps * 32 + (t8 & 1) * 16);
      uint4 v[5];
#pragma unroll
      for (int j = 0; j < 5; j++) v[j].x = INVAL;
      POLL(_Pragma("unroll") for (int j = 0; j < 5; j++) if ((v[j].x ^ pm) & TAGM) v[j] = ldr128(j < 4 ? zs + j * 32 * 18432 : zs4),
           ((v[0].x ^ pm) | (v[1].x ^ pm) | (v[2].x ^ pm) | (v[3].x ^ pm) | (v[4].x ^ pm)) & TAGM, 1);
      TS(9);
      if (w == 11) {
        const u32 d = chan_of(lane < 4 ? Pm + lane : Ps);
        const char* mp = gs + mod_off(d);
        uint4 ta, tc;
        POLL({ ta = ldr128(mp); tc = ldr128(mp + MODJ); }, ((ta.x ^ pm) | (tc.x ^ pm)) & TAGM, 2);
        const u32 aw = (d & 4) ? ((d & 2) ? ta.w : ta.z) : ((d & 2) ? ta.y : ta.x & ~TAGM);
        const u32 cw = (d & 4) ? ((d & 2) ? tc.w : tc.z) : ((d & 2) ? tc.y : tc.x & ~TAGM);
        const float sa = ((d & 1) ? bhi(aw) : blo(aw)) * F2P64, c1 = rbf(fmaf((d & 1) ? bhi(cw) : blo(cw), F2P64, 1.f));
        const u32 EM = min(max(fu(fmaxf(32.f * fabsf(c1), fabsf(sa))) >> 23, 80u), 250u);
        const float inv = uf((264 - EM) << 23);
        if (lane < 5) { sts64(SM_SC + 16 * lane, pk_hf(16.f * c1 * inv, 16.f * c1 * inv), pk_hf(sa * inv, sa * inv)); sts32(SM_SC + 16 * lane + 8, (EM - 74) << 23); }
        TS(10);
      }
      const u32 dst = SM_ZS + 128 + (t8 & 6) * (ZSS / 2) + (t8 & 1) * ZPS + (t8 >> 3) * 16;
      const u32 sig = t8 / 51, i0 = t8 - 51 * sig;
      bsync(8, 256);
      const uint2 cc = lds64(SM_SC + 8 * (t8 & 6)), c4 = lds64(SM_SC + 64);
#pragma unroll
      for (int j = 0; j < 5; j++) {
        const uint2 c = j < 4 ? cc : c4;
        sts128(j < 4 ? dst + j * 512 : SM_Z4 + (t8 & 1) * ZP4 + (t8 >> 1) * 16, hfma(v[j].x & ~TAGM, c.x, c.y), hfma(v[j].y, c.x, c.y), hfma(v[j].z, c.x, c.y), hfma(v[j].w, c.x, c.y));
      }
      bsync(9, 384);
      TS(11);
#pragma unroll 1
      for (int rd = 0; rd < 2; rd++) {
        const u32 i = i0 + 51 * rd;
        if (sig < 5 && i < 97 && !X_NOWPREP) {
          const u32 za = (sig < 4 ? SM_ZS + 128 + sig * ZSS : SM_Z4) + i * 16, zb = za + (sig < 4 ? ZPS : ZP4);
          const uint4 c2 = lds128(zb - 32), a1 = lds128(za - 16), b1 = lds128(zb - 16), a0 = lds128(za), b0 = lds128(zb);
          const u32 P[17] = {c2.y, c2.w, a1.x, a1.z, b1.x, b1.z, a1.y, a1.w, b1.y, b1.w, a0.x, a0.z, b0.x, b0.z, a0.y, a0.w, b0.y};
          u32 Q[17], D1[15], F4[15], W5[13], D2[17];
#pragma unroll
          for (int j = 1; j < 17; j++) Q[j] = __byte_perm(P[j - 1], P[j], 0x5432);
#pragma unroll
          for (int j = 1; j < 15; j++) D1[j] = hadd(P[j], Q[j]);
#pragma unroll
          for (int j = 2; j < 15; j++) F4[j] = hadd(D1[j], D1[j - 1]);
#pragma unroll
          for (int n = 0; n < 13; n++) W5[n] = hadd(F4[n + 2], P[n]);
#pragma unroll
          for (int j = 5; j < 17; j++) D2[j] = hadd(Q[j], P[j - 1]);
          const u32 wa = SM_R + sig * WSL + i * 16, wb = wa + i * 16;
          u32 o[8];
#pragma unroll
          for (int n = 0; n < 8; n++) o[n] = hadd(D2[n + 5], Q[n + 4]);
          sts128(wb + W5O, W5[5], W5[6], W5[7], W5[8]); sts128(wb + W3O, o[0], o[1], o[2], o[3]);
          if (i < 96) { sts128(wb + W5O + 16, W5[9], W5[10], W5[11], W5[12]); sts128(wb + W3O + 16, o[4], o[5], o[6], o[7]); }
          if (i < 16) { sts128(wa, 0, 0, 0, 0); sts128(wa + W3O - 256, 0, 0, 0, 0); }
          if (i < 64) {
#pragma unroll
            for (int n = 0; n < 8; n++) o[n] = hadd(F4[n + 4], W5[n]);
            sts128(wa + W9O, o[0], o[1], o[2], o[3]); sts128(wa + W9O + 1024, o[4], o[5], o[6], o[7]);
#pragma unroll
            for (int n = 0; n < 8; n++) o[n] = hadd(hadd(Q[n + 8], Q[n + 5]), W5[n + 5]);
            sts128(wa + W7O, o[0], o[1], o[2], o[3]); sts128(wa + W7O + 1024, o[4], o[5], o[6], o[7]);
            sts128(wa + V2O, D2[9], D2[10], D2[11], D2[12]); sts128(wa + V2O + 1024, D2[13], D2[14], D2[15], D2[16]);
          }
        }
        __syncwarp();
        TS(32 + rd);
        if (rd == 0) barrive(10, 384);
      }
      if (w >= 8) barrive(15, 256);
    }
    if (w < 8) {
      bsync(15, 256);
      TS(13);
#pragma unroll 1
      for (u32 sl = w - 4; !X_NOSEG3; sl = 4) {
        const u32 wa = SM_R + sl * WSL + ((lane >> 3) & 1) * 1024 + ((lane & 7) + 8 * (lane >> 4)) * 16;
        const u32 kv = lds32(SM_KV + 4 * sl), bi = (g >> 1) == q ? (hi ? kv << 16 : kv) : 0u;
        float acc[8][4] = {};
#pragma unroll
        for (int j = 0; j < 4; j++) { const uint4 a = ldsm4t(wa + V2O + j * 256); mma8_hf(acc[2 * j], a.x, a.y, bi); mma8_hf(acc[2 * j + 1], a.z, a.w, bi); }
        u32 bt = SM_TAP + sl * TAPS + (TE9 + hi * TEO + (g >> 1) - q) * 4, wt = wa + W9O;
#pragma unroll 1
        for (int ty = 0; ty < 2; ty++) {
          uint4 a[4];
#pragma unroll
          for (int be = 0; be < 4; be++) a[be] = ldsm4t(wt + be * 256);
          u32 b1 = lds32(bt + 112);
#pragma unroll
          for (int d = 0; d < 8; d++) {
            const u32 b0 = lds32(bt + 16 * d + 128);
#pragma unroll
            for (int be = 0; be < 4; be++) if (d + 2 * be < 8) mma_hf(acc[d + 2 * be], a[be].x, a[be].y, a[be].z, a[be].w, b0, b1);
            b1 = b0;
          }
          bt += (TE7 - TE9) * 4; wt += W7O - W9O;
        }
#pragma unroll
        for (int j = 0; j < 8; j++) sts128(SM_S3 + sl * 4096 + j * 512 + lane * 16, fu(acc[j][0]), fu(acc[j][1]), fu(acc[j][2]), fu(acc[j][3]));
        if (w != 4 || sl == 4) break;
      }
      TS(34);
      barrive(11, 256);
      const int u0 = 4 * (w - 4) + 2 * rho;
      const u32 tp = SM_TAP + 4 * TAPS;
      u32 tr = tp + ((hi ? TO : TE) + (g >> 1) - q) * 4;
      u32 zb = SM_Z4 + (q >> 1) * ZP4 + u0 * 128 + zl;
      float acc[4][4] = {};
      uint2 R[8];
#pragma unroll
      for (int j = 0; j < 8; j++) R[j] = lds64(zb + 128 - 16 * j);
      u32 prev = 0;
#pragma unroll 1
      for (int it = 0; it < (X_NOSH ? 0 : 4); it++) {
#pragma unroll
        for (int s = 0; s < 8; s++) {
          const uint2 nw = lds64(zb - 16 * s);
          const u32 t0 = lds32(tr + 32 * s), t1 = lds32(tr + 32 * s + 16);
          mma_hf(acc[2 + (s & 1)], t0, t1, prev, t0, R[s].x, R[s].y);
          mma_hf(acc[s & 1], t0, t1, prev, t0, nw.x, nw.y);
          R[s] = nw; prev = t1;
        }
        zb -= 128; tr += 256;
      }
      { const uint2 nw = lds64(zb); const u32 t0 = lds32(tr); mma_hf(acc[2], t0, 0, prev, t0, R[0].x, R[0].y); mma_hf(acc[0], t0, 0, prev, t0, nw.x, nw.y); }
#pragma unroll 1
      for (int d = X_NOSH ? 0 : min(u0 + 1, 8); d >= 3; d--) {
        const u32 wa = SM_R + 4 * WSL + W5O + rl16 + (u0 - d) * 256, bt = tp + (T5 + g - q) * 4 + 32 * d;
#pragma unroll
        for (int ty = 0; ty < 2; ty++) {
          const uint4 a = ldsm4t(wa + ty * (W3O - W5O));
          const u32 bb = bt + ty * (T3 - T5) * 4;
          mma_hf(acc[ty], a.x, a.y, a.z, a.w, lds32(bb), lds32(bb - 16));
          mma_hf(acc[2 + ty], a.x, a.y, a.z, a.w, lds32(bb + 32), lds32(bb + 16));
        }
      }
      TS(35);
      barrive(12, 288);
      bsync(14, 128);
      const uint2 fc = lds64(SM_SC + 16 * 4 + 8);
      const float F = uf(fc.x) * uf(fc.y);
      char* yp = gs + (G_Y + (8 * u0 + 2 * q) * 18432 + Ps * 32 + 4 * g);
      const u32 pml = ssrc ? 0 : pm;
#pragma unroll
      for (int j = 0; j < 2; j++) {
        uint4 s3 = {0, 0, 0, 0};
        if (u0 >= 8) s3 = lds128(SM_S3 + 4 * 4096 + (u0 - 8 + j) * 512 + lane * 16);
        y_store(acc[2 * j][0] + acc[2 * j + 1][0] + uf(s3.x), acc[2 * j][1] + acc[2 * j + 1][1] + uf(s3.y), acc[2 * j][2] + acc[2 * j + 1][2] + uf(s3.z),
                acc[2 * j][3] + acc[2 * j + 1][3] + uf(s3.w), F, pml, yp + j * 8 * 18432);
      }
      TS(16);
    } else if (w == 9) {
      if (lane == 0) tma3d(SM_UP, &tm_up, SM_MB + 24, 46080, 8 * Pm, 0);
      TS(17);
      bsync(12, 288);
      if (lane == 0) {
        asm volatile("fence.proxy.async.shared::cta;" ::: "memory");
        tma3d(SM_WD, &tm_down, SM_MB + 32, 41472, 72 * (b & 7), 2 * (b >> 3));
      }
    } else if (w == 10) {
      float s1 = 0.f, s2 = 0.f;
#pragma unroll 1
      for (u32 j = lane; j < 96; j += 32) {
        const u32 jj = min(j, 71u);
        const char* mp = gs + mod_off(8 * jj);
        uint4 a, c, r = ldg128(p.wr + 16 * jj);
        POLL({ a = ldr128(mp + 3 * MODJ); c = ldr128(mp + 4 * MODJ); }, ((a.x ^ pm) | (c.x ^ pm)) & TAGM, 3);
        a.x &= ~TAGM; c.x &= ~TAGM;
#pragma unroll 1
        for (int i = j < 72 ? 0 : 4; i < 4; i++) {
          const u32 c1 = bfma(c.x, B2P64, BONE), s = bmul(a.x, B2P64);
          s1 = fmaf(blo(c1), blo(r.x), s1); s1 = fmaf(bhi(c1), bhi(r.x), s1);
          s2 = fmaf(blo(s), blo(r.x), s2); s2 = fmaf(bhi(s), bhi(r.x), s2);
          a.x = a.y; a.y = a.z; a.z = a.w; c.x = c.y; c.y = c.z; c.z = c.w; r.x = r.y; r.y = r.z; r.z = r.w;
        }
      }
#pragma unroll 1
      for (int o = 16; o; o >>= 1) { s1 += __shfl_xor_sync(~0u, s1, o); s2 += __shfl_xor_sync(~0u, s2, o); }
      sts64(SM_RC, fu(s1), fu(s2));
      TS(31);
      barrive(1, 320);
    }
    if (w < 9) P2LOAD();
  }
  post_conv(p, tid + p.zero, b, ep, xv, dk, wr, md);
  if (tid == 352 && s2u(smem) != SM0) __trap();
}

typedef CUresult (*EncFn)(CUtensorMap*, CUtensorMapDataType, cuuint32_t, void*, const cuuint64_t*, const cuuint64_t*, const cuuint32_t*, const cuuint32_t*,
                          CUtensorMapInterleave, CUtensorMapSwizzle, CUtensorMapL2promotion, CUtensorMapFloatOOBfill);
static void make_map(EncFn enc, CUtensorMap* tm, void* ptr, int cols, int rows, int bw, int br, int nb, CUtensorMapSwizzle sw) {
  cuuint64_t gd[3] = {(cuuint64_t)cols, (cuuint64_t)br, (cuuint64_t)(rows / br)}, gs[2] = {(cuuint64_t)cols * 2, (cuuint64_t)cols * 2 * br};
  cuuint32_t bd[3] = {(cuuint32_t)bw, (cuuint32_t)br, (cuuint32_t)nb}, es[3] = {1, 1, 1};
  enc(tm, CU_TENSOR_MAP_DATA_TYPE_BFLOAT16, 3, ptr, gd, gs, bd, es, CU_TENSOR_MAP_INTERLEAVE_NONE, sw, CU_TENSOR_MAP_L2_PROMOTION_NONE, CU_TENSOR_MAP_FLOAT_OOB_FILL_NONE);
}
extern "C" void kernel_launch(void* const* d_in, const int* in_sizes, int n_in, void* d_out, int out_size) {
  static EncFn enc = nullptr;
  static void* scratch = nullptr;
  if (!enc) {
    cudaGetSymbolAddress(&scratch, g_s);
    cudaDriverEntryPointQueryResult qr;
    cudaGetDriverEntryPoint("cuTensorMapEncodeTiled", (void**)&enc, cudaEnableDefault, &qr);
    cudaFuncSetAttribute(fused_kernel, cudaFuncAttributeMaxDynamicSharedMemorySize, SM_TOTAL);
  }
  CUtensorMap tm_mod, tm_gate, tm_up, tm_down;
  make_map(enc, &tm_mod, d_in[13], 3456, 576, 16, 192, 3, CU_TENSOR_MAP_SWIZZLE_32B);
  make_map(enc, &tm_gate, d_in[9], 4608, 576, 40, 192, 3, CU_TENSOR_MAP_SWIZZLE_NONE);
  make_map(enc, &tm_up, d_in[10], 4608, 576, 40, 192, 3, CU_TENSOR_MAP_SWIZZLE_NONE);
  make_map(enc, &tm_down, d_in[11], 576, 4608, 72, 144, 2, CU_TENSOR_MAP_SWIZZLE_NONE);
  Prm p;
  p.x = (const char*)d_in[0]; p.la = (const char*)d_in[1]; p.ai = (const char*)d_in[2]; p.cr = (const char*)d_in[3];
  p.ci = (const char*)d_in[4]; p.ldt = (const char*)d_in[5]; p.dsk = (const char*)d_in[6]; p.wr = (const char*)d_in[8];
  p.c = (const char*)d_in[12]; p.out = (char*)d_out; p.zero = 0; p.gs = (char*)scratch;
  fused_kernel<<<128, 384, SM_TOTAL>>>(p, tm_mod, tm_gate, tm_up, tm_down);
}
```

```cpp
#include <cuda_runtime.h>
#include <cuda.h>
#include <cuda_bf16.h>
#include <cuda_fp16.h>
#include <stdint.h>
#define FUSED 1
#define DEV __device__ __forceinline__
typedef uint32_t u32;

constexpr u32 BLK = 18432, G_Z = 0, G_Y = 128 * BLK, G_MOD = 2 * G_Y, G_KEY = G_MOD + 128 * 128, G_ACT = G_KEY + 128 * 128;
constexpr u32 G_PART = G_ACT + 576 * 128, G_EP = G_PART + 128 * 2048, G_END = G_EP + 128;
__device__ __align__(128) unsigned char g_s[G_END];
#define TS(i)
#define TS0()
#define TSE()
#define ERRF(code)

constexpr int SM0 = 1024;
constexpr int ROW = 1168, SLV = 36864;
constexpr int SM_GATE = SM0, SM_UP = SM_GATE + 46080, SM_XST = SM_UP + 46080, SM_MODS = SM_XST + 16 * ROW, SM_W = SM_MODS + 11008;
constexpr int KTAB = 9216, WSL = 12544, W5O = 128, W3O = 3328, V2O = 6400, W9O = 8448, W7O = 10496;
constexpr int ZPS = 2192, ZSS = 2 * ZPS, ZP4 = 2368;
constexpr int SM_ZS = SM_W + 5 * WSL, SM_Z4 = SM_ZS + 4 * ZSS, SM_TAP = SM_Z4 + 2 * ZP4, TAPS = 3328;
constexpr int SM_MB = SM_TAP + 5 * TAPS;
constexpr int SM_SC = SM_MB + 32;
constexpr int SM_KV = SM_SC + 80;
constexpr int SM_THR = SM_KV + 32;
constexpr int SM_SLOT = SM_THR + 48;
constexpr int SM_KEY = SM_SLOT + 32;
constexpr int SM_ST = SM_KEY + 64;
constexpr int SM_ST2 = SM_ST + 256;
constexpr int SM_RC = SM_ST2 + 256;
constexpr int SM_SP = SM_RC + 192;
constexpr int SM_AF = SM_SP + 1152, SM_SIL = SM_AF + 1152, SM_END = SM_SP + 5760;
constexpr int SM_ONE = SM_MODS + 9 * 1152;
constexpr int SM_WD = SM_W, SM_XS = SM_W + 49152, SM_AC = SM_ZS, SM_RED = SM_AC + 6144, SM_LIST = SM_TAP;
constexpr int SM_TOTAL = SM_END - SM0;
static_assert(SM_W % 1024 == 0 && SM_MODS + 8 * KTAB <= SM_ZS && SM_ZS + 2 * KTAB <= SM_TAP && SM_RED + 10240 <= SM_TAP && SM_XS + 8 * ROW <= SM_ZS, "smem map");
static_assert(SM_MB % 16 == 0 && SM_THR % 16 == 0 && SM_ST % 16 == 0 && SM_SP % 16 == 0 && SM_TOTAL <= 232448, "smem map");
constexpr int TE = 4, TO = 276, T5 = 560, T3 = 624, T9E = 680, T7E = 760, TEO = 40;
constexpr int SPIN = 1 << 16, NEARLY = 4;
constexpr u32 TAGM = 0x40004000u, TAGR = 0x40000000u, INVAL = 0x00004801u;

DEV u32 s2u(const void* p) { return (u32)__cvta_generic_to_shared(p); }
DEV void mma_bf(float (&c)[4], u32 a0, u32 a1, u32 a2, u32 a3, u32 b0, u32 b1) {
  asm("mma.sync.aligned.m16n8k16.row.col.f32.bf16.bf16.f32 {%0,%1,%2,%3},{%4,%5,%6,%7},{%8,%9},{%0,%1,%2,%3};"
      : "+f"(c[0]), "+f"(c[1]), "+f"(c[2]), "+f"(c[3]) : "r"(a0), "r"(a1), "r"(a2), "r"(a3), "r"(b0), "r"(b1));
}
DEV void mma_hf(float (&c)[4], u32 a0, u32 a1, u32 a2, u32 a3, u32 b0, u32 b1) {
  asm("mma.sync.aligned.m16n8k16.row.col.f32.f16.f16.f32 {%0,%1,%2,%3},{%4,%5,%6,%7},{%8,%9},{%0,%1,%2,%3};"
      : "+f"(c[0]), "+f"(c[1]), "+f"(c[2]), "+f"(c[3]) : "r"(a0), "r"(a1), "r"(a2), "r"(a3), "r"(b0), "r"(b1));
}
DEV void mma8_bf(float (&c)[4], u32 a0, u32 a1, u32 b0) {
  asm("mma.sync.aligned.m16n8k8.row.col.f32.bf16.bf16.f32 {%0,%1,%2,%3},{%4,%5},{%6},{%0,%1,%2,%3};"
      : "+f"(c[0]), "+f"(c[1]), "+f"(c[2]), "+f"(c[3]) : "r"(a0), "r"(a1), "r"(b0));
}
DEV void mma8_hf(float (&c)[4], u32 a0, u32 a1, u32 b0) {
  asm("mma.sync.aligned.m16n8k8.row.col.f32.f16.f16.f32 {%0,%1,%2,%3},{%4,%5},{%6},{%0,%1,%2,%3};"
      : "+f"(c[0]), "+f"(c[1]), "+f"(c[2]), "+f"(c[3]) : "r"(a0), "r"(a1), "r"(b0));
}
DEV u32 movm(u32 x) { u32 r; asm("movmatrix.sync.aligned.m8n8.trans.b16 %0,%1;" : "=r"(r) : "r"(x)); return r; }
DEV uint4 ldsm4(u32 a) { uint4 r; asm volatile("ldmatrix.sync.aligned.m8n8.x4.shared.b16 {%0,%1,%2,%3},[%4];" : "=r"(r.x), "=r"(r.y), "=r"(r.z), "=r"(r.w) : "r"(a)); return r; }
DEV uint4 ldsm4t(u32 a) { uint4 r; asm volatile("ldmatrix.sync.aligned.m8n8.x4.trans.shared.b16 {%0,%1,%2,%3},[%4];" : "=r"(r.x), "=r"(r.y), "=r"(r.z), "=r"(r.w) : "r"(a)); return r; }
DEV u32 lds32(u32 a) { u32 r; asm volatile("ld.volatile.shared.u32 %0,[%1];" : "=r"(r) : "r"(a)); return r; }
DEV uint2 lds64(u32 a) { uint2 r; asm volatile("ld.shared.v2.u32 {%0,%1},[%2];" : "=r"(r.x), "=r"(r.y) : "r"(a)); return r; }
DEV uint4 lds128(u32 a) { uint4 r; asm volatile("ld.shared.v4.u32 {%0,%1,%2,%3},[%4];" : "=r"(r.x), "=r"(r.y), "=r"(r.z), "=r"(r.w) : "r"(a)); return r; }
DEV void sts16(u32 a, u32 v) { asm volatile("st.shared.u16 [%0],%1;" ::"r"(a), "h"((unsigned short)v) : "memory"); }
DEV void sts32(u32 a, u32 v) { asm volatile("st.shared.u32 [%0],%1;" ::"r"(a), "r"(v) : "memory"); }
DEV void sts64(u32 a, u32 x, u32 y) { asm volatile("st.shared.v2.u32 [%0],{%1,%2};" ::"r"(a), "r"(x), "r"(y) : "memory"); }
DEV void sts128(u32 a, u32 x, u32 y, u32 z, u32 w) { asm volatile("st.shared.v4.u32 [%0],{%1,%2,%3,%4};" ::"r"(a), "r"(x), "r"(y), "r"(z), "r"(w) : "memory"); }
DEV uint4 ldr128(const void* p) { uint4 v; asm volatile("ld.relaxed.gpu.global.v4.u32 {%0,%1,%2,%3},[%4];" : "=r"(v.x), "=r"(v.y), "=r"(v.z), "=r"(v.w) : "l"(p) : "memory"); return v; }
DEV uint2 ldr64(const void* p) { uint2 v; asm volatile("ld.relaxed.gpu.global.v2.u32 {%0,%1},[%2];" : "=r"(v.x), "=r"(v.y) : "l"(p) : "memory"); return v; }
DEV u32 ldr32(const void* p) { u32 v; asm volatile("ld.relaxed.gpu.global.u32 %0,[%1];" : "=r"(v) : "l"(p) : "memory"); return v; }
DEV void str128(void* p, u32 x, u32 y, u32 z, u32 w) { asm volatile("st.relaxed.gpu.global.v4.u32 [%0],{%1,%2,%3,%4};" ::"l"(p), "r"(x), "r"(y), "r"(z), "r"(w) : "memory"); }
DEV void str64(void* p, u32 x, u32 y) { asm volatile("st.relaxed.gpu.global.v2.u32 [%0],{%1,%2};" ::"l"(p), "r"(x), "r"(y) : "memory"); }
DEV void str32(void* p, u32 x) { asm volatile("st.relaxed.gpu.global.u32 [%0],%1;" ::"l"(p), "r"(x) : "memory"); }
DEV void str16(void* p, u32 x) { asm volatile("st.relaxed.gpu.global.u16 [%0],%1;" ::"l"(p), "h"((unsigned short)x) : "memory"); }
DEV uint4 ldg128(const void* p) { uint4 v; asm volatile("ld.global.nc.v4.u32 {%0,%1,%2,%3},[%4];" : "=r"(v.x), "=r"(v.y), "=r"(v.z), "=r"(v.w) : "l"(p)); return v; }
DEV uint2 ldg64(const void* p) { uint2 v; asm volatile("ld.global.nc.v2.u32 {%0,%1},[%2];" : "=r"(v.x), "=r"(v.y) : "l"(p)); return v; }
DEV u32 ldg32(const void* p) { u32 v; asm volatile("ld.global.nc.u32 %0,[%1];" : "=r"(v) : "l"(p)); return v; }
DEV u32 ldg16(const void* p) { unsigned short v; asm volatile("ld.global.nc.u16 %0,[%1];" : "=h"(v) : "l"(p)); return v; }
#define bsync(id, n) asm volatile("bar.sync %0,%1;" ::"n"(id), "n"(n) : "memory")
#define barrive(id, n) asm volatile("bar.arrive %0,%1;" ::"n"(id), "n"(n) : "memory")
DEV void mb_init(u32 a) { asm volatile("mbarrier.init.shared.b64 [%0],1;" ::"r"(a) : "memory"); }
DEV void mb_expect(u32 a, u32 bytes) { asm volatile("mbarrier.arrive.expect_tx.shared.b64 _,[%0],%1;" ::"r"(a), "r"(bytes) : "memory"); }
DEV void mb_wait(u32 a) {
  u32 ok; int it = 0;
  do { asm volatile("{.reg .pred p; mbarrier.try_wait.parity.shared.b64 p,[%1],0; selp.u32 %0,1,0,p;}" : "=r"(ok) : "r"(a) : "memory"); } while (!ok && ++it < SPIN);
}
DEV void bulk_out(void* dst, u32 src) { asm volatile("cp.async.bulk.global.shared::cta.bulk_group [%0],[%1],1152;" ::"l"(dst), "r"(src) : "memory"); }
DEV void tma3d(u32 dst, const CUtensorMap* tm, u32 mb, int c0, int c2) {
  asm volatile("cp.async.bulk.tensor.3d.shared::cluster.global.mbarrier::complete_tx::bytes [%0],[%1,{%3,0,%4}],[%2];"
               ::"r"(dst), "l"((uint64_t)tm), "r"(mb), "r"(c0), "r"(c2) : "memory");
}
DEV float blo(u32 w) { return __uint_as_float(w << 16); }
DEV float bhi(u32 w) { return __uint_as_float(w & 0xffff0000u); }
DEV u32 pk_bf(float lo, float hi) { u32 r; asm("cvt.rn.bf16x2.f32 %0,%1,%2;" : "=r"(r) : "f"(hi), "f"(lo)); return r; }
DEV u32 pk_hf(float lo, float hi) { u32 r; asm("cvt.rn.f16x2.f32 %0,%1,%2;" : "=r"(r) : "f"(hi), "f"(lo)); return r; }
DEV float rbf(float x) { return __uint_as_float(pk_bf(0.f, x) & 0xffff0000u); }
DEV u32 bfma(u32 a, u32 b, u32 c) { u32 r; asm("fma.rn.bf16x2 %0,%1,%2,%3;" : "=r"(r) : "r"(a), "r"(b), "r"(c)); return r; }
DEV u32 bmul(u32 a, u32 b) { u32 r; asm("mul.rn.bf16x2 %0,%1,%2;" : "=r"(r) : "r"(a), "r"(b)); return r; }
DEV u32 badd(u32 a, u32 b) { u32 r; asm("add.rn.bf16x2 %0,%1,%2;" : "=r"(r) : "r"(a), "r"(b)); return r; }
DEV u32 hadd(u32 a, u32 b) { u32 r; asm("add.rn.f16x2 %0,%1,%2;" : "=r"(r) : "r"(a), "r"(b)); return r; }
DEV u32 hfma(u32 a, u32 b, u32 c) { u32 r; asm("fma.rn.f16x2 %0,%1,%2,%3;" : "=r"(r) : "r"(a), "r"(b), "r"(c)); return r; }
struct C2 { u32 re, im; };
DEV C2 cm2(C2 a, C2 b) {
  const __half2 ar = *reinterpret_cast<__half2*>(&a.re), ai = *reinterpret_cast<__half2*>(&a.im), br = *reinterpret_cast<__half2*>(&b.re), bi = *reinterpret_cast<__half2*>(&b.im);
  __half2 re = __hfma2(ar, br, __hneg2(__hmul2(ai, bi))), im = __hfma2(ar, bi, __hmul2(ai, br));
  return {*reinterpret_cast<u32*>(&re), *reinterpret_cast<u32*>(&im)};
}
DEV C2 pk2(const float2 (&a)[2]) { return {pk_hf(a[0].x, a[1].x), pk_hf(a[0].y, a[1].y)}; }
DEV C2 pk2c(const float2 (&a)[2]) { return {pk_hf(a[0].x, a[1].x), pk_hf(-a[0].y, -a[1].y)}; }
DEV u32 cpy(u32 x, u32 zr, int alt) {
  u32 r;
  if (alt) asm volatile("xor.b32 %0,%1,%2;" : "=r"(r) : "r"(x), "r"(zr)); else asm volatile("mad.lo.u32 %0,%2,%2,%1;" : "=r"(r) : "r"(x), "r"(zr));
  return r;
}
DEV float ex2(float x) { float r; asm("ex2.approx.ftz.f32 %0,%1;" : "=f"(r) : "f"(x)); return r; }
DEV float rcpf(float x) { float r; asm("rcp.approx.ftz.f32 %0,%1;" : "=f"(r) : "f"(x)); return r; }
DEV float2 cmul(float2 a, float2 b) { return make_float2(fmaf(a.x, b.x, -a.y * b.y), fmaf(a.x, b.y, a.y * b.x)); }
DEV float2 csq(float2 a) { return make_float2(fmaf(a.x, a.x, -a.y * a.y), (a.x + a.x) * a.y); }
DEV float2 cexp(float lr2, float th) {
  const float m = ex2(lr2);
  return make_float2(m * __cosf(th), m * __sinf(th));
}
DEV float silu_f(float v) { return v * rcpf(1.f + ex2(-1.4426950408889634f * v)); }
constexpr u32 B2P64 = 0x5F805F80u, B2M64 = 0x1F801F80u, BONE = 0x3F803F80u;
constexpr u32 MODJ = 18 * 128;
DEV float sqrta(float x) { float r; asm("sqrt.approx.ftz.f32 %0,%1;" : "=f"(r) : "f"(x)); return r; }
DEV u32 fu(float x) { return __float_as_uint(x); }
DEV float uf(u32 x) { return __uint_as_float(x); }
DEV void mma_hf_o(float (&d)[4], const float (&c)[4], const u32 (&a)[4], u32 b0, u32 b1) {
  asm("mma.sync.aligned.m16n8k16.row.col.f32.f16.f16.f32 {%0,%1,%2,%3},{%4,%5,%6,%7},{%8,%9},{%10,%11,%12,%13};"
      : "=f"(d[0]), "=f"(d[1]), "=f"(d[2]), "=f"(d[3]) : "r"(a[0]), "r"(a[1]), "r"(a[2]), "r"(a[3]), "r"(b0), "r"(b1), "f"(c[0]), "f"(c[1]), "f"(c[2]), "f"(c[3]));
}

DEV void cpa16(u32 dst, const void* src) { asm volatile("cp.async.cg.shared.global [%0],[%1],16;" ::"r"(dst), "l"(src) : "memory"); }
DEV void tm_pre(const CUtensorMap* tm) { asm volatile("prefetch.tensormap [%0];" ::"l"((uint64_t)tm) : "memory"); }
#define PROXY_FENCE() asm volatile("fence.proxy.async.shared::cta;" ::: "memory")
struct Prm {
  const char *x, *la, *ai, *cr, *ci, *ldt, *c;
  char* gs;
  const char *dsk, *wr;
  char* out;
  u32 zero;
};
constexpr float LOG2E = 1.4426950408889634f, F2P64 = 1.8446744073709552e19f, F2M64 = 5.421010862427522e-20f;

DEV void y_store(float c0, float c1, float c2, float c3, u32 F, u32 pml, char* yp) {
  str32(yp, bmul(pk_bf(c0, c2), F) | pml);
  str32(yp + BLK, bmul(pk_bf(c1, c3), F) | pml);
}
#define POLL(load, cond_bad, code) { int it_ = 0; do { load; if (++it_ > SPIN) { ERRF(code); break; } } while (__any_sync(~0u, (cond_bad))); }
#define POLLW(load, cond_bad, code) { int it_ = 0; while (__any_sync(~0u, (cond_bad))) { if (++it_ > SPIN) { ERRF(code); break; } load; } }

DEV void post_conv(const Prm& p, const u32 tid, const u32 b, const u32 ep) {
  const u32 w = tid >> 5, lane = tid & 31;
  const u32 g = lane >> 2, q = lane & 3, e = g >> 2, h = (g >> 1) & 1, hi = g & 1;
  const u32 rho = b & 1, par = (ep + 1) & 1, pm = par ? TAGM : 0;
  char* const gs = p.gs;
  const u32 cho = 128 * w + 64 * e + 16 * q;
  u32 x1[4][4], h2[4][4], key[4], lt;
  char* const rowp = gs + (b * BLK + (4 * h + 8 * hi) * 1152 + cho);
  if (w < 9) {
    const char* ysrc = gs + (G_Y + b * BLK + w * 2048 + (q >> 1) * 1024 + (g >> 1) * 256 + hi * 32 + (q & 1) * 16);
    uint4 yv[4];
    if (w < 4) {
#pragma unroll
      for (int v = 0; v < 4; v++) yv[v] = ldr128(ysrc + 64 * v);
    } else {
#pragma unroll
      for (int v = 0; v < 4; v++) yv[v].x = INVAL;
    }
    const u32 ma = SM_MODS + cho, xa = SM_XST + (2 * h + 4 * hi) * ROW + cho;
    const uint4 sa = lds128(ma), ca = lds128(ma + 1152), ga = lds128(ma + 2304), dk = lds128(ma + 6912);
    const uint4 rb = lds128((g & 2) ? SM_ONE + 16 * hi : (ma ^ 64) + 8064 + 1152 * hi);
    const u32 saw[4] = {sa.x, sa.y, sa.z, sa.w}, caw[4] = {ca.x, ca.y, ca.z, ca.w}, gaw[4] = {ga.x, ga.y, ga.z, ga.w}, dw[4] = {dk.x, dk.y, dk.z, dk.w};
    u32 hD[4][4];
#pragma unroll
    for (int k = 0; k < 4; k++) {
      const uint4 st = lds128(SM_ST + 16 * (2 * h + 4 * hi + (k & 1) + 8 * (k >> 1))), xv = lds128(xa + ((k & 1) + 8 * (k >> 1)) * ROW);
      x1[k][0] = xv.x; x1[k][1] = xv.y; x1[k][2] = xv.z; x1[k][3] = xv.w;
#pragma unroll
      for (int v = 0; v < 4; v++) {
        const u32 d = badd(x1[k][v], st.x), z = bfma(d, st.y, bmul(d, st.z));
        hD[k][v] = bmul(badd(bmul(z, caw[v]), saw[v]), dw[v]);
      }
    }
    const bool own = (q >> 1) == e;
    const u32 spw = SM_SP + (2 * w + e) * 320 + (g & 3) * 16 + (own ? ((q & 1) == h ? 4 : 12) : 8 - 8 * (q & 1));
    TS(18);
    if (w >= 4) bsync(12, 320);
    POLLW(_Pragma("unroll") for (int v = 0; v < 4; v++) if ((yv[v].x ^ pm) & TAGM) yv[v] = ldr128(ysrc + 64 * v),
          ((yv[0].x ^ pm) | (yv[1].x ^ pm) | (yv[2].x ^ pm) | (yv[3].x ^ pm)) & TAGM, 5);
    TS(19);
#pragma unroll
    for (int k = 0; k < 4; k += 2) {
      float X[4] = {}, Y[4] = {}, R[4] = {};
#pragma unroll
      for (int v = 0; v < 4; v++) {
        const u32 y0 = k ? yv[v].z : yv[v].x & ~TAGM, y1 = k ? yv[v].w : yv[v].y;
        x1[k][v] = badd(x1[k][v], bmul(gaw[v], bfma(movm(y0), B2P64, hD[k][v])));
        x1[k + 1][v] = badd(x1[k + 1][v], bmul(gaw[v], bfma(movm(y1), B2P64, hD[k + 1][v])));
        mma8_bf(X, x1[k][v], x1[k + 1][v], x1[k][v]); mma8_bf(Y, x1[k][v], x1[k + 1][v], x1[k + 1][v]);
        if (v & 1) mma_bf(R, x1[k][v - 1], x1[k + 1][v - 1], x1[k][v], x1[k + 1][v], v & 2 ? rb.z : rb.x, v & 2 ? rb.w : rb.y);
      }
      sts32(spw + k * 64, fu(own ? (hi ? X[1] : X[0]) : R[0] + R[1]));
      sts32(spw + k * 64 + 64, fu(own ? (hi ? Y[3] : Y[2]) : R[2] + R[3]));
    }
    barrive(1, 320);
    TS(36);
    const uint4 sb = lds128(ma + 3456), cb = lds128(ma + 4608), gb = lds128(ma + 5760);
    const u32 sbw[4] = {sb.x, sb.y, sb.z, sb.w}, cbw[4] = {cb.x, cb.y, cb.z, cb.w}, gbw[4] = {gb.x, gb.y, gb.z, gb.w};
    bsync(2, 320);
    TS(37);
    lt = lds32(SM_THR + 36);
#pragma unroll
    for (int k = 0; k < 4; k++) {
      const uint4 st = lds128(SM_ST2 + 64 * k + 16 * (g & 3));
      key[k] = st.w;
      u32 o[4];
#pragma unroll
      for (int v = 0; v < 4; v++) {
        const u32 d = badd(x1[k][v], st.x), z = bfma(d, st.y, bmul(d, st.z));
        h2[k][v] = badd(bmul(z, cbw[v]), sbw[v]);
        o[v] = badd(x1[k][v], bmul(gbw[v], h2[k][v]));
      }
      h2[k][0] = bmul(h2[k][0], B2M64) | TAGR;
      if (key[k] >= lt) str128(rowp + k * 1152, h2[k][0], h2[k][1], h2[k][2], h2[k][3]);
      sts128(xa + ((k & 1) + 8 * (k >> 1)) * ROW, o[0], o[1], o[2], o[3]);
    }
    PROXY_FENCE();
    barrive(3, 320);
    TS(21);
  } else if (w == 10) {
    bsync(14, 224);
    uint2 rc = lds64(SM_RC + 8 * min(lane, 17u));
    float r1 = lane < 18 ? uf(rc.x) : 0.f, r2 = lane < 18 ? uf(rc.y) : 0.f;
#pragma unroll 1
    for (int o = 16; o; o >>= 1) { r1 += __shfl_xor_sync(~0u, r1, o); r2 += __shfl_xor_sync(~0u, r2, o); }
    const u32 tl = 4 * ((lane >> 1) & 1) + ((lane >> 2) & 3) + 8 * (lane & 1), kl = (2047 - 16 * b - tl) << 2 | par * 3;
    const u32 row = SM_XST + ((lane & 2) + 4 * (lane & 1) + ((lane >> 2) & 1) + (lane & 8)) * ROW;
    char* const op = p.out + (b * BLK + tl * 1152);
    const u32 spr = SM_SP + (lane >> 4) * 9 * 320 + (lane & 15) * 16;
    TS(31);
    bsync(1, 320);
    float S1 = 0.f, S2 = 0.f, S3 = 0.f;
#pragma unroll
    for (int i = 0; i < 9; i++) { uint4 t = lds128(spr + i * 320); S1 += uf(t.x); S2 += uf(t.y); S3 += uf(t.z); }
    S1 += __shfl_xor_sync(~0u, S1, 16); S2 += __shfl_xor_sync(~0u, S2, 16); S3 += __shfl_xor_sync(~0u, S3, 16);
    const float mu = S1 * (1.f / 576.f), var = fmaxf(fmaf(-mu, mu, S2 * (1.f / 576.f)), 0.f);
    const float m = rbf(mu), rs = rcpf(rbf(sqrta(rbf(rbf(var) + 1e-5f))));
    const u32 rb = pk_bf(0.f, fmaf(fmaf(-m, r1, S3), rs, r2) + 0.f);
    const u32 ok = ((rb ^ (((int)rb >> 31) | 0x80000000)) & 0xffff0000u) | kl;
    if (lane < 16) str32(gs + (G_KEY + b * 128 + 4 * lane), ok);
    TS(20);
    const float rh = rbf(rs);
    sts128(SM_ST2 + 16 * (lane & 15), pk_bf(-m, -m), pk_bf(rh, rh), pk_bf(rs - rh, rs - rh), ok);
    sts32(SM_KEY + 4 * (lane & 15), ok);
    __syncwarp();
    const uint4 o0 = lds128(SM_KEY + 2 * (lane & 16)), o1 = lds128(SM_KEY + 2 * (lane & 16) + 16);
    u32 lr = (o0.x > ok) + (o0.y > ok) + (o0.z > ok) + (o0.w > ok) + (o1.x > ok) + (o1.y > ok) + (o1.z > ok) + (o1.w > ok);
    lr += __shfl_xor_sync(~0u, lr, 16);
    if (lr == NEARLY - 1) sts32(SM_THR + 36, ok);
    barrive(2, 320);
    bsync(3, 320);
    if (lane < 16 && lr >= 8) bulk_out(op, row);
    bsync(6, 320);
    if (lane < 16 && lr < 8 && ok < lds32(SM_SLOT + 28)) bulk_out(op, row);
    asm volatile("cp.async.bulk.commit_group;" ::: "memory");
  }
  uint4 rv[3];
  const char* rs_;
  if (w < 8) {
    const char* ks = gs + (G_KEY + (8 * g + w) * 128 + q * 16);
    const u32 kt = par * 3;
    uint4 ka, kc;
    POLL({ ka = ldr128(ks); kc = ldr128(ks + 8192); }, ((ka.x ^ kt) | (kc.x ^ kt)) & 3, 6);
    TS(23);
    const u32 kk[8] = {ka.x, ka.y, ka.z, ka.w, kc.x, kc.y, kc.z, kc.w};
    u32 mx = max(max(max(kk[0], kk[1]), max(kk[2], kk[3])), max(max(kk[4], kk[5]), max(kk[6], kk[7])));
#pragma unroll
    for (int o = 4; o < 32; o *= 2) mx = max(mx, __shfl_xor_sync(~0u, mx, o));
    if (lane < 4) asm volatile("red.shared.max.u32 [%0],%1;" ::"r"(SM_THR + 16 * (w & 1) + 4 * lane), "r"(mx) : "memory");
    bsync(4, 256);
    TS(33);
    const uint4 t0 = lds128(SM_THR), t1 = lds128(SM_THR + 16);
    u32 L0 = min(min(min(t0.x, t0.y), min(t0.z, t0.w)), min(min(t1.x, t1.y), min(t1.z, t1.w)));
#pragma unroll 1
    for (int it = 0; it < 128; it++) {
      u32 c = 0;
#pragma unroll
      for (int j = 0; j < 8; j++) c += kk[j] >= L0 ? 4 : 0;
      if (c) {
        u32 a;
        asm volatile("atom.shared.add.u32 %0,[%1],%2;" : "=r"(a) : "r"(SM_THR + 32), "r"(c) : "memory");
#pragma unroll
        for (int j = 0; j < 8; j++) if (kk[j] >= L0) { sts32(SM_LIST + a, kk[j]); a += 4; }
      }
      bsync(5, 256);
      TS(38);
      const u32 n = lds32(SM_THR + 32), m0 = lds32(SM_LIST + 4 * lane), my = 4 * lane < n ? m0 : 0;
      const uint4 cd = lds128(SM_LIST + 16 * w);
      const u32 cc[4] = {cd.x, cd.y, cd.z, cd.w};
#pragma unroll
      for (int j = 0; j < 4; j++) {
        const u32 r = __popc(__ballot_sync(~0u, my > cc[j]));
        if (r < 8 && 16 * w + 4 * j < n) sts32(SM_SLOT + 4 * r, cc[j]);
      }
      if (n <= 128) break;
      bsync(15, 256);
      L0 = lds32(SM_SLOT + 28);
      sts32(SM_THR + 32, 0);
      bsync(15, 256);
    }
  }
  if (w < 9) {
    bsync(6, 320);
    TS(24);
    const u32 g8 = lds32(SM_SLOT + 28);
    if (w < 8) {
      rs_ = gs + ((2047 - ((lds32(SM_SLOT + 4 * w) >> 2) & 2047)) * 1152 + lane * 16);
      rv[0] = ldr128(rs_); rv[1] = ldr128(rs_ + 512);
      rv[2].x = TAGR;
      if (lane < 8) rv[2] = ldr128(rs_ + 1024);
    }
    if (__any_sync(~0u, max(max(key[0], key[1]), max(key[2], key[3])) >= g8)) {
#pragma unroll
      for (int k = 0; k < 4; k++) if (key[k] >= g8) {
        if (key[k] < lt) str128(rowp + k * 1152, h2[k][0], h2[k][1], h2[k][2], h2[k][3]);
        str128(rowp + (G_Y + k * 1152), bmul(x1[k][0], B2M64) | TAGR, x1[k][1], x1[k][2], x1[k][3]);
      }
    }
  }
  const u32 kq = w & 3, tg = 2 - (w >> 2);
  uint4 A[24];
  {
    const u32 row = 144 * kq + 8 * (lane >> 4) + (lane & 7), ab = (lane & 8) ? SM_UP : SM_GATE;
    mb_wait(SM_MB + 8); mb_wait(SM_MB + 16);
    if (tg < 2) {
      const u32 aa = ab + row * 64 + (((2 * tg) ^ ((lane & 7) >> 1)) << 4);
#pragma unroll
      for (int s = 0; s < 9; s++) { A[s] = ldsm4t(aa + s * 1024); A[9 + s] = ldsm4t((aa ^ 16) + s * 1024); }
    } else {
#pragma unroll
      for (int s = 0; s < 9; s++) A[s] = ldsm4t(ab + SLV + row * 16 + s * 256);
    }
  }
  TS(22);
  if (w < 8) {
    POLLW({ rv[0] = ldr128(rs_); rv[1] = ldr128(rs_ + 512); if (lane < 8) rv[2] = ldr128(rs_ + 1024); },
          ((rv[0].x ^ TAGR) | (rv[1].x ^ TAGR) | (rv[2].x ^ TAGR)) & TAGM, 8);
#pragma unroll
    for (int j = 0; j < 3; j++) if (j < 2 || lane < 8) sts128(SM_XS + w * ROW + lane * 16 + j * 512, bmul(rv[j].x ^ TAGR, B2P64), rv[j].y, rv[j].z, rv[j].w);
  }
  __syncthreads();
  TS(25);
  {
    float c0[2][4] = {}, c1[2][4] = {};
    const u32 ba = SM_XS + (lane & 7) * ROW + (18 * kq + (lane >> 3)) * 16;
    uint4 bb[5];
#pragma unroll
    for (int s = 0; s < 5; s++) bb[s] = ldsm4(ba + s * 64);
#pragma unroll
    for (int s = 0; s < 9; s++) mma_bf(c0[s & 1], A[s].x, A[s].y, A[s].z, A[s].w, s & 1 ? bb[s >> 1].z : bb[s >> 1].x, s & 1 ? bb[s >> 1].w : bb[s >> 1].y);
    const u32 ra = SM_RED + (8 * tg + kq) * 512 + lane * 16;
    if (tg < 2) {
#pragma unroll
      for (int s = 0; s < 9; s++) mma_bf(c1[s & 1], A[9 + s].x, A[9 + s].y, A[9 + s].z, A[9 + s].w, s & 1 ? bb[s >> 1].z : bb[s >> 1].x, s & 1 ? bb[s >> 1].w : bb[s >> 1].y);
      sts128(ra + 2048, fu(c1[0][0] + c1[1][0]), fu(c1[0][1] + c1[1][1]), fu(c1[0][2] + c1[1][2]), fu(c1[0][3] + c1[1][3]));
    }
    sts128(ra, fu(c0[0][0] + c0[1][0]), fu(c0[0][1] + c0[1][1]), fu(c0[0][2] + c0[1][2]), fu(c0[0][3] + c0[1][3]));
  }
  TS(39);
  __syncthreads();
  if (w >= 7 + rho) {
    const u32 t = 11 - w;
    float s[4] = {};
#pragma unroll
    for (int i = 0; i < 4; i++) { const uint4 u = lds128(SM_RED + (t * 4 + i) * 512 + lane * 16); s[0] += uf(u.x); s[1] += uf(u.y); s[2] += uf(u.z); s[3] += uf(u.w); }
    const u32 sg = pk_bf(silu_f(rbf(s[0])), silu_f(rbf(s[1])));
    const u32 act = movm(bmul(bmul(sg, pk_bf(s[2], s[3])), B2M64));
    str32(gs + (G_ACT + (t < 4 ? 4 * b + t : 512 + (b >> 1)) * 128 + lane * 4), act | (q ? 0 : pm));
  }
  TS(26);
  if (b < 108) {
    const char* src = gs + (G_ACT + (b / 9) * 6144 + tid * 16);
    uint4 a = ldr128(src);
    if (w < 4) {
      const u32 aa = SM_WD + (8 * (lane >> 4) + (lane & 7)) * 128 + (((2 * w + ((lane >> 3) & 1)) ^ (lane & 7)) << 4);
      mb_wait(SM_MB + 24);
#pragma unroll
      for (int s = 0; s < 24; s++) A[s] = ldsm4t(aa + s * 2048);
    }
    TS(28);
    POLLW(a = ldr128(src), (a.x ^ pm) & TAGM, 9);
    sts128(SM_AC + tid * 16, a.x & ~TAGM, a.y, a.z, a.w);
    TS(27);
    if (w < 4) {
      bsync(8, 384);
      float c[4][4] = {};
#pragma unroll
      for (int s = 0; s < 12; s++) {
        const uint4 bb = ldsm4(SM_AC + lane * 16 + s * 512);
        mma_bf(c[2 * (s & 1)], A[2 * s].x, A[2 * s].y, A[2 * s].z, A[2 * s].w, bb.x, bb.y);
        mma_bf(c[2 * (s & 1) + 1], A[2 * s + 1].x, A[2 * s + 1].y, A[2 * s + 1].z, A[2 * s + 1].w, bb.z, bb.w);
      }
      char* dst = gs + (G_PART + b * 2048 + w * 512 + lane * 8);
      u32 o[4];
#pragma unroll
      for (int i = 0; i < 4; i++) o[i] = (fu(((c[0][i] + c[1][i]) + (c[2][i] + c[3][i])) * F2P64) & ~1u) | par;
      str64(dst, o[0], o[1]); str64(dst + 256, o[2], o[3]);
      TS(29);
    } else barrive(8, 384);
  }
  if (w == 8 && b < 72) {
    const u32 kg = lds32(SM_SLOT + 4 * g), ro = (2047 - ((kg >> 2) & 2047)) * 1152 + 16 * b;
    const char* src = gs + (G_PART + (b >> 3) * 2048 + (b & 7) * 256 + lane * 8);
    const char* xs = gs + (G_Y + ro);
    uint4 xt;
    POLL(xt = ldr128(xs), (xt.x ^ TAGR) & TAGM, 10);
    const u32 x1w = (q & 2) ? ((q & 1) ? xt.w : xt.z) : ((q & 1) ? xt.y : bmul(xt.x ^ TAGR, B2P64));
    const u32 gw = lds32(SM_MODS + 5760 + 16 * b + 4 * q);
    const u32 hw = lds32(SM_XS + g * ROW + b * 16 + q * 4);
    const float sgm = rcpf(1.f + ex2(-LOG2E * bhi(kg ^ (~((int)kg >> 31) | 0x80000000))));
    char* const dst = p.out + (ro + 4 * q);
    uint2 v[12];
#pragma unroll
    for (int j = 0; j < 12; j++) v[j] = make_uint2(1, 0);
    u32 bad;
    POLL({ bad = 0; _Pragma("unroll") for (int j = 0; j < 12; j++) { if (((v[j].x ^ par) | (v[j].y ^ par)) & 1) v[j] = ldr64(src + j * 9 * 2048); }
           _Pragma("unroll") for (int j = 0; j < 12; j++) bad |= (v[j].x ^ par) | (v[j].y ^ par); }, bad & 1, 11);
    float s0[4] = {}, s1[4] = {};
#pragma unroll
    for (int j = 0; j < 12; j++) { s0[j & 3] += uf(v[j].x); s1[j & 3] += uf(v[j].y); }
    const u32 y = movm(pk_bf((s0[0] + s0[1]) + (s0[2] + s0[3]), (s1[0] + s1[1]) + (s1[2] + s1[3])));
    *(u32*)dst = badd(x1w, bmul(gw, badd(hw, bmul(y, pk_bf(sgm, sgm)))));
    if (b == 0 && lane == 0) str32(gs + G_EP, ep + 1);
    TS(30); TSE();
  }
  if (w == 10) asm volatile("cp.async.bulk.wait_group.read 0;" ::: "memory");
}

__global__ void __launch_bounds__(384, 1)
fused_kernel(const Prm p, const __grid_constant__ CUtensorMap tm_mod, const __grid_constant__ CUtensorMap tm_gate, const __grid_constant__ CUtensorMap tm_gs,
             const __grid_constant__ CUtensorMap tm_up, const __grid_constant__ CUtensorMap tm_us, const __grid_constant__ CUtensorMap tm_down) {
  extern __shared__ __align__(1024) unsigned char smem[];
  if (threadIdx.x == 352) {
#pragma unroll
    for (int i = 0; i < 4; i++) mb_init(SM_MB + 8 * i);
    asm volatile("fence.mbarrier_init.release.cluster;" ::: "memory");
    tm_pre(&tm_mod); tm_pre(&tm_gate);
  }
  const u32 tid = __shfl_sync(~0u, threadIdx.x, threadIdx.x & 31), b = __shfl_sync(~0u, blockIdx.x, 0);
  const u32 w = tid >> 5, lane = tid & 31;
  const u32 g = lane >> 2, q = lane & 3, hi = g & 1;
  const u32 rho = b & 1, Ps = 512 + (b >> 1);
  char* const gs = p.gs;
  TS0();
  const bool kw = w != 8 && w != 11;
  const u32 ksig = w < 8 ? (w & 3) : 4, khf = w < 8 ? (w >> 2) : (w & 1);
  u32 la, ai, ldt; uint2 cr, ci;
  {
    const u32 d = w < 8 ? 4 * b + ksig : Ps, o = d * 256 + 8 * lane;
    const char* cp = p.c + (576 * (w & 1) + 24 * min(lane, 23u));
    la = ldg32(kw ? p.la + (o + 4 * khf) : cp); ai = ldg32(kw ? p.ai + (o + 4 * khf) : cp + 4);
    cr = ldg64(kw ? p.cr + o : cp + 8); ci = ldg64(kw ? p.ci + o : cp + 16); ldt = ldg16(p.ldt + 2 * d);
  }
  const u32 zr = tid >> 16;
  const u32 epv = ldr32(gs + (G_EP + zr));
  const u32 tp = SM_TAP + ksig * TAPS;
  if (kw && !khf) {
#pragma unroll 1
    for (u32 i = lane * 16; i < TAPS; i += 512) sts128(tp + i, 0, 0, 0, 0);
  }
  if (tid >= 380) str128(gs + (G_MOD + b * 128 + q * 16), INVAL, 0, 1, 0);
  if (w < 9) {
    const char* xp = p.x + (b * BLK + (lane >> 3) * 1152 + 128 * w + 16 * (lane & 7));
    const u32 xd = SM_XST + (((lane >> 3) & 1) + 8 * (lane >> 4)) * ROW + 128 * w + 16 * (lane & 7);
#pragma unroll
    for (int i = 0; i < 4; i++) cpa16(xd + 2 * ROW * i, xp + 4608 * i);
  }
  const u32 ktab = w < 8 ? SM_MODS + w * KTAB : SM_ZS + (w - 9) * KTAB;
  float k2048 = 0.f;
  u32 FK;
  if (kw) {
    u32 mx = __vmaxu2(__vmaxu2(cr.x & 0x7fff7fff, cr.y & 0x7fff7fff), __vmaxu2(ci.x & 0x7fff7fff, ci.y & 0x7fff7fff));
    const u32 E = max(__reduce_max_sync(~0u, max(mx & 0xffff, mx >> 16)) >> 7, 8u);
    TS(1);
    const float dt = rbf(ex2(blo(ldt) * LOG2E)), csc = uf((257 - E) << 23 | (fu(dt) & 0x7fffff));
    FK = fu(uf(fu(dt) & 0x7f800000) * uf((E - 2) << 23));
    const u32 crw = khf ? cr.y : cr.x, ciw = khf ? ci.y : ci.x;
    float2 C[2], w4[2], w8[2], w16[2], w32[2], w64[2], w128[2], w256[2], w512[2], a1[2], a2[2], a3[2], t0[2], t1[2], s3[2];
#pragma unroll
    for (int m = 0; m < 2; m++) {
      const float lr2 = rbf(ex2((m ? bhi(la) : blo(la)) * LOG2E)) * dt * -LOG2E, th = (m ? bhi(ai) : blo(ai)) * dt;
      C[m] = make_float2((m ? bhi(crw) : blo(crw)) * csc, (m ? bhi(ciw) : blo(ciw)) * csc);
      const float2 w1 = cexp(lr2, th), w2 = csq(w1);
      w64[m] = cexp(64.f * lr2, 64.f * th);
      w4[m] = csq(w2); w8[m] = csq(w4[m]); w16[m] = csq(w8[m]); w32[m] = csq(w16[m]);
      w128[m] = csq(w64[m]); w256[m] = csq(w128[m]); w512[m] = csq(w256[m]);
      const float2 w1024 = csq(w512[m]);
      a1[m] = cmul(C[m], w1); a2[m] = cmul(C[m], w2); a3[m] = cmul(a1[m], w2);
      t0[m] = cmul(C[m], w1024); t1[m] = cmul(t0[m], w128[m]); s3[m] = cmul(w8[m], w16[m]);
      k2048 += fmaf(t0[m].x, w1024.x, -t0[m].y * w1024.y);
    }
    C2 B0[8], B1[8], B2[8], S[8];
    B0[0] = pk2(C); B0[1] = pk2(a1); B0[2] = pk2(a2); B0[3] = pk2(a3);
    const C2 h4 = pk2(w4), h256 = pk2(w256), h512 = pk2(w512);
#pragma unroll
    for (int i = 0; i < 4; i++) B0[4 + i] = cm2(B0[i], h4);
#pragma unroll
    for (int i = 0; i < 4; i++) B1[i] = cm2(B0[2 * i], h256);
    B1[4] = cm2(B0[0], h512); B1[5] = cm2(B0[4], h512);
    B1[6] = cm2(B1[4], h256); B1[7] = cm2(B1[5], h256);
    const u32 ta = ktab + lane * 128, f = ((lane & 3) << 5) | ((lane & 4) << 2);
#pragma unroll
    for (int i = 0; i < 8; i++) sts128(ta + ((i << 4) ^ f), B0[i].re, B0[i].im, B1[i].re, B1[i].im);
    B2[0] = pk2(t0); B2[1] = pk2(t1);
    B2[2] = cm2(B2[0], h256); B2[3] = cm2(B2[1], h256);
#pragma unroll
    for (int i = 0; i < 4; i++) B2[4 + i] = cm2(B2[i], h512);
    S[0] = {0x3C003C00u, 0u}; S[1] = pk2c(w8); S[2] = pk2c(w16); S[3] = pk2c(s3); S[4] = pk2c(w32);
#pragma unroll
    for (int i = 1; i < 4; i++) S[4 + i] = cm2(S[i], S[4]);
#pragma unroll
    for (int i = 0; i < 8; i++) sts128(ta + 4096 + ((i << 4) ^ f), B2[i].re, B2[i].im, S[i].re, S[i].im);
    const C2 m64 = pk2c(w64), m128 = pk2c(w128);
    sts128(ktab + 8192 + lane * 16, m64.re, m64.im, m128.re, m128.im);
    __syncwarp();
  } else {
    u32 sa = SM_SIL + 576 * (w & 1) + 24 * min(lane, 23u);
#pragma unroll 1
    for (int j = 0; j < 6; j++) {
      sts32(sa, pk_bf(silu_f(blo(la)), silu_f(bhi(la))));
      la = ai; ai = cr.x; cr.x = cr.y; cr.y = ci.x; ci.x = ci.y; sa += 4;
    }
    if (tid == 352 && b < 36) { mb_expect(SM_MB, 36864); tma3d(SM_UP, &tm_mod, SM_MB, 32 * b, 0); }
    bsync(7, 64);
  }
  TS(2);
  const u32 ep = __reduce_or_sync(~0u, epv), par = (ep + 1) & 1, pm = par ? TAGM : 0;
  if (w < 9) {
    asm volatile("cp.async.wait_all;" ::: "memory");
    __syncwarp();
    TS(4);
    const u32 xa = SM_XST + (lane & 15) * ROW + 128 * w + 16 * (lane >> 4);
    float s[4] = {}, X[2][4] = {}, Y[2][4] = {};
#pragma unroll
    for (int j = 0; j < 4; j++) {
      const uint4 a = ldsm4(xa + 32 * j);
      mma8_bf(X[0], a.x, a.y, a.x); mma8_bf(Y[0], a.x, a.y, a.y);
      mma8_bf(X[1], a.z, a.w, a.z); mma8_bf(Y[1], a.z, a.w, a.w);
      mma_bf(s, a.x, a.y, a.z, a.w, BONE, BONE);
    }
    uint4 t[4];
#pragma unroll
    for (int j = 0; j < 4; j++) t[j] = ldsm4t(xa + 32 * j);
    const float u0 = hi ? X[0][1] + X[1][1] : X[0][0] + X[1][0], u1 = hi ? Y[0][3] + Y[1][3] : Y[0][2] + Y[1][2];
    if (q == g >> 1) sts128(SM_SP + w * 128 + g * 16, fu(s[0]), fu(u0), fu(s[2]), fu(u1));
    bsync(1, 320);
    TS(7);
    const u32 spr = SM_SP + (lane & 7) * 16 + (lane & 8);
    const uint2 t8 = lds64(spr + 1024);
    const float f8 = lane < 16 ? 1.f : 0.f;
    float S1 = uf(t8.x) * f8, S2 = uf(t8.y) * f8;
#pragma unroll
    for (int i = 0; i < 4; i++) { const uint2 u = lds64(spr + (lane & 16) * 32 + i * 128); S1 += uf(u.x); S2 += uf(u.y); }
    S1 += __shfl_xor_sync(~0u, S1, 16); S2 += __shfl_xor_sync(~0u, S2, 16);
    const float mu = S1 * (1.f / 576.f), var = fmaxf(fmaf(-mu, mu, S2 * (1.f / 576.f)), 0.f);
    const float m = rbf(mu), rs = rcpf(rbf(sqrta(rbf(rbf(var) + 1e-5f))));
    const float ra = rs * 0.0625f;
    sts64(SM_AF + w * 128 + (lane & 15) * 8, fu(ra), fu(-m * ra));
    __syncwarp();
    const uint4 f0 = lds128(SM_AF + w * 128 + q * 16), f1 = lds128(SM_AF + w * 128 + 64 + q * 16);
    char* const zdst = gs + (b * BLK + w * 2048 + lane * 8);
    const u32 pz = (q & 1) ? 0 : pm;
#pragma unroll
    for (int j = 0; j < 8; j++) {
      const u32 x0 = j & 1 ? t[j >> 1].z : t[j >> 1].x, x1 = j & 1 ? t[j >> 1].w : t[j >> 1].y;
      str64(zdst + 256 * j, pk_hf(fmaf(blo(x0), uf(f0.x), uf(f0.y)), fmaf(bhi(x0), uf(f0.z), uf(f0.w))) | pz,
            pk_hf(fmaf(blo(x1), uf(f1.x), uf(f1.y)), fmaf(bhi(x1), uf(f1.z), uf(f1.w))));
    }
    if (w == 8) {
      const float rh = rbf(rs);
      sts128(SM_ST + 16 * (lane & 15), pk_bf(-m, -m), pk_bf(rh, rh), pk_bf(rs - rh, rs - rh), 0);
    }
    TS(5);
  } else if (w == 11) {
    bsync(1, 320);
    if (lane == 0) {
      if (b >= 36 && b < 108) { mb_expect(SM_MB, 36864); tma3d(SM_UP, &tm_mod, SM_MB, 32 * b, 0); }
      mb_expect(SM_MB + 8, rho ? SLV : 46080);
      tma3d(SM_GATE, &tm_gate, SM_MB + 8, 32 * b, 0);
      if (!rho) tma3d(SM_GATE + SLV, &tm_gs, SM_MB + 8, 4096 + 4 * b, 0);
      tm_pre(&tm_up); tm_pre(&tm_down);
    }
  }
  if (kw) {
    float D[5][4] = {};
    u32 ta = ktab + q * 128 + ((g ^ (q << 1)) << 4), tm = ktab + 8192 + q * 16;
#pragma unroll 2
    for (int s = 0; s < 8; s++) {
      const uint4 ca = lds128(ta), cb = lds128(ta + 4096), ma = lds128(tm);
      ta = (ta + 512) ^ 16; tm += 64;
      k2048 += __shfl_xor_sync(~0u, k2048, 16 >> s);
      const C2 s0 = {cb.z, cb.w}, s1 = cm2(s0, {ma.x, ma.y}), s2 = cm2(s0, {ma.z, ma.w}), s3 = cm2(s1, {ma.z, ma.w});
      mma_hf(D[0], s0.re, s1.re, s0.im, s1.im, ca.x, ca.y);
      mma_hf(D[2], s0.re, s1.re, s0.im, s1.im, ca.z, ca.w);
      mma_hf(D[4], s0.re, s1.re, s0.im, s1.im, cb.x, cb.y);
      mma_hf(D[1], s2.re, s3.re, s2.im, s3.im, ca.x, ca.y);
      mma_hf(D[3], s2.re, s3.re, s2.im, s3.im, ca.z, ca.w);
    }
    TS(3);
    const u32 xa = (w < 8 ? SM_MODS + (4 + ksig) * KTAB : SM_ZS) + lane * 16;
    if (khf) {
      __syncwarp();
#pragma unroll
      for (int j = 0; j < 5; j++) sts128(xa + 512 * j, fu(D[j][0]), fu(D[j][1]), fu(D[j][2]), fu(D[j][3]));
      if (lane == 0) sts32(xa + 2560, fu(k2048));
      asm volatile("bar.arrive %0,64;" ::"r"(2 + ksig) : "memory");
    } else {
      const u32 t1 = tp + (q < 2 ? (128 + 4 * g + 2 * q) * 4 : T3 * 4 + ((32 * q - 64 + g) ^ 1) * 2);
      const u32 x = 16 * q + (g >> 1) + hi + 1, tb = tp + (hi ? T7E : T9E) * 4 - 4;
      const u32 te = tb + (x + 2 * (x & 1)) * 2, to = tb + TEO * 4 + (x ^ 1) * 2;
      asm volatile("bar.sync %0,64;" ::"r"(2 + ksig) : "memory");
#pragma unroll
      for (int j = 0; j < 5; j++) { const uint4 t = lds128(xa + 512 * j); D[j][0] += uf(t.x); D[j][1] += uf(t.y); D[j][2] += uf(t.z); D[j][3] += uf(t.w); }
      k2048 = (k2048 + uf(lds32(xa + 2560))) * 0.125f;
#pragma unroll
      for (int r = 0; r < 4; r++) {
        const u32 v = pk_hf(D[2 + (r >> 1)][2 * (r & 1)], D[2 + (r >> 1)][2 * (r & 1) + 1]);
        if (q < 2) {
          const u32 vv = __byte_perm(v, v, 0x1010);
          sts32(t1 + (TO + 32 * r) * 4, vv); sts16(t1 + (TO + 32 * r + 1) * 4 + 2, v >> 16); sts16(t1 + (TO + 32 * r - 1) * 4, v);
          sts64(t1 + (TE + 32 * r) * 4, vv, __byte_perm(v, v, 0x1032));
        } else {
          sts16(t1 + 16 * r, v >> 16);
          if (r == 0 && lane == 2) {
            const u32 vv = __byte_perm(v, v, 0x1010);
            sts32(tp + (TO + 256) * 4, vv); sts16(tp + (TO + 257) * 4 + 2, v); sts16(tp + (TO + 255) * 4, v); sts64(tp + (TE + 256) * 4, vv, vv);
          } else sts16(t1 + 16 * r - ((T3 - T5) * 4 + 6) + 8 * hi, v);
        }
      }
#pragma unroll
      for (int r = 0; r < 2; r++) {
        const u32 v = pk_hf(D[4][2 * r], D[4][2 * r + 1]);
        if (r == 0 && lane == 0) { sts16(tp + T5 * 4 + 62 * 2, v); sts32(SM_KV + 4 * ksig, v & 0xffff); sts16(tp + (T9E + TEO) * 4 + 62 * 2, pk_hf(k2048, 0.f)); sts32(SM_SC + 16 * ksig + 12, FK); }
        else { sts16(te + 8 * r, v); sts16(to + 8 * r, v); }
        sts16(te + 8 * r + 16, v >> 16); sts16(to + 8 * r + 16, v >> 16);
      }
      __syncwarp();
#pragma unroll
      for (int r = 0; r < 4; r++) {
        const u32 v = pk_hf(D[r >> 1][2 * (r & 1) + 1], D[r >> 1][2 * (r & 1)]), t2 = tp + lane * 4 + 128 * r;
        sts32(t2 + TO * 4, v); sts16(t2 + TE * 4, v >> 16); sts16(t2 + (TE + 1) * 4 + 2, v);
      }
      __syncwarp();
    }
  }
  TS(6);
  const u32 r0 = (lane & 7) + ((lane >> 3) & 1) + 8 * (lane >> 4) - 1;
  const u32 rl16 = (r0 ^ ((r0 >> 3) & 3)) * 16;
  const u32 pml = (g & 3) ? 0 : pm;
  if (w < 4) {
    asm volatile("setmaxnreg.inc.sync.aligned.u32 232;");
    const u32 tr = tp + ((hi ? TO : TE) + (g >> 1) - q) * 4;
    u32 T[33][4], B5[5][2], B3[5][2];
#pragma unroll
    for (int d = 0; d < 33; d++) {
      T[d][0] = lds32(tr + 32 * d); T[d][1] = lds32(tr + 32 * d + 16);
      T[d][2] = d ? cpy(T[d - 1][1], zr, 0) : zr; T[d][3] = cpy(T[d][0], zr, 1);
    }
    const u32 bt = tp + (T5 + g - q) * 4;
#pragma unroll
    for (int d = 0; d < 5; d++) {
      B5[d][0] = lds32(bt + 32 * d); B5[d][1] = lds32(bt + 32 * d - 16);
      B3[d][0] = lds32(bt + 32 * d + (T3 - T5) * 4); B3[d][1] = lds32(bt + 32 * d - 16 + (T3 - T5) * 4);
    }
    u32 za = SM_ZS + 16 + w * ZSS + ((lane >> 3) & 1) * ZPS + ((lane & 7) + (lane >> 4)) * 16;
    u32 wa = SM_W + W5O + w * WSL + rl16;
    u32 sa = SM_W + W9O + w * WSL + lane * 16;
    u32 yo = G_Y + 2 * q * BLK + (4 * b + w) * 32 + 4 * g;
    TS(8);
    lds32(za);
    bsync(9, 384);
    TS(11);
    float A[4][4] = {};
    uint4 Z[4];
    Z[0] = ldsm4(za); Z[1] = ldsm4(za + 32);
    const u32 F = __byte_perm(fu(uf(lds32(SM_SC + 16 * w + 8)) * uf(FK)), 0, 0x3232);
    const float ZERO[4] = {};
#define STEP(s, b0, b1) { _Pragma("unroll") for (int i = 0; i < 4; i++) mma_hf_o(A[i], A[i], T[8 * i + 7 - (s)], b0, b1); }
#define PAIR(n) { Z[(n + 2) & 3] = ldsm4(za + 32 * (n + 2)); STEP(2 * n, Z[n].x, Z[n].y); STEP(2 * n + 1, Z[n].z, Z[n].w); }
#define LAST(N) float O[4]; mma_hf_o(O, A[0], T[0], Z[3].z, Z[3].w); \
    _Pragma("unroll") for (int i = 0; i < 3; i++) mma_hf_o(A[i], A[i + 1], T[8 * i + 8], Z[3].z, Z[3].w); \
    mma_hf_o(A[3], N, T[32], Z[3].z, Z[3].w);
#pragma unroll 1
    for (int j = 0; j < 4; j++) {
      PAIR(0); PAIR(1); PAIR(2);
      Z[1] = ldsm4(za + 160); STEP(6, Z[3].x, Z[3].y);
      LAST(ZERO);
      y_store(O[0], O[1], O[2], O[3], F, pml, gs + yo);
      za += 128; yo += 8 * BLK;
      TS(40 + j);
    }
    bsync(10, 352);
#pragma unroll 1
    for (int j = 4; j < 13; j++) {
      const uint4 a5 = ldsm4t(wa), a3 = ldsm4t(wa + (W3O - W5O)), s3 = lds128(sa);
      PAIR(0);
      float N[4] = {uf(s3.x), uf(s3.y), uf(s3.z), uf(s3.w)};
#pragma unroll
      for (int i = 0; i < 4; i++) mma_hf(A[i], a5.x, a5.y, a5.z, a5.w, B5[i][0], B5[i][1]);
      mma_hf(N, a5.x, a5.y, a5.z, a5.w, B5[4][0], B5[4][1]);
      PAIR(1);
#pragma unroll
      for (int i = 0; i < 4; i++) mma_hf(A[i], a3.x, a3.y, a3.z, a3.w, B3[i][0], B3[i][1]);
      mma_hf(N, a3.x, a3.y, a3.z, a3.w, B3[4][0], B3[4][1]);
      PAIR(2);
      Z[1] = ldsm4(za + 160); STEP(6, Z[3].x, Z[3].y);
      LAST(N);
      y_store(O[0], O[1], O[2], O[3], F, pml, gs + yo);
      za += 128; wa = (wa + 256) ^ 32; sa += 512; yo += 8 * BLK;
      TS(40 + j);
    }
    {
      float X[3][4] = {};
#pragma unroll
      for (int ty = 0; ty < 2; ty++) {
        const uint4 a = ldsm4t(wa + ty * (W3O - W5O)), c = ldsm4t((wa ^ 32) + 256 + ty * (W3O - W5O)), d = ldsm4t(wa + 512 + ty * (W3O - W5O));
#pragma unroll
        for (int i = 0; i < 3; i++) mma_hf(A[i], a.x, a.y, a.z, a.w, ty ? B3[i][0] : B5[i][0], ty ? B3[i][1] : B5[i][1]);
#pragma unroll
        for (int i = 0; i < 2; i++) mma_hf(X[i], c.x, c.y, c.z, c.w, ty ? B3[i][0] : B5[i][0], ty ? B3[i][1] : B5[i][1]);
        mma_hf(X[2], d.x, d.y, d.z, d.w, ty ? B3[0][0] : B5[0][0], ty ? B3[0][1] : B5[0][1]);
      }
      barrive(12, 320);
#pragma unroll
      for (int n = 0; n < 4; n++) {
        const uint4 f0 = n < 2 ? Z[n] : ldsm4(za + 32 * n), f1 = ldsm4(za + 32 * n + 128), f2 = ldsm4(za + 32 * n + 256);
#pragma unroll
        for (int s = 2 * n; s < 2 * n + 2; s++) {
#pragma unroll
          for (int i = 0; i < 3; i++) mma_hf_o(A[i], A[i], T[8 * i + 7 - s], s & 1 ? f0.z : f0.x, s & 1 ? f0.w : f0.y);
          mma_hf_o(X[0], X[0], T[7 - s], s & 1 ? f1.z : f1.x, s & 1 ? f1.w : f1.y); mma_hf_o(X[1], X[1], T[15 - s], s & 1 ? f1.z : f1.x, s & 1 ? f1.w : f1.y);
          mma_hf_o(X[2], X[2], T[7 - s], s & 1 ? f2.z : f2.x, s & 1 ? f2.w : f2.y);
        }
      }
      y_store(A[0][0], A[0][1], A[0][2], A[0][3], F, pml, gs + yo);
      y_store(A[1][0] + X[0][0], A[1][1] + X[0][1], A[1][2] + X[0][2], A[1][3] + X[0][3], F, pml, gs + yo + 8 * BLK);
      y_store(A[2][0] + X[1][0] + X[2][0], A[2][1] + X[1][1] + X[2][1], A[2][2] + X[1][2] + X[2][2], A[2][3] + X[1][3] + X[2][3], F, pml, gs + yo + 16 * BLK);
    }
    TS(15);
    bsync(14, 224);
  } else {
    asm volatile("setmaxnreg.dec.sync.aligned.u32 136;");
    const u32 t8 = tid - 128;
#pragma unroll 1
    for (int ph = 0; ph < 2; ph++) {
      if (!kw && (ph ? b >= 36 && b < 108 : b < 36)) {
        float c[2][4] = {};
        u32 aa = SM_UP + ((lane & 7) + 8 * (lane >> 4)) * 64 + (((2 * (w & 1) + ((lane >> 3) & 1)) ^ ((lane & 7) >> 1)) << 4);
        u32 ba = SM_SIL + (lane >> 3) * 16;
        mb_wait(SM_MB);
#pragma unroll 1
        for (int s = 0; s < 6; s++) {
#pragma unroll
          for (int i = 0; i < 3; i++) {
            const uint4 a0 = ldsm4t(aa + i * 2048), a1 = ldsm4t(aa + i * 2048 + 1024), bb = ldsm4(ba + i * 64);
            mma_bf(c[0], a0.x, a0.y, a0.z, a0.w, bb.x, bb.y); mma_bf(c[1], a1.x, a1.y, a1.z, a1.w, bb.z, bb.w);
          }
          aa += 6144; ba += 192;
        }
        const float v = (q & 1) ? c[0][2] + c[1][2] : c[0][0] + c[1][0];
        if (q < 2) str16(gs + (G_MOD + b * 128 + 32 * (w & 1) + 2 * g + 16 * q), pk_bf(rbf(v) * F2M64, 0.f) | (g < 2 ? pm : 0));
      }
      if (ph) break;
      TS(12);
      const char* zs = gs + ((t8 >> 3) * BLK + b * 128 + (t8 & 7) * 16);
      const char* zs4 = gs + ((t8 >> 1) * BLK + Ps * 32 + (t8 & 1) * 16);
      uint4 v[5];
#pragma unroll
      for (int j = 0; j < 5; j++) v[j].x = INVAL;
      POLL(_Pragma("unroll") for (int j = 0; j < 5; j++) if ((v[j].x ^ pm) & TAGM) v[j] = ldr128(j < 4 ? zs + j * 32 * BLK : zs4),
           ((v[0].x ^ pm) | (v[1].x ^ pm) | (v[2].x ^ pm) | (v[3].x ^ pm) | (v[4].x ^ pm)) & TAGM, 1);
      TS(9);
      if (w == 11) {
        const u32 d = lane < 4 ? 4 * b + lane : Ps;
        const char* mp = gs + (G_MOD + (d >> 5) * 128 + (d & 24) * 2);
        uint4 ta, tc;
        POLL({ ta = ldr128(mp); tc = ldr128(mp + MODJ); }, ((ta.x ^ pm) | (tc.x ^ pm)) & TAGM, 2);
        const u32 aw = (d & 4) ? ((d & 2) ? ta.w : ta.z) : ((d & 2) ? ta.y : ta.x & ~TAGM);
        const u32 cw = (d & 4) ? ((d & 2) ? tc.w : tc.z) : ((d & 2) ? tc.y : tc.x & ~TAGM);
        const float sa = ((d & 1) ? bhi(aw) : blo(aw)) * F2P64, c1 = rbf(fmaf((d & 1) ? bhi(cw) : blo(cw), F2P64, 1.f));
        const u32 EM = min(max(fu(fmaxf(32.f * fabsf(c1), fabsf(sa))) >> 23, 80u), 250u);
        const float inv = uf((264 - EM) << 23);
        if (lane < 5) { sts64(SM_SC + 16 * lane, pk_hf(16.f * c1 * inv, 16.f * c1 * inv), pk_hf(sa * inv, sa * inv)); sts32(SM_SC + 16 * lane + 8, (EM - 74) << 23); }
        TS(10);
      }
      const u32 dst = SM_ZS + 128 + (t8 & 7) * ZPS + (t8 >> 3) * 16;
      bsync(8, 256);
      const uint2 cc = lds64(SM_SC + 8 * (t8 & 6)), c4 = lds64(SM_SC + 64);
#pragma unroll
      for (int j = 0; j < 5; j++) {
        const uint2 c = j < 4 ? cc : c4;
        sts128(j < 4 ? dst + j * 512 : SM_Z4 + 256 + (t8 & 1) * ZP4 + (t8 >> 1) * 16, hfma(v[j].x & ~TAGM, c.x, c.y), hfma(v[j].y, c.x, c.y), hfma(v[j].z, c.x, c.y), hfma(v[j].w, c.x, c.y));
      }
      if (t8 < 96) sts128(t8 < 64 ? dst - 128 : SM_Z4 + (t8 & 1) * ZP4 + (t8 & 30) * 8, 0, 0, 0, 0);
      bsync(9, 384);
      TS(11);
      const bool lng = w < 8 || w == 9;
      const u32 ts = lane + 32 * (w == 8 ? 0 : w - 9);
      const u32 sig = lng ? ksig : ts >> 4, l2 = lng ? lane : 32 + (ts & 15);
      if (!lng) {
#pragma unroll
        for (int i = 0; i < 3; i++) if (i < 2 || ts < 64) str128(gs + (G_Y + (96 + 12 * i + (ts >> 3)) * BLK + b * 128 + (ts & 7) * 16), INVAL, 0, 1, 0);
        str128(gs + (G_PART + b * 2048 + ts * 16), INVAL, 0, 1, 0);
        str128(gs + (ts < 32 ? G_PART + b * 2048 + 1536 + ts * 16 : ts < 64 ? G_ACT + b * 512 + (ts & 31) * 16 : G_Y + (96 + 16 * rho + ((ts & 31) >> 1)) * BLK + Ps * 32 + (ts & 1) * 16), INVAL, 0, 1, 0);
        if (ts < (rho ? 4 : 12)) str128(gs + (ts < 4 ? G_KEY + b * 128 + ts * 16 : G_ACT + Ps * 128 + (ts - 4) * 16), INVAL, 0, 1, 0);
      }
      const u32 wb = SM_W + sig * WSL;
      if (sig < 5) {
        const u32 za = (sig < 4 ? SM_ZS + 128 + sig * ZSS : SM_Z4 + 256) + l2 * 32, zb = za + (sig < 4 ? ZPS : ZP4);
        const uint4 c0 = lds128(zb - 32), c1 = lds128(za - 16), c2 = lds128(zb - 16), c3 = lds128(za), c4 = lds128(zb), c5 = lds128(za + 16), c6 = lds128(zb + 16);
        const u32 P[25] = {c0.z, c0.w, c1.x, c1.y, c1.z, c1.w, c2.x, c2.y, c2.z, c2.w, c3.x, c3.y, c3.z, c3.w, c4.x, c4.y, c4.z, c4.w, c5.x, c5.y, c5.z, c5.w, c6.x, c6.y, c6.z};
        u32 Q[25], D1[24], F4[23], W5[21], W3[17];
#pragma unroll
        for (int j = 1; j < 25; j++) Q[j] = __byte_perm(P[j - 1], P[j], 0x5432);
#pragma unroll
        for (int j = 1; j < 24; j++) D1[j] = hadd(P[j], Q[j]);
#pragma unroll
        for (int j = 2; j < 23; j++) F4[j] = hadd(D1[j], D1[j - 1]);
#pragma unroll
        for (int n = 0; n < 21; n++) W5[n] = hadd(F4[n + 2], P[n]);
#pragma unroll
        for (int n = 0; n < 17; n++) W3[n] = hadd(Q[n + 8], D1[n + 7]);
        const u32 a0 = wb + W5O + 64 * l2 + 16 * ((l2 >> 1) & 3);
#pragma unroll
        for (int i = 0; i < 4; i++) {
          sts128(a0 ^ (16 * i), W5[4 * i + 5], W5[4 * i + 6], W5[4 * i + 7], W5[4 * i + 8]);
          sts128((a0 ^ (16 * i)) + (W3O - W5O), W3[4 * i + 1], W3[4 * i + 2], W3[4 * i + 3], W3[4 * i + 4]);
        }
        if (lng) {
          if (lane < 16) sts128(wb + (lane & 7) * 16 + (lane & 8) * 400, 0, 0, 0, 0);
          const u32 a1 = wb + 32 * lane + 16 * ((lane >> 2) & 1);
#pragma unroll
          for (int i = 0; i < 4; i++) {
            const u32 a = (a1 ^ (16 * (i >> 1))) + 1024 * (i & 1), n = 4 * i;
            sts128(a + V2O, hadd(Q[n + 9], P[n + 8]), hadd(Q[n + 10], P[n + 9]), hadd(Q[n + 11], P[n + 10]), hadd(Q[n + 12], P[n + 11]));
            sts128(a + W9O, hadd(F4[n + 4], W5[n]), hadd(F4[n + 5], W5[n + 1]), hadd(F4[n + 6], W5[n + 2]), hadd(F4[n + 7], W5[n + 3]));
            sts128(a + W7O, hadd(F4[n + 6], W3[n]), hadd(F4[n + 7], W3[n + 1]), hadd(F4[n + 8], W3[n + 2]), hadd(F4[n + 9], W3[n + 3]));
          }
        }
      }
      __syncwarp();
      TS(32);
      if (lng) {
        const u32 wa = wb + ((lane >> 3) & 1) * 1024 + (((lane & 7) ^ (lane >> 4)) + 8 * (lane >> 4)) * 16;
        const u32 kv = lds32(SM_KV + 4 * sig), bi = (g >> 1) == q ? (hi ? kv << 16 : kv) : 0u;
        float acc[8][4] = {};
#pragma unroll
        for (int j = 0; j < 4; j++) { const uint4 a = ldsm4t(wa + V2O + j * 256); mma8_hf(acc[2 * j], a.x, a.y, bi); mma8_hf(acc[2 * j + 1], a.z, a.w, bi); }
        u32 bt = tp + (T9E + hi * TEO + (g >> 1) - q) * 4, wt = wa + W9O;
#pragma unroll 1
        for (int ty = 0; ty < 2; ty++) {
          uint4 a[4];
#pragma unroll
          for (int be = 0; be < 4; be++) a[be] = ldsm4t(wt + be * 256);
          u32 b1 = lds32(bt - 16);
#pragma unroll
          for (int d = 0; d < 8; d++) {
            const u32 b0 = lds32(bt + 16 * d);
#pragma unroll
            for (int be = 0; be < 4; be++) if (d + 2 * be < 8) mma_hf(acc[d + 2 * be], a[be].x, a[be].y, a[be].z, a[be].w, b0, b1);
            b1 = b0;
          }
          bt += (T7E - T9E) * 4; wt += W7O - W9O;
        }
        __syncwarp();
#pragma unroll
        for (int j = 0; j < 8; j++) sts128(wb + W9O + j * 512 + lane * 16, fu(acc[j][0]), fu(acc[j][1]), fu(acc[j][2]), fu(acc[j][3]));
        TS(34);
      }
      if (w != 9) barrive(10, 352);
      if (w >= 8) barrive(11, 256);
    }
    if (w < 8) {
      const int u0 = 4 * (w - 4) + 2 * rho;
      const u32 t4 = SM_TAP + 4 * TAPS;
      u32 tr = t4 + ((hi ? TO : TE) + (g >> 1) - q) * 4;
      u32 zb = SM_Z4 + 256 + ((lane >> 3) & 1) * ZP4 + u0 * 128 + (lane & 7) * 16 + (lane >> 4) * 128;
      float acc[4][4] = {};
      u32 prev = 0;
#pragma unroll 1
      for (int it = min(u0 + 2, 4); it; it--) {
#pragma unroll
        for (int s = 0; s < 8; s++) {
          const uint4 z = ldsm4(zb - 16 * s);
          const u32 t0 = lds32(tr + 32 * s), t1 = lds32(tr + 32 * s + 16);
          mma_hf(acc[s & 1], t0, t1, prev, t0, z.x, z.y);
          mma_hf(acc[2 + (s & 1)], t0, t1, prev, t0, z.z, z.w);
          prev = t1;
        }
        zb -= 128; tr += 256;
      }
      { const uint4 z = ldsm4(zb); const u32 t0 = lds32(tr), t1 = lds32(tr + 16); mma_hf(acc[0], t0, t1, prev, t0, z.x, z.y); mma_hf(acc[2], t0, t1, prev, t0, z.z, z.w); }
      bsync(11, 256);
      u32 wa = (SM_W + 4 * WSL + W5O + rl16 + (u0 - 3) * 256) ^ 32, bt = t4 + (T5 + g - q) * 4;
#pragma unroll 1
      for (int al = min(u0 - 2, 6); al > 0; al--) {
#pragma unroll
        for (int ty = 0; ty < 2; ty++) {
          const uint4 a = ldsm4t(wa + ty * (W3O - W5O));
          const u32 bb = bt + ty * (T3 - T5) * 4;
          mma_hf(acc[ty], a.x, a.y, a.z, a.w, lds32(bb - 32), lds32(bb - 48));
          mma_hf(acc[2 + ty], a.x, a.y, a.z, a.w, lds32(bb), lds32(bb - 16));
        }
        wa = (wa - 256) ^ 32; bt += 32;
      }
      TS(35);
      const uint2 fc = lds64(SM_SC + 16 * 4 + 8);
      const u32 F = __byte_perm(fu(uf(fc.x) * uf(fc.y)), 0, 0x3232);
      char* yp = gs + (G_Y + (8 * u0 + 2 * q) * BLK + Ps * 32 + 4 * g);
#pragma unroll
      for (int j = 0; j < 2; j++) {
        uint4 s3 = {0, 0, 0, 0};
        if (u0 >= 8) s3 = lds128(SM_W + 4 * WSL + W9O + (u0 - 8 + j) * 512 + lane * 16);
        y_store(acc[2 * j][0] + acc[2 * j + 1][0] + uf(s3.x), acc[2 * j][1] + acc[2 * j + 1][1] + uf(s3.y), acc[2 * j][2] + acc[2 * j + 1][2] + uf(s3.z),
                acc[2 * j][3] + acc[2 * j + 1][3] + uf(s3.w), F, pml, yp + j * 8 * BLK);
      }
      TS(16);
    } else {
      if (!kw) bsync(7, 64);
      if (tid == 352) {
        PROXY_FENCE();
        mb_expect(SM_MB + 16, rho ? SLV : 46080);
        tma3d(SM_UP, &tm_up, SM_MB + 16, 32 * b, 0);
        if (!rho) tma3d(SM_UP + SLV, &tm_us, SM_MB + 16, 4096 + 4 * b, 0);
      }
      TS(17);
      if (w > 8) {
        const u32 t = tid - 288, c = min(t, 71u);
        const char* mp = gs + (G_MOD + (c >> 2) * 128 + (c & 3) * 16);
        const uint4 dk = ldg128(p.dsk + 16 * c), wr = ldg128(p.wr + 16 * c);
        uint4 md[6];
        POLL(_Pragma("unroll") for (int j = 0; j < 6; j++) md[j] = ldr128(mp + j * MODJ),
             ((md[0].x ^ pm) | (md[1].x ^ pm) | (md[2].x ^ pm) | (md[3].x ^ pm) | (md[4].x ^ pm) | (md[5].x ^ pm)) & TAGM, 4);
        const u32 ma = SM_MODS + 16 * c;
#pragma unroll
        for (int j = 0; j < 6; j++) {
          const u32 o = (j % 3 == 1) ? BONE : 0x80008000u;
          md[j] = make_uint4(bfma(md[j].x & ~TAGM, B2P64, o), bfma(md[j].y, B2P64, o), bfma(md[j].z, B2P64, o), bfma(md[j].w, B2P64, o));
          sts128(ma + 1152 * j, md[j].x, md[j].y, md[j].z, md[j].w);
        }
        sts128(ma + 1152 * 6, dk.x, dk.y, dk.z, dk.w);
        const uint4 H = make_uint4(bmul(md[4].x, wr.x), bmul(md[4].y, wr.y), bmul(md[4].z, wr.z), bmul(md[4].w, wr.w));
        sts128(ma + 1152 * 7, H.x, H.y, H.z, H.w);
        sts128(ma + 1152 * 8, bfma(md[4].x, wr.x, H.x ^ 0x80008000u), bfma(md[4].y, wr.y, H.y ^ 0x80008000u), bfma(md[4].z, wr.z, H.z ^ 0x80008000u), bfma(md[4].w, wr.w, H.w ^ 0x80008000u));
        float c4[4] = {};
        mma_bf(c4, md[4].x, md[3].x, md[4].y, md[3].y, wr.x, wr.y); mma_bf(c4, md[4].z, md[3].z, md[4].w, md[3].w, wr.z, wr.w);
        if (q == g >> 1) sts64(SM_RC + (t >> 2) * 8, fu(hi ? c4[1] : c4[0]), fu(hi ? c4[3] : c4[2]));
        if (t < 5) sts128(t < 2 ? SM_ONE + 16 * t : SM_THR + 16 * t - 32, t ? 0 : BONE, t ? 0 : BONE, t ? 0 : BONE, t ? 0 : BONE);
        TS(14);
        barrive(13, 256);
        if (w != 10) barrive(14, 224);
        if (w == 9) {
          bsync(12, 320);
          if (lane == 0 && b < 108) {
            PROXY_FENCE();
            mb_expect(SM_MB + 24, 49152);
            tma3d(SM_WD, &tm_down, SM_MB + 24, 64 * (b % 9), 2 * (b / 9));
          }
        }
      }
    }
    if (w < 9) bsync(13, 256);
  }
  post_conv(p, tid + p.zero, b, ep);
  if (tid == 352 && s2u(smem) != SM0) __trap();
}

typedef CUresult (*EncFn)(CUtensorMap*, CUtensorMapDataType, cuuint32_t, void*, const cuuint64_t*, const cuuint64_t*, const cuuint32_t*, const cuuint32_t*,
                          CUtensorMapInterleave, CUtensorMapSwizzle, CUtensorMapL2promotion, CUtensorMapFloatOOBfill);
static void make_map(EncFn enc, CUtensorMap* tm, void* ptr, int cols, int rows, int bw, int nb, CUtensorMapSwizzle sw) {
  cuuint64_t gd[3] = {(cuuint64_t)cols, 192, (cuuint64_t)(rows / 192)}, gs[2] = {(cuuint64_t)cols * 2, (cuuint64_t)cols * 2 * 192};
  cuuint32_t bd[3] = {(cuuint32_t)bw, 192, (cuuint32_t)nb}, es[3] = {1, 1, 1};
  enc(tm, CU_TENSOR_MAP_DATA_TYPE_BFLOAT16, 3, ptr, gd, gs, bd, es, CU_TENSOR_MAP_INTERLEAVE_NONE, sw, CU_TENSOR_MAP_L2_PROMOTION_NONE, CU_TENSOR_MAP_FLOAT_OOB_FILL_NONE);
}
extern "C" void kernel_launch(void* const* d_in, const int* in_sizes, int n_in, void* d_out, int out_size) {
  static EncFn enc = nullptr;
  static void* scratch = nullptr;
  if (!enc) {
    cudaGetSymbolAddress(&scratch, g_s);
    cudaDriverEntryPointQueryResult qr;
    cudaGetDriverEntryPoint("cuTensorMapEncodeTiled", (void**)&enc, cudaEnableDefault, &qr);
    cudaFuncSetAttribute(fused_kernel, cudaFuncAttributeMaxDynamicSharedMemorySize, SM_TOTAL);
  }
  CUtensorMap tm_mod, tm_gate, tm_gs, tm_up, tm_us, tm_down;
  make_map(enc, &tm_mod, d_in[13], 3456, 576, 32, 3, CU_TENSOR_MAP_SWIZZLE_64B);
  make_map(enc, &tm_gate, d_in[9], 4608, 576, 32, 3, CU_TENSOR_MAP_SWIZZLE_64B);
  make_map(enc, &tm_gs, d_in[9], 4608, 576, 8, 3, CU_TENSOR_MAP_SWIZZLE_NONE);
  make_map(enc, &tm_up, d_in[10], 4608, 576, 32, 3, CU_TENSOR_MAP_SWIZZLE_64B);
  make_map(enc, &tm_us, d_in[10], 4608, 576, 8, 3, CU_TENSOR_MAP_SWIZZLE_NONE);
  make_map(enc, &tm_down, d_in[11], 576, 4608, 64, 2, CU_TENSOR_MAP_SWIZZLE_128B);
  Prm p;
  p.x = (const char*)d_in[0]; p.la = (const char*)d_in[1]; p.ai = (const char*)d_in[2]; p.cr = (const char*)d_in[3];
  p.ci = (const char*)d_in[4]; p.ldt = (const char*)d_in[5]; p.dsk = (const char*)d_in[6]; p.wr = (const char*)d_in[8];
  p.c = (const char*)d_in[12]; p.out = (char*)d_out; p.zero = 0; p.gs = (char*)scratch;
  fused_kernel<<<128, 384, SM_TOTAL>>>(p, tm_mod, tm_gate, tm_gs, tm_up, tm_us, tm_down);
}
```

```cpp
#include <cuda_runtime.h>
#include <cuda.h>
#include <cuda_bf16.h>
#include <cuda_fp16.h>
#include <stdint.h>
#define FUSED 1
#define DEV __device__ __forceinline__
typedef uint32_t u32;

constexpr u32 BLK = 18432, G_Z = 0, G_Y = 128 * BLK, G_MOD = 2 * G_Y, G_KEY = G_MOD + 128 * 128, G_ACT = G_KEY + 128 * 128;
constexpr u32 G_PART = G_ACT + 576 * 128, G_EP = G_PART + 128 * 2048, G_END = G_EP + 128;
__device__ __align__(128) unsigned char g_s[G_END];
#define TS(i)
#define TS0()
#define TSE()
#define ERRF(code)

constexpr int SM0 = 1024;
constexpr int ROW = 1168, SLV = 36864;
constexpr int SM_GATE = SM0, SM_UP = SM_GATE + 46080, SM_XST = SM_UP + 46080, SM_MODS = SM_XST + 16 * ROW, SM_W = SM_MODS + 11008;
constexpr int KTAB = 9216, WSL = 12544, W5O = 128, W3O = 3328, V2O = 6400, W9O = 8448, W7O = 10496;
constexpr int ZPS = 2192, ZSS = 2 * ZPS, ZP4 = 2368;
constexpr int SM_ZS = SM_W + 5 * WSL, SM_Z4 = SM_ZS + 4 * ZSS, SM_TAP = SM_Z4 + 2 * ZP4, TAPS = 3328;
constexpr int SM_MB = SM_TAP + 5 * TAPS;
constexpr int SM_SC = SM_MB + 32;
constexpr int SM_KV = SM_SC + 80;
constexpr int SM_THR = SM_KV + 32;
constexpr int SM_SLOT = SM_THR + 48;
constexpr int SM_KEY = SM_SLOT + 32;
constexpr int SM_ST = SM_KEY + 64;
constexpr int SM_ST2 = SM_ST + 256;
constexpr int SM_RC = SM_ST2 + 256;
constexpr int SM_SP = SM_RC + 192;
constexpr int SM_AF = SM_SP + 1152, SM_SIL = SM_AF + 1152, SM_END = SM_SP + 5760;
constexpr int SM_ONE = SM_MODS + 9 * 1152;
constexpr int SM_WD = SM_W, SM_XS = SM_W + 49152, SM_AC = SM_ZS, SM_RED = SM_AC + 6144, SM_LIST = SM_TAP;
constexpr int SM_TOTAL = SM_END - SM0;
static_assert(SM_W % 1024 == 0 && SM_MODS + 8 * KTAB <= SM_ZS && SM_ZS + 2 * KTAB <= SM_TAP && SM_RED + 10240 <= SM_TAP && SM_XS + 8 * ROW <= SM_ZS, "smem map");
static_assert(SM_MB % 16 == 0 && SM_THR % 16 == 0 && SM_ST % 16 == 0 && SM_SP % 16 == 0 && SM_TOTAL <= 232448, "smem map");
constexpr int TE = 4, TO = 276, T5 = 560, T3 = 624, T9E = 680, T7E = 760, TEO = 40;
constexpr int SPIN = 1 << 16, NEARLY = 4;
constexpr u32 TAGM = 0x40004000u, TAGR = 0x40000000u, INVAL = 0x00004801u;

DEV u32 s2u(const void* p) { return (u32)__cvta_generic_to_shared(p); }
DEV void mma_bf(float (&c)[4], u32 a0, u32 a1, u32 a2, u32 a3, u32 b0, u32 b1) {
  asm("mma.sync.aligned.m16n8k16.row.col.f32.bf16.bf16.f32 {%0,%1,%2,%3},{%4,%5,%6,%7},{%8,%9},{%0,%1,%2,%3};"
      : "+f"(c[0]), "+f"(c[1]), "+f"(c[2]), "+f"(c[3]) : "r"(a0), "r"(a1), "r"(a2), "r"(a3), "r"(b0), "r"(b1));
}
DEV void mma_hf(float (&c)[4], u32 a0, u32 a1, u32 a2, u32 a3, u32 b0, u32 b1) {
  asm("mma.sync.aligned.m16n8k16.row.col.f32.f16.f16.f32 {%0,%1,%2,%3},{%4,%5,%6,%7},{%8,%9},{%0,%1,%2,%3};"
      : "+f"(c[0]), "+f"(c[1]), "+f"(c[2]), "+f"(c[3]) : "r"(a0), "r"(a1), "r"(a2), "r"(a3), "r"(b0), "r"(b1));
}
DEV void mma8_bf(float (&c)[4], u32 a0, u32 a1, u32 b0) {
  asm("mma.sync.aligned.m16n8k8.row.col.f32.bf16.bf16.f32 {%0,%1,%2,%3},{%4,%5},{%6},{%0,%1,%2,%3};"
      : "+f"(c[0]), "+f"(c[1]), "+f"(c[2]), "+f"(c[3]) : "r"(a0), "r"(a1), "r"(b0));
}
DEV void mma8_hf(float (&c)[4], u32 a0, u32 a1, u32 b0) {
  asm("mma.sync.aligned.m16n8k8.row.col.f32.f16.f16.f32 {%0,%1,%2,%3},{%4,%5},{%6},{%0,%1,%2,%3};"
      : "+f"(c[0]), "+f"(c[1]), "+f"(c[2]), "+f"(c[3]) : "r"(a0), "r"(a1), "r"(b0));
}
DEV u32 movm(u32 x) { u32 r; asm("movmatrix.sync.aligned.m8n8.trans.b16 %0,%1;" : "=r"(r) : "r"(x)); return r; }
DEV uint4 ldsm4(u32 a) { uint4 r; asm volatile("ldmatrix.sync.aligned.m8n8.x4.shared.b16 {%0,%1,%2,%3},[%4];" : "=r"(r.x), "=r"(r.y), "=r"(r.z), "=r"(r.w) : "r"(a)); return r; }
DEV uint4 ldsm4t(u32 a) { uint4 r; asm volatile("ldmatrix.sync.aligned.m8n8.x4.trans.shared.b16 {%0,%1,%2,%3},[%4];" : "=r"(r.x), "=r"(r.y), "=r"(r.z), "=r"(r.w) : "r"(a)); return r; }
DEV u32 lds32(u32 a) { u32 r; asm volatile("ld.volatile.shared.u32 %0,[%1];" : "=r"(r) : "r"(a)); return r; }
DEV uint2 lds64(u32 a) { uint2 r; asm volatile("ld.shared.v2.u32 {%0,%1},[%2];" : "=r"(r.x), "=r"(r.y) : "r"(a)); return r; }
DEV uint4 lds128(u32 a) { uint4 r; asm volatile("ld.shared.v4.u32 {%0,%1,%2,%3},[%4];" : "=r"(r.x), "=r"(r.y), "=r"(r.z), "=r"(r.w) : "r"(a)); return r; }
DEV void sts16(u32 a, u32 v) { asm volatile("st.shared.u16 [%0],%1;" ::"r"(a), "h"((unsigned short)v) : "memory"); }
DEV void sts32(u32 a, u32 v) { asm volatile("st.shared.u32 [%0],%1;" ::"r"(a), "r"(v) : "memory"); }
DEV void sts64(u32 a, u32 x, u32 y) { asm volatile("st.shared.v2.u32 [%0],{%1,%2};" ::"r"(a), "r"(x), "r"(y) : "memory"); }
DEV void sts128(u32 a, u32 x, u32 y, u32 z, u32 w) { asm volatile("st.shared.v4.u32 [%0],{%1,%2,%3,%4};" ::"r"(a), "r"(x), "r"(y), "r"(z), "r"(w) : "memory"); }
DEV uint4 ldr128(const void* p) { uint4 v; asm volatile("ld.relaxed.gpu.global.v4.u32 {%0,%1,%2,%3},[%4];" : "=r"(v.x), "=r"(v.y), "=r"(v.z), "=r"(v.w) : "l"(p) : "memory"); return v; }
DEV uint2 ldr64(const void* p) { uint2 v; asm volatile("ld.relaxed.gpu.global.v2.u32 {%0,%1},[%2];" : "=r"(v.x), "=r"(v.y) : "l"(p) : "memory"); return v; }
DEV u32 ldr32(const void* p) { u32 v; asm volatile("ld.relaxed.gpu.global.u32 %0,[%1];" : "=r"(v) : "l"(p) : "memory"); return v; }
DEV void str128(void* p, u32 x, u32 y, u32 z, u32 w) { asm volatile("st.relaxed.gpu.global.v4.u32 [%0],{%1,%2,%3,%4};" ::"l"(p), "r"(x), "r"(y), "r"(z), "r"(w) : "memory"); }
DEV void str64(void* p, u32 x, u32 y) { asm volatile("st.relaxed.gpu.global.v2.u32 [%0],{%1,%2};" ::"l"(p), "r"(x), "r"(y) : "memory"); }
DEV void str32(void* p, u32 x) { asm volatile("st.relaxed.gpu.global.u32 [%0],%1;" ::"l"(p), "r"(x) : "memory"); }
DEV void str16(void* p, u32 x) { asm volatile("st.relaxed.gpu.global.u16 [%0],%1;" ::"l"(p), "h"((unsigned short)x) : "memory"); }
DEV uint4 ldg128(const void* p) { uint4 v; asm volatile("ld.global.nc.v4.u32 {%0,%1,%2,%3},[%4];" : "=r"(v.x), "=r"(v.y), "=r"(v.z), "=r"(v.w) : "l"(p)); return v; }
DEV uint2 ldg64(const void* p) { uint2 v; asm volatile("ld.global.nc.v2.u32 {%0,%1},[%2];" : "=r"(v.x), "=r"(v.y) : "l"(p)); return v; }
DEV u32 ldg32(const void* p) { u32 v; asm volatile("ld.global.nc.u32 %0,[%1];" : "=r"(v) : "l"(p)); return v; }
DEV u32 ldg16(const void* p) { unsigned short v; asm volatile("ld.global.nc.u16 %0,[%1];" : "=h"(v) : "l"(p)); return v; }
#define bsync(id, n) asm volatile("bar.sync %0,%1;" ::"n"(id), "n"(n) : "memory")
#define barrive(id, n) asm volatile("bar.arrive %0,%1;" ::"n"(id), "n"(n) : "memory")
DEV void mb_init(u32 a) { asm volatile("mbarrier.init.shared.b64 [%0],1;" ::"r"(a) : "memory"); }
DEV void mb_expect(u32 a, u32 bytes) { asm volatile("mbarrier.arrive.expect_tx.shared.b64 _,[%0],%1;" ::"r"(a), "r"(bytes) : "memory"); }
DEV void mb_wait(u32 a) {
  u32 ok; int it = 0;
  do { asm volatile("{.reg .pred p; mbarrier.try_wait.parity.shared.b64 p,[%1],0; selp.u32 %0,1,0,p;}" : "=r"(ok) : "r"(a) : "memory"); } while (!ok && ++it < SPIN);
}
DEV void bulk_out(void* dst, u32 src) { asm volatile("cp.async.bulk.global.shared::cta.bulk_group [%0],[%1],1152;" ::"l"(dst), "r"(src) : "memory"); }
DEV void tma3d(u32 dst, const CUtensorMap* tm, u32 mb, int c0, int c2) {
  asm volatile("cp.async.bulk.tensor.3d.shared::cluster.global.mbarrier::complete_tx::bytes [%0],[%1,{%3,0,%4}],[%2];"
               ::"r"(dst), "l"((uint64_t)tm), "r"(mb), "r"(c0), "r"(c2) : "memory");
}
DEV float blo(u32 w) { return __uint_as_float(w << 16); }
DEV float bhi(u32 w) { return __uint_as_float(w & 0xffff0000u); }
DEV u32 pk_bf(float lo, float hi) { u32 r; asm("cvt.rn.bf16x2.f32 %0,%1,%2;" : "=r"(r) : "f"(hi), "f"(lo)); return r; }
DEV u32 pk_hf(float lo, float hi) { u32 r; asm("cvt.rn.f16x2.f32 %0,%1,%2;" : "=r"(r) : "f"(hi), "f"(lo)); return r; }
DEV float rbf(float x) { return __uint_as_float(pk_bf(0.f, x) & 0xffff0000u); }
DEV u32 bfma(u32 a, u32 b, u32 c) { u32 r; asm("fma.rn.bf16x2 %0,%1,%2,%3;" : "=r"(r) : "r"(a), "r"(b), "r"(c)); return r; }
DEV u32 bmul(u32 a, u32 b) { u32 r; asm("mul.rn.bf16x2 %0,%1,%2;" : "=r"(r) : "r"(a), "r"(b)); return r; }
DEV u32 badd(u32 a, u32 b) { u32 r; asm("add.rn.bf16x2 %0,%1,%2;" : "=r"(r) : "r"(a), "r"(b)); return r; }
DEV u32 hadd(u32 a, u32 b) { u32 r; asm("add.rn.f16x2 %0,%1,%2;" : "=r"(r) : "r"(a), "r"(b)); return r; }
DEV u32 hfma(u32 a, u32 b, u32 c) { u32 r; asm("fma.rn.f16x2 %0,%1,%2,%3;" : "=r"(r) : "r"(a), "r"(b), "r"(c)); return r; }
struct C2 { u32 re, im; };
DEV C2 cm2(C2 a, C2 b) {
  const __half2 ar = *reinterpret_cast<__half2*>(&a.re), ai = *reinterpret_cast<__half2*>(&a.im), br = *reinterpret_cast<__half2*>(&b.re), bi = *reinterpret_cast<__half2*>(&b.im);
  __half2 re = __hfma2(ar, br, __hneg2(__hmul2(ai, bi))), im = __hfma2(ar, bi, __hmul2(ai, br));
  return {*reinterpret_cast<u32*>(&re), *reinterpret_cast<u32*>(&im)};
}
DEV C2 pk2(const float2 (&a)[2]) { return {pk_hf(a[0].x, a[1].x), pk_hf(a[0].y, a[1].y)}; }
DEV C2 pk2c(const float2 (&a)[2]) { return {pk_hf(a[0].x, a[1].x), pk_hf(-a[0].y, -a[1].y)}; }
DEV u32 cpy(u32 x, u32 zr, int alt) {
  u32 r;
  if (alt) asm volatile("xor.b32 %0,%1,%2;" : "=r"(r) : "r"(x), "r"(zr)); else asm volatile("mad.lo.u32 %0,%2,%2,%1;" : "=r"(r) : "r"(x), "r"(zr));
  return r;
}
DEV float ex2(float x) { float r; asm("ex2.approx.ftz.f32 %0,%1;" : "=f"(r) : "f"(x)); return r; }
DEV float rcpf(float x) { float r; asm("rcp.approx.ftz.f32 %0,%1;" : "=f"(r) : "f"(x)); return r; }
DEV float2 cmul(float2 a, float2 b) { return make_float2(fmaf(a.x, b.x, -a.y * b.y), fmaf(a.x, b.y, a.y * b.x)); }
DEV float2 csq(float2 a) { return make_float2(fmaf(a.x, a.x, -a.y * a.y), (a.x + a.x) * a.y); }
DEV float2 cexp(float lr2, float th) {
  const float m = ex2(lr2);
  return make_float2(m * __cosf(th), m * __sinf(th));
}
DEV float silu_f(float v) { return v * rcpf(1.f + ex2(-1.4426950408889634f * v)); }
constexpr u32 B2P64 = 0x5F805F80u, B2M64 = 0x1F801F80u, BONE = 0x3F803F80u;
constexpr u32 MODJ = 18 * 128;
DEV float sqrta(float x) { float r; asm("sqrt.approx.ftz.f32 %0,%1;" : "=f"(r) : "f"(x)); return r; }
DEV u32 fu(float x) { return __float_as_uint(x); }
DEV float uf(u32 x) { return __uint_as_float(x); }
DEV void mma_hf_o(float (&d)[4], const float (&c)[4], const u32 (&a)[4], u32 b0, u32 b1) {
  asm("mma.sync.aligned.m16n8k16.row.col.f32.f16.f16.f32 {%0,%1,%2,%3},{%4,%5,%6,%7},{%8,%9},{%10,%11,%12,%13};"
      : "=f"(d[0]), "=f"(d[1]), "=f"(d[2]), "=f"(d[3]) : "r"(a[0]), "r"(a[1]), "r"(a[2]), "r"(a[3]), "r"(b0), "r"(b1), "f"(c[0]), "f"(c[1]), "f"(c[2]), "f"(c[3]));
}

DEV void cpa16(u32 dst, const void* src) { asm volatile("cp.async.cg.shared.global [%0],[%1],16;" ::"r"(dst), "l"(src) : "memory"); }
DEV void tm_pre(const CUtensorMap* tm) { asm volatile("prefetch.tensormap [%0];" ::"l"((uint64_t)tm) : "memory"); }
#define PROXY_FENCE() asm volatile("fence.proxy.async.shared::cta;" ::: "memory")
struct Prm {
  const char *x, *la, *ai, *cr, *ci, *ldt, *c;
  char* gs;
  const char *dsk, *wr;
  char* out;
  u32 zero;
};
constexpr float LOG2E = 1.4426950408889634f, F2P64 = 1.8446744073709552e19f, F2M64 = 5.421010862427522e-20f;

DEV void y_store(float c0, float c1, float c2, float c3, u32 F, u32 pml, char* yp) {
  str32(yp, bmul(pk_bf(c0, c2), F) | pml);
  str32(yp + BLK, bmul(pk_bf(c1, c3), F) | pml);
}
#define POLL(load, cond_bad, code) { int it_ = 0; do { load; if (++it_ > SPIN) { ERRF(code); break; } } while (__any_sync(~0u, (cond_bad))); }
#define POLLW(load, cond_bad, code) { int it_ = 0; while (__any_sync(~0u, (cond_bad))) { if (++it_ > SPIN) { ERRF(code); break; } load; } }

DEV void post_conv(const Prm& p, const u32 tid, const u32 b, const u32 ep) {
  const u32 w = tid >> 5, lane = tid & 31;
  const u32 g = lane >> 2, q = lane & 3, e = g >> 2, h = (g >> 1) & 1, hi = g & 1;
  const u32 rho = b & 1, par = (ep + 1) & 1, pm = par ? TAGM : 0;
  char* const gs = p.gs;
  const u32 cho = 128 * w + 64 * e + 16 * q;
  u32 x1[4][4], h2[4][4], key[4], lt;
  char* const rowp = gs + (b * BLK + (4 * h + 8 * hi) * 1152 + cho);
  if (w < 9) {
    const char* ysrc = gs + (G_Y + b * BLK + w * 2048 + (q >> 1) * 1024 + (g >> 1) * 256 + hi * 32 + (q & 1) * 16);
    uint4 yv[4];
    if (w < 4) {
#pragma unroll
      for (int v = 0; v < 4; v++) yv[v] = ldr128(ysrc + 64 * v);
    } else {
#pragma unroll
      for (int v = 0; v < 4; v++) yv[v].x = INVAL;
    }
    const u32 ma = SM_MODS + cho, xa = SM_XST + (2 * h + 4 * hi) * ROW + cho;
    const uint4 sa = lds128(ma), ca = lds128(ma + 1152), ga = lds128(ma + 2304), dk = lds128(ma + 6912);
    const uint4 rb = lds128((g & 2) ? SM_ONE + 16 * hi : (ma ^ 64) + 8064 + 1152 * hi);
    const u32 saw[4] = {sa.x, sa.y, sa.z, sa.w}, caw[4] = {ca.x, ca.y, ca.z, ca.w}, gaw[4] = {ga.x, ga.y, ga.z, ga.w}, dw[4] = {dk.x, dk.y, dk.z, dk.w};
    u32 hD[4][4];
#pragma unroll
    for (int k = 0; k < 4; k++) {
      const uint4 st = lds128(SM_ST + 16 * (2 * h + 4 * hi + (k & 1) + 8 * (k >> 1))), xv = lds128(xa + ((k & 1) + 8 * (k >> 1)) * ROW);
      x1[k][0] = xv.x; x1[k][1] = xv.y; x1[k][2] = xv.z; x1[k][3] = xv.w;
#pragma unroll
      for (int v = 0; v < 4; v++) {
        const u32 d = badd(x1[k][v], st.x), z = bfma(d, st.y, bmul(d, st.z));
        hD[k][v] = bmul(badd(bmul(z, caw[v]), saw[v]), dw[v]);
      }
    }
    const bool own = (q >> 1) == e;
    const u32 spw = SM_SP + (2 * w + e) * 320 + (g & 3) * 16 + (own ? ((q & 1) == h ? 4 : 12) : 8 - 8 * (q & 1));
    TS(18);
    if (w >= 4) bsync(12, 320);
    POLLW(_Pragma("unroll") for (int v = 0; v < 4; v++) if ((yv[v].x ^ pm) & TAGM) yv[v] = ldr128(ysrc + 64 * v),
          ((yv[0].x ^ pm) | (yv[1].x ^ pm) | (yv[2].x ^ pm) | (yv[3].x ^ pm)) & TAGM, 5);
    TS(19);
#pragma unroll
    for (int k = 0; k < 4; k += 2) {
      float X[4] = {}, Y[4] = {}, R[4] = {};
#pragma unroll
      for (int v = 0; v < 4; v++) {
        const u32 y0 = k ? yv[v].z : yv[v].x & ~TAGM, y1 = k ? yv[v].w : yv[v].y;
        x1[k][v] = badd(x1[k][v], bmul(gaw[v], bfma(movm(y0), B2P64, hD[k][v])));
        x1[k + 1][v] = badd(x1[k + 1][v], bmul(gaw[v], bfma(movm(y1), B2P64, hD[k + 1][v])));
        mma8_bf(X, x1[k][v], x1[k + 1][v], x1[k][v]); mma8_bf(Y, x1[k][v], x1[k + 1][v], x1[k + 1][v]);
        if (v & 1) mma_bf(R, x1[k][v - 1], x1[k + 1][v - 1], x1[k][v], x1[k + 1][v], v & 2 ? rb.z : rb.x, v & 2 ? rb.w : rb.y);
      }
      sts32(spw + k * 64, fu(own ? (hi ? X[1] : X[0]) : R[0] + R[1]));
      sts32(spw + k * 64 + 64, fu(own ? (hi ? Y[3] : Y[2]) : R[2] + R[3]));
    }
    barrive(1, 320);
    TS(36);
    const uint4 sb = lds128(ma + 3456), cb = lds128(ma + 4608), gb = lds128(ma + 5760);
    const u32 sbw[4] = {sb.x, sb.y, sb.z, sb.w}, cbw[4] = {cb.x, cb.y, cb.z, cb.w}, gbw[4] = {gb.x, gb.y, gb.z, gb.w};
    bsync(2, 320);
    TS(37);
    lt = lds32(SM_THR + 36);
#pragma unroll
    for (int k = 0; k < 4; k++) {
      const uint4 st = lds128(SM_ST2 + 64 * k + 16 * (g & 3));
      key[k] = st.w;
      u32 o[4];
#pragma unroll
      for (int v = 0; v < 4; v++) {
        const u32 d = badd(x1[k][v], st.x), z = bfma(d, st.y, bmul(d, st.z));
        h2[k][v] = badd(bmul(z, cbw[v]), sbw[v]);
        o[v] = badd(x1[k][v], bmul(gbw[v], h2[k][v]));
      }
      h2[k][0] = bmul(h2[k][0], B2M64) | TAGR;
      if (key[k] >= lt) str128(rowp + k * 1152, h2[k][0], h2[k][1], h2[k][2], h2[k][3]);
      sts128(xa + ((k & 1) + 8 * (k >> 1)) * ROW, o[0], o[1], o[2], o[3]);
    }
    PROXY_FENCE();
    barrive(3, 320);
    TS(21);
  } else if (w == 10) {
    bsync(14, 224);
    uint2 rc = lds64(SM_RC + 8 * min(lane, 17u));
    float r1 = lane < 18 ? uf(rc.x) : 0.f, r2 = lane < 18 ? uf(rc.y) : 0.f;
#pragma unroll 1
    for (int o = 16; o; o >>= 1) { r1 += __shfl_xor_sync(~0u, r1, o); r2 += __shfl_xor_sync(~0u, r2, o); }
    const u32 tl = 4 * ((lane >> 1) & 1) + ((lane >> 2) & 3) + 8 * (lane & 1), kl = (2047 - 16 * b - tl) << 2 | par * 3;
    const u32 row = SM_XST + ((lane & 2) + 4 * (lane & 1) + ((lane >> 2) & 1) + (lane & 8)) * ROW;
    char* const op = p.out + (b * BLK + tl * 1152);
    const u32 spr = SM_SP + (lane >> 4) * 9 * 320 + (lane & 15) * 16;
    TS(31);
    bsync(1, 320);
    float S1 = 0.f, S2 = 0.f, S3 = 0.f;
#pragma unroll
    for (int i = 0; i < 9; i++) { uint4 t = lds128(spr + i * 320); S1 += uf(t.x); S2 += uf(t.y); S3 += uf(t.z); }
    S1 += __shfl_xor_sync(~0u, S1, 16); S2 += __shfl_xor_sync(~0u, S2, 16); S3 += __shfl_xor_sync(~0u, S3, 16);
    const float mu = S1 * (1.f / 576.f), var = fmaxf(fmaf(-mu, mu, S2 * (1.f / 576.f)), 0.f);
    const float m = rbf(mu), rs = rcpf(rbf(sqrta(rbf(rbf(var) + 1e-5f))));
    const u32 rb = pk_bf(0.f, fmaf(fmaf(-m, r1, S3), rs, r2) + 0.f);
    const u32 ok = ((rb ^ (((int)rb >> 31) | 0x80000000)) & 0xffff0000u) | kl;
    if (lane < 16) str32(gs + (G_KEY + b * 128 + 4 * lane), ok);
    TS(20);
    const float rh = rbf(rs);
    sts128(SM_ST2 + 16 * (lane & 15), pk_bf(-m, -m), pk_bf(rh, rh), pk_bf(rs - rh, rs - rh), ok);
    sts32(SM_KEY + 4 * (lane & 15), ok);
    __syncwarp();
    const uint4 o0 = lds128(SM_KEY + 2 * (lane & 16)), o1 = lds128(SM_KEY + 2 * (lane & 16) + 16);
    u32 lr = (o0.x > ok) + (o0.y > ok) + (o0.z > ok) + (o0.w > ok) + (o1.x > ok) + (o1.y > ok) + (o1.z > ok) + (o1.w > ok);
    lr += __shfl_xor_sync(~0u, lr, 16);
    if (lr == NEARLY - 1) sts32(SM_THR + 36, ok);
    barrive(2, 320);
    bsync(3, 320);
    if (lane < 16 && lr >= 8) bulk_out(op, row);
    bsync(6, 320);
    if (lane < 16 && lr < 8 && ok < lds32(SM_SLOT + 28)) bulk_out(op, row);
    asm volatile("cp.async.bulk.commit_group;" ::: "memory");
  }
  uint4 rv[3];
  const char* rs_;
  if (w < 8) {
    const char* ks = gs + (G_KEY + (8 * g + w) * 128 + q * 16);
    const u32 kt = par * 3;
    uint4 ka, kc;
    POLL({ ka = ldr128(ks); kc = ldr128(ks + 8192); }, ((ka.x ^ kt) | (kc.x ^ kt)) & 3, 6);
    TS(23);
    const u32 kk[8] = {ka.x, ka.y, ka.z, ka.w, kc.x, kc.y, kc.z, kc.w};
    u32 mx = max(max(max(kk[0], kk[1]), max(kk[2], kk[3])), max(max(kk[4], kk[5]), max(kk[6], kk[7])));
#pragma unroll
    for (int o = 4; o < 32; o *= 2) mx = max(mx, __shfl_xor_sync(~0u, mx, o));
    if (lane < 4) asm volatile("red.shared.max.u32 [%0],%1;" ::"r"(SM_THR + 16 * (w & 1) + 4 * lane), "r"(mx) : "memory");
    bsync(4, 256);
    TS(33);
    const uint4 t0 = lds128(SM_THR), t1 = lds128(SM_THR + 16);
    u32 L0 = min(min(min(t0.x, t0.y), min(t0.z, t0.w)), min(min(t1.x, t1.y), min(t1.z, t1.w)));
#pragma unroll 1
    for (int it = 0; it < 128; it++) {
      u32 c = 0;
#pragma unroll
      for (int j = 0; j < 8; j++) c += kk[j] >= L0 ? 4 : 0;
      if (c) {
        u32 a;
        asm volatile("atom.shared.add.u32 %0,[%1],%2;" : "=r"(a) : "r"(SM_THR + 32), "r"(c) : "memory");
#pragma unroll
        for (int j = 0; j < 8; j++) if (kk[j] >= L0) { sts32(SM_LIST + a, kk[j]); a += 4; }
      }
      bsync(5, 256);
      TS(38);
      const u32 n = lds32(SM_THR + 32), m0 = lds32(SM_LIST + 4 * lane), my = 4 * lane < n ? m0 : 0;
      const uint4 cd = lds128(SM_LIST + 16 * w);
      const u32 cc[4] = {cd.x, cd.y, cd.z, cd.w};
#pragma unroll
      for (int j = 0; j < 4; j++) {
        const u32 r = __popc(__ballot_sync(~0u, my > cc[j]));
        if (r < 8 && 16 * w + 4 * j < n) sts32(SM_SLOT + 4 * r, cc[j]);
      }
      if (n <= 128) break;
      bsync(15, 256);
      L0 = lds32(SM_SLOT + 28);
      sts32(SM_THR + 32, 0);
      bsync(15, 256);
    }
  }
  if (w < 9) {
    bsync(6, 320);
    TS(24);
    const u32 g8 = lds32(SM_SLOT + 28);
    if (w < 8) {
      rs_ = gs + ((2047 - ((lds32(SM_SLOT + 4 * w) >> 2) & 2047)) * 1152 + lane * 16);
      rv[0] = ldr128(rs_); rv[1] = ldr128(rs_ + 512);
      rv[2].x = TAGR;
      if (lane < 8) rv[2] = ldr128(rs_ + 1024);
    }
    if (__any_sync(~0u, max(max(key[0], key[1]), max(key[2], key[3])) >= g8)) {
#pragma unroll
      for (int k = 0; k < 4; k++) if (key[k] >= g8) {
        if (key[k] < lt) str128(rowp + k * 1152, h2[k][0], h2[k][1], h2[k][2], h2[k][3]);
        str128(rowp + (G_Y + k * 1152), bmul(x1[k][0], B2M64) | TAGR, x1[k][1], x1[k][2], x1[k][3]);
      }
    }
  }
  const u32 kq = w & 3, tg = 2 - (w >> 2);
  uint4 A[24];
  {
    const u32 row = 144 * kq + 8 * (lane >> 4) + (lane & 7), ab = (lane & 8) ? SM_UP : SM_GATE;
    mb_wait(SM_MB + 8); mb_wait(SM_MB + 16);
    if (tg < 2) {
      const u32 aa = ab + row * 64 + (((2 * tg) ^ ((lane & 7) >> 1)) << 4);
#pragma unroll
      for (int s = 0; s < 9; s++) { A[s] = ldsm4t(aa + s * 1024); A[9 + s] = ldsm4t((aa ^ 16) + s * 1024); }
    } else {
#pragma unroll
      for (int s = 0; s < 9; s++) A[s] = ldsm4t(ab + SLV + row * 16 + s * 256);
    }
  }
  TS(22);
  if (w < 8) {
    POLLW({ rv[0] = ldr128(rs_); rv[1] = ldr128(rs_ + 512); if (lane < 8) rv[2] = ldr128(rs_ + 1024); },
          ((rv[0].x ^ TAGR) | (rv[1].x ^ TAGR) | (rv[2].x ^ TAGR)) & TAGM, 8);
#pragma unroll
    for (int j = 0; j < 3; j++) if (j < 2 || lane < 8) sts128(SM_XS + w * ROW + lane * 16 + j * 512, bmul(rv[j].x ^ TAGR, B2P64), rv[j].y, rv[j].z, rv[j].w);
  }
  __syncthreads();
  TS(25);
  {
    float c0[2][4] = {}, c1[2][4] = {};
    const u32 ba = SM_XS + (lane & 7) * ROW + (18 * kq + (lane >> 3)) * 16;
    uint4 bb[5];
#pragma unroll
    for (int s = 0; s < 5; s++) bb[s] = ldsm4(ba + s * 64);
#pragma unroll
    for (int s = 0; s < 9; s++) mma_bf(c0[s & 1], A[s].x, A[s].y, A[s].z, A[s].w, s & 1 ? bb[s >> 1].z : bb[s >> 1].x, s & 1 ? bb[s >> 1].w : bb[s >> 1].y);
    const u32 ra = SM_RED + (8 * tg + kq) * 512 + lane * 16;
    if (tg < 2) {
#pragma unroll
      for (int s = 0; s < 9; s++) mma_bf(c1[s & 1], A[9 + s].x, A[9 + s].y, A[9 + s].z, A[9 + s].w, s & 1 ? bb[s >> 1].z : bb[s >> 1].x, s & 1 ? bb[s >> 1].w : bb[s >> 1].y);
      sts128(ra + 2048, fu(c1[0][0] + c1[1][0]), fu(c1[0][1] + c1[1][1]), fu(c1[0][2] + c1[1][2]), fu(c1[0][3] + c1[1][3]));
    }
    sts128(ra, fu(c0[0][0] + c0[1][0]), fu(c0[0][1] + c0[1][1]), fu(c0[0][2] + c0[1][2]), fu(c0[0][3] + c0[1][3]));
  }
  TS(39);
  __syncthreads();
  if (w >= 7 + rho) {
    const u32 t = 11 - w;
    float s[4] = {};
#pragma unroll
    for (int i = 0; i < 4; i++) { const uint4 u = lds128(SM_RED + (t * 4 + i) * 512 + lane * 16); s[0] += uf(u.x); s[1] += uf(u.y); s[2] += uf(u.z); s[3] += uf(u.w); }
    const u32 sg = pk_bf(silu_f(rbf(s[0])), silu_f(rbf(s[1])));
    const u32 act = movm(bmul(bmul(sg, pk_bf(s[2], s[3])), B2M64));
    str32(gs + (G_ACT + (t < 4 ? 4 * b + t : 512 + (b >> 1)) * 128 + lane * 4), act | (q ? 0 : pm));
  }
  TS(26);
  if (b < 108) {
    const char* src = gs + (G_ACT + (b / 9) * 6144 + tid * 16);
    uint4 a = ldr128(src);
    if (w < 4) {
      const u32 aa = SM_WD + (8 * (lane >> 4) + (lane & 7)) * 128 + (((2 * w + ((lane >> 3) & 1)) ^ (lane & 7)) << 4);
      mb_wait(SM_MB + 24);
#pragma unroll
      for (int s = 0; s < 24; s++) A[s] = ldsm4t(aa + s * 2048);
    }
    TS(28);
    POLLW(a = ldr128(src), (a.x ^ pm) & TAGM, 9);
    sts128(SM_AC + tid * 16, a.x & ~TAGM, a.y, a.z, a.w);
    TS(27);
    if (w < 4) {
      bsync(8, 384);
      float c[4][4] = {};
#pragma unroll
      for (int s = 0; s < 12; s++) {
        const uint4 bb = ldsm4(SM_AC + lane * 16 + s * 512);
        mma_bf(c[2 * (s & 1)], A[2 * s].x, A[2 * s].y, A[2 * s].z, A[2 * s].w, bb.x, bb.y);
        mma_bf(c[2 * (s & 1) + 1], A[2 * s + 1].x, A[2 * s + 1].y, A[2 * s + 1].z, A[2 * s + 1].w, bb.z, bb.w);
      }
      char* dst = gs + (G_PART + b * 2048 + w * 512 + lane * 8);
      u32 o[4];
#pragma unroll
      for (int i = 0; i < 4; i++) o[i] = (fu(((c[0][i] + c[1][i]) + (c[2][i] + c[3][i])) * F2P64) & ~1u) | par;
      str64(dst, o[0], o[1]); str64(dst + 256, o[2], o[3]);
      TS(29);
    } else barrive(8, 384);
  }
  if (w == 8 && b < 72) {
    const u32 kg = lds32(SM_SLOT + 4 * g), ro = (2047 - ((kg >> 2) & 2047)) * 1152 + 16 * b;
    const char* src = gs + (G_PART + (b >> 3) * 2048 + (b & 7) * 256 + lane * 8);
    const char* xs = gs + (G_Y + ro);
    uint4 xt;
    POLL(xt = ldr128(xs), (xt.x ^ TAGR) & TAGM, 10);
    const u32 x1w = (q & 2) ? ((q & 1) ? xt.w : xt.z) : ((q & 1) ? xt.y : bmul(xt.x ^ TAGR, B2P64));
    const u32 gw = lds32(SM_MODS + 5760 + 16 * b + 4 * q);
    const u32 hw = lds32(SM_XS + g * ROW + b * 16 + q * 4);
    const float sgm = rcpf(1.f + ex2(-LOG2E * bhi(kg ^ (~((int)kg >> 31) | 0x80000000))));
    char* const dst = p.out + (ro + 4 * q);
    uint2 v[12];
#pragma unroll
    for (int j = 0; j < 12; j++) v[j] = make_uint2(1, 0);
    u32 bad;
    POLL({ bad = 0; _Pragma("unroll") for (int j = 0; j < 12; j++) { if (((v[j].x ^ par) | (v[j].y ^ par)) & 1) v[j] = ldr64(src + j * 9 * 2048); }
           _Pragma("unroll") for (int j = 0; j < 12; j++) bad |= (v[j].x ^ par) | (v[j].y ^ par); }, bad & 1, 11);
    float s0[4] = {}, s1[4] = {};
#pragma unroll
    for (int j = 0; j < 12; j++) { s0[j & 3] += uf(v[j].x); s1[j & 3] += uf(v[j].y); }
    const u32 y = movm(pk_bf((s0[0] + s0[1]) + (s0[2] + s0[3]), (s1[0] + s1[1]) + (s1[2] + s1[3])));
    *(u32*)dst = badd(x1w, bmul(gw, badd(hw, bmul(y, pk_bf(sgm, sgm)))));
    if (b == 0 && lane == 0) str32(gs + G_EP, ep + 1);
    TS(30); TSE();
  }
  if (w == 10) asm volatile("cp.async.bulk.wait_group.read 0;" ::: "memory");
}

__global__ void __launch_bounds__(384, 1)
fused_kernel(const Prm p, const __grid_constant__ CUtensorMap tm_mod, const __grid_constant__ CUtensorMap tm_gate, const __grid_constant__ CUtensorMap tm_gs,
             const __grid_constant__ CUtensorMap tm_up, const __grid_constant__ CUtensorMap tm_us, const __grid_constant__ CUtensorMap tm_down) {
  extern __shared__ __align__(1024) unsigned char smem[];
  if (threadIdx.x == 352) {
#pragma unroll
    for (int i = 0; i < 4; i++) mb_init(SM_MB + 8 * i);
    asm volatile("fence.mbarrier_init.release.cluster;" ::: "memory");
    tm_pre(&tm_mod); tm_pre(&tm_gate);
  }
  const u32 tid = __shfl_sync(~0u, threadIdx.x, threadIdx.x & 31), b = __shfl_sync(~0u, blockIdx.x, 0);
  const u32 w = tid >> 5, lane = tid & 31;
  const u32 g = lane >> 2, q = lane & 3, hi = g & 1;
  const u32 rho = b & 1, Ps = 512 + (b >> 1);
  char* const gs = p.gs;
  TS0();
  const bool kw = w != 8 && w != 11;
  const u32 ksig = w < 8 ? (w & 3) : 4, khf = w < 8 ? (w >> 2) : (w & 1);
  u32 la, ai, ldt; uint2 cr, ci;
  {
    const u32 d = w < 8 ? 4 * b + ksig : Ps, o = d * 256 + 8 * lane;
    const char* cp = p.c + (576 * (w & 1) + 24 * min(lane, 23u));
    la = ldg32(kw ? p.la + (o + 4 * khf) : cp); ai = ldg32(kw ? p.ai + (o + 4 * khf) : cp + 4);
    cr = ldg64(kw ? p.cr + o : cp + 8); ci = ldg64(kw ? p.ci + o : cp + 16); ldt = ldg16(p.ldt + 2 * d);
  }
  const u32 zr = tid >> 16;
  const u32 epv = ldr32(gs + (G_EP + zr));
  const u32 tp = SM_TAP + ksig * TAPS;
  if (kw && !khf) {
#pragma unroll 1
    for (u32 i = lane * 16; i < TAPS; i += 512) sts128(tp + i, 0, 0, 0, 0);
  }
  if (tid >= 380) str128(gs + (G_MOD + b * 128 + q * 16), INVAL, 0, 1, 0);
  if (w < 9) {
    const char* xp = p.x + (b * BLK + (lane >> 3) * 1152 + 128 * w + 16 * (lane & 7));
    const u32 xd = SM_XST + (((lane >> 3) & 1) + 8 * (lane >> 4)) * ROW + 128 * w + 16 * (lane & 7);
#pragma unroll
    for (int i = 0; i < 4; i++) cpa16(xd + 2 * ROW * i, xp + 4608 * i);
  }
  const u32 ktab = w < 8 ? SM_MODS + w * KTAB : SM_ZS + (w - 9) * KTAB;
  float k2048 = 0.f;
  u32 FK;
  if (kw) {
    u32 mx = __vmaxu2(__vmaxu2(cr.x & 0x7fff7fff, cr.y & 0x7fff7fff), __vmaxu2(ci.x & 0x7fff7fff, ci.y & 0x7fff7fff));
    const u32 E = max(__reduce_max_sync(~0u, max(mx & 0xffff, mx >> 16)) >> 7, 8u);
    TS(1);
    const float dt = rbf(ex2(blo(ldt) * LOG2E)), csc = uf((257 - E) << 23 | (fu(dt) & 0x7fffff));
    FK = fu(uf(fu(dt) & 0x7f800000) * uf((E - 2) << 23));
    const u32 crw = khf ? cr.y : cr.x, ciw = khf ? ci.y : ci.x;
    float2 C[2], w4[2], w8[2], w16[2], w32[2], w64[2], w128[2], w256[2], w512[2], a1[2], a2[2], a3[2], t0[2], t1[2], s3[2];
#pragma unroll
    for (int m = 0; m < 2; m++) {
      const float lr2 = rbf(ex2((m ? bhi(la) : blo(la)) * LOG2E)) * dt * -LOG2E, th = (m ? bhi(ai) : blo(ai)) * dt;
      C[m] = make_float2((m ? bhi(crw) : blo(crw)) * csc, (m ? bhi(ciw) : blo(ciw)) * csc);
      const float2 w1 = cexp(lr2, th), w2 = csq(w1);
      w64[m] = cexp(64.f * lr2, 64.f * th);
      w4[m] = csq(w2); w8[m] = csq(w4[m]); w16[m] = csq(w8[m]); w32[m] = csq(w16[m]);
      w128[m] = csq(w64[m]); w256[m] = csq(w128[m]); w512[m] = csq(w256[m]);
      const float2 w1024 = csq(w512[m]);
      a1[m] = cmul(C[m], w1); a2[m] = cmul(C[m], w2); a3[m] = cmul(a1[m], w2);
      t0[m] = cmul(C[m], w1024); t1[m] = cmul(t0[m], w128[m]); s3[m] = cmul(w8[m], w16[m]);
      k2048 += fmaf(t0[m].x, w1024.x, -t0[m].y * w1024.y);
    }
    C2 B0[8], B1[8], B2[8], S[8];
    B0[0] = pk2(C); B0[1] = pk2(a1); B0[2] = pk2(a2); B0[3] = pk2(a3);
    const C2 h4 = pk2(w4), h256 = pk2(w256), h512 = pk2(w512);
#pragma unroll
    for (int i = 0; i < 4; i++) B0[4 + i] = cm2(B0[i], h4);
#pragma unroll
    for (int i = 0; i < 4; i++) B1[i] = cm2(B0[2 * i], h256);
    B1[4] = cm2(B0[0], h512); B1[5] = cm2(B0[4], h512);
    B1[6] = cm2(B1[4], h256); B1[7] = cm2(B1[5], h256);
    const u32 ta = ktab + lane * 128, f = ((lane & 3) << 5) | ((lane & 4) << 2);
#pragma unroll
    for (int i = 0; i < 8; i++) sts128(ta + ((i << 4) ^ f), B0[i].re, B0[i].im, B1[i].re, B1[i].im);
    B2[0] = pk2(t0); B2[1] = pk2(t1);
    B2[2] = cm2(B2[0], h256); B2[3] = cm2(B2[1], h256);
#pragma unroll
    for (int i = 0; i < 4; i++) B2[4 + i] = cm2(B2[i], h512);
    S[0] = {0x3C003C00u, 0u}; S[1] = pk2c(w8); S[2] = pk2c(w16); S[3] = pk2c(s3); S[4] = pk2c(w32);
#pragma unroll
    for (int i = 1; i < 4; i++) S[4 + i] = cm2(S[i], S[4]);
#pragma unroll
    for (int i = 0; i < 8; i++) sts128(ta + 4096 + ((i << 4) ^ f), B2[i].re, B2[i].im, S[i].re, S[i].im);
    const C2 m64 = pk2c(w64), m128 = pk2c(w128);
    sts128(ktab + 8192 + lane * 16, m64.re, m64.im, m128.re, m128.im);
    __syncwarp();
  } else {
    u32 sa = SM_SIL + 576 * (w & 1) + 24 * min(lane, 23u);
#pragma unroll 1
    for (int j = 0; j < 6; j++) {
      sts32(sa, pk_bf(silu_f(blo(la)), silu_f(bhi(la))));
      la = ai; ai = cr.x; cr.x = cr.y; cr.y = ci.x; ci.x = ci.y; sa += 4;
    }
    if (tid == 352 && b < 36) { mb_expect(SM_MB, 36864); tma3d(SM_UP, &tm_mod, SM_MB, 32 * b, 0); }
    bsync(7, 64);
  }
  TS(2);
  const u32 ep = __reduce_or_sync(~0u, epv), par = (ep + 1) & 1, pm = par ? TAGM : 0;
  if (w < 9) {
    asm volatile("cp.async.wait_all;" ::: "memory");
    __syncwarp();
    TS(4);
    const u32 xa = SM_XST + (lane & 15) * ROW + 128 * w + 16 * (lane >> 4);
    float s[4] = {}, X[2][4] = {}, Y[2][4] = {};
#pragma unroll
    for (int j = 0; j < 4; j++) {
      const uint4 a = ldsm4(xa + 32 * j);
      mma8_bf(X[0], a.x, a.y, a.x); mma8_bf(Y[0], a.x, a.y, a.y);
      mma8_bf(X[1], a.z, a.w, a.z); mma8_bf(Y[1], a.z, a.w, a.w);
      mma_bf(s, a.x, a.y, a.z, a.w, BONE, BONE);
    }
    uint4 t[4];
#pragma unroll
    for (int j = 0; j < 4; j++) t[j] = ldsm4t(xa + 32 * j);
    const float u0 = hi ? X[0][1] + X[1][1] : X[0][0] + X[1][0], u1 = hi ? Y[0][3] + Y[1][3] : Y[0][2] + Y[1][2];
    if (q == g >> 1) sts128(SM_SP + w * 128 + g * 16, fu(s[0]), fu(u0), fu(s[2]), fu(u1));
    bsync(1, 320);
    TS(7);
    const u32 spr = SM_SP + (lane & 7) * 16 + (lane & 8);
    const uint2 t8 = lds64(spr + 1024);
    const float f8 = lane < 16 ? 1.f : 0.f;
    float S1 = uf(t8.x) * f8, S2 = uf(t8.y) * f8;
#pragma unroll
    for (int i = 0; i < 4; i++) { const uint2 u = lds64(spr + (lane & 16) * 32 + i * 128); S1 += uf(u.x); S2 += uf(u.y); }
    S1 += __shfl_xor_sync(~0u, S1, 16); S2 += __shfl_xor_sync(~0u, S2, 16);
    const float mu = S1 * (1.f / 576.f), var = fmaxf(fmaf(-mu, mu, S2 * (1.f / 576.f)), 0.f);
    const float m = rbf(mu), rs = rcpf(rbf(sqrta(rbf(rbf(var) + 1e-5f))));
    const float ra = rs * 0.0625f;
    sts64(SM_AF + w * 128 + (lane & 15) * 8, fu(ra), fu(-m * ra));
    __syncwarp();
    const uint4 f0 = lds128(SM_AF + w * 128 + q * 16), f1 = lds128(SM_AF + w * 128 + 64 + q * 16);
    char* const zdst = gs + (b * BLK + w * 2048 + lane * 8);
    const u32 pz = (q & 1) ? 0 : pm;
#pragma unroll
    for (int j = 0; j < 8; j++) {
      const u32 x0 = j & 1 ? t[j >> 1].z : t[j >> 1].x, x1 = j & 1 ? t[j >> 1].w : t[j >> 1].y;
      str64(zdst + 256 * j, pk_hf(fmaf(blo(x0), uf(f0.x), uf(f0.y)), fmaf(bhi(x0), uf(f0.z), uf(f0.w))) | pz,
            pk_hf(fmaf(blo(x1), uf(f1.x), uf(f1.y)), fmaf(bhi(x1), uf(f1.z), uf(f1.w))));
    }
    if (w == 8) {
      const float rh = rbf(rs);
      sts128(SM_ST + 16 * (lane & 15), pk_bf(-m, -m), pk_bf(rh, rh), pk_bf(rs - rh, rs - rh), 0);
    }
    TS(5);
  } else if (w == 11) {
    bsync(1, 320);
    if (lane == 0) {
      if (b >= 36 && b < 108) { mb_expect(SM_MB, 36864); tma3d(SM_UP, &tm_mod, SM_MB, 32 * b, 0); }
      mb_expect(SM_MB + 8, rho ? SLV : 46080);
      tma3d(SM_GATE, &tm_gate, SM_MB + 8, 32 * b, 0);
      if (!rho) tma3d(SM_GATE + SLV, &tm_gs, SM_MB + 8, 4096 + 4 * b, 0);
      tm_pre(&tm_up); tm_pre(&tm_down);
    }
  }
  if (kw) {
    float D[5][4] = {};
    u32 ta = ktab + q * 128 + ((g ^ (q << 1)) << 4), tm = ktab + 8192 + q * 16;
#pragma unroll 2
    for (int s = 0; s < 8; s++) {
      const uint4 ca = lds128(ta), cb = lds128(ta + 4096), ma = lds128(tm);
      ta = (ta + 512) ^ 16; tm += 64;
      k2048 += __shfl_xor_sync(~0u, k2048, 16 >> s);
      const C2 s0 = {cb.z, cb.w}, s1 = cm2(s0, {ma.x, ma.y}), s2 = cm2(s0, {ma.z, ma.w}), s3 = cm2(s1, {ma.z, ma.w});
      mma_hf(D[0], s0.re, s1.re, s0.im, s1.im, ca.x, ca.y);
      mma_hf(D[2], s0.re, s1.re, s0.im, s1.im, ca.z, ca.w);
      mma_hf(D[4], s0.re, s1.re, s0.im, s1.im, cb.x, cb.y);
      mma_hf(D[1], s2.re, s3.re, s2.im, s3.im, ca.x, ca.y);
      mma_hf(D[3], s2.re, s3.re, s2.im, s3.im, ca.z, ca.w);
    }
    TS(3);
    const u32 xa = (w < 8 ? SM_MODS + (4 + ksig) * KTAB : SM_ZS) + lane * 16;
    if (khf) {
      __syncwarp();
#pragma unroll
      for (int j = 0; j < 5; j++) sts128(xa + 512 * j, fu(D[j][0]), fu(D[j][1]), fu(D[j][2]), fu(D[j][3]));
      if (lane == 0) sts32(xa + 2560, fu(k2048));
      asm volatile("bar.arrive %0,64;" ::"r"(2 + ksig) : "memory");
    } else {
      const u32 t1 = tp + (q < 2 ? (128 + 4 * g + 2 * q) * 4 : T3 * 4 + ((32 * q - 64 + g) ^ 1) * 2);
      const u32 x = 16 * q + (g >> 1) + hi + 1, tb = tp + (hi ? T7E : T9E) * 4 - 4;
      const u32 te = tb + (x + 2 * (x & 1)) * 2, to = tb + TEO * 4 + (x ^ 1) * 2;
      asm volatile("bar.sync %0,64;" ::"r"(2 + ksig) : "memory");
#pragma unroll
      for (int j = 0; j < 5; j++) { const uint4 t = lds128(xa + 512 * j); D[j][0] += uf(t.x); D[j][1] += uf(t.y); D[j][2] += uf(t.z); D[j][3] += uf(t.w); }
      k2048 = (k2048 + uf(lds32(xa + 2560))) * 0.125f;
#pragma unroll
      for (int r = 0; r < 4; r++) {
        const u32 v = pk_hf(D[2 + (r >> 1)][2 * (r & 1)], D[2 + (r >> 1)][2 * (r & 1) + 1]);
        if (q < 2) {
          const u32 vv = __byte_perm(v, v, 0x1010);
          sts32(t1 + (TO + 32 * r) * 4, vv); sts16(t1 + (TO + 32 * r + 1) * 4 + 2, v >> 16); sts16(t1 + (TO + 32 * r - 1) * 4, v);
          sts64(t1 + (TE + 32 * r) * 4, vv, __byte_perm(v, v, 0x1032));
        } else {
          sts16(t1 + 16 * r, v >> 16);
          if (r == 0 && lane == 2) {
            const u32 vv = __byte_perm(v, v, 0x1010);
            sts32(tp + (TO + 256) * 4, vv); sts16(tp + (TO + 257) * 4 + 2, v); sts16(tp + (TO + 255) * 4, v); sts64(tp + (TE + 256) * 4, vv, vv);
          } else sts16(t1 + 16 * r - ((T3 - T5) * 4 + 6) + 8 * hi, v);
        }
      }
#pragma unroll
      for (int r = 0; r < 2; r++) {
        const u32 v = pk_hf(D[4][2 * r], D[4][2 * r + 1]);
        if (r == 0 && lane == 0) { sts16(tp + T5 * 4 + 62 * 2, v); sts32(SM_KV + 4 * ksig, v & 0xffff); sts16(tp + (T9E + TEO) * 4 + 62 * 2, pk_hf(k2048, 0.f)); sts32(SM_SC + 16 * ksig + 12, FK); }
        else { sts16(te + 8 * r, v); sts16(to + 8 * r, v); }
        sts16(te + 8 * r + 16, v >> 16); sts16(to + 8 * r + 16, v >> 16);
      }
      __syncwarp();
#pragma unroll
      for (int r = 0; r < 4; r++) {
        const u32 v = pk_hf(D[r >> 1][2 * (r & 1) + 1], D[r >> 1][2 * (r & 1)]), t2 = tp + lane * 4 + 128 * r;
        sts32(t2 + TO * 4, v); sts16(t2 + TE * 4, v >> 16); sts16(t2 + (TE + 1) * 4 + 2, v);
      }
      __syncwarp();
    }
  }
  TS(6);
  const u32 r0 = (lane & 7) + ((lane >> 3) & 1) + 8 * (lane >> 4) - 1;
  const u32 rl16 = (r0 ^ ((r0 >> 3) & 3)) * 16;
  const u32 pml = (g & 3) ? 0 : pm;
  if (w < 4) {
    asm volatile("setmaxnreg.inc.sync.aligned.u32 232;");
    const u32 tr = tp + ((hi ? TO : TE) + (g >> 1) - q) * 4;
    u32 T[33][4], B5[5][2], B3[5][2];
#pragma unroll
    for (int d = 0; d < 33; d++) {
      T[d][0] = lds32(tr + 32 * d); T[d][1] = lds32(tr + 32 * d + 16);
      T[d][2] = d ? cpy(T[d - 1][1], zr, 0) : zr; T[d][3] = cpy(T[d][0], zr, 1);
    }
    const u32 bt = tp + (T5 + g - q) * 4;
#pragma unroll
    for (int d = 0; d < 5; d++) {
      B5[d][0] = lds32(bt + 32 * d); B5[d][1] = lds32(bt + 32 * d - 16);
      B3[d][0] = lds32(bt + 32 * d + (T3 - T5) * 4); B3[d][1] = lds32(bt + 32 * d - 16 + (T3 - T5) * 4);
    }
    u32 za = SM_ZS + 16 + w * ZSS + ((lane >> 3) & 1) * ZPS + ((lane & 7) + (lane >> 4)) * 16;
    u32 wa = SM_W + W5O + w * WSL + rl16;
    u32 sa = SM_W + W9O + w * WSL + lane * 16;
    u32 yo = G_Y + 2 * q * BLK + (4 * b + w) * 32 + 4 * g;
    TS(8);
    lds32(za);
    bsync(9, 384);
    TS(11);
    float A[4][4] = {};
    uint4 Z[4];
    Z[0] = ldsm4(za); Z[1] = ldsm4(za + 32);
    const u32 F = __byte_perm(fu(uf(lds32(SM_SC + 16 * w + 8)) * uf(FK)), 0, 0x3232);
#define STEP(s, b0, b1) { _Pragma("unroll") for (int i = 0; i < 4; i++) mma_hf_o(A[i], A[i], T[8 * i + 7 - (s)], b0, b1); }
#define PAIR(n) { Z[(n + 2) & 3] = ldsm4(za + 32 * (n + 2)); STEP(2 * n, Z[n].x, Z[n].y); STEP(2 * n + 1, Z[n].z, Z[n].w); }
#define LAST(N) mma8_hf(N, T[32][1], zr, Z[3].y); float O[4]; mma_hf_o(O, A[0], T[0], Z[3].z, Z[3].w); \
    _Pragma("unroll") for (int i = 0; i < 3; i++) mma_hf_o(A[i], A[i + 1], T[8 * i + 8], Z[3].z, Z[3].w); \
    mma_hf_o(A[3], N, T[32], Z[3].z, Z[3].w);
#pragma unroll 1
    for (int j = 0; j < 4; j++) {
      PAIR(0); PAIR(1); PAIR(2);
      Z[1] = ldsm4(za + 160); STEP(6, Z[3].x, Z[3].y);
      float N[4] = {};
      LAST(N);
      y_store(O[0], O[1], O[2], O[3], F, pml, gs + yo);
      za += 128; yo += 8 * BLK;
      TS(40 + j);
    }
    bsync(10, 352);
#pragma unroll 1
    for (int j = 4; j < 13; j++) {
      const uint4 a5 = ldsm4t(wa), a3 = ldsm4t(wa + (W3O - W5O)), s3 = lds128(sa);
      PAIR(0);
      float N[4] = {uf(s3.x), uf(s3.y), uf(s3.z), uf(s3.w)};
#pragma unroll
      for (int i = 0; i < 4; i++) mma_hf(A[i], a5.x, a5.y, a5.z, a5.w, B5[i][0], B5[i][1]);
      mma_hf(N, a5.x, a5.y, a5.z, a5.w, B5[4][0], B5[4][1]);
      PAIR(1);
#pragma unroll
      for (int i = 0; i < 4; i++) mma_hf(A[i], a3.x, a3.y, a3.z, a3.w, B3[i][0], B3[i][1]);
      mma_hf(N, a3.x, a3.y, a3.z, a3.w, B3[4][0], B3[4][1]);
      PAIR(2);
      Z[1] = ldsm4(za + 160); STEP(6, Z[3].x, Z[3].y);
      LAST(N);
      y_store(O[0], O[1], O[2], O[3], F, pml, gs + yo);
      za += 128; wa = (wa + 256) ^ 32; sa += 512; yo += 8 * BLK;
      TS(40 + j);
    }
    {
      float X[3][4] = {};
#pragma unroll
      for (int ty = 0; ty < 2; ty++) {
        const uint4 a = ldsm4t(wa + ty * (W3O - W5O)), c = ldsm4t((wa ^ 32) + 256 + ty * (W3O - W5O)), d = ldsm4t(wa + 512 + ty * (W3O - W5O));
#pragma unroll
        for (int i = 0; i < 3; i++) mma_hf(A[i], a.x, a.y, a.z, a.w, ty ? B3[i][0] : B5[i][0], ty ? B3[i][1] : B5[i][1]);
#pragma unroll
        for (int i = 0; i < 2; i++) mma_hf(X[i], c.x, c.y, c.z, c.w, ty ? B3[i][0] : B5[i][0], ty ? B3[i][1] : B5[i][1]);
        mma_hf(X[2], d.x, d.y, d.z, d.w, ty ? B3[0][0] : B5[0][0], ty ? B3[0][1] : B5[0][1]);
      }
      barrive(12, 320);
#pragma unroll
      for (int n = 0; n < 4; n++) {
        const uint4 f0 = n < 2 ? Z[n] : ldsm4(za + 32 * n), f1 = ldsm4(za + 32 * n + 128), f2 = ldsm4(za + 32 * n + 256);
#pragma unroll
        for (int s = 2 * n; s < 2 * n + 2; s++) {
#pragma unroll
          for (int i = 0; i < 3; i++) mma_hf_o(A[i], A[i], T[8 * i + 7 - s], s & 1 ? f0.z : f0.x, s & 1 ? f0.w : f0.y);
          mma_hf_o(X[0], X[0], T[7 - s], s & 1 ? f1.z : f1.x, s & 1 ? f1.w : f1.y); mma_hf_o(X[1], X[1], T[15 - s], s & 1 ? f1.z : f1.x, s & 1 ? f1.w : f1.y);
          mma_hf_o(X[2], X[2], T[7 - s], s & 1 ? f2.z : f2.x, s & 1 ? f2.w : f2.y);
        }
      }
      y_store(A[0][0], A[0][1], A[0][2], A[0][3], F, pml, gs + yo);
      y_store(A[1][0] + X[0][0], A[1][1] + X[0][1], A[1][2] + X[0][2], A[1][3] + X[0][3], F, pml, gs + yo + 8 * BLK);
      y_store(A[2][0] + X[1][0] + X[2][0], A[2][1] + X[1][1] + X[2][1], A[2][2] + X[1][2] + X[2][2], A[2][3] + X[1][3] + X[2][3], F, pml, gs + yo + 16 * BLK);
    }
    TS(15);
    bsync(14, 224);
  } else {
    asm volatile("setmaxnreg.dec.sync.aligned.u32 136;");
    const u32 t8 = tid - 128;
#pragma unroll 1
    for (int ph = 0; ph < 2; ph++) {
      if (!kw && (ph ? b >= 36 && b < 108 : b < 36)) {
        float c[2][4] = {};
        u32 aa = SM_UP + ((lane & 7) + 8 * (lane >> 4)) * 64 + (((2 * (w & 1) + ((lane >> 3) & 1)) ^ ((lane & 7) >> 1)) << 4);
        u32 ba = SM_SIL + (lane >> 3) * 16;
        mb_wait(SM_MB);
#pragma unroll 1
        for (int s = 0; s < 6; s++) {
#pragma unroll
          for (int i = 0; i < 3; i++) {
            const uint4 a0 = ldsm4t(aa + i * 2048), a1 = ldsm4t(aa + i * 2048 + 1024), bb = ldsm4(ba + i * 64);
            mma_bf(c[0], a0.x, a0.y, a0.z, a0.w, bb.x, bb.y); mma_bf(c[1], a1.x, a1.y, a1.z, a1.w, bb.z, bb.w);
          }
          aa += 6144; ba += 192;
        }
        const float v = (q & 1) ? c[0][2] + c[1][2] : c[0][0] + c[1][0];
        if (q < 2) str16(gs + (G_MOD + b * 128 + 32 * (w & 1) + 2 * g + 16 * q), pk_bf(rbf(v) * F2M64, 0.f) | (g < 2 ? pm : 0));
      }
      if (ph) break;
      TS(12);
      const char* zs = gs + ((t8 >> 3) * BLK + b * 128 + (t8 & 7) * 16);
      const char* zs4 = gs + ((t8 >> 1) * BLK + Ps * 32 + (t8 & 1) * 16);
      uint4 v[5];
#pragma unroll
      for (int j = 0; j < 5; j++) v[j].x = INVAL;
      POLL(_Pragma("unroll") for (int j = 0; j < 5; j++) if ((v[j].x ^ pm) & TAGM) v[j] = ldr128(j < 4 ? zs + j * 32 * BLK : zs4),
           ((v[0].x ^ pm) | (v[1].x ^ pm) | (v[2].x ^ pm) | (v[3].x ^ pm) | (v[4].x ^ pm)) & TAGM, 1);
      TS(9);
      if (w == 11) {
        const u32 d = lane < 4 ? 4 * b + lane : Ps;
        const char* mp = gs + (G_MOD + (d >> 5) * 128 + (d & 24) * 2);
        uint4 ta, tc;
        POLL({ ta = ldr128(mp); tc = ldr128(mp + MODJ); }, ((ta.x ^ pm) | (tc.x ^ pm)) & TAGM, 2);
        const u32 aw = (d & 4) ? ((d & 2) ? ta.w : ta.z) : ((d & 2) ? ta.y : ta.x & ~TAGM);
        const u32 cw = (d & 4) ? ((d & 2) ? tc.w : tc.z) : ((d & 2) ? tc.y : tc.x & ~TAGM);
        const float sa = ((d & 1) ? bhi(aw) : blo(aw)) * F2P64, c1 = rbf(fmaf((d & 1) ? bhi(cw) : blo(cw), F2P64, 1.f));
        const u32 EM = min(max(fu(fmaxf(32.f * fabsf(c1), fabsf(sa))) >> 23, 80u), 250u);
        const float inv = uf((264 - EM) << 23);
        if (lane < 5) { sts64(SM_SC + 16 * lane, pk_hf(16.f * c1 * inv, 16.f * c1 * inv), pk_hf(sa * inv, sa * inv)); sts32(SM_SC + 16 * lane + 8, (EM - 74) << 23); }
        TS(10);
      }
      const u32 dst = SM_ZS + 128 + (t8 & 7) * ZPS + (t8 >> 3) * 16;
      bsync(8, 256);
      const uint2 cc = lds64(SM_SC + 8 * (t8 & 6)), c4 = lds64(SM_SC + 64);
#pragma unroll
      for (int j = 0; j < 5; j++) {
        const uint2 c = j < 4 ? cc : c4;
        sts128(j < 4 ? dst + j * 512 : SM_Z4 + 256 + (t8 & 1) * ZP4 + (t8 >> 1) * 16, hfma(v[j].x & ~TAGM, c.x, c.y), hfma(v[j].y, c.x, c.y), hfma(v[j].z, c.x, c.y), hfma(v[j].w, c.x, c.y));
      }
      if (t8 < 96) sts128(t8 < 64 ? dst - 128 : SM_Z4 + (t8 & 1) * ZP4 + (t8 & 30) * 8, 0, 0, 0, 0);
      bsync(9, 384);
      TS(11);
      const bool lng = w < 8 || w == 9;
      const u32 ts = lane + 32 * (w == 8 ? 0 : w - 9);
      const u32 sig = lng ? ksig : ts >> 4, l2 = lng ? lane : 32 + (ts & 15);
      if (!lng) {
#pragma unroll
        for (int i = 0; i < 3; i++) if (i < 2 || ts < 64) str128(gs + (G_Y + (96 + 12 * i + (ts >> 3)) * BLK + b * 128 + (ts & 7) * 16), INVAL, 0, 1, 0);
        str128(gs + (G_PART + b * 2048 + ts * 16), INVAL, 0, 1, 0);
        str128(gs + (ts < 32 ? G_PART + b * 2048 + 1536 + ts * 16 : ts < 64 ? G_ACT + b * 512 + (ts & 31) * 16 : G_Y + (96 + 16 * rho + ((ts & 31) >> 1)) * BLK + Ps * 32 + (ts & 1) * 16), INVAL, 0, 1, 0);
        if (ts < (rho ? 4 : 12)) str128(gs + (ts < 4 ? G_KEY + b * 128 + ts * 16 : G_ACT + Ps * 128 + (ts - 4) * 16), INVAL, 0, 1, 0);
      }
      const u32 wb = SM_W + sig * WSL;
      if (sig < 5) {
        const u32 za = (sig < 4 ? SM_ZS + 128 + sig * ZSS : SM_Z4 + 256) + l2 * 32, zb = za + (sig < 4 ? ZPS : ZP4);
        const uint4 c0 = lds128(zb - 32), c1 = lds128(za - 16), c2 = lds128(zb - 16), c3 = lds128(za), c4 = lds128(zb), c5 = lds128(za + 16), c6 = lds128(zb + 16);
        const u32 P[25] = {c0.z, c0.w, c1.x, c1.y, c1.z, c1.w, c2.x, c2.y, c2.z, c2.w, c3.x, c3.y, c3.z, c3.w, c4.x, c4.y, c4.z, c4.w, c5.x, c5.y, c5.z, c5.w, c6.x, c6.y, c6.z};
        u32 Q[25], D1[24], F4[23], W5[21], W3[17];
#pragma unroll
        for (int j = 1; j < 25; j++) Q[j] = __byte_perm(P[j - 1], P[j], 0x5432);
#pragma unroll
        for (int j = 1; j < 24; j++) D1[j] = hadd(P[j], Q[j]);
#pragma unroll
        for (int j = 2; j < 23; j++) F4[j] = hadd(D1[j], D1[j - 1]);
#pragma unroll
        for (int n = 0; n < 21; n++) W5[n] = hadd(F4[n + 2], P[n]);
#pragma unroll
        for (int n = 0; n < 17; n++) W3[n] = hadd(Q[n + 8], D1[n + 7]);
        const u32 a0 = wb + W5O + 64 * l2 + 16 * ((l2 >> 1) & 3);
#pragma unroll
        for (int i = 0; i < 4; i++) {
          sts128(a0 ^ (16 * i), W5[4 * i + 5], W5[4 * i + 6], W5[4 * i + 7], W5[4 * i + 8]);
          sts128((a0 ^ (16 * i)) + (W3O - W5O), W3[4 * i + 1], W3[4 * i + 2], W3[4 * i + 3], W3[4 * i + 4]);
        }
        if (lng) {
          if (lane < 16) sts128(wb + (lane & 7) * 16 + (lane & 8) * 400, 0, 0, 0, 0);
          const u32 a1 = wb + 32 * lane + 16 * ((lane >> 2) & 1);
#pragma unroll
          for (int i = 0; i < 4; i++) {
            const u32 a = (a1 ^ (16 * (i >> 1))) + 1024 * (i & 1), n = 4 * i;
            sts128(a + V2O, hadd(Q[n + 9], P[n + 8]), hadd(Q[n + 10], P[n + 9]), hadd(Q[n + 11], P[n + 10]), hadd(Q[n + 12], P[n + 11]));
            sts128(a + W9O, hadd(F4[n + 4], W5[n]), hadd(F4[n + 5], W5[n + 1]), hadd(F4[n + 6], W5[n + 2]), hadd(F4[n + 7], W5[n + 3]));
            sts128(a + W7O, hadd(F4[n + 6], W3[n]), hadd(F4[n + 7], W3[n + 1]), hadd(F4[n + 8], W3[n + 2]), hadd(F4[n + 9], W3[n + 3]));
          }
        }
      }
      __syncwarp();
      TS(32);
      if (lng) {
        const u32 wa = wb + ((lane >> 3) & 1) * 1024 + (((lane & 7) ^ (lane >> 4)) + 8 * (lane >> 4)) * 16;
        const u32 kv = lds32(SM_KV + 4 * sig), bi = (g >> 1) == q ? (hi ? kv << 16 : kv) : 0u;
        float acc[8][4] = {};
#pragma unroll
        for (int j = 0; j < 4; j++) { const uint4 a = ldsm4t(wa + V2O + j * 256); mma8_hf(acc[2 * j], a.x, a.y, bi); mma8_hf(acc[2 * j + 1], a.z, a.w, bi); }
        u32 bt = tp + (T9E + hi * TEO + (g >> 1) - q) * 4, wt = wa + W9O;
#pragma unroll 1
        for (int ty = 0; ty < 2; ty++) {
          uint4 a[4];
#pragma unroll
          for (int be = 0; be < 4; be++) a[be] = ldsm4t(wt + be * 256);
          u32 b1 = lds32(bt - 16);
#pragma unroll
          for (int d = 0; d < 8; d++) {
            const u32 b0 = lds32(bt + 16 * d);
#pragma unroll
            for (int be = 0; be < 4; be++) if (d + 2 * be < 8) mma_hf(acc[d + 2 * be], a[be].x, a[be].y, a[be].z, a[be].w, b0, b1);
            b1 = b0;
          }
          bt += (T7E - T9E) * 4; wt += W7O - W9O;
        }
        __syncwarp();
#pragma unroll
        for (int j = 0; j < 8; j++) sts128(wb + W9O + j * 512 + lane * 16, fu(acc[j][0]), fu(acc[j][1]), fu(acc[j][2]), fu(acc[j][3]));
        TS(34);
      }
      if (w != 9) barrive(10, 352);
      if (w >= 8) barrive(11, 256);
    }
    if (w < 8) {
      const int u0 = 4 * (w - 4) + 2 * rho;
      const u32 t4 = SM_TAP + 4 * TAPS;
      u32 tr = t4 + ((hi ? TO : TE) + (g >> 1) - q) * 4;
      u32 zb = SM_Z4 + 256 + ((lane >> 3) & 1) * ZP4 + u0 * 128 + (lane & 7) * 16 + (lane >> 4) * 128;
      float acc[4][4] = {};
      u32 prev = 0;
#pragma unroll 1
      for (int it = min(u0 + 2, 4); it; it--) {
#pragma unroll
        for (int s = 0; s < 8; s++) {
          const uint4 z = ldsm4(zb - 16 * s);
          const u32 t0 = lds32(tr + 32 * s), t1 = lds32(tr + 32 * s + 16);
          mma_hf(acc[s & 1], t0, t1, prev, t0, z.x, z.y);
          mma_hf(acc[2 + (s & 1)], t0, t1, prev, t0, z.z, z.w);
          prev = t1;
        }
        zb -= 128; tr += 256;
      }
      {
        const uint4 z = ldsm4(zb); const u32 t0 = lds32(tr), t1 = lds32(tr + 16);
        mma_hf(acc[0], t0, t1, prev, t0, z.x, z.y); mma_hf(acc[2], t0, t1, prev, t0, z.z, z.w);
        if (w > 4) { const uint4 y = ldsm4(zb - 16); mma8_hf(acc[1], t1, zr, y.y); mma8_hf(acc[3], t1, zr, y.w); }
      }
      bsync(11, 256);
      u32 wa = (SM_W + 4 * WSL + W5O + rl16 + (u0 - 3) * 256) ^ 32, bt = t4 + (T5 + g - q) * 4;
#pragma unroll 1
      for (int al = min(u0 - 2, 6); al > 0; al--) {
#pragma unroll
        for (int ty = 0; ty < 2; ty++) {
          const uint4 a = ldsm4t(wa + ty * (W3O - W5O));
          const u32 bb = bt + ty * (T3 - T5) * 4;
          mma_hf(acc[ty], a.x, a.y, a.z, a.w, lds32(bb - 32), lds32(bb - 48));
          mma_hf(acc[2 + ty], a.x, a.y, a.z, a.w, lds32(bb), lds32(bb - 16));
        }
        wa = (wa - 256) ^ 32; bt += 32;
      }
      TS(35);
      const uint2 fc = lds64(SM_SC + 16 * 4 + 8);
      const u32 F = __byte_perm(fu(uf(fc.x) * uf(fc.y)), 0, 0x3232);
      char* yp = gs + (G_Y + (8 * u0 + 2 * q) * BLK + Ps * 32 + 4 * g);
#pragma unroll
      for (int j = 0; j < 2; j++) {
        uint4 s3 = {0, 0, 0, 0};
        if (u0 >= 8) s3 = lds128(SM_W + 4 * WSL + W9O + (u0 - 8 + j) * 512 + lane * 16);
        y_store(acc[2 * j][0] + acc[2 * j + 1][0] + uf(s3.x), acc[2 * j][1] + acc[2 * j + 1][1] + uf(s3.y), acc[2 * j][2] + acc[2 * j + 1][2] + uf(s3.z),
                acc[2 * j][3] + acc[2 * j + 1][3] + uf(s3.w), F, pml, yp + j * 8 * BLK);
      }
      TS(16);
    } else {
      if (!kw) bsync(7, 64);
      if (tid == 352) {
        PROXY_FENCE();
        mb_expect(SM_MB + 16, rho ? SLV : 46080);
        tma3d(SM_UP, &tm_up, SM_MB + 16, 32 * b, 0);
        if (!rho) tma3d(SM_UP + SLV, &tm_us, SM_MB + 16, 4096 + 4 * b, 0);
      }
      TS(17);
      if (w > 8) {
        const u32 t = tid - 288, c = min(t, 71u);
        const char* mp = gs + (G_MOD + (c >> 2) * 128 + (c & 3) * 16);
        const uint4 dk = ldg128(p.dsk + 16 * c), wr = ldg128(p.wr + 16 * c);
        uint4 md[6];
        POLL(_Pragma("unroll") for (int j = 0; j < 6; j++) md[j] = ldr128(mp + j * MODJ),
             ((md[0].x ^ pm) | (md[1].x ^ pm) | (md[2].x ^ pm) | (md[3].x ^ pm) | (md[4].x ^ pm) | (md[5].x ^ pm)) & TAGM, 4);
        const u32 ma = SM_MODS + 16 * c;
#pragma unroll
        for (int j = 0; j < 6; j++) {
          const u32 o = (j % 3 == 1) ? BONE : 0x80008000u;
          md[j] = make_uint4(bfma(md[j].x & ~TAGM, B2P64, o), bfma(md[j].y, B2P64, o), bfma(md[j].z, B2P64, o), bfma(md[j].w, B2P64, o));
          sts128(ma + 1152 * j, md[j].x, md[j].y, md[j].z, md[j].w);
        }
        sts128(ma + 1152 * 6, dk.x, dk.y, dk.z, dk.w);
        const uint4 H = make_uint4(bmul(md[4].x, wr.x), bmul(md[4].y, wr.y), bmul(md[4].z, wr.z), bmul(md[4].w, wr.w));
        sts128(ma + 1152 * 7, H.x, H.y, H.z, H.w);
        sts128(ma + 1152 * 8, bfma(md[4].x, wr.x, H.x ^ 0x80008000u), bfma(md[4].y, wr.y, H.y ^ 0x80008000u), bfma(md[4].z, wr.z, H.z ^ 0x80008000u), bfma(md[4].w, wr.w, H.w ^ 0x80008000u));
        float c4[4] = {};
        mma_bf(c4, md[4].x, md[3].x, md[4].y, md[3].y, wr.x, wr.y); mma_bf(c4, md[4].z, md[3].z, md[4].w, md[3].w, wr.z, wr.w);
        if (q == g >> 1) sts64(SM_RC + (t >> 2) * 8, fu(hi ? c4[1] : c4[0]), fu(hi ? c4[3] : c4[2]));
        if (t < 5) sts128(t < 2 ? SM_ONE + 16 * t : SM_THR + 16 * t - 32, t ? 0 : BONE, t ? 0 : BONE, t ? 0 : BONE, t ? 0 : BONE);
        TS(14);
        barrive(13, 256);
        if (w != 10) barrive(14, 224);
        if (w == 9) {
          bsync(12, 320);
          if (lane == 0 && b < 108) {
            PROXY_FENCE();
            mb_expect(SM_MB + 24, 49152);
            tma3d(SM_WD, &tm_down, SM_MB + 24, 64 * (b % 9), 2 * (b / 9));
          }
        }
      }
    }
    if (w < 9) bsync(13, 256);
  }
  post_conv(p, tid + p.zero, b, ep);
  if (tid == 352 && s2u(smem) != SM0) __trap();
}

typedef CUresult (*EncFn)(CUtensorMap*, CUtensorMapDataType, cuuint32_t, void*, const cuuint64_t*, const cuuint64_t*, const cuuint32_t*, const cuuint32_t*,
                          CUtensorMapInterleave, CUtensorMapSwizzle, CUtensorMapL2promotion, CUtensorMapFloatOOBfill);
static void make_map(EncFn enc, CUtensorMap* tm, void* ptr, int cols, int rows, int bw, int nb, CUtensorMapSwizzle sw) {
  cuuint64_t gd[3] = {(cuuint64_t)cols, 192, (cuuint64_t)(rows / 192)}, gs[2] = {(cuuint64_t)cols * 2, (cuuint64_t)cols * 2 * 192};
  cuuint32_t bd[3] = {(cuuint32_t)bw, 192, (cuuint32_t)nb}, es[3] = {1, 1, 1};
  enc(tm, CU_TENSOR_MAP_DATA_TYPE_BFLOAT16, 3, ptr, gd, gs, bd, es, CU_TENSOR_MAP_INTERLEAVE_NONE, sw, CU_TENSOR_MAP_L2_PROMOTION_NONE, CU_TENSOR_MAP_FLOAT_OOB_FILL_NONE);
}
extern "C" void kernel_launch(void* const* d_in, const int* in_sizes, int n_in, void* d_out, int out_size) {
  static EncFn enc = nullptr;
  static void* scratch = nullptr;
  if (!enc) {
    cudaGetSymbolAddress(&scratch, g_s);
    cudaDriverEntryPointQueryResult qr;
    cudaGetDriverEntryPoint("cuTensorMapEncodeTiled", (void**)&enc, cudaEnableDefault, &qr);
    cudaFuncSetAttribute(fused_kernel, cudaFuncAttributeMaxDynamicSharedMemorySize, SM_TOTAL);
  }
  CUtensorMap tm_mod, tm_gate, tm_gs, tm_up, tm_us, tm_down;
  make_map(enc, &tm_mod, d_in[13], 3456, 576, 32, 3, CU_TENSOR_MAP_SWIZZLE_64B);
  make_map(enc, &tm_gate, d_in[9], 4608, 576, 32, 3, CU_TENSOR_MAP_SWIZZLE_64B);
  make_map(enc, &tm_gs, d_in[9], 4608, 576, 8, 3, CU_TENSOR_MAP_SWIZZLE_NONE);
  make_map(enc, &tm_up, d_in[10], 4608, 576, 32, 3, CU_TENSOR_MAP_SWIZZLE_64B);
  make_map(enc, &tm_us, d_in[10], 4608, 576, 8, 3, CU_TENSOR_MAP_SWIZZLE_NONE);
  make_map(enc, &tm_down, d_in[11], 576, 4608, 64, 2, CU_TENSOR_MAP_SWIZZLE_128B);
  Prm p;
  p.x = (const char*)d_in[0]; p.la = (const char*)d_in[1]; p.ai = (const char*)d_in[2]; p.cr = (const char*)d_in[3];
  p.ci = (const char*)d_in[4]; p.ldt = (const char*)d_in[5]; p.dsk = (const char*)d_in[6]; p.wr = (const char*)d_in[8];
  p.c = (const char*)d_in[12]; p.out = (char*)d_out; p.zero = 0; p.gs = (char*)scratch;
  fused_kernel<<<128, 384, SM_TOTAL>>>(p, tm_mod, tm_gate, tm_gs, tm_up, tm_us, tm_down);
}
```

```cpp
#include <cuda_runtime.h>
#include <cuda.h>
#include <cuda_bf16.h>
#include <cuda_fp16.h>
#include <stdint.h>
#define FUSED 1
#define DEV __device__ __forceinline__
typedef uint32_t u32;

constexpr u32 BLK = 18432, G_Z = 0, G_Y = 128 * BLK, G_MOD = 2 * G_Y, G_KEY = G_MOD + 128 * 128, G_ACT = G_KEY + 128 * 128;
constexpr u32 G_PART = G_ACT + 576 * 128, G_EP = G_PART + 128 * 2048, G_END = G_EP + 128;
__device__ __align__(128) unsigned char g_s[G_END];
#define TS(i)
#define TS0()
#define TSE()
#define TSD()
#define TSX 0
#define ERRF(code)

constexpr int SM0 = 1024;
constexpr int ROW = 1168, SLV = 36864;
constexpr int SM_GATE = SM0, SM_UP = SM_GATE + 46080, SM_XST = SM_UP + 46080, SM_MODS = SM_XST + 16 * ROW, SM_W = SM_MODS + 11008;
constexpr int KTAB = 9216, WSL = 12544, W5O = 128, W3O = 3328, V2O = 6400, W9O = 8448, W7O = 10496;
constexpr int ZPS = 2192, ZSS = 2 * ZPS, ZP4 = 2368;
constexpr int SM_ZS = SM_W + 5 * WSL, SM_Z4 = SM_ZS + 4 * ZSS, SM_TAP = SM_Z4 + 2 * ZP4, TAPS = 3328;
constexpr int SM_MB = SM_TAP + 5 * TAPS;
constexpr int SM_SC = SM_MB + 32;
constexpr int SM_KV = SM_SC + 80;
constexpr int SM_THR = SM_KV + 32;
constexpr int SM_SLOT = SM_THR + 48;
constexpr int SM_KEY = SM_SLOT + 32;
constexpr int SM_ST = SM_KEY + 64;
constexpr int SM_ST2 = SM_ST + 256;
constexpr int SM_RC = SM_ST2 + 256;
constexpr int SM_SP = SM_RC + 192;
constexpr int SM_AF = SM_SP + 1152, SM_SIL = SM_AF + 1152, SM_END = SM_SP + 5760;
constexpr int SM_ONE = SM_MODS + 9 * 1152;
constexpr int SM_WD = SM_W, SM_XS = SM_W + 49152, SM_AC = SM_ZS, SM_RED = SM_AC + 6144, SM_LIST = SM_TAP;
constexpr int SM_TSB = SM_END, SM_TOTAL = SM_END + TSX - SM0;
static_assert(SM_W % 1024 == 0 && SM_MODS + 8 * KTAB <= SM_ZS && SM_ZS + 2 * KTAB <= SM_TAP && SM_RED + 10240 <= SM_TAP && SM_XS + 8 * ROW <= SM_ZS, "smem map");
static_assert(SM_MB % 16 == 0 && SM_THR % 16 == 0 && SM_ST % 16 == 0 && SM_SP % 16 == 0 && SM_TOTAL <= 232448, "smem map");
constexpr int TE = 4, TO = 276, T5 = 560, T3 = 624, T9E = 680, T7E = 760, TEO = 40;
#define DX 0
#define DMOD 1200
#define PFG 1
constexpr int SPIN = 1 << 16, NEARLY = 4;
constexpr u32 TAGM = 0x40004000u, TAGR = 0x40000000u, INVAL = 0x00004801u;

DEV u32 s2u(const void* p) { return (u32)__cvta_generic_to_shared(p); }
DEV void mma_bf(float (&c)[4], u32 a0, u32 a1, u32 a2, u32 a3, u32 b0, u32 b1) {
  asm("mma.sync.aligned.m16n8k16.row.col.f32.bf16.bf16.f32 {%0,%1,%2,%3},{%4,%5,%6,%7},{%8,%9},{%0,%1,%2,%3};"
      : "+f"(c[0]), "+f"(c[1]), "+f"(c[2]), "+f"(c[3]) : "r"(a0), "r"(a1), "r"(a2), "r"(a3), "r"(b0), "r"(b1));
}
DEV void mma_hf(float (&c)[4], u32 a0, u32 a1, u32 a2, u32 a3, u32 b0, u32 b1) {
  asm("mma.sync.aligned.m16n8k16.row.col.f32.f16.f16.f32 {%0,%1,%2,%3},{%4,%5,%6,%7},{%8,%9},{%0,%1,%2,%3};"
      : "+f"(c[0]), "+f"(c[1]), "+f"(c[2]), "+f"(c[3]) : "r"(a0), "r"(a1), "r"(a2), "r"(a3), "r"(b0), "r"(b1));
}
DEV void mma8_bf(float (&c)[4], u32 a0, u32 a1, u32 b0) {
  asm("mma.sync.aligned.m16n8k8.row.col.f32.bf16.bf16.f32 {%0,%1,%2,%3},{%4,%5},{%6},{%0,%1,%2,%3};"
      : "+f"(c[0]), "+f"(c[1]), "+f"(c[2]), "+f"(c[3]) : "r"(a0), "r"(a1), "r"(b0));
}
DEV void mma8_hf(float (&c)[4], u32 a0, u32 a1, u32 b0) {
  asm("mma.sync.aligned.m16n8k8.row.col.f32.f16.f16.f32 {%0,%1,%2,%3},{%4,%5},{%6},{%0,%1,%2,%3};"
      : "+f"(c[0]), "+f"(c[1]), "+f"(c[2]), "+f"(c[3]) : "r"(a0), "r"(a1), "r"(b0));
}
DEV u32 movm(u32 x) { u32 r; asm("movmatrix.sync.aligned.m8n8.trans.b16 %0,%1;" : "=r"(r) : "r"(x)); return r; }
DEV uint4 ldsm4(u32 a) { uint4 r; asm volatile("ldmatrix.sync.aligned.m8n8.x4.shared.b16 {%0,%1,%2,%3},[%4];" : "=r"(r.x), "=r"(r.y), "=r"(r.z), "=r"(r.w) : "r"(a)); return r; }
DEV uint4 ldsm4t(u32 a) { uint4 r; asm volatile("ldmatrix.sync.aligned.m8n8.x4.trans.shared.b16 {%0,%1,%2,%3},[%4];" : "=r"(r.x), "=r"(r.y), "=r"(r.z), "=r"(r.w) : "r"(a)); return r; }
DEV u32 lds32(u32 a) { u32 r; asm volatile("ld.volatile.shared.u32 %0,[%1];" : "=r"(r) : "r"(a)); return r; }
DEV uint2 lds64(u32 a) { uint2 r; asm volatile("ld.shared.v2.u32 {%0,%1},[%2];" : "=r"(r.x), "=r"(r.y) : "r"(a)); return r; }
DEV uint4 lds128(u32 a) { uint4 r; asm volatile("ld.shared.v4.u32 {%0,%1,%2,%3},[%4];" : "=r"(r.x), "=r"(r.y), "=r"(r.z), "=r"(r.w) : "r"(a)); return r; }
DEV void sts16(u32 a, u32 v) { asm volatile("st.shared.u16 [%0],%1;" ::"r"(a), "h"((unsigned short)v) : "memory"); }
DEV void sts32(u32 a, u32 v) { asm volatile("st.shared.u32 [%0],%1;" ::"r"(a), "r"(v) : "memory"); }
DEV void sts64(u32 a, u32 x, u32 y) { asm volatile("st.shared.v2.u32 [%0],{%1,%2};" ::"r"(a), "r"(x), "r"(y) : "memory"); }
DEV void sts128(u32 a, u32 x, u32 y, u32 z, u32 w) { asm volatile("st.shared.v4.u32 [%0],{%1,%2,%3,%4};" ::"r"(a), "r"(x), "r"(y), "r"(z), "r"(w) : "memory"); }
DEV uint4 ldr128(const void* p) { uint4 v; asm volatile("ld.relaxed.gpu.global.v4.u32 {%0,%1,%2,%3},[%4];" : "=r"(v.x), "=r"(v.y), "=r"(v.z), "=r"(v.w) : "l"(p) : "memory"); return v; }
DEV uint2 ldr64(const void* p) { uint2 v; asm volatile("ld.relaxed.gpu.global.v2.u32 {%0,%1},[%2];" : "=r"(v.x), "=r"(v.y) : "l"(p) : "memory"); return v; }
DEV u32 ldr32(const void* p) { u32 v; asm volatile("ld.relaxed.gpu.global.u32 %0,[%1];" : "=r"(v) : "l"(p) : "memory"); return v; }
DEV void str128(void* p, u32 x, u32 y, u32 z, u32 w) { asm volatile("st.relaxed.gpu.global.v4.u32 [%0],{%1,%2,%3,%4};" ::"l"(p), "r"(x), "r"(y), "r"(z), "r"(w) : "memory"); }
DEV void str64(void* p, u32 x, u32 y) { asm volatile("st.relaxed.gpu.global.v2.u32 [%0],{%1,%2};" ::"l"(p), "r"(x), "r"(y) : "memory"); }
DEV void str32(void* p, u32 x) { asm volatile("st.relaxed.gpu.global.u32 [%0],%1;" ::"l"(p), "r"(x) : "memory"); }
DEV void str16(void* p, u32 x) { asm volatile("st.relaxed.gpu.global.u16 [%0],%1;" ::"l"(p), "h"((unsigned short)x) : "memory"); }
DEV uint4 ldg128(const void* p) { uint4 v; asm volatile("ld.global.nc.v4.u32 {%0,%1,%2,%3},[%4];" : "=r"(v.x), "=r"(v.y), "=r"(v.z), "=r"(v.w) : "l"(p)); return v; }
DEV uint2 ldg64(const void* p) { uint2 v; asm volatile("ld.global.nc.v2.u32 {%0,%1},[%2];" : "=r"(v.x), "=r"(v.y) : "l"(p)); return v; }
DEV u32 ldg32(const void* p) { u32 v; asm volatile("ld.global.nc.u32 %0,[%1];" : "=r"(v) : "l"(p)); return v; }
DEV u32 ldg16(const void* p) { unsigned short v; asm volatile("ld.global.nc.u16 %0,[%1];" : "=h"(v) : "l"(p)); return v; }
#define bsync(id, n) asm volatile("bar.sync %0,%1;" ::"n"(id), "n"(n) : "memory")
#define barrive(id, n) asm volatile("bar.arrive %0,%1;" ::"n"(id), "n"(n) : "memory")
DEV void mb_init(u32 a) { asm volatile("mbarrier.init.shared.b64 [%0],1;" ::"r"(a) : "memory"); }
DEV void mb_expect(u32 a, u32 bytes) { asm volatile("mbarrier.arrive.expect_tx.shared.b64 _,[%0],%1;" ::"r"(a), "r"(bytes) : "memory"); }
DEV void mb_wait(u32 a, u32 ph = 0) {
  u32 ok; int it = 0;
  do { asm volatile("{.reg .pred p; mbarrier.try_wait.parity.shared.b64 p,[%1],%2; selp.u32 %0,1,0,p;}" : "=r"(ok) : "r"(a), "r"(ph) : "memory"); } while (!ok && ++it < SPIN);
}
template <int N> DEV void bulk_out(void* dst, u32 src) { asm volatile("cp.async.bulk.global.shared::cta.bulk_group [%0],[%1],%2;" ::"l"(dst), "r"(src), "n"(N) : "memory"); }
constexpr u32 WSH = 41472;
template <int N> DEV void l2_pre(const void* p) { asm volatile("cp.async.bulk.prefetch.L2.global [%0],%1;" ::"l"(p), "n"(N) : "memory"); }
DEV void tma3d(u32 dst, const CUtensorMap* tm, u32 mb, int c0, int c2) {
  asm volatile("cp.async.bulk.tensor.3d.shared::cluster.global.mbarrier::complete_tx::bytes [%0],[%1,{%3,0,%4}],[%2];"
               ::"r"(dst), "l"((uint64_t)tm), "r"(mb), "r"(c0), "r"(c2) : "memory");
}
DEV float blo(u32 w) { return __uint_as_float(w << 16); }
DEV float bhi(u32 w) { return __uint_as_float(w & 0xffff0000u); }
DEV u32 pk_bf(float lo, float hi) { u32 r; asm("cvt.rn.bf16x2.f32 %0,%1,%2;" : "=r"(r) : "f"(hi), "f"(lo)); return r; }
DEV u32 pk_hf(float lo, float hi) { u32 r; asm("cvt.rn.f16x2.f32 %0,%1,%2;" : "=r"(r) : "f"(hi), "f"(lo)); return r; }
DEV float rbf(float x) { return __uint_as_float(pk_bf(0.f, x) & 0xffff0000u); }
DEV u32 bfma(u32 a, u32 b, u32 c) { u32 r; asm("fma.rn.bf16x2 %0,%1,%2,%3;" : "=r"(r) : "r"(a), "r"(b), "r"(c)); return r; }
DEV u32 bmul(u32 a, u32 b) { u32 r; asm("mul.rn.bf16x2 %0,%1,%2;" : "=r"(r) : "r"(a), "r"(b)); return r; }
DEV u32 badd(u32 a, u32 b) { u32 r; asm("add.rn.bf16x2 %0,%1,%2;" : "=r"(r) : "r"(a), "r"(b)); return r; }
DEV u32 hadd(u32 a, u32 b) { u32 r; asm("add.rn.f16x2 %0,%1,%2;" : "=r"(r) : "r"(a), "r"(b)); return r; }
DEV u32 hfma(u32 a, u32 b, u32 c) { u32 r; asm("fma.rn.f16x2 %0,%1,%2,%3;" : "=r"(r) : "r"(a), "r"(b), "r"(c)); return r; }
struct C2 { u32 re, im; };
DEV C2 cm2(C2 a, C2 b) {
  const __half2 ar = *reinterpret_cast<__half2*>(&a.re), ai = *reinterpret_cast<__half2*>(&a.im), br = *reinterpret_cast<__half2*>(&b.re), bi = *reinterpret_cast<__half2*>(&b.im);
  __half2 re = __hfma2(ar, br, __hneg2(__hmul2(ai, bi))), im = __hfma2(ar, bi, __hmul2(ai, br));
  return {*reinterpret_cast<u32*>(&re), *reinterpret_cast<u32*>(&im)};
}
DEV C2 pk2(const float2 (&a)[2]) { return {pk_hf(a[0].x, a[1].x), pk_hf(a[0].y, a[1].y)}; }
DEV C2 pk2c(const float2 (&a)[2]) { return {pk_hf(a[0].x, a[1].x), pk_hf(-a[0].y, -a[1].y)}; }
DEV u32 cpy(u32 x, u32 zr, int alt) {
  u32 r;
  if (alt) asm volatile("xor.b32 %0,%1,%2;" : "=r"(r) : "r"(x), "r"(zr)); else asm volatile("mad.lo.u32 %0,%2,%2,%1;" : "=r"(r) : "r"(x), "r"(zr));
  return r;
}
DEV u32 clk() { u32 r; asm volatile("mov.u32 %0,%%clock;" : "=r"(r)::"memory"); return r; }
DEV float ex2(float x) { float r; asm("ex2.approx.ftz.f32 %0,%1;" : "=f"(r) : "f"(x)); return r; }
DEV float rcpf(float x) { float r; asm("rcp.approx.ftz.f32 %0,%1;" : "=f"(r) : "f"(x)); return r; }
DEV float2 cmul(float2 a, float2 b) { return make_float2(fmaf(a.x, b.x, -a.y * b.y), fmaf(a.x, b.y, a.y * b.x)); }
DEV float2 csq(float2 a) { return make_float2(fmaf(a.x, a.x, -a.y * a.y), (a.x + a.x) * a.y); }
DEV float2 cexp(float lr2, float th) {
  const float m = ex2(lr2);
  return make_float2(m * __cosf(th), m * __sinf(th));
}
DEV float silu_f(float v) { return v * rcpf(1.f + ex2(-1.4426950408889634f * v)); }
constexpr u32 B2P64 = 0x5F805F80u, B2M64 = 0x1F801F80u, BONE = 0x3F803F80u;
constexpr u32 MODJ = 18 * 128;
DEV float sqrta(float x) { float r; asm("sqrt.approx.ftz.f32 %0,%1;" : "=f"(r) : "f"(x)); return r; }
DEV u32 fu(float x) { return __float_as_uint(x); }
DEV float uf(u32 x) { return __uint_as_float(x); }
DEV void mma_hf_o(float (&d)[4], const float (&c)[4], const u32 (&a)[4], u32 b0, u32 b1) {
  asm("mma.sync.aligned.m16n8k16.row.col.f32.f16.f16.f32 {%0,%1,%2,%3},{%4,%5,%6,%7},{%8,%9},{%10,%11,%12,%13};"
      : "=f"(d[0]), "=f"(d[1]), "=f"(d[2]), "=f"(d[3]) : "r"(a[0]), "r"(a[1]), "r"(a[2]), "r"(a[3]), "r"(b0), "r"(b1), "f"(c[0]), "f"(c[1]), "f"(c[2]), "f"(c[3]));
}

DEV void cpa16(u32 dst, const void* src) { asm volatile("cp.async.cg.shared.global [%0],[%1],16;" ::"r"(dst), "l"(src) : "memory"); }
DEV void tm_pre(const CUtensorMap* tm) { asm volatile("prefetch.tensormap [%0];" ::"l"((uint64_t)tm) : "memory"); }
#define PROXY_FENCE() asm volatile("fence.proxy.async.shared::cta;" ::: "memory")
struct Prm {
  const char *x, *la, *ai, *cr, *ci, *ldt, *c;
  char* gs;
  const char *dsk, *wr, *wg, *wu, *wd;
  char* out;
  u32 zero;
};
constexpr float LOG2E = 1.4426950408889634f, F2P64 = 1.8446744073709552e19f, F2M64 = 5.421010862427522e-20f;

DEV void y_store(float c0, float c1, float c2, float c3, u32 F, u32 pml, char* yp) {
  str32(yp, bmul(pk_bf(c0, c2), F) | pml);
  str32(yp + BLK, bmul(pk_bf(c1, c3), F) | pml);
}
#define POLL(load, cond_bad, code) { int it_ = 0; do { load; if (++it_ > SPIN) { ERRF(code); break; } } while (__any_sync(~0u, (cond_bad))); }
#define POLLW(load, cond_bad, code) { int it_ = 0; while (__any_sync(~0u, (cond_bad))) { if (++it_ > SPIN) { ERRF(code); break; } load; } }

DEV void post_conv(const Prm& p, const CUtensorMap* tm_down, const u32 tid, const u32 b, const u32 ep) {
  const u32 w = tid >> 5, lane = tid & 31;
  const u32 g = lane >> 2, q = lane & 3, e = g >> 2, h = (g >> 1) & 1, hi = g & 1;
  const u32 rho = b & 1, par = (ep + 1) & 1, pm = par ? TAGM : 0;
  char* const gs = p.gs;
  const u32 cho = 128 * w + 64 * e + 16 * q;
  u32 x1[4][4], h2[4][4], key[4], lt;
  char* const rowp = gs + (b * BLK + (4 * h + 8 * hi) * 1152 + cho);
  if (w < 9) {
    const char* ysrc = gs + (G_Y + b * BLK + w * 2048 + (q >> 1) * 1024 + (g >> 1) * 256 + hi * 32 + (q & 1) * 16);
    uint4 yv[4];
    if (w < 4) {
#pragma unroll
      for (int v = 0; v < 4; v++) yv[v] = ldr128(ysrc + 64 * v);
    } else {
#pragma unroll
      for (int v = 0; v < 4; v++) yv[v].x = INVAL;
    }
    const u32 ma = SM_MODS + cho, xa = SM_XST + (2 * h + 4 * hi) * ROW + cho;
    const uint4 sa = lds128(ma), ca = lds128(ma + 1152), ga = lds128(ma + 2304), dk = lds128(ma + 6912);
    const uint4 rb = lds128((g & 2) ? SM_ONE + 16 * hi : (ma ^ 64) + 8064 + 1152 * hi);
    const u32 saw[4] = {sa.x, sa.y, sa.z, sa.w}, caw[4] = {ca.x, ca.y, ca.z, ca.w}, gaw[4] = {ga.x, ga.y, ga.z, ga.w}, dw[4] = {dk.x, dk.y, dk.z, dk.w};
    u32 hD[4][4];
#pragma unroll
    for (int k = 0; k < 4; k++) {
      const uint4 st = lds128(SM_ST + 16 * (2 * h + 4 * hi + (k & 1) + 8 * (k >> 1))), xv = lds128(xa + ((k & 1) + 8 * (k >> 1)) * ROW);
      x1[k][0] = xv.x; x1[k][1] = xv.y; x1[k][2] = xv.z; x1[k][3] = xv.w;
#pragma unroll
      for (int v = 0; v < 4; v++) {
        const u32 d = badd(x1[k][v], st.x), z = bfma(d, st.y, bmul(d, st.z));
        hD[k][v] = bmul(badd(bmul(z, caw[v]), saw[v]), dw[v]);
      }
    }
    const bool own = (q >> 1) == e;
    const u32 spw = SM_SP + (2 * w + e) * 320 + (g & 3) * 16 + (own ? ((q & 1) == h ? 4 : 12) : 8 - 8 * (q & 1));
    TS(18);
    if (w >= 4) bsync(12, 288);
    POLLW(_Pragma("unroll") for (int v = 0; v < 4; v++) if ((yv[v].x ^ pm) & TAGM) yv[v] = ldr128(ysrc + 64 * v),
          ((yv[0].x ^ pm) | (yv[1].x ^ pm) | (yv[2].x ^ pm) | (yv[3].x ^ pm)) & TAGM, 5);
    TS(19);
#pragma unroll
    for (int k = 0; k < 4; k += 2) {
      float X[4] = {}, Y[4] = {}, R[4] = {};
#pragma unroll
      for (int v = 0; v < 4; v++) {
        const u32 y0 = k ? yv[v].z : yv[v].x & ~TAGM, y1 = k ? yv[v].w : yv[v].y;
        x1[k][v] = badd(x1[k][v], bmul(gaw[v], bfma(movm(y0), B2P64, hD[k][v])));
        x1[k + 1][v] = badd(x1[k + 1][v], bmul(gaw[v], bfma(movm(y1), B2P64, hD[k + 1][v])));
        mma8_bf(X, x1[k][v], x1[k + 1][v], x1[k][v]); mma8_bf(Y, x1[k][v], x1[k + 1][v], x1[k + 1][v]);
        if (v & 1) mma_bf(R, x1[k][v - 1], x1[k + 1][v - 1], x1[k][v], x1[k + 1][v], v & 2 ? rb.z : rb.x, v & 2 ? rb.w : rb.y);
      }
      sts32(spw + k * 64, fu(own ? (hi ? X[1] : X[0]) : R[0] + R[1]));
      sts32(spw + k * 64 + 64, fu(own ? (hi ? Y[3] : Y[2]) : R[2] + R[3]));
    }
    barrive(1, 320);
    TS(36);
    const uint4 sb = lds128(ma + 3456), cb = lds128(ma + 4608), gb = lds128(ma + 5760);
    const u32 sbw[4] = {sb.x, sb.y, sb.z, sb.w}, cbw[4] = {cb.x, cb.y, cb.z, cb.w}, gbw[4] = {gb.x, gb.y, gb.z, gb.w};
    bsync(2, 320);
    TS(37);
    lt = lds32(SM_THR + 36);
#pragma unroll
    for (int k = 0; k < 4; k++) {
      const uint4 st = lds128(SM_ST2 + 64 * k + 16 * (g & 3));
      key[k] = st.w;
      u32 o[4];
#pragma unroll
      for (int v = 0; v < 4; v++) {
        const u32 d = badd(x1[k][v], st.x), z = bfma(d, st.y, bmul(d, st.z));
        h2[k][v] = badd(bmul(z, cbw[v]), sbw[v]);
        o[v] = badd(x1[k][v], bmul(gbw[v], h2[k][v]));
      }
      h2[k][0] = bmul(h2[k][0], B2M64) | TAGR;
      if (key[k] >= lt) str128(rowp + k * 1152, h2[k][0], h2[k][1], h2[k][2], h2[k][3]);
      sts128(xa + ((k & 1) + 8 * (k >> 1)) * ROW, o[0], o[1], o[2], o[3]);
    }
    barrive(3, 320);
    TS(21);
  } else if (w == 10) {
    bsync(14, 224);
    uint2 rc = lds64(SM_RC + 8 * min(lane, 17u));
    float r1 = lane < 18 ? uf(rc.x) : 0.f, r2 = lane < 18 ? uf(rc.y) : 0.f;
#pragma unroll 1
    for (int o = 16; o; o >>= 1) { r1 += __shfl_xor_sync(~0u, r1, o); r2 += __shfl_xor_sync(~0u, r2, o); }
    const u32 tl = 4 * ((lane >> 1) & 1) + ((lane >> 2) & 3) + 8 * (lane & 1), kl = (2047 - 16 * b - tl) << 2 | par * 3;
    const u32 row = SM_XST + ((lane & 2) + 4 * (lane & 1) + ((lane >> 2) & 1) + (lane & 8)) * ROW;
    char* const op = p.out + (b * BLK + tl * 1152);
    const u32 spr = SM_SP + (lane >> 4) * 9 * 320 + (lane & 15) * 16;
    TS(31);
    bsync(1, 320);
    barrive(7, 64);
    float S1 = 0.f, S2 = 0.f, S3 = 0.f;
#pragma unroll
    for (int i = 0; i < 9; i++) { uint4 t = lds128(spr + i * 320); S1 += uf(t.x); S2 += uf(t.y); S3 += uf(t.z); }
    S1 += __shfl_xor_sync(~0u, S1, 16); S2 += __shfl_xor_sync(~0u, S2, 16); S3 += __shfl_xor_sync(~0u, S3, 16);
    const float mu = S1 * (1.f / 576.f), var = fmaxf(fmaf(-mu, mu, S2 * (1.f / 576.f)), 0.f);
    const float m = rbf(mu), rs = rcpf(rbf(sqrta(rbf(rbf(var) + 1e-5f))));
    const u32 rb = pk_bf(0.f, fmaf(fmaf(-m, r1, S3), rs, r2) + 0.f);
    const u32 ok = ((rb ^ (((int)rb >> 31) | 0x80000000)) & 0xffff0000u) | kl;
    if (lane < 16) str32(gs + (G_KEY + b * 128 + 4 * lane), ok);
    TS(20);
    const float rh = rbf(rs);
    sts128(SM_ST2 + 16 * (lane & 15), pk_bf(-m, -m), pk_bf(rh, rh), pk_bf(rs - rh, rs - rh), ok);
    sts32(SM_KEY + 4 * (lane & 15), ok);
    __syncwarp();
    const uint4 o0 = lds128(SM_KEY + 2 * (lane & 16)), o1 = lds128(SM_KEY + 2 * (lane & 16) + 16);
    u32 lr = (o0.x > ok) + (o0.y > ok) + (o0.z > ok) + (o0.w > ok) + (o1.x > ok) + (o1.y > ok) + (o1.z > ok) + (o1.w > ok);
    lr += __shfl_xor_sync(~0u, lr, 16);
    if (lr == NEARLY - 1) sts32(SM_THR + 36, ok);
    barrive(2, 320);
    bsync(3, 320);
    PROXY_FENCE();
    if (lane < 16 && lr >= 8) bulk_out<1152>(op, row);
    bsync(6, 320);
    if (lane < 16 && lr < 8 && ok < lds32(SM_SLOT + 28)) bulk_out<1152>(op, row);
    asm volatile("cp.async.bulk.commit_group;" ::: "memory");
  }
  uint4 rv[3];
  const char* rs_;
  if (w < 8) {
    const char* ks = gs + (G_KEY + (8 * g + w) * 128 + q * 16);
    const u32 kt = par * 3;
    uint4 ka, kc;
    POLL({ ka = ldr128(ks); kc = ldr128(ks + 8192); }, ((ka.x ^ kt) | (kc.x ^ kt)) & 3, 6);
    TS(23);
    const u32 kk[8] = {ka.x, ka.y, ka.z, ka.w, kc.x, kc.y, kc.z, kc.w};
    u32 mx = max(max(max(kk[0], kk[1]), max(kk[2], kk[3])), max(max(kk[4], kk[5]), max(kk[6], kk[7])));
#pragma unroll
    for (int o = 4; o < 32; o *= 2) mx = max(mx, __shfl_xor_sync(~0u, mx, o));
    if (lane < 4) asm volatile("red.shared.max.u32 [%0],%1;" ::"r"(SM_THR + 16 * (w & 1) + 4 * lane), "r"(mx) : "memory");
    bsync(4, 256);
    TS(33);
    const uint4 t0 = lds128(SM_THR), t1 = lds128(SM_THR + 16);
    u32 L0 = min(min(min(t0.x, t0.y), min(t0.z, t0.w)), min(min(t1.x, t1.y), min(t1.z, t1.w)));
#pragma unroll 1
    for (int it = 0; it < 128; it++) {
      u32 c = 0;
#pragma unroll
      for (int j = 0; j < 8; j++) c += kk[j] >= L0 ? 4 : 0;
      if (c) {
        u32 a;
        asm volatile("atom.shared.add.u32 %0,[%1],%2;" : "=r"(a) : "r"(SM_THR + 32), "r"(c) : "memory");
#pragma unroll
        for (int j = 0; j < 8; j++) if (kk[j] >= L0) { sts32(SM_LIST + a, kk[j]); a += 4; }
      }
      bsync(5, 256);
      TS(38);
      const u32 n = lds32(SM_THR + 32), m0 = lds32(SM_LIST + 4 * lane), my = 4 * lane < n ? m0 : 0;
      const uint4 cd = lds128(SM_LIST + 16 * w);
      const u32 cc[4] = {cd.x, cd.y, cd.z, cd.w};
#pragma unroll
      for (int j = 0; j < 4; j++) {
        const u32 r = __popc(__ballot_sync(~0u, my > cc[j]));
        if (r < 8 && 16 * w + 4 * j < n) sts32(SM_SLOT + 4 * r, cc[j]);
      }
      if (n <= 128) break;
      bsync(15, 256);
      L0 = lds32(SM_SLOT + 28);
      sts32(SM_THR + 32, 0);
      bsync(15, 256);
    }
  }
  if (w < 9) {
    bsync(6, 320);
    TS(24);
    const u32 g8 = lds32(SM_SLOT + 28);
    if (w < 8) {
      rs_ = gs + ((2047 - ((lds32(SM_SLOT + 4 * w) >> 2) & 2047)) * 1152 + lane * 16);
      rv[0] = ldr128(rs_); rv[1] = ldr128(rs_ + 512);
      rv[2].x = TAGR;
      if (lane < 8) rv[2] = ldr128(rs_ + 1024);
    }
    if (__any_sync(~0u, max(max(key[0], key[1]), max(key[2], key[3])) >= g8)) {
#pragma unroll
      for (int k = 0; k < 4; k++) if (key[k] >= g8) {
        if (key[k] < lt) str128(rowp + k * 1152, h2[k][0], h2[k][1], h2[k][2], h2[k][3]);
        str128(rowp + (G_Y + k * 1152), bmul(x1[k][0], B2M64) | TAGR, x1[k][1], x1[k][2], x1[k][3]);
      }
    }
  }
  const u32 kq = w & 3, tg = 2 - (w >> 2);
  uint4 A[24];
  {
    const u32 row = 144 * kq + 8 * (lane >> 4) + (lane & 7), ab = (lane & 8) ? SM_UP : SM_GATE;
    mb_wait(SM_MB + 8); mb_wait(SM_MB + 16);
    if (tg < 2) {
      const u32 aa = ab + row * 64 + (((2 * tg) ^ ((lane & 7) >> 1)) << 4);
#pragma unroll
      for (int s = 0; s < 9; s++) { A[s] = ldsm4t(aa + s * 1024); A[9 + s] = ldsm4t((aa ^ 16) + s * 1024); }
    } else {
#pragma unroll
      for (int s = 0; s < 9; s++) A[s] = ldsm4t(ab + SLV + row * 16 + s * 256);
    }
  }
  TS(22);
  if (w == 9) {
    bsync(7, 64);
    if (lane == 0 && b < 108) {
      PROXY_FENCE();
#pragma unroll 1
      for (int i = 0; i < 4; i++) {
        if (i) mb_wait(SM_MB + 24, ~i & 1);
        mb_expect(SM_MB + 24, 12288);
        tma3d(SM_WD + 12288 * i, tm_down, SM_MB + 24, 64 * (b % 9), 4 * (b / 9) + i);
      }
    }
    __syncwarp();
    TS(13);
  }
  if (w < 8) {
    POLLW({ rv[0] = ldr128(rs_); rv[1] = ldr128(rs_ + 512); if (lane < 8) rv[2] = ldr128(rs_ + 1024); },
          ((rv[0].x ^ TAGR) | (rv[1].x ^ TAGR) | (rv[2].x ^ TAGR)) & TAGM, 8);
#pragma unroll
    for (int j = 0; j < 3; j++) if (j < 2 || lane < 8) sts128(SM_XS + w * ROW + lane * 16 + j * 512, bmul(rv[j].x ^ TAGR, B2P64), rv[j].y, rv[j].z, rv[j].w);
  }
  __syncthreads();
  TS(25);
  {
    float c0[2][4] = {}, c1[2][4] = {};
    const u32 ba = SM_XS + (lane & 7) * ROW + (18 * kq + (lane >> 3)) * 16;
    uint4 bb[5];
#pragma unroll
    for (int s = 0; s < 5; s++) bb[s] = ldsm4(ba + s * 64);
#pragma unroll
    for (int s = 0; s < 9; s++) mma_bf(c0[s & 1], A[s].x, A[s].y, A[s].z, A[s].w, s & 1 ? bb[s >> 1].z : bb[s >> 1].x, s & 1 ? bb[s >> 1].w : bb[s >> 1].y);
    const u32 ra = SM_RED + (8 * tg + kq) * 512 + lane * 16;
    if (tg < 2) {
#pragma unroll
      for (int s = 0; s < 9; s++) mma_bf(c1[s & 1], A[9 + s].x, A[9 + s].y, A[9 + s].z, A[9 + s].w, s & 1 ? bb[s >> 1].z : bb[s >> 1].x, s & 1 ? bb[s >> 1].w : bb[s >> 1].y);
      sts128(ra + 2048, fu(c1[0][0] + c1[1][0]), fu(c1[0][1] + c1[1][1]), fu(c1[0][2] + c1[1][2]), fu(c1[0][3] + c1[1][3]));
    }
    sts128(ra, fu(c0[0][0] + c0[1][0]), fu(c0[0][1] + c0[1][1]), fu(c0[0][2] + c0[1][2]), fu(c0[0][3] + c0[1][3]));
  }
  TS(39);
  __syncthreads();
  if (w >= 7 + rho) {
    const u32 t = 11 - w;
    float s[4] = {};
#pragma unroll
    for (int i = 0; i < 4; i++) { const uint4 u = lds128(SM_RED + (t * 4 + i) * 512 + lane * 16); s[0] += uf(u.x); s[1] += uf(u.y); s[2] += uf(u.z); s[3] += uf(u.w); }
    const u32 sg = pk_bf(silu_f(rbf(s[0])), silu_f(rbf(s[1])));
    const u32 act = movm(bmul(bmul(sg, pk_bf(s[2], s[3])), B2M64));
    str32(gs + (G_ACT + (t < 4 ? 4 * b + t : 512 + (b >> 1)) * 128 + lane * 4), act | (q ? 0 : pm));
  }
  TS(26);
  if (b < 108) {
    const char* src = gs + (G_ACT + (b / 9) * 6144 + tid * 16);
    uint4 a = ldr128(src);
    if (w < 4) {
      const u32 aa = SM_WD + (8 * (lane >> 4) + (lane & 7)) * 128 + (((2 * w + ((lane >> 3) & 1)) ^ (lane & 7)) << 4);
      mb_wait(SM_MB + 24, 1);
#pragma unroll
      for (int s = 0; s < 24; s++) A[s] = ldsm4t(aa + s * 2048);
    }
    TS(28);
    POLLW(a = ldr128(src), (a.x ^ pm) & TAGM, 9);
    sts128(SM_AC + tid * 16, a.x & ~TAGM, a.y, a.z, a.w);
    TS(27);
    if (w < 4) {
      bsync(8, 384);
      float c[4][4] = {};
#pragma unroll
      for (int s = 0; s < 12; s++) {
        const uint4 bb = ldsm4(SM_AC + lane * 16 + s * 512);
        mma_bf(c[2 * (s & 1)], A[2 * s].x, A[2 * s].y, A[2 * s].z, A[2 * s].w, bb.x, bb.y);
        mma_bf(c[2 * (s & 1) + 1], A[2 * s + 1].x, A[2 * s + 1].y, A[2 * s + 1].z, A[2 * s + 1].w, bb.z, bb.w);
      }
      char* dst = gs + (G_PART + b * 2048 + w * 512 + lane * 8);
      u32 o[4];
#pragma unroll
      for (int i = 0; i < 4; i++) o[i] = (fu(((c[0][i] + c[1][i]) + (c[2][i] + c[3][i])) * F2P64) & ~1u) | par;
      str64(dst, o[0], o[1]); str64(dst + 256, o[2], o[3]);
      TS(29);
    } else barrive(8, 384);
  }
  if (w == 8 && b < 72) {
    const u32 kg = lds32(SM_SLOT + 4 * g), ro = (2047 - ((kg >> 2) & 2047)) * 1152 + 16 * b;
    const char* src = gs + (G_PART + (b >> 3) * 2048 + (b & 7) * 256 + lane * 8);
    const char* xs = gs + (G_Y + ro);
    uint4 xt;
    POLL(xt = ldr128(xs), (xt.x ^ TAGR) & TAGM, 10);
    const u32 x1w = (q & 2) ? ((q & 1) ? xt.w : xt.z) : ((q & 1) ? xt.y : bmul(xt.x ^ TAGR, B2P64));
    const u32 gw = lds32(SM_MODS + 5760 + 16 * b + 4 * q);
    const u32 hw = lds32(SM_XS + g * ROW + b * 16 + q * 4);
    const float sgm = rcpf(1.f + ex2(-LOG2E * bhi(kg ^ (~((int)kg >> 31) | 0x80000000))));
    char* const dst = p.out + (ro + 4 * q);
    uint2 v[12];
#pragma unroll
    for (int j = 0; j < 12; j++) v[j] = make_uint2(1, 0);
    u32 bad;
    POLL({ bad = 0; _Pragma("unroll") for (int j = 0; j < 12; j++) { if (((v[j].x ^ par) | (v[j].y ^ par)) & 1) v[j] = ldr64(src + j * 9 * 2048); }
           _Pragma("unroll") for (int j = 0; j < 12; j++) bad |= (v[j].x ^ par) | (v[j].y ^ par); }, bad & 1, 11);
    float s0[4] = {}, s1[4] = {};
#pragma unroll
    for (int j = 0; j < 12; j++) { s0[j & 3] += uf(v[j].x); s1[j & 3] += uf(v[j].y); }
    const u32 y = movm(pk_bf((s0[0] + s0[1]) + (s0[2] + s0[3]), (s1[0] + s1[1]) + (s1[2] + s1[3])));
    *(u32*)dst = badd(x1w, bmul(gw, badd(hw, bmul(y, pk_bf(sgm, sgm)))));
    if (b == 0 && lane == 0) str32(gs + G_EP, ep + 1);
    TS(30); TSE();
  }
  if (w == 10) asm volatile("cp.async.bulk.wait_group.read 0;" ::: "memory");
}

__global__ void __launch_bounds__(384, 1)
fused_kernel(const Prm p, const __grid_constant__ CUtensorMap tm_mod, const __grid_constant__ CUtensorMap tm_gate, const __grid_constant__ CUtensorMap tm_gs,
             const __grid_constant__ CUtensorMap tm_up, const __grid_constant__ CUtensorMap tm_us, const __grid_constant__ CUtensorMap tm_down) {
  extern __shared__ __align__(1024) unsigned char smem[];
  if (threadIdx.x == 352) {
#pragma unroll
    for (int i = 0; i < 4; i++) mb_init(SM_MB + 8 * i);
    asm volatile("fence.mbarrier_init.release.cluster;" ::: "memory");
    tm_pre(&tm_mod);
  }
  const u32 tid = __shfl_sync(~0u, threadIdx.x, threadIdx.x & 31), b = blockIdx.x + p.zero;
  const u32 w = tid >> 5, lane = tid & 31;
  const u32 g = lane >> 2, q = lane & 3, hi = g & 1;
  const u32 rho = b & 1, Ps = 512 + (b >> 1);
  char* const gs = p.gs;
  TS0();
  const bool kw = w != 8 && w != 11;
  const u32 ksig = w < 8 ? (w & 3) : 4, khf = w < 8 ? (w >> 2) : (w & 1);
  u32 la, ai, ldt; uint2 cr, ci;
  {
    const u32 d = w < 8 ? 4 * b + ksig : Ps, o = d * 256 + 8 * lane;
    const char* cp = p.c + (576 * (w & 1) + 24 * min(lane, 23u));
    la = ldg32(kw ? p.la + (o + 4 * khf) : cp); ai = ldg32(kw ? p.ai + (o + 4 * khf) : cp + 4);
    cr = ldg64(kw ? p.cr + o : cp + 8); ci = ldg64(kw ? p.ci + o : cp + 16); ldt = ldg16(p.ldt + 2 * d);
  }
  const u32 zr = tid >> 16, t0 = clk();
  const u32 epv = ldr32(gs + (G_EP + zr));
  const u32 tp = SM_TAP + ksig * TAPS;
  if (kw && !khf) {
#pragma unroll 1
    for (u32 i = lane * 16; i < TAPS; i += 512) sts128(tp + i, 0, 0, 0, 0);
  }
  if (tid >= 252) str128(gs + (tid >= 380 ? G_MOD + b * 128 + q * 16 : b * BLK + 16384 - 252 * 16 + tid * 16), INVAL, 0, 1, 0);
  if (tid == 352 && b < 36) { while (clk() - t0 < DMOD); mb_expect(SM_MB, 36864); tma3d(SM_UP, &tm_mod, SM_MB, 32 * b, 0); }
  if (w < 9) {
    while ((int)(clk() - t0) < DX);
    const char* xp = p.x + (b * BLK + (lane >> 3) * 1152 + 128 * w + 16 * (lane & 7));
    const u32 xd = SM_XST + (((lane >> 3) & 1) + 8 * (lane >> 4)) * ROW + 128 * w + 16 * (lane & 7);
#pragma unroll
    for (int i = 0; i < 4; i++) cpa16(xd + 2 * ROW * i, xp + 4608 * i);
  }
  const u32 ktab = w < 8 ? SM_MODS + w * KTAB : SM_ZS + (w - 9) * KTAB;
  float k2048 = 0.f;
  if (kw) {
    u32 mx = __vmaxu2(__vmaxu2(cr.x & 0x7fff7fff, cr.y & 0x7fff7fff), __vmaxu2(ci.x & 0x7fff7fff, ci.y & 0x7fff7fff));
    const u32 E = max(__reduce_max_sync(~0u, max(mx & 0xffff, mx >> 16)) >> 7, 8u);
    TS(1);
    const float dt = rbf(ex2(blo(ldt) * LOG2E)), csc = uf((257 - E) << 23 | (fu(dt) & 0x7fffff));
    sts32(SM_SC + 16 * ksig + 12, fu(uf(fu(dt) & 0x7f800000) * uf((E - 2) << 23)));
    const u32 crw = khf ? cr.y : cr.x, ciw = khf ? ci.y : ci.x;
    float2 C[2], w4[2], w8[2], w16[2], w32[2], w64[2], w128[2], w256[2], w512[2], a1[2], a2[2], a3[2], t0[2], t1[2], s3[2];
#pragma unroll
    for (int m = 0; m < 2; m++) {
      const float lr2 = rbf(ex2((m ? bhi(la) : blo(la)) * LOG2E)) * dt * -LOG2E, th = (m ? bhi(ai) : blo(ai)) * dt;
      C[m] = make_float2((m ? bhi(crw) : blo(crw)) * csc, (m ? bhi(ciw) : blo(ciw)) * csc);
      const float2 w1 = cexp(lr2, th), w2 = csq(w1);
      w64[m] = cexp(64.f * lr2, 64.f * th);
      w4[m] = csq(w2); w8[m] = csq(w4[m]); w16[m] = csq(w8[m]); w32[m] = csq(w16[m]);
      w128[m] = csq(w64[m]); w256[m] = csq(w128[m]); w512[m] = csq(w256[m]);
      const float2 w1024 = csq(w512[m]);
      a1[m] = cmul(C[m], w1); a2[m] = cmul(C[m], w2); a3[m] = cmul(a1[m], w2);
      t0[m] = cmul(C[m], w1024); t1[m] = cmul(t0[m], w128[m]); s3[m] = cmul(w8[m], w16[m]);
      k2048 += fmaf(t0[m].x, w1024.x, -t0[m].y * w1024.y);
    }
    C2 B0[8], B1[8], B2[8], S[8];
    B0[0] = pk2(C); B0[1] = pk2(a1); B0[2] = pk2(a2); B0[3] = pk2(a3);
    const C2 h4 = pk2(w4), h256 = pk2(w256), h512 = pk2(w512);
#pragma unroll
    for (int i = 0; i < 4; i++) B0[4 + i] = cm2(B0[i], h4);
#pragma unroll
    for (int i = 0; i < 4; i++) B1[i] = cm2(B0[2 * i], h256);
    B1[4] = cm2(B0[0], h512); B1[5] = cm2(B0[4], h512);
    B1[6] = cm2(B1[4], h256); B1[7] = cm2(B1[5], h256);
    const u32 ta = ktab + lane * 128, f = ((lane & 3) << 5) | ((lane & 4) << 2);
#pragma unroll
    for (int i = 0; i < 8; i++) sts128(ta + ((i << 4) ^ f), B0[i].re, B0[i].im, B1[i].re, B1[i].im);
    B2[0] = pk2(t0); B2[1] = pk2(t1);
    B2[2] = cm2(B2[0], h256); B2[3] = cm2(B2[1], h256);
#pragma unroll
    for (int i = 0; i < 4; i++) B2[4 + i] = cm2(B2[i], h512);
    S[0] = {0x3C003C00u, 0u}; S[1] = pk2c(w8); S[2] = pk2c(w16); S[3] = pk2c(s3); S[4] = pk2c(w32);
#pragma unroll
    for (int i = 1; i < 4; i++) S[4 + i] = cm2(S[i], S[4]);
#pragma unroll
    for (int i = 0; i < 8; i++) sts128(ta + 4096 + ((i << 4) ^ f), B2[i].re, B2[i].im, S[i].re, S[i].im);
    const C2 m64 = pk2c(w64), m128 = pk2c(w128);
    sts128(ktab + 8192 + lane * 16, m64.re, m64.im, m128.re, m128.im);
    __syncwarp();
  } else {
    u32 sa = SM_SIL + 576 * (w & 1) + 24 * min(lane, 23u);
#pragma unroll 1
    for (int j = 0; j < 6; j++) {
      sts32(sa, pk_bf(silu_f(blo(la)), silu_f(bhi(la))));
      la = ai; ai = cr.x; cr.x = cr.y; cr.y = ci.x; ci.x = ci.y; sa += 4;
    }
    bsync(7, 64);
  }
  TS(2);
  const u32 ep = __reduce_or_sync(~0u, epv), par = (ep + 1) & 1, pm = par ? TAGM : 0;
  if (w < 9) {
    asm volatile("cp.async.wait_all;" ::: "memory");
    __syncwarp();
    TS(4);
    if (tid == 256 && b >= 36 && b < 108) { mb_expect(SM_MB, 36864); tma3d(SM_UP, &tm_mod, SM_MB, 32 * b, 0); }
    const u32 xa = SM_XST + (lane & 15) * ROW + 128 * w + 16 * (lane >> 4);
    float s[4] = {}, X[2][4] = {}, Y[2][4] = {};
#pragma unroll
    for (int j = 0; j < 4; j++) {
      const uint4 a = ldsm4(xa + 32 * j);
      mma8_bf(X[0], a.x, a.y, a.x); mma8_bf(Y[0], a.x, a.y, a.y);
      mma8_bf(X[1], a.z, a.w, a.z); mma8_bf(Y[1], a.z, a.w, a.w);
      mma_bf(s, a.x, a.y, a.z, a.w, BONE, BONE);
    }
    uint4 t[4];
#pragma unroll
    for (int j = 0; j < 4; j++) t[j] = ldsm4t(xa + 32 * j);
    const float u0 = hi ? X[0][1] + X[1][1] : X[0][0] + X[1][0], u1 = hi ? Y[0][3] + Y[1][3] : Y[0][2] + Y[1][2];
    if (q == g >> 1) sts128(SM_SP + w * 128 + g * 16, fu(s[0]), fu(u0), fu(s[2]), fu(u1));
    bsync(1, 288);
    TS(7);
    const u32 spr = SM_SP + (lane & 7) * 16 + (lane & 8);
    const uint2 t8 = lds64(spr + 1024);
    const float f8 = lane < 16 ? 1.f : 0.f;
    float S1 = uf(t8.x) * f8, S2 = uf(t8.y) * f8;
#pragma unroll
    for (int i = 0; i < 4; i++) { const uint2 u = lds64(spr + (lane & 16) * 32 + i * 128); S1 += uf(u.x); S2 += uf(u.y); }
    S1 += __shfl_xor_sync(~0u, S1, 16); S2 += __shfl_xor_sync(~0u, S2, 16);
    const float mu = S1 * (1.f / 576.f), var = fmaxf(fmaf(-mu, mu, S2 * (1.f / 576.f)), 0.f);
    const float m = rbf(mu), rs = rcpf(rbf(sqrta(rbf(rbf(var) + 1e-5f))));
    const float ra = rs * 0.0625f;
    sts64(SM_AF + w * 128 + (lane & 15) * 8, fu(ra), fu(-m * ra));
    __syncwarp();
    TS(55);
    const uint4 f0 = lds128(SM_AF + w * 128 + q * 16), f1 = lds128(SM_AF + w * 128 + 64 + q * 16);
    const u32 zdst = SM_GATE + w * 2048 + lane * 8;
    const u32 pz = (q & 1) ? 0 : pm;
#pragma unroll
    for (int j = 0; j < 8; j++) {
      const u32 x0 = j & 1 ? t[j >> 1].z : t[j >> 1].x, x1 = j & 1 ? t[j >> 1].w : t[j >> 1].y;
      sts64(zdst + 256 * j, pk_hf(fmaf(blo(x0), uf(f0.x), uf(f0.y)), fmaf(bhi(x0), uf(f0.z), uf(f0.w))) | pz,
            pk_hf(fmaf(blo(x1), uf(f1.x), uf(f1.y)), fmaf(bhi(x1), uf(f1.z), uf(f1.w))));
    }
    TS(53);
    if (w < 8) barrive(15, 288);
    else {
      bsync(15, 288);
      TS(54);
      if (lane == 0) {
        PROXY_FENCE();
        bulk_out<BLK>(gs + b * BLK, SM_GATE);
        asm volatile("cp.async.bulk.commit_group;" ::: "memory");
        if (PFG) l2_pre<WSH / 2>(p.wg + b * WSH);
      }
      const float rh = rbf(rs);
      sts128(SM_ST + 16 * (lane & 15), pk_bf(-m, -m), pk_bf(rh, rh), pk_bf(rs - rh, rs - rh), 0);
    }
    TS(5);
  } else if (w == 11) {
    {
      if (b < 108) {
        float c[4][4] = {};
        u32 aa = SM_UP + ((lane & 7) + 8 * (lane >> 4)) * 64 + ((((lane >> 3) & 1) ^ ((lane & 7) >> 1)) << 4);
        u32 ba = SM_SIL + (lane >> 3) * 16;
        uint4 a[2][10];
#define GLD(n) { _Pragma("unroll") for (int i = 0; i < 2; i++) { a[n][5 * i] = ldsm4(ba + i * 64); \
          _Pragma("unroll") for (int k = 0; k < 4; k++) a[n][5 * i + 1 + k] = ldsm4t((k & 2 ? aa ^ 32 : aa) + i * 2048 + (k & 1) * 1024); } aa += 4096; ba += 128; }
#define GMM(n) { _Pragma("unroll") for (int i = 0; i < 2; i++) _Pragma("unroll") for (int k = 0; k < 4; k++) { const uint4 f = a[n][5 * i + 1 + k], bb = a[n][5 * i]; \
          mma_bf(c[k], f.x, f.y, f.z, f.w, k & 1 ? bb.z : bb.x, k & 1 ? bb.w : bb.y); } }
        mb_wait(SM_MB);
        TS(56);
        GLD(0);
#pragma unroll 1
        for (int s = 0; s < 4; s++) { GLD(1); GMM(0); GLD(0); GMM(1); }
        GMM(0);
        const float v0 = (q & 1) ? c[0][2] + c[1][2] : c[0][0] + c[1][0], v1 = (q & 1) ? c[2][2] + c[3][2] : c[2][0] + c[3][0];
        str16(gs + (G_MOD + b * 128 + 2 * g + 16 * q), pk_bf(rbf((q & 2) ? v1 : v0) * F2M64, 0.f) | (g < 2 ? pm : 0));
        TS(57);
      }
      const u32 d = lane < 4 ? 4 * b + lane : Ps;
      const char* mp = gs + (G_MOD + (d >> 5) * 128 + (d & 24) * 2);
      uint4 ta, tc;
      POLL({ ta = ldr128(mp); tc = ldr128(mp + MODJ); }, ((ta.x ^ pm) | (tc.x ^ pm)) & TAGM, 2);
      const u32 aw = (d & 4) ? ((d & 2) ? ta.w : ta.z) : ((d & 2) ? ta.y : ta.x & ~TAGM);
      const u32 cw = (d & 4) ? ((d & 2) ? tc.w : tc.z) : ((d & 2) ? tc.y : tc.x & ~TAGM);
      const float sa = ((d & 1) ? bhi(aw) : blo(aw)) * F2P64, c1 = rbf(fmaf((d & 1) ? bhi(cw) : blo(cw), F2P64, 1.f));
      const u32 EM = min(max(fu(fmaxf(32.f * fabsf(c1), fabsf(sa))) >> 23, 80u), 250u);
      const float inv = uf((264 - EM) << 23);
      if (lane < 5) { sts64(SM_SC + 16 * lane, pk_hf(16.f * c1 * inv, 16.f * c1 * inv), pk_hf(sa * inv, sa * inv)); sts32(SM_SC + 16 * lane + 8, (EM - 74) << 23); }
      TS(10);
    }
  }
  if (kw) {
    float D[5][4] = {};
    u32 ta = ktab + q * 128 + ((g ^ (q << 1)) << 4), tm = ktab + 8192 + q * 16;
#pragma unroll 2
    for (int s = 0; s < 8; s++) {
      const uint4 ca = lds128(ta), cb = lds128(ta + 4096), ma = lds128(tm);
      ta = (ta + 512) ^ 16; tm += 64;
      k2048 += __shfl_xor_sync(~0u, k2048, 16 >> s);
      const C2 s0 = {cb.z, cb.w}, s1 = cm2(s0, {ma.x, ma.y}), s2 = cm2(s0, {ma.z, ma.w}), s3 = cm2(s1, {ma.z, ma.w});
      mma_hf(D[0], s0.re, s1.re, s0.im, s1.im, ca.x, ca.y);
      mma_hf(D[2], s0.re, s1.re, s0.im, s1.im, ca.z, ca.w);
      mma_hf(D[4], s0.re, s1.re, s0.im, s1.im, cb.x, cb.y);
      mma_hf(D[1], s2.re, s3.re, s2.im, s3.im, ca.x, ca.y);
      mma_hf(D[3], s2.re, s3.re, s2.im, s3.im, ca.z, ca.w);
    }
    TS(3);
    const u32 xa = (w < 8 ? SM_MODS + (4 + ksig) * KTAB : SM_ZS) + lane * 16;
    if (khf) {
      __syncwarp();
#pragma unroll
      for (int j = 0; j < 5; j++) sts128(xa + 512 * j, fu(D[j][0]), fu(D[j][1]), fu(D[j][2]), fu(D[j][3]));
      if (lane == 0) sts32(xa + 2560, fu(k2048));
      asm volatile("bar.arrive %0,64;" ::"r"(2 + ksig) : "memory");
    } else {
      const u32 t1 = tp + (q < 2 ? (128 + 4 * g + 2 * q) * 4 : T3 * 4 + ((32 * q - 64 + g) ^ 1) * 2);
      const u32 x = 16 * q + (g >> 1) + hi + 1, tb = tp + (hi ? T7E : T9E) * 4 - 4;
      const u32 te = tb + (x + 2 * (x & 1)) * 2, to = tb + TEO * 4 + (x ^ 1) * 2;
      asm volatile("bar.sync %0,64;" ::"r"(2 + ksig) : "memory");
#pragma unroll
      for (int j = 0; j < 5; j++) { const uint4 t = lds128(xa + 512 * j); D[j][0] += uf(t.x); D[j][1] += uf(t.y); D[j][2] += uf(t.z); D[j][3] += uf(t.w); }
      k2048 = (k2048 + uf(lds32(xa + 2560))) * 0.125f;
#pragma unroll
      for (int r = 0; r < 4; r++) {
        const u32 v = pk_hf(D[2 + (r >> 1)][2 * (r & 1)], D[2 + (r >> 1)][2 * (r & 1) + 1]);
        if (q < 2) {
          const u32 vv = __byte_perm(v, v, 0x1010);
          sts32(t1 + (TO + 32 * r) * 4, vv); sts16(t1 + (TO + 32 * r + 1) * 4 + 2, v >> 16); sts16(t1 + (TO + 32 * r - 1) * 4, v);
          sts64(t1 + (TE + 32 * r) * 4, vv, __byte_perm(v, v, 0x1032));
        } else {
          sts16(t1 + 16 * r, v >> 16);
          if (r == 0 && lane == 2) {
            const u32 vv = __byte_perm(v, v, 0x1010);
            sts32(tp + (TO + 256) * 4, vv); sts16(tp + (TO + 257) * 4 + 2, v); sts16(tp + (TO + 255) * 4, v); sts64(tp + (TE + 256) * 4, vv, vv);
          } else sts16(t1 + 16 * r - ((T3 - T5) * 4 + 6) + 8 * hi, v);
        }
      }
#pragma unroll
      for (int r = 0; r < 2; r++) {
        const u32 v = pk_hf(D[4][2 * r], D[4][2 * r + 1]);
        if (r == 0 && lane == 0) { sts16(tp + T5 * 4 + 62 * 2, v); sts32(SM_KV + 4 * ksig, v & 0xffff); sts16(tp + (T9E + TEO) * 4 + 62 * 2, pk_hf(k2048, 0.f)); }
        else { sts16(te + 8 * r, v); sts16(to + 8 * r, v); }
        sts16(te + 8 * r + 16, v >> 16); sts16(to + 8 * r + 16, v >> 16);
      }
      __syncwarp();
#pragma unroll
      for (int r = 0; r < 4; r++) {
        const u32 v = pk_hf(D[r >> 1][2 * (r & 1) + 1], D[r >> 1][2 * (r & 1)]), t2 = tp + lane * 4 + 128 * r;
        sts32(t2 + TO * 4, v); sts16(t2 + TE * 4, v >> 16); sts16(t2 + (TE + 1) * 4 + 2, v);
      }
      __syncwarp();
    }
  }
  TS(6);
  const u32 r0 = (lane & 7) + ((lane >> 3) & 1) + 8 * (lane >> 4) - 1;
  const u32 rl16 = (r0 ^ ((r0 >> 3) & 3)) * 16;
  const u32 pml = (g & 3) ? 0 : pm;
  if (w < 4) {
    asm volatile("setmaxnreg.inc.sync.aligned.u32 232;");
    const u32 tr = tp + ((hi ? TO : TE) + (g >> 1) - q) * 4;
    u32 T[33][4], B5[5][2], B3[5][2];
#pragma unroll
    for (int d = 0; d < 33; d++) {
      T[d][0] = lds32(tr + 32 * d); T[d][1] = lds32(tr + 32 * d + 16);
      T[d][2] = d ? cpy(T[d - 1][1], zr, 0) : zr; T[d][3] = cpy(T[d][0], zr, 1);
    }
    const u32 bt = tp + (T5 + g - q) * 4;
#pragma unroll
    for (int d = 0; d < 5; d++) {
      B5[d][0] = lds32(bt + 32 * d); B5[d][1] = lds32(bt + 32 * d - 16);
      B3[d][0] = lds32(bt + 32 * d + (T3 - T5) * 4); B3[d][1] = lds32(bt + 32 * d - 16 + (T3 - T5) * 4);
    }
    u32 za = SM_ZS + 16 + w * ZSS + ((lane >> 3) & 1) * ZPS + ((lane & 7) + (lane >> 4)) * 16;
    u32 wa = SM_W + W5O + w * WSL + rl16;
    u32 sa = SM_W + W9O + w * WSL + lane * 16;
    u32 yo = G_Y + 2 * q * BLK + (4 * b + w) * 32 + 4 * g;
    TS(8);
    lds32(za);
    bsync(9, 384);
    TS(11);
    float A[4][4] = {};
    uint4 Z[4];
    Z[0] = ldsm4(za); Z[1] = ldsm4(za + 32);
    const uint2 fc = lds64(SM_SC + 16 * w + 8);
    const u32 F = __byte_perm(fu(uf(fc.x) * uf(fc.y)), 0, 0x3232);
#define STEP(s, b0, b1) { _Pragma("unroll") for (int i = 0; i < 4; i++) mma_hf_o(A[i], A[i], T[8 * i + 7 - (s)], b0, b1); }
#define PAIR(n) { Z[(n + 2) & 3] = ldsm4(za + 32 * (n + 2)); STEP(2 * n, Z[n].x, Z[n].y); STEP(2 * n + 1, Z[n].z, Z[n].w); }
#define LAST(N) mma8_hf(N, T[32][1], zr, Z[3].y); float O[4]; mma_hf_o(O, A[0], T[0], Z[3].z, Z[3].w); \
    _Pragma("unroll") for (int i = 0; i < 3; i++) mma_hf_o(A[i], A[i + 1], T[8 * i + 8], Z[3].z, Z[3].w); \
    mma_hf_o(A[3], N, T[32], Z[3].z, Z[3].w);
#pragma unroll 1
    for (int j = 0; j < 4; j++) {
      PAIR(0); PAIR(1); PAIR(2);
      Z[1] = ldsm4(za + 160); STEP(6, Z[3].x, Z[3].y);
      float N[4] = {};
      LAST(N);
      y_store(O[0], O[1], O[2], O[3], F, pml, gs + yo);
      za += 128; yo += 8 * BLK;
      TS(40 + j);
    }
    bsync(10, 352);
#pragma unroll 1
    for (int j = 4; j < 13; j++) {
      const uint4 a5 = ldsm4t(wa), a3 = ldsm4t(wa + (W3O - W5O)), s3 = lds128(sa);
      PAIR(0);
      float N[4] = {uf(s3.x), uf(s3.y), uf(s3.z), uf(s3.w)};
#pragma unroll
      for (int i = 0; i < 4; i++) mma_hf(A[i], a5.x, a5.y, a5.z, a5.w, B5[i][0], B5[i][1]);
      mma_hf(N, a5.x, a5.y, a5.z, a5.w, B5[4][0], B5[4][1]);
      PAIR(1);
#pragma unroll
      for (int i = 0; i < 4; i++) mma_hf(A[i], a3.x, a3.y, a3.z, a3.w, B3[i][0], B3[i][1]);
      mma_hf(N, a3.x, a3.y, a3.z, a3.w, B3[4][0], B3[4][1]);
      PAIR(2);
      Z[1] = ldsm4(za + 160); STEP(6, Z[3].x, Z[3].y);
      LAST(N);
      y_store(O[0], O[1], O[2], O[3], F, pml, gs + yo);
      za += 128; wa = (wa + 256) ^ 32; sa += 512; yo += 8 * BLK;
      TS(40 + j);
    }
    {
      float X[3][4] = {};
#pragma unroll
      for (int ty = 0; ty < 2; ty++) {
        const uint4 a = ldsm4t(wa + ty * (W3O - W5O)), c = ldsm4t((wa ^ 32) + 256 + ty * (W3O - W5O)), d = ldsm4t(wa + 512 + ty * (W3O - W5O));
#pragma unroll
        for (int i = 0; i < 3; i++) mma_hf(A[i], a.x, a.y, a.z, a.w, ty ? B3[i][0] : B5[i][0], ty ? B3[i][1] : B5[i][1]);
#pragma unroll
        for (int i = 0; i < 2; i++) mma_hf(X[i], c.x, c.y, c.z, c.w, ty ? B3[i][0] : B5[i][0], ty ? B3[i][1] : B5[i][1]);
        mma_hf(X[2], d.x, d.y, d.z, d.w, ty ? B3[0][0] : B5[0][0], ty ? B3[0][1] : B5[0][1]);
      }
      barrive(12, 288);
#pragma unroll
      for (int n = 0; n < 4; n++) {
        const uint4 f0 = n < 2 ? Z[n] : ldsm4(za + 32 * n), f1 = ldsm4(za + 32 * n + 128), f2 = ldsm4(za + 32 * n + 256);
#pragma unroll
        for (int s = 2 * n; s < 2 * n + 2; s++) {
#pragma unroll
          for (int i = 0; i < 3; i++) mma_hf_o(A[i], A[i], T[8 * i + 7 - s], s & 1 ? f0.z : f0.x, s & 1 ? f0.w : f0.y);
          mma_hf_o(X[0], X[0], T[7 - s], s & 1 ? f1.z : f1.x, s & 1 ? f1.w : f1.y); mma_hf_o(X[1], X[1], T[15 - s], s & 1 ? f1.z : f1.x, s & 1 ? f1.w : f1.y);
          mma_hf_o(X[2], X[2], T[7 - s], s & 1 ? f2.z : f2.x, s & 1 ? f2.w : f2.y);
        }
      }
      y_store(A[0][0], A[0][1], A[0][2], A[0][3], F, pml, gs + yo);
      y_store(A[1][0] + X[0][0], A[1][1] + X[0][1], A[1][2] + X[0][2], A[1][3] + X[0][3], F, pml, gs + yo + 8 * BLK);
      y_store(A[2][0] + X[1][0] + X[2][0], A[2][1] + X[1][1] + X[2][1], A[2][2] + X[1][2] + X[2][2], A[2][3] + X[1][3] + X[2][3], F, pml, gs + yo + 16 * BLK);
    }
    TS(15);
    bsync(14, 224);
  } else {
    asm volatile("setmaxnreg.dec.sync.aligned.u32 136;");
    const u32 t8 = tid - 128;
    {
      TS(12);
      if (PFG && tid == 288) l2_pre<WSH / 2>(p.wg + (b * WSH + WSH / 2));
      const char* zs = gs + ((16 * w - 64 + (lane >> 3)) * BLK + b * 128 + (lane & 7) * 16);
      const char* zs4 = gs + ((t8 >> 1) * BLK + Ps * 32 + (t8 & 1) * 16);
      uint4 v[5];
      POLL(v[4] = ldr128(zs4), (v[4].x ^ pm) & TAGM, 1);
      TS(58);
#pragma unroll
      for (int j = 0; j < 4; j++) v[j] = ldr128(zs + j * 4 * BLK);
      bsync(8, 256);
      const uint2 cc = lds64(SM_SC + 8 * (t8 & 6)), c4 = lds64(SM_SC + 64);
      POLLW(_Pragma("unroll") for (int j = 0; j < 4; j++) if ((v[j].x ^ pm) & TAGM) v[j] = ldr128(zs + j * 4 * BLK),
           ((v[0].x ^ pm) | (v[1].x ^ pm) | (v[2].x ^ pm) | (v[3].x ^ pm)) & TAGM, 1);
      TS(9);
      const u32 dst = SM_ZS + 128 + (t8 & 7) * ZPS + (16 * w - 64 + (lane >> 3)) * 16;
#pragma unroll
      for (int j = 4; j >= 0; j--) {
        const uint2 c = j < 4 ? cc : c4;
        sts128(j < 4 ? dst + j * 64 : SM_Z4 + 256 + (t8 & 1) * ZP4 + (t8 >> 1) * 16, hfma(v[j].x & ~TAGM, c.x, c.y), hfma(v[j].y, c.x, c.y), hfma(v[j].z, c.x, c.y), hfma(v[j].w, c.x, c.y));
      }
      if (t8 < 96) sts128(t8 < 64 ? SM_ZS + (t8 & 7) * ZPS + (t8 >> 3) * 16 : SM_Z4 + (t8 & 1) * ZP4 + (t8 & 30) * 8, 0, 0, 0, 0);
      asm volatile("cp.async.bulk.wait_group.read 0;" ::: "memory");
      bsync(9, 384);
      TS(11);
      if (tid == 352) {
        mb_expect(SM_MB + 8, rho ? SLV : 46080);
        tma3d(SM_GATE, &tm_gate, SM_MB + 8, 32 * b, 0);
        if (!rho) tma3d(SM_GATE + SLV, &tm_gs, SM_MB + 8, 4096 + 4 * b, 0);
        l2_pre<WSH>(p.wu + b * WSH);
      }
      const bool lng = w < 8 || w == 9;
      const u32 ts = lane + 32 * (w == 8 ? 0 : w - 9);
      const u32 sig = lng ? ksig : ts >> 4, l2 = lng ? lane : 32 + (ts & 15);
      if (!lng) {
#pragma unroll
        for (int i = 0; i < 3; i++) if (i < 2 || ts < 64) str128(gs + (G_Y + (96 + 12 * i + (ts >> 3)) * BLK + b * 128 + (ts & 7) * 16), INVAL, 0, 1, 0);
        str128(gs + (G_PART + b * 2048 + ts * 16), INVAL, 0, 1, 0);
        str128(gs + (ts < 32 ? G_PART + b * 2048 + 1536 + ts * 16 : ts < 64 ? G_ACT + b * 512 + (ts & 31) * 16 : G_Y + (96 + 16 * rho + ((ts & 31) >> 1)) * BLK + Ps * 32 + (ts & 1) * 16), INVAL, 0, 1, 0);
        if (ts < (rho ? 4 : 12)) str128(gs + (ts < 4 ? G_KEY + b * 128 + ts * 16 : G_ACT + Ps * 128 + (ts - 4) * 16), INVAL, 0, 1, 0);
      }
      const u32 wb = SM_W + sig * WSL;
      if (sig < 5) {
        const u32 za = (sig < 4 ? SM_ZS + 128 + sig * ZSS : SM_Z4 + 256) + l2 * 32, zb = za + (sig < 4 ? ZPS : ZP4);
        const uint4 c0 = lds128(zb - 32), c1 = lds128(za - 16), c2 = lds128(zb - 16), c3 = lds128(za), c4 = lds128(zb), c5 = lds128(za + 16), c6 = lds128(zb + 16);
        const u32 P[25] = {c0.z, c0.w, c1.x, c1.y, c1.z, c1.w, c2.x, c2.y, c2.z, c2.w, c3.x, c3.y, c3.z, c3.w, c4.x, c4.y, c4.z, c4.w, c5.x, c5.y, c5.z, c5.w, c6.x, c6.y, c6.z};
        u32 Q[25], D1[24], F4[23], W5[21], W3[17];
#pragma unroll
        for (int j = 1; j < 25; j++) Q[j] = __byte_perm(P[j - 1], P[j], 0x5432);
#pragma unroll
        for (int j = 1; j < 24; j++) D1[j] = hadd(P[j], Q[j]);
#pragma unroll
        for (int j = 2; j < 23; j++) F4[j] = hadd(D1[j], D1[j - 1]);
#pragma unroll
        for (int n = 0; n < 21; n++) W5[n] = hadd(F4[n + 2], P[n]);
#pragma unroll
        for (int n = 0; n < 17; n++) W3[n] = hadd(Q[n + 8], D1[n + 7]);
        const u32 a0 = wb + W5O + 64 * l2 + 16 * ((l2 >> 1) & 3);
#pragma unroll
        for (int i = 0; i < 4; i++) {
          sts128(a0 ^ (16 * i), W5[4 * i + 5], W5[4 * i + 6], W5[4 * i + 7], W5[4 * i + 8]);
          sts128((a0 ^ (16 * i)) + (W3O - W5O), W3[4 * i + 1], W3[4 * i + 2], W3[4 * i + 3], W3[4 * i + 4]);
        }
        if (lng) {
          if (lane < 16) sts128(wb + (lane & 7) * 16 + (lane & 8) * 400, 0, 0, 0, 0);
          const u32 a1 = wb + 32 * lane + 16 * ((lane >> 2) & 1);
#pragma unroll
          for (int i = 0; i < 4; i++) {
            const u32 a = (a1 ^ (16 * (i >> 1))) + 1024 * (i & 1), n = 4 * i;
            sts128(a + V2O, hadd(Q[n + 9], P[n + 8]), hadd(Q[n + 10], P[n + 9]), hadd(Q[n + 11], P[n + 10]), hadd(Q[n + 12], P[n + 11]));
            sts128(a + W9O, hadd(F4[n + 4], W5[n]), hadd(F4[n + 5], W5[n + 1]), hadd(F4[n + 6], W5[n + 2]), hadd(F4[n + 7], W5[n + 3]));
            sts128(a + W7O, hadd(F4[n + 6], W3[n]), hadd(F4[n + 7], W3[n + 1]), hadd(F4[n + 8], W3[n + 2]), hadd(F4[n + 9], W3[n + 3]));
          }
        }
      }
      __syncwarp();
      TS(32);
      if (lng) {
        const u32 wa = wb + ((lane >> 3) & 1) * 1024 + (((lane & 7) ^ (lane >> 4)) + 8 * (lane >> 4)) * 16;
        const u32 kv = lds32(SM_KV + 4 * sig), bi = (g >> 1) == q ? (hi ? kv << 16 : kv) : 0u;
        float acc[8][4] = {};
#pragma unroll
        for (int j = 0; j < 4; j++) { const uint4 a = ldsm4t(wa + V2O + j * 256); mma8_hf(acc[2 * j], a.x, a.y, bi); mma8_hf(acc[2 * j + 1], a.z, a.w, bi); }
        u32 bt = tp + (T9E + hi * TEO + (g >> 1) - q) * 4, wt = wa + W9O;
#pragma unroll 1
        for (int ty = 0; ty < 2; ty++) {
          uint4 a[4];
#pragma unroll
          for (int be = 0; be < 4; be++) a[be] = ldsm4t(wt + be * 256);
          u32 b1 = lds32(bt - 16);
#pragma unroll
          for (int d = 0; d < 8; d++) {
            const u32 b0 = lds32(bt + 16 * d);
#pragma unroll
            for (int be = 0; be < 4; be++) if (d + 2 * be < 8) mma_hf(acc[d + 2 * be], a[be].x, a[be].y, a[be].z, a[be].w, b0, b1);
            b1 = b0;
          }
          bt += (T7E - T9E) * 4; wt += W7O - W9O;
        }
        __syncwarp();
#pragma unroll
        for (int j = 0; j < 8; j++) sts128(wb + W9O + j * 512 + lane * 16, fu(acc[j][0]), fu(acc[j][1]), fu(acc[j][2]), fu(acc[j][3]));
        TS(34);
      }
      if (w != 9) barrive(10, 352);
      if (w >= 8) barrive(11, 256);
    }
    if (w < 8) {
      const int u0 = 4 * (w - 4) + 2 * rho;
      const u32 t4 = SM_TAP + 4 * TAPS;
      u32 tr = t4 + ((hi ? TO : TE) + (g >> 1) - q) * 4;
      u32 zb = SM_Z4 + 256 + ((lane >> 3) & 1) * ZP4 + u0 * 128 + (lane & 7) * 16 + (lane >> 4) * 128;
      float acc[4][4] = {};
      u32 prev = 0;
#pragma unroll 1
      for (int it = min(u0 + 2, 4); it; it--) {
#pragma unroll
        for (int s = 0; s < 8; s++) {
          const uint4 z = ldsm4(zb - 16 * s);
          const u32 t0 = lds32(tr + 32 * s), t1 = lds32(tr + 32 * s + 16);
          mma_hf(acc[s & 1], t0, t1, prev, t0, z.x, z.y);
          mma_hf(acc[2 + (s & 1)], t0, t1, prev, t0, z.z, z.w);
          prev = t1;
        }
        zb -= 128; tr += 256;
      }
      {
        const uint4 z = ldsm4(zb); const u32 t0 = lds32(tr), t1 = lds32(tr + 16);
        mma_hf(acc[0], t0, t1, prev, t0, z.x, z.y); mma_hf(acc[2], t0, t1, prev, t0, z.z, z.w);
        if (w > 4) { const uint4 y = ldsm4(zb - 16); mma8_hf(acc[1], t1, zr, y.y); mma8_hf(acc[3], t1, zr, y.w); }
      }
      bsync(11, 256);
      u32 wa = (SM_W + 4 * WSL + W5O + rl16 + (u0 - 3) * 256) ^ 32, bt = t4 + (T5 + g - q) * 4;
#pragma unroll 1
      for (int al = min(u0 - 2, 6); al > 0; al--) {
#pragma unroll
        for (int ty = 0; ty < 2; ty++) {
          const uint4 a = ldsm4t(wa + ty * (W3O - W5O));
          const u32 bb = bt + ty * (T3 - T5) * 4;
          mma_hf(acc[ty], a.x, a.y, a.z, a.w, lds32(bb - 32), lds32(bb - 48));
          mma_hf(acc[2 + ty], a.x, a.y, a.z, a.w, lds32(bb), lds32(bb - 16));
        }
        wa = (wa - 256) ^ 32; bt += 32;
      }
      TS(35);
      const uint2 fc = lds64(SM_SC + 16 * 4 + 8);
      const u32 F = __byte_perm(fu(uf(fc.x) * uf(fc.y)), 0, 0x3232);
      char* yp = gs + (G_Y + (8 * u0 + 2 * q) * BLK + Ps * 32 + 4 * g);
#pragma unroll
      for (int j = 0; j < 2; j++) {
        uint4 s3 = {0, 0, 0, 0};
        if (u0 >= 8) s3 = lds128(SM_W + 4 * WSL + W9O + (u0 - 8 + j) * 512 + lane * 16);
        y_store(acc[2 * j][0] + acc[2 * j + 1][0] + uf(s3.x), acc[2 * j][1] + acc[2 * j + 1][1] + uf(s3.y), acc[2 * j][2] + acc[2 * j + 1][2] + uf(s3.z),
                acc[2 * j][3] + acc[2 * j + 1][3] + uf(s3.w), F, pml, yp + j * 8 * BLK);
      }
      TS(16);
    } else {
      if (tid == 256) {
        PROXY_FENCE();
        mb_wait(SM_MB + 8);
        mb_expect(SM_MB + 16, rho ? SLV : 46080);
        tma3d(SM_UP, &tm_up, SM_MB + 16, 32 * b, 0);
        if (!rho) tma3d(SM_UP + SLV, &tm_us, SM_MB + 16, 4096 + 4 * b, 0);
        l2_pre<WSH>(p.wd + b * WSH);
      }
      TS(17);
      if (w > 8) {
        const u32 t = tid - 288, c = min(t, 71u);
        const char* mp = gs + (G_MOD + (c >> 2) * 128 + (c & 3) * 16);
        const uint4 dk = ldg128(p.dsk + 16 * c), wr = ldg128(p.wr + 16 * c);
        uint4 md[6];
        POLL(_Pragma("unroll") for (int j = 0; j < 6; j++) md[j] = ldr128(mp + j * MODJ),
             ((md[0].x ^ pm) | (md[1].x ^ pm) | (md[2].x ^ pm) | (md[3].x ^ pm) | (md[4].x ^ pm) | (md[5].x ^ pm)) & TAGM, 4);
        const u32 ma = SM_MODS + 16 * c;
#pragma unroll
        for (int j = 0; j < 6; j++) {
          const u32 o = (j % 3 == 1) ? BONE : 0x80008000u;
          md[j] = make_uint4(bfma(md[j].x & ~TAGM, B2P64, o), bfma(md[j].y, B2P64, o), bfma(md[j].z, B2P64, o), bfma(md[j].w, B2P64, o));
          sts128(ma + 1152 * j, md[j].x, md[j].y, md[j].z, md[j].w);
        }
        sts128(ma + 1152 * 6, dk.x, dk.y, dk.z, dk.w);
        const uint4 H = make_uint4(bmul(md[4].x, wr.x), bmul(md[4].y, wr.y), bmul(md[4].z, wr.z), bmul(md[4].w, wr.w));
        sts128(ma + 1152 * 7, H.x, H.y, H.z, H.w);
        sts128(ma + 1152 * 8, bfma(md[4].x, wr.x, H.x ^ 0x80008000u), bfma(md[4].y, wr.y, H.y ^ 0x80008000u), bfma(md[4].z, wr.z, H.z ^ 0x80008000u), bfma(md[4].w, wr.w, H.w ^ 0x80008000u));
        float c4[4] = {};
        mma_bf(c4, md[4].x, md[3].x, md[4].y, md[3].y, wr.x, wr.y); mma_bf(c4, md[4].z, md[3].z, md[4].w, md[3].w, wr.z, wr.w);
        if (q == g >> 1) sts64(SM_RC + (t >> 2) * 8, fu(hi ? c4[1] : c4[0]), fu(hi ? c4[3] : c4[2]));
        if (t < 5) sts128(t < 2 ? SM_ONE + 16 * t : SM_THR + 16 * t - 32, t ? 0 : BONE, t ? 0 : BONE, t ? 0 : BONE, t ? 0 : BONE);
        TS(14);
        barrive(13, 256);
        if (w != 10) barrive(14, 224);
      }
    }
    if (w < 9) bsync(13, 256);
  }
  post_conv(p, &tm_down, tid + p.zero, b, ep);
  TSD();
  if (tid == 352 && s2u(smem) != SM0) __trap();
}

typedef CUresult (*EncFn)(CUtensorMap*, CUtensorMapDataType, cuuint32_t, void*, const cuuint64_t*, const cuuint64_t*, const cuuint32_t*, const cuuint32_t*,
                          CUtensorMapInterleave, CUtensorMapSwizzle, CUtensorMapL2promotion, CUtensorMapFloatOOBfill);
static void make_map(EncFn enc, CUtensorMap* tm, void* ptr, int cols, int rows, int bw, int nb, CUtensorMapSwizzle sw, int gr = 192) {
  cuuint64_t gd[3] = {(cuuint64_t)cols, (cuuint64_t)gr, (cuuint64_t)(rows / gr)}, gs[2] = {(cuuint64_t)cols * 2, (cuuint64_t)cols * 2 * gr};
  cuuint32_t bd[3] = {(cuuint32_t)bw, (cuuint32_t)gr, (cuuint32_t)nb}, es[3] = {1, 1, 1};
  enc(tm, CU_TENSOR_MAP_DATA_TYPE_BFLOAT16, 3, ptr, gd, gs, bd, es, CU_TENSOR_MAP_INTERLEAVE_NONE, sw, CU_TENSOR_MAP_L2_PROMOTION_NONE, CU_TENSOR_MAP_FLOAT_OOB_FILL_NONE);
}
extern "C" void kernel_launch(void* const* d_in, const int* in_sizes, int n_in, void* d_out, int out_size) {
  static EncFn enc = nullptr;
  static void* scratch = nullptr;
  if (!enc) {
    cudaGetSymbolAddress(&scratch, g_s);
    cudaDriverEntryPointQueryResult qr;
    cudaGetDriverEntryPoint("cuTensorMapEncodeTiled", (void**)&enc, cudaEnableDefault, &qr);
    cudaFuncSetAttribute(fused_kernel, cudaFuncAttributeMaxDynamicSharedMemorySize, SM_TOTAL);
  }
  CUtensorMap tm_mod, tm_gate, tm_gs, tm_up, tm_us, tm_down;
  make_map(enc, &tm_mod, d_in[13], 3456, 576, 32, 3, CU_TENSOR_MAP_SWIZZLE_64B);
  make_map(enc, &tm_gate, d_in[9], 4608, 576, 32, 3, CU_TENSOR_MAP_SWIZZLE_64B);
  make_map(enc, &tm_gs, d_in[9], 4608, 576, 8, 3, CU_TENSOR_MAP_SWIZZLE_NONE);
  make_map(enc, &tm_up, d_in[10], 4608, 576, 32, 3, CU_TENSOR_MAP_SWIZZLE_64B);
  make_map(enc, &tm_us, d_in[10], 4608, 576, 8, 3, CU_TENSOR_MAP_SWIZZLE_NONE);
  make_map(enc, &tm_down, d_in[11], 576, 4608, 64, 1, CU_TENSOR_MAP_SWIZZLE_128B, 96);
  Prm p;
  p.x = (const char*)d_in[0]; p.la = (const char*)d_in[1]; p.ai = (const char*)d_in[2]; p.cr = (const char*)d_in[3];
  p.ci = (const char*)d_in[4]; p.ldt = (const char*)d_in[5]; p.dsk = (const char*)d_in[6]; p.wr = (const char*)d_in[8];
  p.wg = (const char*)d_in[9]; p.wu = (const char*)d_in[10]; p.wd = (const char*)d_in[11];
  p.c = (const char*)d_in[12]; p.out = (char*)d_out; p.zero = 0; p.gs = (char*)scratch;
  fused_kernel<<<128, 384, SM_TOTAL>>>(p, tm_mod, tm_gate, tm_gs, tm_up, tm_us, tm_down);
}
```

```cpp
#include <cuda_runtime.h>
#include <cuda.h>
#include <cuda_bf16.h>
#include <cuda_fp16.h>
#include <stdint.h>
#define FUSED 1
#define DEV __device__ __forceinline__
typedef uint32_t u32;

constexpr u32 BLK = 18432, G_Z = 0, G_Y = 128 * BLK, G_MOD = 2 * G_Y, G_KEY = G_MOD + 128 * 128, G_ACT = G_KEY + 128 * 128;
constexpr u32 G_PART = G_ACT + 576 * 128, G_EP = G_PART + 128 * 2048, G_END = G_EP + 128;
__device__ __align__(128) unsigned char g_s[G_END];
#define TS(i)
#define TS0()
#define TSE()
#define TSD()
#define TSX 0
#define ERRF(code)

constexpr int SM0 = 1024;
constexpr int ROW = 1168, SLV = 36864;
constexpr int SM_GATE = SM0, SM_UP = SM_GATE + 46080, SM_XST = SM_UP + 46080, SM_MODS = SM_XST + 16 * ROW, SM_W = SM_MODS + 11008;
constexpr int KTAB = 9216, WSL = 12544, W5O = 128, W3O = 3328, V2O = 6400, W9O = 8448, W7O = 10496;
constexpr int ZPS = 2192, ZSS = 2 * ZPS, ZP4 = 2368;
constexpr int SM_ZS = SM_W + 5 * WSL, SM_Z4 = SM_ZS + 4 * ZSS, SM_TAP = SM_Z4 + 2 * ZP4, TAPS = 3328;
constexpr int SM_MB = SM_TAP + 5 * TAPS;
constexpr int SM_SC = SM_MB + 32;
constexpr int SM_KV = SM_SC + 80;
constexpr int SM_THR = SM_KV + 32;
constexpr int SM_SLOT = SM_THR + 48;
constexpr int SM_KEY = SM_SLOT + 32;
constexpr int SM_ST = SM_KEY + 64;
constexpr int SM_ST2 = SM_ST + 256;
constexpr int SM_RC = SM_ST2 + 256;
constexpr int SM_SP = SM_RC + 192;
constexpr int SM_AF = SM_SP + 1152, SM_SIL = SM_AF + 1152, SM_END = SM_SP + 5760;
constexpr int SM_ONE = SM_MODS + 9 * 1152;
constexpr int SM_WD = SM_W, SM_XS = SM_W + 49152, SM_AC = SM_ZS, SM_RED = SM_AC + 6144, SM_LIST = SM_TAP;
constexpr int SM_TSB = SM_END, SM_TOTAL = SM_END + TSX - SM0;
static_assert(SM_W % 1024 == 0 && SM_MODS + 8 * KTAB <= SM_ZS && SM_ZS + 2 * KTAB <= SM_TAP && SM_RED + 10240 <= SM_TAP && SM_XS + 8 * ROW <= SM_ZS, "smem map");
static_assert(SM_MB % 16 == 0 && SM_THR % 16 == 0 && SM_ST % 16 == 0 && SM_SP % 16 == 0 && SM_TOTAL <= 232448, "smem map");
constexpr int TE = 4, TO = 276, T5 = 560, T3 = 624, T9E = 680, T7E = 760, TEO = 40;
#define UPM 2
#define PFD 1
#define MT 10
#define DX 0
#define DMOD 1000
#define PFG 1
constexpr int SPIN = 1 << 16, NEARLY = 4;
constexpr u32 TAGM = 0x40004000u, TAGR = 0x40000000u, INVAL = 0x00004801u;

DEV u32 s2u(const void* p) { return (u32)__cvta_generic_to_shared(p); }
DEV void mma_bf(float (&c)[4], u32 a0, u32 a1, u32 a2, u32 a3, u32 b0, u32 b1) {
  asm("mma.sync.aligned.m16n8k16.row.col.f32.bf16.bf16.f32 {%0,%1,%2,%3},{%4,%5,%6,%7},{%8,%9},{%0,%1,%2,%3};"
      : "+f"(c[0]), "+f"(c[1]), "+f"(c[2]), "+f"(c[3]) : "r"(a0), "r"(a1), "r"(a2), "r"(a3), "r"(b0), "r"(b1));
}
DEV void mma_hf(float (&c)[4], u32 a0, u32 a1, u32 a2, u32 a3, u32 b0, u32 b1) {
  asm("mma.sync.aligned.m16n8k16.row.col.f32.f16.f16.f32 {%0,%1,%2,%3},{%4,%5,%6,%7},{%8,%9},{%0,%1,%2,%3};"
      : "+f"(c[0]), "+f"(c[1]), "+f"(c[2]), "+f"(c[3]) : "r"(a0), "r"(a1), "r"(a2), "r"(a3), "r"(b0), "r"(b1));
}
DEV void mma8_bf(float (&c)[4], u32 a0, u32 a1, u32 b0) {
  asm("mma.sync.aligned.m16n8k8.row.col.f32.bf16.bf16.f32 {%0,%1,%2,%3},{%4,%5},{%6},{%0,%1,%2,%3};"
      : "+f"(c[0]), "+f"(c[1]), "+f"(c[2]), "+f"(c[3]) : "r"(a0), "r"(a1), "r"(b0));
}
DEV void mma8_hf(float (&c)[4], u32 a0, u32 a1, u32 b0) {
  asm("mma.sync.aligned.m16n8k8.row.col.f32.f16.f16.f32 {%0,%1,%2,%3},{%4,%5},{%6},{%0,%1,%2,%3};"
      : "+f"(c[0]), "+f"(c[1]), "+f"(c[2]), "+f"(c[3]) : "r"(a0), "r"(a1), "r"(b0));
}
DEV u32 movm(u32 x) { u32 r; asm("movmatrix.sync.aligned.m8n8.trans.b16 %0,%1;" : "=r"(r) : "r"(x)); return r; }
DEV uint4 ldsm4(u32 a) { uint4 r; asm volatile("ldmatrix.sync.aligned.m8n8.x4.shared.b16 {%0,%1,%2,%3},[%4];" : "=r"(r.x), "=r"(r.y), "=r"(r.z), "=r"(r.w) : "r"(a)); return r; }
DEV uint4 ldsm4t(u32 a) { uint4 r; asm volatile("ldmatrix.sync.aligned.m8n8.x4.trans.shared.b16 {%0,%1,%2,%3},[%4];" : "=r"(r.x), "=r"(r.y), "=r"(r.z), "=r"(r.w) : "r"(a)); return r; }
DEV u32 lds32(u32 a) { u32 r; asm volatile("ld.volatile.shared.u32 %0,[%1];" : "=r"(r) : "r"(a)); return r; }
DEV uint2 lds64(u32 a) { uint2 r; asm volatile("ld.shared.v2.u32 {%0,%1},[%2];" : "=r"(r.x), "=r"(r.y) : "r"(a)); return r; }
DEV uint4 lds128(u32 a) { uint4 r; asm volatile("ld.shared.v4.u32 {%0,%1,%2,%3},[%4];" : "=r"(r.x), "=r"(r.y), "=r"(r.z), "=r"(r.w) : "r"(a)); return r; }
DEV void sts16(u32 a, u32 v) { asm volatile("st.shared.u16 [%0],%1;" ::"r"(a), "h"((unsigned short)v) : "memory"); }
DEV void sts32(u32 a, u32 v) { asm volatile("st.shared.u32 [%0],%1;" ::"r"(a), "r"(v) : "memory"); }
DEV void sts64(u32 a, u32 x, u32 y) { asm volatile("st.shared.v2.u32 [%0],{%1,%2};" ::"r"(a), "r"(x), "r"(y) : "memory"); }
DEV void sts128(u32 a, u32 x, u32 y, u32 z, u32 w) { asm volatile("st.shared.v4.u32 [%0],{%1,%2,%3,%4};" ::"r"(a), "r"(x), "r"(y), "r"(z), "r"(w) : "memory"); }
DEV uint4 ldr128(const void* p) { uint4 v; asm volatile("ld.relaxed.gpu.global.v4.u32 {%0,%1,%2,%3},[%4];" : "=r"(v.x), "=r"(v.y), "=r"(v.z), "=r"(v.w) : "l"(p) : "memory"); return v; }
DEV uint2 ldr64(const void* p) { uint2 v; asm volatile("ld.relaxed.gpu.global.v2.u32 {%0,%1},[%2];" : "=r"(v.x), "=r"(v.y) : "l"(p) : "memory"); return v; }
DEV u32 ldr32(const void* p) { u32 v; asm volatile("ld.relaxed.gpu.global.u32 %0,[%1];" : "=r"(v) : "l"(p) : "memory"); return v; }
DEV void str128(void* p, u32 x, u32 y, u32 z, u32 w) { asm volatile("st.relaxed.gpu.global.v4.u32 [%0],{%1,%2,%3,%4};" ::"l"(p), "r"(x), "r"(y), "r"(z), "r"(w) : "memory"); }
DEV void str64(void* p, u32 x, u32 y) { asm volatile("st.relaxed.gpu.global.v2.u32 [%0],{%1,%2};" ::"l"(p), "r"(x), "r"(y) : "memory"); }
DEV void str32(void* p, u32 x) { asm volatile("st.relaxed.gpu.global.u32 [%0],%1;" ::"l"(p), "r"(x) : "memory"); }
DEV void str16(void* p, u32 x) { asm volatile("st.relaxed.gpu.global.u16 [%0],%1;" ::"l"(p), "h"((unsigned short)x) : "memory"); }
DEV uint4 ldg128(const void* p) { uint4 v; asm volatile("ld.global.nc.v4.u32 {%0,%1,%2,%3},[%4];" : "=r"(v.x), "=r"(v.y), "=r"(v.z), "=r"(v.w) : "l"(p)); return v; }
DEV uint2 ldg64(const void* p) { uint2 v; asm volatile("ld.global.nc.v2.u32 {%0,%1},[%2];" : "=r"(v.x), "=r"(v.y) : "l"(p)); return v; }
DEV u32 ldg32(const void* p) { u32 v; asm volatile("ld.global.nc.u32 %0,[%1];" : "=r"(v) : "l"(p)); return v; }
DEV u32 ldg16(const void* p) { unsigned short v; asm volatile("ld.global.nc.u16 %0,[%1];" : "=h"(v) : "l"(p)); return v; }
#define bsync(id, n) asm volatile("bar.sync %0,%1;" ::"n"(id), "n"(n) : "memory")
#define barrive(id, n) asm volatile("bar.arrive %0,%1;" ::"n"(id), "n"(n) : "memory")
DEV void mb_init(u32 a) { asm volatile("mbarrier.init.shared.b64 [%0],1;" ::"r"(a) : "memory"); }
DEV void mb_expect(u32 a, u32 bytes) { asm volatile("mbarrier.arrive.expect_tx.shared.b64 _,[%0],%1;" ::"r"(a), "r"(bytes) : "memory"); }
DEV void mb_wait(u32 a, u32 ph = 0) {
  u32 ok; int it = 0;
  do { asm volatile("{.reg .pred p; mbarrier.try_wait.parity.shared.b64 p,[%1],%2; selp.u32 %0,1,0,p;}" : "=r"(ok) : "r"(a), "r"(ph) : "memory"); } while (!ok && ++it < SPIN);
}
template <int N> DEV void bulk_out(void* dst, u32 src) { asm volatile("cp.async.bulk.global.shared::cta.bulk_group [%0],[%1],%2;" ::"l"(dst), "r"(src), "n"(N) : "memory"); }
constexpr u32 WSH = 41472;
template <int N> DEV void l2_pre(const void* p) { asm volatile("cp.async.bulk.prefetch.L2.global [%0],%1;" ::"l"(p), "n"(N) : "memory"); }
DEV void tma3d(u32 dst, const CUtensorMap* tm, u32 mb, int c0, int c2) {
  asm volatile("cp.async.bulk.tensor.3d.shared::cluster.global.mbarrier::complete_tx::bytes [%0],[%1,{%3,0,%4}],[%2];"
               ::"r"(dst), "l"((uint64_t)tm), "r"(mb), "r"(c0), "r"(c2) : "memory");
}
DEV float blo(u32 w) { return __uint_as_float(w << 16); }
DEV float bhi(u32 w) { return __uint_as_float(w & 0xffff0000u); }
DEV u32 pk_bf(float lo, float hi) { u32 r; asm("cvt.rn.bf16x2.f32 %0,%1,%2;" : "=r"(r) : "f"(hi), "f"(lo)); return r; }
DEV u32 pk_hf(float lo, float hi) { u32 r; asm("cvt.rn.f16x2.f32 %0,%1,%2;" : "=r"(r) : "f"(hi), "f"(lo)); return r; }
DEV float rbf(float x) { return __uint_as_float(pk_bf(0.f, x) & 0xffff0000u); }
DEV u32 bfma(u32 a, u32 b, u32 c) { u32 r; asm("fma.rn.bf16x2 %0,%1,%2,%3;" : "=r"(r) : "r"(a), "r"(b), "r"(c)); return r; }
DEV u32 bmul(u32 a, u32 b) { u32 r; asm("mul.rn.bf16x2 %0,%1,%2;" : "=r"(r) : "r"(a), "r"(b)); return r; }
DEV u32 badd(u32 a, u32 b) { u32 r; asm("add.rn.bf16x2 %0,%1,%2;" : "=r"(r) : "r"(a), "r"(b)); return r; }
DEV u32 hadd(u32 a, u32 b) { u32 r; asm("add.rn.f16x2 %0,%1,%2;" : "=r"(r) : "r"(a), "r"(b)); return r; }
DEV u32 hfma(u32 a, u32 b, u32 c) { u32 r; asm("fma.rn.f16x2 %0,%1,%2,%3;" : "=r"(r) : "r"(a), "r"(b), "r"(c)); return r; }
struct C2 { u32 re, im; };
DEV C2 cm2(C2 a, C2 b) {
  const __half2 ar = *reinterpret_cast<__half2*>(&a.re), ai = *reinterpret_cast<__half2*>(&a.im), br = *reinterpret_cast<__half2*>(&b.re), bi = *reinterpret_cast<__half2*>(&b.im);
  __half2 re = __hfma2(ar, br, __hneg2(__hmul2(ai, bi))), im = __hfma2(ar, bi, __hmul2(ai, br));
  return {*reinterpret_cast<u32*>(&re), *reinterpret_cast<u32*>(&im)};
}
DEV C2 pk2(const float2 (&a)[2]) { return {pk_hf(a[0].x, a[1].x), pk_hf(a[0].y, a[1].y)}; }
DEV C2 pk2c(const float2 (&a)[2]) { return {pk_hf(a[0].x, a[1].x), pk_hf(-a[0].y, -a[1].y)}; }
DEV u32 cpy(u32 x, u32 zr, int alt) {
  u32 r;
  if (alt) asm volatile("xor.b32 %0,%1,%2;" : "=r"(r) : "r"(x), "r"(zr)); else asm volatile("mad.lo.u32 %0,%2,%2,%1;" : "=r"(r) : "r"(x), "r"(zr));
  return r;
}
DEV u32 opq(u32 x) { u32 r; asm volatile("mov.u32 %0,%1;" : "=r"(r) : "r"(x)); return r; }
DEV u32 row16(u32 lane) { const u32 r0 = (lane & 7) + ((lane >> 3) & 1) + 8 * (lane >> 4) - 1; return (r0 ^ ((r0 >> 3) & 3)) * 16; }
DEV u32 clk() { u32 r; asm volatile("mov.u32 %0,%%clock;" : "=r"(r)::"memory"); return r; }
DEV float ex2(float x) { float r; asm("ex2.approx.ftz.f32 %0,%1;" : "=f"(r) : "f"(x)); return r; }
DEV float rcpf(float x) { float r; asm("rcp.approx.ftz.f32 %0,%1;" : "=f"(r) : "f"(x)); return r; }
DEV float2 cmul(float2 a, float2 b) { return make_float2(fmaf(a.x, b.x, -a.y * b.y), fmaf(a.x, b.y, a.y * b.x)); }
DEV float2 csq(float2 a) { return make_float2(fmaf(a.x, a.x, -a.y * a.y), (a.x + a.x) * a.y); }
DEV float2 cexp(float lr2, float th) {
  const float m = ex2(lr2);
  return make_float2(m * __cosf(th), m * __sinf(th));
}
DEV float silu_f(float v) { return v * rcpf(1.f + ex2(-1.4426950408889634f * v)); }
constexpr u32 B2P64 = 0x5F805F80u, B2M64 = 0x1F801F80u, BONE = 0x3F803F80u;
constexpr u32 MODJ = 18 * 128;
DEV float sqrta(float x) { float r; asm("sqrt.approx.ftz.f32 %0,%1;" : "=f"(r) : "f"(x)); return r; }
DEV u32 fu(float x) { return __float_as_uint(x); }
DEV float uf(u32 x) { return __uint_as_float(x); }
DEV void mma_hf_o(float (&d)[4], const float (&c)[4], const u32 (&a)[4], u32 b0, u32 b1) {
  asm("mma.sync.aligned.m16n8k16.row.col.f32.f16.f16.f32 {%0,%1,%2,%3},{%4,%5,%6,%7},{%8,%9},{%10,%11,%12,%13};"
      : "=f"(d[0]), "=f"(d[1]), "=f"(d[2]), "=f"(d[3]) : "r"(a[0]), "r"(a[1]), "r"(a[2]), "r"(a[3]), "r"(b0), "r"(b1), "f"(c[0]), "f"(c[1]), "f"(c[2]), "f"(c[3]));
}

DEV void mma_hf_t(float (&c)[4], const u32 (&a)[4], u32 b0, u32 b1) { mma_hf(c, a[0], a[1], a[2], a[3], b0, b1); }
DEV void cpa16(u32 dst, const void* src) { asm volatile("cp.async.cg.shared.global [%0],[%1],16;" ::"r"(dst), "l"(src) : "memory"); }
DEV void tm_pre(const CUtensorMap* tm) { asm volatile("prefetch.tensormap [%0];" ::"l"((uint64_t)tm) : "memory"); }
#define PROXY_FENCE() asm volatile("fence.proxy.async.shared::cta;" ::: "memory")
struct Prm {
  const char *la, *ai, *cr, *ci, *ldt;
  u32 zero;
  const char *x, *c;
  char* gs;
  const char *dsk, *wr, *wg, *wu, *wd;
  char* out;
};
constexpr float LOG2E = 1.4426950408889634f, F2P64 = 1.8446744073709552e19f, F2M64 = 5.421010862427522e-20f;

DEV void y_store(float c0, float c1, float c2, float c3, u32 F, u32 pml, char* yp) {
  str32(yp, bmul(pk_bf(c0, c2), F) | pml);
  str32(yp + BLK, bmul(pk_bf(c1, c3), F) | pml);
}
#define POLL(load, cond_bad, code) { int it_ = 0; do { load; if (++it_ > SPIN) { ERRF(code); break; } } while (__any_sync(~0u, (cond_bad))); }
#define POLLW(load, cond_bad, code) { int it_ = 0; while (__any_sync(~0u, (cond_bad))) { if (++it_ > SPIN) { ERRF(code); break; } load; } }

DEV void post_conv(const Prm& p, const CUtensorMap* tm_down, const u32 tid, const u32 b, const u32 ep) {
  const u32 w = tid >> 5, lane = tid & 31;
  const u32 g = lane >> 2, q = lane & 3, e = g >> 2, h = (g >> 1) & 1, hi = g & 1;
  const u32 rho = b & 1, par = (ep + 1) & 1, pm = par ? TAGM : 0;
  char* const gs = p.gs;
  const u32 cho = 128 * w + 64 * e + 16 * q;
  u32 x1[4][4], h2[4][4], key[4], lt;
  char* const rowp = gs + (b * BLK + (4 * h + 8 * hi) * 1152 + cho);
  if (w < 9) {
    const char* ysrc = gs + (G_Y + b * BLK + w * 2048 + (q >> 1) * 1024 + (g >> 1) * 256 + hi * 32 + (q & 1) * 16);
    uint4 yv[4];
    if (w < 4) {
#pragma unroll
      for (int v = 0; v < 4; v++) yv[v] = ldr128(ysrc + 64 * v);
    } else {
#pragma unroll
      for (int v = 0; v < 4; v++) yv[v].x = INVAL;
    }
    const u32 ma = SM_MODS + cho, xa = SM_XST + (2 * h + 4 * hi) * ROW + cho;
    const uint4 sa = lds128(ma), ca = lds128(ma + 1152), ga = lds128(ma + 2304), dk = lds128(ma + 6912);
    const uint4 rb = lds128((g & 2) ? SM_ONE + 16 * hi : (ma ^ 64) + 8064 + 1152 * hi);
    const u32 saw[4] = {sa.x, sa.y, sa.z, sa.w}, caw[4] = {ca.x, ca.y, ca.z, ca.w}, gaw[4] = {ga.x, ga.y, ga.z, ga.w}, dw[4] = {dk.x, dk.y, dk.z, dk.w};
    u32 hD[4][4];
#pragma unroll
    for (int k = 0; k < 4; k++) {
      const uint4 st = lds128(SM_ST + 16 * (2 * h + 4 * hi + (k & 1) + 8 * (k >> 1))), xv = lds128(xa + ((k & 1) + 8 * (k >> 1)) * ROW);
      x1[k][0] = xv.x; x1[k][1] = xv.y; x1[k][2] = xv.z; x1[k][3] = xv.w;
#pragma unroll
      for (int v = 0; v < 4; v++) {
        const u32 d = badd(x1[k][v], st.x), z = bfma(d, st.y, bmul(d, st.z));
        hD[k][v] = bmul(badd(bmul(z, caw[v]), saw[v]), dw[v]);
      }
    }
    const bool own = (q >> 1) == e;
    const u32 spw = SM_SP + (2 * w + e) * 320 + (g & 3) * 16 + (own ? ((q & 1) == h ? 4 : 12) : 8 - 8 * (q & 1));
    TS(18);
    if (w >= 4) bsync(12, 288);
    POLLW(_Pragma("unroll") for (int v = 0; v < 4; v++) if ((yv[v].x ^ pm) & TAGM) yv[v] = ldr128(ysrc + 64 * v),
          ((yv[0].x ^ pm) | (yv[1].x ^ pm) | (yv[2].x ^ pm) | (yv[3].x ^ pm)) & TAGM, 5);
    TS(19);
#pragma unroll
    for (int k = 0; k < 4; k += 2) {
      float X[4] = {}, Y[4] = {}, R[4] = {};
#pragma unroll
      for (int v = 0; v < 4; v++) {
        const u32 y0 = k ? yv[v].z : yv[v].x & ~TAGM, y1 = k ? yv[v].w : yv[v].y;
        x1[k][v] = badd(x1[k][v], bmul(gaw[v], bfma(movm(y0), B2P64, hD[k][v])));
        x1[k + 1][v] = badd(x1[k + 1][v], bmul(gaw[v], bfma(movm(y1), B2P64, hD[k + 1][v])));
        mma8_bf(X, x1[k][v], x1[k + 1][v], x1[k][v]); mma8_bf(Y, x1[k][v], x1[k + 1][v], x1[k + 1][v]);
        if (v & 1) mma_bf(R, x1[k][v - 1], x1[k + 1][v - 1], x1[k][v], x1[k + 1][v], v & 2 ? rb.z : rb.x, v & 2 ? rb.w : rb.y);
      }
      sts32(spw + k * 64, fu(own ? (hi ? X[1] : X[0]) : R[0] + R[1]));
      sts32(spw + k * 64 + 64, fu(own ? (hi ? Y[3] : Y[2]) : R[2] + R[3]));
    }
    barrive(1, 320);
    TS(36);
    const uint4 sb = lds128(ma + 3456), cb = lds128(ma + 4608), gb = lds128(ma + 5760);
    const u32 sbw[4] = {sb.x, sb.y, sb.z, sb.w}, cbw[4] = {cb.x, cb.y, cb.z, cb.w}, gbw[4] = {gb.x, gb.y, gb.z, gb.w};
    bsync(2, 320);
    TS(37);
    lt = lds32(SM_THR + 36);
#pragma unroll
    for (int k = 0; k < 4; k++) {
      const uint4 st = lds128(SM_ST2 + 64 * k + 16 * (g & 3));
      key[k] = st.w;
      u32 o[4];
#pragma unroll
      for (int v = 0; v < 4; v++) {
        const u32 d = badd(x1[k][v], st.x), z = bfma(d, st.y, bmul(d, st.z));
        h2[k][v] = badd(bmul(z, cbw[v]), sbw[v]);
        o[v] = badd(x1[k][v], bmul(gbw[v], h2[k][v]));
      }
      h2[k][0] = bmul(h2[k][0], B2M64) | TAGR;
      if (key[k] >= lt) str128(rowp + k * 1152, h2[k][0], h2[k][1], h2[k][2], h2[k][3]);
      sts128(xa + ((k & 1) + 8 * (k >> 1)) * ROW, o[0], o[1], o[2], o[3]);
    }
    barrive(3, 320);
    TS(21);
  } else if (w == 10) {
    uint2 rc = lds64(SM_RC + 8 * min(lane, 17u));
    float r1 = lane < 18 ? uf(rc.x) : 0.f, r2 = lane < 18 ? uf(rc.y) : 0.f;
#pragma unroll 1
    for (int o = 16; o; o >>= 1) { r1 += __shfl_xor_sync(~0u, r1, o); r2 += __shfl_xor_sync(~0u, r2, o); }
    const u32 tl = 4 * ((lane >> 1) & 1) + ((lane >> 2) & 3) + 8 * (lane & 1), kl = (2047 - 16 * b - tl) << 2 | par * 3;
    const u32 row = SM_XST + ((lane & 2) + 4 * (lane & 1) + ((lane >> 2) & 1) + (lane & 8)) * ROW;
    char* const op = p.out + (b * BLK + tl * 1152);
    const u32 spr = SM_SP + (lane >> 4) * 9 * 320 + (lane & 15) * 16;
    TS(31);
    bsync(1, 320);
    barrive(7, 64);
    float S1 = 0.f, S2 = 0.f, S3 = 0.f;
#pragma unroll
    for (int i = 0; i < 9; i++) { uint4 t = lds128(spr + i * 320); S1 += uf(t.x); S2 += uf(t.y); S3 += uf(t.z); }
    S1 += __shfl_xor_sync(~0u, S1, 16); S2 += __shfl_xor_sync(~0u, S2, 16); S3 += __shfl_xor_sync(~0u, S3, 16);
    const float mu = S1 * (1.f / 576.f), var = fmaxf(fmaf(-mu, mu, S2 * (1.f / 576.f)), 0.f);
    const float m = rbf(mu), rs = rcpf(rbf(sqrta(rbf(rbf(var) + 1e-5f))));
    const u32 rb = pk_bf(0.f, fmaf(fmaf(-m, r1, S3), rs, r2) + 0.f);
    const u32 ok = ((rb ^ (((int)rb >> 31) | 0x80000000)) & 0xffff0000u) | kl;
    if (lane < 16) str32(gs + (G_KEY + b * 128 + 4 * lane), ok);
    TS(20);
    const float rh = rbf(rs);
    sts128(SM_ST2 + 16 * (lane & 15), pk_bf(-m, -m), pk_bf(rh, rh), pk_bf(rs - rh, rs - rh), ok);
    sts32(SM_KEY + 4 * (lane & 15), ok);
    __syncwarp();
    const uint4 o0 = lds128(SM_KEY + 2 * (lane & 16)), o1 = lds128(SM_KEY + 2 * (lane & 16) + 16);
    u32 lr = (o0.x > ok) + (o0.y > ok) + (o0.z > ok) + (o0.w > ok) + (o1.x > ok) + (o1.y > ok) + (o1.z > ok) + (o1.w > ok);
    lr += __shfl_xor_sync(~0u, lr, 16);
    if (lr == NEARLY - 1) sts32(SM_THR + 36, ok);
    barrive(2, 320);
    bsync(3, 320);
    PROXY_FENCE();
    if (lane < 16 && lr >= 8) bulk_out<1152>(op, row);
    bsync(6, 320);
    if (lane < 16 && lr < 8 && ok < lds32(SM_SLOT + 28)) bulk_out<1152>(op, row);
    asm volatile("cp.async.bulk.commit_group;" ::: "memory");
  }
  uint4 rv[3];
  const char* rs_;
  if (w < 8) {
    const char* ks = gs + (G_KEY + (8 * g + w) * 128 + q * 16);
    const u32 kt = par * 3;
    uint4 ka, kc;
    POLL({ ka = ldr128(ks); kc = ldr128(ks + 8192); }, ((ka.x ^ kt) | (kc.x ^ kt)) & 3, 6);
    TS(23);
    const u32 kk[8] = {ka.x, ka.y, ka.z, ka.w, kc.x, kc.y, kc.z, kc.w};
    u32 mx = max(max(max(kk[0], kk[1]), max(kk[2], kk[3])), max(max(kk[4], kk[5]), max(kk[6], kk[7])));
#pragma unroll
    for (int o = 4; o < 32; o *= 2) mx = max(mx, __shfl_xor_sync(~0u, mx, o));
    if (lane < 4) asm volatile("red.shared.max.u32 [%0],%1;" ::"r"(SM_THR + 16 * (w & 1) + 4 * lane), "r"(mx) : "memory");
    bsync(4, 256);
    TS(33);
    const uint4 t0 = lds128(SM_THR), t1 = lds128(SM_THR + 16);
    u32 L0 = min(min(min(t0.x, t0.y), min(t0.z, t0.w)), min(min(t1.x, t1.y), min(t1.z, t1.w)));
#pragma unroll 1
    for (int it = 0; it < 128; it++) {
      u32 c = 0;
#pragma unroll
      for (int j = 0; j < 8; j++) c += kk[j] >= L0 ? 4 : 0;
      if (c) {
        u32 a;
        asm volatile("atom.shared.add.u32 %0,[%1],%2;" : "=r"(a) : "r"(SM_THR + 32), "r"(c) : "memory");
#pragma unroll
        for (int j = 0; j < 8; j++) if (kk[j] >= L0) { sts32(SM_LIST + a, kk[j]); a += 4; }
      }
      bsync(5, 256);
      TS(38);
      const u32 n = lds32(SM_THR + 32), m0 = lds32(SM_LIST + 4 * lane), my = 4 * lane < n ? m0 : 0;
      const uint4 cd = lds128(SM_LIST + 16 * w);
      const u32 cc[4] = {cd.x, cd.y, cd.z, cd.w};
#pragma unroll
      for (int j = 0; j < 4; j++) {
        const u32 r = __popc(__ballot_sync(~0u, my > cc[j]));
        if (r < 8 && 16 * w + 4 * j < n) sts32(SM_SLOT + 4 * r, cc[j]);
      }
      if (n <= 128) break;
      bsync(15, 256);
      L0 = lds32(SM_SLOT + 28);
      sts32(SM_THR + 32, 0);
      bsync(15, 256);
    }
  }
  if (w < 9) {
    bsync(6, 320);
    TS(24);
    const u32 g8 = lds32(SM_SLOT + 28);
    if (w < 8) {
      rs_ = gs + ((2047 - ((lds32(SM_SLOT + 4 * w) >> 2) & 2047)) * 1152 + lane * 16);
      rv[0] = ldr128(rs_); rv[1] = ldr128(rs_ + 512);
      rv[2].x = TAGR;
      if (lane < 8) rv[2] = ldr128(rs_ + 1024);
    }
    if (__any_sync(~0u, max(max(key[0], key[1]), max(key[2], key[3])) >= g8)) {
#pragma unroll
      for (int k = 0; k < 4; k++) if (key[k] >= g8) {
        if (key[k] < lt) str128(rowp + k * 1152, h2[k][0], h2[k][1], h2[k][2], h2[k][3]);
        str128(rowp + (G_Y + k * 1152), bmul(x1[k][0], B2M64) | TAGR, x1[k][1], x1[k][2], x1[k][3]);
      }
    }
  }
  asm volatile("setmaxnreg.inc.sync.aligned.u32 168;");
  const u32 kq = w & 3, tg = 2 - (w >> 2);
  uint4 A[24];
  {
    const u32 row = 144 * kq + 8 * (lane >> 4) + (lane & 7), ab = (lane & 8) ? SM_UP : SM_GATE;
    mb_wait(SM_MB + 8); mb_wait(SM_MB + 16);
    if (tg < 2) {
      const u32 aa = ab + row * 64 + (((2 * tg) ^ ((lane & 7) >> 1)) << 4);
#pragma unroll
      for (int s = 0; s < 9; s++) { A[s] = ldsm4t(aa + s * 1024); A[9 + s] = ldsm4t((aa ^ 16) + s * 1024); }
    } else {
#pragma unroll
      for (int s = 0; s < 9; s++) A[s] = ldsm4t(ab + SLV + row * 16 + s * 256);
    }
  }
  TS(22);
  if (w == 9) {
    bsync(7, 64);
    if (lane == 0 && b < 108) {
      PROXY_FENCE();
#pragma unroll 1
      for (int i = 0; i < 4; i++) {
        if (i) mb_wait(SM_MB + 24, ~i & 1);
        mb_expect(SM_MB + 24, 12288);
        tma3d(SM_WD + 12288 * i, tm_down, SM_MB + 24, 64 * (b % 9), 4 * (b / 9) + i);
      }
    }
    __syncwarp();
    TS(13);
  }
  if (w < 8) {
    POLLW({ rv[0] = ldr128(rs_); rv[1] = ldr128(rs_ + 512); if (lane < 8) rv[2] = ldr128(rs_ + 1024); },
          ((rv[0].x ^ TAGR) | (rv[1].x ^ TAGR) | (rv[2].x ^ TAGR)) & TAGM, 8);
#pragma unroll
    for (int j = 0; j < 3; j++) if (j < 2 || lane < 8) sts128(SM_XS + w * ROW + lane * 16 + j * 512, bmul(rv[j].x ^ TAGR, B2P64), rv[j].y, rv[j].z, rv[j].w);
  }
  __syncthreads();
  TS(25);
  {
    float c0[2][4] = {}, c1[2][4] = {};
    const u32 ba = SM_XS + (lane & 7) * ROW + (18 * kq + (lane >> 3)) * 16;
    uint4 bb[5];
#pragma unroll
    for (int s = 0; s < 5; s++) bb[s] = ldsm4(ba + s * 64);
#pragma unroll
    for (int s = 0; s < 9; s++) mma_bf(c0[s & 1], A[s].x, A[s].y, A[s].z, A[s].w, s & 1 ? bb[s >> 1].z : bb[s >> 1].x, s & 1 ? bb[s >> 1].w : bb[s >> 1].y);
    const u32 ra = SM_RED + (8 * tg + kq) * 512 + lane * 16;
    if (tg < 2) {
#pragma unroll
      for (int s = 0; s < 9; s++) mma_bf(c1[s & 1], A[9 + s].x, A[9 + s].y, A[9 + s].z, A[9 + s].w, s & 1 ? bb[s >> 1].z : bb[s >> 1].x, s & 1 ? bb[s >> 1].w : bb[s >> 1].y);
      sts128(ra + 2048, fu(c1[0][0] + c1[1][0]), fu(c1[0][1] + c1[1][1]), fu(c1[0][2] + c1[1][2]), fu(c1[0][3] + c1[1][3]));
    }
    sts128(ra, fu(c0[0][0] + c0[1][0]), fu(c0[0][1] + c0[1][1]), fu(c0[0][2] + c0[1][2]), fu(c0[0][3] + c0[1][3]));
  }
  TS(39);
  __syncthreads();
  if (w >= 7 + rho) {
    const u32 t = 11 - w;
    float s[4] = {};
#pragma unroll
    for (int i = 0; i < 4; i++) { const uint4 u = lds128(SM_RED + (t * 4 + i) * 512 + lane * 16); s[0] += uf(u.x); s[1] += uf(u.y); s[2] += uf(u.z); s[3] += uf(u.w); }
    const u32 sg = pk_bf(silu_f(rbf(s[0])), silu_f(rbf(s[1])));
    const u32 act = movm(bmul(bmul(sg, pk_bf(s[2], s[3])), B2M64));
    str32(gs + (G_ACT + (t < 4 ? 4 * b + t : 512 + (b >> 1)) * 128 + lane * 4), act | (q ? 0 : pm));
  }
  TS(26);
  if (b < 108) {
    const char* src = gs + (G_ACT + (b / 9) * 6144 + tid * 16);
    uint4 a = ldr128(src);
    if (w < 4) {
      const u32 aa = SM_WD + (8 * (lane >> 4) + (lane & 7)) * 128 + (((2 * w + ((lane >> 3) & 1)) ^ (lane & 7)) << 4);
      mb_wait(SM_MB + 24, 1);
#pragma unroll
      for (int s = 0; s < 24; s++) A[s] = ldsm4t(aa + s * 2048);
    }
    TS(28);
    POLLW(a = ldr128(src), (a.x ^ pm) & TAGM, 9);
    sts128(SM_AC + tid * 16, a.x & ~TAGM, a.y, a.z, a.w);
    TS(27);
    if (w < 4) {
      bsync(8, 384);
      float c[4][4] = {};
#pragma unroll
      for (int s = 0; s < 12; s++) {
        const uint4 bb = ldsm4(SM_AC + lane * 16 + s * 512);
        mma_bf(c[2 * (s & 1)], A[2 * s].x, A[2 * s].y, A[2 * s].z, A[2 * s].w, bb.x, bb.y);
        mma_bf(c[2 * (s & 1) + 1], A[2 * s + 1].x, A[2 * s + 1].y, A[2 * s + 1].z, A[2 * s + 1].w, bb.z, bb.w);
      }
      char* dst = gs + (G_PART + b * 2048 + w * 512 + lane * 8);
      u32 o[4];
#pragma unroll
      for (int i = 0; i < 4; i++) o[i] = (fu(((c[0][i] + c[1][i]) + (c[2][i] + c[3][i])) * F2P64) & ~1u) | par;
      str64(dst, o[0], o[1]); str64(dst + 256, o[2], o[3]);
      TS(29);
    } else barrive(8, 384);
  }
  if (w == 8 && b < 72) {
    const u32 kg = lds32(SM_SLOT + 4 * g), ro = (2047 - ((kg >> 2) & 2047)) * 1152 + 16 * b;
    const char* src = gs + (G_PART + (b >> 3) * 2048 + (b & 7) * 256 + lane * 8);
    const char* xs = gs + (G_Y + ro);
    uint4 xt;
    POLL(xt = ldr128(xs), (xt.x ^ TAGR) & TAGM, 10);
    const u32 x1w = (q & 2) ? ((q & 1) ? xt.w : xt.z) : ((q & 1) ? xt.y : bmul(xt.x ^ TAGR, B2P64));
    const u32 gw = lds32(SM_MODS + 5760 + 16 * b + 4 * q);
    const u32 hw = lds32(SM_XS + g * ROW + b * 16 + q * 4);
    const float sgm = rcpf(1.f + ex2(-LOG2E * bhi(kg ^ (~((int)kg >> 31) | 0x80000000))));
    char* const dst = p.out + (ro + 4 * q);
    uint2 v[12];
#pragma unroll
    for (int j = 0; j < 12; j++) v[j] = make_uint2(1, 0);
    u32 bad;
    POLL({ bad = 0; _Pragma("unroll") for (int j = 0; j < 12; j++) { if (((v[j].x ^ par) | (v[j].y ^ par)) & 1) v[j] = ldr64(src + j * 9 * 2048); }
           _Pragma("unroll") for (int j = 0; j < 12; j++) bad |= (v[j].x ^ par) | (v[j].y ^ par); }, bad & 1, 11);
    float s0[4] = {}, s1[4] = {};
#pragma unroll
    for (int j = 0; j < 12; j++) { s0[j & 3] += uf(v[j].x); s1[j & 3] += uf(v[j].y); }
    const u32 y = movm(pk_bf((s0[0] + s0[1]) + (s0[2] + s0[3]), (s1[0] + s1[1]) + (s1[2] + s1[3])));
    *(u32*)dst = badd(x1w, bmul(gw, badd(hw, bmul(y, pk_bf(sgm, sgm)))));
    if (b == 0 && lane == 0) str32(gs + G_EP, ep + 1);
    TS(30); TSE();
  }
  if (w == 10) asm volatile("cp.async.bulk.wait_group.read 0;" ::: "memory");
}

__global__ void __launch_bounds__(384, 1)
fused_kernel(const Prm p, const __grid_constant__ CUtensorMap tm_mod, const __grid_constant__ CUtensorMap tm_gate, const __grid_constant__ CUtensorMap tm_gs,
             const __grid_constant__ CUtensorMap tm_up, const __grid_constant__ CUtensorMap tm_us, const __grid_constant__ CUtensorMap tm_down) {
  extern __shared__ __align__(1024) unsigned char smem[];
  u32 la, ai, ldt; uint2 cr, ci;
  {
    const u32 t = threadIdx.x, d = t < 256 ? 4 * blockIdx.x + ((t >> 5) & 3) : 512 + (blockIdx.x >> 1), o = d * 256 + 8 * (t & 31), o4 = o + ((t < 256 ? t >> 5 : t >> 3) & 4);
    asm volatile("{.reg .pred p; .reg .u16 h; setp.ne.u32 p,%7,0; @p ld.global.nc.u32 %0,[%8]; @p ld.global.nc.u32 %1,[%9]; @p ld.global.nc.v2.u32 {%2,%3},[%10];"
                 "@p ld.global.nc.v2.u32 {%4,%5},[%11]; @p ld.global.nc.u16 h,[%12]; cvt.u32.u16 %6,h;}"
                 : "=r"(la), "=r"(ai), "=r"(cr.x), "=r"(cr.y), "=r"(ci.x), "=r"(ci.y), "=r"(ldt)
                 : "r"(0x6ffu >> (t >> 5) & 1), "l"(p.la + o4), "l"(p.ai + o4), "l"(p.cr + o), "l"(p.ci + o), "l"(p.ldt + 2 * d));
  }
  const u32 t0 = clk();
  const u32 tid = __shfl_sync(~0u, threadIdx.x, threadIdx.x & 31), b = blockIdx.x + p.zero;
  const u32 w = tid >> 5, lane = tid & 31;
  const u32 g = lane >> 2, q = lane & 3, hi = g & 1;
  const u32 rho = b & 1, Ps = 512 + (b >> 1);
  char* const gs = p.gs;
  TS0();
  const bool kw = w != 8 && w != 11;
  const u32 ksig = w < 8 ? (w & 3) : 4, khf = w < 8 ? (w >> 2) : (w & 1);
  if (!kw) {
    if (tid == 352) {
#pragma unroll
      for (int i = 0; i < 4; i++) mb_init(SM_MB + 8 * i);
      asm volatile("fence.mbarrier_init.release.cluster;" ::: "memory");
      tm_pre(&tm_mod);
    }
    const char* cp = p.c + (576 * (w & 1) + 24 * min(lane, 23u));
    const uint2 c0 = ldg64(cp);
    la = c0.x; ai = c0.y; cr = ldg64(cp + 8); ci = ldg64(cp + 16);
  }
  const u32 zr = tid >> 16;
  const u32 epv = ldr32(gs + (G_EP + zr));
  const u32 tp = SM_TAP + ksig * TAPS;
  if (kw && !khf) {
#pragma unroll 1
    for (u32 i = lane * 16; i < TAPS; i += 512) sts128(tp + i, 0, 0, 0, 0);
  }
  if (tid >= 252) str128(gs + (tid >= 380 ? G_MOD + b * 128 + q * 16 : b * BLK + 16384 - 252 * 16 + tid * 16), INVAL, 0, 1, 0);
  if (tid == 352 && b < 36) { while (clk() - t0 < DMOD); mb_expect(SM_MB, 36864); tma3d(SM_UP, &tm_mod, SM_MB, 32 * b, 0); }
  if (w < 9) {
    while ((int)(clk() - t0) < DX);
    const char* xp = p.x + (b * BLK + (lane >> 3) * 1152 + 128 * w + 16 * (lane & 7));
    const u32 xd = SM_XST + (((lane >> 3) & 1) + 8 * (lane >> 4)) * ROW + 128 * w + 16 * (lane & 7);
#pragma unroll
    for (int i = 0; i < 4; i++) cpa16(xd + 2 * ROW * i, xp + 4608 * i);
  }
  const u32 ktab = w < 8 ? SM_MODS + w * KTAB : SM_ZS + (w - 9) * KTAB;
  float k2048 = 0.f;
  if (kw) {
    u32 mx = __vmaxu2(__vmaxu2(cr.x & 0x7fff7fff, cr.y & 0x7fff7fff), __vmaxu2(ci.x & 0x7fff7fff, ci.y & 0x7fff7fff));
    const u32 E = max(__reduce_max_sync(~0u, max(mx & 0xffff, mx >> 16)) >> 7, 8u);
    TS(1);
    const float dt = rbf(ex2(blo(ldt) * LOG2E)), csc = uf((257 - E) << 23 | (fu(dt) & 0x7fffff));
    sts32(SM_SC + 16 * ksig + 12, fu(uf(fu(dt) & 0x7f800000) * uf((E - 2) << 23)));
    const u32 crw = khf ? cr.y : cr.x, ciw = khf ? ci.y : ci.x;
    float2 C[2], w4[2], w8[2], w16[2], w32[2], w64[2], w128[2], w256[2], w512[2], a1[2], a2[2], a3[2], t0[2], t1[2], s3[2];
#pragma unroll
    for (int m = 0; m < 2; m++) {
      const float lr2 = rbf(ex2((m ? bhi(la) : blo(la)) * LOG2E)) * dt * -LOG2E, th = (m ? bhi(ai) : blo(ai)) * dt;
      C[m] = make_float2((m ? bhi(crw) : blo(crw)) * csc, (m ? bhi(ciw) : blo(ciw)) * csc);
      const float2 w1 = cexp(lr2, th), w2 = csq(w1);
      w64[m] = cexp(64.f * lr2, 64.f * th);
      w4[m] = csq(w2); w8[m] = csq(w4[m]); w16[m] = csq(w8[m]); w32[m] = csq(w16[m]);
      w128[m] = csq(w64[m]); w256[m] = csq(w128[m]); w512[m] = csq(w256[m]);
      const float2 w1024 = csq(w512[m]);
      a1[m] = cmul(C[m], w1); a2[m] = cmul(C[m], w2); a3[m] = cmul(a1[m], w2);
      t0[m] = cmul(C[m], w1024); t1[m] = cmul(t0[m], w128[m]); s3[m] = cmul(w8[m], w16[m]);
      k2048 += fmaf(t0[m].x, w1024.x, -t0[m].y * w1024.y);
    }
    C2 B0[8], B1[8], B2[8], S[8];
    B0[0] = pk2(C); B0[1] = pk2(a1); B0[2] = pk2(a2); B0[3] = pk2(a3);
    const C2 h4 = pk2(w4), h256 = pk2(w256), h512 = pk2(w512);
#pragma unroll
    for (int i = 0; i < 4; i++) B0[4 + i] = cm2(B0[i], h4);
#pragma unroll
    for (int i = 0; i < 4; i++) B1[i] = cm2(B0[2 * i], h256);
    B1[4] = cm2(B0[0], h512); B1[5] = cm2(B0[4], h512);
    B1[6] = cm2(B1[4], h256); B1[7] = cm2(B1[5], h256);
    const u32 ta = ktab + lane * 128, f = ((lane & 3) << 5) | ((lane & 4) << 2);
#pragma unroll
    for (int i = 0; i < 8; i++) sts128(ta + ((i << 4) ^ f), B0[i].re, B0[i].im, B1[i].re, B1[i].im);
    B2[0] = pk2(t0); B2[1] = pk2(t1);
    B2[2] = cm2(B2[0], h256); B2[3] = cm2(B2[1], h256);
#pragma unroll
    for (int i = 0; i < 4; i++) B2[4 + i] = cm2(B2[i], h512);
    S[0] = {0x3C003C00u, 0u}; S[1] = pk2c(w8); S[2] = pk2c(w16); S[3] = pk2c(s3); S[4] = pk2c(w32);
#pragma unroll
    for (int i = 1; i < 4; i++) S[4 + i] = cm2(S[i], S[4]);
#pragma unroll
    for (int i = 0; i < 8; i++) sts128(ta + 4096 + ((i << 4) ^ f), B2[i].re, B2[i].im, S[i].re, S[i].im);
    const C2 m64 = pk2c(w64), m128 = pk2c(w128);
    sts128(ktab + 8192 + lane * 16, m64.re, m64.im, m128.re, m128.im);
    __syncwarp();
  } else {
    u32 sa = SM_SIL + 576 * (w & 1) + 24 * min(lane, 23u);
#pragma unroll 1
    for (int j = 0; j < 6; j++) {
      sts32(sa, pk_bf(silu_f(blo(la)), silu_f(bhi(la))));
      la = ai; ai = cr.x; cr.x = cr.y; cr.y = ci.x; ci.x = ci.y; sa += 4;
    }
    bsync(7, 64);
  }
  TS(2);
  const u32 ep = __reduce_or_sync(~0u, epv), par = (ep + 1) & 1, pm = par ? TAGM : 0;
  if (w < 9) {
    asm volatile("cp.async.wait_all;" ::: "memory");
    __syncwarp();
    TS(4);
    if (tid == 256 && b >= 36 && b < 108) { mb_expect(SM_MB, 36864); tma3d(SM_UP, &tm_mod, SM_MB, 32 * b, 0); }
    const u32 xa = SM_XST + (lane & 15) * ROW + 128 * w + 16 * (lane >> 4);
    float s[4] = {}, X[2][4] = {}, Y[2][4] = {};
#pragma unroll
    for (int j = 0; j < 4; j++) {
      const uint4 a = ldsm4(xa + 32 * j);
      mma8_bf(X[0], a.x, a.y, a.x); mma8_bf(Y[0], a.x, a.y, a.y);
      mma8_bf(X[1], a.z, a.w, a.z); mma8_bf(Y[1], a.z, a.w, a.w);
      mma_bf(s, a.x, a.y, a.z, a.w, BONE, BONE);
    }
    uint4 t[4];
#pragma unroll
    for (int j = 0; j < 4; j++) t[j] = ldsm4t(xa + 32 * j);
    const float u0 = hi ? X[0][1] + X[1][1] : X[0][0] + X[1][0], u1 = hi ? Y[0][3] + Y[1][3] : Y[0][2] + Y[1][2];
    if (q == g >> 1) sts128(SM_SP + w * 128 + g * 16, fu(s[0]), fu(u0), fu(s[2]), fu(u1));
    bsync(1, 288);
    TS(7);
    const u32 spr = SM_SP + (lane & 7) * 16 + (lane & 8);
    const uint2 t8 = lds64(spr + 1024);
    const float f8 = lane < 16 ? 1.f : 0.f;
    float S1 = uf(t8.x) * f8, S2 = uf(t8.y) * f8;
#pragma unroll
    for (int i = 0; i < 4; i++) { const uint2 u = lds64(spr + (lane & 16) * 32 + i * 128); S1 += uf(u.x); S2 += uf(u.y); }
    S1 += __shfl_xor_sync(~0u, S1, 16); S2 += __shfl_xor_sync(~0u, S2, 16);
    const float mu = S1 * (1.f / 576.f), var = fmaxf(fmaf(-mu, mu, S2 * (1.f / 576.f)), 0.f);
    const float m = rbf(mu), rs = rcpf(rbf(sqrta(rbf(rbf(var) + 1e-5f))));
    const float ra = rs * 0.0625f;
    sts64(SM_AF + w * 128 + (lane & 15) * 8, fu(ra), fu(-m * ra));
    __syncwarp();
    TS(55);
    const uint4 f0 = lds128(SM_AF + w * 128 + q * 16), f1 = lds128(SM_AF + w * 128 + 64 + q * 16);
    const u32 zdst = SM_GATE + w * 2048 + lane * 8;
    const u32 pz = (q & 1) ? 0 : pm;
#pragma unroll
    for (int j = 0; j < 8; j++) {
      const u32 x0 = j & 1 ? t[j >> 1].z : t[j >> 1].x, x1 = j & 1 ? t[j >> 1].w : t[j >> 1].y;
      sts64(zdst + 256 * j, pk_hf(fmaf(blo(x0), uf(f0.x), uf(f0.y)), fmaf(bhi(x0), uf(f0.z), uf(f0.w))) | pz,
            pk_hf(fmaf(blo(x1), uf(f1.x), uf(f1.y)), fmaf(bhi(x1), uf(f1.z), uf(f1.w))));
    }
    TS(53);
    if (w < 8) barrive(15, 288);
    else {
      bsync(15, 288);
      TS(54);
      if (lane == 0) {
        PROXY_FENCE();
        bulk_out<BLK>(gs + b * BLK, SM_GATE);
        asm volatile("cp.async.bulk.commit_group;" ::: "memory");
        if (PFG & 1) l2_pre<WSH / 2>(p.wg + b * WSH);
      }
      const float rh = rbf(rs);
      sts128(SM_ST + 16 * (lane & 15), pk_bf(-m, -m), pk_bf(rh, rh), pk_bf(rs - rh, rs - rh), 0);
    }
    TS(5);
  }
  if (kw) {
    float D[5][4] = {};
    u32 ta = ktab + q * 128 + ((g ^ (q << 1)) << 4), tm = ktab + 8192 + q * 16;
#pragma unroll 2
    for (int s = 0; s < 8; s++) {
      const uint4 ca = lds128(ta), cb = lds128(ta + 4096), ma = lds128(tm);
      ta = (ta + 512) ^ 16; tm += 64;
      k2048 += __shfl_xor_sync(~0u, k2048, 16 >> s);
      const C2 s0 = {cb.z, cb.w}, s1 = cm2(s0, {ma.x, ma.y}), s2 = cm2(s0, {ma.z, ma.w}), s3 = cm2(s1, {ma.z, ma.w});
      mma_hf(D[0], s0.re, s1.re, s0.im, s1.im, ca.x, ca.y);
      mma_hf(D[2], s0.re, s1.re, s0.im, s1.im, ca.z, ca.w);
      mma_hf(D[4], s0.re, s1.re, s0.im, s1.im, cb.x, cb.y);
      mma_hf(D[1], s2.re, s3.re, s2.im, s3.im, ca.x, ca.y);
      mma_hf(D[3], s2.re, s3.re, s2.im, s3.im, ca.z, ca.w);
    }
    TS(3);
    const u32 xa = (w < 8 ? SM_MODS + (4 + ksig) * KTAB : SM_ZS) + lane * 16;
    if (khf) {
      __syncwarp();
#pragma unroll
      for (int j = 0; j < 5; j++) sts128(xa + 512 * j, fu(D[j][0]), fu(D[j][1]), fu(D[j][2]), fu(D[j][3]));
      if (lane == 0) sts32(xa + 2560, fu(k2048));
      asm volatile("bar.arrive %0,64;" ::"r"(2 + ksig) : "memory");
    } else {
      const u32 t1 = tp + (q < 2 ? (128 + 4 * g + 2 * q) * 4 : T3 * 4 + ((32 * q - 64 + g) ^ 1) * 2);
      const u32 x = 16 * q + (g >> 1) + hi + 1, tb = tp + (hi ? T7E : T9E) * 4 - 4;
      const u32 te = tb + (x + 2 * (x & 1)) * 2, to = tb + TEO * 4 + (x ^ 1) * 2;
      asm volatile("bar.sync %0,64;" ::"r"(2 + ksig) : "memory");
#pragma unroll
      for (int j = 0; j < 5; j++) { const uint4 t = lds128(xa + 512 * j); D[j][0] += uf(t.x); D[j][1] += uf(t.y); D[j][2] += uf(t.z); D[j][3] += uf(t.w); }
      k2048 = (k2048 + uf(lds32(xa + 2560))) * 0.125f;
#pragma unroll
      for (int r = 0; r < 4; r++) {
        const u32 v = pk_hf(D[2 + (r >> 1)][2 * (r & 1)], D[2 + (r >> 1)][2 * (r & 1) + 1]);
        if (q < 2) {
          const u32 vv = __byte_perm(v, v, 0x1010);
          sts32(t1 + (TO + 32 * r) * 4, vv); sts16(t1 + (TO + 32 * r + 1) * 4 + 2, v >> 16); sts16(t1 + (TO + 32 * r - 1) * 4, v);
          sts64(t1 + (TE + 32 * r) * 4, vv, __byte_perm(v, v, 0x1032));
        } else {
          sts16(t1 + 16 * r, v >> 16);
          if (r == 0 && lane == 2) {
            const u32 vv = __byte_perm(v, v, 0x1010);
            sts32(tp + (TO + 256) * 4, vv); sts16(tp + (TO + 257) * 4 + 2, v); sts16(tp + (TO + 255) * 4, v); sts64(tp + (TE + 256) * 4, vv, vv);
          } else sts16(t1 + 16 * r - ((T3 - T5) * 4 + 6) + 8 * hi, v);
        }
      }
#pragma unroll
      for (int r = 0; r < 2; r++) {
        const u32 v = pk_hf(D[4][2 * r], D[4][2 * r + 1]);
        if (r == 0 && lane == 0) { sts16(tp + T5 * 4 + 62 * 2, v); sts32(SM_KV + 4 * ksig, v & 0xffff); sts16(tp + (T9E + TEO) * 4 + 62 * 2, pk_hf(k2048, 0.f)); }
        else { sts16(te + 8 * r, v); sts16(to + 8 * r, v); }
        sts16(te + 8 * r + 16, v >> 16); sts16(to + 8 * r + 16, v >> 16);
      }
      __syncwarp();
#pragma unroll
      for (int r = 0; r < 4; r++) {
        const u32 v = pk_hf(D[r >> 1][2 * (r & 1) + 1], D[r >> 1][2 * (r & 1)]), t2 = tp + lane * 4 + 128 * r;
        sts32(t2 + TO * 4, v); sts16(t2 + TE * 4, v >> 16); sts16(t2 + (TE + 1) * 4 + 2, v);
      }
      __syncwarp();
    }
  } else if (w == 11 && b < 108) {
    float c[4][4] = {};
    u32 aa = SM_UP + ((lane & 7) + 8 * (lane >> 4)) * 64 + ((((lane >> 3) & 1) ^ ((lane & 7) >> 1)) << 4);
    u32 ba = SM_SIL + (lane >> 3) * 16;
    uint4 a[2][10];
#define GLD(n) { _Pragma("unroll") for (int i = 0; i < 2; i++) { a[n][5 * i] = ldsm4(ba + i * 64); \
      _Pragma("unroll") for (int k = 0; k < 4; k++) a[n][5 * i + 1 + k] = ldsm4t((k & 2 ? aa ^ 32 : aa) + i * 2048 + (k & 1) * 1024); } aa += 4096; ba += 128; }
#define GMM(n) { _Pragma("unroll") for (int i = 0; i < 2; i++) _Pragma("unroll") for (int k = 0; k < 4; k++) { const uint4 f = a[n][5 * i + 1 + k], bb = a[n][5 * i]; \
      mma_bf(c[k], f.x, f.y, f.z, f.w, k & 1 ? bb.z : bb.x, k & 1 ? bb.w : bb.y); } }
    mb_wait(SM_MB);
    TS(56);
    GLD(0);
#pragma unroll 1
    for (int s = 0; s < 4; s++) { GLD(1); GMM(0); GLD(0); GMM(1); }
    GMM(0);
    const float v0 = (q & 1) ? c[0][2] + c[1][2] : c[0][0] + c[1][0], v1 = (q & 1) ? c[2][2] + c[3][2] : c[2][0] + c[3][0];
    str16(gs + (G_MOD + b * 128 + 2 * g + 16 * q), pk_bf(rbf((q & 2) ? v1 : v0) * F2M64, 0.f) | (g < 2 ? pm : 0));
    TS(57);
  }
  TS(6);
  u32 tid2 = tid;
  if (w < 4) {
    asm volatile("setmaxnreg.inc.sync.aligned.u32 232;");
    const u32 tid = tid2 + p.zero, w = tid >> 5, lane = tid & 31, g = lane >> 2, q = lane & 3, hi = g & 1, zr = tid >> 16, tp = SM_TAP + w * TAPS;
    const u32 pml = opq((g & 3) ? 0 : pm);
    const u32 tr = tp + ((hi ? TO : TE) + (g >> 1) - q) * 4;
    u32 T[33][4], B5[5][2], B3[5][2];
#pragma unroll
    for (int d = 0; d < 33; d++) {
      T[d][0] = lds32(tr + 32 * d); T[d][1] = lds32(tr + 32 * d + 16);
      T[d][2] = cpy(d ? T[d - 1][1] : zr, zr, 0); T[d][3] = cpy(T[d][0], zr, 1);
    }
    const u32 t33 = cpy(T[32][1], zr, 0), z33 = cpy(zr, zr, 1);
    const u32 bt = tp + (T5 + g - q) * 4;
#pragma unroll
    for (int d = 0; d < 5; d++) {
      B5[d][0] = lds32(bt + 32 * d); B5[d][1] = lds32(bt + 32 * d - 16);
      B3[d][0] = lds32(bt + 32 * d + (T3 - T5) * 4); B3[d][1] = lds32(bt + 32 * d - 16 + (T3 - T5) * 4);
    }
    u32 za = opq(SM_ZS + 16 + w * ZSS + ((lane >> 3) & 1) * ZPS + ((lane & 7) + (lane >> 4)) * 16);
    u32 wa = opq(SM_W + W5O + w * WSL + row16(lane));
    u32 sa = opq(SM_W + W9O + w * WSL + lane * 16);
    u32 yo = opq(G_Y + 2 * q * BLK + (4 * b + w) * 32 + 4 * g);
    const u32 fa = opq(SM_SC + 16 * w + 8);
    TS(8);
    bsync(9, 384);
    TS(11);
    float A[4][4] = {};
    uint4 Z[4];
    Z[0] = ldsm4(za); Z[1] = ldsm4(za + 32);
    const uint2 fc = lds64(fa);
    const u32 F = __byte_perm(fu(uf(fc.x) * uf(fc.y)), 0, 0x3232);
#define STEP(s, b0, b1) { _Pragma("unroll") for (int i = 0; i < 4; i++) mma_hf_t(A[i], T[8 * i + 7 - (s)], b0, b1); }
#define PAIR(n) { Z[(n + 2) & 3] = ldsm4(za + 32 * (n + 2)); STEP(2 * n, Z[n].x, Z[n].y); STEP(2 * n + 1, Z[n].z, Z[n].w); }
#define LAST(N) mma8_hf(N, t33, z33, Z[3].y); float O[4]; mma_hf_o(O, A[0], T[0], Z[3].z, Z[3].w); \
    _Pragma("unroll") for (int i = 0; i < 3; i++) mma_hf_o(A[i], A[i + 1], T[8 * i + 8], Z[3].z, Z[3].w); \
    mma_hf_o(A[3], N, T[32], Z[3].z, Z[3].w);
#pragma unroll 1
    for (int j = 0; j < 4; j++) {
      PAIR(0); PAIR(1); PAIR(2);
      Z[1] = ldsm4(za + 160); STEP(6, Z[3].x, Z[3].y);
      float N[4] = {};
      LAST(N);
      y_store(O[0], O[1], O[2], O[3], F, pml, gs + yo);
      za += 128; yo += 8 * BLK;
      TS(40 + j);
    }
    bsync(10, 352);
#pragma unroll 1
    for (int j = 4; j < 13; j++) {
      if (j == 8) bsync(14, 224);
      const uint4 a5 = ldsm4t(wa), a3 = ldsm4t(wa + (W3O - W5O)), s3 = lds128(sa);
      PAIR(0);
      float N[4] = {uf(s3.x), uf(s3.y), uf(s3.z), uf(s3.w)};
#pragma unroll
      for (int i = 0; i < 4; i++) mma_hf(A[i], a5.x, a5.y, a5.z, a5.w, B5[i][0], B5[i][1]);
      mma_hf(N, a5.x, a5.y, a5.z, a5.w, B5[4][0], B5[4][1]);
      PAIR(1);
#pragma unroll
      for (int i = 0; i < 4; i++) mma_hf(A[i], a3.x, a3.y, a3.z, a3.w, B3[i][0], B3[i][1]);
      mma_hf(N, a3.x, a3.y, a3.z, a3.w, B3[4][0], B3[4][1]);
      PAIR(2);
      Z[1] = ldsm4(za + 160); STEP(6, Z[3].x, Z[3].y);
      LAST(N);
      y_store(O[0], O[1], O[2], O[3], F, pml, gs + yo);
      za += 128; wa = (wa + 256) ^ 32; sa += 512; yo += 8 * BLK;
      TS(40 + j);
    }
    {
      float X[3][4] = {};
#pragma unroll
      for (int ty = 0; ty < 2; ty++) {
        const uint4 a = ldsm4t(wa + ty * (W3O - W5O)), c = ldsm4t((wa ^ 32) + 256 + ty * (W3O - W5O)), d = ldsm4t(wa + 512 + ty * (W3O - W5O));
#pragma unroll
        for (int i = 0; i < 3; i++) mma_hf(A[i], a.x, a.y, a.z, a.w, ty ? B3[i][0] : B5[i][0], ty ? B3[i][1] : B5[i][1]);
#pragma unroll
        for (int i = 0; i < 2; i++) mma_hf(X[i], c.x, c.y, c.z, c.w, ty ? B3[i][0] : B5[i][0], ty ? B3[i][1] : B5[i][1]);
        mma_hf(X[2], d.x, d.y, d.z, d.w, ty ? B3[0][0] : B5[0][0], ty ? B3[0][1] : B5[0][1]);
      }
      asm volatile("mov.u32 %0,%%tid.x;" : "=r"(tid2));
#pragma unroll
      for (int n = 0; n < 4; n++) {
        const uint4 f0 = n < 2 ? Z[n] : ldsm4(za + 32 * n), f1 = ldsm4(za + 32 * n + 128), f2 = ldsm4(za + 32 * n + 256);
#pragma unroll
        for (int s = 2 * n; s < 2 * n + 2; s++) {
#pragma unroll
          for (int i = 0; i < 3; i++) mma_hf_t(A[i], T[8 * i + 7 - s], s & 1 ? f0.z : f0.x, s & 1 ? f0.w : f0.y);
          mma_hf_t(X[0], T[7 - s], s & 1 ? f1.z : f1.x, s & 1 ? f1.w : f1.y); mma_hf_t(X[1], T[15 - s], s & 1 ? f1.z : f1.x, s & 1 ? f1.w : f1.y);
          mma_hf_t(X[2], T[7 - s], s & 1 ? f2.z : f2.x, s & 1 ? f2.w : f2.y);
        }
      }
      y_store(A[0][0], A[0][1], A[0][2], A[0][3], F, pml, gs + yo);
      y_store(A[1][0] + X[0][0], A[1][1] + X[0][1], A[1][2] + X[0][2], A[1][3] + X[0][3], F, pml, gs + yo + 8 * BLK);
      y_store(A[2][0] + X[1][0] + X[2][0], A[2][1] + X[1][1] + X[2][1], A[2][2] + X[1][2] + X[2][2], A[2][3] + X[1][3] + X[2][3], F, pml, gs + yo + 16 * BLK);
    }
    barrive(12, 288);
    TS(15);
    asm volatile("setmaxnreg.dec.sync.aligned.u32 168;");
  } else {
    asm volatile("setmaxnreg.dec.sync.aligned.u32 136;");
    const u32 t8 = tid - 128, pml = (g & 3) ? 0 : pm;
    {
      TS(12);
      if (PFG == 1 && tid == 288) l2_pre<WSH / 2>(p.wg + (b * WSH + WSH / 2));
      const char* zs = gs + ((16 * w - 64 + (lane >> 3)) * BLK + b * 128 + (lane & 7) * 16);
      const char* zs4 = gs + ((t8 >> 1) * BLK + Ps * 32 + (t8 & 1) * 16);
      uint4 v[5];
      v[4].x = INVAL;
      if (w == 9) {
        const u32 d = lane < 4 ? 4 * b + lane : Ps;
        const char* mp = gs + (G_MOD + (d >> 5) * 128 + (d & 24) * 2);
        uint4 ta, tc;
        POLL({ ta = ldr128(mp); tc = ldr128(mp + MODJ); v[4] = ldr128(zs4); }, ((ta.x ^ pm) | (tc.x ^ pm)) & TAGM, 2);
        const u32 aw = (d & 4) ? ((d & 2) ? ta.w : ta.z) : ((d & 2) ? ta.y : ta.x & ~TAGM);
        const u32 cw = (d & 4) ? ((d & 2) ? tc.w : tc.z) : ((d & 2) ? tc.y : tc.x & ~TAGM);
        const float sa = ((d & 1) ? bhi(aw) : blo(aw)) * F2P64, c1 = rbf(fmaf((d & 1) ? bhi(cw) : blo(cw), F2P64, 1.f));
        const u32 EM = min(max(fu(fmaxf(32.f * fabsf(c1), fabsf(sa))) >> 23, 80u), 250u);
        const float inv = uf((264 - EM) << 23);
        if (lane < 5) { sts64(SM_SC + 16 * lane, pk_hf(16.f * c1 * inv, 16.f * c1 * inv), pk_hf(sa * inv, sa * inv)); sts32(SM_SC + 16 * lane + 8, (EM - 74) << 23); }
        TS(10);
      }
      POLLW(v[4] = ldr128(zs4), (v[4].x ^ pm) & TAGM, 1);
      TS(58);
#pragma unroll
      for (int j = 0; j < 4; j++) v[j] = ldr128(zs + j * 4 * BLK);
      if (PFG == 2 && tid == 256) l2_pre<WSH>(p.wg + b * WSH);
      if (PFG == 3 && tid == 256) l2_pre<WSH / 2>(p.wg + (b * WSH + WSH / 2));
      bsync(8, 256);
      const uint2 cc = lds64(SM_SC + 8 * (t8 & 6)), c4 = lds64(SM_SC + 64);
      POLLW(_Pragma("unroll") for (int j = 0; j < 4; j++) if ((v[j].x ^ pm) & TAGM) v[j] = ldr128(zs + j * 4 * BLK),
           ((v[0].x ^ pm) | (v[1].x ^ pm) | (v[2].x ^ pm) | (v[3].x ^ pm)) & TAGM, 1);
      TS(9);
      const u32 dst = SM_ZS + 128 + (t8 & 7) * ZPS + (16 * w - 64 + (lane >> 3)) * 16;
#pragma unroll
      for (int j = 4; j >= 0; j--) {
        const uint2 c = j < 4 ? cc : c4;
        sts128(j < 4 ? dst + j * 64 : SM_Z4 + 256 + (t8 & 1) * ZP4 + (t8 >> 1) * 16, hfma(v[j].x & ~TAGM, c.x, c.y), hfma(v[j].y, c.x, c.y), hfma(v[j].z, c.x, c.y), hfma(v[j].w, c.x, c.y));
      }
      if (t8 < 96) sts128(t8 < 64 ? SM_ZS + (t8 & 7) * ZPS + (t8 >> 3) * 16 : SM_Z4 + (t8 & 1) * ZP4 + (t8 & 30) * 8, 0, 0, 0, 0);
      asm volatile("cp.async.bulk.wait_group.read 0;" ::: "memory");
      bsync(9, 384);
      TS(11);
      const bool lng = w < 8 || w == 9;
      const u32 ts = lane + 32 * (w == 8 ? 0 : w - 9), c = min(ts, 71u), ma = SM_MODS + 16 * c;
      const u32 sig = lng ? ksig : ts >> 4, l2 = lng ? lane : 32 + (ts & 15);
      const char* mq = gs + (G_MOD + (c >> 2) * 128 + (c & 3) * 16);
      if (!lng) {
#pragma unroll
        for (int j = 0; j < 6; j++) cpa16(ma + 1152 * j, mq + j * MODJ);
        cpa16(ma + 1152 * 6, p.dsk + 16 * c); cpa16(ma + 1152 * 7, p.wr + 16 * c);
        if (tid == 352) {
          PROXY_FENCE();
          mb_expect(SM_MB + 8, rho ? SLV : 46080);
          tma3d(SM_GATE, &tm_gate, SM_MB + 8, 32 * b, 0);
          if (!rho) tma3d(SM_GATE + SLV, &tm_gs, SM_MB + 8, 4096 + 4 * b, 0);
          if (UPM) {
            mb_expect(SM_MB + 16, rho ? SLV : 46080);
            tma3d(SM_UP, &tm_up, SM_MB + 16, 32 * b, 0);
            if (!rho) tma3d(SM_UP + SLV, &tm_us, SM_MB + 16, 4096 + 4 * b, 0);
          } else l2_pre<WSH>(p.wu + b * WSH);
        }
      }
      const u32 wb = SM_W + sig * WSL;
      if (sig < 5) {
        const u32 za = (sig < 4 ? SM_ZS + 128 + sig * ZSS : SM_Z4 + 256) + l2 * 32, zb = za + (sig < 4 ? ZPS : ZP4);
        const uint4 c0 = lds128(zb - 32), c1 = lds128(za - 16), c2 = lds128(zb - 16), c3 = lds128(za), c4 = lds128(zb), c5 = lds128(za + 16), c6 = lds128(zb + 16);
        const u32 P[25] = {c0.z, c0.w, c1.x, c1.y, c1.z, c1.w, c2.x, c2.y, c2.z, c2.w, c3.x, c3.y, c3.z, c3.w, c4.x, c4.y, c4.z, c4.w, c5.x, c5.y, c5.z, c5.w, c6.x, c6.y, c6.z};
        u32 Q[25], D1[24], F4[23], W5[21], W3[17];
#pragma unroll
        for (int j = 1; j < 25; j++) Q[j] = __byte_perm(P[j - 1], P[j], 0x5432);
#pragma unroll
        for (int j = 1; j < 24; j++) D1[j] = hadd(P[j], Q[j]);
#pragma unroll
        for (int j = 2; j < 23; j++) F4[j] = hadd(D1[j], D1[j - 1]);
#pragma unroll
        for (int n = 0; n < 21; n++) W5[n] = hadd(F4[n + 2], P[n]);
#pragma unroll
        for (int n = 0; n < 17; n++) W3[n] = hadd(Q[n + 8], D1[n + 7]);
        const u32 a0 = wb + W5O + 64 * l2 + 16 * ((l2 >> 1) & 3);
#pragma unroll
        for (int i = 0; i < 4; i++) {
          sts128(a0 ^ (16 * i), W5[4 * i + 5], W5[4 * i + 6], W5[4 * i + 7], W5[4 * i + 8]);
          sts128((a0 ^ (16 * i)) + (W3O - W5O), W3[4 * i + 1], W3[4 * i + 2], W3[4 * i + 3], W3[4 * i + 4]);
        }
        if (lng) {
          if (lane < 16) sts128(wb + (lane & 7) * 16 + (lane & 8) * 400, 0, 0, 0, 0);
          const u32 a1 = wb + 32 * lane + 16 * ((lane >> 2) & 1);
#pragma unroll
          for (int i = 0; i < 4; i++) {
            const u32 a = (a1 ^ (16 * (i >> 1))) + 1024 * (i & 1), n = 4 * i;
            sts128(a + V2O, hadd(Q[n + 9], P[n + 8]), hadd(Q[n + 10], P[n + 9]), hadd(Q[n + 11], P[n + 10]), hadd(Q[n + 12], P[n + 11]));
            sts128(a + W9O, hadd(F4[n + 4], W5[n]), hadd(F4[n + 5], W5[n + 1]), hadd(F4[n + 6], W5[n + 2]), hadd(F4[n + 7], W5[n + 3]));
            sts128(a + W7O, hadd(F4[n + 6], W3[n]), hadd(F4[n + 7], W3[n + 1]), hadd(F4[n + 8], W3[n + 2]), hadd(F4[n + 9], W3[n + 3]));
          }
        }
      }
      __syncwarp();
      TS(32);
      if (lng) {
        const u32 wa = wb + ((lane >> 3) & 1) * 1024 + (((lane & 7) ^ (lane >> 4)) + 8 * (lane >> 4)) * 16;
        const u32 kv = lds32(SM_KV + 4 * sig), bi = (g >> 1) == q ? (hi ? kv << 16 : kv) : 0u;
        float acc[8][4] = {};
#pragma unroll
        for (int j = 0; j < 4; j++) { const uint4 a = ldsm4t(wa + V2O + j * 256); mma8_hf(acc[2 * j], a.x, a.y, bi); mma8_hf(acc[2 * j + 1], a.z, a.w, bi); }
        u32 bt = tp + (T9E + hi * TEO + (g >> 1) - q) * 4, wt = wa + W9O;
#pragma unroll 1
        for (int ty = 0; ty < 2; ty++) {
          uint4 a[4];
#pragma unroll
          for (int be = 0; be < 4; be++) a[be] = ldsm4t(wt + be * 256);
          u32 b1 = lds32(bt - 16);
#pragma unroll
          for (int d = 0; d < 8; d++) {
            const u32 b0 = lds32(bt + 16 * d);
#pragma unroll
            for (int be = 0; be < 4; be++) if (d + 2 * be < 8) mma_hf(acc[d + 2 * be], a[be].x, a[be].y, a[be].z, a[be].w, b0, b1);
            b1 = b0;
          }
          bt += (T7E - T9E) * 4; wt += W7O - W9O;
        }
        __syncwarp();
#pragma unroll
        for (int j = 0; j < 8; j++) sts128(wb + W9O + j * 512 + lane * 16, fu(acc[j][0]), fu(acc[j][1]), fu(acc[j][2]), fu(acc[j][3]));
        TS(34);
      }
      if (w != 9) barrive(10, 352);
      if (!lng) {
        asm volatile("cp.async.wait_all;" ::: "memory");
        uint4 md[6];
#pragma unroll
        for (int j = 0; j < 6; j++) md[j] = lds128(ma + 1152 * j);
        const uint4 wr = lds128(ma + 1152 * 7);
        POLLW(_Pragma("unroll") for (int j = 0; j < 6; j++) md[j] = ldr128(mq + j * MODJ),
              ((md[0].x ^ pm) | (md[1].x ^ pm) | (md[2].x ^ pm) | (md[3].x ^ pm) | (md[4].x ^ pm) | (md[5].x ^ pm)) & TAGM, 4);
        TS(61);
#pragma unroll
        for (int j = 0; j < 6; j++) {
          const u32 o = (j % 3 == 1) ? BONE : 0x80008000u;
          md[j] = make_uint4(bfma(md[j].x & ~TAGM, B2P64, o), bfma(md[j].y, B2P64, o), bfma(md[j].z, B2P64, o), bfma(md[j].w, B2P64, o));
          sts128(ma + 1152 * j, md[j].x, md[j].y, md[j].z, md[j].w);
        }
        const uint4 H = make_uint4(bmul(md[4].x, wr.x), bmul(md[4].y, wr.y), bmul(md[4].z, wr.z), bmul(md[4].w, wr.w));
        sts128(ma + 1152 * 7, H.x, H.y, H.z, H.w);
        sts128(ma + 1152 * 8, bfma(md[4].x, wr.x, H.x ^ 0x80008000u), bfma(md[4].y, wr.y, H.y ^ 0x80008000u), bfma(md[4].z, wr.z, H.z ^ 0x80008000u), bfma(md[4].w, wr.w, H.w ^ 0x80008000u));
        float c4[4] = {};
        mma_bf(c4, md[4].x, md[3].x, md[4].y, md[3].y, wr.x, wr.y); mma_bf(c4, md[4].z, md[3].z, md[4].w, md[3].w, wr.z, wr.w);
        if (q == g >> 1) sts64(SM_RC + (ts >> 2) * 8, fu(hi ? c4[1] : c4[0]), fu(hi ? c4[3] : c4[2]));
        if (ts < 5) sts128(ts < 2 ? SM_ONE + 16 * ts : SM_THR + 16 * ts - 32, ts ? 0 : BONE, ts ? 0 : BONE, ts ? 0 : BONE, ts ? 0 : BONE);
        TS(14);
#pragma unroll 1
        for (u32 i = 64 * MT + ts; i < 1024; i += 96) str128(gs + (G_Y + (i >> 3) * BLK + b * 128 + (ts & 7) * 16), INVAL, 0, 1, 0);
        str128(gs + (G_Y + (32 * (ts >> 5) + 16 * rho + ((ts & 31) >> 1)) * BLK + Ps * 32 + (ts & 1) * 16), INVAL, 0, 1, 0);
        str128(gs + (G_PART + b * 2048 + ts * 16), INVAL, 0, 1, 0);
        str128(gs + (ts < 32 ? G_PART + b * 2048 + 1536 + ts * 16 : ts < 64 ? G_ACT + b * 512 + (ts & 31) * 16 : G_Y + (96 + 16 * rho + ((ts & 31) >> 1)) * BLK + Ps * 32 + (ts & 1) * 16), INVAL, 0, 1, 0);
        if (ts < (rho ? 4 : 12)) str128(gs + (ts < 4 ? G_KEY + b * 128 + ts * 16 : G_ACT + Ps * 128 + (ts - 4) * 16), INVAL, 0, 1, 0);
        barrive(14, 224);
        bsync(13, 96);
      }
      if (w >= 8) barrive(11, 256);
    }
    if (w < 8) {
      const int u0 = 4 * (w - 4) + 2 * rho;
      const u32 t4 = SM_TAP + 4 * TAPS;
      u32 tr = t4 + ((hi ? TO : TE) + (g >> 1) - q) * 4;
      u32 zb = SM_Z4 + 256 + ((lane >> 3) & 1) * ZP4 + u0 * 128 + (lane & 7) * 16 + (lane >> 4) * 128;
      float acc[4][4] = {};
      u32 prev = 0;
#pragma unroll 1
      for (int it = min(u0 + 2, 4); it; it--) {
#pragma unroll
        for (int s = 0; s < 8; s++) {
          const uint4 z = ldsm4(zb - 16 * s);
          const u32 t0 = lds32(tr + 32 * s), t1 = lds32(tr + 32 * s + 16);
          mma_hf(acc[s & 1], t0, t1, prev, t0, z.x, z.y);
          mma_hf(acc[2 + (s & 1)], t0, t1, prev, t0, z.z, z.w);
          prev = t1;
        }
        zb -= 128; tr += 256;
      }
      {
        const uint4 z = ldsm4(zb); const u32 t0 = lds32(tr), t1 = lds32(tr + 16);
        mma_hf(acc[0], t0, t1, prev, t0, z.x, z.y); mma_hf(acc[2], t0, t1, prev, t0, z.z, z.w);
        if (w > 4) { const uint4 y = ldsm4(zb - 16); mma8_hf(acc[1], t1, zr, y.y); mma8_hf(acc[3], t1, zr, y.w); }
      }
      bsync(11, 256);
      u32 wa = (SM_W + 4 * WSL + W5O + row16(lane) + (u0 - 3) * 256) ^ 32, bt = t4 + (T5 + g - q) * 4;
#pragma unroll 1
      for (int al = min(u0 - 2, 6); al > 0; al--) {
#pragma unroll
        for (int ty = 0; ty < 2; ty++) {
          const uint4 a = ldsm4t(wa + ty * (W3O - W5O));
          const u32 bb = bt + ty * (T3 - T5) * 4;
          mma_hf(acc[ty], a.x, a.y, a.z, a.w, lds32(bb - 32), lds32(bb - 48));
          mma_hf(acc[2 + ty], a.x, a.y, a.z, a.w, lds32(bb), lds32(bb - 16));
        }
        wa = (wa - 256) ^ 32; bt += 32;
      }
      TS(35);
      const uint2 fc = lds64(SM_SC + 16 * 4 + 8);
      const u32 F = __byte_perm(fu(uf(fc.x) * uf(fc.y)), 0, 0x3232);
      char* yp = gs + (G_Y + (8 * u0 + 2 * q) * BLK + Ps * 32 + 4 * g);
#pragma unroll
      for (int j = 0; j < 2; j++) {
        uint4 s3 = {0, 0, 0, 0};
        if (u0 >= 8) s3 = lds128(SM_W + 4 * WSL + W9O + (u0 - 8 + j) * 512 + lane * 16);
        y_store(acc[2 * j][0] + acc[2 * j + 1][0] + uf(s3.x), acc[2 * j][1] + acc[2 * j + 1][1] + uf(s3.y), acc[2 * j][2] + acc[2 * j + 1][2] + uf(s3.z),
                acc[2 * j][3] + acc[2 * j + 1][3] + uf(s3.w), F, pml, yp + j * 8 * BLK);
      }
      TS(16);
    } else {
      if (tid == 352) {
        mb_wait(SM_MB + 8);
        if (!UPM) {
          mb_expect(SM_MB + 16, rho ? SLV : 46080);
          tma3d(SM_UP, &tm_up, SM_MB + 16, 32 * b, 0);
          if (!rho) tma3d(SM_UP + SLV, &tm_us, SM_MB + 16, 4096 + 4 * b, 0);
        }
        if (UPM == 2) mb_wait(SM_MB + 16);
        if (PFD) l2_pre<WSH>(p.wd + b * WSH);
      }
      TS(17);
    }
  }
  post_conv(p, &tm_down, tid2 + p.zero, b, ep);
  TSD();
  if (s2u(smem) != SM0) __trap();
}

typedef CUresult (*EncFn)(CUtensorMap*, CUtensorMapDataType, cuuint32_t, void*, const cuuint64_t*, const cuuint64_t*, const cuuint32_t*, const cuuint32_t*,
                          CUtensorMapInterleave, CUtensorMapSwizzle, CUtensorMapL2promotion, CUtensorMapFloatOOBfill);
static void make_map(EncFn enc, CUtensorMap* tm, void* ptr, int cols, int rows, int bw, int nb, CUtensorMapSwizzle sw, int gr = 192) {
  cuuint64_t gd[3] = {(cuuint64_t)cols, (cuuint64_t)gr, (cuuint64_t)(rows / gr)}, gs[2] = {(cuuint64_t)cols * 2, (cuuint64_t)cols * 2 * gr};
  cuuint32_t bd[3] = {(cuuint32_t)bw, (cuuint32_t)gr, (cuuint32_t)nb}, es[3] = {1, 1, 1};
  enc(tm, CU_TENSOR_MAP_DATA_TYPE_BFLOAT16, 3, ptr, gd, gs, bd, es, CU_TENSOR_MAP_INTERLEAVE_NONE, sw, CU_TENSOR_MAP_L2_PROMOTION_NONE, CU_TENSOR_MAP_FLOAT_OOB_FILL_NONE);
}
extern "C" void kernel_launch(void* const* d_in, const int* in_sizes, int n_in, void* d_out, int out_size) {
  static EncFn enc = nullptr;
  static void* scratch = nullptr;
  if (!enc) {
    cudaGetSymbolAddress(&scratch, g_s);
    cudaDriverEntryPointQueryResult qr;
    cudaGetDriverEntryPoint("cuTensorMapEncodeTiled", (void**)&enc, cudaEnableDefault, &qr);
    cudaFuncSetAttribute(fused_kernel, cudaFuncAttributeMaxDynamicSharedMemorySize, SM_TOTAL);
  }
  CUtensorMap tm_mod, tm_gate, tm_gs, tm_up, tm_us, tm_down;
  make_map(enc, &tm_mod, d_in[13], 3456, 576, 32, 3, CU_TENSOR_MAP_SWIZZLE_64B);
  make_map(enc, &tm_gate, d_in[9], 4608, 576, 32, 3, CU_TENSOR_MAP_SWIZZLE_64B);
  make_map(enc, &tm_gs, d_in[9], 4608, 576, 8, 3, CU_TENSOR_MAP_SWIZZLE_NONE);
  make_map(enc, &tm_up, d_in[10], 4608, 576, 32, 3, CU_TENSOR_MAP_SWIZZLE_64B);
  make_map(enc, &tm_us, d_in[10], 4608, 576, 8, 3, CU_TENSOR_MAP_SWIZZLE_NONE);
  make_map(enc, &tm_down, d_in[11], 576, 4608, 64, 1, CU_TENSOR_MAP_SWIZZLE_128B, 96);
  Prm p;
  p.x = (const char*)d_in[0]; p.la = (const char*)d_in[1]; p.ai = (const char*)d_in[2]; p.cr = (const char*)d_in[3];
  p.ci = (const char*)d_in[4]; p.ldt = (const char*)d_in[5]; p.dsk = (const char*)d_in[6]; p.wr = (const char*)d_in[8];
  p.wg = (const char*)d_in[9]; p.wu = (const char*)d_in[10]; p.wd = (const char*)d_in[11];
  p.c = (const char*)d_in[12]; p.out = (char*)d_out; p.zero = 0; p.gs = (char*)scratch;
  fused_kernel<<<128, 384, SM_TOTAL>>>(p, tm_mod, tm_gate, tm_gs, tm_up, tm_us, tm_down);
}
```

```cpp
#include <cuda_runtime.h>
#include <cuda.h>
#include <cuda_bf16.h>
#include <cuda_fp16.h>
#include <stdint.h>
#define FUSED 1
#define DEV __device__ __forceinline__
typedef uint32_t u32;

constexpr u32 BLK = 18432, G_Z = 0, G_Y = 128 * BLK, G_MOD = 2 * G_Y, G_KEY = G_MOD + 128 * 128, G_ACT = G_KEY + 128 * 128;
constexpr u32 G_PART = G_ACT + 576 * 128, G_EP = G_PART + 128 * 2048, G_END = G_EP + 128;
__device__ __align__(128) unsigned char g_s[G_END];
#define TS(i)
#define TS0()
#define TSE()
#define TSD()
#define TSX 0
#define ERRF(code)

constexpr int SM0 = 1024;
constexpr int ROW = 1168, SLV = 36864;
constexpr int SM_GATE = SM0, SM_UP = SM_GATE + 46080, SM_XST = SM_UP + 46080, SM_MODS = SM_XST + 16 * ROW, SM_W = SM_MODS + 11008;
constexpr int KTAB = 9216, WSL = 12544, W5O = 128, W3O = 3328, V2O = 6400, W9O = 8448, W7O = 10496;
constexpr int ZPS = 2192, ZSS = 2 * ZPS, ZP4 = 2368;
constexpr int SM_ZS = SM_W + 5 * WSL, SM_Z4 = SM_ZS + 4 * ZSS, SM_TAP = SM_Z4 + 2 * ZP4, TAPS = 3328;
constexpr int SM_MB = SM_TAP + 5 * TAPS;
constexpr int SM_SC = SM_MB + 32;
constexpr int SM_KV = SM_SC + 80;
constexpr int SM_THR = SM_KV + 32;
constexpr int SM_SLOT = SM_THR + 48;
constexpr int SM_KEY = SM_SLOT + 32;
constexpr int SM_ST = SM_KEY + 64;
constexpr int SM_ST2 = SM_ST + 256;
constexpr int SM_RC = SM_ST2 + 256;
constexpr int SM_SP = SM_RC + 192;
constexpr int SM_AF = SM_SP + 1152, SM_SIL = SM_AF + 1152, SM_INV = SM_SIL + 1152, SM_END = SM_SP + 5760;
constexpr int SM_ONE = SM_MODS + 9 * 1152;
constexpr int SM_WD = SM_W, SM_XS = SM_W + 49152, SM_AC = SM_ZS, SM_RED = SM_AC + 6144, SM_LIST = SM_TAP;
constexpr int SM_TSB = SM_END, SM_TOTAL = SM_END + TSX - SM0;
static_assert(SM_W % 1024 == 0 && SM_MODS + 8 * KTAB <= SM_ZS && SM_ZS + 2 * KTAB <= SM_TAP && SM_RED + 10240 <= SM_TAP && SM_XS + 8 * ROW <= SM_ZS, "smem map");
static_assert(SM_MB % 16 == 0 && SM_THR % 16 == 0 && SM_ST % 16 == 0 && SM_SP % 16 == 0 && SM_TOTAL <= 232448, "smem map");
constexpr int TE = 4, TO = 276, T5 = 560, T3 = 624, T9E = 680, T7E = 760, TEO = 40;
#define UPM 2
#define PFD 1
#define MT 10
#define DECL 1
#define DG 0
#define MKT 0
#define DX 0
#define DMOD 1000
#define PFG 1
constexpr int SPIN = 1 << 16, NEARLY = 4;
constexpr u32 TAGM = 0x40004000u, TAGR = 0x40000000u, INVAL = 0x00004801u;

DEV u32 s2u(const void* p) { return (u32)__cvta_generic_to_shared(p); }
DEV void mma_bf(float (&c)[4], u32 a0, u32 a1, u32 a2, u32 a3, u32 b0, u32 b1) {
  asm("mma.sync.aligned.m16n8k16.row.col.f32.bf16.bf16.f32 {%0,%1,%2,%3},{%4,%5,%6,%7},{%8,%9},{%0,%1,%2,%3};"
      : "+f"(c[0]), "+f"(c[1]), "+f"(c[2]), "+f"(c[3]) : "r"(a0), "r"(a1), "r"(a2), "r"(a3), "r"(b0), "r"(b1));
}
DEV void mma_hf(float (&c)[4], u32 a0, u32 a1, u32 a2, u32 a3, u32 b0, u32 b1) {
  asm("mma.sync.aligned.m16n8k16.row.col.f32.f16.f16.f32 {%0,%1,%2,%3},{%4,%5,%6,%7},{%8,%9},{%0,%1,%2,%3};"
      : "+f"(c[0]), "+f"(c[1]), "+f"(c[2]), "+f"(c[3]) : "r"(a0), "r"(a1), "r"(a2), "r"(a3), "r"(b0), "r"(b1));
}
DEV void mma8_bf(float (&c)[4], u32 a0, u32 a1, u32 b0) {
  asm("mma.sync.aligned.m16n8k8.row.col.f32.bf16.bf16.f32 {%0,%1,%2,%3},{%4,%5},{%6},{%0,%1,%2,%3};"
      : "+f"(c[0]), "+f"(c[1]), "+f"(c[2]), "+f"(c[3]) : "r"(a0), "r"(a1), "r"(b0));
}
DEV void mma8_hf(float (&c)[4], u32 a0, u32 a1, u32 b0) {
  asm("mma.sync.aligned.m16n8k8.row.col.f32.f16.f16.f32 {%0,%1,%2,%3},{%4,%5},{%6},{%0,%1,%2,%3};"
      : "+f"(c[0]), "+f"(c[1]), "+f"(c[2]), "+f"(c[3]) : "r"(a0), "r"(a1), "r"(b0));
}
DEV u32 movm(u32 x) { u32 r; asm("movmatrix.sync.aligned.m8n8.trans.b16 %0,%1;" : "=r"(r) : "r"(x)); return r; }
DEV uint4 ldsm4(u32 a) { uint4 r; asm volatile("ldmatrix.sync.aligned.m8n8.x4.shared.b16 {%0,%1,%2,%3},[%4];" : "=r"(r.x), "=r"(r.y), "=r"(r.z), "=r"(r.w) : "r"(a)); return r; }
DEV uint4 ldsm4t(u32 a) { uint4 r; asm volatile("ldmatrix.sync.aligned.m8n8.x4.trans.shared.b16 {%0,%1,%2,%3},[%4];" : "=r"(r.x), "=r"(r.y), "=r"(r.z), "=r"(r.w) : "r"(a)); return r; }
DEV u32 lds32(u32 a) { u32 r; asm volatile("ld.volatile.shared.u32 %0,[%1];" : "=r"(r) : "r"(a)); return r; }
DEV uint2 lds64(u32 a) { uint2 r; asm volatile("ld.shared.v2.u32 {%0,%1},[%2];" : "=r"(r.x), "=r"(r.y) : "r"(a)); return r; }
DEV uint4 lds128(u32 a) { uint4 r; asm volatile("ld.shared.v4.u32 {%0,%1,%2,%3},[%4];" : "=r"(r.x), "=r"(r.y), "=r"(r.z), "=r"(r.w) : "r"(a)); return r; }
DEV void sts16(u32 a, u32 v) { asm volatile("st.shared.u16 [%0],%1;" ::"r"(a), "h"((unsigned short)v) : "memory"); }
DEV void sts32(u32 a, u32 v) { asm volatile("st.shared.u32 [%0],%1;" ::"r"(a), "r"(v) : "memory"); }
DEV void sts64(u32 a, u32 x, u32 y) { asm volatile("st.shared.v2.u32 [%0],{%1,%2};" ::"r"(a), "r"(x), "r"(y) : "memory"); }
DEV void sts128(u32 a, u32 x, u32 y, u32 z, u32 w) { asm volatile("st.shared.v4.u32 [%0],{%1,%2,%3,%4};" ::"r"(a), "r"(x), "r"(y), "r"(z), "r"(w) : "memory"); }
DEV uint4 ldr128(const void* p) { uint4 v; asm volatile("ld.relaxed.gpu.global.v4.u32 {%0,%1,%2,%3},[%4];" : "=r"(v.x), "=r"(v.y), "=r"(v.z), "=r"(v.w) : "l"(p) : "memory"); return v; }
DEV uint2 ldr64(const void* p) { uint2 v; asm volatile("ld.relaxed.gpu.global.v2.u32 {%0,%1},[%2];" : "=r"(v.x), "=r"(v.y) : "l"(p) : "memory"); return v; }
DEV u32 ldr32(const void* p) { u32 v; asm volatile("ld.relaxed.gpu.global.u32 %0,[%1];" : "=r"(v) : "l"(p) : "memory"); return v; }
DEV void str128(void* p, u32 x, u32 y, u32 z, u32 w) { asm volatile("st.relaxed.gpu.global.v4.u32 [%0],{%1,%2,%3,%4};" ::"l"(p), "r"(x), "r"(y), "r"(z), "r"(w) : "memory"); }
DEV void str64(void* p, u32 x, u32 y) { asm volatile("st.relaxed.gpu.global.v2.u32 [%0],{%1,%2};" ::"l"(p), "r"(x), "r"(y) : "memory"); }
DEV void str32(void* p, u32 x) { asm volatile("st.relaxed.gpu.global.u32 [%0],%1;" ::"l"(p), "r"(x) : "memory"); }
DEV void str16(void* p, u32 x) { asm volatile("st.relaxed.gpu.global.u16 [%0],%1;" ::"l"(p), "h"((unsigned short)x) : "memory"); }
DEV uint4 ldg128(const void* p) { uint4 v; asm volatile("ld.global.nc.v4.u32 {%0,%1,%2,%3},[%4];" : "=r"(v.x), "=r"(v.y), "=r"(v.z), "=r"(v.w) : "l"(p)); return v; }
DEV uint2 ldg64(const void* p) { uint2 v; asm volatile("ld.global.nc.v2.u32 {%0,%1},[%2];" : "=r"(v.x), "=r"(v.y) : "l"(p)); return v; }
DEV u32 ldg32(const void* p) { u32 v; asm volatile("ld.global.nc.u32 %0,[%1];" : "=r"(v) : "l"(p)); return v; }
DEV u32 ldg16(const void* p) { unsigned short v; asm volatile("ld.global.nc.u16 %0,[%1];" : "=h"(v) : "l"(p)); return v; }
#define bsync(id, n) asm volatile("bar.sync %0,%1;" ::"n"(id), "n"(n) : "memory")
#define barrive(id, n) asm volatile("bar.arrive %0,%1;" ::"n"(id), "n"(n) : "memory")
DEV void mb_init(u32 a) { asm volatile("mbarrier.init.shared.b64 [%0],1;" ::"r"(a) : "memory"); }
DEV void mb_expect(u32 a, u32 bytes) { asm volatile("mbarrier.arrive.expect_tx.shared.b64 _,[%0],%1;" ::"r"(a), "r"(bytes) : "memory"); }
DEV void mb_wait(u32 a, u32 ph = 0) {
  u32 ok; int it = 0;
  do { asm volatile("{.reg .pred p; mbarrier.try_wait.parity.shared.b64 p,[%1],%2; selp.u32 %0,1,0,p;}" : "=r"(ok) : "r"(a), "r"(ph) : "memory"); } while (!ok && ++it < SPIN);
}
template <int N> DEV void bulk_out(void* dst, u32 src) { asm volatile("cp.async.bulk.global.shared::cta.bulk_group [%0],[%1],%2;" ::"l"(dst), "r"(src), "n"(N) : "memory"); }
constexpr u32 WSH = 41472;
template <int N> DEV void l2_pre(const void* p) { asm volatile("cp.async.bulk.prefetch.L2.global [%0],%1;" ::"l"(p), "n"(N) : "memory"); }
DEV void tma3d(u32 dst, const CUtensorMap* tm, u32 mb, int c0, int c2) {
  asm volatile("cp.async.bulk.tensor.3d.shared::cluster.global.mbarrier::complete_tx::bytes [%0],[%1,{%3,0,%4}],[%2];"
               ::"r"(dst), "l"((uint64_t)tm), "r"(mb), "r"(c0), "r"(c2) : "memory");
}
DEV float blo(u32 w) { return __uint_as_float(w << 16); }
DEV float bhi(u32 w) { return __uint_as_float(w & 0xffff0000u); }
DEV u32 pk_bf(float lo, float hi) { u32 r; asm("cvt.rn.bf16x2.f32 %0,%1,%2;" : "=r"(r) : "f"(hi), "f"(lo)); return r; }
DEV u32 pk_hf(float lo, float hi) { u32 r; asm("cvt.rn.f16x2.f32 %0,%1,%2;" : "=r"(r) : "f"(hi), "f"(lo)); return r; }
DEV float rbf(float x) { return __uint_as_float(pk_bf(0.f, x) & 0xffff0000u); }
DEV u32 bfma(u32 a, u32 b, u32 c) { u32 r; asm("fma.rn.bf16x2 %0,%1,%2,%3;" : "=r"(r) : "r"(a), "r"(b), "r"(c)); return r; }
DEV u32 bmul(u32 a, u32 b) { u32 r; asm("mul.rn.bf16x2 %0,%1,%2;" : "=r"(r) : "r"(a), "r"(b)); return r; }
DEV u32 badd(u32 a, u32 b) { u32 r; asm("add.rn.bf16x2 %0,%1,%2;" : "=r"(r) : "r"(a), "r"(b)); return r; }
DEV u32 hadd(u32 a, u32 b) { u32 r; asm("add.rn.f16x2 %0,%1,%2;" : "=r"(r) : "r"(a), "r"(b)); return r; }
DEV u32 hfma(u32 a, u32 b, u32 c) { u32 r; asm("fma.rn.f16x2 %0,%1,%2,%3;" : "=r"(r) : "r"(a), "r"(b), "r"(c)); return r; }
struct C2 { u32 re, im; };
DEV C2 cm2(C2 a, C2 b) {
  const __half2 ar = *reinterpret_cast<__half2*>(&a.re), ai = *reinterpret_cast<__half2*>(&a.im), br = *reinterpret_cast<__half2*>(&b.re), bi = *reinterpret_cast<__half2*>(&b.im);
  __half2 re = __hfma2(ar, br, __hneg2(__hmul2(ai, bi))), im = __hfma2(ar, bi, __hmul2(ai, br));
  return {*reinterpret_cast<u32*>(&re), *reinterpret_cast<u32*>(&im)};
}
DEV C2 pk2(const float2 (&a)[2]) { return {pk_hf(a[0].x, a[1].x), pk_hf(a[0].y, a[1].y)}; }
DEV C2 pk2c(const float2 (&a)[2]) { return {pk_hf(a[0].x, a[1].x), pk_hf(-a[0].y, -a[1].y)}; }
DEV u32 cpy(u32 x, u32 zr, int alt) {
  u32 r;
  if (alt) asm volatile("xor.b32 %0,%1,%2;" : "=r"(r) : "r"(x), "r"(zr)); else asm volatile("mad.lo.u32 %0,%2,%2,%1;" : "=r"(r) : "r"(x), "r"(zr));
  return r;
}
DEV u32 opq(u32 x) { u32 r; asm volatile("mov.u32 %0,%1;" : "=r"(r) : "r"(x)); return r; }
DEV u32 row16(u32 lane) { const u32 r0 = (lane & 7) + ((lane >> 3) & 1) + 8 * (lane >> 4) - 1; return (r0 ^ ((r0 >> 3) & 3)) * 16; }
DEV u32 clk() { u32 r; asm volatile("mov.u32 %0,%%clock;" : "=r"(r)::"memory"); return r; }
DEV float ex2(float x) { float r; asm("ex2.approx.ftz.f32 %0,%1;" : "=f"(r) : "f"(x)); return r; }
DEV float rcpf(float x) { float r; asm("rcp.approx.ftz.f32 %0,%1;" : "=f"(r) : "f"(x)); return r; }
DEV float2 cmul(float2 a, float2 b) { return make_float2(fmaf(a.x, b.x, -a.y * b.y), fmaf(a.x, b.y, a.y * b.x)); }
DEV float2 csq(float2 a) { return make_float2(fmaf(a.x, a.x, -a.y * a.y), (a.x + a.x) * a.y); }
DEV float2 cexp(float lr2, float th) {
  const float m = ex2(lr2);
  return make_float2(m * __cosf(th), m * __sinf(th));
}
DEV float silu_f(float v) { return v * rcpf(1.f + ex2(-1.4426950408889634f * v)); }
constexpr u32 B2P64 = 0x5F805F80u, B2M64 = 0x1F801F80u, BONE = 0x3F803F80u;
constexpr u32 MODJ = 18 * 128;
DEV float sqrta(float x) { float r; asm("sqrt.approx.ftz.f32 %0,%1;" : "=f"(r) : "f"(x)); return r; }
DEV u32 fu(float x) { return __float_as_uint(x); }
DEV float uf(u32 x) { return __uint_as_float(x); }
DEV void mma_hf_o(float (&d)[4], const float (&c)[4], const u32 (&a)[4], u32 b0, u32 b1) {
  asm("mma.sync.aligned.m16n8k16.row.col.f32.f16.f16.f32 {%0,%1,%2,%3},{%4,%5,%6,%7},{%8,%9},{%10,%11,%12,%13};"
      : "=f"(d[0]), "=f"(d[1]), "=f"(d[2]), "=f"(d[3]) : "r"(a[0]), "r"(a[1]), "r"(a[2]), "r"(a[3]), "r"(b0), "r"(b1), "f"(c[0]), "f"(c[1]), "f"(c[2]), "f"(c[3]));
}

DEV void mma_hf_t(float (&c)[4], const u32 (&a)[4], u32 b0, u32 b1) { mma_hf(c, a[0], a[1], a[2], a[3], b0, b1); }
DEV void cpa16(u32 dst, const void* src) { asm volatile("cp.async.cg.shared.global [%0],[%1],16;" ::"r"(dst), "l"(src) : "memory"); }
DEV void tm_pre(const CUtensorMap* tm) { asm volatile("prefetch.tensormap [%0];" ::"l"((uint64_t)tm) : "memory"); }
#define PROXY_FENCE() asm volatile("fence.proxy.async.shared::cta;" ::: "memory")
struct Prm {
  const char *la, *ai, *cr, *ci, *ldt;
  u32 zero;
  const char *x, *c;
  char* gs;
  const char *dsk, *wr, *wg, *wu, *wd;
  char* out;
};
constexpr float LOG2E = 1.4426950408889634f, F2P64 = 1.8446744073709552e19f, F2M64 = 5.421010862427522e-20f;

template <int S> DEV void y_store(float c0, float c1, float c2, float c3, u32 F, u32 pml, char* yp) {
  str32(yp, bmul(pk_bf(c0, c2), F) | pml);
  str32(yp + S, bmul(pk_bf(c1, c3), F) | pml);
}
#define POLL(load, cond_bad, code) { int it_ = 0; do { load; if (++it_ > SPIN) { ERRF(code); break; } } while (__any_sync(~0u, (cond_bad))); }
#define POLLW(load, cond_bad, code) { int it_ = 0; while (__any_sync(~0u, (cond_bad))) { if (++it_ > SPIN) { ERRF(code); break; } load; } }

DEV void post_conv(const Prm& p, const CUtensorMap* tm_down, const u32 tid, const u32 b, const u32 ep) {
  const u32 w = tid >> 5, lane = tid & 31;
  const u32 g = lane >> 2, q = lane & 3, e = g >> 2, h = (g >> 1) & 1, hi = g & 1;
  const u32 rho = b & 1, par = (ep + 1) & 1, pm = par ? TAGM : 0;
  char* const gs = p.gs;
  const u32 cho = 128 * w + 64 * e + 16 * q;
  u32 x1[4][4], h2[4][4], key[4], lt;
  char* const rowp = gs + (b * BLK + (4 * h + 8 * hi) * 1152 + cho);
  if (w < 9) {
    const u32 yc = 8 * (q >> 1) + 2 * (g >> 1), y1 = w < 8 ? 64 : 4 * BLK, y2 = w < 8 ? BLK : 8 * BLK;
    const char* ysrc = gs + (G_Y + (q & 1) * 16 + (w < 8 ? (16 * w + yc) * BLK + b * 128 + hi * 32 : (8 * yc + 2 * hi + ((b >> 4) & 1)) * BLK + 16384 + ((b >> 5) * 16 + (b & 15)) * 32));
    const char* const ys[4] = {ysrc, ysrc + y1, ysrc + y2, ysrc + (y1 + y2)};
    uint4 yv[4];
    if (w < 4) {
#pragma unroll
      for (int v = 0; v < 4; v++) yv[v] = ldr128(ys[v]);
    } else {
#pragma unroll
      for (int v = 0; v < 4; v++) yv[v].x = INVAL;
    }
    const u32 ma = SM_MODS + cho, xa = SM_XST + (2 * h + 4 * hi) * ROW + cho;
    const uint4 sa = lds128(ma), ca = lds128(ma + 1152), ga = lds128(ma + 2304), dk = lds128(ma + 6912);
    const uint4 rb = lds128((g & 2) ? SM_ONE + 16 * hi : (ma ^ 64) + 8064 + 1152 * hi);
    const u32 saw[4] = {sa.x, sa.y, sa.z, sa.w}, caw[4] = {ca.x, ca.y, ca.z, ca.w}, gaw[4] = {ga.x, ga.y, ga.z, ga.w}, dw[4] = {dk.x, dk.y, dk.z, dk.w};
    u32 hD[4][4];
#pragma unroll
    for (int k = 0; k < 4; k++) {
      const uint4 st = lds128(SM_ST + 16 * (2 * h + 4 * hi + (k & 1) + 8 * (k >> 1))), xv = lds128(xa + ((k & 1) + 8 * (k >> 1)) * ROW);
      x1[k][0] = xv.x; x1[k][1] = xv.y; x1[k][2] = xv.z; x1[k][3] = xv.w;
#pragma unroll
      for (int v = 0; v < 4; v++) {
        const u32 d = badd(x1[k][v], st.x), z = bfma(d, st.y, bmul(d, st.z));
        hD[k][v] = bmul(badd(bmul(z, caw[v]), saw[v]), dw[v]);
      }
    }
    const bool own = (q >> 1) == e;
    const u32 spw = SM_SP + (2 * w + e) * 320 + (g & 3) * 16 + (own ? ((q & 1) == h ? 4 : 12) : 8 - 8 * (q & 1));
    TS(18);
    if (w >= 4) bsync(12, 288);
    POLLW(_Pragma("unroll") for (int v = 0; v < 4; v++) if ((yv[v].x ^ pm) & TAGM) yv[v] = ldr128(ys[v]),
          ((yv[0].x ^ pm) | (yv[1].x ^ pm) | (yv[2].x ^ pm) | (yv[3].x ^ pm)) & TAGM, 5);
    TS(19);
    if (DECL && w < 4) asm volatile("setmaxnreg.dec.sync.aligned.u32 168;");
#pragma unroll
    for (int k = 0; k < 4; k += 2) {
      float X[4] = {}, Y[4] = {}, R[4] = {};
#pragma unroll
      for (int v = 0; v < 4; v++) {
        const u32 y0 = k ? yv[v].z : yv[v].x & ~TAGM, y1 = k ? yv[v].w : yv[v].y;
        x1[k][v] = badd(x1[k][v], bmul(gaw[v], bfma(movm(y0), B2P64, hD[k][v])));
        x1[k + 1][v] = badd(x1[k + 1][v], bmul(gaw[v], bfma(movm(y1), B2P64, hD[k + 1][v])));
        mma8_bf(X, x1[k][v], x1[k + 1][v], x1[k][v]); mma8_bf(Y, x1[k][v], x1[k + 1][v], x1[k + 1][v]);
        if (v & 1) mma_bf(R, x1[k][v - 1], x1[k + 1][v - 1], x1[k][v], x1[k + 1][v], v & 2 ? rb.z : rb.x, v & 2 ? rb.w : rb.y);
      }
      sts32(spw + k * 64, fu(own ? (hi ? X[1] : X[0]) : R[0] + R[1]));
      sts32(spw + k * 64 + 64, fu(own ? (hi ? Y[3] : Y[2]) : R[2] + R[3]));
    }
    barrive(1, 320);
    TS(36);
    const uint4 sb = lds128(ma + 3456), cb = lds128(ma + 4608), gb = lds128(ma + 5760);
    const u32 sbw[4] = {sb.x, sb.y, sb.z, sb.w}, cbw[4] = {cb.x, cb.y, cb.z, cb.w}, gbw[4] = {gb.x, gb.y, gb.z, gb.w};
    bsync(2, 320);
    TS(37);
    lt = lds32(SM_THR + 36);
#pragma unroll
    for (int k = 0; k < 4; k++) {
      const uint4 st = lds128(SM_ST2 + 64 * k + 16 * (g & 3));
      key[k] = st.w;
      u32 o[4];
#pragma unroll
      for (int v = 0; v < 4; v++) {
        const u32 d = badd(x1[k][v], st.x), z = bfma(d, st.y, bmul(d, st.z));
        h2[k][v] = badd(bmul(z, cbw[v]), sbw[v]);
        o[v] = badd(x1[k][v], bmul(gbw[v], h2[k][v]));
      }
      h2[k][0] = bmul(h2[k][0], B2M64) | TAGR;
      if (key[k] >= lt) str128(rowp + k * 1152, h2[k][0], h2[k][1], h2[k][2], h2[k][3]);
      sts128(xa + ((k & 1) + 8 * (k >> 1)) * ROW, o[0], o[1], o[2], o[3]);
    }
    barrive(3, 320);
    TS(21);
  } else if (w == 10) {
    uint2 rc = lds64(SM_RC + 8 * min(lane, 17u));
    float r1 = lane < 18 ? uf(rc.x) : 0.f, r2 = lane < 18 ? uf(rc.y) : 0.f;
#pragma unroll 1
    for (int o = 16; o; o >>= 1) { r1 += __shfl_xor_sync(~0u, r1, o); r2 += __shfl_xor_sync(~0u, r2, o); }
    const u32 tl = 4 * ((lane >> 1) & 1) + ((lane >> 2) & 3) + 8 * (lane & 1), kl = (2047 - 16 * b - tl) << 2 | par * 3;
    const u32 row = SM_XST + ((lane & 2) + 4 * (lane & 1) + ((lane >> 2) & 1) + (lane & 8)) * ROW;
    char* const op = p.out + (b * BLK + tl * 1152);
    const u32 spr = SM_SP + (lane >> 4) * 9 * 320 + (lane & 15) * 16;
    TS(31);
    bsync(1, 320);
    barrive(7, 64);
    float S1 = 0.f, S2 = 0.f, S3 = 0.f;
#pragma unroll
    for (int i = 0; i < 9; i++) { uint4 t = lds128(spr + i * 320); S1 += uf(t.x); S2 += uf(t.y); S3 += uf(t.z); }
    S1 += __shfl_xor_sync(~0u, S1, 16); S2 += __shfl_xor_sync(~0u, S2, 16); S3 += __shfl_xor_sync(~0u, S3, 16);
    const float mu = S1 * (1.f / 576.f), var = fmaxf(fmaf(-mu, mu, S2 * (1.f / 576.f)), 0.f);
    const float m = rbf(mu), rs = rcpf(rbf(sqrta(rbf(rbf(var) + 1e-5f))));
    const u32 rb = pk_bf(0.f, fmaf(fmaf(-m, r1, S3), rs, r2) + 0.f);
    const u32 ok = ((rb ^ (((int)rb >> 31) | 0x80000000)) & 0xffff0000u) | kl;
    if (lane < 16) str32(gs + (G_KEY + b * 128 + 4 * lane), ok);
    TS(20);
    const float rh = rbf(rs);
    sts128(SM_ST2 + 16 * (lane & 15), pk_bf(-m, -m), pk_bf(rh, rh), pk_bf(rs - rh, rs - rh), ok);
    sts32(SM_KEY + 4 * (lane & 15), ok);
    __syncwarp();
    const uint4 o0 = lds128(SM_KEY + 2 * (lane & 16)), o1 = lds128(SM_KEY + 2 * (lane & 16) + 16);
    u32 lr = (o0.x > ok) + (o0.y > ok) + (o0.z > ok) + (o0.w > ok) + (o1.x > ok) + (o1.y > ok) + (o1.z > ok) + (o1.w > ok);
    lr += __shfl_xor_sync(~0u, lr, 16);
    if (lr == NEARLY - 1) sts32(SM_THR + 36, ok);
    barrive(2, 320);
    bsync(3, 320);
    PROXY_FENCE();
    if (lane < 16 && lr >= 8) bulk_out<1152>(op, row);
    bsync(6, 320);
    if (lane < 16 && lr < 8 && ok < lds32(SM_SLOT + 28)) bulk_out<1152>(op, row);
    asm volatile("cp.async.bulk.commit_group;" ::: "memory");
  }
  uint4 rv[3];
  const char* rs_;
  if (w < 8) {
    const char* ks = gs + (G_KEY + (8 * g + w) * 128 + q * 16);
    const u32 kt = par * 3;
    uint4 ka, kc;
    POLL({ ka = ldr128(ks); kc = ldr128(ks + 8192); }, ((ka.x ^ kt) | (kc.x ^ kt)) & 3, 6);
    TS(23);
    const u32 kk[8] = {ka.x, ka.y, ka.z, ka.w, kc.x, kc.y, kc.z, kc.w};
    u32 mx = max(max(max(kk[0], kk[1]), max(kk[2], kk[3])), max(max(kk[4], kk[5]), max(kk[6], kk[7])));
#pragma unroll
    for (int o = 4; o < 32; o *= 2) mx = max(mx, __shfl_xor_sync(~0u, mx, o));
    if (lane < 4) asm volatile("red.shared.max.u32 [%0],%1;" ::"r"(SM_THR + 16 * (w & 1) + 4 * lane), "r"(mx) : "memory");
    bsync(4, 256);
    TS(33);
    const uint4 t0 = lds128(SM_THR), t1 = lds128(SM_THR + 16);
    u32 L0 = min(min(min(t0.x, t0.y), min(t0.z, t0.w)), min(min(t1.x, t1.y), min(t1.z, t1.w)));
#pragma unroll 1
    for (int it = 0; it < 128; it++) {
      u32 c = 0;
#pragma unroll
      for (int j = 0; j < 8; j++) c += kk[j] >= L0 ? 4 : 0;
      if (c) {
        u32 a;
        asm volatile("atom.shared.add.u32 %0,[%1],%2;" : "=r"(a) : "r"(SM_THR + 32), "r"(c) : "memory");
#pragma unroll
        for (int j = 0; j < 8; j++) if (kk[j] >= L0) { sts32(SM_LIST + a, kk[j]); a += 4; }
      }
      bsync(5, 256);
      TS(38);
      const u32 n = lds32(SM_THR + 32), m0 = lds32(SM_LIST + 4 * lane), my = 4 * lane < n ? m0 : 0;
      const uint4 cd = lds128(SM_LIST + 16 * w);
      const u32 cc[4] = {cd.x, cd.y, cd.z, cd.w};
#pragma unroll
      for (int j = 0; j < 4; j++) {
        const u32 r = __popc(__ballot_sync(~0u, my > cc[j]));
        if (r < 8 && 16 * w + 4 * j < n) sts32(SM_SLOT + 4 * r, cc[j]);
      }
      if (n <= 128) break;
      bsync(15, 256);
      L0 = lds32(SM_SLOT + 28);
      sts32(SM_THR + 32, 0);
      bsync(15, 256);
    }
  }
  if (w < 9) {
    bsync(6, 320);
    TS(24);
    const u32 g8 = lds32(SM_SLOT + 28);
    if (w < 8) {
      rs_ = gs + ((2047 - ((lds32(SM_SLOT + 4 * w) >> 2) & 2047)) * 1152 + lane * 16);
      rv[0] = ldr128(rs_); rv[1] = ldr128(rs_ + 512);
      rv[2].x = TAGR;
      if (lane < 8) rv[2] = ldr128(rs_ + 1024);
    }
    if (__any_sync(~0u, max(max(key[0], key[1]), max(key[2], key[3])) >= g8)) {
#pragma unroll
      for (int k = 0; k < 4; k++) if (key[k] >= g8) {
        if (key[k] < lt) str128(rowp + k * 1152, h2[k][0], h2[k][1], h2[k][2], h2[k][3]);
        str128(rowp + (G_Y + k * 1152), bmul(x1[k][0], B2M64) | TAGR, x1[k][1], x1[k][2], x1[k][3]);
      }
    }
  }
  asm volatile("setmaxnreg.inc.sync.aligned.u32 168;");
  const u32 kq = w & 3, tg = 2 - (w >> 2);
  uint4 A[24];
  {
    const u32 row = 144 * kq + 8 * (lane >> 4) + (lane & 7), ab = (lane & 8) ? SM_UP : SM_GATE;
    mb_wait(SM_MB + 8); mb_wait(SM_MB + 16);
    if (tg < 2) {
      const u32 aa = ab + row * 64 + (((2 * tg) ^ ((lane & 7) >> 1)) << 4);
#pragma unroll
      for (int s = 0; s < 9; s++) { A[s] = ldsm4t(aa + s * 1024); A[9 + s] = ldsm4t((aa ^ 16) + s * 1024); }
    } else {
#pragma unroll
      for (int s = 0; s < 9; s++) A[s] = ldsm4t(ab + SLV + row * 16 + s * 256);
    }
  }
  TS(22);
  if (w == 9) {
    bsync(7, 64);
    if (lane == 0 && b < 108) {
      PROXY_FENCE();
#pragma unroll 1
      for (int i = 0; i < 4; i++) {
        if (i) mb_wait(SM_MB + 24, ~i & 1);
        mb_expect(SM_MB + 24, 12288);
        tma3d(SM_WD + 12288 * i, tm_down, SM_MB + 24, 64 * (b % 9), 4 * (b / 9) + i);
      }
    }
    __syncwarp();
    TS(13);
  }
  if (w < 8) {
    POLLW({ rv[0] = ldr128(rs_); rv[1] = ldr128(rs_ + 512); if (lane < 8) rv[2] = ldr128(rs_ + 1024); },
          ((rv[0].x ^ TAGR) | (rv[1].x ^ TAGR) | (rv[2].x ^ TAGR)) & TAGM, 8);
#pragma unroll
    for (int j = 0; j < 3; j++) if (j < 2 || lane < 8) sts128(SM_XS + w * ROW + lane * 16 + j * 512, bmul(rv[j].x ^ TAGR, B2P64), rv[j].y, rv[j].z, rv[j].w);
  }
  __syncthreads();
  TS(25);
  {
    float c0[2][4] = {}, c1[2][4] = {};
    const u32 ba = SM_XS + (lane & 7) * ROW + (18 * kq + (lane >> 3)) * 16;
    uint4 bb[5];
#pragma unroll
    for (int s = 0; s < 5; s++) bb[s] = ldsm4(ba + s * 64);
#pragma unroll
    for (int s = 0; s < 9; s++) mma_bf(c0[s & 1], A[s].x, A[s].y, A[s].z, A[s].w, s & 1 ? bb[s >> 1].z : bb[s >> 1].x, s & 1 ? bb[s >> 1].w : bb[s >> 1].y);
    const u32 ra = SM_RED + (8 * tg + kq) * 512 + lane * 16;
    if (tg < 2) {
#pragma unroll
      for (int s = 0; s < 9; s++) mma_bf(c1[s & 1], A[9 + s].x, A[9 + s].y, A[9 + s].z, A[9 + s].w, s & 1 ? bb[s >> 1].z : bb[s >> 1].x, s & 1 ? bb[s >> 1].w : bb[s >> 1].y);
      sts128(ra + 2048, fu(c1[0][0] + c1[1][0]), fu(c1[0][1] + c1[1][1]), fu(c1[0][2] + c1[1][2]), fu(c1[0][3] + c1[1][3]));
    }
    sts128(ra, fu(c0[0][0] + c0[1][0]), fu(c0[0][1] + c0[1][1]), fu(c0[0][2] + c0[1][2]), fu(c0[0][3] + c0[1][3]));
  }
  TS(39);
  __syncthreads();
  if (w >= 7 + rho) {
    const u32 t = 11 - w;
    float s[4] = {};
#pragma unroll
    for (int i = 0; i < 4; i++) { const uint4 u = lds128(SM_RED + (t * 4 + i) * 512 + lane * 16); s[0] += uf(u.x); s[1] += uf(u.y); s[2] += uf(u.z); s[3] += uf(u.w); }
    const u32 sg = pk_bf(silu_f(rbf(s[0])), silu_f(rbf(s[1])));
    const u32 act = movm(bmul(bmul(sg, pk_bf(s[2], s[3])), B2M64));
    str32(gs + (G_ACT + (t < 4 ? 4 * b + t : 512 + (b >> 1)) * 128 + lane * 4), act | (q ? 0 : pm));
  }
  TS(26);
  if (b < 108) {
    const char* src = gs + (G_ACT + (b / 9) * 6144 + tid * 16);
    uint4 a = ldr128(src);
    if (w < 4) {
      const u32 aa = SM_WD + (8 * (lane >> 4) + (lane & 7)) * 128 + (((2 * w + ((lane >> 3) & 1)) ^ (lane & 7)) << 4);
      mb_wait(SM_MB + 24, 1);
#pragma unroll
      for (int s = 0; s < 24; s++) A[s] = ldsm4t(aa + s * 2048);
    }
    TS(28);
    POLLW(a = ldr128(src), (a.x ^ pm) & TAGM, 9);
    sts128(SM_AC + tid * 16, a.x & ~TAGM, a.y, a.z, a.w);
    TS(27);
    if (w < 4) {
      bsync(8, 384);
      float c[4][4] = {};
#pragma unroll
      for (int s = 0; s < 12; s++) {
        const uint4 bb = ldsm4(SM_AC + lane * 16 + s * 512);
        mma_bf(c[2 * (s & 1)], A[2 * s].x, A[2 * s].y, A[2 * s].z, A[2 * s].w, bb.x, bb.y);
        mma_bf(c[2 * (s & 1) + 1], A[2 * s + 1].x, A[2 * s + 1].y, A[2 * s + 1].z, A[2 * s + 1].w, bb.z, bb.w);
      }
      char* dst = gs + (G_PART + b * 2048 + w * 512 + lane * 8);
      u32 o[4];
#pragma unroll
      for (int i = 0; i < 4; i++) o[i] = (fu(((c[0][i] + c[1][i]) + (c[2][i] + c[3][i])) * F2P64) & ~1u) | par;
      str64(dst, o[0], o[1]); str64(dst + 256, o[2], o[3]);
      TS(29);
    } else barrive(8, 384);
  }
  if (w == 8 && b < 72) {
    const u32 kg = lds32(SM_SLOT + 4 * g), ro = (2047 - ((kg >> 2) & 2047)) * 1152 + 16 * b;
    const char* src = gs + (G_PART + (b >> 3) * 2048 + (b & 7) * 256 + lane * 8);
    const char* xs = gs + (G_Y + ro);
    uint4 xt;
    POLL(xt = ldr128(xs), (xt.x ^ TAGR) & TAGM, 10);
    const u32 x1w = (q & 2) ? ((q & 1) ? xt.w : xt.z) : ((q & 1) ? xt.y : bmul(xt.x ^ TAGR, B2P64));
    const u32 gw = lds32(SM_MODS + 5760 + 16 * b + 4 * q);
    const u32 hw = lds32(SM_XS + g * ROW + b * 16 + q * 4);
    const float sgm = rcpf(1.f + ex2(-LOG2E * bhi(kg ^ (~((int)kg >> 31) | 0x80000000))));
    char* const dst = p.out + (ro + 4 * q);
    uint2 v[12];
#pragma unroll
    for (int j = 0; j < 12; j++) v[j] = make_uint2(1, 0);
    u32 bad;
    POLL({ bad = 0; _Pragma("unroll") for (int j = 0; j < 12; j++) { if (((v[j].x ^ par) | (v[j].y ^ par)) & 1) v[j] = ldr64(src + j * 9 * 2048); }
           _Pragma("unroll") for (int j = 0; j < 12; j++) bad |= (v[j].x ^ par) | (v[j].y ^ par); }, bad & 1, 11);
    float s0[4] = {}, s1[4] = {};
#pragma unroll
    for (int j = 0; j < 12; j++) { s0[j & 3] += uf(v[j].x); s1[j & 3] += uf(v[j].y); }
    const u32 y = movm(pk_bf((s0[0] + s0[1]) + (s0[2] + s0[3]), (s1[0] + s1[1]) + (s1[2] + s1[3])));
    *(u32*)dst = badd(x1w, bmul(gw, badd(hw, bmul(y, pk_bf(sgm, sgm)))));
    if (b == 0 && lane == 0) str32(gs + G_EP, ep + 1);
    TS(30); TSE();
  }
  if (w == 10) asm volatile("cp.async.bulk.wait_group.read 0;" ::: "memory");
}

__global__ void __launch_bounds__(384, 1)
fused_kernel(const Prm p, const __grid_constant__ CUtensorMap tm_mod, const __grid_constant__ CUtensorMap tm_gate, const __grid_constant__ CUtensorMap tm_gs,
             const __grid_constant__ CUtensorMap tm_up, const __grid_constant__ CUtensorMap tm_us, const __grid_constant__ CUtensorMap tm_down) {
  extern __shared__ __align__(1024) unsigned char smem[];
  u32 la, ai, ldt; uint2 cr, ci;
  {
    const u32 t = threadIdx.x, d = t < 256 ? 4 * blockIdx.x + ((t >> 5) & 3) : 512 + (blockIdx.x >> 1), o = d * 256 + 8 * (t & 31), o4 = o + ((t < 256 ? t >> 5 : t >> 3) & 4);
    asm volatile("{.reg .pred p; .reg .u16 h; setp.ne.u32 p,%7,0; @p ld.global.nc.u32 %0,[%8]; @p ld.global.nc.u32 %1,[%9]; @p ld.global.nc.v2.u32 {%2,%3},[%10];"
                 "@p ld.global.nc.v2.u32 {%4,%5},[%11]; @p ld.global.nc.u16 h,[%12]; cvt.u32.u16 %6,h;}"
                 : "=r"(la), "=r"(ai), "=r"(cr.x), "=r"(cr.y), "=r"(ci.x), "=r"(ci.y), "=r"(ldt)
                 : "r"(0x6ffu >> (t >> 5) & 1), "l"(p.la + o4), "l"(p.ai + o4), "l"(p.cr + o), "l"(p.ci + o), "l"(p.ldt + 2 * d));
  }
  const u32 t0 = clk();
  const u32 tid = __shfl_sync(~0u, threadIdx.x, threadIdx.x & 31), b = blockIdx.x + p.zero;
  const u32 w = tid >> 5, lane = tid & 31;
  const u32 g = lane >> 2, q = lane & 3, hi = g & 1;
  const u32 rho = b & 1, Ps = 512 + (b >> 1);
  char* const gs = p.gs;
  TS0();
  const bool kw = w != 8 && w != 11;
  const u32 ksig = w < 8 ? (w & 3) : 4, khf = w < 8 ? (w >> 2) : (w & 1);
  if (!kw) {
    if (tid == 352) {
#pragma unroll
      for (int i = 0; i < 4; i++) mb_init(SM_MB + 8 * i);
      asm volatile("fence.mbarrier_init.release.cluster;" ::: "memory");
      tm_pre(&tm_mod);
    }
    const char* cp = p.c + (576 * (w & 1) + 24 * min(lane, 23u));
    const uint2 c0 = ldg64(cp);
    la = c0.x; ai = c0.y; cr = ldg64(cp + 8); ci = ldg64(cp + 16);
  }
  const u32 zr = tid >> 16;
  const u32 epv = ldr32(gs + (G_EP + zr));
  const u32 tp = SM_TAP + ksig * TAPS;
  if (kw && !khf) {
#pragma unroll 1
    for (u32 i = lane * 16; i < TAPS; i += 512) sts128(tp + i, 0, 0, 0, 0);
  }
  if (tid < 128) sts128(SM_INV + 16 * tid, INVAL, 0, 1, 0);
  if (tid >= 252) str128(gs + (tid >= 380 ? G_MOD + b * 128 + q * 16 : b * BLK + 16384 - 252 * 16 + tid * 16), INVAL, 0, 1, 0);
  if (tid == 352 && b < 36) { while (clk() - t0 < DMOD); mb_expect(SM_MB, 36864); tma3d(SM_UP, &tm_mod, SM_MB, 32 * b, 0); }
  if (w < 9) {
    while ((int)(clk() - t0) < DX);
    const char* xp = p.x + (b * BLK + (lane >> 3) * 1152 + 128 * w + 16 * (lane & 7));
    const u32 xd = SM_XST + (((lane >> 3) & 1) + 8 * (lane >> 4)) * ROW + 128 * w + 16 * (lane & 7);
#pragma unroll
    for (int i = 0; i < 4; i++) cpa16(xd + 2 * ROW * i, xp + 4608 * i);
  }
  const u32 ktab = w < 8 ? SM_MODS + w * KTAB : SM_ZS + (w - 9) * KTAB;
  float k2048 = 0.f;
  if (kw) {
    u32 mx = __vmaxu2(__vmaxu2(cr.x & 0x7fff7fff, cr.y & 0x7fff7fff), __vmaxu2(ci.x & 0x7fff7fff, ci.y & 0x7fff7fff));
    const u32 E = max(__reduce_max_sync(~0u, max(mx & 0xffff, mx >> 16)) >> 7, 8u);
    TS(1);
    const float dt = rbf(ex2(blo(ldt) * LOG2E)), csc = uf((257 - E) << 23 | (fu(dt) & 0x7fffff));
    sts32(SM_SC + 16 * ksig + 12, fu(uf(fu(dt) & 0x7f800000) * uf((E - 2) << 23)));
    const u32 crw = khf ? cr.y : cr.x, ciw = khf ? ci.y : ci.x;
    float2 C[2], w4[2], w8[2], w16[2], w32[2], w64[2], w128[2], w256[2], w512[2], a1[2], a2[2], a3[2], t0[2], t1[2], s3[2];
#pragma unroll
    for (int m = 0; m < 2; m++) {
      const float lr2 = rbf(ex2((m ? bhi(la) : blo(la)) * LOG2E)) * dt * -LOG2E, th = (m ? bhi(ai) : blo(ai)) * dt;
      C[m] = make_float2((m ? bhi(crw) : blo(crw)) * csc, (m ? bhi(ciw) : blo(ciw)) * csc);
      const float2 w1 = cexp(lr2, th), w2 = csq(w1);
      w64[m] = cexp(64.f * lr2, 64.f * th);
      w4[m] = csq(w2); w8[m] = csq(w4[m]); w16[m] = csq(w8[m]); w32[m] = csq(w16[m]);
      w128[m] = csq(w64[m]); w256[m] = csq(w128[m]); w512[m] = csq(w256[m]);
      const float2 w1024 = csq(w512[m]);
      a1[m] = cmul(C[m], w1); a2[m] = cmul(C[m], w2); a3[m] = cmul(a1[m], w2);
      t0[m] = cmul(C[m], w1024); t1[m] = cmul(t0[m], w128[m]); s3[m] = cmul(w8[m], w16[m]);
      k2048 += fmaf(t0[m].x, w1024.x, -t0[m].y * w1024.y);
    }
    C2 B0[8], B1[8], B2[8], S[8];
    B0[0] = pk2(C); B0[1] = pk2(a1); B0[2] = pk2(a2); B0[3] = pk2(a3);
    const C2 h4 = pk2(w4), h256 = pk2(w256), h512 = pk2(w512);
#pragma unroll
    for (int i = 0; i < 4; i++) B0[4 + i] = cm2(B0[i], h4);
#pragma unroll
    for (int i = 0; i < 4; i++) B1[i] = cm2(B0[2 * i], h256);
    B1[4] = cm2(B0[0], h512); B1[5] = cm2(B0[4], h512);
    B1[6] = cm2(B1[4], h256); B1[7] = cm2(B1[5], h256);
    const u32 ta = ktab + lane * 128, f = ((lane & 3) << 5) | ((lane & 4) << 2);
#pragma unroll
    for (int i = 0; i < 8; i++) sts128(ta + ((i << 4) ^ f), B0[i].re, B0[i].im, B1[i].re, B1[i].im);
    B2[0] = pk2(t0); B2[1] = pk2(t1);
    B2[2] = cm2(B2[0], h256); B2[3] = cm2(B2[1], h256);
#pragma unroll
    for (int i = 0; i < 4; i++) B2[4 + i] = cm2(B2[i], h512);
    S[0] = {0x3C003C00u, 0u}; S[1] = pk2c(w8); S[2] = pk2c(w16); S[3] = pk2c(s3); S[4] = pk2c(w32);
#pragma unroll
    for (int i = 1; i < 4; i++) S[4 + i] = cm2(S[i], S[4]);
#pragma unroll
    for (int i = 0; i < 8; i++) sts128(ta + 4096 + ((i << 4) ^ f), B2[i].re, B2[i].im, S[i].re, S[i].im);
    const C2 m64 = pk2c(w64), m128 = pk2c(w128);
    sts128(ktab + 8192 + lane * 16, m64.re, m64.im, m128.re, m128.im);
    __syncwarp();
  } else {
    u32 sa = SM_SIL + 576 * (w & 1) + 24 * min(lane, 23u);
#pragma unroll 1
    for (int j = 0; j < 6; j++) {
      sts32(sa, pk_bf(silu_f(blo(la)), silu_f(bhi(la))));
      la = ai; ai = cr.x; cr.x = cr.y; cr.y = ci.x; ci.x = ci.y; sa += 4;
    }
    bsync(7, 64);
  }
  TS(2);
  const u32 ep = __reduce_or_sync(~0u, epv), par = (ep + 1) & 1, pm = par ? TAGM : 0;
  if (w < 9) {
    asm volatile("cp.async.wait_all;" ::: "memory");
    __syncwarp();
    TS(4);
    if (tid == 256 && b >= 36 && b < 108) { mb_expect(SM_MB, 36864); tma3d(SM_UP, &tm_mod, SM_MB, 32 * b, 0); }
    const u32 xa = SM_XST + (lane & 15) * ROW + 128 * w + 16 * (lane >> 4);
    float s[4] = {}, X[2][4] = {}, Y[2][4] = {};
#pragma unroll
    for (int j = 0; j < 4; j++) {
      const uint4 a = ldsm4(xa + 32 * j);
      mma8_bf(X[0], a.x, a.y, a.x); mma8_bf(Y[0], a.x, a.y, a.y);
      mma8_bf(X[1], a.z, a.w, a.z); mma8_bf(Y[1], a.z, a.w, a.w);
      mma_bf(s, a.x, a.y, a.z, a.w, BONE, BONE);
    }
    uint4 t[4];
#pragma unroll
    for (int j = 0; j < 4; j++) t[j] = ldsm4t(xa + 32 * j);
    const float u0 = hi ? X[0][1] + X[1][1] : X[0][0] + X[1][0], u1 = hi ? Y[0][3] + Y[1][3] : Y[0][2] + Y[1][2];
    if (q == g >> 1) sts128(SM_SP + w * 128 + g * 16, fu(s[0]), fu(u0), fu(s[2]), fu(u1));
    bsync(1, 288);
    TS(7);
    const u32 spr = SM_SP + (lane & 7) * 16 + (lane & 8);
    const uint2 t8 = lds64(spr + 1024);
    const float f8 = lane < 16 ? 1.f : 0.f;
    float S1 = uf(t8.x) * f8, S2 = uf(t8.y) * f8;
#pragma unroll
    for (int i = 0; i < 4; i++) { const uint2 u = lds64(spr + (lane & 16) * 32 + i * 128); S1 += uf(u.x); S2 += uf(u.y); }
    S1 += __shfl_xor_sync(~0u, S1, 16); S2 += __shfl_xor_sync(~0u, S2, 16);
    const float mu = S1 * (1.f / 576.f), var = fmaxf(fmaf(-mu, mu, S2 * (1.f / 576.f)), 0.f);
    const float m = rbf(mu), rs = rcpf(rbf(sqrta(rbf(rbf(var) + 1e-5f))));
    const float ra = rs * 0.0625f;
    sts64(SM_AF + w * 128 + (lane & 15) * 8, fu(ra), fu(-m * ra));
    __syncwarp();
    TS(55);
    const uint4 f0 = lds128(SM_AF + w * 128 + q * 16), f1 = lds128(SM_AF + w * 128 + 64 + q * 16);
    const u32 zdst = SM_GATE + w * 2048 + lane * 8;
    const u32 pz = (q & 1) ? 0 : pm;
#pragma unroll
    for (int j = 0; j < 8; j++) {
      const u32 x0 = j & 1 ? t[j >> 1].z : t[j >> 1].x, x1 = j & 1 ? t[j >> 1].w : t[j >> 1].y;
      sts64(zdst + 256 * j, pk_hf(fmaf(blo(x0), uf(f0.x), uf(f0.y)), fmaf(bhi(x0), uf(f0.z), uf(f0.w))) | pz,
            pk_hf(fmaf(blo(x1), uf(f1.x), uf(f1.y)), fmaf(bhi(x1), uf(f1.z), uf(f1.w))));
    }
    TS(53);
    if (w < 8) barrive(15, 288);
    else {
      bsync(15, 288);
      TS(54);
      if (lane == 0) {
        PROXY_FENCE();
        bulk_out<BLK>(gs + b * BLK, SM_GATE);
        asm volatile("cp.async.bulk.commit_group;" ::: "memory");
        if (PFG & 1) l2_pre<WSH / 2>(p.wg + b * WSH);
      }
      const float rh = rbf(rs);
      sts128(SM_ST + 16 * (lane & 15), pk_bf(-m, -m), pk_bf(rh, rh), pk_bf(rs - rh, rs - rh), 0);
    }
    TS(5);
  }
  if (kw) {
    float D[5][4] = {};
    u32 ta = ktab + q * 128 + ((g ^ (q << 1)) << 4), tm = ktab + 8192 + q * 16;
#pragma unroll 2
    for (int s = 0; s < 8; s++) {
      const uint4 ca = lds128(ta), cb = lds128(ta + 4096), ma = lds128(tm);
      ta = (ta + 512) ^ 16; tm += 64;
      k2048 += __shfl_xor_sync(~0u, k2048, 16 >> s);
      const C2 s0 = {cb.z, cb.w}, s1 = cm2(s0, {ma.x, ma.y}), s2 = cm2(s0, {ma.z, ma.w}), s3 = cm2(s1, {ma.z, ma.w});
      mma_hf(D[0], s0.re, s1.re, s0.im, s1.im, ca.x, ca.y);
      mma_hf(D[2], s0.re, s1.re, s0.im, s1.im, ca.z, ca.w);
      mma_hf(D[4], s0.re, s1.re, s0.im, s1.im, cb.x, cb.y);
      mma_hf(D[1], s2.re, s3.re, s2.im, s3.im, ca.x, ca.y);
      mma_hf(D[3], s2.re, s3.re, s2.im, s3.im, ca.z, ca.w);
    }
    TS(3);
    const u32 xa = (w < 8 ? SM_MODS + (4 + ksig) * KTAB : SM_ZS) + lane * 16;
    if (khf) {
      __syncwarp();
#pragma unroll
      for (int j = 0; j < 5; j++) sts128(xa + 512 * j, fu(D[j][0]), fu(D[j][1]), fu(D[j][2]), fu(D[j][3]));
      if (lane == 0) sts32(xa + 2560, fu(k2048));
      asm volatile("bar.arrive %0,64;" ::"r"(2 + ksig) : "memory");
    } else {
      const u32 t1 = tp + (q < 2 ? (128 + 4 * g + 2 * q) * 4 : T3 * 4 + ((32 * q - 64 + g) ^ 1) * 2);
      const u32 x = 16 * q + (g >> 1) + hi + 1, tb = tp + (hi ? T7E : T9E) * 4 - 4;
      const u32 te = tb + (x + 2 * (x & 1)) * 2, to = tb + TEO * 4 + (x ^ 1) * 2;
      asm volatile("bar.sync %0,64;" ::"r"(2 + ksig) : "memory");
#pragma unroll
      for (int j = 0; j < 5; j++) { const uint4 t = lds128(xa + 512 * j); D[j][0] += uf(t.x); D[j][1] += uf(t.y); D[j][2] += uf(t.z); D[j][3] += uf(t.w); }
      k2048 = (k2048 + uf(lds32(xa + 2560))) * 0.125f;
#pragma unroll
      for (int r = 0; r < 4; r++) {
        const u32 v = pk_hf(D[2 + (r >> 1)][2 * (r & 1)], D[2 + (r >> 1)][2 * (r & 1) + 1]);
        if (q < 2) {
          const u32 vv = __byte_perm(v, v, 0x1010);
          sts32(t1 + (TO + 32 * r) * 4, vv); sts16(t1 + (TO + 32 * r + 1) * 4 + 2, v >> 16); sts16(t1 + (TO + 32 * r - 1) * 4, v);
          sts64(t1 + (TE + 32 * r) * 4, vv, __byte_perm(v, v, 0x1032));
        } else {
          sts16(t1 + 16 * r, v >> 16);
          if (r == 0 && lane == 2) {
            const u32 vv = __byte_perm(v, v, 0x1010);
            sts32(tp + (TO + 256) * 4, vv); sts16(tp + (TO + 257) * 4 + 2, v); sts16(tp + (TO + 255) * 4, v); sts64(tp + (TE + 256) * 4, vv, vv);
          } else sts16(t1 + 16 * r - ((T3 - T5) * 4 + 6) + 8 * hi, v);
        }
      }
#pragma unroll
      for (int r = 0; r < 2; r++) {
        const u32 v = pk_hf(D[4][2 * r], D[4][2 * r + 1]);
        if (r == 0 && lane == 0) { sts16(tp + T5 * 4 + 62 * 2, v); sts32(SM_KV + 4 * ksig, v & 0xffff); sts16(tp + (T9E + TEO) * 4 + 62 * 2, pk_hf(k2048, 0.f)); }
        else { sts16(te + 8 * r, v); sts16(to + 8 * r, v); }
        sts16(te + 8 * r + 16, v >> 16); sts16(to + 8 * r + 16, v >> 16);
      }
      __syncwarp();
#pragma unroll
      for (int r = 0; r < 4; r++) {
        const u32 v = pk_hf(D[r >> 1][2 * (r & 1) + 1], D[r >> 1][2 * (r & 1)]), t2 = tp + lane * 4 + 128 * r;
        sts32(t2 + TO * 4, v); sts16(t2 + TE * 4, v >> 16); sts16(t2 + (TE + 1) * 4 + 2, v);
      }
      __syncwarp();
    }
  } else if (w == 11 && b < 108) {
    float c[4][4] = {};
    u32 aa = SM_UP + ((lane & 7) + 8 * (lane >> 4)) * 64 + ((((lane >> 3) & 1) ^ ((lane & 7) >> 1)) << 4);
    u32 ba = SM_SIL + (lane >> 3) * 16;
    uint4 a[2][10];
#define GLD(n) { _Pragma("unroll") for (int i = 0; i < 2; i++) { a[n][5 * i] = ldsm4(ba + i * 64); \
      _Pragma("unroll") for (int k = 0; k < 4; k++) a[n][5 * i + 1 + k] = ldsm4t((k & 2 ? aa ^ 32 : aa) + i * 2048 + (k & 1) * 1024); } aa += 4096; ba += 128; }
#define GMM(n) { _Pragma("unroll") for (int i = 0; i < 2; i++) _Pragma("unroll") for (int k = 0; k < 4; k++) { const uint4 f = a[n][5 * i + 1 + k], bb = a[n][5 * i]; \
      mma_bf(c[k], f.x, f.y, f.z, f.w, k & 1 ? bb.z : bb.x, k & 1 ? bb.w : bb.y); } }
    mb_wait(SM_MB);
    TS(56);
    GLD(0);
#pragma unroll 1
    for (int s = 0; s < 4; s++) { GLD(1); GMM(0); GLD(0); GMM(1); }
    GMM(0);
    const float v0 = (q & 1) ? c[0][2] + c[1][2] : c[0][0] + c[1][0], v1 = (q & 1) ? c[2][2] + c[3][2] : c[2][0] + c[3][0];
    str16(gs + (G_MOD + b * 128 + 2 * g + 16 * q), pk_bf(rbf((q & 2) ? v1 : v0) * F2M64, 0.f) | (g < 2 ? pm : 0));
    TS(57);
  }
  TS(6);
  u32 tid2 = tid;
  if (w < 4) {
    asm volatile("setmaxnreg.inc.sync.aligned.u32 232;");
    const u32 tid = tid2 + p.zero, w = tid >> 5, lane = tid & 31, g = lane >> 2, q = lane & 3, hi = g & 1, zr = tid >> 16, tp = SM_TAP + w * TAPS;
    const u32 pml = opq((g & 3) ? 0 : pm);
    const u32 tr = tp + ((hi ? TO : TE) + (g >> 1) - q) * 4;
    u32 T[33][4], B5[5][2], B3[5][2];
#pragma unroll
    for (int d = 0; d < 33; d++) {
      T[d][0] = lds32(tr + 32 * d); T[d][1] = lds32(tr + 32 * d + 16);
      T[d][2] = cpy(d ? T[d - 1][1] : zr, zr, 0); T[d][3] = cpy(T[d][0], zr, 1);
    }
    const u32 t33 = cpy(T[32][1], zr, 0), z33 = cpy(zr, zr, 1);
    const u32 bt = tp + (T5 + g - q) * 4;
#pragma unroll
    for (int d = 0; d < 5; d++) {
      B5[d][0] = lds32(bt + 32 * d); B5[d][1] = lds32(bt + 32 * d - 16);
      B3[d][0] = lds32(bt + 32 * d + (T3 - T5) * 4); B3[d][1] = lds32(bt + 32 * d - 16 + (T3 - T5) * 4);
    }
    u32 za = opq(SM_ZS + 16 + w * ZSS + ((lane >> 3) & 1) * ZPS + ((lane & 7) + (lane >> 4)) * 16);
    u32 wa = opq(SM_W + W5O + w * WSL + row16(lane));
    u32 sa = opq(SM_W + W9O - 2048 + w * WSL + lane * 16);
    u32 yo = opq(G_Y + b * BLK + 256 * q + w * 32 + 4 * g);
    const u32 fa = opq(SM_SC + 16 * w + 8);
    TS(8);
    bsync(9, 384);
    TS(11);
    float A[4][4] = {};
    uint4 Z[4];
    Z[0] = ldsm4(za); Z[1] = ldsm4(za + 32);
    const uint2 fc = lds64(fa);
    const u32 F = __byte_perm(fu(uf(fc.x) * uf(fc.y)), 0, 0x3232);
#define STEP(s, b0, b1) { _Pragma("unroll") for (int i = 0; i < 4; i++) mma_hf_t(A[i], T[8 * i + 7 - (s)], b0, b1); }
#define PAIR(n) { Z[(n + 2) & 3] = ldsm4(za + 32 * (n + 2)); STEP(2 * n, Z[n].x, Z[n].y); STEP(2 * n + 1, Z[n].z, Z[n].w); }
#define LAST(N) mma8_hf(N, t33, z33, Z[3].y); float O[4]; mma_hf_o(O, A[0], T[0], Z[3].z, Z[3].w); \
    _Pragma("unroll") for (int i = 0; i < 3; i++) mma_hf_o(A[i], A[i + 1], T[8 * i + 8], Z[3].z, Z[3].w); \
    mma_hf_o(A[3], N, T[32], Z[3].z, Z[3].w);
#pragma unroll 1
    for (int j = 0; j < 4; j++) {
      PAIR(0); PAIR(1); PAIR(2);
      Z[1] = ldsm4(za + 160); STEP(6, Z[3].x, Z[3].y);
      float N[4] = {};
      LAST(N);
      y_store<128>(O[0], O[1], O[2], O[3], F, pml, gs + yo);
      za += 128; yo += 1024;
      TS(40 + j);
    }
    bsync(10, 352);
#pragma unroll 1
    for (int j = 4; j < 13; j++) {
      if (j == 8) bsync(14, 352);
      const uint4 a5 = ldsm4t(wa), a3 = ldsm4t(wa + (W3O - W5O));
      uint4 s3 = {0, 0, 0, 0};
      if (j >= 8) s3 = lds128(sa);
      PAIR(0);
      float N[4] = {};
#pragma unroll
      for (int i = 0; i < 4; i++) mma_hf(A[i], a5.x, a5.y, a5.z, a5.w, B5[i][0], B5[i][1]);
      mma_hf(N, a5.x, a5.y, a5.z, a5.w, B5[4][0], B5[4][1]);
      PAIR(1);
#pragma unroll
      for (int i = 0; i < 4; i++) mma_hf(A[i], a3.x, a3.y, a3.z, a3.w, B3[i][0], B3[i][1]);
      mma_hf(N, a3.x, a3.y, a3.z, a3.w, B3[4][0], B3[4][1]);
      PAIR(2);
      Z[1] = ldsm4(za + 160); STEP(6, Z[3].x, Z[3].y);
      LAST(N);
      y_store<128>(O[0] + uf(s3.x), O[1] + uf(s3.y), O[2] + uf(s3.z), O[3] + uf(s3.w), F, pml, gs + yo);
      za += 128; wa = (wa + 256) ^ 32; sa += 512; yo += 1024;
      TS(40 + j);
    }
    {
      const uint4 s3 = lds128(sa), s4 = lds128(sa + 512), s5 = lds128(sa + 1024);
      float X[3][4] = {{uf(s4.x), uf(s4.y), uf(s4.z), uf(s4.w)}, {}, {uf(s5.x), uf(s5.y), uf(s5.z), uf(s5.w)}};
#pragma unroll
      for (int ty = 0; ty < 2; ty++) {
        const uint4 a = ldsm4t(wa + ty * (W3O - W5O)), c = ldsm4t((wa ^ 32) + 256 + ty * (W3O - W5O)), d = ldsm4t(wa + 512 + ty * (W3O - W5O));
#pragma unroll
        for (int i = 0; i < 3; i++) mma_hf(A[i], a.x, a.y, a.z, a.w, ty ? B3[i][0] : B5[i][0], ty ? B3[i][1] : B5[i][1]);
#pragma unroll
        for (int i = 0; i < 2; i++) mma_hf(X[i], c.x, c.y, c.z, c.w, ty ? B3[i][0] : B5[i][0], ty ? B3[i][1] : B5[i][1]);
        mma_hf(X[2], d.x, d.y, d.z, d.w, ty ? B3[0][0] : B5[0][0], ty ? B3[0][1] : B5[0][1]);
      }
      asm volatile("mov.u32 %0,%%tid.x;" : "=r"(tid2));
#pragma unroll
      for (int n = 0; n < 4; n++) {
        const uint4 f0 = n < 2 ? Z[n] : ldsm4(za + 32 * n), f1 = ldsm4(za + 32 * n + 128), f2 = ldsm4(za + 32 * n + 256);
#pragma unroll
        for (int s = 2 * n; s < 2 * n + 2; s++) {
#pragma unroll
          for (int i = 0; i < 3; i++) mma_hf_t(A[i], T[8 * i + 7 - s], s & 1 ? f0.z : f0.x, s & 1 ? f0.w : f0.y);
          mma_hf_t(X[0], T[7 - s], s & 1 ? f1.z : f1.x, s & 1 ? f1.w : f1.y); mma_hf_t(X[1], T[15 - s], s & 1 ? f1.z : f1.x, s & 1 ? f1.w : f1.y);
          mma_hf_t(X[2], T[7 - s], s & 1 ? f2.z : f2.x, s & 1 ? f2.w : f2.y);
        }
      }
      y_store<128>(A[0][0] + uf(s3.x), A[0][1] + uf(s3.y), A[0][2] + uf(s3.z), A[0][3] + uf(s3.w), F, pml, gs + yo);
      y_store<128>(A[1][0] + X[0][0], A[1][1] + X[0][1], A[1][2] + X[0][2], A[1][3] + X[0][3], F, pml, gs + yo + 1024);
      y_store<128>(A[2][0] + X[1][0] + X[2][0], A[2][1] + X[1][1] + X[2][1], A[2][2] + X[1][2] + X[2][2], A[2][3] + X[1][3] + X[2][3], F, pml, gs + yo + 2048);
    }
    barrive(12, 288);
    TS(15);
    if (!DECL) asm volatile("setmaxnreg.dec.sync.aligned.u32 168;");
  } else {
    asm volatile("setmaxnreg.dec.sync.aligned.u32 136;");
    const u32 t8 = tid - 128, pml = (g & 3) ? 0 : pm;
    {
      TS(12);
      if (PFG == 1 && tid == 288) l2_pre<WSH / 2>(p.wg + (b * WSH + WSH / 2));
      const char* zs = gs + ((16 * w - 64 + (lane >> 3)) * BLK + b * 128 + (lane & 7) * 16);
      const char* zs4 = gs + ((t8 >> 1) * BLK + Ps * 32 + (t8 & 1) * 16);
      uint4 v[5];
      v[4].x = INVAL;
      if (w == 9) {
        const u32 d = lane < 4 ? 4 * b + lane : Ps;
        const char* mp = gs + (G_MOD + (d >> 5) * 128 + (d & 24) * 2);
        uint4 ta, tc;
        POLL({ ta = ldr128(mp); tc = ldr128(mp + MODJ); v[4] = ldr128(zs4); }, ((ta.x ^ pm) | (tc.x ^ pm)) & TAGM, 2);
        const u32 aw = (d & 4) ? ((d & 2) ? ta.w : ta.z) : ((d & 2) ? ta.y : ta.x & ~TAGM);
        const u32 cw = (d & 4) ? ((d & 2) ? tc.w : tc.z) : ((d & 2) ? tc.y : tc.x & ~TAGM);
        const float sa = ((d & 1) ? bhi(aw) : blo(aw)) * F2P64, c1 = rbf(fmaf((d & 1) ? bhi(cw) : blo(cw), F2P64, 1.f));
        const u32 EM = min(max(fu(fmaxf(32.f * fabsf(c1), fabsf(sa))) >> 23, 80u), 250u);
        const float inv = uf((264 - EM) << 23);
        if (lane < 5) { sts64(SM_SC + 16 * lane, pk_hf(16.f * c1 * inv, 16.f * c1 * inv), pk_hf(sa * inv, sa * inv)); sts32(SM_SC + 16 * lane + 8, (EM - 74) << 23); }
        TS(10);
      }
      POLLW(v[4] = ldr128(zs4), (v[4].x ^ pm) & TAGM, 1);
      TS(58);
#pragma unroll
      for (int j = 0; j < 4; j++) v[j] = ldr128(zs + j * 4 * BLK);
#define MARKERS() if (tid == 256) { \
        bulk_out<2048>(gs + (G_Y + 16384 + b * BLK), SM_INV); \
        _Pragma("unroll") for (int i = MT / 2; i < 8; i++) bulk_out<2048>(gs + (G_Y + 2048 * i + b * BLK), SM_INV); \
        bulk_out<2048>(gs + (G_PART + b * 2048), SM_INV); bulk_out<512>(gs + (G_ACT + b * 512), SM_INV); \
        bulk_out<64>(gs + (G_KEY + b * 128), SM_INV); if (!rho) bulk_out<128>(gs + (G_ACT + Ps * 128), SM_INV); \
        asm volatile("cp.async.bulk.commit_group;" ::: "memory"); }
      if (MKT == 0) MARKERS();
      if (PFG == 2 && tid == 256) l2_pre<WSH>(p.wg + b * WSH);
      if (PFG == 3 && tid == 256) l2_pre<WSH / 2>(p.wg + (b * WSH + WSH / 2));
      bsync(8, 256);
      const uint2 cc = lds64(SM_SC + 8 * (t8 & 6)), c4 = lds64(SM_SC + 64);
      POLLW(_Pragma("unroll") for (int j = 0; j < 4; j++) if ((v[j].x ^ pm) & TAGM) v[j] = ldr128(zs + j * 4 * BLK),
           ((v[0].x ^ pm) | (v[1].x ^ pm) | (v[2].x ^ pm) | (v[3].x ^ pm)) & TAGM, 1);
      TS(9);
      const u32 dst = SM_ZS + 128 + (t8 & 7) * ZPS + (16 * w - 64 + (lane >> 3)) * 16;
#pragma unroll
      for (int j = 4; j >= 0; j--) {
        const uint2 c = j < 4 ? cc : c4;
        sts128(j < 4 ? dst + j * 64 : SM_Z4 + 256 + (t8 & 1) * ZP4 + (t8 >> 1) * 16, hfma(v[j].x & ~TAGM, c.x, c.y), hfma(v[j].y, c.x, c.y), hfma(v[j].z, c.x, c.y), hfma(v[j].w, c.x, c.y));
      }
      if (t8 < 96) sts128(t8 < 64 ? SM_ZS + (t8 & 7) * ZPS + (t8 >> 3) * 16 : SM_Z4 + (t8 & 1) * ZP4 + (t8 & 30) * 8, 0, 0, 0, 0);
      if (MKT == 0) asm volatile("cp.async.bulk.wait_group.read 1;" ::: "memory");
      else asm volatile("cp.async.bulk.wait_group.read 0;" ::: "memory");
      bsync(9, 384);
      TS(11);
      if (MKT == 1) MARKERS();
      const bool lng = w < 8 || w == 9;
      const u32 ts = lane + 32 * (w == 8 ? 0 : w - 9), c = min(ts, 71u), ma = SM_MODS + 16 * c;
      const u32 sig = lng ? ksig : ts >> 4, l2 = lng ? lane : 32 + (ts & 15);
      const char* mq = gs + (G_MOD + (c >> 2) * 128 + (c & 3) * 16);
      if (!lng) {
#pragma unroll
        for (int j = 0; j < 6; j++) cpa16(ma + 1152 * j, mq + j * MODJ);
        cpa16(ma + 1152 * 6, p.dsk + 16 * c); cpa16(ma + 1152 * 7, p.wr + 16 * c);
        if (tid == 352) {
          PROXY_FENCE();
          while ((int)(clk() - t0) < DG);
          mb_expect(SM_MB + 8, rho ? SLV : 46080);
          tma3d(SM_GATE, &tm_gate, SM_MB + 8, 32 * b, 0);
          if (!rho) tma3d(SM_GATE + SLV, &tm_gs, SM_MB + 8, 4096 + 4 * b, 0);
          if (UPM) {
            mb_expect(SM_MB + 16, rho ? SLV : 46080);
            tma3d(SM_UP, &tm_up, SM_MB + 16, 32 * b, 0);
            if (!rho) tma3d(SM_UP + SLV, &tm_us, SM_MB + 16, 4096 + 4 * b, 0);
          } else l2_pre<WSH>(p.wu + b * WSH);
        }
      }
      const u32 wb = SM_W + sig * WSL;
      if (sig < 5) {
        const u32 za = (sig < 4 ? SM_ZS + 128 + sig * ZSS : SM_Z4 + 256) + l2 * 32, zb = za + (sig < 4 ? ZPS : ZP4);
        const uint4 c0 = lds128(zb - 32), c1 = lds128(za - 16), c2 = lds128(zb - 16), c3 = lds128(za), c4 = lds128(zb), c5 = lds128(za + 16), c6 = lds128(zb + 16);
        const u32 P[25] = {c0.z, c0.w, c1.x, c1.y, c1.z, c1.w, c2.x, c2.y, c2.z, c2.w, c3.x, c3.y, c3.z, c3.w, c4.x, c4.y, c4.z, c4.w, c5.x, c5.y, c5.z, c5.w, c6.x, c6.y, c6.z};
        u32 Q[25], D1[24], F4[23], W5[21], W3[17];
#pragma unroll
        for (int j = 1; j < 25; j++) Q[j] = __byte_perm(P[j - 1], P[j], 0x5432);
#pragma unroll
        for (int j = 1; j < 24; j++) D1[j] = hadd(P[j], Q[j]);
#pragma unroll
        for (int j = 2; j < 23; j++) F4[j] = hadd(D1[j], D1[j - 1]);
#pragma unroll
        for (int n = 0; n < 21; n++) W5[n] = hadd(F4[n + 2], P[n]);
#pragma unroll
        for (int n = 0; n < 17; n++) W3[n] = hadd(Q[n + 8], D1[n + 7]);
        const u32 a0 = wb + W5O + 64 * l2 + 16 * ((l2 >> 1) & 3);
#pragma unroll
        for (int i = 0; i < 4; i++) {
          sts128(a0 ^ (16 * i), W5[4 * i + 5], W5[4 * i + 6], W5[4 * i + 7], W5[4 * i + 8]);
          sts128((a0 ^ (16 * i)) + (W3O - W5O), W3[4 * i + 1], W3[4 * i + 2], W3[4 * i + 3], W3[4 * i + 4]);
        }
        if (lng) {
          if (lane < 16) sts128(wb + (lane & 7) * 16 + (lane & 8) * 400, 0, 0, 0, 0);
          const u32 a1 = wb + 32 * lane + 16 * ((lane >> 2) & 1);
#pragma unroll
          for (int i = 0; i < 4; i++) {
            const u32 a = (a1 ^ (16 * (i >> 1))) + 1024 * (i & 1), n = 4 * i;
            sts128(a + V2O, hadd(Q[n + 9], P[n + 8]), hadd(Q[n + 10], P[n + 9]), hadd(Q[n + 11], P[n + 10]), hadd(Q[n + 12], P[n + 11]));
            sts128(a + W9O, hadd(F4[n + 4], W5[n]), hadd(F4[n + 5], W5[n + 1]), hadd(F4[n + 6], W5[n + 2]), hadd(F4[n + 7], W5[n + 3]));
            sts128(a + W7O, hadd(F4[n + 6], W3[n]), hadd(F4[n + 7], W3[n + 1]), hadd(F4[n + 8], W3[n + 2]), hadd(F4[n + 9], W3[n + 3]));
          }
        }
      }
      if (w != 9) barrive(10, 352);
      __syncwarp();
      TS(32);
      if (lng) {
        const u32 wa = wb + ((lane >> 3) & 1) * 1024 + (((lane & 7) ^ (lane >> 4)) + 8 * (lane >> 4)) * 16;
        const u32 kv = lds32(SM_KV + 4 * sig), bi = (g >> 1) == q ? (hi ? kv << 16 : kv) : 0u;
        float acc[8][4] = {};
#pragma unroll
        for (int j = 0; j < 4; j++) { const uint4 a = ldsm4t(wa + V2O + j * 256); mma8_hf(acc[2 * j], a.x, a.y, bi); mma8_hf(acc[2 * j + 1], a.z, a.w, bi); }
        u32 bt = tp + (T9E + hi * TEO + (g >> 1) - q) * 4, wt = wa + W9O;
#pragma unroll 1
        for (int ty = 0; ty < 2; ty++) {
          uint4 a[4];
#pragma unroll
          for (int be = 0; be < 4; be++) a[be] = ldsm4t(wt + be * 256);
          u32 b1 = lds32(bt - 16);
#pragma unroll
          for (int d = 0; d < 8; d++) {
            const u32 b0 = lds32(bt + 16 * d);
#pragma unroll
            for (int be = 0; be < 4; be++) if (d + 2 * be < 8) mma_hf(acc[d + 2 * be], a[be].x, a[be].y, a[be].z, a[be].w, b0, b1);
            b1 = b0;
          }
          bt += (T7E - T9E) * 4; wt += W7O - W9O;
        }
        __syncwarp();
#pragma unroll
        for (int j = 0; j < 8; j++) sts128(wb + W9O + j * 512 + lane * 16, fu(acc[j][0]), fu(acc[j][1]), fu(acc[j][2]), fu(acc[j][3]));
        if (w != 9) barrive(14, 352);
        TS(34);
      }
      if (!lng) {
        asm volatile("cp.async.wait_all;" ::: "memory");
        uint4 md[6];
#pragma unroll
        for (int j = 0; j < 6; j++) md[j] = lds128(ma + 1152 * j);
        const uint4 wr = lds128(ma + 1152 * 7);
        POLLW(_Pragma("unroll") for (int j = 0; j < 6; j++) md[j] = ldr128(mq + j * MODJ),
              ((md[0].x ^ pm) | (md[1].x ^ pm) | (md[2].x ^ pm) | (md[3].x ^ pm) | (md[4].x ^ pm) | (md[5].x ^ pm)) & TAGM, 4);
        TS(61);
#pragma unroll
        for (int j = 0; j < 6; j++) {
          const u32 o = (j % 3 == 1) ? BONE : 0x80008000u;
          md[j] = make_uint4(bfma(md[j].x & ~TAGM, B2P64, o), bfma(md[j].y, B2P64, o), bfma(md[j].z, B2P64, o), bfma(md[j].w, B2P64, o));
          sts128(ma + 1152 * j, md[j].x, md[j].y, md[j].z, md[j].w);
        }
        const uint4 H = make_uint4(bmul(md[4].x, wr.x), bmul(md[4].y, wr.y), bmul(md[4].z, wr.z), bmul(md[4].w, wr.w));
        sts128(ma + 1152 * 7, H.x, H.y, H.z, H.w);
        sts128(ma + 1152 * 8, bfma(md[4].x, wr.x, H.x ^ 0x80008000u), bfma(md[4].y, wr.y, H.y ^ 0x80008000u), bfma(md[4].z, wr.z, H.z ^ 0x80008000u), bfma(md[4].w, wr.w, H.w ^ 0x80008000u));
        float c4[4] = {};
        mma_bf(c4, md[4].x, md[3].x, md[4].y, md[3].y, wr.x, wr.y); mma_bf(c4, md[4].z, md[3].z, md[4].w, md[3].w, wr.z, wr.w);
        if (q == g >> 1) sts64(SM_RC + (ts >> 2) * 8, fu(hi ? c4[1] : c4[0]), fu(hi ? c4[3] : c4[2]));
        if (ts < 5) sts128(ts < 2 ? SM_ONE + 16 * ts : SM_THR + 16 * ts - 32, ts ? 0 : BONE, ts ? 0 : BONE, ts ? 0 : BONE, ts ? 0 : BONE);
        TS(14);
        if (MKT == 2) MARKERS();
        if (w == 8) asm volatile("cp.async.bulk.wait_group 0;" ::: "memory");
        barrive(14, 352);
        bsync(13, 96);
      }
      if (w >= 8) barrive(11, 256);
    }
    if (w < 8) {
      const int u0 = 4 * (w - 4) + 2 * rho;
      const u32 t4 = SM_TAP + 4 * TAPS;
      u32 tr = t4 + ((hi ? TO : TE) + (g >> 1) - q) * 4;
      u32 zb = SM_Z4 + 256 + ((lane >> 3) & 1) * ZP4 + u0 * 128 + (lane & 7) * 16 + (lane >> 4) * 128;
      float acc[4][4] = {};
      u32 prev = 0;
#pragma unroll 1
      for (int it = min(u0 + 2, 4); it; it--) {
#pragma unroll
        for (int s = 0; s < 8; s++) {
          const uint4 z = ldsm4(zb - 16 * s);
          const u32 t0 = lds32(tr + 32 * s), t1 = lds32(tr + 32 * s + 16);
          mma_hf(acc[s & 1], t0, t1, prev, t0, z.x, z.y);
          mma_hf(acc[2 + (s & 1)], t0, t1, prev, t0, z.z, z.w);
          prev = t1;
        }
        zb -= 128; tr += 256;
      }
      {
        const uint4 z = ldsm4(zb); const u32 t0 = lds32(tr), t1 = lds32(tr + 16);
        mma_hf(acc[0], t0, t1, prev, t0, z.x, z.y); mma_hf(acc[2], t0, t1, prev, t0, z.z, z.w);
        if (w > 4) { const uint4 y = ldsm4(zb - 16); mma8_hf(acc[1], t1, zr, y.y); mma8_hf(acc[3], t1, zr, y.w); }
      }
      bsync(11, 256);
      u32 wa = (SM_W + 4 * WSL + W5O + row16(lane) + (u0 - 3) * 256) ^ 32, bt = t4 + (T5 + g - q) * 4;
#pragma unroll 1
      for (int al = min(u0 - 2, 6); al > 0; al--) {
#pragma unroll
        for (int ty = 0; ty < 2; ty++) {
          const uint4 a = ldsm4t(wa + ty * (W3O - W5O));
          const u32 bb = bt + ty * (T3 - T5) * 4;
          mma_hf(acc[ty], a.x, a.y, a.z, a.w, lds32(bb - 32), lds32(bb - 48));
          mma_hf(acc[2 + ty], a.x, a.y, a.z, a.w, lds32(bb), lds32(bb - 16));
        }
        wa = (wa - 256) ^ 32; bt += 32;
      }
      TS(35);
      const uint2 fc = lds64(SM_SC + 16 * 4 + 8);
      const u32 F = __byte_perm(fu(uf(fc.x) * uf(fc.y)), 0, 0x3232);
      char* yp = gs + (G_Y + 16384 - 2048 + b * BLK + w * 512 + q * 64 + 4 * g);
#pragma unroll
      for (int j = 0; j < 2; j++) {
        uint4 s3 = {0, 0, 0, 0};
        if (u0 >= 8) s3 = lds128(SM_W + 4 * WSL + W9O + (u0 - 8 + j) * 512 + lane * 16);
        y_store<32>(acc[2 * j][0] + acc[2 * j + 1][0] + uf(s3.x), acc[2 * j][1] + acc[2 * j + 1][1] + uf(s3.y), acc[2 * j][2] + acc[2 * j + 1][2] + uf(s3.z),
                acc[2 * j][3] + acc[2 * j + 1][3] + uf(s3.w), F, pml, yp + j * 256);
      }
      TS(16);
    } else {
      if (tid == 352) {
        mb_wait(SM_MB + 8);
        if (!UPM) {
          mb_expect(SM_MB + 16, rho ? SLV : 46080);
          tma3d(SM_UP, &tm_up, SM_MB + 16, 32 * b, 0);
          if (!rho) tma3d(SM_UP + SLV, &tm_us, SM_MB + 16, 4096 + 4 * b, 0);
        }
        if (UPM == 2) mb_wait(SM_MB + 16);
        if (PFD) l2_pre<WSH>(p.wd + b * WSH);
      }
      TS(17);
    }
  }
  post_conv(p, &tm_down, tid2 + p.zero, b, ep);
  TSD();
  if (s2u(smem) != SM0) __trap();
}

typedef CUresult (*EncFn)(CUtensorMap*, CUtensorMapDataType, cuuint32_t, void*, const cuuint64_t*, const cuuint64_t*, const cuuint32_t*, const cuuint32_t*,
                          CUtensorMapInterleave, CUtensorMapSwizzle, CUtensorMapL2promotion, CUtensorMapFloatOOBfill);
static void make_map(EncFn enc, CUtensorMap* tm, void* ptr, int cols, int rows, int bw, int nb, CUtensorMapSwizzle sw, int gr = 192) {
  cuuint64_t gd[3] = {(cuuint64_t)cols, (cuuint64_t)gr, (cuuint64_t)(rows / gr)}, gs[2] = {(cuuint64_t)cols * 2, (cuuint64_t)cols * 2 * gr};
  cuuint32_t bd[3] = {(cuuint32_t)bw, (cuuint32_t)gr, (cuuint32_t)nb}, es[3] = {1, 1, 1};
  enc(tm, CU_TENSOR_MAP_DATA_TYPE_BFLOAT16, 3, ptr, gd, gs, bd, es, CU_TENSOR_MAP_INTERLEAVE_NONE, sw, CU_TENSOR_MAP_L2_PROMOTION_NONE, CU_TENSOR_MAP_FLOAT_OOB_FILL_NONE);
}
extern "C" void kernel_launch(void* const* d_in, const int* in_sizes, int n_in, void* d_out, int out_size) {
  static EncFn enc = nullptr;
  static void* scratch = nullptr;
  if (!enc) {
    cudaGetSymbolAddress(&scratch, g_s);
    cudaDriverEntryPointQueryResult qr;
    cudaGetDriverEntryPoint("cuTensorMapEncodeTiled", (void**)&enc, cudaEnableDefault, &qr);
    cudaFuncSetAttribute(fused_kernel, cudaFuncAttributeMaxDynamicSharedMemorySize, SM_TOTAL);
  }
  CUtensorMap tm_mod, tm_gate, tm_gs, tm_up, tm_us, tm_down;
  make_map(enc, &tm_mod, d_in[13], 3456, 576, 32, 3, CU_TENSOR_MAP_SWIZZLE_64B);
  make_map(enc, &tm_gate, d_in[9], 4608, 576, 32, 3, CU_TENSOR_MAP_SWIZZLE_64B);
  make_map(enc, &tm_gs, d_in[9], 4608, 576, 8, 3, CU_TENSOR_MAP_SWIZZLE_NONE);
  make_map(enc, &tm_up, d_in[10], 4608, 576, 32, 3, CU_TENSOR_MAP_SWIZZLE_64B);
  make_map(enc, &tm_us, d_in[10], 4608, 576, 8, 3, CU_TENSOR_MAP_SWIZZLE_NONE);
  make_map(enc, &tm_down, d_in[11], 576, 4608, 64, 1, CU_TENSOR_MAP_SWIZZLE_128B, 96);
  Prm p;
  p.x = (const char*)d_in[0]; p.la = (const char*)d_in[1]; p.ai = (const char*)d_in[2]; p.cr = (const char*)d_in[3];
  p.ci = (const char*)d_in[4]; p.ldt = (const char*)d_in[5]; p.dsk = (const char*)d_in[6]; p.wr = (const char*)d_in[8];
  p.wg = (const char*)d_in[9]; p.wu = (const char*)d_in[10]; p.wd = (const char*)d_in[11];
  p.c = (const char*)d_in[12]; p.out = (char*)d_out; p.zero = 0; p.gs = (char*)scratch;
  fused_kernel<<<128, 384, SM_TOTAL>>>(p, tm_mod, tm_gate, tm_gs, tm_up, tm_us, tm_down);
}
```

```cpp
#include <cuda_runtime.h>
#include <cuda.h>
#include <cuda_bf16.h>
#include <cuda_fp16.h>
#include <stdint.h>
#define FUSED 1
#define DEV __device__ __forceinline__
typedef uint32_t u32;

constexpr u32 BLK = 18432, G_Z = 0, G_Y = 128 * BLK, G_MOD = 2 * G_Y, G_KEY = G_MOD + 128 * 128, G_ACT = G_KEY + 128 * 128;
constexpr u32 G_PART = G_ACT + 576 * 128, G_EP = G_PART + 128 * 2048, G_END = G_EP + 128;
__device__ __align__(128) unsigned char g_s[G_END];
#define TS(i)
#define TS0()
#define TSE()
#define TSD()
#define TSX 0
#define ERRF(code)

constexpr int SM0 = 1024;
constexpr int ROW = 1168, SLV = 36864;
constexpr int SM_GATE = SM0, SM_UP = SM_GATE + 46080, SM_XST = SM_UP + 46080, SM_MODS = SM_XST + 16 * ROW, SM_W = SM_MODS + 11008;
constexpr int KTAB = 9216, WSL = 12544, W5O = 128, W3O = 3328, V2O = 6400, W9O = 8448, W7O = 10496;
constexpr int ZPS = 2192, ZSS = 2 * ZPS, ZP4 = 2368;
constexpr int SM_ZS = SM_W + 5 * WSL, SM_Z4 = SM_ZS + 4 * ZSS, SM_TAP = SM_Z4 + 2 * ZP4, TAPS = 3328;
constexpr int SM_MB = SM_TAP + 5 * TAPS;
constexpr int SM_SC = SM_MB + 32;
constexpr int SM_KV = SM_SC + 80;
constexpr int SM_THR = SM_KV + 32;
constexpr int SM_SLOT = SM_THR + 48;
constexpr int SM_KEY = SM_SLOT + 32;
constexpr int SM_ST = SM_KEY + 64;
constexpr int SM_ST2 = SM_ST + 256;
constexpr int SM_RC = SM_ST2 + 256;
constexpr int SM_SP = SM_RC + 192;
constexpr int SM_AF = SM_SP + 1152, SM_SIL = SM_AF + 1152, SM_INV = SM_SIL + 1152, SM_END = SM_SP + 5760;
constexpr int SM_ONE = SM_MODS + 9 * 1152;
constexpr int SM_WD = SM_W, SM_XS = SM_W + 36864, SM_AC = SM_ZS, SM_RED = SM_AC + 6144;
constexpr int SM_TSB = SM_END, SM_TOTAL = SM_END + TSX - SM0;
static_assert(SM_W % 1024 == 0 && SM_TAP % 1024 == 0 && SM_MODS + 8 * KTAB <= SM_ZS && SM_ZS + 2 * KTAB <= SM_TAP && SM_RED + 10240 <= SM_TAP && SM_XS + 8 * ROW <= SM_ZS, "smem map");
static_assert(SM_MB % 16 == 0 && SM_THR % 16 == 0 && SM_ST % 16 == 0 && SM_SP % 16 == 0 && SM_TOTAL <= 232448, "smem map");
constexpr int TE = 4, TO = 276, T5 = 560, T3 = 624, T9E = 680, T7E = 760, TEO = 40;
#define MT 10
#define DECL 1
#define MKT 1
#define KST 128
#define DE1 1
#define DE2 4
#define DE3 5
#define OUTA 2
#define OUTB 7
#define PFW 1
#define PFU 0
#define KD 0
#define D0C 0
#define YE 72
#define YL 104
#define YD 400
#define KD1 0
#define AD 0
#define PD 0
#define ZD 0
#define DD 1000
#define YP 0
#define PFP 200
#define GE 0
constexpr u32 KS2 = KST >= 32 ? 16 : 2048;
#define DX 0
#define DMOD 1000
#define PFG 1
constexpr int SPIN = 1 << 16, NEARLY = 4;
constexpr u32 TAGM = 0x40004000u, TAGR = 0x40000000u, INVAL = 0x00004801u;

DEV u32 s2u(const void* p) { return (u32)__cvta_generic_to_shared(p); }
DEV void mma_bf(float (&c)[4], u32 a0, u32 a1, u32 a2, u32 a3, u32 b0, u32 b1) {
  asm("mma.sync.aligned.m16n8k16.row.col.f32.bf16.bf16.f32 {%0,%1,%2,%3},{%4,%5,%6,%7},{%8,%9},{%0,%1,%2,%3};"
      : "+f"(c[0]), "+f"(c[1]), "+f"(c[2]), "+f"(c[3]) : "r"(a0), "r"(a1), "r"(a2), "r"(a3), "r"(b0), "r"(b1));
}
DEV void mma_hf(float (&c)[4], u32 a0, u32 a1, u32 a2, u32 a3, u32 b0, u32 b1) {
  asm("mma.sync.aligned.m16n8k16.row.col.f32.f16.f16.f32 {%0,%1,%2,%3},{%4,%5,%6,%7},{%8,%9},{%0,%1,%2,%3};"
      : "+f"(c[0]), "+f"(c[1]), "+f"(c[2]), "+f"(c[3]) : "r"(a0), "r"(a1), "r"(a2), "r"(a3), "r"(b0), "r"(b1));
}
DEV void mma8_bf(float (&c)[4], u32 a0, u32 a1, u32 b0) {
  asm("mma.sync.aligned.m16n8k8.row.col.f32.bf16.bf16.f32 {%0,%1,%2,%3},{%4,%5},{%6},{%0,%1,%2,%3};"
      : "+f"(c[0]), "+f"(c[1]), "+f"(c[2]), "+f"(c[3]) : "r"(a0), "r"(a1), "r"(b0));
}
DEV void mma8_hf(float (&c)[4], u32 a0, u32 a1, u32 b0) {
  asm("mma.sync.aligned.m16n8k8.row.col.f32.f16.f16.f32 {%0,%1,%2,%3},{%4,%5},{%6},{%0,%1,%2,%3};"
      : "+f"(c[0]), "+f"(c[1]), "+f"(c[2]), "+f"(c[3]) : "r"(a0), "r"(a1), "r"(b0));
}
DEV u32 movm(u32 x) { u32 r; asm("movmatrix.sync.aligned.m8n8.trans.b16 %0,%1;" : "=r"(r) : "r"(x)); return r; }
DEV uint4 ldsm4(u32 a) { uint4 r; asm volatile("ldmatrix.sync.aligned.m8n8.x4.shared.b16 {%0,%1,%2,%3},[%4];" : "=r"(r.x), "=r"(r.y), "=r"(r.z), "=r"(r.w) : "r"(a)); return r; }
DEV uint4 ldsm4t(u32 a) { uint4 r; asm volatile("ldmatrix.sync.aligned.m8n8.x4.trans.shared.b16 {%0,%1,%2,%3},[%4];" : "=r"(r.x), "=r"(r.y), "=r"(r.z), "=r"(r.w) : "r"(a)); return r; }
DEV u32 lds32(u32 a) { u32 r; asm volatile("ld.volatile.shared.u32 %0,[%1];" : "=r"(r) : "r"(a)); return r; }
DEV uint2 lds64(u32 a) { uint2 r; asm volatile("ld.shared.v2.u32 {%0,%1},[%2];" : "=r"(r.x), "=r"(r.y) : "r"(a)); return r; }
DEV uint4 lds128(u32 a) { uint4 r; asm volatile("ld.shared.v4.u32 {%0,%1,%2,%3},[%4];" : "=r"(r.x), "=r"(r.y), "=r"(r.z), "=r"(r.w) : "r"(a)); return r; }
DEV void sts16(u32 a, u32 v) { asm volatile("st.shared.u16 [%0],%1;" ::"r"(a), "h"((unsigned short)v) : "memory"); }
DEV void sts32(u32 a, u32 v) { asm volatile("st.shared.u32 [%0],%1;" ::"r"(a), "r"(v) : "memory"); }
DEV void sts64(u32 a, u32 x, u32 y) { asm volatile("st.shared.v2.u32 [%0],{%1,%2};" ::"r"(a), "r"(x), "r"(y) : "memory"); }
DEV void sts128(u32 a, u32 x, u32 y, u32 z, u32 w) { asm volatile("st.shared.v4.u32 [%0],{%1,%2,%3,%4};" ::"r"(a), "r"(x), "r"(y), "r"(z), "r"(w) : "memory"); }
DEV uint4 ldr128(const void* p) { uint4 v; asm volatile("ld.relaxed.gpu.global.v4.u32 {%0,%1,%2,%3},[%4];" : "=r"(v.x), "=r"(v.y), "=r"(v.z), "=r"(v.w) : "l"(p) : "memory"); return v; }
DEV uint2 ldr64(const void* p) { uint2 v; asm volatile("ld.relaxed.gpu.global.v2.u32 {%0,%1},[%2];" : "=r"(v.x), "=r"(v.y) : "l"(p) : "memory"); return v; }
DEV u32 ldr32(const void* p) { u32 v; asm volatile("ld.relaxed.gpu.global.u32 %0,[%1];" : "=r"(v) : "l"(p) : "memory"); return v; }
DEV void str128(void* p, u32 x, u32 y, u32 z, u32 w) { asm volatile("st.relaxed.gpu.global.v4.u32 [%0],{%1,%2,%3,%4};" ::"l"(p), "r"(x), "r"(y), "r"(z), "r"(w) : "memory"); }
DEV void str64(void* p, u32 x, u32 y) { asm volatile("st.relaxed.gpu.global.v2.u32 [%0],{%1,%2};" ::"l"(p), "r"(x), "r"(y) : "memory"); }
DEV void str32(void* p, u32 x) { asm volatile("st.relaxed.gpu.global.u32 [%0],%1;" ::"l"(p), "r"(x) : "memory"); }
DEV void str16(void* p, u32 x) { asm volatile("st.relaxed.gpu.global.u16 [%0],%1;" ::"l"(p), "h"((unsigned short)x) : "memory"); }
DEV uint4 ldg128(const void* p) { uint4 v; asm volatile("ld.global.nc.v4.u32 {%0,%1,%2,%3},[%4];" : "=r"(v.x), "=r"(v.y), "=r"(v.z), "=r"(v.w) : "l"(p)); return v; }
DEV uint2 ldg64(const void* p) { uint2 v; asm volatile("ld.global.nc.v2.u32 {%0,%1},[%2];" : "=r"(v.x), "=r"(v.y) : "l"(p)); return v; }
DEV u32 ldg32(const void* p) { u32 v; asm volatile("ld.global.nc.u32 %0,[%1];" : "=r"(v) : "l"(p)); return v; }
DEV u32 ldg16(const void* p) { unsigned short v; asm volatile("ld.global.nc.u16 %0,[%1];" : "=h"(v) : "l"(p)); return v; }
#define bsync(id, n) asm volatile("bar.sync %0,%1;" ::"n"(id), "n"(n) : "memory")
#define barrive(id, n) asm volatile("bar.arrive %0,%1;" ::"n"(id), "n"(n) : "memory")
DEV void mb_init(u32 a) { asm volatile("mbarrier.init.shared.b64 [%0],1;" ::"r"(a) : "memory"); }
DEV void mb_expect(u32 a, u32 bytes) { asm volatile("mbarrier.arrive.expect_tx.shared.b64 _,[%0],%1;" ::"r"(a), "r"(bytes) : "memory"); }
DEV void mb_wait(u32 a, u32 ph = 0) {
  u32 ok; int it = 0;
  do { asm volatile("{.reg .pred p; mbarrier.try_wait.parity.shared.b64 p,[%1],%2; selp.u32 %0,1,0,p;}" : "=r"(ok) : "r"(a), "r"(ph) : "memory"); } while (!ok && ++it < SPIN);
}
template <int N> DEV void bulk_out(void* dst, u32 src) { asm volatile("cp.async.bulk.global.shared::cta.bulk_group [%0],[%1],%2;" ::"l"(dst), "r"(src), "n"(N) : "memory"); }
constexpr u32 WSH = 41472;
DEV void l2_line(const void* p) { asm volatile("prefetch.global.L2 [%0];" ::"l"(p) : "memory"); }
template <int N> DEV void l2_pre(const void* p) { asm volatile("cp.async.bulk.prefetch.L2.global [%0],%1;" ::"l"(p), "n"(N) : "memory"); }
DEV void tma3d(u32 dst, const CUtensorMap* tm, u32 mb, int c0, int c2) {
  asm volatile("cp.async.bulk.tensor.3d.shared::cluster.global.mbarrier::complete_tx::bytes [%0],[%1,{%3,0,%4}],[%2];"
               ::"r"(dst), "l"((uint64_t)tm), "r"(mb), "r"(c0), "r"(c2) : "memory");
}
DEV float blo(u32 w) { return __uint_as_float(w << 16); }
DEV float bhi(u32 w) { return __uint_as_float(w & 0xffff0000u); }
DEV u32 pk_bf(float lo, float hi) { u32 r; asm("cvt.rn.bf16x2.f32 %0,%1,%2;" : "=r"(r) : "f"(hi), "f"(lo)); return r; }
DEV u32 pk_hf(float lo, float hi) { u32 r; asm("cvt.rn.f16x2.f32 %0,%1,%2;" : "=r"(r) : "f"(hi), "f"(lo)); return r; }
DEV float rbf(float x) { return __uint_as_float(pk_bf(0.f, x) & 0xffff0000u); }
DEV u32 bfma(u32 a, u32 b, u32 c) { u32 r; asm("fma.rn.bf16x2 %0,%1,%2,%3;" : "=r"(r) : "r"(a), "r"(b), "r"(c)); return r; }
DEV u32 bmul(u32 a, u32 b) { u32 r; asm("mul.rn.bf16x2 %0,%1,%2;" : "=r"(r) : "r"(a), "r"(b)); return r; }
DEV u32 badd(u32 a, u32 b) { u32 r; asm("add.rn.bf16x2 %0,%1,%2;" : "=r"(r) : "r"(a), "r"(b)); return r; }
DEV u32 hadd(u32 a, u32 b) { u32 r; asm("add.rn.f16x2 %0,%1,%2;" : "=r"(r) : "r"(a), "r"(b)); return r; }
DEV u32 hfma(u32 a, u32 b, u32 c) { u32 r; asm("fma.rn.f16x2 %0,%1,%2,%3;" : "=r"(r) : "r"(a), "r"(b), "r"(c)); return r; }
struct C2 { u32 re, im; };
DEV C2 cm2(C2 a, C2 b) {
  const __half2 ar = *reinterpret_cast<__half2*>(&a.re), ai = *reinterpret_cast<__half2*>(&a.im), br = *reinterpret_cast<__half2*>(&b.re), bi = *reinterpret_cast<__half2*>(&b.im);
  __half2 re = __hfma2(ar, br, __hneg2(__hmul2(ai, bi))), im = __hfma2(ar, bi, __hmul2(ai, br));
  return {*reinterpret_cast<u32*>(&re), *reinterpret_cast<u32*>(&im)};
}
DEV C2 pk2(const float2 (&a)[2]) { return {pk_hf(a[0].x, a[1].x), pk_hf(a[0].y, a[1].y)}; }
DEV C2 pk2c(const float2 (&a)[2]) { return {pk_hf(a[0].x, a[1].x), pk_hf(-a[0].y, -a[1].y)}; }
DEV u32 cpy(u32 x, u32 zr, int alt) {
  u32 r;
  if (alt) asm volatile("xor.b32 %0,%1,%2;" : "=r"(r) : "r"(x), "r"(zr)); else asm volatile("mad.lo.u32 %0,%2,%2,%1;" : "=r"(r) : "r"(x), "r"(zr));
  return r;
}
DEV u32 opq(u32 x) { u32 r; asm volatile("mov.u32 %0,%1;" : "=r"(r) : "r"(x)); return r; }
DEV u32 row16(u32 lane) { const u32 r0 = (lane & 7) + ((lane >> 3) & 1) + 8 * (lane >> 4) - 1; return (r0 ^ ((r0 >> 3) & 3)) * 16; }
DEV u32 clk() { u32 r; asm volatile("mov.u32 %0,%%clock;" : "=r"(r)::"memory"); return r; }
DEV void wait_clk(u32 t, int d) { while ((int)(clk() - t) < d); }
DEV float ex2(float x) { float r; asm("ex2.approx.ftz.f32 %0,%1;" : "=f"(r) : "f"(x)); return r; }
DEV float rcpf(float x) { float r; asm("rcp.approx.ftz.f32 %0,%1;" : "=f"(r) : "f"(x)); return r; }
DEV float2 cmul(float2 a, float2 b) { return make_float2(fmaf(a.x, b.x, -a.y * b.y), fmaf(a.x, b.y, a.y * b.x)); }
DEV float2 csq(float2 a) { return make_float2(fmaf(a.x, a.x, -a.y * a.y), (a.x + a.x) * a.y); }
DEV float2 cexp(float lr2, float th) {
  const float m = ex2(lr2);
  return make_float2(m * __cosf(th), m * __sinf(th));
}
DEV float silu_f(float v) { return v * rcpf(1.f + ex2(-1.4426950408889634f * v)); }
constexpr u32 B2P64 = 0x5F805F80u, B2M64 = 0x1F801F80u, BONE = 0x3F803F80u;
constexpr u32 MODJ = 18 * 128;
DEV float sqrta(float x) { float r; asm("sqrt.approx.ftz.f32 %0,%1;" : "=f"(r) : "f"(x)); return r; }
DEV u32 fu(float x) { return __float_as_uint(x); }
DEV float uf(u32 x) { return __uint_as_float(x); }
DEV void mma_hf_o(float (&d)[4], const float (&c)[4], const u32 (&a)[4], u32 b0, u32 b1) {
  asm("mma.sync.aligned.m16n8k16.row.col.f32.f16.f16.f32 {%0,%1,%2,%3},{%4,%5,%6,%7},{%8,%9},{%10,%11,%12,%13};"
      : "=f"(d[0]), "=f"(d[1]), "=f"(d[2]), "=f"(d[3]) : "r"(a[0]), "r"(a[1]), "r"(a[2]), "r"(a[3]), "r"(b0), "r"(b1), "f"(c[0]), "f"(c[1]), "f"(c[2]), "f"(c[3]));
}

DEV void mma_hf_t(float (&c)[4], const u32 (&a)[4], u32 b0, u32 b1) { mma_hf(c, a[0], a[1], a[2], a[3], b0, b1); }
DEV void cpa16(u32 dst, const void* src) { asm volatile("cp.async.cg.shared.global [%0],[%1],16;" ::"r"(dst), "l"(src) : "memory"); }
DEV void tm_pre(const CUtensorMap* tm) { asm volatile("prefetch.tensormap [%0];" ::"l"((uint64_t)tm) : "memory"); }
#define PROXY_FENCE() asm volatile("fence.proxy.async.shared::cta;" ::: "memory")
struct Prm {
  const char *la, *ai, *cr, *ci, *ldt;
  u32 zero;
  const char *x, *c;
  char* gs;
  const char *dsk, *wr, *wg, *wu, *wd;
  char* out;
};
constexpr float LOG2E = 1.4426950408889634f, F2P64 = 1.8446744073709552e19f, F2M64 = 5.421010862427522e-20f;

template <int S> DEV void y_store(float c0, float c1, float c2, float c3, u32 F, u32 pml, char* yp) {
  str32(yp, bmul(pk_bf(c0, c2), F) | pml);
  str32(yp + S, bmul(pk_bf(c1, c3), F) | pml);
}
DEV uint4 top4(uint4 a, uint4 b) {
  const u32 c0 = max(a.x, b.w), c1 = max(a.y, b.z), c2 = max(a.z, b.y), c3 = max(a.w, b.x);
  const u32 d0 = max(c0, c2), d2 = min(c0, c2), d1 = max(c1, c3), d3 = min(c1, c3);
  return make_uint4(max(d0, d1), min(d0, d1), max(d2, d3), min(d2, d3));
}
#define POLL(load, cond_bad, code) { int it_ = 0; do { load; if (++it_ > SPIN) { ERRF(code); break; } } while (__any_sync(~0u, (cond_bad))); }
#define POLLW(load, cond_bad, code) { int it_ = 0; while (__any_sync(~0u, (cond_bad))) { if (++it_ > SPIN) { ERRF(code); break; } load; } }

#define DOWN(E) if (tid == 288 && b < 108) { const u32 c0 = 64 * (b % 9), c2 = 4 * (b / 9); \
    if (!D0C && E == 1) { mb_expect(SM_MB + 24, 49152); tma3d(SM_TAP, tm_down, SM_MB + 24, c0, c2); } \
    if (DE1 == E) tma3d(SM_WD, tm_down, SM_MB + 24, c0, c2 + 1); \
    if (DE2 == E) tma3d(SM_WD + 12288, tm_down, SM_MB + 24, c0, c2 + 2); \
    if (DE3 == E) tma3d(SM_WD + 24576, tm_down, SM_MB + 24, c0, c2 + 3); }
#define OUTR(E) if (((OUTA == E) | (OUTB == E) << 1) & ot) { const u32 tl = 4 * ((lane >> 1) & 1) + ((lane >> 2) & 3) + 8 * (lane & 1); \
    bulk_out<1152>(p.out + (b * BLK + tl * 1152), SM_XST + ((lane & 2) + 4 * (lane & 1) + ((lane >> 2) & 1) + (lane & 8)) * ROW); \
    asm volatile("cp.async.bulk.commit_group;" ::: "memory"); }
DEV void ffn_tail(const Prm& p, const CUtensorMap* tm_down, uint4 (&A)[24], const u32 tid, const u32 b, const u32 par, const u32 ot) {
  const u32 w = tid >> 5, lane = tid & 31, g = lane >> 2, q = lane & 3, kq = w & 3, tg = w >> 2;
  const u32 rho = b & 1, pm = par ? TAGM : 0;
  char* const gs = p.gs;
  __syncthreads();
  TS(25);
  DOWN(5);
  {
    float c0[2][4] = {}, c1[2][4] = {};
    const u32 ba = SM_XS + (lane & 7) * ROW + (18 * kq + (lane >> 3)) * 16;
    uint4 bb[5];
#pragma unroll
    for (int s = 0; s < 5; s++) bb[s] = ldsm4(ba + s * 64);
#pragma unroll
    for (int s = 0; s < 9; s++) mma_bf(c0[s & 1], A[s].x, A[s].y, A[s].z, A[s].w, s & 1 ? bb[s >> 1].z : bb[s >> 1].x, s & 1 ? bb[s >> 1].w : bb[s >> 1].y);
    const u32 ra = SM_RED + (8 * tg + kq) * 512 + lane * 16;
    if (tg < 2) {
#pragma unroll
      for (int s = 0; s < 9; s++) mma_bf(c1[s & 1], A[9 + s].x, A[9 + s].y, A[9 + s].z, A[9 + s].w, s & 1 ? bb[s >> 1].z : bb[s >> 1].x, s & 1 ? bb[s >> 1].w : bb[s >> 1].y);
      sts128(ra + 2048, fu(c1[0][0] + c1[1][0]), fu(c1[0][1] + c1[1][1]), fu(c1[0][2] + c1[1][2]), fu(c1[0][3] + c1[1][3]));
    }
    sts128(ra, fu(c0[0][0] + c0[1][0]), fu(c0[0][1] + c0[1][1]), fu(c0[0][2] + c0[1][2]), fu(c0[0][3] + c0[1][3]));
  }
  TS(39);
  __syncthreads();
  const u32 tr = clk();
  OUTR(6);
  if (w - 3 - rho < 5 - rho) {
    const u32 t = 7 - w;
    float s[4] = {};
#pragma unroll
    for (int i = 0; i < 4; i++) { const uint4 u = lds128(SM_RED + (t * 4 + i) * 512 + lane * 16); s[0] += uf(u.x); s[1] += uf(u.y); s[2] += uf(u.z); s[3] += uf(u.w); }
    const u32 sg = pk_bf(silu_f(rbf(s[0])), silu_f(rbf(s[1])));
    const u32 act = movm(bmul(bmul(sg, pk_bf(s[2], s[3])), B2M64));
    str32(gs + (G_ACT + (t < 4 ? 4 * b + t : 512 + (b >> 1)) * 128 + lane * 4), act | (q ? 0 : pm));
  }
  TS(26);
  if (b < 108) {
    const char* src = gs + (G_ACT + (b / 9) * 6144 + tid * 16);
    uint4 a;
    if (AD) a.x = INVAL; else a = ldr128(src);
    if (AD && w >= 4) wait_clk(tr, AD);
    if (w < 4) {
      const u32 aa = SM_WD + (8 * (lane >> 4) + (lane & 7)) * 128 + (((2 * w + ((lane >> 3) & 1)) ^ (lane & 7)) << 4);
      mb_wait(SM_MB + 24);
#pragma unroll
      for (int s = 0; s < 24; s++) A[s] = ldsm4t(aa + (s < 6 ? SM_TAP - SM_WD : -12288) + s * 2048);
    }
    TS(28);
    POLLW(a = ldr128(src), (a.x ^ pm) & TAGM, 9);
    sts128(SM_AC + tid * 16, a.x & ~TAGM, a.y, a.z, a.w);
    TS(27);
    if (w < 4) {
      bsync(8, 384);
      float c[4][4] = {};
#pragma unroll
      for (int s = 0; s < 12; s++) {
        const uint4 bb = ldsm4(SM_AC + lane * 16 + s * 512);
        mma_bf(c[2 * (s & 1)], A[2 * s].x, A[2 * s].y, A[2 * s].z, A[2 * s].w, bb.x, bb.y);
        mma_bf(c[2 * (s & 1) + 1], A[2 * s + 1].x, A[2 * s + 1].y, A[2 * s + 1].z, A[2 * s + 1].w, bb.z, bb.w);
      }
      char* dst = gs + (G_PART + b * 2048 + w * 512 + lane * 8);
      u32 o[4];
#pragma unroll
      for (int i = 0; i < 4; i++) o[i] = (fu(((c[0][i] + c[1][i]) + (c[2][i] + c[3][i])) * F2P64) & ~1u) | par;
      str64(dst, o[0], o[1]); str64(dst + 256, o[2], o[3]);
      TS(29);
    } else barrive(8, 384);
  }
  OUTR(7);
  if (w == 8 && b < 72) {
    const u32 ta = clk();
    const u32 kg = lds32(SM_SLOT + 4 * g), ro = (2047 - ((kg >> 2) & 2047)) * 1152 + 16 * b;
    const char* src = gs + (G_PART + (b >> 3) * 2048 + (b & 7) * 256 + lane * 8);
    const char* xs = gs + (G_Y + ro);
    uint4 xt;
    POLL(xt = ldr128(xs), (xt.x ^ TAGR) & TAGM, 10);
    const u32 x1w = (q & 2) ? ((q & 1) ? xt.w : xt.z) : ((q & 1) ? xt.y : bmul(xt.x ^ TAGR, B2P64));
    const u32 gw = lds32(SM_MODS + 5760 + 16 * b + 4 * q);
    const u32 hw = lds32(SM_XS + g * ROW + b * 16 + q * 4);
    const float sgm = rcpf(1.f + ex2(-LOG2E * bhi(kg ^ (~((int)kg >> 31) | 0x80000000))));
    char* const dst = p.out + (ro + 4 * q);
    uint2 v[12];
#pragma unroll
    for (int j = 0; j < 12; j++) v[j] = make_uint2(1, 0);
    u32 bad;
    if (PD) wait_clk(ta, PD);
    POLL({ bad = 0; _Pragma("unroll") for (int j = 0; j < 12; j++) { if (((v[j].x ^ par) | (v[j].y ^ par)) & 1) v[j] = ldr64(src + j * 9 * 2048); }
           _Pragma("unroll") for (int j = 0; j < 12; j++) bad |= (v[j].x ^ par) | (v[j].y ^ par); }, bad & 1, 11);
    float s0[4] = {}, s1[4] = {};
#pragma unroll
    for (int j = 0; j < 12; j++) { s0[j & 3] += uf(v[j].x); s1[j & 3] += uf(v[j].y); }
    const u32 y = movm(pk_bf((s0[0] + s0[1]) + (s0[2] + s0[3]), (s1[0] + s1[1]) + (s1[2] + s1[3])));
    *(u32*)dst = badd(x1w, bmul(gw, badd(hw, bmul(y, pk_bf(sgm, sgm)))));
    if (b == 0 && lane == 0) str32(gs + G_EP, par);
    TS(30); TSE();
  }
  if (w == 10) asm volatile("cp.async.bulk.wait_group.read 0;" ::: "memory");
}

DEV void post_conv(const Prm& p, const CUtensorMap* tm_down, const u32 tid, const u32 b) {
  const u32 w = tid >> 5, lane = tid & 31;
  const u32 g = lane >> 2, q = lane & 3, e = g >> 2, h = (g >> 1) & 1, hi = g & 1;
  const u32 pm = lds32(SM_THR + 4), par = pm >> 30;
  char* const gs = p.gs;
  const u32 cho = 128 * w + 64 * e + 16 * q;
  u32 x1[4][4], h2[4][4], key[4], lt;
  char* const rowp = gs + (b * BLK + (4 * h + 8 * hi) * 1152 + cho);
  u32 ot = 0;
  uint4 A[24];
#define AROW(t) const u32 arow = 144 * ((t >> 5) & 3) + ((t >> 1) & 8) + (t & 7), ab = (t & 8) ? SM_UP : SM_GATE;
#define AFRAG9() { _Pragma("unroll") for (int s = 0; s < 9; s++) A[s] = ldsm4t(ab + SLV + arow * 16 + s * 256); }
  if (w < 9) {
    const u32 yc = 8 * (q >> 1) + 2 * (g >> 1), y1 = w < 8 ? 64 : 4 * BLK, y2 = w < 8 ? BLK : 8 * BLK;
    const char* ysrc = gs + (G_Y + (q & 1) * 16 + (w < 8 ? (16 * w + yc) * BLK + b * 128 + hi * 32 : (8 * yc + 2 * hi + ((b >> 4) & 1)) * BLK + 16384 + ((b >> 5) * 16 + (b & 15)) * 32));
    const char* const ys[4] = {ysrc, ysrc + y1, ysrc + y2, ysrc + (y1 + y2)};
    uint4 yv[4];
    u32 tc = clk();
    if (w < 4 && (!YD || b < YL)) {
#pragma unroll
      for (int v = 0; v < 4; v++) yv[v] = ldr128(ys[v]);
    } else {
#pragma unroll
      for (int v = 0; v < 4; v++) yv[v].x = INVAL;
    }
    const u32 ma = SM_MODS + cho, xa = SM_XST + (2 * h + 4 * hi) * ROW + cho;
    const uint4 sa = lds128(ma), ca = lds128(ma + 1152), ga = lds128(ma + 2304), dk = lds128(ma + 6912);
    const uint4 rb = lds128((g & 2) ? SM_ONE + 16 * hi : (ma ^ 64) + 8064 + 1152 * hi);
    const u32 saw[4] = {sa.x, sa.y, sa.z, sa.w}, caw[4] = {ca.x, ca.y, ca.z, ca.w}, gaw[4] = {ga.x, ga.y, ga.z, ga.w}, dw[4] = {dk.x, dk.y, dk.z, dk.w};
    u32 hD[4][4];
#pragma unroll
    for (int k = 0; k < 4; k++) {
      const uint4 st = lds128(SM_ST + 16 * (2 * h + 4 * hi + (k & 1) + 8 * (k >> 1))), xv = lds128(xa + ((k & 1) + 8 * (k >> 1)) * ROW);
      x1[k][0] = xv.x; x1[k][1] = xv.y; x1[k][2] = xv.z; x1[k][3] = xv.w;
#pragma unroll
      for (int v = 0; v < 4; v++) {
        const u32 d = badd(x1[k][v], st.x), z = bfma(d, st.y, bmul(d, st.z));
        hD[k][v] = bmul(badd(bmul(z, caw[v]), saw[v]), dw[v]);
      }
    }
    const bool own = (q >> 1) == e;
    const u32 spw = SM_SP + (2 * w + e) * 320 + (g & 3) * 16 + (own ? ((q & 1) == h ? 4 : 12) : 8 - 8 * (q & 1));
    TS(18);
    if (w >= 4) { if (w < 8 && b < YE) barrive(12, 288); else bsync(12, 288); tc = clk(); }
    if (w == 8) barrive(7, 64);
    if (YD && b >= YL) wait_clk(tc, YD);
    POLLW(_Pragma("unroll") for (int v = 0; v < 4; v++) if ((yv[v].x ^ pm) & TAGM) yv[v] = ldr128(ys[v]),
          ((yv[0].x ^ pm) | (yv[1].x ^ pm) | (yv[2].x ^ pm) | (yv[3].x ^ pm)) & TAGM, 5);
    TS(19);
    if (DECL && w < 4) asm volatile("setmaxnreg.dec.sync.aligned.u32 168;");
#pragma unroll
    for (int k = 0; k < 4; k += 2) {
      float X[4] = {}, Y[4] = {}, R[4] = {};
#pragma unroll
      for (int v = 0; v < 4; v++) {
        const u32 y0 = k ? yv[v].z : yv[v].x & ~TAGM, y1 = k ? yv[v].w : yv[v].y;
        x1[k][v] = badd(x1[k][v], bmul(gaw[v], bfma(movm(y0), B2P64, hD[k][v])));
        x1[k + 1][v] = badd(x1[k + 1][v], bmul(gaw[v], bfma(movm(y1), B2P64, hD[k + 1][v])));
        mma8_bf(X, x1[k][v], x1[k + 1][v], x1[k][v]); mma8_bf(Y, x1[k][v], x1[k + 1][v], x1[k + 1][v]);
        if (v & 1) mma_bf(R, x1[k][v - 1], x1[k + 1][v - 1], x1[k][v], x1[k + 1][v], v & 2 ? rb.z : rb.x, v & 2 ? rb.w : rb.y);
      }
      sts32(spw + k * 64, fu(own ? (hi ? X[1] : X[0]) : R[0] + R[1]));
      sts32(spw + k * 64 + 64, fu(own ? (hi ? Y[3] : Y[2]) : R[2] + R[3]));
    }
    barrive(1, 320);
    TS(36);
    const uint4 sb = lds128(ma + 3456), cb = lds128(ma + 4608), gb = lds128(ma + 5760);
    const u32 sbw[4] = {sb.x, sb.y, sb.z, sb.w}, cbw[4] = {cb.x, cb.y, cb.z, cb.w}, gbw[4] = {gb.x, gb.y, gb.z, gb.w};
    bsync(2, 320);
    TS(37);
    lt = lds32(SM_THR);
#pragma unroll
    for (int k = 0; k < 4; k++) {
      const uint4 st = lds128(SM_ST2 + 64 * k + 16 * (g & 3));
      key[k] = st.w;
      u32 o[4];
#pragma unroll
      for (int v = 0; v < 4; v++) {
        const u32 d = badd(x1[k][v], st.x), z = bfma(d, st.y, bmul(d, st.z));
        h2[k][v] = badd(bmul(z, cbw[v]), sbw[v]);
        o[v] = badd(x1[k][v], bmul(gbw[v], h2[k][v]));
      }
      h2[k][0] = bmul(h2[k][0], B2M64) | TAGR;
      if (key[k] >= lt) str128(rowp + k * 1152, h2[k][0], h2[k][1], h2[k][2], h2[k][3]);
      sts128(xa + ((k & 1) + 8 * (k >> 1)) * ROW, o[0], o[1], o[2], o[3]);
    }
    barrive(3, 320);
    TS(21);
    asm volatile("setmaxnreg.inc.sync.aligned.u32 168;");
    mb_wait(SM_MB + 8); mb_wait(SM_MB + 16);
    const u32 t3 = tid ^ p.zero;
    AROW(t3);
    if (t3 < 256) {
      const u32 aa = ab + arow * 64 + ((((t3 >> 6) & 2) ^ ((t3 & 7) >> 1)) << 4);
#pragma unroll
      for (int s = 0; s < 9; s++) { A[s] = ldsm4t(aa + s * 1024); A[9 + s] = ldsm4t((aa ^ 16) + s * 1024); }
    } else AFRAG9();
    TS(22);
    bsync(6, 352);
    TS(24);
    const u32 g8 = lds32(SM_SLOT + 28);
    const char* const rs_ = gs + (((~lds32(SM_SLOT + 4 * (w & 7)) >> 2) & 2047) * 1152 + lane * 16);
    uint4 rv[3];
    rv[0].x = rv[1].x = rv[2].x = TAGR;
    if (w < 8) { rv[0] = ldr128(rs_); rv[1] = ldr128(rs_ + 512); if (lane < 8) rv[2] = ldr128(rs_ + 1024); barrive(15, 320); }
    if (__any_sync(~0u, max(max(key[0], key[1]), max(key[2], key[3])) >= g8)) {
#pragma unroll
      for (int k = 0; k < 4; k++) if (key[k] >= g8) {
        if (key[k] < lt) str128(rowp + k * 1152, h2[k][0], h2[k][1], h2[k][2], h2[k][3]);
        str128(rowp + (G_Y + k * 1152), bmul(x1[k][0], B2M64) | TAGR, x1[k][1], x1[k][2], x1[k][3]);
      }
    }
    POLLW({ rv[0] = ldr128(rs_); rv[1] = ldr128(rs_ + 512); if (lane < 8) rv[2] = ldr128(rs_ + 1024); },
          ((rv[0].x ^ TAGR) | (rv[1].x ^ TAGR) | (rv[2].x ^ TAGR)) & TAGM, 8);
    TS(38);
#pragma unroll
    for (int j = 0; j < 3; j++) if (w < 8 && (j < 2 || lane < 8)) sts128(SM_XS + w * ROW + lane * 16 + j * 512, bmul(rv[j].x ^ TAGR, B2P64), rv[j].y, rv[j].z, rv[j].w);
  } else {
    u32 ok, lr;
    if (w == 10) {
      uint2 rc = lds64(SM_RC + 8 * min(lane, 17u));
      float r1 = lane < 18 ? uf(rc.x) : 0.f, r2 = lane < 18 ? uf(rc.y) : 0.f;
#pragma unroll 1
      for (int o = 16; o; o >>= 1) { r1 += __shfl_xor_sync(~0u, r1, o); r2 += __shfl_xor_sync(~0u, r2, o); }
      const u32 tl = 4 * ((lane >> 1) & 1) + ((lane >> 2) & 3) + 8 * (lane & 1), kl = (2047 - 16 * b - tl) << 2 | par * 3;
      char* const kp = gs + (G_KEY + b * KST);
      const u32 spr = SM_SP + (lane >> 4) * 9 * 320 + (lane & 15) * 16;
      TS(31);
      bsync(1, 320);
      float S1 = 0.f, S2 = 0.f, S3 = 0.f;
#pragma unroll
      for (int i = 0; i < 9; i++) { uint4 t = lds128(spr + i * 320); S1 += uf(t.x); S2 += uf(t.y); S3 += uf(t.z); }
      S1 += __shfl_xor_sync(~0u, S1, 16); S2 += __shfl_xor_sync(~0u, S2, 16); S3 += __shfl_xor_sync(~0u, S3, 16);
      const float mu = S1 * (1.f / 576.f), var = fmaxf(fmaf(-mu, mu, S2 * (1.f / 576.f)), 0.f);
      const float m = rbf(mu), rs = rcpf(rbf(sqrta(rbf(rbf(var) + 1e-5f))));
      const u32 rb = pk_bf(0.f, fmaf(fmaf(-m, r1, S3), rs, r2) + 0.f);
      ok = ((rb ^ (((int)rb >> 31) | 0x80000000)) & 0xffff0000u) | kl;
      const float rh = rbf(rs);
      sts32(SM_KEY + 4 * (lane & 15), ok);
      sts128(SM_ST2 + 16 * (lane & 15), pk_bf(-m, -m), pk_bf(rh, rh), pk_bf(rs - rh, rs - rh), ok);
      __syncwarp();
      const uint4 o0 = lds128(SM_KEY + 2 * (lane & 16)), o1 = lds128(SM_KEY + 2 * (lane & 16) + 16);
      lr = (o0.x > ok) + (o0.y > ok) + (o0.z > ok) + (o0.w > ok) + (o1.x > ok) + (o1.y > ok) + (o1.z > ok) + (o1.w > ok);
      lr += __shfl_xor_sync(~0u, lr, 16);
      if (lane < 16 && lr < 8) str32(kp + (4 * lr + (lr >> 2) * (KS2 - 16)), ok);
      if (lr == NEARLY - 1) sts32(SM_THR, ok);
      barrive(2, 320);
      barrive(4, 64);
      TS(20);
    } else if (w == 9) {
      bsync(7, 64);
      wait_clk(clk(), DD);
      PROXY_FENCE();
      DOWN(1);
    }
    asm volatile("setmaxnreg.inc.sync.aligned.u32 168;");
    mb_wait(SM_MB + 8); mb_wait(SM_MB + 16);
    AROW(tid);
    AFRAG9();
    TS(22);
    if (w == 10) {
      bsync(3, 320);
      PROXY_FENCE();
      ot = lane < 16 && lr >= 8;
      OUTR(2);
      bsync(6, 352);
      if (lane < 16 && lr < 8 && ok < lds32(SM_SLOT + 28)) ot = 2;
      bsync(15, 320);
      OUTR(4);
    } else if (w == 9) {
      bsync(5, 64);
      DOWN(3);
      bsync(15, 320);
      DOWN(4);
      TS(13);
    } else {
      const char* ks = gs + (G_KEY + lane * KST);
      const u32 kt = par * 3;
      uint4 L[4];
      bsync(4, 64);
      if (KD) wait_clk(clk(), b < YL ? KD : KD1);
#pragma unroll
      for (int j = 0; j < 4; j++) L[j] = ldr128(ks + j * 32 * KST);
      POLLW(_Pragma("unroll") for (int j = 0; j < 4; j++) if ((L[j].x ^ kt) & 3) L[j] = ldr128(ks + j * 32 * KST), ((L[0].x ^ kt) | (L[1].x ^ kt) | (L[2].x ^ kt) | (L[3].x ^ kt)) & 3, 6);
      barrive(5, 64);
      TS(23);
      uint4 H = top4(top4(L[0], L[1]), top4(L[2], L[3]));
      const u32 h4 = H.w;
      u32 m;
#pragma unroll
      for (int r = 0; r < 8; r++) {
        m = __reduce_max_sync(~0u, H.x);
        if (H.x == m) { sts32(SM_SLOT + 4 * r, H.x); H = make_uint4(H.y, H.z, H.w, 0); }
      }
      if (__builtin_expect(__any_sync(~0u, h4 > m), 0)) {
        uint4 M[4];
        POLL(_Pragma("unroll") for (int j = 0; j < 4; j++) M[j] = ldr128(ks + j * 32 * KST + KS2), ((M[0].x ^ kt) | (M[1].x ^ kt) | (M[2].x ^ kt) | (M[3].x ^ kt)) & 3, 7);
        m = ~0u;
#pragma unroll 1
        for (int r = 0; r < 8; r++) {
          u32 hd = 0;
#pragma unroll
          for (int j = 0; j < 4; j++) {
            const u32 kk[8] = {L[j].x, L[j].y, L[j].z, L[j].w, M[j].x, M[j].y, M[j].z, M[j].w};
#pragma unroll
            for (int i = 0; i < 8; i++) if (kk[i] < m) hd = max(hd, kk[i]);
          }
          m = __reduce_max_sync(~0u, hd);
          sts32(SM_SLOT + 4 * r, m);
        }
      }
      barrive(6, 352);
      TS(33);
    }
  }
  ffn_tail(p, tm_down, A, tid | p.zero, b, par, ot);
}

__global__ void __launch_bounds__(384, 1)
fused_kernel(const Prm p, const __grid_constant__ CUtensorMap tm_mod, const __grid_constant__ CUtensorMap tm_gate, const __grid_constant__ CUtensorMap tm_gs,
             const __grid_constant__ CUtensorMap tm_up, const __grid_constant__ CUtensorMap tm_us, const __grid_constant__ CUtensorMap tm_down) {
  extern __shared__ __align__(1024) unsigned char smem[];
  u32 la, ai, ldt; uint2 cr, ci;
  {
    const u32 t = threadIdx.x, d = t < 256 ? 4 * blockIdx.x + ((t >> 5) & 3) : 512 + (blockIdx.x >> 1), o = d * 256 + 8 * (t & 31), o4 = o + ((t < 256 ? t >> 5 : t >> 3) & 4);
    asm volatile("{.reg .pred p; .reg .u16 h; setp.ne.u32 p,%7,0; @p ld.global.nc.u32 %0,[%8]; @p ld.global.nc.u32 %1,[%9]; @p ld.global.nc.v2.u32 {%2,%3},[%10];"
                 "@p ld.global.nc.v2.u32 {%4,%5},[%11]; @p ld.global.nc.u16 h,[%12]; cvt.u32.u16 %6,h;}"
                 : "=r"(la), "=r"(ai), "=r"(cr.x), "=r"(cr.y), "=r"(ci.x), "=r"(ci.y), "=r"(ldt)
                 : "r"(0x6ffu >> (t >> 5) & 1), "l"(p.la + o4), "l"(p.ai + o4), "l"(p.cr + o), "l"(p.ci + o), "l"(p.ldt + 2 * d));
  }
  const u32 t0 = clk();
  const u32 tid = __shfl_sync(~0u, threadIdx.x, threadIdx.x & 31), b = blockIdx.x + p.zero;
  const u32 w = tid >> 5, lane = tid & 31;
  const u32 g = lane >> 2, q = lane & 3, hi = g & 1;
  const u32 rho = b & 1, Ps = 512 + (b >> 1);
  char* const gs = p.gs;
  TS0();
  const bool kw = w != 8 && w != 11;
  const u32 ksig = w < 8 ? (w & 3) : 4, khf = w < 8 ? (w >> 2) : (w & 1);
  if (!kw) {
    if (tid == 352) {
#pragma unroll
      for (int i = 0; i < 4; i++) mb_init(SM_MB + 8 * i);
      asm volatile("fence.mbarrier_init.release.cluster;" ::: "memory");
      tm_pre(&tm_mod);
    }
    const char* cp = p.c + (576 * (w & 1) + 24 * min(lane, 23u));
    const uint2 c0 = ldg64(cp);
    la = c0.x; ai = c0.y; cr = ldg64(cp + 8); ci = ldg64(cp + 16);
  }
  const u32 zr = tid >> 16;
  const u32 epv = ldr32(gs + (G_EP + zr));
  const u32 tp = SM_TAP + ksig * TAPS;
  if (kw && !khf) {
#pragma unroll 1
    for (u32 i = lane * 16; i < TAPS; i += 512) sts128(tp + i, 0, 0, 0, 0);
  }
  if (tid < 128) sts128(SM_INV + 16 * tid, INVAL, 0, 1, 0);
  if (tid >= 252) str128(gs + (tid >= 380 ? G_MOD + b * 128 + q * 16 : b * BLK + 16384 - 252 * 16 + tid * 16), INVAL, 0, 1, 0);
  if (tid == 352 && b < 36) { while (clk() - t0 < DMOD); mb_expect(SM_MB, 36864); tma3d(SM_UP, &tm_mod, SM_MB, 32 * b, 0); }
  if (w < 9) {
    while ((int)(clk() - t0) < DX);
    const char* xp = p.x + (b * BLK + (lane >> 3) * 1152 + 128 * w + 16 * (lane & 7));
    const u32 xd = SM_XST + (((lane >> 3) & 1) + 8 * (lane >> 4)) * ROW + 128 * w + 16 * (lane & 7);
#pragma unroll
    for (int i = 0; i < 4; i++) cpa16(xd + 2 * ROW * i, xp + 4608 * i);
  }
  const u32 ktab = w < 8 ? SM_MODS + w * KTAB : SM_ZS + (w - 9) * KTAB;
  float k2048 = 0.f;
  if (kw) {
    u32 mx = __vmaxu2(__vmaxu2(cr.x & 0x7fff7fff, cr.y & 0x7fff7fff), __vmaxu2(ci.x & 0x7fff7fff, ci.y & 0x7fff7fff));
    const u32 E = max(__reduce_max_sync(~0u, max(mx & 0xffff, mx >> 16)) >> 7, 8u);
    TS(1);
    const float dt = rbf(ex2(blo(ldt) * LOG2E)), csc = uf((257 - E) << 23 | (fu(dt) & 0x7fffff));
    sts32(SM_SC + 16 * ksig + 12, fu(uf(fu(dt) & 0x7f800000) * uf((E - 2) << 23)));
    const u32 crw = khf ? cr.y : cr.x, ciw = khf ? ci.y : ci.x;
    float2 C[2], w4[2], w8[2], w16[2], w32[2], w64[2], w128[2], w256[2], w512[2], a1[2], a2[2], a3[2], t0[2], t1[2], s3[2];
#pragma unroll
    for (int m = 0; m < 2; m++) {
      const float lr2 = rbf(ex2((m ? bhi(la) : blo(la)) * LOG2E)) * dt * -LOG2E, th = (m ? bhi(ai) : blo(ai)) * dt;
      C[m] = make_float2((m ? bhi(crw) : blo(crw)) * csc, (m ? bhi(ciw) : blo(ciw)) * csc);
      const float2 w1 = cexp(lr2, th), w2 = csq(w1);
      w64[m] = cexp(64.f * lr2, 64.f * th);
      w4[m] = csq(w2); w8[m] = csq(w4[m]); w16[m] = csq(w8[m]); w32[m] = csq(w16[m]);
      w128[m] = csq(w64[m]); w256[m] = csq(w128[m]); w512[m] = csq(w256[m]);
      const float2 w1024 = csq(w512[m]);
      a1[m] = cmul(C[m], w1); a2[m] = cmul(C[m], w2); a3[m] = cmul(a1[m], w2);
      t0[m] = cmul(C[m], w1024); t1[m] = cmul(t0[m], w128[m]); s3[m] = cmul(w8[m], w16[m]);
      k2048 += fmaf(t0[m].x, w1024.x, -t0[m].y * w1024.y);
    }
    C2 B0[8], B1[8], B2[8], S[8];
    B0[0] = pk2(C); B0[1] = pk2(a1); B0[2] = pk2(a2); B0[3] = pk2(a3);
    const C2 h4 = pk2(w4), h256 = pk2(w256), h512 = pk2(w512);
#pragma unroll
    for (int i = 0; i < 4; i++) B0[4 + i] = cm2(B0[i], h4);
#pragma unroll
    for (int i = 0; i < 4; i++) B1[i] = cm2(B0[2 * i], h256);
    B1[4] = cm2(B0[0], h512); B1[5] = cm2(B0[4], h512);
    B1[6] = cm2(B1[4], h256); B1[7] = cm2(B1[5], h256);
    const u32 ta = ktab + lane * 128, f = ((lane & 3) << 5) | ((lane & 4) << 2);
#pragma unroll
    for (int i = 0; i < 8; i++) sts128(ta + ((i << 4) ^ f), B0[i].re, B0[i].im, B1[i].re, B1[i].im);
    B2[0] = pk2(t0); B2[1] = pk2(t1);
    B2[2] = cm2(B2[0], h256); B2[3] = cm2(B2[1], h256);
#pragma unroll
    for (int i = 0; i < 4; i++) B2[4 + i] = cm2(B2[i], h512);
    S[0] = {0x3C003C00u, 0u}; S[1] = pk2c(w8); S[2] = pk2c(w16); S[3] = pk2c(s3); S[4] = pk2c(w32);
#pragma unroll
    for (int i = 1; i < 4; i++) S[4 + i] = cm2(S[i], S[4]);
#pragma unroll
    for (int i = 0; i < 8; i++) sts128(ta + 4096 + ((i << 4) ^ f), B2[i].re, B2[i].im, S[i].re, S[i].im);
    const C2 m64 = pk2c(w64), m128 = pk2c(w128);
    sts128(ktab + 8192 + lane * 16, m64.re, m64.im, m128.re, m128.im);
    __syncwarp();
  } else {
    u32 sa = SM_SIL + 576 * (w & 1) + 24 * min(lane, 23u);
#pragma unroll 1
    for (int j = 0; j < 6; j++) {
      sts32(sa, pk_bf(silu_f(blo(la)), silu_f(bhi(la))));
      la = ai; ai = cr.x; cr.x = cr.y; cr.y = ci.x; ci.x = ci.y; sa += 4;
    }
    bsync(7, 64);
  }
  TS(2);
  const u32 pm = (__reduce_or_sync(~0u, epv) & 1) ? 0 : TAGM;
  sts32(SM_THR + 4, pm);
  if (w < 9) {
    asm volatile("cp.async.wait_all;" ::: "memory");
    __syncwarp();
    TS(4);
    if (tid == 256 && b >= 36 && b < 108) { mb_expect(SM_MB, 36864); tma3d(SM_UP, &tm_mod, SM_MB, 32 * b, 0); }
    const u32 xa = SM_XST + (lane & 15) * ROW + 128 * w + 16 * (lane >> 4);
    float s[4] = {}, X[2][4] = {}, Y[2][4] = {};
#pragma unroll
    for (int j = 0; j < 4; j++) {
      const uint4 a = ldsm4(xa + 32 * j);
      mma8_bf(X[0], a.x, a.y, a.x); mma8_bf(Y[0], a.x, a.y, a.y);
      mma8_bf(X[1], a.z, a.w, a.z); mma8_bf(Y[1], a.z, a.w, a.w);
      mma_bf(s, a.x, a.y, a.z, a.w, BONE, BONE);
    }
    uint4 t[4];
#pragma unroll
    for (int j = 0; j < 4; j++) t[j] = ldsm4t(xa + 32 * j);
    const float u0 = hi ? X[0][1] + X[1][1] : X[0][0] + X[1][0], u1 = hi ? Y[0][3] + Y[1][3] : Y[0][2] + Y[1][2];
    if (q == g >> 1) sts128(SM_SP + w * 128 + g * 16, fu(s[0]), fu(u0), fu(s[2]), fu(u1));
    bsync(1, 288);
    TS(7);
    const u32 spr = SM_SP + (lane & 7) * 16 + (lane & 8);
    const uint2 t8 = lds64(spr + 1024);
    const float f8 = lane < 16 ? 1.f : 0.f;
    float S1 = uf(t8.x) * f8, S2 = uf(t8.y) * f8;
#pragma unroll
    for (int i = 0; i < 4; i++) { const uint2 u = lds64(spr + (lane & 16) * 32 + i * 128); S1 += uf(u.x); S2 += uf(u.y); }
    S1 += __shfl_xor_sync(~0u, S1, 16); S2 += __shfl_xor_sync(~0u, S2, 16);
    const float mu = S1 * (1.f / 576.f), var = fmaxf(fmaf(-mu, mu, S2 * (1.f / 576.f)), 0.f);
    const float m = rbf(mu), rs = rcpf(rbf(sqrta(rbf(rbf(var) + 1e-5f))));
    const float ra = rs * 0.0625f;
    sts64(SM_AF + w * 128 + (lane & 15) * 8, fu(ra), fu(-m * ra));
    __syncwarp();
    TS(55);
    const uint4 f0 = lds128(SM_AF + w * 128 + q * 16), f1 = lds128(SM_AF + w * 128 + 64 + q * 16);
    const u32 zdst = SM_GATE + w * 2048 + lane * 8;
    const u32 pz = (q & 1) ? 0 : pm;
#pragma unroll
    for (int j = 0; j < 8; j++) {
      const u32 x0 = j & 1 ? t[j >> 1].z : t[j >> 1].x, x1 = j & 1 ? t[j >> 1].w : t[j >> 1].y;
      sts64(zdst + 256 * j, pk_hf(fmaf(blo(x0), uf(f0.x), uf(f0.y)), fmaf(bhi(x0), uf(f0.z), uf(f0.w))) | pz,
            pk_hf(fmaf(blo(x1), uf(f1.x), uf(f1.y)), fmaf(bhi(x1), uf(f1.z), uf(f1.w))));
    }
    TS(53);
    if (w < 8) barrive(15, 288);
    else {
      bsync(15, 288);
      TS(54);
      if (lane == 0) {
        PROXY_FENCE();
        bulk_out<BLK>(gs + b * BLK, SM_GATE);
        asm volatile("cp.async.bulk.commit_group;" ::: "memory");
        if (PFG & 1) l2_pre<WSH / 2>(p.wg + b * WSH);
      }
      const float rh = rbf(rs);
      sts128(SM_ST + 16 * (lane & 15), pk_bf(-m, -m), pk_bf(rh, rh), pk_bf(rs - rh, rs - rh), 0);
    }
    TS(5);
  }
  if (kw) {
    float D[5][4] = {};
    u32 ta = ktab + q * 128 + ((g ^ (q << 1)) << 4), tm = ktab + 8192 + q * 16;
#pragma unroll 2
    for (int s = 0; s < 8; s++) {
      const uint4 ca = lds128(ta), cb = lds128(ta + 4096), ma = lds128(tm);
      ta = (ta + 512) ^ 16; tm += 64;
      k2048 += __shfl_xor_sync(~0u, k2048, 16 >> s);
      const C2 s0 = {cb.z, cb.w}, s1 = cm2(s0, {ma.x, ma.y}), s2 = cm2(s0, {ma.z, ma.w}), s3 = cm2(s1, {ma.z, ma.w});
      mma_hf(D[0], s0.re, s1.re, s0.im, s1.im, ca.x, ca.y);
      mma_hf(D[2], s0.re, s1.re, s0.im, s1.im, ca.z, ca.w);
      mma_hf(D[4], s0.re, s1.re, s0.im, s1.im, cb.x, cb.y);
      mma_hf(D[1], s2.re, s3.re, s2.im, s3.im, ca.x, ca.y);
      mma_hf(D[3], s2.re, s3.re, s2.im, s3.im, ca.z, ca.w);
    }
    TS(3);
    const u32 xa = (w < 8 ? SM_MODS + (4 + ksig) * KTAB : SM_ZS) + lane * 16;
    if (khf) {
      __syncwarp();
#pragma unroll
      for (int j = 0; j < 5; j++) sts128(xa + 512 * j, fu(D[j][0]), fu(D[j][1]), fu(D[j][2]), fu(D[j][3]));
      if (lane == 0) sts32(xa + 2560, fu(k2048));
      asm volatile("bar.arrive %0,64;" ::"r"(2 + ksig) : "memory");
    } else {
      const u32 t1 = tp + (q < 2 ? (128 + 4 * g + 2 * q) * 4 : T3 * 4 + ((32 * q - 64 + g) ^ 1) * 2);
      const u32 x = 16 * q + (g >> 1) + hi + 1, tb = tp + (hi ? T7E : T9E) * 4 - 4;
      const u32 te = tb + (x + 2 * (x & 1)) * 2, to = tb + TEO * 4 + (x ^ 1) * 2;
      asm volatile("bar.sync %0,64;" ::"r"(2 + ksig) : "memory");
#pragma unroll
      for (int j = 0; j < 5; j++) { const uint4 t = lds128(xa + 512 * j); D[j][0] += uf(t.x); D[j][1] += uf(t.y); D[j][2] += uf(t.z); D[j][3] += uf(t.w); }
      k2048 = (k2048 + uf(lds32(xa + 2560))) * 0.125f;
#pragma unroll
      for (int r = 0; r < 4; r++) {
        const u32 v = pk_hf(D[2 + (r >> 1)][2 * (r & 1)], D[2 + (r >> 1)][2 * (r & 1) + 1]);
        if (q < 2) {
          const u32 vv = __byte_perm(v, v, 0x1010);
          sts32(t1 + (TO + 32 * r) * 4, vv); sts16(t1 + (TO + 32 * r + 1) * 4 + 2, v >> 16); sts16(t1 + (TO + 32 * r - 1) * 4, v);
          sts64(t1 + (TE + 32 * r) * 4, vv, __byte_perm(v, v, 0x1032));
        } else {
          sts16(t1 + 16 * r, v >> 16);
          if (r == 0 && lane == 2) {
            const u32 vv = __byte_perm(v, v, 0x1010);
            sts32(tp + (TO + 256) * 4, vv); sts16(tp + (TO + 257) * 4 + 2, v); sts16(tp + (TO + 255) * 4, v); sts64(tp + (TE + 256) * 4, vv, vv);
          } else sts16(t1 + 16 * r - ((T3 - T5) * 4 + 6) + 8 * hi, v);
        }
      }
#pragma unroll
      for (int r = 0; r < 2; r++) {
        const u32 v = pk_hf(D[4][2 * r], D[4][2 * r + 1]);
        if (r == 0 && lane == 0) { sts16(tp + T5 * 4 + 62 * 2, v); sts32(SM_KV + 4 * ksig, v & 0xffff); sts16(tp + (T9E + TEO) * 4 + 62 * 2, pk_hf(k2048, 0.f)); }
        else { sts16(te + 8 * r, v); sts16(to + 8 * r, v); }
        sts16(te + 8 * r + 16, v >> 16); sts16(to + 8 * r + 16, v >> 16);
      }
      __syncwarp();
#pragma unroll
      for (int r = 0; r < 4; r++) {
        const u32 v = pk_hf(D[r >> 1][2 * (r & 1) + 1], D[r >> 1][2 * (r & 1)]), t2 = tp + lane * 4 + 128 * r;
        sts32(t2 + TO * 4, v); sts16(t2 + TE * 4, v >> 16); sts16(t2 + (TE + 1) * 4 + 2, v);
      }
      __syncwarp();
    }
  } else if (w == 11 && b < 108) {
    float c[4][4] = {};
    u32 aa = SM_UP + ((lane & 7) + 8 * (lane >> 4)) * 64 + ((((lane >> 3) & 1) ^ ((lane & 7) >> 1)) << 4);
    u32 ba = SM_SIL + (lane >> 3) * 16;
    uint4 a[2][10];
#define GLD(n) { _Pragma("unroll") for (int i = 0; i < 2; i++) { a[n][5 * i] = ldsm4(ba + i * 64); \
      _Pragma("unroll") for (int k = 0; k < 4; k++) a[n][5 * i + 1 + k] = ldsm4t((k & 2 ? aa ^ 32 : aa) + i * 2048 + (k & 1) * 1024); } aa += 4096; ba += 128; }
#define GMM(n) { _Pragma("unroll") for (int i = 0; i < 2; i++) _Pragma("unroll") for (int k = 0; k < 4; k++) { const uint4 f = a[n][5 * i + 1 + k], bb = a[n][5 * i]; \
      mma_bf(c[k], f.x, f.y, f.z, f.w, k & 1 ? bb.z : bb.x, k & 1 ? bb.w : bb.y); } }
    mb_wait(SM_MB);
    TS(56);
    GLD(0);
#pragma unroll 1
    for (int s = 0; s < 4; s++) { GLD(1); GMM(0); GLD(0); GMM(1); }
    GMM(0);
    const float v0 = (q & 1) ? c[0][2] + c[1][2] : c[0][0] + c[1][0], v1 = (q & 1) ? c[2][2] + c[3][2] : c[2][0] + c[3][0];
    str16(gs + (G_MOD + b * 128 + 2 * g + 16 * q), pk_bf(rbf((q & 2) ? v1 : v0) * F2M64, 0.f) | (g < 2 ? pm : 0));
    TS(57);
  }
  TS(6);
  u32 tid2 = tid;
  if (w < 4) {
    asm volatile("setmaxnreg.inc.sync.aligned.u32 232;");
    const u32 tid = tid2 + p.zero, w = tid >> 5, lane = tid & 31, g = lane >> 2, q = lane & 3, hi = g & 1, zr = tid >> 16, tp = SM_TAP + w * TAPS;
    const u32 pml = opq((g & 3) ? 0 : pm);
    const u32 tr = tp + ((hi ? TO : TE) + (g >> 1) - q) * 4;
    u32 T[33][4], B5[5][2], B3[5][2];
#pragma unroll
    for (int d = 0; d < 33; d++) {
      T[d][0] = lds32(tr + 32 * d); T[d][1] = lds32(tr + 32 * d + 16);
      T[d][2] = cpy(d ? T[d - 1][1] : zr, zr, 0); T[d][3] = cpy(T[d][0], zr, 1);
    }
    const u32 t33 = cpy(T[32][1], zr, 0), z33 = cpy(zr, zr, 1);
    const u32 bt = tp + (T5 + g - q) * 4;
#pragma unroll
    for (int d = 0; d < 5; d++) {
      B5[d][0] = lds32(bt + 32 * d); B5[d][1] = lds32(bt + 32 * d - 16);
      B3[d][0] = lds32(bt + 32 * d + (T3 - T5) * 4); B3[d][1] = lds32(bt + 32 * d - 16 + (T3 - T5) * 4);
    }
    u32 za = opq(SM_ZS + 16 + w * ZSS + ((lane >> 3) & 1) * ZPS + ((lane & 7) + (lane >> 4)) * 16);
    u32 wa = opq(SM_W + W5O + w * WSL + row16(lane));
    u32 sa = opq(SM_W + W9O - 2048 + w * WSL + lane * 16);
    u32 yo = opq(G_Y + b * BLK + 256 * q + w * 32 + 4 * g);
    const u32 fa = opq(SM_SC + 16 * w + 8);
    TS(8);
    bsync(9, 384);
    TS(11);
    float A[4][4] = {};
    uint4 Z[4];
    Z[0] = ldsm4(za); Z[1] = ldsm4(za + 32);
    const uint2 fc = lds64(fa);
    const u32 F = __byte_perm(fu(uf(fc.x) * uf(fc.y)), 0, 0x3232);
#define STEP(s, b0, b1) { _Pragma("unroll") for (int i = 0; i < 4; i++) mma_hf_t(A[i], T[8 * i + 7 - (s)], b0, b1); }
#define PAIR(n) { Z[(n + 2) & 3] = ldsm4(za + 32 * (n + 2)); STEP(2 * n, Z[n].x, Z[n].y); STEP(2 * n + 1, Z[n].z, Z[n].w); }
#define LAST(N) mma8_hf(N, t33, z33, Z[3].y); float O[4]; mma_hf_o(O, A[0], T[0], Z[3].z, Z[3].w); \
    _Pragma("unroll") for (int i = 0; i < 3; i++) mma_hf_o(A[i], A[i + 1], T[8 * i + 8], Z[3].z, Z[3].w); \
    mma_hf_o(A[3], N, T[32], Z[3].z, Z[3].w);
#pragma unroll 1
    for (int j = 0; j < 4; j++) {
      PAIR(0); PAIR(1); PAIR(2);
      Z[1] = ldsm4(za + 160); STEP(6, Z[3].x, Z[3].y);
      float N[4] = {};
      LAST(N);
      y_store<128>(O[0], O[1], O[2], O[3], F, pml, gs + yo);
      za += 128; yo += 1024;
      TS(40 + j);
    }
    bsync(10, 352);
#pragma unroll 1
    for (int j = 4; j < 13; j++) {
      if (j == 8) bsync(14, 352);
      const uint4 a5 = ldsm4t(wa), a3 = ldsm4t(wa + (W3O - W5O));
      uint4 s3 = {0, 0, 0, 0};
      if (j >= 8) s3 = lds128(sa);
      PAIR(0);
      float N[4] = {};
#pragma unroll
      for (int i = 0; i < 4; i++) mma_hf(A[i], a5.x, a5.y, a5.z, a5.w, B5[i][0], B5[i][1]);
      mma_hf(N, a5.x, a5.y, a5.z, a5.w, B5[4][0], B5[4][1]);
      PAIR(1);
#pragma unroll
      for (int i = 0; i < 4; i++) mma_hf(A[i], a3.x, a3.y, a3.z, a3.w, B3[i][0], B3[i][1]);
      mma_hf(N, a3.x, a3.y, a3.z, a3.w, B3[4][0], B3[4][1]);
      PAIR(2);
      Z[1] = ldsm4(za + 160); STEP(6, Z[3].x, Z[3].y);
      LAST(N);
      y_store<128>(O[0] + uf(s3.x), O[1] + uf(s3.y), O[2] + uf(s3.z), O[3] + uf(s3.w), F, pml, gs + yo);
      za += 128; wa = (wa + 256) ^ 32; sa += 512; yo += 1024;
      TS(40 + j);
    }
    {
      const uint4 s3 = lds128(sa), s4 = lds128(sa + 512), s5 = lds128(sa + 1024);
      float X[3][4] = {{uf(s4.x), uf(s4.y), uf(s4.z), uf(s4.w)}, {}, {uf(s5.x), uf(s5.y), uf(s5.z), uf(s5.w)}};
#pragma unroll
      for (int ty = 0; ty < 2; ty++) {
        const uint4 a = ldsm4t(wa + ty * (W3O - W5O)), c = ldsm4t((wa ^ 32) + 256 + ty * (W3O - W5O)), d = ldsm4t(wa + 512 + ty * (W3O - W5O));
#pragma unroll
        for (int i = 0; i < 3; i++) mma_hf(A[i], a.x, a.y, a.z, a.w, ty ? B3[i][0] : B5[i][0], ty ? B3[i][1] : B5[i][1]);
#pragma unroll
        for (int i = 0; i < 2; i++) mma_hf(X[i], c.x, c.y, c.z, c.w, ty ? B3[i][0] : B5[i][0], ty ? B3[i][1] : B5[i][1]);
        mma_hf(X[2], d.x, d.y, d.z, d.w, ty ? B3[0][0] : B5[0][0], ty ? B3[0][1] : B5[0][1]);
      }
      asm volatile("mov.u32 %0,%%tid.x;" : "=r"(tid2));
#pragma unroll
      for (int n = 0; n < 4; n++) {
        const uint4 f0 = n < 2 ? Z[n] : ldsm4(za + 32 * n), f1 = ldsm4(za + 32 * n + 128), f2 = ldsm4(za + 32 * n + 256);
#pragma unroll
        for (int s = 2 * n; s < 2 * n + 2; s++) {
#pragma unroll
          for (int i = 0; i < 3; i++) mma_hf_t(A[i], T[8 * i + 7 - s], s & 1 ? f0.z : f0.x, s & 1 ? f0.w : f0.y);
          mma_hf_t(X[0], T[7 - s], s & 1 ? f1.z : f1.x, s & 1 ? f1.w : f1.y); mma_hf_t(X[1], T[15 - s], s & 1 ? f1.z : f1.x, s & 1 ? f1.w : f1.y);
          mma_hf_t(X[2], T[7 - s], s & 1 ? f2.z : f2.x, s & 1 ? f2.w : f2.y);
        }
      }
      y_store<128>(A[0][0] + uf(s3.x), A[0][1] + uf(s3.y), A[0][2] + uf(s3.z), A[0][3] + uf(s3.w), F, pml, gs + yo);
      y_store<128>(A[1][0] + X[0][0], A[1][1] + X[0][1], A[1][2] + X[0][2], A[1][3] + X[0][3], F, pml, gs + yo + 1024);
      y_store<128>(A[2][0] + X[1][0] + X[2][0], A[2][1] + X[1][1] + X[2][1], A[2][2] + X[1][2] + X[2][2], A[2][3] + X[1][3] + X[2][3], F, pml, gs + yo + 2048);
    }
    barrive(12, 288);
    TS(15);
    if (!DECL) asm volatile("setmaxnreg.dec.sync.aligned.u32 168;");
  } else {
    asm volatile("setmaxnreg.dec.sync.aligned.u32 136;");
    const u32 t8 = tid - 128, pml = (g & 3) ? 0 : pm;
    {
      TS(12);
      if (PFG == 1 && tid == 288) l2_pre<WSH / 2>(p.wg + (b * WSH + WSH / 2));
      const char* zs = gs + ((16 * w - 64 + (lane >> 3)) * BLK + b * 128 + (lane & 7) * 16);
      const char* zs4 = gs + ((t8 >> 1) * BLK + Ps * 32 + (t8 & 1) * 16);
      uint4 v[5];
      v[4].x = INVAL;
      if (ZD) wait_clk(t0, ZD);
      if (w == 9) {
        const u32 d = lane < 4 ? 4 * b + lane : Ps;
        const char* mp = gs + (G_MOD + (d >> 5) * 128 + (d & 24) * 2);
        uint4 ta, tc;
        POLL({ ta = ldr128(mp); tc = ldr128(mp + MODJ); v[4] = ldr128(zs4); }, ((ta.x ^ pm) | (tc.x ^ pm)) & TAGM, 2);
        const u32 aw = (d & 4) ? ((d & 2) ? ta.w : ta.z) : ((d & 2) ? ta.y : ta.x & ~TAGM);
        const u32 cw = (d & 4) ? ((d & 2) ? tc.w : tc.z) : ((d & 2) ? tc.y : tc.x & ~TAGM);
        const float sa = ((d & 1) ? bhi(aw) : blo(aw)) * F2P64, c1 = rbf(fmaf((d & 1) ? bhi(cw) : blo(cw), F2P64, 1.f));
        const u32 EM = min(max(fu(fmaxf(32.f * fabsf(c1), fabsf(sa))) >> 23, 80u), 250u);
        const float inv = uf((264 - EM) << 23);
        if (lane < 5) { sts64(SM_SC + 16 * lane, pk_hf(16.f * c1 * inv, 16.f * c1 * inv), pk_hf(sa * inv, sa * inv)); sts32(SM_SC + 16 * lane + 8, (EM - 74) << 23); }
        TS(10);
      }
      POLLW(v[4] = ldr128(zs4), (v[4].x ^ pm) & TAGM, 1);
      TS(58);
#pragma unroll
      for (int j = 0; j < 4; j++) v[j] = ldr128(zs + j * 4 * BLK);
#define MARKERS() if (tid == 256) { \
        bulk_out<2048>(gs + (G_Y + 16384 + b * BLK), SM_INV); \
        _Pragma("unroll") for (int i = MT / 2; i < 8; i++) bulk_out<2048>(gs + (G_Y + 2048 * i + b * BLK), SM_INV); \
        bulk_out<2048>(gs + (G_PART + b * 2048), SM_INV); bulk_out<512>(gs + (G_ACT + b * 512), SM_INV); \
        bulk_out<16>(gs + (G_KEY + b * KST), SM_INV); bulk_out<16>(gs + (G_KEY + KS2 + b * KST), SM_INV); if (!rho) bulk_out<128>(gs + (G_ACT + Ps * 128), SM_INV); \
        asm volatile("cp.async.bulk.commit_group;" ::: "memory"); }
      if (PFU == 2 && tid == 256) l2_pre<WSH>(p.wu + b * WSH);
      if (GE && tid == 256) {
        asm volatile("cp.async.bulk.wait_group.read 0;" ::: "memory");
#pragma unroll
        for (int i = 0; i < GE; i++) tma3d(SM_GATE + 12288 * i, &tm_gate, SM_MB + 8, 32 * b, i);
      }
      if (MKT == 0) MARKERS();
      if (PFG == 2 && tid == 256) l2_pre<WSH>(p.wg + b * WSH);
      if (PFG == 3 && tid == 256) l2_pre<WSH / 2>(p.wg + (b * WSH + WSH / 2));
      bsync(8, 256);
      const uint2 cc = lds64(SM_SC + 8 * (t8 & 6)), c4 = lds64(SM_SC + 64);
      POLLW(_Pragma("unroll") for (int j = 0; j < 4; j++) if ((v[j].x ^ pm) & TAGM) v[j] = ldr128(zs + j * 4 * BLK),
           ((v[0].x ^ pm) | (v[1].x ^ pm) | (v[2].x ^ pm) | (v[3].x ^ pm)) & TAGM, 1);
      TS(9);
      const u32 dst = SM_ZS + 128 + (t8 & 7) * ZPS + (16 * w - 64 + (lane >> 3)) * 16;
#pragma unroll
      for (int j = 4; j >= 0; j--) {
        const uint2 c = j < 4 ? cc : c4;
        sts128(j < 4 ? dst + j * 64 : SM_Z4 + 256 + (t8 & 1) * ZP4 + (t8 >> 1) * 16, hfma(v[j].x & ~TAGM, c.x, c.y), hfma(v[j].y, c.x, c.y), hfma(v[j].z, c.x, c.y), hfma(v[j].w, c.x, c.y));
      }
      if (t8 < 96) sts128(t8 < 64 ? SM_ZS + (t8 & 7) * ZPS + (t8 >> 3) * 16 : SM_Z4 + (t8 & 1) * ZP4 + (t8 & 30) * 8, 0, 0, 0, 0);
      if (MKT == 0) asm volatile("cp.async.bulk.wait_group.read 1;" ::: "memory");
      else asm volatile("cp.async.bulk.wait_group.read 0;" ::: "memory");
      bsync(9, 384);
      TS(11);
      if (MKT == 1) MARKERS();
      const bool lng = w < 8 || w == 9;
      const u32 ts = lane + 32 * (w == 8 ? 0 : w - 9), c = min(ts, 71u), ma = SM_MODS + 16 * c;
      const u32 sig = lng ? ksig : ts >> 4, l2 = lng ? lane : 32 + (ts & 15);
      const char* mq = gs + (G_MOD + (c >> 2) * 128 + (c & 3) * 16);
      if (!lng) {
#pragma unroll
        for (int j = 0; j < 6; j++) cpa16(ma + 1152 * j, mq + j * MODJ);
        cpa16(ma + 1152 * 6, p.dsk + 16 * c); cpa16(ma + 1152 * 7, p.wr + 16 * c);
        if (PFU == 3) {
#pragma unroll
          for (int j = 0; j < 4; j++) if (ts < 81) l2_line(p.wu + (b * WSH + (81 * j + ts) * 128));
        }
        if (tid == 352) {
          PROXY_FENCE();
          if (PFU == 1) l2_pre<WSH>(p.wu + b * WSH);
          mb_expect(SM_MB + 8, rho ? SLV : 46080);
#pragma unroll
          for (int i = GE; i < 3; i++) tma3d(SM_GATE + 12288 * i, &tm_gate, SM_MB + 8, 32 * b, i);
          if (!rho) tma3d(SM_GATE + SLV, &tm_gs, SM_MB + 8, 4096 + 4 * b, 0);
          mb_expect(SM_MB + 16, rho ? SLV : 46080);
          tma3d(SM_UP, &tm_up, SM_MB + 16, 32 * b, 0);
          if (!rho) tma3d(SM_UP + SLV, &tm_us, SM_MB + 16, 4096 + 4 * b, 0);
        }
      }
      const u32 wb = SM_W + sig * WSL;
      if (sig < 5) {
        const u32 za = (sig < 4 ? SM_ZS + 128 + sig * ZSS : SM_Z4 + 256) + l2 * 32, zb = za + (sig < 4 ? ZPS : ZP4);
        const uint4 c0 = lds128(zb - 32), c1 = lds128(za - 16), c2 = lds128(zb - 16), c3 = lds128(za), c4 = lds128(zb), c5 = lds128(za + 16), c6 = lds128(zb + 16);
        const u32 P[25] = {c0.z, c0.w, c1.x, c1.y, c1.z, c1.w, c2.x, c2.y, c2.z, c2.w, c3.x, c3.y, c3.z, c3.w, c4.x, c4.y, c4.z, c4.w, c5.x, c5.y, c5.z, c5.w, c6.x, c6.y, c6.z};
        u32 Q[25], D1[24], F4[23], W5[21], W3[17];
#pragma unroll
        for (int j = 1; j < 25; j++) Q[j] = __byte_perm(P[j - 1], P[j], 0x5432);
#pragma unroll
        for (int j = 1; j < 24; j++) D1[j] = hadd(P[j], Q[j]);
#pragma unroll
        for (int j = 2; j < 23; j++) F4[j] = hadd(D1[j], D1[j - 1]);
#pragma unroll
        for (int n = 0; n < 21; n++) W5[n] = hadd(F4[n + 2], P[n]);
#pragma unroll
        for (int n = 0; n < 17; n++) W3[n] = hadd(Q[n + 8], D1[n + 7]);
        const u32 a0 = wb + W5O + 64 * l2 + 16 * ((l2 >> 1) & 3);
#pragma unroll
        for (int i = 0; i < 4; i++) {
          sts128(a0 ^ (16 * i), W5[4 * i + 5], W5[4 * i + 6], W5[4 * i + 7], W5[4 * i + 8]);
          sts128((a0 ^ (16 * i)) + (W3O - W5O), W3[4 * i + 1], W3[4 * i + 2], W3[4 * i + 3], W3[4 * i + 4]);
        }
        if (lng) {
          if (lane < 16) sts128(wb + (lane & 7) * 16 + (lane & 8) * 400, 0, 0, 0, 0);
          const u32 a1 = wb + 32 * lane + 16 * ((lane >> 2) & 1);
#pragma unroll
          for (int i = 0; i < 4; i++) {
            const u32 a = (a1 ^ (16 * (i >> 1))) + 1024 * (i & 1), n = 4 * i;
            sts128(a + V2O, hadd(Q[n + 9], P[n + 8]), hadd(Q[n + 10], P[n + 9]), hadd(Q[n + 11], P[n + 10]), hadd(Q[n + 12], P[n + 11]));
            sts128(a + W9O, hadd(F4[n + 4], W5[n]), hadd(F4[n + 5], W5[n + 1]), hadd(F4[n + 6], W5[n + 2]), hadd(F4[n + 7], W5[n + 3]));
            sts128(a + W7O, hadd(F4[n + 6], W3[n]), hadd(F4[n + 7], W3[n + 1]), hadd(F4[n + 8], W3[n + 2]), hadd(F4[n + 9], W3[n + 3]));
          }
        }
      }
      if (w != 9) barrive(10, 352);
      __syncwarp();
      TS(32);
      if (lng) {
        const u32 wa = wb + ((lane >> 3) & 1) * 1024 + (((lane & 7) ^ (lane >> 4)) + 8 * (lane >> 4)) * 16;
        const u32 kv = lds32(SM_KV + 4 * sig), bi = (g >> 1) == q ? (hi ? kv << 16 : kv) : 0u;
        float acc[8][4] = {};
#pragma unroll
        for (int j = 0; j < 4; j++) { const uint4 a = ldsm4t(wa + V2O + j * 256); mma8_hf(acc[2 * j], a.x, a.y, bi); mma8_hf(acc[2 * j + 1], a.z, a.w, bi); }
        u32 bt = tp + (T9E + hi * TEO + (g >> 1) - q) * 4, wt = wa + W9O;
#pragma unroll 1
        for (int ty = 0; ty < 2; ty++) {
          uint4 a[4];
#pragma unroll
          for (int be = 0; be < 4; be++) a[be] = ldsm4t(wt + be * 256);
          u32 b1 = lds32(bt - 16);
#pragma unroll
          for (int d = 0; d < 8; d++) {
            const u32 b0 = lds32(bt + 16 * d);
#pragma unroll
            for (int be = 0; be < 4; be++) if (d + 2 * be < 8) mma_hf(acc[d + 2 * be], a[be].x, a[be].y, a[be].z, a[be].w, b0, b1);
            b1 = b0;
          }
          bt += (T7E - T9E) * 4; wt += W7O - W9O;
        }
        __syncwarp();
#pragma unroll
        for (int j = 0; j < 8; j++) sts128(wb + W9O + j * 512 + lane * 16, fu(acc[j][0]), fu(acc[j][1]), fu(acc[j][2]), fu(acc[j][3]));
        if (w != 9) barrive(14, 352);
        TS(34);
      }
      if (!lng) {
        asm volatile("cp.async.wait_all;" ::: "memory");
        uint4 md[6];
#pragma unroll
        for (int j = 0; j < 6; j++) md[j] = lds128(ma + 1152 * j);
        const uint4 wr = lds128(ma + 1152 * 7);
        POLLW(_Pragma("unroll") for (int j = 0; j < 6; j++) md[j] = ldr128(mq + j * MODJ),
              ((md[0].x ^ pm) | (md[1].x ^ pm) | (md[2].x ^ pm) | (md[3].x ^ pm) | (md[4].x ^ pm) | (md[5].x ^ pm)) & TAGM, 4);
        TS(61);
#pragma unroll
        for (int j = 0; j < 6; j++) {
          const u32 o = (j % 3 == 1) ? BONE : 0x80008000u;
          md[j] = make_uint4(bfma(md[j].x & ~TAGM, B2P64, o), bfma(md[j].y, B2P64, o), bfma(md[j].z, B2P64, o), bfma(md[j].w, B2P64, o));
          sts128(ma + 1152 * j, md[j].x, md[j].y, md[j].z, md[j].w);
        }
        const uint4 H = make_uint4(bmul(md[4].x, wr.x), bmul(md[4].y, wr.y), bmul(md[4].z, wr.z), bmul(md[4].w, wr.w));
        sts128(ma + 1152 * 7, H.x, H.y, H.z, H.w);
        sts128(ma + 1152 * 8, bfma(md[4].x, wr.x, H.x ^ 0x80008000u), bfma(md[4].y, wr.y, H.y ^ 0x80008000u), bfma(md[4].z, wr.z, H.z ^ 0x80008000u), bfma(md[4].w, wr.w, H.w ^ 0x80008000u));
        float c4[4] = {};
        mma_bf(c4, md[4].x, md[3].x, md[4].y, md[3].y, wr.x, wr.y); mma_bf(c4, md[4].z, md[3].z, md[4].w, md[3].w, wr.z, wr.w);
        if (q == g >> 1) sts64(SM_RC + (ts >> 2) * 8, fu(hi ? c4[1] : c4[0]), fu(hi ? c4[3] : c4[2]));
        if (ts < 2) sts128(SM_ONE + 16 * ts, ts ? 0 : BONE, ts ? 0 : BONE, ts ? 0 : BONE, ts ? 0 : BONE);
        TS(14);
        if (MKT == 2) MARKERS();
        if (w == 8) asm volatile("cp.async.bulk.wait_group 0;" ::: "memory");
        if (w == 8) barrive(14, 352);
        if (PFW == 2) {
#pragma unroll
          for (int j = 0; j < 4; j++) if (ts < 81) l2_line(p.wd + (b * WSH + (81 * j + ts) * 128));
        }
        bsync(13, 96);
      }
      if (w >= 8) barrive(11, 256);
    }
    if (w < 8) {
      const int u0 = 4 * (w - 4) + 2 * rho;
      const u32 t4 = SM_TAP + 4 * TAPS;
      u32 tr = t4 + ((hi ? TO : TE) + (g >> 1) - q) * 4;
      u32 zb = SM_Z4 + 256 + ((lane >> 3) & 1) * ZP4 + u0 * 128 + (lane & 7) * 16 + (lane >> 4) * 128;
      float acc[4][4] = {};
      u32 prev = 0;
#pragma unroll 1
      for (int it = min(u0 + 2, 4); it; it--) {
#pragma unroll
        for (int s = 0; s < 8; s++) {
          const uint4 z = ldsm4(zb - 16 * s);
          const u32 t0 = lds32(tr + 32 * s), t1 = lds32(tr + 32 * s + 16);
          mma_hf(acc[s & 1], t0, t1, prev, t0, z.x, z.y);
          mma_hf(acc[2 + (s & 1)], t0, t1, prev, t0, z.z, z.w);
          prev = t1;
        }
        zb -= 128; tr += 256;
      }
      {
        const uint4 z = ldsm4(zb); const u32 t0 = lds32(tr), t1 = lds32(tr + 16);
        mma_hf(acc[0], t0, t1, prev, t0, z.x, z.y); mma_hf(acc[2], t0, t1, prev, t0, z.z, z.w);
        if (w > 4) { const uint4 y = ldsm4(zb - 16); mma8_hf(acc[1], t1, zr, y.y); mma8_hf(acc[3], t1, zr, y.w); }
      }
      bsync(11, 256);
      u32 wa = (SM_W + 4 * WSL + W5O + row16(lane) + (u0 - 3) * 256) ^ 32, bt = t4 + (T5 + g - q) * 4;
#pragma unroll 1
      for (int al = min(u0 - 2, 6); al > 0; al--) {
#pragma unroll
        for (int ty = 0; ty < 2; ty++) {
          const uint4 a = ldsm4t(wa + ty * (W3O - W5O));
          const u32 bb = bt + ty * (T3 - T5) * 4;
          mma_hf(acc[ty], a.x, a.y, a.z, a.w, lds32(bb - 32), lds32(bb - 48));
          mma_hf(acc[2 + ty], a.x, a.y, a.z, a.w, lds32(bb), lds32(bb - 16));
        }
        wa = (wa - 256) ^ 32; bt += 32;
      }
      TS(35);
      const uint2 fc = lds64(SM_SC + 16 * 4 + 8);
      const u32 F = __byte_perm(fu(uf(fc.x) * uf(fc.y)), 0, 0x3232);
      char* yp = gs + (G_Y + 16384 - 2048 + b * BLK + w * 512 + q * 64 + 4 * g);
#pragma unroll
      for (int j = 0; j < 2; j++) {
        uint4 s3 = {0, 0, 0, 0};
        if (u0 >= 8) s3 = lds128(SM_W + 4 * WSL + W9O + (u0 - 8 + j) * 512 + lane * 16);
        y_store<32>(acc[2 * j][0] + acc[2 * j + 1][0] + uf(s3.x), acc[2 * j][1] + acc[2 * j + 1][1] + uf(s3.y), acc[2 * j][2] + acc[2 * j + 1][2] + uf(s3.z),
                acc[2 * j][3] + acc[2 * j + 1][3] + uf(s3.w), F, pml, yp + j * 256);
      }
      TS(16);
    } else {
      if (PFW == 3 && w == 9) {
#pragma unroll 1
        for (int j = 0; j < 12; j++) { if (lane < 27) l2_line(p.wd + (b * WSH + (27 * j + lane) * 128)); wait_clk(clk(), PFP); }
      }
      if (w >= 10) bsync(14, 352);
      if (w == 10 && b < YP) {
        wait_clk(clk(), 480 * ((int)(b >> 3) - 6));
        const char* yp = gs + (G_Y + (lane >> 2) * BLK + b * 128 + (lane & 3) * 32);
        u32 t = 0;
#pragma unroll
        for (int i = 0; i < 8; i++) t |= ldr32(yp + 8 * BLK * i);
        sts32(SM_KEY + 4 * (lane & 15), t);
      }
      if (PFW < 2 && tid == 352) { mb_wait(SM_MB + 8); if (PFW) mb_wait(SM_MB + 16); l2_pre<WSH>(p.wd + b * WSH); }
      if (D0C && tid == 352 && b < 108) {
        mb_wait(SM_MB + 16);
        PROXY_FENCE();
        mb_expect(SM_MB + 24, 49152);
        tma3d(SM_TAP, &tm_down, SM_MB + 24, 64 * (b % 9), 4 * (b / 9));
      }
      TS(17);
    }
  }
  post_conv(p, &tm_down, tid2 + p.zero, b);
  TSD();
  if (s2u(smem) != SM0) __trap();
}

typedef CUresult (*EncFn)(CUtensorMap*, CUtensorMapDataType, cuuint32_t, void*, const cuuint64_t*, const cuuint64_t*, const cuuint32_t*, const cuuint32_t*,
                          CUtensorMapInterleave, CUtensorMapSwizzle, CUtensorMapL2promotion, CUtensorMapFloatOOBfill);
static void make_map(EncFn enc, CUtensorMap* tm, void* ptr, int cols, int rows, int bw, int nb, CUtensorMapSwizzle sw, int gr = 192) {
  cuuint64_t gd[3] = {(cuuint64_t)cols, (cuuint64_t)gr, (cuuint64_t)(rows / gr)}, gs[2] = {(cuuint64_t)cols * 2, (cuuint64_t)cols * 2 * gr};
  cuuint32_t bd[3] = {(cuuint32_t)bw, (cuuint32_t)gr, (cuuint32_t)nb}, es[3] = {1, 1, 1};
  enc(tm, CU_TENSOR_MAP_DATA_TYPE_BFLOAT16, 3, ptr, gd, gs, bd, es, CU_TENSOR_MAP_INTERLEAVE_NONE, sw, CU_TENSOR_MAP_L2_PROMOTION_NONE, CU_TENSOR_MAP_FLOAT_OOB_FILL_NONE);
}
extern "C" void kernel_launch(void* const* d_in, const int* in_sizes, int n_in, void* d_out, int out_size) {
  static EncFn enc = nullptr;
  static void* scratch = nullptr;
  if (!enc) {
    cudaGetSymbolAddress(&scratch, g_s);
    cudaDriverEntryPointQueryResult qr;
    cudaGetDriverEntryPoint("cuTensorMapEncodeTiled", (void**)&enc, cudaEnableDefault, &qr);
    cudaFuncSetAttribute(fused_kernel, cudaFuncAttributeMaxDynamicSharedMemorySize, SM_TOTAL);
  }
  CUtensorMap tm_mod, tm_gate, tm_gs, tm_up, tm_us, tm_down;
  make_map(enc, &tm_mod, d_in[13], 3456, 576, 32, 3, CU_TENSOR_MAP_SWIZZLE_64B);
  make_map(enc, &tm_gate, d_in[9], 4608, 576, 32, 1, CU_TENSOR_MAP_SWIZZLE_64B);
  make_map(enc, &tm_gs, d_in[9], 4608, 576, 8, 3, CU_TENSOR_MAP_SWIZZLE_NONE);
  make_map(enc, &tm_up, d_in[10], 4608, 576, 32, 3, CU_TENSOR_MAP_SWIZZLE_64B);
  make_map(enc, &tm_us, d_in[10], 4608, 576, 8, 3, CU_TENSOR_MAP_SWIZZLE_NONE);
  make_map(enc, &tm_down, d_in[11], 576, 4608, 64, 1, CU_TENSOR_MAP_SWIZZLE_128B, 96);
  Prm p;
  p.x = (const char*)d_in[0]; p.la = (const char*)d_in[1]; p.ai = (const char*)d_in[2]; p.cr = (const char*)d_in[3];
  p.ci = (const char*)d_in[4]; p.ldt = (const char*)d_in[5]; p.dsk = (const char*)d_in[6]; p.wr = (const char*)d_in[8];
  p.wg = (const char*)d_in[9]; p.wu = (const char*)d_in[10]; p.wd = (const char*)d_in[11];
  p.c = (const char*)d_in[12]; p.out = (char*)d_out; p.zero = 0; p.gs = (char*)scratch;
  fused_kernel<<<128, 384, SM_TOTAL>>>(p, tm_mod, tm_gate, tm_gs, tm_up, tm_us, tm_down);
}
```

```cpp
#include <cuda_runtime.h>
#include <cuda.h>
#include <cuda_bf16.h>
#include <cuda_fp16.h>
#include <stdint.h>
#define FUSED 1
#define DEV __device__ __forceinline__
typedef uint32_t u32;

constexpr u32 BLK = 18432, G_Z = 0, G_Y = 128 * BLK, G_MOD = 2 * G_Y, G_KEY = G_MOD + 128 * 128, G_ACT = G_KEY + 128 * 128;
constexpr u32 G_PART = G_ACT + 576 * 128, G_EP = G_PART + 128 * 2048, G_END = G_EP + 128;
__device__ __align__(128) unsigned char g_s[G_END];
#define TS(i)
#define TS0()
#define TSE()
#define TSD()
#define TSX 0
#define TSN(code, n)
#define ERRF(code)

constexpr int SM0 = 1024;
constexpr int ROW = 1168, SLV = 36864;
constexpr int SM_GATE = SM0, SM_UP = SM_GATE + 46080, SM_XST = SM_UP + 46080, SM_MODS = SM_XST + 16 * ROW, SM_W = SM_MODS + 11008;
constexpr int KTAB = 9216, WSL = 12544, W5O = 128, W3O = 3328, V2O = 6400, W9O = 8448, W7O = 10496;
constexpr int ZPS = 2192, ZSS = 2 * ZPS, ZP4 = 2368;
constexpr int SM_ZS = SM_W + 5 * WSL, SM_Z4 = SM_ZS + 4 * ZSS, SM_TAP = SM_Z4 + 2 * ZP4, TAPS = 3328;
constexpr int SM_MB = SM_TAP + 5 * TAPS;
constexpr int SM_SC = SM_MB + 32;
constexpr int SM_KV = SM_SC + 80;
constexpr int SM_THR = SM_KV + 32;
constexpr int SM_SLOT = SM_THR + 48;
constexpr int SM_KEY = SM_SLOT + 32;
constexpr int SM_ST = SM_KEY + 64;
constexpr int SM_ST2 = SM_ST + 256;
constexpr int SM_RC = SM_ST2 + 256;
constexpr int SM_SP = SM_RC + 192;
constexpr int SM_AF = SM_SP + 1152, SM_SIL = SM_AF + 1152, SM_INV = SM_SIL + 1152, SM_END = SM_SP + 5760;
constexpr int SM_ONE = SM_MODS + 9 * 1152;
constexpr int SM_WD = SM_W, SM_XS = SM_W + 36864, SM_AC = SM_ZS, SM_RED = SM_AC + 6144;
constexpr int SM_TSB = SM_END, SM_TOTAL = SM_END + TSX - SM0;
static_assert(SM_W % 1024 == 0 && SM_TAP % 1024 == 0 && SM_MODS + 8 * KTAB <= SM_ZS && SM_ZS + 2 * KTAB <= SM_TAP && SM_RED + 10240 <= SM_TAP && SM_XS + 8 * ROW <= SM_ZS, "smem map");
static_assert(SM_MB % 16 == 0 && SM_THR % 16 == 0 && SM_ST % 16 == 0 && SM_SP % 16 == 0 && SM_TOTAL <= 232448, "smem map");
constexpr int TE = 4, TO = 276, T5 = 560, T3 = 624, T9E = 680, T7E = 760, TEO = 40;
#define MT 10
#define DECL 1
#define MKT 1
#define KST 128
#define DE1 1
#define DE2 4
#define DE3 5
#define OUTA 2
#define OUTB 7
#define PFW 1
#define PFU 0
#define KD 700
#define D0C 0
#define YE 72
#define YL 104
#define YD 250
#define YS 0
#define YD0 0
#define YD8 0
#define KD1 1
#define AD 0
#define PD 0
#define ZD 0
#define DD 1000
#define YP 0
#define PFP 200
#define GE 0
#define NB8 8
#define DX 0
#define DMOD 1000
#define PFG 1
constexpr int SPIN = 1 << 16, NEARLY = 4;
constexpr u32 TAGM = 0x40004000u, TAGR = 0x40000000u, INVAL = 0x00004801u;

DEV u32 s2u(const void* p) { return (u32)__cvta_generic_to_shared(p); }
DEV void mma_bf(float (&c)[4], u32 a0, u32 a1, u32 a2, u32 a3, u32 b0, u32 b1) {
  asm("mma.sync.aligned.m16n8k16.row.col.f32.bf16.bf16.f32 {%0,%1,%2,%3},{%4,%5,%6,%7},{%8,%9},{%0,%1,%2,%3};"
      : "+f"(c[0]), "+f"(c[1]), "+f"(c[2]), "+f"(c[3]) : "r"(a0), "r"(a1), "r"(a2), "r"(a3), "r"(b0), "r"(b1));
}
DEV void mma_hf(float (&c)[4], u32 a0, u32 a1, u32 a2, u32 a3, u32 b0, u32 b1) {
  asm("mma.sync.aligned.m16n8k16.row.col.f32.f16.f16.f32 {%0,%1,%2,%3},{%4,%5,%6,%7},{%8,%9},{%0,%1,%2,%3};"
      : "+f"(c[0]), "+f"(c[1]), "+f"(c[2]), "+f"(c[3]) : "r"(a0), "r"(a1), "r"(a2), "r"(a3), "r"(b0), "r"(b1));
}
DEV void mma8_bf(float (&c)[4], u32 a0, u32 a1, u32 b0) {
  asm("mma.sync.aligned.m16n8k8.row.col.f32.bf16.bf16.f32 {%0,%1,%2,%3},{%4,%5},{%6},{%0,%1,%2,%3};"
      : "+f"(c[0]), "+f"(c[1]), "+f"(c[2]), "+f"(c[3]) : "r"(a0), "r"(a1), "r"(b0));
}
DEV void mma8_hf(float (&c)[4], u32 a0, u32 a1, u32 b0) {
  asm("mma.sync.aligned.m16n8k8.row.col.f32.f16.f16.f32 {%0,%1,%2,%3},{%4,%5},{%6},{%0,%1,%2,%3};"
      : "+f"(c[0]), "+f"(c[1]), "+f"(c[2]), "+f"(c[3]) : "r"(a0), "r"(a1), "r"(b0));
}
DEV u32 movm(u32 x) { u32 r; asm("movmatrix.sync.aligned.m8n8.trans.b16 %0,%1;" : "=r"(r) : "r"(x)); return r; }
DEV uint4 ldsm4(u32 a) { uint4 r; asm volatile("ldmatrix.sync.aligned.m8n8.x4.shared.b16 {%0,%1,%2,%3},[%4];" : "=r"(r.x), "=r"(r.y), "=r"(r.z), "=r"(r.w) : "r"(a)); return r; }
DEV uint4 ldsm4t(u32 a) { uint4 r; asm volatile("ldmatrix.sync.aligned.m8n8.x4.trans.shared.b16 {%0,%1,%2,%3},[%4];" : "=r"(r.x), "=r"(r.y), "=r"(r.z), "=r"(r.w) : "r"(a)); return r; }
DEV u32 lds32(u32 a) { u32 r; asm volatile("ld.volatile.shared.u32 %0,[%1];" : "=r"(r) : "r"(a)); return r; }
DEV uint2 lds64(u32 a) { uint2 r; asm volatile("ld.shared.v2.u32 {%0,%1},[%2];" : "=r"(r.x), "=r"(r.y) : "r"(a)); return r; }
DEV uint4 lds128(u32 a) { uint4 r; asm volatile("ld.shared.v4.u32 {%0,%1,%2,%3},[%4];" : "=r"(r.x), "=r"(r.y), "=r"(r.z), "=r"(r.w) : "r"(a)); return r; }
DEV void sts16(u32 a, u32 v) { asm volatile("st.shared.u16 [%0],%1;" ::"r"(a), "h"((unsigned short)v) : "memory"); }
DEV void sts32(u32 a, u32 v) { asm volatile("st.shared.u32 [%0],%1;" ::"r"(a), "r"(v) : "memory"); }
DEV void sts64(u32 a, u32 x, u32 y) { asm volatile("st.shared.v2.u32 [%0],{%1,%2};" ::"r"(a), "r"(x), "r"(y) : "memory"); }
DEV void sts128(u32 a, u32 x, u32 y, u32 z, u32 w) { asm volatile("st.shared.v4.u32 [%0],{%1,%2,%3,%4};" ::"r"(a), "r"(x), "r"(y), "r"(z), "r"(w) : "memory"); }
DEV uint4 ldr128(const void* p) { uint4 v; asm volatile("ld.relaxed.gpu.global.v4.u32 {%0,%1,%2,%3},[%4];" : "=r"(v.x), "=r"(v.y), "=r"(v.z), "=r"(v.w) : "l"(p) : "memory"); return v; }
DEV uint2 ldr64(const void* p) { uint2 v; asm volatile("ld.relaxed.gpu.global.v2.u32 {%0,%1},[%2];" : "=r"(v.x), "=r"(v.y) : "l"(p) : "memory"); return v; }
DEV u32 ldr32(const void* p) { u32 v; asm volatile("ld.relaxed.gpu.global.u32 %0,[%1];" : "=r"(v) : "l"(p) : "memory"); return v; }
DEV void str128(void* p, u32 x, u32 y, u32 z, u32 w) { asm volatile("st.relaxed.gpu.global.v4.u32 [%0],{%1,%2,%3,%4};" ::"l"(p), "r"(x), "r"(y), "r"(z), "r"(w) : "memory"); }
DEV void str64(void* p, u32 x, u32 y) { asm volatile("st.relaxed.gpu.global.v2.u32 [%0],{%1,%2};" ::"l"(p), "r"(x), "r"(y) : "memory"); }
DEV void str32(void* p, u32 x) { asm volatile("st.relaxed.gpu.global.u32 [%0],%1;" ::"l"(p), "r"(x) : "memory"); }
DEV void str16(void* p, u32 x) { asm volatile("st.relaxed.gpu.global.u16 [%0],%1;" ::"l"(p), "h"((unsigned short)x) : "memory"); }
DEV uint4 ldg128(const void* p) { uint4 v; asm volatile("ld.global.nc.v4.u32 {%0,%1,%2,%3},[%4];" : "=r"(v.x), "=r"(v.y), "=r"(v.z), "=r"(v.w) : "l"(p)); return v; }
DEV uint2 ldg64(const void* p) { uint2 v; asm volatile("ld.global.nc.v2.u32 {%0,%1},[%2];" : "=r"(v.x), "=r"(v.y) : "l"(p)); return v; }
DEV u32 ldg32(const void* p) { u32 v; asm volatile("ld.global.nc.u32 %0,[%1];" : "=r"(v) : "l"(p)); return v; }
DEV u32 ldg16(const void* p) { unsigned short v; asm volatile("ld.global.nc.u16 %0,[%1];" : "=h"(v) : "l"(p)); return v; }
#define bsync(id, n) asm volatile("bar.sync %0,%1;" ::"n"(id), "n"(n) : "memory")
#define barrive(id, n) asm volatile("bar.arrive %0,%1;" ::"n"(id), "n"(n) : "memory")
DEV void mb_init(u32 a) { asm volatile("mbarrier.init.shared.b64 [%0],1;" ::"r"(a) : "memory"); }
DEV void mb_expect(u32 a, u32 bytes) { asm volatile("mbarrier.arrive.expect_tx.shared.b64 _,[%0],%1;" ::"r"(a), "r"(bytes) : "memory"); }
DEV void mb_wait(u32 a, u32 ph = 0) {
  u32 ok; int it = 0;
  do { asm volatile("{.reg .pred p; mbarrier.try_wait.parity.shared.b64 p,[%1],%2; selp.u32 %0,1,0,p;}" : "=r"(ok) : "r"(a), "r"(ph) : "memory"); } while (!ok && ++it < SPIN);
}
template <int N> DEV void bulk_out(void* dst, u32 src) { asm volatile("cp.async.bulk.global.shared::cta.bulk_group [%0],[%1],%2;" ::"l"(dst), "r"(src), "n"(N) : "memory"); }
constexpr u32 WSH = 41472;
DEV void l2_line(const void* p) { asm volatile("prefetch.global.L2 [%0];" ::"l"(p) : "memory"); }
template <int N> DEV void l2_pre(const void* p) { asm volatile("cp.async.bulk.prefetch.L2.global [%0],%1;" ::"l"(p), "n"(N) : "memory"); }
DEV void tma3d(u32 dst, const CUtensorMap* tm, u32 mb, int c0, int c2) {
  asm volatile("cp.async.bulk.tensor.3d.shared::cluster.global.mbarrier::complete_tx::bytes [%0],[%1,{%3,0,%4}],[%2];"
               ::"r"(dst), "l"((uint64_t)tm), "r"(mb), "r"(c0), "r"(c2) : "memory");
}
DEV float blo(u32 w) { return __uint_as_float(w << 16); }
DEV float bhi(u32 w) { return __uint_as_float(w & 0xffff0000u); }
DEV u32 pk_bf(float lo, float hi) { u32 r; asm("cvt.rn.bf16x2.f32 %0,%1,%2;" : "=r"(r) : "f"(hi), "f"(lo)); return r; }
DEV u32 pk_hf(float lo, float hi) { u32 r; asm("cvt.rn.f16x2.f32 %0,%1,%2;" : "=r"(r) : "f"(hi), "f"(lo)); return r; }
DEV float rbf(float x) { return __uint_as_float(pk_bf(0.f, x) & 0xffff0000u); }
DEV u32 bfma(u32 a, u32 b, u32 c) { u32 r; asm("fma.rn.bf16x2 %0,%1,%2,%3;" : "=r"(r) : "r"(a), "r"(b), "r"(c)); return r; }
DEV u32 bmul(u32 a, u32 b) { u32 r; asm("mul.rn.bf16x2 %0,%1,%2;" : "=r"(r) : "r"(a), "r"(b)); return r; }
DEV u32 badd(u32 a, u32 b) { u32 r; asm("add.rn.bf16x2 %0,%1,%2;" : "=r"(r) : "r"(a), "r"(b)); return r; }
DEV u32 hadd(u32 a, u32 b) { u32 r; asm("add.rn.f16x2 %0,%1,%2;" : "=r"(r) : "r"(a), "r"(b)); return r; }
DEV u32 hfma(u32 a, u32 b, u32 c) { u32 r; asm("fma.rn.f16x2 %0,%1,%2,%3;" : "=r"(r) : "r"(a), "r"(b), "r"(c)); return r; }
struct C2 { u32 re, im; };
DEV C2 cm2(C2 a, C2 b) {
  const __half2 ar = *reinterpret_cast<__half2*>(&a.re), ai = *reinterpret_cast<__half2*>(&a.im), br = *reinterpret_cast<__half2*>(&b.re), bi = *reinterpret_cast<__half2*>(&b.im);
  __half2 re = __hfma2(ar, br, __hneg2(__hmul2(ai, bi))), im = __hfma2(ar, bi, __hmul2(ai, br));
  return {*reinterpret_cast<u32*>(&re), *reinterpret_cast<u32*>(&im)};
}
DEV C2 pk2(const float2 (&a)[2]) { return {pk_hf(a[0].x, a[1].x), pk_hf(a[0].y, a[1].y)}; }
DEV C2 pk2c(const float2 (&a)[2]) { return {pk_hf(a[0].x, a[1].x), pk_hf(-a[0].y, -a[1].y)}; }
DEV u32 cpy(u32 x, u32 zr, int alt) {
  u32 r;
  if (alt) asm volatile("xor.b32 %0,%1,%2;" : "=r"(r) : "r"(x), "r"(zr)); else asm volatile("mad.lo.u32 %0,%2,%2,%1;" : "=r"(r) : "r"(x), "r"(zr));
  return r;
}
DEV u32 opq(u32 x) { u32 r; asm volatile("mov.u32 %0,%1;" : "=r"(r) : "r"(x)); return r; }
DEV u32 chan(u32 b, u32 i) { return 16 * (b >> 2) + 2 * (b & 3) + (i & 1) + 4 * (i & 2); }
DEV u32 row16(u32 lane) { const u32 r0 = (lane & 7) + ((lane >> 3) & 1) + 8 * (lane >> 4) - 1; return (r0 ^ ((r0 >> 3) & 3)) * 16; }
DEV u32 clk() { u32 r; asm volatile("mov.u32 %0,%%clock;" : "=r"(r)::"memory"); return r; }
DEV void wait_clk(u32 t, int d) { while ((int)(clk() - t) < d); }
DEV float ex2(float x) { float r; asm("ex2.approx.ftz.f32 %0,%1;" : "=f"(r) : "f"(x)); return r; }
DEV float rcpf(float x) { float r; asm("rcp.approx.ftz.f32 %0,%1;" : "=f"(r) : "f"(x)); return r; }
DEV float2 cmul(float2 a, float2 b) { return make_float2(fmaf(a.x, b.x, -a.y * b.y), fmaf(a.x, b.y, a.y * b.x)); }
DEV float2 csq(float2 a) { return make_float2(fmaf(a.x, a.x, -a.y * a.y), (a.x + a.x) * a.y); }
DEV float2 cexp(float lr2, float th) {
  const float m = ex2(lr2);
  return make_float2(m * __cosf(th), m * __sinf(th));
}
DEV float silu_f(float v) { return v * rcpf(1.f + ex2(-1.4426950408889634f * v)); }
constexpr u32 B2P64 = 0x5F805F80u, B2M64 = 0x1F801F80u, BONE = 0x3F803F80u;
constexpr u32 MODJ = 18 * 128;
DEV float sqrta(float x) { float r; asm("sqrt.approx.ftz.f32 %0,%1;" : "=f"(r) : "f"(x)); return r; }
DEV u32 fu(float x) { return __float_as_uint(x); }
DEV float uf(u32 x) { return __uint_as_float(x); }
DEV void mma_hf_o(float (&d)[4], const float (&c)[4], const u32 (&a)[4], u32 b0, u32 b1) {
  asm("mma.sync.aligned.m16n8k16.row.col.f32.f16.f16.f32 {%0,%1,%2,%3},{%4,%5,%6,%7},{%8,%9},{%10,%11,%12,%13};"
      : "=f"(d[0]), "=f"(d[1]), "=f"(d[2]), "=f"(d[3]) : "r"(a[0]), "r"(a[1]), "r"(a[2]), "r"(a[3]), "r"(b0), "r"(b1), "f"(c[0]), "f"(c[1]), "f"(c[2]), "f"(c[3]));
}

DEV void mma_hf_t(float (&c)[4], const u32 (&a)[4], u32 b0, u32 b1) { mma_hf(c, a[0], a[1], a[2], a[3], b0, b1); }
DEV void cpa16(u32 dst, const void* src) { asm volatile("cp.async.cg.shared.global [%0],[%1],16;" ::"r"(dst), "l"(src) : "memory"); }
DEV void tm_pre(const CUtensorMap* tm) { asm volatile("prefetch.tensormap [%0];" ::"l"((uint64_t)tm) : "memory"); }
#define PROXY_FENCE() asm volatile("fence.proxy.async.shared::cta;" ::: "memory")
struct Prm {
  const char *la, *ai, *cr, *ci, *ldt;
  u32 zero;
  const char *x, *c;
  char* gs;
  const char *dsk, *wr, *wg, *wu, *wd;
  char* out;
};
constexpr float LOG2E = 1.4426950408889634f, F2P64 = 1.8446744073709552e19f, F2M64 = 5.421010862427522e-20f;

template <int S> DEV void y_store(float c0, float c1, float c2, float c3, u32 F, u32 pml, char* yp) {
  str32(yp, bmul(pk_bf(c0, c2), F) | pml);
  str32(yp + S, bmul(pk_bf(c1, c3), F) | pml);
}
DEV void merge4(u32 (&h)[8], uint4 a, uint4 b) {
  const u32 e1 = min(a.x, b.x), e2 = max(a.z, b.z), o1 = min(a.y, b.y), o2 = max(a.w, b.w), o0 = max(a.y, b.y), e3 = min(a.z, b.z);
  const u32 f1 = max(e1, e2), f2 = min(e1, e2), p1 = max(o1, o2), p2 = min(o1, o2);
  h[0] = max(a.x, b.x); h[1] = max(o0, f1); h[2] = min(o0, f1); h[3] = max(p1, f2); h[4] = min(p1, f2); h[5] = max(p2, e3); h[6] = min(p2, e3); h[7] = min(a.w, b.w);
}
DEV void top8(u32 (&a)[8], uint4 l, uint4 m) {
  u32 b[8];
  merge4(b, l, m);
#pragma unroll
  for (int i = 0; i < 8; i++) a[i] = max(a[i], b[7 - i]);
#pragma unroll
  for (int s = 4; s; s >>= 1)
#pragma unroll
    for (int i = 0; i < 8; i++) if (!(i & s)) { const u32 x = a[i], y = a[i + s]; a[i] = max(x, y); a[i + s] = min(x, y); }
}
#define POLL(load, cond_bad, code) { int it_ = 0; do { load; if (++it_ > SPIN) { ERRF(code); break; } } while (__any_sync(~0u, (cond_bad))); }
#define POLLW(load, cond_bad, code) { int it_ = 0; while (__any_sync(~0u, (cond_bad))) { if (++it_ > SPIN) { ERRF(code); break; } load; } TSN(code, it_); }

#define DOWN(E) if (tid == 288 && b < 108) { const u32 c0 = 64 * (b % 9), c2 = 4 * (b / 9); \
    if (!D0C && E == 1) { mb_expect(SM_MB + 24, 49152); tma3d(SM_TAP, tm_down, SM_MB + 24, c0, c2); } \
    if (DE1 == E) tma3d(SM_WD, tm_down, SM_MB + 24, c0, c2 + 1); \
    if (DE2 == E) tma3d(SM_WD + 12288, tm_down, SM_MB + 24, c0, c2 + 2); \
    if (DE3 == E) tma3d(SM_WD + 24576, tm_down, SM_MB + 24, c0, c2 + 3); }
#define OUTR(E) if (((OUTA == E) | (OUTB == E) << 1) & ot) { const u32 tl = 4 * ((lane >> 1) & 1) + ((lane >> 2) & 3) + 8 * (lane & 1); \
    bulk_out<1152>(p.out + (b * BLK + tl * 1152), SM_XST + ((lane & 2) + 4 * (lane & 1) + ((lane >> 2) & 1) + (lane & 8)) * ROW); \
    asm volatile("cp.async.bulk.commit_group;" ::: "memory"); }
DEV void ffn_tail(const Prm& p, const CUtensorMap* tm_down, uint4 (&A)[24], const u32 tid, const u32 b, const u32 par, const u32 ot) {
  const u32 w = tid >> 5, lane = tid & 31, g = lane >> 2, q = lane & 3, kq = w & 3, tg = w >> 2;
  const u32 rho = b & 1, pm = par ? TAGM : 0;
  char* const gs = p.gs;
  __syncthreads();
  TS(25);
  DOWN(5);
  {
    float c0[2][4] = {}, c1[2][4] = {};
    const u32 ba = SM_XS + (lane & 7) * ROW + (18 * kq + (lane >> 3)) * 16;
    uint4 bb[5];
#pragma unroll
    for (int s = 0; s < 5; s++) bb[s] = ldsm4(ba + s * 64);
#pragma unroll
    for (int s = 0; s < 9; s++) mma_bf(c0[s & 1], A[s].x, A[s].y, A[s].z, A[s].w, s & 1 ? bb[s >> 1].z : bb[s >> 1].x, s & 1 ? bb[s >> 1].w : bb[s >> 1].y);
    const u32 ra = SM_RED + (8 * tg + kq) * 512 + lane * 16;
    if (tg < 2) {
#pragma unroll
      for (int s = 0; s < 9; s++) mma_bf(c1[s & 1], A[9 + s].x, A[9 + s].y, A[9 + s].z, A[9 + s].w, s & 1 ? bb[s >> 1].z : bb[s >> 1].x, s & 1 ? bb[s >> 1].w : bb[s >> 1].y);
      sts128(ra + 2048, fu(c1[0][0] + c1[1][0]), fu(c1[0][1] + c1[1][1]), fu(c1[0][2] + c1[1][2]), fu(c1[0][3] + c1[1][3]));
    }
    sts128(ra, fu(c0[0][0] + c0[1][0]), fu(c0[0][1] + c0[1][1]), fu(c0[0][2] + c0[1][2]), fu(c0[0][3] + c0[1][3]));
  }
  TS(39);
  __syncthreads();
  const u32 tr = clk();
  OUTR(6);
  if (w - 3 - rho < 5 - rho) {
    const u32 t = 7 - w;
    float s[4] = {};
#pragma unroll
    for (int i = 0; i < 4; i++) { const uint4 u = lds128(SM_RED + (t * 4 + i) * 512 + lane * 16); s[0] += uf(u.x); s[1] += uf(u.y); s[2] += uf(u.z); s[3] += uf(u.w); }
    const u32 sg = pk_bf(silu_f(rbf(s[0])), silu_f(rbf(s[1])));
    const u32 act = movm(bmul(bmul(sg, pk_bf(s[2], s[3])), B2M64));
    str32(gs + (G_ACT + (t < 4 ? 4 * b + t : 512 + (b >> 1)) * 128 + lane * 4), act | (q ? 0 : pm));
  }
  TS(26);
  if (b < 108) {
    const char* src = gs + (G_ACT + (b / 9) * 6144 + tid * 16);
    uint4 a;
    if (AD) a.x = INVAL; else a = ldr128(src);
    if (AD && w >= 4) wait_clk(tr, AD);
    if (w < 4) {
      const u32 aa = SM_WD + (8 * (lane >> 4) + (lane & 7)) * 128 + (((2 * w + ((lane >> 3) & 1)) ^ (lane & 7)) << 4);
      mb_wait(SM_MB + 24);
#pragma unroll
      for (int s = 0; s < 24; s++) A[s] = ldsm4t(aa + (s < 6 ? SM_TAP - SM_WD : -12288) + s * 2048);
    }
    TS(28);
    POLLW(a = ldr128(src), (a.x ^ pm) & TAGM, 9);
    sts128(SM_AC + tid * 16, a.x & ~TAGM, a.y, a.z, a.w);
    TS(27);
    if (w < 4) {
      bsync(8, 384);
      float c[4][4] = {};
#pragma unroll
      for (int s = 0; s < 12; s++) {
        const uint4 bb = ldsm4(SM_AC + lane * 16 + s * 512);
        mma_bf(c[2 * (s & 1)], A[2 * s].x, A[2 * s].y, A[2 * s].z, A[2 * s].w, bb.x, bb.y);
        mma_bf(c[2 * (s & 1) + 1], A[2 * s + 1].x, A[2 * s + 1].y, A[2 * s + 1].z, A[2 * s + 1].w, bb.z, bb.w);
      }
      char* dst = gs + (G_PART + b * 2048 + w * 512 + lane * 8);
      u32 o[4];
#pragma unroll
      for (int i = 0; i < 4; i++) o[i] = (fu(((c[0][i] + c[1][i]) + (c[2][i] + c[3][i])) * F2P64) & ~1u) | par;
      str64(dst, o[0], o[1]); str64(dst + 256, o[2], o[3]);
      TS(29);
    } else barrive(8, 384);
  }
  OUTR(7);
  if (w == 8 && b < 72) {
    const u32 ta = clk();
    const u32 kg = lds32(SM_SLOT + 4 * g), ro = (2047 - ((kg >> 2) & 2047)) * 1152 + 16 * b;
    const char* src = gs + (G_PART + (b >> 3) * 2048 + (b & 7) * 256 + lane * 8);
    const char* xs = gs + (G_Y + ro);
    uint4 xt;
    POLL(xt = ldr128(xs), (xt.x ^ TAGR) & TAGM, 10);
    const u32 x1w = (q & 2) ? ((q & 1) ? xt.w : xt.z) : ((q & 1) ? xt.y : bmul(xt.x ^ TAGR, B2P64));
    const u32 gw = lds32(SM_MODS + 5760 + 16 * b + 4 * q);
    const u32 hw = lds32(SM_XS + g * ROW + b * 16 + q * 4);
    const float sgm = rcpf(1.f + ex2(-LOG2E * bhi(kg ^ (~((int)kg >> 31) | 0x80000000))));
    char* const dst = p.out + (ro + 4 * q);
    uint2 v[12];
#pragma unroll
    for (int j = 0; j < 12; j++) v[j] = make_uint2(1, 0);
    u32 bad;
    if (PD) wait_clk(ta, PD);
    POLL({ bad = 0; _Pragma("unroll") for (int j = 0; j < 12; j++) { if (((v[j].x ^ par) | (v[j].y ^ par)) & 1) v[j] = ldr64(src + j * 9 * 2048); }
           _Pragma("unroll") for (int j = 0; j < 12; j++) bad |= (v[j].x ^ par) | (v[j].y ^ par); }, bad & 1, 11);
    float s0[4] = {}, s1[4] = {};
#pragma unroll
    for (int j = 0; j < 12; j++) { s0[j & 3] += uf(v[j].x); s1[j & 3] += uf(v[j].y); }
    const u32 y = movm(pk_bf((s0[0] + s0[1]) + (s0[2] + s0[3]), (s1[0] + s1[1]) + (s1[2] + s1[3])));
    *(u32*)dst = badd(x1w, bmul(gw, badd(hw, bmul(y, pk_bf(sgm, sgm)))));
    if (b == 0 && lane == 0) str32(gs + G_EP, par);
    TS(30); TSE();
  }
  if (w == 10) asm volatile("cp.async.bulk.wait_group.read 0;" ::: "memory");
}

DEV void post_conv(const Prm& p, const CUtensorMap* tm_down, const u32 tid, const u32 b) {
  const u32 w = tid >> 5, lane = tid & 31;
  const u32 g = lane >> 2, q = lane & 3, e = g >> 2, h = (g >> 1) & 1, hi = g & 1;
  const u32 pm = lds32(SM_THR + 4), par = pm >> 30;
  char* const gs = p.gs;
  const u32 cho = 128 * w + 64 * e + 16 * q;
  u32 x1[4][4], h2[4][4], key[4], lt;
  char* const rowp = gs + (b * BLK + (4 * h + 8 * hi) * 1152 + cho);
  u32 ot = 0;
  uint4 A[24];
#define AROW(t) const u32 arow = 144 * ((t >> 5) & 3) + ((t >> 1) & 8) + (t & 7), ab = (t & 8) ? SM_UP : SM_GATE;
#define AFRAG9() { _Pragma("unroll") for (int s = 0; s < 9; s++) A[s] = ldsm4t(ab + SLV + arow * 16 + s * 256); }
  if (w < 9) {
    const u32 yc = 8 * (q >> 1) + 2 * (g >> 1), y1 = w < 8 ? BLK : 4 * BLK, y2 = 2 * y1;
    const char* ysrc = gs + (G_Y + (q & 1) * 16 + (w < 8 ? (16 * w + 8 * (q >> 1) + (g & 4)) * BLK + b * 128 + (g & 3) * 32 : (8 * yc + 2 * hi + ((b >> 4) & 1)) * BLK + 16384 + ((b >> 5) * 16 + (b & 15)) * 32));
    const char* const ys[4] = {ysrc, ysrc + y1, ysrc + y2, ysrc + (y1 + y2)};
    uint4 yv[4];
    u32 tc = clk();
    if (w < 4 && !YD0 && (!YD || b < YL)) {
#pragma unroll
      for (int v = 0; v < 4; v++) yv[v] = ldr128(ys[v]);
    } else {
#pragma unroll
      for (int v = 0; v < 4; v++) yv[v].x = INVAL;
    }
    const u32 ma = SM_MODS + cho, xa = SM_XST + (2 * h + 4 * hi) * ROW + cho;
    const uint4 sa = lds128(ma), ca = lds128(ma + 1152), ga = lds128(ma + 2304), dk = lds128(ma + 6912);
    const uint4 rb = lds128((g & 2) ? SM_ONE + 16 * hi : (ma ^ 64) + 8064 + 1152 * hi);
    const u32 saw[4] = {sa.x, sa.y, sa.z, sa.w}, caw[4] = {ca.x, ca.y, ca.z, ca.w}, gaw[4] = {ga.x, ga.y, ga.z, ga.w}, dw[4] = {dk.x, dk.y, dk.z, dk.w};
    u32 hD[4][4];
#pragma unroll
    for (int k = 0; k < 4; k++) {
      const uint4 st = lds128(SM_ST + 16 * (2 * h + 4 * hi + (k & 1) + 8 * (k >> 1))), xv = lds128(xa + ((k & 1) + 8 * (k >> 1)) * ROW);
      x1[k][0] = xv.x; x1[k][1] = xv.y; x1[k][2] = xv.z; x1[k][3] = xv.w;
#pragma unroll
      for (int v = 0; v < 4; v++) {
        const u32 d = badd(x1[k][v], st.x), z = bfma(d, st.y, bmul(d, st.z));
        hD[k][v] = bmul(badd(bmul(z, caw[v]), saw[v]), dw[v]);
      }
    }
    const bool own = (q >> 1) == e;
    const u32 spw = SM_SP + (2 * w + e) * 320 + (g & 3) * 16 + (own ? ((q & 1) == h ? 4 : 12) : 8 - 8 * (q & 1));
    TS(18);
    if (w >= 4 || (YS && b >= YL)) { if (w < 8 && b < YE) barrive(12, 288); else bsync(12, 288); tc = clk(); }
    if (w == 8) barrive(7, 64);
    if (YD && b >= YL) wait_clk(tc, YD);
    if (YD0 && b < YL && (w < 4 || (w == 8 ? YD8 : b >= YE))) wait_clk(tc, w < 4 ? YD0 : YD8);
    TS(13);
    POLLW(_Pragma("unroll") for (int v = 0; v < 4; v++) if ((yv[v].x ^ pm) & TAGM) yv[v] = ldr128(ys[v]),
          ((yv[0].x ^ pm) | (yv[1].x ^ pm) | (yv[2].x ^ pm) | (yv[3].x ^ pm)) & TAGM, 5);
    TS(19);
    if (DECL && w < 4) asm volatile("setmaxnreg.dec.sync.aligned.u32 168;");
#pragma unroll
    for (int k = 0; k < 4; k += 2) {
      float X[4] = {}, Y[4] = {}, R[4] = {};
#pragma unroll
      for (int v = 0; v < 4; v++) {
        const u32 y0 = k ? yv[v].z : yv[v].x & ~TAGM, y1 = k ? yv[v].w : yv[v].y;
        x1[k][v] = badd(x1[k][v], bmul(gaw[v], bfma(movm(y0), B2P64, hD[k][v])));
        x1[k + 1][v] = badd(x1[k + 1][v], bmul(gaw[v], bfma(movm(y1), B2P64, hD[k + 1][v])));
        mma8_bf(X, x1[k][v], x1[k + 1][v], x1[k][v]); mma8_bf(Y, x1[k][v], x1[k + 1][v], x1[k + 1][v]);
        if (v & 1) mma_bf(R, x1[k][v - 1], x1[k + 1][v - 1], x1[k][v], x1[k + 1][v], v & 2 ? rb.z : rb.x, v & 2 ? rb.w : rb.y);
      }
      sts32(spw + k * 64, fu(own ? (hi ? X[1] : X[0]) : R[0] + R[1]));
      sts32(spw + k * 64 + 64, fu(own ? (hi ? Y[3] : Y[2]) : R[2] + R[3]));
    }
    barrive(1, 320);
    TS(36);
    const uint4 sb = lds128(ma + 3456), cb = lds128(ma + 4608), gb = lds128(ma + 5760);
    const u32 sbw[4] = {sb.x, sb.y, sb.z, sb.w}, cbw[4] = {cb.x, cb.y, cb.z, cb.w}, gbw[4] = {gb.x, gb.y, gb.z, gb.w};
    bsync(2, 320);
    TS(37);
    lt = lds32(SM_THR);
#pragma unroll
    for (int k = 0; k < 4; k++) {
      const uint4 st = lds128(SM_ST2 + 64 * k + 16 * (g & 3));
      key[k] = st.w;
      u32 o[4];
#pragma unroll
      for (int v = 0; v < 4; v++) {
        const u32 d = badd(x1[k][v], st.x), z = bfma(d, st.y, bmul(d, st.z));
        h2[k][v] = badd(bmul(z, cbw[v]), sbw[v]);
        o[v] = badd(x1[k][v], bmul(gbw[v], h2[k][v]));
      }
      h2[k][0] = bmul(h2[k][0], B2M64) | TAGR;
      if (key[k] >= lt) str128(rowp + k * 1152, h2[k][0], h2[k][1], h2[k][2], h2[k][3]);
      sts128(xa + ((k & 1) + 8 * (k >> 1)) * ROW, o[0], o[1], o[2], o[3]);
    }
    barrive(3, 320);
    TS(21);
    asm volatile("setmaxnreg.inc.sync.aligned.u32 168;");
    mb_wait(SM_MB + 8); mb_wait(SM_MB + 16);
    const u32 t3 = tid ^ p.zero;
    AROW(t3);
    if (t3 < 256) {
      const u32 aa = ab + arow * 64 + ((((t3 >> 6) & 2) ^ ((t3 & 7) >> 1)) << 4);
#pragma unroll
      for (int s = 0; s < 9; s++) { A[s] = ldsm4t(aa + s * 1024); A[9 + s] = ldsm4t((aa ^ 16) + s * 1024); }
    } else AFRAG9();
    TS(22);
    bsync(6, 352);
    TS(24);
    const u32 g8 = lds32(SM_SLOT + 28);
    const char* const rs_ = gs + (((~lds32(SM_SLOT + 4 * (w & 7)) >> 2) & 2047) * 1152 + lane * 16);
    uint4 rv[3];
    rv[0].x = rv[1].x = rv[2].x = TAGR;
    if (w < 8) { rv[0] = ldr128(rs_); rv[1] = ldr128(rs_ + 512); if (lane < 8) rv[2] = ldr128(rs_ + 1024); barrive(15, 320); }
    if (__any_sync(~0u, max(max(key[0], key[1]), max(key[2], key[3])) >= g8)) {
#pragma unroll
      for (int k = 0; k < 4; k++) if (key[k] >= g8) {
        if (key[k] < lt) str128(rowp + k * 1152, h2[k][0], h2[k][1], h2[k][2], h2[k][3]);
        str128(rowp + (G_Y + k * 1152), bmul(x1[k][0], B2M64) | TAGR, x1[k][1], x1[k][2], x1[k][3]);
      }
    }
    POLLW({ rv[0] = ldr128(rs_); rv[1] = ldr128(rs_ + 512); if (lane < 8) rv[2] = ldr128(rs_ + 1024); },
          ((rv[0].x ^ TAGR) | (rv[1].x ^ TAGR) | (rv[2].x ^ TAGR)) & TAGM, 8);
    TS(38);
#pragma unroll
    for (int j = 0; j < 3; j++) if (w < 8 && (j < 2 || lane < 8)) sts128(SM_XS + w * ROW + lane * 16 + j * 512, bmul(rv[j].x ^ TAGR, B2P64), rv[j].y, rv[j].z, rv[j].w);
  } else {
    u32 ok, lr;
    if (w == 10) {
      uint2 rc = lds64(SM_RC + 8 * min(lane, 17u));
      float r1 = lane < 18 ? uf(rc.x) : 0.f, r2 = lane < 18 ? uf(rc.y) : 0.f;
#pragma unroll 1
      for (int o = 16; o; o >>= 1) { r1 += __shfl_xor_sync(~0u, r1, o); r2 += __shfl_xor_sync(~0u, r2, o); }
      const u32 tl = 4 * ((lane >> 1) & 1) + ((lane >> 2) & 3) + 8 * (lane & 1), kl = (2047 - 16 * b - tl) << 2 | par * 3;
      char* const kp = gs + (G_KEY + b * KST);
      const u32 spr = SM_SP + (lane >> 4) * 9 * 320 + (lane & 15) * 16;
      TS(31);
      bsync(1, 320);
      float S1 = 0.f, S2 = 0.f, S3 = 0.f;
#pragma unroll
      for (int i = 0; i < 9; i++) { uint4 t = lds128(spr + i * 320); S1 += uf(t.x); S2 += uf(t.y); S3 += uf(t.z); }
      S1 += __shfl_xor_sync(~0u, S1, 16); S2 += __shfl_xor_sync(~0u, S2, 16); S3 += __shfl_xor_sync(~0u, S3, 16);
      const float mu = S1 * (1.f / 576.f), var = fmaxf(fmaf(-mu, mu, S2 * (1.f / 576.f)), 0.f);
      const float m = rbf(mu), rs = rcpf(rbf(sqrta(rbf(rbf(var) + 1e-5f))));
      const u32 rb = pk_bf(0.f, fmaf(fmaf(-m, r1, S3), rs, r2) + 0.f);
      ok = ((rb ^ (((int)rb >> 31) | 0x80000000)) & 0xffff0000u) | kl;
      const float rh = rbf(rs);
      sts32(SM_KEY + 4 * (lane & 15), ok);
      sts128(SM_ST2 + 16 * (lane & 15), pk_bf(-m, -m), pk_bf(rh, rh), pk_bf(rs - rh, rs - rh), ok);
      __syncwarp();
      const uint4 o0 = lds128(SM_KEY + 2 * (lane & 16)), o1 = lds128(SM_KEY + 2 * (lane & 16) + 16);
      lr = (o0.x > ok) + (o0.y > ok) + (o0.z > ok) + (o0.w > ok) + (o1.x > ok) + (o1.y > ok) + (o1.z > ok) + (o1.w > ok);
      lr += __shfl_xor_sync(~0u, lr, 16);
      if (lane < 16 && lr < 8) str32(kp + 4 * lr, ok);
      if (lr == (b < NB8 ? 7 : NEARLY - 1)) sts32(SM_THR, ok);
      barrive(2, 320);
      barrive(4, 64);
      TS(20);
    } else if (w == 9) {
      bsync(7, 64);
      wait_clk(clk(), DD);
      PROXY_FENCE();
      DOWN(1);
    }
    asm volatile("setmaxnreg.inc.sync.aligned.u32 168;");
    mb_wait(SM_MB + 8); mb_wait(SM_MB + 16);
    AROW(tid);
    AFRAG9();
    TS(22);
    if (w == 10) {
      bsync(3, 320);
      PROXY_FENCE();
      ot = lane < 16 && lr >= 8;
      OUTR(2);
      bsync(6, 352);
      if (lane < 16 && lr < 8 && ok < lds32(SM_SLOT + 28)) ot = 2;
      bsync(15, 320);
      OUTR(4);
    } else if (w == 9) {
      bsync(5, 64);
      DOWN(3);
      bsync(15, 320);
      DOWN(4);
      TS(13);
    } else {
      const char* ks = gs + (G_KEY + (lane >> 1) * KST + (lane & 1) * 16);
      const u32 kt = par * 3;
      uint4 L[8];
#define KBAD(j) ((L[j].x ^ kt) & 3)
#define KLD(j) L[j] = ldr128(ks + j * 16 * KST)
      bsync(4, 64);
      if (KD) wait_clk(clk(), b < YL ? KD : KD1);
#pragma unroll
      for (int j = 0; j < 8; j++) KLD(j);
      POLLW(_Pragma("unroll") for (int j = 0; j < 8; j++) if (KBAD(j)) KLD(j), KBAD(0) | KBAD(1) | KBAD(2) | KBAD(3) | KBAD(4) | KBAD(5), 6);
      if (KBAD(6)) KLD(6);
      if (KBAD(7)) KLD(7);
      u32 H[8];
      merge4(H, L[0], L[1]); top8(H, L[2], L[3]); top8(H, L[4], L[5]);
      POLLW({ if (KBAD(6)) KLD(6); if (KBAD(7)) KLD(7); }, KBAD(6) | KBAD(7), 7);
      barrive(5, 64);
      TS(23);
      top8(H, L[6], L[7]);
#pragma unroll
      for (int r = 0; r < 8; r++) {
        const u32 m = __reduce_max_sync(~0u, H[0]), h0 = H[0];
        sts32(SM_SLOT + 4 * r, m);
        if (r < 7) asm("{.reg .u32 t; sub.u32 t,%1,%2; min.u32 t,t,1; mad.lo.u32 %0,t,%3,%4;}" : "=r"(H[0]) : "r"(m), "r"(h0), "r"(h0 - H[1]), "r"(H[1]));
#pragma unroll
        for (int i = 1; i < 7 - r; i++) H[i] = h0 == m ? H[i + 1] : H[i];
      }
      barrive(6, 352);
      TS(33);
    }
  }
  ffn_tail(p, tm_down, A, tid | p.zero, b, par, ot);
}

__global__ void __launch_bounds__(384, 1)
fused_kernel(const Prm p, const __grid_constant__ CUtensorMap tm_mod, const __grid_constant__ CUtensorMap tm_gate, const __grid_constant__ CUtensorMap tm_gs,
             const __grid_constant__ CUtensorMap tm_up, const __grid_constant__ CUtensorMap tm_us, const __grid_constant__ CUtensorMap tm_down) {
  extern __shared__ __align__(1024) unsigned char smem[];
  u32 la, ai, ldt; uint2 cr, ci;
  {
    const u32 t = threadIdx.x, d = t < 256 ? chan(blockIdx.x, t >> 5) : 512 + (blockIdx.x >> 1), o = d * 256 + 8 * (t & 31), o4 = o + ((t < 256 ? t >> 5 : t >> 3) & 4);
    asm volatile("{.reg .pred p; .reg .u16 h; setp.ne.u32 p,%7,0; @p ld.global.nc.u32 %0,[%8]; @p ld.global.nc.u32 %1,[%9]; @p ld.global.nc.v2.u32 {%2,%3},[%10];"
                 "@p ld.global.nc.v2.u32 {%4,%5},[%11]; @p ld.global.nc.u16 h,[%12]; cvt.u32.u16 %6,h;}"
                 : "=r"(la), "=r"(ai), "=r"(cr.x), "=r"(cr.y), "=r"(ci.x), "=r"(ci.y), "=r"(ldt)
                 : "r"(0x6ffu >> (t >> 5) & 1), "l"(p.la + o4), "l"(p.ai + o4), "l"(p.cr + o), "l"(p.ci + o), "l"(p.ldt + 2 * d));
  }
  const u32 t0 = clk();
  const u32 tid = __shfl_sync(~0u, threadIdx.x, threadIdx.x & 31), b = blockIdx.x + p.zero;
  const u32 w = tid >> 5, lane = tid & 31;
  const u32 g = lane >> 2, q = lane & 3, hi = g & 1;
  const u32 rho = b & 1, Ps = 512 + (b >> 1);
  char* const gs = p.gs;
  TS0();
  const bool kw = w != 8 && w != 11;
  const u32 ksig = w < 8 ? (w & 3) : 4, khf = w < 8 ? (w >> 2) : (w & 1);
  if (!kw) {
    if (tid == 352) {
#pragma unroll
      for (int i = 0; i < 4; i++) mb_init(SM_MB + 8 * i);
      asm volatile("fence.mbarrier_init.release.cluster;" ::: "memory");
      tm_pre(&tm_mod);
    }
    const char* cp = p.c + (576 * (w & 1) + 24 * min(lane, 23u));
    const uint2 c0 = ldg64(cp);
    la = c0.x; ai = c0.y; cr = ldg64(cp + 8); ci = ldg64(cp + 16);
  }
  const u32 zr = tid >> 16;
  const u32 epv = ldr32(gs + (G_EP + zr));
  const u32 tp = SM_TAP + ksig * TAPS;
  if (kw && !khf) {
#pragma unroll 1
    for (u32 i = lane * 16; i < TAPS; i += 512) sts128(tp + i, 0, 0, 0, 0);
  }
  if (tid < 128) sts128(SM_INV + 16 * tid, INVAL, 0, 1, 0);
  if (tid >= 252) str128(gs + (tid >= 380 ? G_MOD + b * 128 + q * 16 : b * BLK + 16384 - 252 * 16 + tid * 16), INVAL, 0, 1, 0);
  if (tid == 352 && b < 36) { while (clk() - t0 < DMOD); mb_expect(SM_MB, 36864); tma3d(SM_UP, &tm_mod, SM_MB, 32 * b, 0); }
  if (w < 9) {
    while ((int)(clk() - t0) < DX);
    const char* xp = p.x + (b * BLK + (lane >> 3) * 1152 + 128 * w + 16 * (lane & 7));
    const u32 xd = SM_XST + (((lane >> 3) & 1) + 8 * (lane >> 4)) * ROW + 128 * w + 16 * (lane & 7);
#pragma unroll
    for (int i = 0; i < 4; i++) cpa16(xd + 2 * ROW * i, xp + 4608 * i);
  }
  const u32 ktab = w < 8 ? SM_MODS + w * KTAB : SM_ZS + (w - 9) * KTAB;
  float k2048 = 0.f;
  if (kw) {
    u32 mx = __vmaxu2(__vmaxu2(cr.x & 0x7fff7fff, cr.y & 0x7fff7fff), __vmaxu2(ci.x & 0x7fff7fff, ci.y & 0x7fff7fff));
    const u32 E = max(__reduce_max_sync(~0u, max(mx & 0xffff, mx >> 16)) >> 7, 8u);
    TS(1);
    const float dt = rbf(ex2(blo(ldt) * LOG2E)), csc = uf((257 - E) << 23 | (fu(dt) & 0x7fffff));
    sts32(SM_SC + 16 * ksig + 12, fu(uf(fu(dt) & 0x7f800000) * uf((E - 2) << 23)));
    const u32 crw = khf ? cr.y : cr.x, ciw = khf ? ci.y : ci.x;
    float2 C[2], w4[2], w8[2], w16[2], w32[2], w64[2], w128[2], w256[2], w512[2], a1[2], a2[2], a3[2], t0[2], t1[2], s3[2];
#pragma unroll
    for (int m = 0; m < 2; m++) {
      const float lr2 = rbf(ex2((m ? bhi(la) : blo(la)) * LOG2E)) * dt * -LOG2E, th = (m ? bhi(ai) : blo(ai)) * dt;
      C[m] = make_float2((m ? bhi(crw) : blo(crw)) * csc, (m ? bhi(ciw) : blo(ciw)) * csc);
      const float2 w1 = cexp(lr2, th), w2 = csq(w1);
      w64[m] = cexp(64.f * lr2, 64.f * th);
      w4[m] = csq(w2); w8[m] = csq(w4[m]); w16[m] = csq(w8[m]); w32[m] = csq(w16[m]);
      w128[m] = csq(w64[m]); w256[m] = csq(w128[m]); w512[m] = csq(w256[m]);
      const float2 w1024 = csq(w512[m]);
      a1[m] = cmul(C[m], w1); a2[m] = cmul(C[m], w2); a3[m] = cmul(a1[m], w2);
      t0[m] = cmul(C[m], w1024); t1[m] = cmul(t0[m], w128[m]); s3[m] = cmul(w8[m], w16[m]);
      k2048 += fmaf(t0[m].x, w1024.x, -t0[m].y * w1024.y);
    }
    C2 B0[8], B1[8], B2[8], S[8];
    B0[0] = pk2(C); B0[1] = pk2(a1); B0[2] = pk2(a2); B0[3] = pk2(a3);
    const C2 h4 = pk2(w4), h256 = pk2(w256), h512 = pk2(w512);
#pragma unroll
    for (int i = 0; i < 4; i++) B0[4 + i] = cm2(B0[i], h4);
#pragma unroll
    for (int i = 0; i < 4; i++) B1[i] = cm2(B0[2 * i], h256);
    B1[4] = cm2(B0[0], h512); B1[5] = cm2(B0[4], h512);
    B1[6] = cm2(B1[4], h256); B1[7] = cm2(B1[5], h256);
    const u32 ta = ktab + lane * 128, f = ((lane & 3) << 5) | ((lane & 4) << 2);
#pragma unroll
    for (int i = 0; i < 8; i++) sts128(ta + ((i << 4) ^ f), B0[i].re, B0[i].im, B1[i].re, B1[i].im);
    B2[0] = pk2(t0); B2[1] = pk2(t1);
    B2[2] = cm2(B2[0], h256); B2[3] = cm2(B2[1], h256);
#pragma unroll
    for (int i = 0; i < 4; i++) B2[4 + i] = cm2(B2[i], h512);
    S[0] = {0x3C003C00u, 0u}; S[1] = pk2c(w8); S[2] = pk2c(w16); S[3] = pk2c(s3); S[4] = pk2c(w32);
#pragma unroll
    for (int i = 1; i < 4; i++) S[4 + i] = cm2(S[i], S[4]);
#pragma unroll
    for (int i = 0; i < 8; i++) sts128(ta + 4096 + ((i << 4) ^ f), B2[i].re, B2[i].im, S[i].re, S[i].im);
    const C2 m64 = pk2c(w64), m128 = pk2c(w128);
    sts128(ktab + 8192 + lane * 16, m64.re, m64.im, m128.re, m128.im);
    __syncwarp();
  } else {
    u32 sa = SM_SIL + 576 * (w & 1) + 24 * min(lane, 23u);
#pragma unroll 1
    for (int j = 0; j < 6; j++) {
      sts32(sa, pk_bf(silu_f(blo(la)), silu_f(bhi(la))));
      la = ai; ai = cr.x; cr.x = cr.y; cr.y = ci.x; ci.x = ci.y; sa += 4;
    }
    bsync(7, 64);
  }
  TS(2);
  const u32 pm = (__reduce_or_sync(~0u, epv) & 1) ? 0 : TAGM;
  sts32(SM_THR + 4, pm);
  if (w < 9) {
    asm volatile("cp.async.wait_all;" ::: "memory");
    __syncwarp();
    TS(4);
    if (tid == 256 && b >= 36 && b < 108) { mb_expect(SM_MB, 36864); tma3d(SM_UP, &tm_mod, SM_MB, 32 * b, 0); }
    const u32 xa = SM_XST + (lane & 15) * ROW + 128 * w + 16 * (lane >> 4);
    float s[4] = {}, X[2][4] = {}, Y[2][4] = {};
#pragma unroll
    for (int j = 0; j < 4; j++) {
      const uint4 a = ldsm4(xa + 32 * j);
      mma8_bf(X[0], a.x, a.y, a.x); mma8_bf(Y[0], a.x, a.y, a.y);
      mma8_bf(X[1], a.z, a.w, a.z); mma8_bf(Y[1], a.z, a.w, a.w);
      mma_bf(s, a.x, a.y, a.z, a.w, BONE, BONE);
    }
    uint4 t[4];
#pragma unroll
    for (int j = 0; j < 4; j++) t[j] = ldsm4t(xa + 32 * j);
    const float u0 = hi ? X[0][1] + X[1][1] : X[0][0] + X[1][0], u1 = hi ? Y[0][3] + Y[1][3] : Y[0][2] + Y[1][2];
    if (q == g >> 1) sts128(SM_SP + w * 128 + g * 16, fu(s[0]), fu(u0), fu(s[2]), fu(u1));
    bsync(1, 288);
    TS(7);
    const u32 spr = SM_SP + (lane & 7) * 16 + (lane & 8);
    const uint2 t8 = lds64(spr + 1024);
    const float f8 = lane < 16 ? 1.f : 0.f;
    float S1 = uf(t8.x) * f8, S2 = uf(t8.y) * f8;
#pragma unroll
    for (int i = 0; i < 4; i++) { const uint2 u = lds64(spr + (lane & 16) * 32 + i * 128); S1 += uf(u.x); S2 += uf(u.y); }
    S1 += __shfl_xor_sync(~0u, S1, 16); S2 += __shfl_xor_sync(~0u, S2, 16);
    const float mu = S1 * (1.f / 576.f), var = fmaxf(fmaf(-mu, mu, S2 * (1.f / 576.f)), 0.f);
    const float m = rbf(mu), rs = rcpf(rbf(sqrta(rbf(rbf(var) + 1e-5f))));
    const float ra = rs * 0.0625f;
    sts64(SM_AF + w * 128 + (lane & 15) * 8, fu(ra), fu(-m * ra));
    __syncwarp();
    TS(55);
    const uint4 f0 = lds128(SM_AF + w * 128 + q * 16), f1 = lds128(SM_AF + w * 128 + 64 + q * 16);
    const u32 zdst = SM_GATE + w * 2048 + (g >> 1) * 128 + (lane & 15) * 8;
    const u32 pz = (q & 1) ? 0 : pm;
#pragma unroll
    for (int j = 0; j < 8; j++) {
      const u32 x0 = j & 1 ? t[j >> 1].z : t[j >> 1].x, x1 = j & 1 ? t[j >> 1].w : t[j >> 1].y;
      sts64((j & 1 ? zdst ^ 64 : zdst) + 512 * (j >> 1), pk_hf(fmaf(blo(x0), uf(f0.x), uf(f0.y)), fmaf(bhi(x0), uf(f0.z), uf(f0.w))) | pz,
            pk_hf(fmaf(blo(x1), uf(f1.x), uf(f1.y)), fmaf(bhi(x1), uf(f1.z), uf(f1.w))));
    }
    TS(53);
    if (w < 8) barrive(15, 288);
    else {
      bsync(15, 288);
      TS(54);
      if (lane == 0) {
        PROXY_FENCE();
        bulk_out<BLK>(gs + b * BLK, SM_GATE);
        asm volatile("cp.async.bulk.commit_group;" ::: "memory");
        if (PFG & 1) l2_pre<WSH / 2>(p.wg + b * WSH);
      }
      const float rh = rbf(rs);
      sts128(SM_ST + 16 * (lane & 15), pk_bf(-m, -m), pk_bf(rh, rh), pk_bf(rs - rh, rs - rh), 0);
    }
    TS(5);
  }
  if (kw) {
    float D[5][4] = {};
    u32 ta = ktab + q * 128 + ((g ^ (q << 1)) << 4), tm = ktab + 8192 + q * 16;
#pragma unroll 2
    for (int s = 0; s < 8; s++) {
      const uint4 ca = lds128(ta), cb = lds128(ta + 4096), ma = lds128(tm);
      ta = (ta + 512) ^ 16; tm += 64;
      k2048 += __shfl_xor_sync(~0u, k2048, 16 >> s);
      const C2 s0 = {cb.z, cb.w}, s1 = cm2(s0, {ma.x, ma.y}), s2 = cm2(s0, {ma.z, ma.w}), s3 = cm2(s1, {ma.z, ma.w});
      mma_hf(D[0], s0.re, s1.re, s0.im, s1.im, ca.x, ca.y);
      mma_hf(D[2], s0.re, s1.re, s0.im, s1.im, ca.z, ca.w);
      mma_hf(D[4], s0.re, s1.re, s0.im, s1.im, cb.x, cb.y);
      mma_hf(D[1], s2.re, s3.re, s2.im, s3.im, ca.x, ca.y);
      mma_hf(D[3], s2.re, s3.re, s2.im, s3.im, ca.z, ca.w);
    }
    TS(3);
    const u32 xa = (w < 8 ? SM_MODS + (4 + ksig) * KTAB : SM_ZS) + lane * 16;
    if (khf) {
      __syncwarp();
#pragma unroll
      for (int j = 0; j < 5; j++) sts128(xa + 512 * j, fu(D[j][0]), fu(D[j][1]), fu(D[j][2]), fu(D[j][3]));
      if (lane == 0) sts32(xa + 2560, fu(k2048));
      asm volatile("bar.arrive %0,64;" ::"r"(2 + ksig) : "memory");
    } else {
      const u32 t1 = tp + (q < 2 ? (128 + 4 * g + 2 * q) * 4 : T3 * 4 + ((32 * q - 64 + g) ^ 1) * 2);
      const u32 x = 16 * q + (g >> 1) + hi + 1, tb = tp + (hi ? T7E : T9E) * 4 - 4;
      const u32 te = tb + (x + 2 * (x & 1)) * 2, to = tb + TEO * 4 + (x ^ 1) * 2;
      asm volatile("bar.sync %0,64;" ::"r"(2 + ksig) : "memory");
#pragma unroll
      for (int j = 0; j < 5; j++) { const uint4 t = lds128(xa + 512 * j); D[j][0] += uf(t.x); D[j][1] += uf(t.y); D[j][2] += uf(t.z); D[j][3] += uf(t.w); }
      k2048 = (k2048 + uf(lds32(xa + 2560))) * 0.125f;
#pragma unroll
      for (int r = 0; r < 4; r++) {
        const u32 v = pk_hf(D[2 + (r >> 1)][2 * (r & 1)], D[2 + (r >> 1)][2 * (r & 1) + 1]);
        if (q < 2) {
          const u32 vv = __byte_perm(v, v, 0x1010);
          sts32(t1 + (TO + 32 * r) * 4, vv); sts16(t1 + (TO + 32 * r + 1) * 4 + 2, v >> 16); sts16(t1 + (TO + 32 * r - 1) * 4, v);
          sts64(t1 + (TE + 32 * r) * 4, vv, __byte_perm(v, v, 0x1032));
        } else {
          sts16(t1 + 16 * r, v >> 16);
          if (r == 0 && lane == 2) {
            const u32 vv = __byte_perm(v, v, 0x1010);
            sts32(tp + (TO + 256) * 4, vv); sts16(tp + (TO + 257) * 4 + 2, v); sts16(tp + (TO + 255) * 4, v); sts64(tp + (TE + 256) * 4, vv, vv);
          } else sts16(t1 + 16 * r - ((T3 - T5) * 4 + 6) + 8 * hi, v);
        }
      }
#pragma unroll
      for (int r = 0; r < 2; r++) {
        const u32 v = pk_hf(D[4][2 * r], D[4][2 * r + 1]);
        if (r == 0 && lane == 0) { sts16(tp + T5 * 4 + 62 * 2, v); sts32(SM_KV + 4 * ksig, v & 0xffff); sts16(tp + (T9E + TEO) * 4 + 62 * 2, pk_hf(k2048, 0.f)); }
        else { sts16(te + 8 * r, v); sts16(to + 8 * r, v); }
        sts16(te + 8 * r + 16, v >> 16); sts16(to + 8 * r + 16, v >> 16);
      }
      __syncwarp();
#pragma unroll
      for (int r = 0; r < 4; r++) {
        const u32 v = pk_hf(D[r >> 1][2 * (r & 1) + 1], D[r >> 1][2 * (r & 1)]), t2 = tp + lane * 4 + 128 * r;
        sts32(t2 + TO * 4, v); sts16(t2 + TE * 4, v >> 16); sts16(t2 + (TE + 1) * 4 + 2, v);
      }
      __syncwarp();
    }
  } else if (w == 11 && b < 108) {
    float c[4][4] = {};
    u32 aa = SM_UP + ((lane & 7) + 8 * (lane >> 4)) * 64 + ((((lane >> 3) & 1) ^ ((lane & 7) >> 1)) << 4);
    u32 ba = SM_SIL + (lane >> 3) * 16;
    uint4 a[2][10];
#define GLD(n) { _Pragma("unroll") for (int i = 0; i < 2; i++) { a[n][5 * i] = ldsm4(ba + i * 64); \
      _Pragma("unroll") for (int k = 0; k < 4; k++) a[n][5 * i + 1 + k] = ldsm4t((k & 2 ? aa ^ 32 : aa) + i * 2048 + (k & 1) * 1024); } aa += 4096; ba += 128; }
#define GMM(n) { _Pragma("unroll") for (int i = 0; i < 2; i++) _Pragma("unroll") for (int k = 0; k < 4; k++) { const uint4 f = a[n][5 * i + 1 + k], bb = a[n][5 * i]; \
      mma_bf(c[k], f.x, f.y, f.z, f.w, k & 1 ? bb.z : bb.x, k & 1 ? bb.w : bb.y); } }
    mb_wait(SM_MB);
    TS(56);
    GLD(0);
#pragma unroll 1
    for (int s = 0; s < 4; s++) { GLD(1); GMM(0); GLD(0); GMM(1); }
    GMM(0);
    const float v0 = (q & 1) ? c[0][2] + c[1][2] : c[0][0] + c[1][0], v1 = (q & 1) ? c[2][2] + c[3][2] : c[2][0] + c[3][0];
    str16(gs + (G_MOD + b * 128 + 2 * g + 16 * q), pk_bf(rbf((q & 2) ? v1 : v0) * F2M64, 0.f) | (g < 2 ? pm : 0));
    TS(57);
  }
  TS(6);
  u32 tid2 = tid;
  if (w < 4) {
    asm volatile("setmaxnreg.inc.sync.aligned.u32 232;");
    const u32 tid = tid2 + p.zero, w = tid >> 5, lane = tid & 31, g = lane >> 2, q = lane & 3, hi = g & 1, zr = tid >> 16, tp = SM_TAP + w * TAPS;
    const u32 pml = opq((g & 3) ? 0 : pm);
    const u32 tr = tp + ((hi ? TO : TE) + (g >> 1) - q) * 4;
    u32 T[33][4], B5[5][2], B3[5][2];
#pragma unroll
    for (int d = 0; d < 33; d++) {
      T[d][0] = lds32(tr + 32 * d); T[d][1] = lds32(tr + 32 * d + 16);
      T[d][2] = cpy(d ? T[d - 1][1] : zr, zr, 0); T[d][3] = cpy(T[d][0], zr, 1);
    }
    const u32 t33 = cpy(T[32][1], zr, 0), z33 = cpy(zr, zr, 1);
    const u32 bt = tp + (T5 + g - q) * 4;
#pragma unroll
    for (int d = 0; d < 5; d++) {
      B5[d][0] = lds32(bt + 32 * d); B5[d][1] = lds32(bt + 32 * d - 16);
      B3[d][0] = lds32(bt + 32 * d + (T3 - T5) * 4); B3[d][1] = lds32(bt + 32 * d - 16 + (T3 - T5) * 4);
    }
    u32 za = opq(SM_ZS + 16 + w * ZSS + ((lane >> 3) & 1) * ZPS + ((lane & 7) + (lane >> 4)) * 16);
    u32 wa = opq(SM_W + W5O + w * WSL + row16(lane));
    u32 sa = opq(SM_W + W9O - 2048 + w * WSL + lane * 16);
    u32 yo = opq(G_Y + b * BLK + 256 * q + w * 32 + 4 * g);
    const u32 fa = opq(SM_SC + 16 * w + 8);
    TS(8);
    bsync(9, 384);
    TS(11);
    float A[4][4] = {};
    uint4 Z[4];
    Z[0] = ldsm4(za); Z[1] = ldsm4(za + 32);
    const uint2 fc = lds64(fa);
    const u32 F = __byte_perm(fu(uf(fc.x) * uf(fc.y)), 0, 0x3232);
#define STEP(s, b0, b1) { _Pragma("unroll") for (int i = 0; i < 4; i++) mma_hf_t(A[i], T[8 * i + 7 - (s)], b0, b1); }
#define PAIR(n) { Z[(n + 2) & 3] = ldsm4(za + 32 * (n + 2)); STEP(2 * n, Z[n].x, Z[n].y); STEP(2 * n + 1, Z[n].z, Z[n].w); }
#define LAST(N) mma8_hf(N, t33, z33, Z[3].y); float O[4]; mma_hf_o(O, A[0], T[0], Z[3].z, Z[3].w); \
    _Pragma("unroll") for (int i = 0; i < 3; i++) mma_hf_o(A[i], A[i + 1], T[8 * i + 8], Z[3].z, Z[3].w); \
    mma_hf_o(A[3], N, T[32], Z[3].z, Z[3].w);
#pragma unroll 1
    for (int j = 0; j < 4; j++) {
      PAIR(0); PAIR(1); PAIR(2);
      Z[1] = ldsm4(za + 160); STEP(6, Z[3].x, Z[3].y);
      float N[4] = {};
      LAST(N);
      y_store<128>(O[0], O[1], O[2], O[3], F, pml, gs + yo);
      za += 128; yo += 1024;
      TS(40 + j);
    }
    bsync(10, 352);
#pragma unroll 1
    for (int j = 4; j < 13; j++) {
      if (j == 8) bsync(14, 352);
      const uint4 a5 = ldsm4t(wa), a3 = ldsm4t(wa + (W3O - W5O));
      uint4 s3 = {0, 0, 0, 0};
      if (j >= 8) s3 = lds128(sa);
      PAIR(0);
      float N[4] = {};
#pragma unroll
      for (int i = 0; i < 4; i++) mma_hf(A[i], a5.x, a5.y, a5.z, a5.w, B5[i][0], B5[i][1]);
      mma_hf(N, a5.x, a5.y, a5.z, a5.w, B5[4][0], B5[4][1]);
      PAIR(1);
#pragma unroll
      for (int i = 0; i < 4; i++) mma_hf(A[i], a3.x, a3.y, a3.z, a3.w, B3[i][0], B3[i][1]);
      mma_hf(N, a3.x, a3.y, a3.z, a3.w, B3[4][0], B3[4][1]);
      PAIR(2);
      Z[1] = ldsm4(za + 160); STEP(6, Z[3].x, Z[3].y);
      LAST(N);
      y_store<128>(O[0] + uf(s3.x), O[1] + uf(s3.y), O[2] + uf(s3.z), O[3] + uf(s3.w), F, pml, gs + yo);
      za += 128; wa = (wa + 256) ^ 32; sa += 512; yo += 1024;
      TS(40 + j);
    }
    {
      const uint4 s3 = lds128(sa), s4 = lds128(sa + 512), s5 = lds128(sa + 1024);
      float X[3][4] = {{uf(s4.x), uf(s4.y), uf(s4.z), uf(s4.w)}, {}, {uf(s5.x), uf(s5.y), uf(s5.z), uf(s5.w)}};
#pragma unroll
      for (int ty = 0; ty < 2; ty++) {
        const uint4 a = ldsm4t(wa + ty * (W3O - W5O)), c = ldsm4t((wa ^ 32) + 256 + ty * (W3O - W5O)), d = ldsm4t(wa + 512 + ty * (W3O - W5O));
#pragma unroll
        for (int i = 0; i < 3; i++) mma_hf(A[i], a.x, a.y, a.z, a.w, ty ? B3[i][0] : B5[i][0], ty ? B3[i][1] : B5[i][1]);
#pragma unroll
        for (int i = 0; i < 2; i++) mma_hf(X[i], c.x, c.y, c.z, c.w, ty ? B3[i][0] : B5[i][0], ty ? B3[i][1] : B5[i][1]);
        mma_hf(X[2], d.x, d.y, d.z, d.w, ty ? B3[0][0] : B5[0][0], ty ? B3[0][1] : B5[0][1]);
      }
      asm volatile("mov.u32 %0,%%tid.x;" : "=r"(tid2));
#pragma unroll
      for (int n = 0; n < 4; n++) {
        const uint4 f0 = n < 2 ? Z[n] : ldsm4(za + 32 * n), f1 = ldsm4(za + 32 * n + 128), f2 = ldsm4(za + 32 * n + 256);
#pragma unroll
        for (int s = 2 * n; s < 2 * n + 2; s++) {
#pragma unroll
          for (int i = 0; i < 3; i++) mma_hf_t(A[i], T[8 * i + 7 - s], s & 1 ? f0.z : f0.x, s & 1 ? f0.w : f0.y);
          mma_hf_t(X[0], T[7 - s], s & 1 ? f1.z : f1.x, s & 1 ? f1.w : f1.y); mma_hf_t(X[1], T[15 - s], s & 1 ? f1.z : f1.x, s & 1 ? f1.w : f1.y);
          mma_hf_t(X[2], T[7 - s], s & 1 ? f2.z : f2.x, s & 1 ? f2.w : f2.y);
        }
      }
      y_store<128>(A[0][0] + uf(s3.x), A[0][1] + uf(s3.y), A[0][2] + uf(s3.z), A[0][3] + uf(s3.w), F, pml, gs + yo);
      y_store<128>(A[1][0] + X[0][0], A[1][1] + X[0][1], A[1][2] + X[0][2], A[1][3] + X[0][3], F, pml, gs + yo + 1024);
      y_store<128>(A[2][0] + X[1][0] + X[2][0], A[2][1] + X[1][1] + X[2][1], A[2][2] + X[1][2] + X[2][2], A[2][3] + X[1][3] + X[2][3], F, pml, gs + yo + 2048);
    }
    if (!YS || b < YL) barrive(12, 288);
    TS(15);
    if (!DECL) asm volatile("setmaxnreg.dec.sync.aligned.u32 168;");
  } else {
    asm volatile("setmaxnreg.dec.sync.aligned.u32 136;");
    const u32 t8 = tid - 128, pml = (g & 3) ? 0 : pm;
    {
      TS(12);
      if (PFG == 1 && tid == 288) l2_pre<WSH / 2>(p.wg + (b * WSH + WSH / 2));
      const char* zs = gs + ((16 * w - 64 + (lane >> 3)) * BLK + b * 128 + ((lane & 7) * 16 ^ rho * 64));
      const char* zs4 = gs + ((t8 >> 1) * BLK + (Ps >> 4) * 512 + (Ps & 6) * 64 + ((Ps >> 2 ^ Ps) & 2) * 32 + (Ps & 1) * 32 + (t8 & 1) * 16);
      uint4 v[5];
      v[4].x = INVAL;
      if (ZD) wait_clk(t0, ZD);
      if (w == 9) {
        const u32 d = lane < 4 ? chan(b, lane) : Ps;
        const char* mp = gs + (G_MOD + (d >> 5) * 128 + (d & 24) * 2);
        uint4 ta, tc;
        POLL({ ta = ldr128(mp); tc = ldr128(mp + MODJ); v[4] = ldr128(zs4); }, ((ta.x ^ pm) | (tc.x ^ pm)) & TAGM, 2);
        const u32 aw = (d & 4) ? ((d & 2) ? ta.w : ta.z) : ((d & 2) ? ta.y : ta.x & ~TAGM);
        const u32 cw = (d & 4) ? ((d & 2) ? tc.w : tc.z) : ((d & 2) ? tc.y : tc.x & ~TAGM);
        const float sa = ((d & 1) ? bhi(aw) : blo(aw)) * F2P64, c1 = rbf(fmaf((d & 1) ? bhi(cw) : blo(cw), F2P64, 1.f));
        const u32 EM = min(max(fu(fmaxf(32.f * fabsf(c1), fabsf(sa))) >> 23, 80u), 250u);
        const float inv = uf((264 - EM) << 23);
        if (lane < 5) { sts64(SM_SC + 16 * lane, pk_hf(16.f * c1 * inv, 16.f * c1 * inv), pk_hf(sa * inv, sa * inv)); sts32(SM_SC + 16 * lane + 8, (EM - 74) << 23); }
        TS(10);
      }
      POLLW(v[4] = ldr128(zs4), (v[4].x ^ pm) & TAGM, 1);
      TS(58);
#pragma unroll
      for (int j = 0; j < 4; j++) v[j] = ldr128(zs + j * 4 * BLK);
#define MARKERS() if (tid == 256) { \
        bulk_out<2048>(gs + (G_Y + 16384 + b * BLK), SM_INV); \
        _Pragma("unroll") for (int i = MT / 2; i < 8; i++) bulk_out<2048>(gs + (G_Y + 2048 * i + b * BLK), SM_INV); \
        bulk_out<2048>(gs + (G_PART + b * 2048), SM_INV); bulk_out<512>(gs + (G_ACT + b * 512), SM_INV); \
        bulk_out<32>(gs + (G_KEY + b * KST), SM_INV); if (!rho) bulk_out<128>(gs + (G_ACT + Ps * 128), SM_INV); \
        asm volatile("cp.async.bulk.commit_group;" ::: "memory"); }
      if (PFU == 2 && tid == 256) l2_pre<WSH>(p.wu + b * WSH);
      if (GE && tid == 256) {
        asm volatile("cp.async.bulk.wait_group.read 0;" ::: "memory");
#pragma unroll
        for (int i = 0; i < GE; i++) tma3d(SM_GATE + 12288 * i, &tm_gate, SM_MB + 8, 32 * b, i);
      }
      if (MKT == 0) MARKERS();
      if (PFG == 2 && tid == 256) l2_pre<WSH>(p.wg + b * WSH);
      if (PFG == 3 && tid == 256) l2_pre<WSH / 2>(p.wg + (b * WSH + WSH / 2));
      bsync(8, 256);
      const uint2 cc = lds64(SM_SC + 8 * (t8 & 6)), c4 = lds64(SM_SC + 64);
      POLLW(_Pragma("unroll") for (int j = 0; j < 4; j++) if ((v[j].x ^ pm) & TAGM) v[j] = ldr128(zs + j * 4 * BLK),
           ((v[0].x ^ pm) | (v[1].x ^ pm) | (v[2].x ^ pm) | (v[3].x ^ pm)) & TAGM, 1);
      TS(9);
      const u32 dst = SM_ZS + 128 + (t8 & 7) * ZPS + (16 * w - 64 + (lane >> 3)) * 16;
#pragma unroll
      for (int j = 4; j >= 0; j--) {
        const uint2 c = j < 4 ? cc : c4;
        sts128(j < 4 ? dst + j * 64 : SM_Z4 + 256 + (t8 & 1) * ZP4 + (t8 >> 1) * 16, hfma(v[j].x & ~TAGM, c.x, c.y), hfma(v[j].y, c.x, c.y), hfma(v[j].z, c.x, c.y), hfma(v[j].w, c.x, c.y));
      }
      if (t8 < 96) sts128(t8 < 64 ? SM_ZS + (t8 & 7) * ZPS + (t8 >> 3) * 16 : SM_Z4 + (t8 & 1) * ZP4 + (t8 & 30) * 8, 0, 0, 0, 0);
      if (MKT == 0) asm volatile("cp.async.bulk.wait_group.read 1;" ::: "memory");
      else asm volatile("cp.async.bulk.wait_group.read 0;" ::: "memory");
      bsync(9, 384);
      TS(11);
      if (MKT == 1) MARKERS();
      const bool lng = w < 8 || w == 9;
      const u32 ts = lane + 32 * (w == 8 ? 0 : w - 9), c = min(ts, 71u), ma = SM_MODS + 16 * c;
      const u32 sig = lng ? ksig : ts >> 4, l2 = lng ? lane : 32 + (ts & 15);
      const char* mq = gs + (G_MOD + (c >> 2) * 128 + (c & 3) * 16);
      if (!lng) {
#pragma unroll
        for (int j = 0; j < 6; j++) cpa16(ma + 1152 * j, mq + j * MODJ);
        cpa16(ma + 1152 * 6, p.dsk + 16 * c); cpa16(ma + 1152 * 7, p.wr + 16 * c);
        if (PFU == 3) {
#pragma unroll
          for (int j = 0; j < 4; j++) if (ts < 81) l2_line(p.wu + (b * WSH + (81 * j + ts) * 128));
        }
        if (tid == 352) {
          PROXY_FENCE();
          if (PFU == 1) l2_pre<WSH>(p.wu + b * WSH);
          mb_expect(SM_MB + 8, rho ? SLV : 46080);
#pragma unroll
          for (int i = GE; i < 3; i++) tma3d(SM_GATE + 12288 * i, &tm_gate, SM_MB + 8, 32 * b, i);
          if (!rho) tma3d(SM_GATE + SLV, &tm_gs, SM_MB + 8, 4096 + 4 * b, 0);
          mb_expect(SM_MB + 16, rho ? SLV : 46080);
          tma3d(SM_UP, &tm_up, SM_MB + 16, 32 * b, 0);
          if (!rho) tma3d(SM_UP + SLV, &tm_us, SM_MB + 16, 4096 + 4 * b, 0);
        }
      }
      const u32 wb = SM_W + sig * WSL;
      if (sig < 5) {
        const u32 za = (sig < 4 ? SM_ZS + 128 + sig * ZSS : SM_Z4 + 256) + l2 * 32, zb = za + (sig < 4 ? ZPS : ZP4);
        const uint4 c0 = lds128(zb - 32), c1 = lds128(za - 16), c2 = lds128(zb - 16), c3 = lds128(za), c4 = lds128(zb), c5 = lds128(za + 16), c6 = lds128(zb + 16);
        const u32 P[25] = {c0.z, c0.w, c1.x, c1.y, c1.z, c1.w, c2.x, c2.y, c2.z, c2.w, c3.x, c3.y, c3.z, c3.w, c4.x, c4.y, c4.z, c4.w, c5.x, c5.y, c5.z, c5.w, c6.x, c6.y, c6.z};
        u32 Q[25], D1[24], F4[23], W5[21], W3[17];
#pragma unroll
        for (int j = 1; j < 25; j++) Q[j] = __byte_perm(P[j - 1], P[j], 0x5432);
#pragma unroll
        for (int j = 1; j < 24; j++) D1[j] = hadd(P[j], Q[j]);
#pragma unroll
        for (int j = 2; j < 23; j++) F4[j] = hadd(D1[j], D1[j - 1]);
#pragma unroll
        for (int n = 0; n < 21; n++) W5[n] = hadd(F4[n + 2], P[n]);
#pragma unroll
        for (int n = 0; n < 17; n++) W3[n] = hadd(Q[n + 8], D1[n + 7]);
        const u32 a0 = wb + W5O + 64 * l2 + 16 * ((l2 >> 1) & 3);
#pragma unroll
        for (int i = 0; i < 4; i++) {
          sts128(a0 ^ (16 * i), W5[4 * i + 5], W5[4 * i + 6], W5[4 * i + 7], W5[4 * i + 8]);
          sts128((a0 ^ (16 * i)) + (W3O - W5O), W3[4 * i + 1], W3[4 * i + 2], W3[4 * i + 3], W3[4 * i + 4]);
        }
        if (lng) {
          if (lane < 16) sts128(wb + (lane & 7) * 16 + (lane & 8) * 400, 0, 0, 0, 0);
          const u32 a1 = wb + 32 * lane + 16 * ((lane >> 2) & 1);
#pragma unroll
          for (int i = 0; i < 4; i++) {
            const u32 a = (a1 ^ (16 * (i >> 1))) + 1024 * (i & 1), n = 4 * i;
            sts128(a + V2O, hadd(Q[n + 9], P[n + 8]), hadd(Q[n + 10], P[n + 9]), hadd(Q[n + 11], P[n + 10]), hadd(Q[n + 12], P[n + 11]));
            sts128(a + W9O, hadd(F4[n + 4], W5[n]), hadd(F4[n + 5], W5[n + 1]), hadd(F4[n + 6], W5[n + 2]), hadd(F4[n + 7], W5[n + 3]));
            sts128(a + W7O, hadd(F4[n + 6], W3[n]), hadd(F4[n + 7], W3[n + 1]), hadd(F4[n + 8], W3[n + 2]), hadd(F4[n + 9], W3[n + 3]));
          }
        }
      }
      if (w != 9) barrive(10, 352);
      __syncwarp();
      TS(32);
      if (lng) {
        const u32 wa = wb + ((lane >> 3) & 1) * 1024 + (((lane & 7) ^ (lane >> 4)) + 8 * (lane >> 4)) * 16;
        const u32 kv = lds32(SM_KV + 4 * sig), bi = (g >> 1) == q ? (hi ? kv << 16 : kv) : 0u;
        float acc[8][4] = {};
#pragma unroll
        for (int j = 0; j < 4; j++) { const uint4 a = ldsm4t(wa + V2O + j * 256); mma8_hf(acc[2 * j], a.x, a.y, bi); mma8_hf(acc[2 * j + 1], a.z, a.w, bi); }
        u32 bt = tp + (T9E + hi * TEO + (g >> 1) - q) * 4, wt = wa + W9O;
#pragma unroll 1
        for (int ty = 0; ty < 2; ty++) {
          uint4 a[4];
#pragma unroll
          for (int be = 0; be < 4; be++) a[be] = ldsm4t(wt + be * 256);
          u32 b1 = lds32(bt - 16);
#pragma unroll
          for (int d = 0; d < 8; d++) {
            const u32 b0 = lds32(bt + 16 * d);
#pragma unroll
            for (int be = 0; be < 4; be++) if (d + 2 * be < 8) mma_hf(acc[d + 2 * be], a[be].x, a[be].y, a[be].z, a[be].w, b0, b1);
            b1 = b0;
          }
          bt += (T7E - T9E) * 4; wt += W7O - W9O;
        }
        __syncwarp();
#pragma unroll
        for (int j = 0; j < 8; j++) sts128(wb + W9O + j * 512 + lane * 16, fu(acc[j][0]), fu(acc[j][1]), fu(acc[j][2]), fu(acc[j][3]));
        if (w != 9) barrive(14, 352);
        TS(34);
      }
      if (!lng) {
        asm volatile("cp.async.wait_all;" ::: "memory");
        uint4 md[6];
#pragma unroll
        for (int j = 0; j < 6; j++) md[j] = lds128(ma + 1152 * j);
        const uint4 wr = lds128(ma + 1152 * 7);
        POLLW(_Pragma("unroll") for (int j = 0; j < 6; j++) md[j] = ldr128(mq + j * MODJ),
              ((md[0].x ^ pm) | (md[1].x ^ pm) | (md[2].x ^ pm) | (md[3].x ^ pm) | (md[4].x ^ pm) | (md[5].x ^ pm)) & TAGM, 4);
#pragma unroll
        for (int j = 0; j < 6; j++) {
          const u32 o = (j % 3 == 1) ? BONE : 0x80008000u;
          md[j] = make_uint4(bfma(md[j].x & ~TAGM, B2P64, o), bfma(md[j].y, B2P64, o), bfma(md[j].z, B2P64, o), bfma(md[j].w, B2P64, o));
          sts128(ma + 1152 * j, md[j].x, md[j].y, md[j].z, md[j].w);
        }
        const uint4 H = make_uint4(bmul(md[4].x, wr.x), bmul(md[4].y, wr.y), bmul(md[4].z, wr.z), bmul(md[4].w, wr.w));
        sts128(ma + 1152 * 7, H.x, H.y, H.z, H.w);
        sts128(ma + 1152 * 8, bfma(md[4].x, wr.x, H.x ^ 0x80008000u), bfma(md[4].y, wr.y, H.y ^ 0x80008000u), bfma(md[4].z, wr.z, H.z ^ 0x80008000u), bfma(md[4].w, wr.w, H.w ^ 0x80008000u));
        float c4[4] = {};
        mma_bf(c4, md[4].x, md[3].x, md[4].y, md[3].y, wr.x, wr.y); mma_bf(c4, md[4].z, md[3].z, md[4].w, md[3].w, wr.z, wr.w);
        if (q == g >> 1) sts64(SM_RC + (ts >> 2) * 8, fu(hi ? c4[1] : c4[0]), fu(hi ? c4[3] : c4[2]));
        if (ts < 2) sts128(SM_ONE + 16 * ts, ts ? 0 : BONE, ts ? 0 : BONE, ts ? 0 : BONE, ts ? 0 : BONE);
        TS(14);
        if (MKT == 2) MARKERS();
        if (w == 8) asm volatile("cp.async.bulk.wait_group 0;" ::: "memory");
        if (w == 8) barrive(14, 352);
        if (PFW == 2) {
#pragma unroll
          for (int j = 0; j < 4; j++) if (ts < 81) l2_line(p.wd + (b * WSH + (81 * j + ts) * 128));
        }
        bsync(13, 96);
      }
      if (w >= 8) barrive(11, 256);
    }
    if (w < 8) {
      const int u0 = 4 * (w - 4) + 2 * rho;
      const u32 t4 = SM_TAP + 4 * TAPS;
      u32 tr = t4 + ((hi ? TO : TE) + (g >> 1) - q) * 4;
      u32 zb = SM_Z4 + 256 + ((lane >> 3) & 1) * ZP4 + u0 * 128 + (lane & 7) * 16 + (lane >> 4) * 128;
      float acc[4][4] = {};
      u32 prev = 0;
#pragma unroll 1
      for (int it = min(u0 + 2, 4); it; it--) {
#pragma unroll
        for (int s = 0; s < 8; s++) {
          const uint4 z = ldsm4(zb - 16 * s);
          const u32 t0 = lds32(tr + 32 * s), t1 = lds32(tr + 32 * s + 16);
          mma_hf(acc[s & 1], t0, t1, prev, t0, z.x, z.y);
          mma_hf(acc[2 + (s & 1)], t0, t1, prev, t0, z.z, z.w);
          prev = t1;
        }
        zb -= 128; tr += 256;
      }
      {
        const uint4 z = ldsm4(zb); const u32 t0 = lds32(tr), t1 = lds32(tr + 16);
        mma_hf(acc[0], t0, t1, prev, t0, z.x, z.y); mma_hf(acc[2], t0, t1, prev, t0, z.z, z.w);
        if (w > 4) { const uint4 y = ldsm4(zb - 16); mma8_hf(acc[1], t1, zr, y.y); mma8_hf(acc[3], t1, zr, y.w); }
      }
      bsync(11, 256);
      u32 wa = (SM_W + 4 * WSL + W5O + row16(lane) + (u0 - 3) * 256) ^ 32, bt = t4 + (T5 + g - q) * 4;
#pragma unroll 1
      for (int al = min(u0 - 2, 6); al > 0; al--) {
#pragma unroll
        for (int ty = 0; ty < 2; ty++) {
          const uint4 a = ldsm4t(wa + ty * (W3O - W5O));
          const u32 bb = bt + ty * (T3 - T5) * 4;
          mma_hf(acc[ty], a.x, a.y, a.z, a.w, lds32(bb - 32), lds32(bb - 48));
          mma_hf(acc[2 + ty], a.x, a.y, a.z, a.w, lds32(bb), lds32(bb - 16));
        }
        wa = (wa - 256) ^ 32; bt += 32;
      }
      TS(35);
      const uint2 fc = lds64(SM_SC + 16 * 4 + 8);
      const u32 F = __byte_perm(fu(uf(fc.x) * uf(fc.y)), 0, 0x3232);
      char* yp = gs + (G_Y + 16384 - 2048 + b * BLK + w * 512 + q * 64 + 4 * g);
#pragma unroll
      for (int j = 0; j < 2; j++) {
        uint4 s3 = {0, 0, 0, 0};
        if (u0 >= 8) s3 = lds128(SM_W + 4 * WSL + W9O + (u0 - 8 + j) * 512 + lane * 16);
        y_store<32>(acc[2 * j][0] + acc[2 * j + 1][0] + uf(s3.x), acc[2 * j][1] + acc[2 * j + 1][1] + uf(s3.y), acc[2 * j][2] + acc[2 * j + 1][2] + uf(s3.z),
                acc[2 * j][3] + acc[2 * j + 1][3] + uf(s3.w), F, pml, yp + j * 256);
      }
      TS(16);
    } else {
      if (PFW == 3 && w == 9) {
#pragma unroll 1
        for (int j = 0; j < 12; j++) { if (lane < 27) l2_line(p.wd + (b * WSH + (27 * j + lane) * 128)); wait_clk(clk(), PFP); }
      }
      if (w >= 10) bsync(14, 352);
      if (w == 10 && b < YP) {
        wait_clk(clk(), 480 * ((int)(b >> 3) - 6));
        const char* yp = gs + (G_Y + (lane >> 2) * BLK + b * 128 + (lane & 3) * 32);
        u32 t = 0;
#pragma unroll
        for (int i = 0; i < 8; i++) t |= ldr32(yp + 8 * BLK * i);
        sts32(SM_KEY + 4 * (lane & 15), t);
      }
      if (PFW < 2 && tid == 352) { mb_wait(SM_MB + 8); if (PFW) mb_wait(SM_MB + 16); l2_pre<WSH>(p.wd + b * WSH); }
      if (D0C && tid == 352 && b < 108) {
        mb_wait(SM_MB + 16);
        PROXY_FENCE();
        mb_expect(SM_MB + 24, 49152);
        tma3d(SM_TAP, &tm_down, SM_MB + 24, 64 * (b % 9), 4 * (b / 9));
      }
      TS(17);
    }
  }
  post_conv(p, &tm_down, tid2 + p.zero, b);
  TSD();
  if (s2u(smem) != SM0) __trap();
}

typedef CUresult (*EncFn)(CUtensorMap*, CUtensorMapDataType, cuuint32_t, void*, const cuuint64_t*, const cuuint64_t*, const cuuint32_t*, const cuuint32_t*,
                          CUtensorMapInterleave, CUtensorMapSwizzle, CUtensorMapL2promotion, CUtensorMapFloatOOBfill);
static void make_map(EncFn enc, CUtensorMap* tm, void* ptr, int cols, int rows, int bw, int nb, CUtensorMapSwizzle sw, int gr = 192) {
  cuuint64_t gd[3] = {(cuuint64_t)cols, (cuuint64_t)gr, (cuuint64_t)(rows / gr)}, gs[2] = {(cuuint64_t)cols * 2, (cuuint64_t)cols * 2 * gr};
  cuuint32_t bd[3] = {(cuuint32_t)bw, (cuuint32_t)gr, (cuuint32_t)nb}, es[3] = {1, 1, 1};
  enc(tm, CU_TENSOR_MAP_DATA_TYPE_BFLOAT16, 3, ptr, gd, gs, bd, es, CU_TENSOR_MAP_INTERLEAVE_NONE, sw, CU_TENSOR_MAP_L2_PROMOTION_NONE, CU_TENSOR_MAP_FLOAT_OOB_FILL_NONE);
}
extern "C" void kernel_launch(void* const* d_in, const int* in_sizes, int n_in, void* d_out, int out_size) {
  static EncFn enc = nullptr;
  static void* scratch = nullptr;
  if (!enc) {
    cudaGetSymbolAddress(&scratch, g_s);
    cudaDriverEntryPointQueryResult qr;
    cudaGetDriverEntryPoint("cuTensorMapEncodeTiled", (void**)&enc, cudaEnableDefault, &qr);
    cudaFuncSetAttribute(fused_kernel, cudaFuncAttributeMaxDynamicSharedMemorySize, SM_TOTAL);
  }
  CUtensorMap tm_mod, tm_gate, tm_gs, tm_up, tm_us, tm_down;
  make_map(enc, &tm_mod, d_in[13], 3456, 576, 32, 3, CU_TENSOR_MAP_SWIZZLE_64B);
  make_map(enc, &tm_gate, d_in[9], 4608, 576, 32, 1, CU_TENSOR_MAP_SWIZZLE_64B);
  make_map(enc, &tm_gs, d_in[9], 4608, 576, 8, 3, CU_TENSOR_MAP_SWIZZLE_NONE);
  make_map(enc, &tm_up, d_in[10], 4608, 576, 32, 3, CU_TENSOR_MAP_SWIZZLE_64B);
  make_map(enc, &tm_us, d_in[10], 4608, 576, 8, 3, CU_TENSOR_MAP_SWIZZLE_NONE);
  make_map(enc, &tm_down, d_in[11], 576, 4608, 64, 1, CU_TENSOR_MAP_SWIZZLE_128B, 96);
  Prm p;
  p.x = (const char*)d_in[0]; p.la = (const char*)d_in[1]; p.ai = (const char*)d_in[2]; p.cr = (const char*)d_in[3];
  p.ci = (const char*)d_in[4]; p.ldt = (const char*)d_in[5]; p.dsk = (const char*)d_in[6]; p.wr = (const char*)d_in[8];
  p.wg = (const char*)d_in[9]; p.wu = (const char*)d_in[10]; p.wd = (const char*)d_in[11];
  p.c = (const char*)d_in[12]; p.out = (char*)d_out; p.zero = 0; p.gs = (char*)scratch;
  fused_kernel<<<128, 384, SM_TOTAL>>>(p, tm_mod, tm_gate, tm_gs, tm_up, tm_us, tm_down);
}
```

```cpp
#include <cuda_runtime.h>
#include <cuda.h>
#include <cuda_bf16.h>
#include <cuda_fp16.h>
#include <stdint.h>
#define FUSED 1
#define DEV __device__ __forceinline__
typedef uint32_t u32;

constexpr u32 BLK = 18432, G_Z = 0, G_Y = 128 * BLK, G_MOD = 2 * G_Y, G_KEY = G_MOD + 128 * 128, G_ACT = G_KEY + 128 * 128;
constexpr u32 G_PART = G_ACT + 576 * 128, G_EP = G_PART + 128 * 2048, G_END = G_EP + 128;
__device__ __align__(128) unsigned char g_s[G_END];
#define TS(i)
#define TS0()
#define TSE()
#define TSD()
#define TSX 0
#define TSN(code, n)
#define ERRF(code)

constexpr int SM0 = 1024;
constexpr int ROW = 1168, SLV = 36864;
constexpr int SM_GATE = SM0, SM_UP = SM_GATE + 46080, SM_XST = SM_UP + 46080, SM_MODS = SM_XST + 16 * ROW, SM_W = SM_MODS + 11008;
constexpr int KTAB = 9216, WSL = 12544, W5O = 128, W3O = 3328, V2O = 6400, W9O = 8448, W7O = 10496;
constexpr int ZPS = 2192, ZSS = 2 * ZPS, ZP4 = 2368;
constexpr int SM_ZS = SM_W + 5 * WSL, SM_Z4 = SM_ZS + 4 * ZSS, SM_TAP = SM_Z4 + 2 * ZP4, TAPS = 3328;
constexpr int SM_MB = SM_TAP + 5 * TAPS;
constexpr int SM_SC = SM_MB + 32;
constexpr int SM_KV = SM_SC + 80;
constexpr int SM_THR = SM_KV + 32;
constexpr int SM_SLOT = SM_THR + 48;
constexpr int SM_KEY = SM_SLOT + 32;
constexpr int SM_ST = SM_KEY + 64;
constexpr int SM_ST2 = SM_ST + 256;
constexpr int SM_RC = SM_ST2 + 256;
constexpr int SM_SP = SM_RC + 192;
constexpr int SM_AF = SM_SP + 1152, SM_SIL = SM_AF + 1152, SM_INV = SM_SIL + 1152, SM_END = SM_SP + 5760;
constexpr int SM_ONE = SM_MODS + 9 * 1152;
constexpr int SM_WD = SM_W, SM_XS = SM_W + 36864, SM_AC = SM_ZS, SM_RED = SM_AC + 6144;
constexpr int SM_TSB = SM_END, SM_TOTAL = SM_END + TSX - SM0;
static_assert(SM_W % 1024 == 0 && SM_TAP % 1024 == 0 && SM_MODS + 8 * KTAB <= SM_ZS && SM_ZS + 2 * KTAB <= SM_TAP && SM_RED + 10240 <= SM_TAP && SM_XS + 8 * ROW <= SM_ZS, "smem map");
static_assert(SM_MB % 16 == 0 && SM_THR % 16 == 0 && SM_ST % 16 == 0 && SM_SP % 16 == 0 && SM_TOTAL <= 232448, "smem map");
constexpr int TE = 4, TO = 276, T5 = 560, T3 = 624, T9E = 680, T7E = 760, TEO = 40;
#define MT 10
#define DECL 1
#define MKT 1
#define KST 128
#define DE1 1
#define DE2 4
#define DE3 5
#define OUTA 2
#define OUTB 7
#define PFW 1
#define PFU 0
#define KD 700
#define D0C 0
#define YE 72
#define YL 104
#define YD 250
#define YS 0
#define YD0 250
#define KD1 1
#define AD 0
#define PD 0
#define ZD 0
#define DD 1000
#define YP 0
#define PFP 200
#define GE 0
#define NB8 8
#define DX 0
#define DMOD 1000
#define PFG 1
constexpr int SPIN = 1 << 16, NEARLY = 4;
constexpr u32 TAGM = 0x40004000u, TAGR = 0x40000000u, INVAL = 0x00004801u;

DEV u32 s2u(const void* p) { return (u32)__cvta_generic_to_shared(p); }
DEV void mma_bf(float (&c)[4], u32 a0, u32 a1, u32 a2, u32 a3, u32 b0, u32 b1) {
  asm("mma.sync.aligned.m16n8k16.row.col.f32.bf16.bf16.f32 {%0,%1,%2,%3},{%4,%5,%6,%7},{%8,%9},{%0,%1,%2,%3};"
      : "+f"(c[0]), "+f"(c[1]), "+f"(c[2]), "+f"(c[3]) : "r"(a0), "r"(a1), "r"(a2), "r"(a3), "r"(b0), "r"(b1));
}
DEV void mma_hf(float (&c)[4], u32 a0, u32 a1, u32 a2, u32 a3, u32 b0, u32 b1) {
  asm("mma.sync.aligned.m16n8k16.row.col.f32.f16.f16.f32 {%0,%1,%2,%3},{%4,%5,%6,%7},{%8,%9},{%0,%1,%2,%3};"
      : "+f"(c[0]), "+f"(c[1]), "+f"(c[2]), "+f"(c[3]) : "r"(a0), "r"(a1), "r"(a2), "r"(a3), "r"(b0), "r"(b1));
}
DEV void mma8_bf(float (&c)[4], u32 a0, u32 a1, u32 b0) {
  asm("mma.sync.aligned.m16n8k8.row.col.f32.bf16.bf16.f32 {%0,%1,%2,%3},{%4,%5},{%6},{%0,%1,%2,%3};"
      : "+f"(c[0]), "+f"(c[1]), "+f"(c[2]), "+f"(c[3]) : "r"(a0), "r"(a1), "r"(b0));
}
DEV void mma8_hf(float (&c)[4], u32 a0, u32 a1, u32 b0) {
  asm("mma.sync.aligned.m16n8k8.row.col.f32.f16.f16.f32 {%0,%1,%2,%3},{%4,%5},{%6},{%0,%1,%2,%3};"
      : "+f"(c[0]), "+f"(c[1]), "+f"(c[2]), "+f"(c[3]) : "r"(a0), "r"(a1), "r"(b0));
}
DEV u32 movm(u32 x) { u32 r; asm("movmatrix.sync.aligned.m8n8.trans.b16 %0,%1;" : "=r"(r) : "r"(x)); return r; }
DEV uint4 ldsm4(u32 a) { uint4 r; asm volatile("ldmatrix.sync.aligned.m8n8.x4.shared.b16 {%0,%1,%2,%3},[%4];" : "=r"(r.x), "=r"(r.y), "=r"(r.z), "=r"(r.w) : "r"(a)); return r; }
DEV uint4 ldsm4t(u32 a) { uint4 r; asm volatile("ldmatrix.sync.aligned.m8n8.x4.trans.shared.b16 {%0,%1,%2,%3},[%4];" : "=r"(r.x), "=r"(r.y), "=r"(r.z), "=r"(r.w) : "r"(a)); return r; }
DEV u32 lds32(u32 a) { u32 r; asm volatile("ld.volatile.shared.u32 %0,[%1];" : "=r"(r) : "r"(a)); return r; }
DEV uint2 lds64(u32 a) { uint2 r; asm volatile("ld.shared.v2.u32 {%0,%1},[%2];" : "=r"(r.x), "=r"(r.y) : "r"(a)); return r; }
DEV uint4 lds128(u32 a) { uint4 r; asm volatile("ld.shared.v4.u32 {%0,%1,%2,%3},[%4];" : "=r"(r.x), "=r"(r.y), "=r"(r.z), "=r"(r.w) : "r"(a)); return r; }
DEV void sts16(u32 a, u32 v) { asm volatile("st.shared.u16 [%0],%1;" ::"r"(a), "h"((unsigned short)v) : "memory"); }
DEV void sts32(u32 a, u32 v) { asm volatile("st.shared.u32 [%0],%1;" ::"r"(a), "r"(v) : "memory"); }
DEV void sts64(u32 a, u32 x, u32 y) { asm volatile("st.shared.v2.u32 [%0],{%1,%2};" ::"r"(a), "r"(x), "r"(y) : "memory"); }
DEV void sts128(u32 a, u32 x, u32 y, u32 z, u32 w) { asm volatile("st.shared.v4.u32 [%0],{%1,%2,%3,%4};" ::"r"(a), "r"(x), "r"(y), "r"(z), "r"(w) : "memory"); }
DEV uint4 ldr128(const void* p) { uint4 v; asm volatile("ld.relaxed.gpu.global.v4.u32 {%0,%1,%2,%3},[%4];" : "=r"(v.x), "=r"(v.y), "=r"(v.z), "=r"(v.w) : "l"(p) : "memory"); return v; }
DEV uint2 ldr64(const void* p) { uint2 v; asm volatile("ld.relaxed.gpu.global.v2.u32 {%0,%1},[%2];" : "=r"(v.x), "=r"(v.y) : "l"(p) : "memory"); return v; }
DEV u32 ldr32(const void* p) { u32 v; asm volatile("ld.relaxed.gpu.global.u32 %0,[%1];" : "=r"(v) : "l"(p) : "memory"); return v; }
DEV void str128(void* p, u32 x, u32 y, u32 z, u32 w) { asm volatile("st.relaxed.gpu.global.v4.u32 [%0],{%1,%2,%3,%4};" ::"l"(p), "r"(x), "r"(y), "r"(z), "r"(w) : "memory"); }
DEV void str64(void* p, u32 x, u32 y) { asm volatile("st.relaxed.gpu.global.v2.u32 [%0],{%1,%2};" ::"l"(p), "r"(x), "r"(y) : "memory"); }
DEV void str32(void* p, u32 x) { asm volatile("st.relaxed.gpu.global.u32 [%0],%1;" ::"l"(p), "r"(x) : "memory"); }
DEV void str16(void* p, u32 x) { asm volatile("st.relaxed.gpu.global.u16 [%0],%1;" ::"l"(p), "h"((unsigned short)x) : "memory"); }
DEV uint4 ldg128(const void* p) { uint4 v; asm volatile("ld.global.nc.v4.u32 {%0,%1,%2,%3},[%4];" : "=r"(v.x), "=r"(v.y), "=r"(v.z), "=r"(v.w) : "l"(p)); return v; }
DEV uint2 ldg64(const void* p) { uint2 v; asm volatile("ld.global.nc.v2.u32 {%0,%1},[%2];" : "=r"(v.x), "=r"(v.y) : "l"(p)); return v; }
DEV u32 ldg32(const void* p) { u32 v; asm volatile("ld.global.nc.u32 %0,[%1];" : "=r"(v) : "l"(p)); return v; }
DEV u32 ldg16(const void* p) { unsigned short v; asm volatile("ld.global.nc.u16 %0,[%1];" : "=h"(v) : "l"(p)); return v; }
#define bsync(id, n) asm volatile("bar.sync %0,%1;" ::"n"(id), "n"(n) : "memory")
#define barrive(id, n) asm volatile("bar.arrive %0,%1;" ::"n"(id), "n"(n) : "memory")
DEV void mb_init(u32 a) { asm volatile("mbarrier.init.shared.b64 [%0],1;" ::"r"(a) : "memory"); }
DEV void mb_expect(u32 a, u32 bytes) { asm volatile("mbarrier.arrive.expect_tx.shared.b64 _,[%0],%1;" ::"r"(a), "r"(bytes) : "memory"); }
DEV void mb_wait(u32 a, u32 ph = 0) {
  u32 ok; int it = 0;
  do { asm volatile("{.reg .pred p; mbarrier.try_wait.parity.shared.b64 p,[%1],%2; selp.u32 %0,1,0,p;}" : "=r"(ok) : "r"(a), "r"(ph) : "memory"); } while (!ok && ++it < SPIN);
}
template <int N> DEV void bulk_out(void* dst, u32 src) { asm volatile("cp.async.bulk.global.shared::cta.bulk_group [%0],[%1],%2;" ::"l"(dst), "r"(src), "n"(N) : "memory"); }
constexpr u32 WSH = 41472;
DEV void l2_line(const void* p) { asm volatile("prefetch.global.L2 [%0];" ::"l"(p) : "memory"); }
template <int N> DEV void l2_pre(const void* p) { asm volatile("cp.async.bulk.prefetch.L2.global [%0],%1;" ::"l"(p), "n"(N) : "memory"); }
DEV void tma3d(u32 dst, const CUtensorMap* tm, u32 mb, int c0, int c2) {
  asm volatile("cp.async.bulk.tensor.3d.shared::cluster.global.mbarrier::complete_tx::bytes [%0],[%1,{%3,0,%4}],[%2];"
               ::"r"(dst), "l"((uint64_t)tm), "r"(mb), "r"(c0), "r"(c2) : "memory");
}
DEV float blo(u32 w) { return __uint_as_float(w << 16); }
DEV float bhi(u32 w) { return __uint_as_float(w & 0xffff0000u); }
DEV u32 pk_bf(float lo, float hi) { u32 r; asm("cvt.rn.bf16x2.f32 %0,%1,%2;" : "=r"(r) : "f"(hi), "f"(lo)); return r; }
DEV u32 pk_hf(float lo, float hi) { u32 r; asm("cvt.rn.f16x2.f32 %0,%1,%2;" : "=r"(r) : "f"(hi), "f"(lo)); return r; }
DEV float rbf(float x) { return __uint_as_float(pk_bf(0.f, x) & 0xffff0000u); }
DEV u32 bfma(u32 a, u32 b, u32 c) { u32 r; asm("fma.rn.bf16x2 %0,%1,%2,%3;" : "=r"(r) : "r"(a), "r"(b), "r"(c)); return r; }
DEV u32 bmul(u32 a, u32 b) { u32 r; asm("mul.rn.bf16x2 %0,%1,%2;" : "=r"(r) : "r"(a), "r"(b)); return r; }
DEV u32 badd(u32 a, u32 b) { u32 r; asm("add.rn.bf16x2 %0,%1,%2;" : "=r"(r) : "r"(a), "r"(b)); return r; }
DEV u32 hadd(u32 a, u32 b) { u32 r; asm("add.rn.f16x2 %0,%1,%2;" : "=r"(r) : "r"(a), "r"(b)); return r; }
DEV u32 hfma(u32 a, u32 b, u32 c) { u32 r; asm("fma.rn.f16x2 %0,%1,%2,%3;" : "=r"(r) : "r"(a), "r"(b), "r"(c)); return r; }
struct C2 { u32 re, im; };
DEV C2 cm2(C2 a, C2 b) {
  const __half2 ar = *reinterpret_cast<__half2*>(&a.re), ai = *reinterpret_cast<__half2*>(&a.im), br = *reinterpret_cast<__half2*>(&b.re), bi = *reinterpret_cast<__half2*>(&b.im);
  __half2 re = __hfma2(ar, br, __hneg2(__hmul2(ai, bi))), im = __hfma2(ar, bi, __hmul2(ai, br));
  return {*reinterpret_cast<u32*>(&re), *reinterpret_cast<u32*>(&im)};
}
DEV C2 pk2(const float2 (&a)[2]) { return {pk_hf(a[0].x, a[1].x), pk_hf(a[0].y, a[1].y)}; }
DEV C2 pk2c(const float2 (&a)[2]) { return {pk_hf(a[0].x, a[1].x), pk_hf(-a[0].y, -a[1].y)}; }
DEV u32 cpy(u32 x, u32 zr, int alt) {
  u32 r;
  if (alt) asm volatile("xor.b32 %0,%1,%2;" : "=r"(r) : "r"(x), "r"(zr)); else asm volatile("mad.lo.u32 %0,%2,%2,%1;" : "=r"(r) : "r"(x), "r"(zr));
  return r;
}
DEV u32 opq(u32 x) { u32 r; asm volatile("mov.u32 %0,%1;" : "=r"(r) : "r"(x)); return r; }
DEV u32 chan(u32 b, u32 i) { return 16 * (b >> 2) + 2 * (b & 3) + (i & 1) + 4 * (i & 2); }
DEV u32 row16(u32 lane) { const u32 r0 = (lane & 7) + ((lane >> 3) & 1) + 8 * (lane >> 4) - 1; return (r0 ^ ((r0 >> 3) & 3)) * 16; }
DEV u32 clk() { u32 r; asm volatile("mov.u32 %0,%%clock;" : "=r"(r)::"memory"); return r; }
DEV void wait_clk(u32 t, int d) { while ((int)(clk() - t) < d); }
DEV float ex2(float x) { float r; asm("ex2.approx.ftz.f32 %0,%1;" : "=f"(r) : "f"(x)); return r; }
DEV float rcpf(float x) { float r; asm("rcp.approx.ftz.f32 %0,%1;" : "=f"(r) : "f"(x)); return r; }
DEV float2 cmul(float2 a, float2 b) { return make_float2(fmaf(a.x, b.x, -a.y * b.y), fmaf(a.x, b.y, a.y * b.x)); }
DEV float2 csq(float2 a) { return make_float2(fmaf(a.x, a.x, -a.y * a.y), (a.x + a.x) * a.y); }
DEV float2 cexp(float lr2, float th) {
  const float m = ex2(lr2);
  return make_float2(m * __cosf(th), m * __sinf(th));
}
DEV float silu_f(float v) { return v * rcpf(1.f + ex2(-1.4426950408889634f * v)); }
constexpr u32 B2P64 = 0x5F805F80u, B2M64 = 0x1F801F80u, BONE = 0x3F803F80u;
constexpr u32 MODJ = 18 * 128;
DEV float sqrta(float x) { float r; asm("sqrt.approx.ftz.f32 %0,%1;" : "=f"(r) : "f"(x)); return r; }
DEV u32 fu(float x) { return __float_as_uint(x); }
DEV float uf(u32 x) { return __uint_as_float(x); }
DEV void mma_hf_o(float (&d)[4], const float (&c)[4], const u32 (&a)[4], u32 b0, u32 b1) {
  asm("mma.sync.aligned.m16n8k16.row.col.f32.f16.f16.f32 {%0,%1,%2,%3},{%4,%5,%6,%7},{%8,%9},{%10,%11,%12,%13};"
      : "=f"(d[0]), "=f"(d[1]), "=f"(d[2]), "=f"(d[3]) : "r"(a[0]), "r"(a[1]), "r"(a[2]), "r"(a[3]), "r"(b0), "r"(b1), "f"(c[0]), "f"(c[1]), "f"(c[2]), "f"(c[3]));
}

DEV void mma_hf_t(float (&c)[4], const u32 (&a)[4], u32 b0, u32 b1) { mma_hf(c, a[0], a[1], a[2], a[3], b0, b1); }
DEV void cpa16(u32 dst, const void* src) { asm volatile("cp.async.cg.shared.global [%0],[%1],16;" ::"r"(dst), "l"(src) : "memory"); }
DEV void tm_pre(const CUtensorMap* tm) { asm volatile("prefetch.tensormap [%0];" ::"l"((uint64_t)tm) : "memory"); }
#define PROXY_FENCE() asm volatile("fence.proxy.async.shared::cta;" ::: "memory")
struct Prm {
  const char *la, *ai, *cr, *ci, *ldt;
  u32 zero;
  const char *x, *c;
  char* gs;
  const char *dsk, *wr, *wg, *wu, *wd;
  char* out;
};
constexpr float LOG2E = 1.4426950408889634f, F2P64 = 1.8446744073709552e19f, F2M64 = 5.421010862427522e-20f;

template <int S> DEV void y_store(float c0, float c1, float c2, float c3, u32 F, u32 pml, char* yp) {
  str32(yp, bmul(pk_bf(c0, c2), F) | pml);
  str32(yp + S, bmul(pk_bf(c1, c3), F) | pml);
}
DEV void merge4(u32 (&h)[8], uint4 a, uint4 b) {
  const u32 e1 = min(a.x, b.x), e2 = max(a.z, b.z), o1 = min(a.y, b.y), o2 = max(a.w, b.w), o0 = max(a.y, b.y), e3 = min(a.z, b.z);
  const u32 f1 = max(e1, e2), f2 = min(e1, e2), p1 = max(o1, o2), p2 = min(o1, o2);
  h[0] = max(a.x, b.x); h[1] = max(o0, f1); h[2] = min(o0, f1); h[3] = max(p1, f2); h[4] = min(p1, f2); h[5] = max(p2, e3); h[6] = min(p2, e3); h[7] = min(a.w, b.w);
}
DEV void top8(u32 (&a)[8], uint4 l, uint4 m) {
  u32 b[8];
  merge4(b, l, m);
#pragma unroll
  for (int i = 0; i < 8; i++) a[i] = max(a[i], b[7 - i]);
#pragma unroll
  for (int s = 4; s; s >>= 1)
#pragma unroll
    for (int i = 0; i < 8; i++) if (!(i & s)) { const u32 x = a[i], y = a[i + s]; a[i] = max(x, y); a[i + s] = min(x, y); }
}
#define POLL(load, cond_bad, code) { int it_ = 0; do { load; if (++it_ > SPIN) { ERRF(code); break; } } while (__any_sync(~0u, (cond_bad))); }
#define POLLW(load, cond_bad, code) { int it_ = 0; while (__any_sync(~0u, (cond_bad))) { if (++it_ > SPIN) { ERRF(code); break; } load; } TSN(code, it_); }

#define DOWN(E) if (tid == 288 && b < 108) { const u32 c0 = 64 * (b % 9), c2 = 4 * (b / 9); \
    if (!D0C && E == 1) { mb_expect(SM_MB + 24, 49152); tma3d(SM_TAP, tm_down, SM_MB + 24, c0, c2); } \
    if (DE1 == E) tma3d(SM_WD, tm_down, SM_MB + 24, c0, c2 + 1); \
    if (DE2 == E) tma3d(SM_WD + 12288, tm_down, SM_MB + 24, c0, c2 + 2); \
    if (DE3 == E) tma3d(SM_WD + 24576, tm_down, SM_MB + 24, c0, c2 + 3); }
#define OUTR(E) if (((OUTA == E) | (OUTB == E) << 1) & ot) { const u32 tl = 4 * ((lane >> 1) & 1) + ((lane >> 2) & 3) + 8 * (lane & 1); \
    bulk_out<1152>(p.out + (b * BLK + tl * 1152), SM_XST + ((lane & 2) + 4 * (lane & 1) + ((lane >> 2) & 1) + (lane & 8)) * ROW); \
    asm volatile("cp.async.bulk.commit_group;" ::: "memory"); }
DEV void ffn_tail(const Prm& p, const CUtensorMap* tm_down, uint4 (&A)[24], const u32 tid, const u32 b, const u32 par, const u32 ot) {
  const u32 w = tid >> 5, lane = tid & 31, g = lane >> 2, q = lane & 3, kq = w & 3, tg = w >> 2;
  const u32 rho = b & 1, pm = par ? TAGM : 0;
  char* const gs = p.gs;
  __syncthreads();
  TS(25);
  DOWN(5);
  {
    float c0[2][4] = {}, c1[2][4] = {};
    const u32 ba = SM_XS + (lane & 7) * ROW + (18 * kq + (lane >> 3)) * 16;
    uint4 bb[5];
#pragma unroll
    for (int s = 0; s < 5; s++) bb[s] = ldsm4(ba + s * 64);
#pragma unroll
    for (int s = 0; s < 9; s++) mma_bf(c0[s & 1], A[s].x, A[s].y, A[s].z, A[s].w, s & 1 ? bb[s >> 1].z : bb[s >> 1].x, s & 1 ? bb[s >> 1].w : bb[s >> 1].y);
    const u32 ra = SM_RED + (8 * tg + kq) * 512 + lane * 16;
    if (tg < 2) {
#pragma unroll
      for (int s = 0; s < 9; s++) mma_bf(c1[s & 1], A[9 + s].x, A[9 + s].y, A[9 + s].z, A[9 + s].w, s & 1 ? bb[s >> 1].z : bb[s >> 1].x, s & 1 ? bb[s >> 1].w : bb[s >> 1].y);
      sts128(ra + 2048, fu(c1[0][0] + c1[1][0]), fu(c1[0][1] + c1[1][1]), fu(c1[0][2] + c1[1][2]), fu(c1[0][3] + c1[1][3]));
    }
    sts128(ra, fu(c0[0][0] + c0[1][0]), fu(c0[0][1] + c0[1][1]), fu(c0[0][2] + c0[1][2]), fu(c0[0][3] + c0[1][3]));
  }
  TS(39);
  __syncthreads();
  const u32 tr = clk();
  OUTR(6);
  if (w - 3 - rho < 5 - rho) {
    const u32 t = 7 - w;
    float s[4] = {};
#pragma unroll
    for (int i = 0; i < 4; i++) { const uint4 u = lds128(SM_RED + (t * 4 + i) * 512 + lane * 16); s[0] += uf(u.x); s[1] += uf(u.y); s[2] += uf(u.z); s[3] += uf(u.w); }
    const u32 sg = pk_bf(silu_f(rbf(s[0])), silu_f(rbf(s[1])));
    const u32 act = movm(bmul(bmul(sg, pk_bf(s[2], s[3])), B2M64));
    str32(gs + (G_ACT + (t < 4 ? 4 * b + t : 512 + (b >> 1)) * 128 + lane * 4), act | (q ? 0 : pm));
  }
  TS(26);
  if (b < 108) {
    const char* src = gs + (G_ACT + (b / 9) * 6144 + tid * 16);
    uint4 a;
    if (AD) a.x = INVAL; else a = ldr128(src);
    if (AD && w >= 4) wait_clk(tr, AD);
    if (w < 4) {
      const u32 aa = SM_WD + (8 * (lane >> 4) + (lane & 7)) * 128 + (((2 * w + ((lane >> 3) & 1)) ^ (lane & 7)) << 4);
      mb_wait(SM_MB + 24);
#pragma unroll
      for (int s = 0; s < 24; s++) A[s] = ldsm4t(aa + (s < 6 ? SM_TAP - SM_WD : -12288) + s * 2048);
    }
    TS(28);
    POLLW(a = ldr128(src), (a.x ^ pm) & TAGM, 9);
    sts128(SM_AC + tid * 16, a.x & ~TAGM, a.y, a.z, a.w);
    TS(27);
    if (w < 4) {
      bsync(8, 384);
      float c[4][4] = {};
#pragma unroll
      for (int s = 0; s < 12; s++) {
        const uint4 bb = ldsm4(SM_AC + lane * 16 + s * 512);
        mma_bf(c[2 * (s & 1)], A[2 * s].x, A[2 * s].y, A[2 * s].z, A[2 * s].w, bb.x, bb.y);
        mma_bf(c[2 * (s & 1) + 1], A[2 * s + 1].x, A[2 * s + 1].y, A[2 * s + 1].z, A[2 * s + 1].w, bb.z, bb.w);
      }
      char* dst = gs + (G_PART + b * 2048 + w * 512 + lane * 8);
      u32 o[4];
#pragma unroll
      for (int i = 0; i < 4; i++) o[i] = (fu(((c[0][i] + c[1][i]) + (c[2][i] + c[3][i])) * F2P64) & ~1u) | par;
      str64(dst, o[0], o[1]); str64(dst + 256, o[2], o[3]);
      TS(29);
    } else barrive(8, 384);
  }
  OUTR(7);
  if (w == 8 && b < 72) {
    const u32 ta = clk();
    const u32 kg = lds32(SM_SLOT + 4 * g), ro = (2047 - ((kg >> 2) & 2047)) * 1152 + 16 * b;
    const char* src = gs + (G_PART + (b >> 3) * 2048 + (b & 7) * 256 + lane * 8);
    const char* xs = gs + (G_Y + ro);
    uint4 xt;
    POLL(xt = ldr128(xs), (xt.x ^ TAGR) & TAGM, 10);
    const u32 x1w = (q & 2) ? ((q & 1) ? xt.w : xt.z) : ((q & 1) ? xt.y : bmul(xt.x ^ TAGR, B2P64));
    const u32 gw = lds32(SM_MODS + 5760 + 16 * b + 4 * q);
    const u32 hw = lds32(SM_XS + g * ROW + b * 16 + q * 4);
    const float sgm = rcpf(1.f + ex2(-LOG2E * bhi(kg ^ (~((int)kg >> 31) | 0x80000000))));
    char* const dst = p.out + (ro + 4 * q);
    uint2 v[12];
#pragma unroll
    for (int j = 0; j < 12; j++) v[j] = make_uint2(1, 0);
    u32 bad;
    if (PD) wait_clk(ta, PD);
    POLL({ bad = 0; _Pragma("unroll") for (int j = 0; j < 12; j++) { if (((v[j].x ^ par) | (v[j].y ^ par)) & 1) v[j] = ldr64(src + j * 9 * 2048); }
           _Pragma("unroll") for (int j = 0; j < 12; j++) bad |= (v[j].x ^ par) | (v[j].y ^ par); }, bad & 1, 11);
    float s0[4] = {}, s1[4] = {};
#pragma unroll
    for (int j = 0; j < 12; j++) { s0[j & 3] += uf(v[j].x); s1[j & 3] += uf(v[j].y); }
    const u32 y = movm(pk_bf((s0[0] + s0[1]) + (s0[2] + s0[3]), (s1[0] + s1[1]) + (s1[2] + s1[3])));
    *(u32*)dst = badd(x1w, bmul(gw, badd(hw, bmul(y, pk_bf(sgm, sgm)))));
    if (b == 0 && lane == 0) str32(gs + G_EP, par);
    TS(30); TSE();
  }
  if (w == 10) asm volatile("cp.async.bulk.wait_group.read 0;" ::: "memory");
}

DEV void post_conv(const Prm& p, const CUtensorMap* tm_down, const u32 tid, const u32 b) {
  const u32 w = tid >> 5, lane = tid & 31;
  const u32 g = lane >> 2, q = lane & 3, e = g >> 2, h = (g >> 1) & 1, hi = g & 1;
  const u32 pm = lds32(SM_THR + 4), par = pm >> 30;
  char* const gs = p.gs;
  const u32 cho = 128 * w + 64 * e + 16 * q;
  u32 x1[4][4], h2[4][4], key[4], lt;
  char* const rowp = gs + (b * BLK + (4 * h + 8 * hi) * 1152 + cho);
  u32 ot = 0;
  uint4 A[24];
#define AROW(t) const u32 arow = 144 * ((t >> 5) & 3) + ((t >> 1) & 8) + (t & 7), ab = (t & 8) ? SM_UP : SM_GATE;
#define AFRAG9() { _Pragma("unroll") for (int s = 0; s < 9; s++) A[s] = ldsm4t(ab + SLV + arow * 16 + s * 256); }
  if (w < 9) {
    const u32 yc = 8 * (q >> 1) + 2 * (g >> 1), y1 = w < 8 ? BLK : 4 * BLK, y2 = 2 * y1;
    const char* ysrc = gs + (G_Y + (q & 1) * 16 + (w < 8 ? (16 * w + 8 * (q >> 1) + (g & 4)) * BLK + b * 128 + (g & 3) * 32 : (8 * yc + 2 * hi + ((b >> 4) & 1)) * BLK + 16384 + ((b >> 5) * 16 + (b & 15)) * 32));
    const char* const ys[4] = {ysrc, ysrc + y1, ysrc + y2, ysrc + (y1 + y2)};
    uint4 yv[4];
    u32 tc = clk();
    if (w < 4 && (YS || b < YL)) {
#pragma unroll
      for (int v = 0; v < 4; v++) yv[v] = ldr128(ys[v]);
    } else {
#pragma unroll
      for (int v = 0; v < 4; v++) yv[v].x = INVAL;
    }
    const u32 ma = SM_MODS + cho, xa = SM_XST + (2 * h + 4 * hi) * ROW + cho;
    const uint4 sa = lds128(ma), ca = lds128(ma + 1152), ga = lds128(ma + 2304), dk = lds128(ma + 6912);
    const uint4 rb = lds128((g & 2) ? SM_ONE + 16 * hi : (ma ^ 64) + 8064 + 1152 * hi);
    const u32 saw[4] = {sa.x, sa.y, sa.z, sa.w}, caw[4] = {ca.x, ca.y, ca.z, ca.w}, gaw[4] = {ga.x, ga.y, ga.z, ga.w}, dw[4] = {dk.x, dk.y, dk.z, dk.w};
    u32 hD[4][4];
#pragma unroll
    for (int k = 0; k < 4; k++) {
      const uint4 st = lds128(SM_ST + 16 * (2 * h + 4 * hi + (k & 1) + 8 * (k >> 1))), xv = lds128(xa + ((k & 1) + 8 * (k >> 1)) * ROW);
      x1[k][0] = xv.x; x1[k][1] = xv.y; x1[k][2] = xv.z; x1[k][3] = xv.w;
#pragma unroll
      for (int v = 0; v < 4; v++) {
        const u32 d = badd(x1[k][v], st.x), z = bfma(d, st.y, bmul(d, st.z));
        hD[k][v] = bmul(badd(bmul(z, caw[v]), saw[v]), dw[v]);
      }
    }
    const bool own = (q >> 1) == e;
    const u32 spw = SM_SP + (2 * w + e) * 320 + (g & 3) * 16 + (own ? ((q & 1) == h ? 4 : 12) : 8 - 8 * (q & 1));
    TS(18);
    if (w >= 4) { if (w < 8 && b < YE) barrive(12, 288); else bsync(12, 288); tc = clk(); }
    if (w == 8) barrive(7, 64);
    if (b >= YL && (!YS || w >= 4)) wait_clk(tc, YD);
    TS(13);
    POLLW(_Pragma("unroll") for (int v = 0; v < 4; v++) if ((yv[v].x ^ pm) & TAGM) yv[v] = ldr128(ys[v]),
          ((yv[0].x ^ pm) | (yv[1].x ^ pm) | (yv[2].x ^ pm) | (yv[3].x ^ pm)) & TAGM, 5);
    TS(19);
    if (DECL && w < 4) asm volatile("setmaxnreg.dec.sync.aligned.u32 168;");
#pragma unroll
    for (int k = 0; k < 4; k += 2) {
      float X[4] = {}, Y[4] = {}, R[4] = {};
#pragma unroll
      for (int v = 0; v < 4; v++) {
        const u32 y0 = k ? yv[v].z : yv[v].x & ~TAGM, y1 = k ? yv[v].w : yv[v].y;
        x1[k][v] = badd(x1[k][v], bmul(gaw[v], bfma(movm(y0), B2P64, hD[k][v])));
        x1[k + 1][v] = badd(x1[k + 1][v], bmul(gaw[v], bfma(movm(y1), B2P64, hD[k + 1][v])));
        mma8_bf(X, x1[k][v], x1[k + 1][v], x1[k][v]); mma8_bf(Y, x1[k][v], x1[k + 1][v], x1[k + 1][v]);
        if (v & 1) mma_bf(R, x1[k][v - 1], x1[k + 1][v - 1], x1[k][v], x1[k + 1][v], v & 2 ? rb.z : rb.x, v & 2 ? rb.w : rb.y);
      }
      sts32(spw + k * 64, fu(own ? (hi ? X[1] : X[0]) : R[0] + R[1]));
      sts32(spw + k * 64 + 64, fu(own ? (hi ? Y[3] : Y[2]) : R[2] + R[3]));
    }
    barrive(1, 320);
    TS(36);
    const uint4 sb = lds128(ma + 3456), cb = lds128(ma + 4608), gb = lds128(ma + 5760);
    const u32 sbw[4] = {sb.x, sb.y, sb.z, sb.w}, cbw[4] = {cb.x, cb.y, cb.z, cb.w}, gbw[4] = {gb.x, gb.y, gb.z, gb.w};
    bsync(2, 320);
    TS(37);
    lt = lds32(SM_THR);
#pragma unroll
    for (int k = 0; k < 4; k++) {
      const uint4 st = lds128(SM_ST2 + 64 * k + 16 * (g & 3));
      key[k] = st.w;
      u32 o[4];
#pragma unroll
      for (int v = 0; v < 4; v++) {
        const u32 d = badd(x1[k][v], st.x), z = bfma(d, st.y, bmul(d, st.z));
        h2[k][v] = badd(bmul(z, cbw[v]), sbw[v]);
        o[v] = badd(x1[k][v], bmul(gbw[v], h2[k][v]));
      }
      h2[k][0] = bmul(h2[k][0], B2M64) | TAGR;
      if (key[k] >= lt) str128(rowp + k * 1152, h2[k][0], h2[k][1], h2[k][2], h2[k][3]);
      sts128(xa + ((k & 1) + 8 * (k >> 1)) * ROW, o[0], o[1], o[2], o[3]);
    }
    barrive(3, 320);
    TS(21);
    asm volatile("setmaxnreg.inc.sync.aligned.u32 168;");
    mb_wait(SM_MB + 8); mb_wait(SM_MB + 16);
    const u32 t3 = tid ^ p.zero;
    AROW(t3);
    if (t3 < 256) {
      const u32 aa = ab + arow * 64 + ((((t3 >> 6) & 2) ^ ((t3 & 7) >> 1)) << 4);
#pragma unroll
      for (int s = 0; s < 9; s++) { A[s] = ldsm4t(aa + s * 1024); A[9 + s] = ldsm4t((aa ^ 16) + s * 1024); }
    } else AFRAG9();
    TS(22);
    bsync(6, 352);
    TS(24);
    const u32 g8 = lds32(SM_SLOT + 28);
    const u32 sk = lds32(SM_SLOT + 4 * (w & 7));
    const char* rs_ = gs + (((~sk >> 2) & 2047) * 1152 + lane * 16);
    uint4 rv[3];
    rv[0].x = rv[1].x = rv[2].x = TAGR;
    if (w < 8) { rv[0] = ldr128(rs_); rv[1] = ldr128(rs_ + 512); if (lane < 8) rv[2] = ldr128(rs_ + 1024); barrive(15, 320); }
    if (__any_sync(~0u, max(max(key[0], key[1]), max(key[2], key[3])) >= g8)) {
#pragma unroll
      for (int k = 0; k < 4; k++) if (key[k] >= g8) {
        if (key[k] < lt) str128(rowp + k * 1152, h2[k][0], h2[k][1], h2[k][2], h2[k][3]);
        str128(rowp + (G_Y + k * 1152), bmul(x1[k][0], B2M64) | TAGR, x1[k][1], x1[k][2], x1[k][3]);
      }
    }
    if (w < 8) {
      bsync(5, 320);
      const u32 sf = lds32(SM_SLOT + 4 * w);
      if (sf != sk) { rs_ = gs + (((~sf >> 2) & 2047) * 1152 + lane * 16); rv[0].x = INVAL; }
    }
    POLLW({ rv[0] = ldr128(rs_); rv[1] = ldr128(rs_ + 512); if (lane < 8) rv[2] = ldr128(rs_ + 1024); },
          ((rv[0].x ^ TAGR) | (rv[1].x ^ TAGR) | (rv[2].x ^ TAGR)) & TAGM, 8);
    TS(38);
#pragma unroll
    for (int j = 0; j < 3; j++) if (w < 8 && (j < 2 || lane < 8)) sts128(SM_XS + w * ROW + lane * 16 + j * 512, bmul(rv[j].x ^ TAGR, B2P64), rv[j].y, rv[j].z, rv[j].w);
  } else {
    u32 ok, lr;
    if (w == 10) {
      uint2 rc = lds64(SM_RC + 8 * min(lane, 17u));
      float r1 = lane < 18 ? uf(rc.x) : 0.f, r2 = lane < 18 ? uf(rc.y) : 0.f;
#pragma unroll 1
      for (int o = 16; o; o >>= 1) { r1 += __shfl_xor_sync(~0u, r1, o); r2 += __shfl_xor_sync(~0u, r2, o); }
      const u32 tl = 4 * ((lane >> 1) & 1) + ((lane >> 2) & 3) + 8 * (lane & 1), kl = (2047 - 16 * b - tl) << 2 | par * 3;
      char* const kp = gs + (G_KEY + b * KST);
      const u32 spr = SM_SP + (lane >> 4) * 9 * 320 + (lane & 15) * 16;
      TS(31);
      bsync(1, 320);
      float S1 = 0.f, S2 = 0.f, S3 = 0.f;
#pragma unroll
      for (int i = 0; i < 9; i++) { uint4 t = lds128(spr + i * 320); S1 += uf(t.x); S2 += uf(t.y); S3 += uf(t.z); }
      S1 += __shfl_xor_sync(~0u, S1, 16); S2 += __shfl_xor_sync(~0u, S2, 16); S3 += __shfl_xor_sync(~0u, S3, 16);
      const float mu = S1 * (1.f / 576.f), var = fmaxf(fmaf(-mu, mu, S2 * (1.f / 576.f)), 0.f);
      const float m = rbf(mu), rs = rcpf(rbf(sqrta(rbf(rbf(var) + 1e-5f))));
      const u32 rb = pk_bf(0.f, fmaf(fmaf(-m, r1, S3), rs, r2) + 0.f);
      ok = ((rb ^ (((int)rb >> 31) | 0x80000000)) & 0xffff0000u) | kl;
      const float rh = rbf(rs);
      sts32(SM_KEY + 4 * (lane & 15), ok);
      sts128(SM_ST2 + 16 * (lane & 15), pk_bf(-m, -m), pk_bf(rh, rh), pk_bf(rs - rh, rs - rh), ok);
      __syncwarp();
      const uint4 o0 = lds128(SM_KEY + 2 * (lane & 16)), o1 = lds128(SM_KEY + 2 * (lane & 16) + 16);
      lr = (o0.x > ok) + (o0.y > ok) + (o0.z > ok) + (o0.w > ok) + (o1.x > ok) + (o1.y > ok) + (o1.z > ok) + (o1.w > ok);
      lr += __shfl_xor_sync(~0u, lr, 16);
      if (lane < 16 && lr < 8) str32(kp + 4 * lr, ok);
      if (lr == (b < NB8 ? 7 : NEARLY - 1)) sts32(SM_THR, ok);
      barrive(2, 320);
      barrive(4, 64);
      TS(20);
    } else if (w == 9) {
      bsync(7, 64);
      wait_clk(clk(), DD);
      PROXY_FENCE();
      DOWN(1);
    }
    asm volatile("setmaxnreg.inc.sync.aligned.u32 168;");
    mb_wait(SM_MB + 8); mb_wait(SM_MB + 16);
    AROW(tid);
    AFRAG9();
    TS(22);
    if (w == 10) {
      bsync(3, 320);
      PROXY_FENCE();
      ot = lane < 16 && lr >= 8;
      OUTR(2);
      bsync(6, 352);
      bsync(15, 320);
      bsync(5, 320);
      if (lane < 16 && lr < 8 && ok < lds32(SM_SLOT + 28)) ot = 2;
      OUTR(4);
    } else if (w == 9) {
      bsync(15, 320);
      DOWN(4);
      TS(13);
    } else {
      const char* ks = gs + (G_KEY + (lane >> 1) * KST + (lane & 1) * 16);
      const u32 kt = par * 3;
      uint4 L[8];
#define KBAD(j) ((L[j].x ^ kt) & 3)
#define KLD(j) L[j] = ldr128(ks + j * 16 * KST)
      bsync(4, 64);
      if (KD) wait_clk(clk(), b < YL ? KD : KD1);
#pragma unroll
      for (int j = 0; j < 8; j++) KLD(j);
      POLLW(_Pragma("unroll") for (int j = 0; j < 8; j++) if (KBAD(j)) KLD(j), KBAD(0) | KBAD(1) | KBAD(2) | KBAD(3) | KBAD(4) | KBAD(5), 6);
      if (KBAD(6)) KLD(6);
      if (KBAD(7)) KLD(7);
      u32 H[8];
      merge4(H, L[0], L[1]); top8(H, L[2], L[3]); top8(H, L[4], L[5]);
#pragma unroll 1
      for (int pass = 0;; pass++) {
        u32 G[8], m;
#pragma unroll
        for (int i = 0; i < 8; i++) G[i] = H[i];
#pragma unroll
        for (int r = 0; r < 8; r++) {
          const u32 h0 = G[0];
          m = __reduce_max_sync(~0u, h0);
          sts32(SM_SLOT + 4 * r, m);
          if (r < 7) asm("{.reg .u32 t; sub.u32 t,%1,%2; min.u32 t,t,1; mad.lo.u32 %0,t,%3,%4;}" : "=r"(G[0]) : "r"(m), "r"(h0), "r"(h0 - G[1]), "r"(G[1]));
#pragma unroll
          for (int i = 1; i < 7 - r; i++) G[i] = h0 == m ? G[i + 1] : G[i];
        }
        if (pass) break;
        barrive(6, 352);
        TS(23);
        POLLW({ if (KBAD(6)) KLD(6); if (KBAD(7)) KLD(7); }, KBAD(6) | KBAD(7), 7);
        if (!__any_sync(~0u, max(L[6].x, L[7].x) > m)) break;
        top8(H, L[6], L[7]);
      }
      barrive(5, 320);
      TS(33);
    }
  }
  ffn_tail(p, tm_down, A, tid | p.zero, b, par, ot);
}

__global__ void __launch_bounds__(384, 1)
fused_kernel(const Prm p, const __grid_constant__ CUtensorMap tm_mod, const __grid_constant__ CUtensorMap tm_gate, const __grid_constant__ CUtensorMap tm_gs,
             const __grid_constant__ CUtensorMap tm_up, const __grid_constant__ CUtensorMap tm_us, const __grid_constant__ CUtensorMap tm_down) {
  extern __shared__ __align__(1024) unsigned char smem[];
  u32 la, ai, ldt; uint2 cr, ci;
  {
    const u32 t = threadIdx.x, d = t < 256 ? chan(blockIdx.x, t >> 5) : 512 + (blockIdx.x >> 1), o = d * 256 + 8 * (t & 31), o4 = o + ((t < 256 ? t >> 5 : t >> 3) & 4);
    asm volatile("{.reg .pred p; .reg .u16 h; setp.ne.u32 p,%7,0; @p ld.global.nc.u32 %0,[%8]; @p ld.global.nc.u32 %1,[%9]; @p ld.global.nc.v2.u32 {%2,%3},[%10];"
                 "@p ld.global.nc.v2.u32 {%4,%5},[%11]; @p ld.global.nc.u16 h,[%12]; cvt.u32.u16 %6,h;}"
                 : "=r"(la), "=r"(ai), "=r"(cr.x), "=r"(cr.y), "=r"(ci.x), "=r"(ci.y), "=r"(ldt)
                 : "r"(0x6ffu >> (t >> 5) & 1), "l"(p.la + o4), "l"(p.ai + o4), "l"(p.cr + o), "l"(p.ci + o), "l"(p.ldt + 2 * d));
  }
  const u32 t0 = clk();
  const u32 tid = __shfl_sync(~0u, threadIdx.x, threadIdx.x & 31), b = blockIdx.x + p.zero;
  const u32 w = tid >> 5, lane = tid & 31;
  const u32 g = lane >> 2, q = lane & 3, hi = g & 1;
  const u32 rho = b & 1, Ps = 512 + (b >> 1);
  char* const gs = p.gs;
  TS0();
  const bool kw = w != 8 && w != 11;
  const u32 ksig = w < 8 ? (w & 3) : 4, khf = w < 8 ? (w >> 2) : (w & 1);
  if (!kw) {
    if (tid == 352) {
#pragma unroll
      for (int i = 0; i < 4; i++) mb_init(SM_MB + 8 * i);
      asm volatile("fence.mbarrier_init.release.cluster;" ::: "memory");
      tm_pre(&tm_mod);
    }
    const char* cp = p.c + (576 * (w & 1) + 24 * min(lane, 23u));
    const uint2 c0 = ldg64(cp);
    la = c0.x; ai = c0.y; cr = ldg64(cp + 8); ci = ldg64(cp + 16);
  }
  const u32 zr = tid >> 16;
  const u32 epv = ldr32(gs + (G_EP + zr));
  const u32 tp = SM_TAP + ksig * TAPS;
  if (kw && !khf) {
#pragma unroll 1
    for (u32 i = lane * 16; i < TAPS; i += 512) sts128(tp + i, 0, 0, 0, 0);
  }
  if (tid < 128) sts128(SM_INV + 16 * tid, INVAL, 0, 1, 0);
  if (tid >= 252) str128(gs + (tid >= 380 ? G_MOD + b * 128 + q * 16 : b * BLK + 16384 - 252 * 16 + tid * 16), INVAL, 0, 1, 0);
  if (tid == 352 && b < 36) { while (clk() - t0 < DMOD); mb_expect(SM_MB, 36864); tma3d(SM_UP, &tm_mod, SM_MB, 32 * b, 0); }
  if (w < 9) {
    while ((int)(clk() - t0) < DX);
    const char* xp = p.x + (b * BLK + (lane >> 3) * 1152 + 128 * w + 16 * (lane & 7));
    const u32 xd = SM_XST + (((lane >> 3) & 1) + 8 * (lane >> 4)) * ROW + 128 * w + 16 * (lane & 7);
#pragma unroll
    for (int i = 0; i < 4; i++) cpa16(xd + 2 * ROW * i, xp + 4608 * i);
  }
  const u32 ktab = w < 8 ? SM_MODS + w * KTAB : SM_ZS + (w - 9) * KTAB;
  float k2048 = 0.f;
  if (kw) {
    u32 mx = __vmaxu2(__vmaxu2(cr.x & 0x7fff7fff, cr.y & 0x7fff7fff), __vmaxu2(ci.x & 0x7fff7fff, ci.y & 0x7fff7fff));
    const u32 E = max(__reduce_max_sync(~0u, max(mx & 0xffff, mx >> 16)) >> 7, 8u);
    TS(1);
    const float dt = rbf(ex2(blo(ldt) * LOG2E)), csc = uf((257 - E) << 23 | (fu(dt) & 0x7fffff));
    sts32(SM_SC + 16 * ksig + 12, fu(uf(fu(dt) & 0x7f800000) * uf((E - 2) << 23)));
    const u32 crw = khf ? cr.y : cr.x, ciw = khf ? ci.y : ci.x;
    float2 C[2], w4[2], w8[2], w16[2], w32[2], w64[2], w128[2], w256[2], w512[2], a1[2], a2[2], a3[2], t0[2], t1[2], s3[2];
#pragma unroll
    for (int m = 0; m < 2; m++) {
      const float lr2 = rbf(ex2((m ? bhi(la) : blo(la)) * LOG2E)) * dt * -LOG2E, th = (m ? bhi(ai) : blo(ai)) * dt;
      C[m] = make_float2((m ? bhi(crw) : blo(crw)) * csc, (m ? bhi(ciw) : blo(ciw)) * csc);
      const float2 w1 = cexp(lr2, th), w2 = csq(w1);
      w64[m] = cexp(64.f * lr2, 64.f * th);
      w4[m] = csq(w2); w8[m] = csq(w4[m]); w16[m] = csq(w8[m]); w32[m] = csq(w16[m]);
      w128[m] = csq(w64[m]); w256[m] = csq(w128[m]); w512[m] = csq(w256[m]);
      const float2 w1024 = csq(w512[m]);
      a1[m] = cmul(C[m], w1); a2[m] = cmul(C[m], w2); a3[m] = cmul(a1[m], w2);
      t0[m] = cmul(C[m], w1024); t1[m] = cmul(t0[m], w128[m]); s3[m] = cmul(w8[m], w16[m]);
      k2048 += fmaf(t0[m].x, w1024.x, -t0[m].y * w1024.y);
    }
    C2 B0[8], B1[8], B2[8], S[8];
    B0[0] = pk2(C); B0[1] = pk2(a1); B0[2] = pk2(a2); B0[3] = pk2(a3);
    const C2 h4 = pk2(w4), h256 = pk2(w256), h512 = pk2(w512);
#pragma unroll
    for (int i = 0; i < 4; i++) B0[4 + i] = cm2(B0[i], h4);
#pragma unroll
    for (int i = 0; i < 4; i++) B1[i] = cm2(B0[2 * i], h256);
    B1[4] = cm2(B0[0], h512); B1[5] = cm2(B0[4], h512);
    B1[6] = cm2(B1[4], h256); B1[7] = cm2(B1[5], h256);
    const u32 ta = ktab + lane * 128, f = ((lane & 3) << 5) | ((lane & 4) << 2);
#pragma unroll
    for (int i = 0; i < 8; i++) sts128(ta + ((i << 4) ^ f), B0[i].re, B0[i].im, B1[i].re, B1[i].im);
    B2[0] = pk2(t0); B2[1] = pk2(t1);
    B2[2] = cm2(B2[0], h256); B2[3] = cm2(B2[1], h256);
#pragma unroll
    for (int i = 0; i < 4; i++) B2[4 + i] = cm2(B2[i], h512);
    S[0] = {0x3C003C00u, 0u}; S[1] = pk2c(w8); S[2] = pk2c(w16); S[3] = pk2c(s3); S[4] = pk2c(w32);
#pragma unroll
    for (int i = 1; i < 4; i++) S[4 + i] = cm2(S[i], S[4]);
#pragma unroll
    for (int i = 0; i < 8; i++) sts128(ta + 4096 + ((i << 4) ^ f), B2[i].re, B2[i].im, S[i].re, S[i].im);
    const C2 m64 = pk2c(w64), m128 = pk2c(w128);
    sts128(ktab + 8192 + lane * 16, m64.re, m64.im, m128.re, m128.im);
    __syncwarp();
  } else {
    u32 sa = SM_SIL + 576 * (w & 1) + 24 * min(lane, 23u);
#pragma unroll 1
    for (int j = 0; j < 6; j++) {
      sts32(sa, pk_bf(silu_f(blo(la)), silu_f(bhi(la))));
      la = ai; ai = cr.x; cr.x = cr.y; cr.y = ci.x; ci.x = ci.y; sa += 4;
    }
    bsync(7, 64);
  }
  TS(2);
  const u32 pm = (__reduce_or_sync(~0u, epv) & 1) ? 0 : TAGM;
  sts32(SM_THR + 4, pm);
  if (w < 9) {
    asm volatile("cp.async.wait_all;" ::: "memory");
    __syncwarp();
    TS(4);
    if (tid == 256 && b >= 36 && b < 108) { mb_expect(SM_MB, 36864); tma3d(SM_UP, &tm_mod, SM_MB, 32 * b, 0); }
    const u32 xa = SM_XST + (lane & 15) * ROW + 128 * w + 16 * (lane >> 4);
    float s[4] = {}, X[2][4] = {}, Y[2][4] = {};
#pragma unroll
    for (int j = 0; j < 4; j++) {
      const uint4 a = ldsm4(xa + 32 * j);
      mma8_bf(X[0], a.x, a.y, a.x); mma8_bf(Y[0], a.x, a.y, a.y);
      mma8_bf(X[1], a.z, a.w, a.z); mma8_bf(Y[1], a.z, a.w, a.w);
      mma_bf(s, a.x, a.y, a.z, a.w, BONE, BONE);
    }
    uint4 t[4];
#pragma unroll
    for (int j = 0; j < 4; j++) t[j] = ldsm4t(xa + 32 * j);
    const float u0 = hi ? X[0][1] + X[1][1] : X[0][0] + X[1][0], u1 = hi ? Y[0][3] + Y[1][3] : Y[0][2] + Y[1][2];
    if (q == g >> 1) sts128(SM_SP + w * 128 + g * 16, fu(s[0]), fu(u0), fu(s[2]), fu(u1));
    bsync(1, 288);
    TS(7);
    const u32 spr = SM_SP + (lane & 7) * 16 + (lane & 8);
    const uint2 t8 = lds64(spr + 1024);
    const float f8 = lane < 16 ? 1.f : 0.f;
    float S1 = uf(t8.x) * f8, S2 = uf(t8.y) * f8;
#pragma unroll
    for (int i = 0; i < 4; i++) { const uint2 u = lds64(spr + (lane & 16) * 32 + i * 128); S1 += uf(u.x); S2 += uf(u.y); }
    S1 += __shfl_xor_sync(~0u, S1, 16); S2 += __shfl_xor_sync(~0u, S2, 16);
    const float mu = S1 * (1.f / 576.f), var = fmaxf(fmaf(-mu, mu, S2 * (1.f / 576.f)), 0.f);
    const float m = rbf(mu), rs = rcpf(rbf(sqrta(rbf(rbf(var) + 1e-5f))));
    const float ra = rs * 0.0625f;
    sts64(SM_AF + w * 128 + (lane & 15) * 8, fu(ra), fu(-m * ra));
    __syncwarp();
    TS(55);
    const uint4 f0 = lds128(SM_AF + w * 128 + q * 16), f1 = lds128(SM_AF + w * 128 + 64 + q * 16);
    const u32 zdst = SM_GATE + w * 2048 + (g >> 1) * 128 + (lane & 15) * 8;
    const u32 pz = (q & 1) ? 0 : pm;
#pragma unroll
    for (int j = 0; j < 8; j++) {
      const u32 x0 = j & 1 ? t[j >> 1].z : t[j >> 1].x, x1 = j & 1 ? t[j >> 1].w : t[j >> 1].y;
      sts64((j & 1 ? zdst ^ 64 : zdst) + 512 * (j >> 1), pk_hf(fmaf(blo(x0), uf(f0.x), uf(f0.y)), fmaf(bhi(x0), uf(f0.z), uf(f0.w))) | pz,
            pk_hf(fmaf(blo(x1), uf(f1.x), uf(f1.y)), fmaf(bhi(x1), uf(f1.z), uf(f1.w))));
    }
    TS(53);
    if (w < 8) barrive(15, 288);
    else {
      bsync(15, 288);
      TS(54);
      if (lane == 0) {
        PROXY_FENCE();
        bulk_out<BLK>(gs + b * BLK, SM_GATE);
        asm volatile("cp.async.bulk.commit_group;" ::: "memory");
        if (PFG & 1) l2_pre<WSH / 2>(p.wg + b * WSH);
      }
      const float rh = rbf(rs);
      sts128(SM_ST + 16 * (lane & 15), pk_bf(-m, -m), pk_bf(rh, rh), pk_bf(rs - rh, rs - rh), 0);
    }
    TS(5);
  }
  if (kw) {
    float D[5][4] = {};
    u32 ta = ktab + q * 128 + ((g ^ (q << 1)) << 4), tm = ktab + 8192 + q * 16;
#pragma unroll 2
    for (int s = 0; s < 8; s++) {
      const uint4 ca = lds128(ta), cb = lds128(ta + 4096), ma = lds128(tm);
      ta = (ta + 512) ^ 16; tm += 64;
      k2048 += __shfl_xor_sync(~0u, k2048, 16 >> s);
      const C2 s0 = {cb.z, cb.w}, s1 = cm2(s0, {ma.x, ma.y}), s2 = cm2(s0, {ma.z, ma.w}), s3 = cm2(s1, {ma.z, ma.w});
      mma_hf(D[0], s0.re, s1.re, s0.im, s1.im, ca.x, ca.y);
      mma_hf(D[2], s0.re, s1.re, s0.im, s1.im, ca.z, ca.w);
      mma_hf(D[4], s0.re, s1.re, s0.im, s1.im, cb.x, cb.y);
      mma_hf(D[1], s2.re, s3.re, s2.im, s3.im, ca.x, ca.y);
      mma_hf(D[3], s2.re, s3.re, s2.im, s3.im, ca.z, ca.w);
    }
    TS(3);
    const u32 xa = (w < 8 ? SM_MODS + (4 + ksig) * KTAB : SM_ZS) + lane * 16;
    if (khf) {
      __syncwarp();
#pragma unroll
      for (int j = 0; j < 5; j++) sts128(xa + 512 * j, fu(D[j][0]), fu(D[j][1]), fu(D[j][2]), fu(D[j][3]));
      if (lane == 0) sts32(xa + 2560, fu(k2048));
      asm volatile("bar.arrive %0,64;" ::"r"(2 + ksig) : "memory");
    } else {
      const u32 t1 = tp + (q < 2 ? (128 + 4 * g + 2 * q) * 4 : T3 * 4 + ((32 * q - 64 + g) ^ 1) * 2);
      const u32 x = 16 * q + (g >> 1) + hi + 1, tb = tp + (hi ? T7E : T9E) * 4 - 4;
      const u32 te = tb + (x + 2 * (x & 1)) * 2, to = tb + TEO * 4 + (x ^ 1) * 2;
      asm volatile("bar.sync %0,64;" ::"r"(2 + ksig) : "memory");
#pragma unroll
      for (int j = 0; j < 5; j++) { const uint4 t = lds128(xa + 512 * j); D[j][0] += uf(t.x); D[j][1] += uf(t.y); D[j][2] += uf(t.z); D[j][3] += uf(t.w); }
      k2048 = (k2048 + uf(lds32(xa + 2560))) * 0.125f;
#pragma unroll
      for (int r = 0; r < 4; r++) {
        const u32 v = pk_hf(D[2 + (r >> 1)][2 * (r & 1)], D[2 + (r >> 1)][2 * (r & 1) + 1]);
        if (q < 2) {
          const u32 vv = __byte_perm(v, v, 0x1010);
          sts32(t1 + (TO + 32 * r) * 4, vv); sts16(t1 + (TO + 32 * r + 1) * 4 + 2, v >> 16); sts16(t1 + (TO + 32 * r - 1) * 4, v);
          sts64(t1 + (TE + 32 * r) * 4, vv, __byte_perm(v, v, 0x1032));
        } else {
          sts16(t1 + 16 * r, v >> 16);
          if (r == 0 && lane == 2) {
            const u32 vv = __byte_perm(v, v, 0x1010);
            sts32(tp + (TO + 256) * 4, vv); sts16(tp + (TO + 257) * 4 + 2, v); sts16(tp + (TO + 255) * 4, v); sts64(tp + (TE + 256) * 4, vv, vv);
          } else sts16(t1 + 16 * r - ((T3 - T5) * 4 + 6) + 8 * hi, v);
        }
      }
#pragma unroll
      for (int r = 0; r < 2; r++) {
        const u32 v = pk_hf(D[4][2 * r], D[4][2 * r + 1]);
        if (r == 0 && lane == 0) { sts16(tp + T5 * 4 + 62 * 2, v); sts32(SM_KV + 4 * ksig, v & 0xffff); sts16(tp + (T9E + TEO) * 4 + 62 * 2, pk_hf(k2048, 0.f)); }
        else { sts16(te + 8 * r, v); sts16(to + 8 * r, v); }
        sts16(te + 8 * r + 16, v >> 16); sts16(to + 8 * r + 16, v >> 16);
      }
      __syncwarp();
#pragma unroll
      for (int r = 0; r < 4; r++) {
        const u32 v = pk_hf(D[r >> 1][2 * (r & 1) + 1], D[r >> 1][2 * (r & 1)]), t2 = tp + lane * 4 + 128 * r;
        sts32(t2 + TO * 4, v); sts16(t2 + TE * 4, v >> 16); sts16(t2 + (TE + 1) * 4 + 2, v);
      }
      __syncwarp();
    }
  } else if (w == 11 && b < 108) {
    float c[4][4] = {};
    u32 aa = SM_UP + ((lane & 7) + 8 * (lane >> 4)) * 64 + ((((lane >> 3) & 1) ^ ((lane & 7) >> 1)) << 4);
    u32 ba = SM_SIL + (lane >> 3) * 16;
    uint4 a[2][10];
#define GLD(n) { _Pragma("unroll") for (int i = 0; i < 2; i++) { a[n][5 * i] = ldsm4(ba + i * 64); \
      _Pragma("unroll") for (int k = 0; k < 4; k++) a[n][5 * i + 1 + k] = ldsm4t((k & 2 ? aa ^ 32 : aa) + i * 2048 + (k & 1) * 1024); } aa += 4096; ba += 128; }
#define GMM(n) { _Pragma("unroll") for (int i = 0; i < 2; i++) _Pragma("unroll") for (int k = 0; k < 4; k++) { const uint4 f = a[n][5 * i + 1 + k], bb = a[n][5 * i]; \
      mma_bf(c[k], f.x, f.y, f.z, f.w, k & 1 ? bb.z : bb.x, k & 1 ? bb.w : bb.y); } }
    mb_wait(SM_MB);
    TS(56);
    GLD(0);
#pragma unroll 1
    for (int s = 0; s < 4; s++) { GLD(1); GMM(0); GLD(0); GMM(1); }
    GMM(0);
    const float v0 = (q & 1) ? c[0][2] + c[1][2] : c[0][0] + c[1][0], v1 = (q & 1) ? c[2][2] + c[3][2] : c[2][0] + c[3][0];
    str16(gs + (G_MOD + b * 128 + 2 * g + 16 * q), pk_bf(rbf((q & 2) ? v1 : v0) * F2M64, 0.f) | (g < 2 ? pm : 0));
    TS(57);
  }
  TS(6);
  u32 tid2 = tid;
  if (w < 4) {
    asm volatile("setmaxnreg.inc.sync.aligned.u32 232;");
    const u32 tid = tid2 + p.zero, w = tid >> 5, lane = tid & 31, g = lane >> 2, q = lane & 3, hi = g & 1, zr = tid >> 16, tp = SM_TAP + w * TAPS;
    const u32 pml = opq((g & 3) ? 0 : pm);
    const u32 tr = tp + ((hi ? TO : TE) + (g >> 1) - q) * 4;
    u32 T[33][4], B5[5][2], B3[5][2];
#pragma unroll
    for (int d = 0; d < 33; d++) {
      T[d][0] = lds32(tr + 32 * d); T[d][1] = lds32(tr + 32 * d + 16);
      T[d][2] = cpy(d ? T[d - 1][1] : zr, zr, 0); T[d][3] = cpy(T[d][0], zr, 1);
    }
    const u32 t33 = cpy(T[32][1], zr, 0), z33 = cpy(zr, zr, 1);
    const u32 bt = tp + (T5 + g - q) * 4;
#pragma unroll
    for (int d = 0; d < 5; d++) {
      B5[d][0] = lds32(bt + 32 * d); B5[d][1] = lds32(bt + 32 * d - 16);
      B3[d][0] = lds32(bt + 32 * d + (T3 - T5) * 4); B3[d][1] = lds32(bt + 32 * d - 16 + (T3 - T5) * 4);
    }
    u32 za = opq(SM_ZS + 16 + w * ZSS + ((lane >> 3) & 1) * ZPS + ((lane & 7) + (lane >> 4)) * 16);
    u32 wa = opq(SM_W + W5O + w * WSL + row16(lane));
    u32 sa = opq(SM_W + W9O - 2048 + w * WSL + lane * 16);
    u32 yo = opq(G_Y + b * BLK + 256 * q + w * 32 + 4 * g);
    const u32 fa = opq(SM_SC + 16 * w + 8);
    TS(8);
    bsync(9, 384);
    TS(11);
    float A[4][4] = {};
    uint4 Z[4];
    Z[0] = ldsm4(za); Z[1] = ldsm4(za + 32);
    const uint2 fc = lds64(fa);
    const u32 F = __byte_perm(fu(uf(fc.x) * uf(fc.y)), 0, 0x3232);
#define STEP(s, b0, b1) { _Pragma("unroll") for (int i = 0; i < 4; i++) mma_hf_t(A[i], T[8 * i + 7 - (s)], b0, b1); }
#define PAIR(n) { Z[(n + 2) & 3] = ldsm4(za + 32 * (n + 2)); STEP(2 * n, Z[n].x, Z[n].y); STEP(2 * n + 1, Z[n].z, Z[n].w); }
#define LAST(N) mma8_hf(N, t33, z33, Z[3].y); float O[4]; mma_hf_o(O, A[0], T[0], Z[3].z, Z[3].w); \
    _Pragma("unroll") for (int i = 0; i < 3; i++) mma_hf_o(A[i], A[i + 1], T[8 * i + 8], Z[3].z, Z[3].w); \
    mma_hf_o(A[3], N, T[32], Z[3].z, Z[3].w);
#pragma unroll 1
    for (int j = 0; j < 4; j++) {
      PAIR(0); PAIR(1); PAIR(2);
      Z[1] = ldsm4(za + 160); STEP(6, Z[3].x, Z[3].y);
      float N[4] = {};
      LAST(N);
      y_store<128>(O[0], O[1], O[2], O[3], F, pml, gs + yo);
      za += 128; yo += 1024;
      TS(40 + j);
    }
    bsync(10, 352);
#pragma unroll 1
    for (int j = 4; j < 13; j++) {
      if (j == 8) bsync(14, 352);
      const uint4 a5 = ldsm4t(wa), a3 = ldsm4t(wa + (W3O - W5O));
      uint4 s3 = {0, 0, 0, 0};
      if (j >= 8) s3 = lds128(sa);
      PAIR(0);
      float N[4] = {};
#pragma unroll
      for (int i = 0; i < 4; i++) mma_hf(A[i], a5.x, a5.y, a5.z, a5.w, B5[i][0], B5[i][1]);
      mma_hf(N, a5.x, a5.y, a5.z, a5.w, B5[4][0], B5[4][1]);
      PAIR(1);
#pragma unroll
      for (int i = 0; i < 4; i++) mma_hf(A[i], a3.x, a3.y, a3.z, a3.w, B3[i][0], B3[i][1]);
      mma_hf(N, a3.x, a3.y, a3.z, a3.w, B3[4][0], B3[4][1]);
      PAIR(2);
      Z[1] = ldsm4(za + 160); STEP(6, Z[3].x, Z[3].y);
      LAST(N);
      y_store<128>(O[0] + uf(s3.x), O[1] + uf(s3.y), O[2] + uf(s3.z), O[3] + uf(s3.w), F, pml, gs + yo);
      za += 128; wa = (wa + 256) ^ 32; sa += 512; yo += 1024;
      TS(40 + j);
    }
    {
      const uint4 s3 = lds128(sa), s4 = lds128(sa + 512), s5 = lds128(sa + 1024);
      float X[3][4] = {{uf(s4.x), uf(s4.y), uf(s4.z), uf(s4.w)}, {}, {uf(s5.x), uf(s5.y), uf(s5.z), uf(s5.w)}};
#pragma unroll
      for (int ty = 0; ty < 2; ty++) {
        const uint4 a = ldsm4t(wa + ty * (W3O - W5O)), c = ldsm4t((wa ^ 32) + 256 + ty * (W3O - W5O)), d = ldsm4t(wa + 512 + ty * (W3O - W5O));
#pragma unroll
        for (int i = 0; i < 3; i++) mma_hf(A[i], a.x, a.y, a.z, a.w, ty ? B3[i][0] : B5[i][0], ty ? B3[i][1] : B5[i][1]);
#pragma unroll
        for (int i = 0; i < 2; i++) mma_hf(X[i], c.x, c.y, c.z, c.w, ty ? B3[i][0] : B5[i][0], ty ? B3[i][1] : B5[i][1]);
        mma_hf(X[2], d.x, d.y, d.z, d.w, ty ? B3[0][0] : B5[0][0], ty ? B3[0][1] : B5[0][1]);
      }
      asm volatile("mov.u32 %0,%%tid.x;" : "=r"(tid2));
#pragma unroll
      for (int n = 0; n < 4; n++) {
        const uint4 f0 = n < 2 ? Z[n] : ldsm4(za + 32 * n), f1 = ldsm4(za + 32 * n + 128), f2 = ldsm4(za + 32 * n + 256);
#pragma unroll
        for (int s = 2 * n; s < 2 * n + 2; s++) {
#pragma unroll
          for (int i = 0; i < 3; i++) mma_hf_t(A[i], T[8 * i + 7 - s], s & 1 ? f0.z : f0.x, s & 1 ? f0.w : f0.y);
          mma_hf_t(X[0], T[7 - s], s & 1 ? f1.z : f1.x, s & 1 ? f1.w : f1.y); mma_hf_t(X[1], T[15 - s], s & 1 ? f1.z : f1.x, s & 1 ? f1.w : f1.y);
          mma_hf_t(X[2], T[7 - s], s & 1 ? f2.z : f2.x, s & 1 ? f2.w : f2.y);
        }
      }
      y_store<128>(A[0][0] + uf(s3.x), A[0][1] + uf(s3.y), A[0][2] + uf(s3.z), A[0][3] + uf(s3.w), F, pml, gs + yo);
      y_store<128>(A[1][0] + X[0][0], A[1][1] + X[0][1], A[1][2] + X[0][2], A[1][3] + X[0][3], F, pml, gs + yo + 1024);
      y_store<128>(A[2][0] + X[1][0] + X[2][0], A[2][1] + X[1][1] + X[2][1], A[2][2] + X[1][2] + X[2][2], A[2][3] + X[1][3] + X[2][3], F, pml, gs + yo + 2048);
    }
    if (!YS || b < YL) barrive(12, 288);
    else { bsync(12, 288); wait_clk(clk(), YD0); }
    TS(15);
    if (!DECL) asm volatile("setmaxnreg.dec.sync.aligned.u32 168;");
  } else {
    asm volatile("setmaxnreg.dec.sync.aligned.u32 136;");
    const u32 t8 = tid - 128, pml = (g & 3) ? 0 : pm;
    {
      TS(12);
      if (PFG == 1 && tid == 288) l2_pre<WSH / 2>(p.wg + (b * WSH + WSH / 2));
      const char* zs = gs + ((16 * w - 64 + (lane >> 3)) * BLK + b * 128 + ((lane & 7) * 16 ^ rho * 64));
      const char* zs4 = gs + ((t8 >> 1) * BLK + (Ps >> 4) * 512 + (Ps & 6) * 64 + ((Ps >> 2 ^ Ps) & 2) * 32 + (Ps & 1) * 32 + (t8 & 1) * 16);
      uint4 v[5];
      v[4].x = INVAL;
      if (ZD) wait_clk(t0, ZD);
      if (w == 9) {
        const u32 d = lane < 4 ? chan(b, lane) : Ps;
        const char* mp = gs + (G_MOD + (d >> 5) * 128 + (d & 24) * 2);
        uint4 ta, tc;
        POLL({ ta = ldr128(mp); tc = ldr128(mp + MODJ); v[4] = ldr128(zs4); }, ((ta.x ^ pm) | (tc.x ^ pm)) & TAGM, 2);
        const u32 aw = (d & 4) ? ((d & 2) ? ta.w : ta.z) : ((d & 2) ? ta.y : ta.x & ~TAGM);
        const u32 cw = (d & 4) ? ((d & 2) ? tc.w : tc.z) : ((d & 2) ? tc.y : tc.x & ~TAGM);
        const float sa = ((d & 1) ? bhi(aw) : blo(aw)) * F2P64, c1 = rbf(fmaf((d & 1) ? bhi(cw) : blo(cw), F2P64, 1.f));
        const u32 EM = min(max(fu(fmaxf(32.f * fabsf(c1), fabsf(sa))) >> 23, 80u), 250u);
        const float inv = uf((264 - EM) << 23);
        if (lane < 5) { sts64(SM_SC + 16 * lane, pk_hf(16.f * c1 * inv, 16.f * c1 * inv), pk_hf(sa * inv, sa * inv)); sts32(SM_SC + 16 * lane + 8, (EM - 74) << 23); }
        TS(10);
      }
      POLLW(v[4] = ldr128(zs4), (v[4].x ^ pm) & TAGM, 1);
      TS(58);
#pragma unroll
      for (int j = 0; j < 4; j++) v[j] = ldr128(zs + j * 4 * BLK);
#define MARKERS() if (tid == 256) { \
        bulk_out<2048>(gs + (G_Y + 16384 + b * BLK), SM_INV); \
        _Pragma("unroll") for (int i = MT / 2; i < 8; i++) bulk_out<2048>(gs + (G_Y + 2048 * i + b * BLK), SM_INV); \
        bulk_out<2048>(gs + (G_PART + b * 2048), SM_INV); bulk_out<512>(gs + (G_ACT + b * 512), SM_INV); \
        bulk_out<32>(gs + (G_KEY + b * KST), SM_INV); if (!rho) bulk_out<128>(gs + (G_ACT + Ps * 128), SM_INV); \
        asm volatile("cp.async.bulk.commit_group;" ::: "memory"); }
      if (PFU == 2 && tid == 256) l2_pre<WSH>(p.wu + b * WSH);
      if (GE && tid == 256) {
        asm volatile("cp.async.bulk.wait_group.read 0;" ::: "memory");
#pragma unroll
        for (int i = 0; i < GE; i++) tma3d(SM_GATE + 12288 * i, &tm_gate, SM_MB + 8, 32 * b, i);
      }
      if (MKT == 0) MARKERS();
      if (PFG == 2 && tid == 256) l2_pre<WSH>(p.wg + b * WSH);
      if (PFG == 3 && tid == 256) l2_pre<WSH / 2>(p.wg + (b * WSH + WSH / 2));
      bsync(8, 256);
      const uint2 cc = lds64(SM_SC + 8 * (t8 & 6)), c4 = lds64(SM_SC + 64);
      POLLW(_Pragma("unroll") for (int j = 0; j < 4; j++) if ((v[j].x ^ pm) & TAGM) v[j] = ldr128(zs + j * 4 * BLK),
           ((v[0].x ^ pm) | (v[1].x ^ pm) | (v[2].x ^ pm) | (v[3].x ^ pm)) & TAGM, 1);
      TS(9);
      const u32 dst = SM_ZS + 128 + (t8 & 7) * ZPS + (16 * w - 64 + (lane >> 3)) * 16;
#pragma unroll
      for (int j = 4; j >= 0; j--) {
        const uint2 c = j < 4 ? cc : c4;
        sts128(j < 4 ? dst + j * 64 : SM_Z4 + 256 + (t8 & 1) * ZP4 + (t8 >> 1) * 16, hfma(v[j].x & ~TAGM, c.x, c.y), hfma(v[j].y, c.x, c.y), hfma(v[j].z, c.x, c.y), hfma(v[j].w, c.x, c.y));
      }
      if (t8 < 96) sts128(t8 < 64 ? SM_ZS + (t8 & 7) * ZPS + (t8 >> 3) * 16 : SM_Z4 + (t8 & 1) * ZP4 + (t8 & 30) * 8, 0, 0, 0, 0);
      if (MKT == 0) asm volatile("cp.async.bulk.wait_group.read 1;" ::: "memory");
      else asm volatile("cp.async.bulk.wait_group.read 0;" ::: "memory");
      bsync(9, 384);
      TS(11);
      if (MKT == 1) MARKERS();
      const bool lng = w < 8 || w == 9;
      const u32 ts = lane + 32 * (w == 8 ? 0 : w - 9), c = min(ts, 71u), ma = SM_MODS + 16 * c;
      const u32 sig = lng ? ksig : ts >> 4, l2 = lng ? lane : 32 + (ts & 15);
      const char* mq = gs + (G_MOD + (c >> 2) * 128 + (c & 3) * 16);
      if (!lng) {
#pragma unroll
        for (int j = 0; j < 6; j++) cpa16(ma + 1152 * j, mq + j * MODJ);
        cpa16(ma + 1152 * 6, p.dsk + 16 * c); cpa16(ma + 1152 * 7, p.wr + 16 * c);
        if (PFU == 3) {
#pragma unroll
          for (int j = 0; j < 4; j++) if (ts < 81) l2_line(p.wu + (b * WSH + (81 * j + ts) * 128));
        }
        if (tid == 352) {
          PROXY_FENCE();
          if (PFU == 1) l2_pre<WSH>(p.wu + b * WSH);
          mb_expect(SM_MB + 8, rho ? SLV : 46080);
#pragma unroll
          for (int i = GE; i < 3; i++) tma3d(SM_GATE + 12288 * i, &tm_gate, SM_MB + 8, 32 * b, i);
          if (!rho) tma3d(SM_GATE + SLV, &tm_gs, SM_MB + 8, 4096 + 4 * b, 0);
          mb_expect(SM_MB + 16, rho ? SLV : 46080);
          tma3d(SM_UP, &tm_up, SM_MB + 16, 32 * b, 0);
          if (!rho) tma3d(SM_UP + SLV, &tm_us, SM_MB + 16, 4096 + 4 * b, 0);
        }
      }
      const u32 wb = SM_W + sig * WSL;
      if (sig < 5) {
        const u32 za = (sig < 4 ? SM_ZS + 128 + sig * ZSS : SM_Z4 + 256) + l2 * 32, zb = za + (sig < 4 ? ZPS : ZP4);
        const uint4 c0 = lds128(zb - 32), c1 = lds128(za - 16), c2 = lds128(zb - 16), c3 = lds128(za), c4 = lds128(zb), c5 = lds128(za + 16), c6 = lds128(zb + 16);
        const u32 P[25] = {c0.z, c0.w, c1.x, c1.y, c1.z, c1.w, c2.x, c2.y, c2.z, c2.w, c3.x, c3.y, c3.z, c3.w, c4.x, c4.y, c4.z, c4.w, c5.x, c5.y, c5.z, c5.w, c6.x, c6.y, c6.z};
        u32 Q[25], D1[24], F4[23], W5[21], W3[17];
#pragma unroll
        for (int j = 1; j < 25; j++) Q[j] = __byte_perm(P[j - 1], P[j], 0x5432);
#pragma unroll
        for (int j = 1; j < 24; j++) D1[j] = hadd(P[j], Q[j]);
#pragma unroll
        for (int j = 2; j < 23; j++) F4[j] = hadd(D1[j], D1[j - 1]);
#pragma unroll
        for (int n = 0; n < 21; n++) W5[n] = hadd(F4[n + 2], P[n]);
#pragma unroll
        for (int n = 0; n < 17; n++) W3[n] = hadd(Q[n + 8], D1[n + 7]);
        const u32 a0 = wb + W5O + 64 * l2 + 16 * ((l2 >> 1) & 3);
#pragma unroll
        for (int i = 0; i < 4; i++) {
          sts128(a0 ^ (16 * i), W5[4 * i + 5], W5[4 * i + 6], W5[4 * i + 7], W5[4 * i + 8]);
          sts128((a0 ^ (16 * i)) + (W3O - W5O), W3[4 * i + 1], W3[4 * i + 2], W3[4 * i + 3], W3[4 * i + 4]);
        }
        if (lng) {
          if (lane < 16) sts128(wb + (lane & 7) * 16 + (lane & 8) * 400, 0, 0, 0, 0);
          const u32 a1 = wb + 32 * lane + 16 * ((lane >> 2) & 1);
#pragma unroll
          for (int i = 0; i < 4; i++) {
            const u32 a = (a1 ^ (16 * (i >> 1))) + 1024 * (i & 1), n = 4 * i;
            sts128(a + V2O, hadd(Q[n + 9], P[n + 8]), hadd(Q[n + 10], P[n + 9]), hadd(Q[n + 11], P[n + 10]), hadd(Q[n + 12], P[n + 11]));
            sts128(a + W9O, hadd(F4[n + 4], W5[n]), hadd(F4[n + 5], W5[n + 1]), hadd(F4[n + 6], W5[n + 2]), hadd(F4[n + 7], W5[n + 3]));
            sts128(a + W7O, hadd(F4[n + 6], W3[n]), hadd(F4[n + 7], W3[n + 1]), hadd(F4[n + 8], W3[n + 2]), hadd(F4[n + 9], W3[n + 3]));
          }
        }
      }
      if (w != 9) barrive(10, 352);
      __syncwarp();
      TS(32);
      if (lng) {
        const u32 wa = wb + ((lane >> 3) & 1) * 1024 + (((lane & 7) ^ (lane >> 4)) + 8 * (lane >> 4)) * 16;
        const u32 kv = lds32(SM_KV + 4 * sig), bi = (g >> 1) == q ? (hi ? kv << 16 : kv) : 0u;
        float acc[8][4] = {};
#pragma unroll
        for (int j = 0; j < 4; j++) { const uint4 a = ldsm4t(wa + V2O + j * 256); mma8_hf(acc[2 * j], a.x, a.y, bi); mma8_hf(acc[2 * j + 1], a.z, a.w, bi); }
        u32 bt = tp + (T9E + hi * TEO + (g >> 1) - q) * 4, wt = wa + W9O;
#pragma unroll 1
        for (int ty = 0; ty < 2; ty++) {
          uint4 a[4];
#pragma unroll
          for (int be = 0; be < 4; be++) a[be] = ldsm4t(wt + be * 256);
          u32 b1 = lds32(bt - 16);
#pragma unroll
          for (int d = 0; d < 8; d++) {
            const u32 b0 = lds32(bt + 16 * d);
#pragma unroll
            for (int be = 0; be < 4; be++) if (d + 2 * be < 8) mma_hf(acc[d + 2 * be], a[be].x, a[be].y, a[be].z, a[be].w, b0, b1);
            b1 = b0;
          }
          bt += (T7E - T9E) * 4; wt += W7O - W9O;
        }
        __syncwarp();
#pragma unroll
        for (int j = 0; j < 8; j++) sts128(wb + W9O + j * 512 + lane * 16, fu(acc[j][0]), fu(acc[j][1]), fu(acc[j][2]), fu(acc[j][3]));
        if (w != 9) barrive(14, 352);
        TS(34);
      }
      if (!lng) {
        asm volatile("cp.async.wait_all;" ::: "memory");
        uint4 md[6];
#pragma unroll
        for (int j = 0; j < 6; j++) md[j] = lds128(ma + 1152 * j);
        const uint4 wr = lds128(ma + 1152 * 7);
        POLLW(_Pragma("unroll") for (int j = 0; j < 6; j++) md[j] = ldr128(mq + j * MODJ),
              ((md[0].x ^ pm) | (md[1].x ^ pm) | (md[2].x ^ pm) | (md[3].x ^ pm) | (md[4].x ^ pm) | (md[5].x ^ pm)) & TAGM, 4);
#pragma unroll
        for (int j = 0; j < 6; j++) {
          const u32 o = (j % 3 == 1) ? BONE : 0x80008000u;
          md[j] = make_uint4(bfma(md[j].x & ~TAGM, B2P64, o), bfma(md[j].y, B2P64, o), bfma(md[j].z, B2P64, o), bfma(md[j].w, B2P64, o));
          sts128(ma + 1152 * j, md[j].x, md[j].y, md[j].z, md[j].w);
        }
        const uint4 H = make_uint4(bmul(md[4].x, wr.x), bmul(md[4].y, wr.y), bmul(md[4].z, wr.z), bmul(md[4].w, wr.w));
        sts128(ma + 1152 * 7, H.x, H.y, H.z, H.w);
        sts128(ma + 1152 * 8, bfma(md[4].x, wr.x, H.x ^ 0x80008000u), bfma(md[4].y, wr.y, H.y ^ 0x80008000u), bfma(md[4].z, wr.z, H.z ^ 0x80008000u), bfma(md[4].w, wr.w, H.w ^ 0x80008000u));
        float c4[4] = {};
        mma_bf(c4, md[4].x, md[3].x, md[4].y, md[3].y, wr.x, wr.y); mma_bf(c4, md[4].z, md[3].z, md[4].w, md[3].w, wr.z, wr.w);
        if (q == g >> 1) sts64(SM_RC + (ts >> 2) * 8, fu(hi ? c4[1] : c4[0]), fu(hi ? c4[3] : c4[2]));
        if (ts < 2) sts128(SM_ONE + 16 * ts, ts ? 0 : BONE, ts ? 0 : BONE, ts ? 0 : BONE, ts ? 0 : BONE);
        TS(14);
        if (MKT == 2) MARKERS();
        if (w == 8) asm volatile("cp.async.bulk.wait_group 0;" ::: "memory");
        if (w == 8) barrive(14, 352);
        if (PFW == 2) {
#pragma unroll
          for (int j = 0; j < 4; j++) if (ts < 81) l2_line(p.wd + (b * WSH + (81 * j + ts) * 128));
        }
        bsync(13, 96);
      }
      if (w >= 8) barrive(11, 256);
    }
    if (w < 8) {
      const int u0 = 4 * (w - 4) + 2 * rho;
      const u32 t4 = SM_TAP + 4 * TAPS;
      u32 tr = t4 + ((hi ? TO : TE) + (g >> 1) - q) * 4;
      u32 zb = SM_Z4 + 256 + ((lane >> 3) & 1) * ZP4 + u0 * 128 + (lane & 7) * 16 + (lane >> 4) * 128;
      float acc[4][4] = {};
      u32 prev = 0;
#pragma unroll 1
      for (int it = min(u0 + 2, 4); it; it--) {
#pragma unroll
        for (int s = 0; s < 8; s++) {
          const uint4 z = ldsm4(zb - 16 * s);
          const u32 t0 = lds32(tr + 32 * s), t1 = lds32(tr + 32 * s + 16);
          mma_hf(acc[s & 1], t0, t1, prev, t0, z.x, z.y);
          mma_hf(acc[2 + (s & 1)], t0, t1, prev, t0, z.z, z.w);
          prev = t1;
        }
        zb -= 128; tr += 256;
      }
      {
        const uint4 z = ldsm4(zb); const u32 t0 = lds32(tr), t1 = lds32(tr + 16);
        mma_hf(acc[0], t0, t1, prev, t0, z.x, z.y); mma_hf(acc[2], t0, t1, prev, t0, z.z, z.w);
        if (w > 4) { const uint4 y = ldsm4(zb - 16); mma8_hf(acc[1], t1, zr, y.y); mma8_hf(acc[3], t1, zr, y.w); }
      }
      bsync(11, 256);
      u32 wa = (SM_W + 4 * WSL + W5O + row16(lane) + (u0 - 3) * 256) ^ 32, bt = t4 + (T5 + g - q) * 4;
#pragma unroll 1
      for (int al = min(u0 - 2, 6); al > 0; al--) {
#pragma unroll
        for (int ty = 0; ty < 2; ty++) {
          const uint4 a = ldsm4t(wa + ty * (W3O - W5O));
          const u32 bb = bt + ty * (T3 - T5) * 4;
          mma_hf(acc[ty], a.x, a.y, a.z, a.w, lds32(bb - 32), lds32(bb - 48));
          mma_hf(acc[2 + ty], a.x, a.y, a.z, a.w, lds32(bb), lds32(bb - 16));
        }
        wa = (wa - 256) ^ 32; bt += 32;
      }
      TS(35);
      const uint2 fc = lds64(SM_SC + 16 * 4 + 8);
      const u32 F = __byte_perm(fu(uf(fc.x) * uf(fc.y)), 0, 0x3232);
      char* yp = gs + (G_Y + 16384 - 2048 + b * BLK + w * 512 + q * 64 + 4 * g);
#pragma unroll
      for (int j = 0; j < 2; j++) {
        uint4 s3 = {0, 0, 0, 0};
        if (u0 >= 8) s3 = lds128(SM_W + 4 * WSL + W9O + (u0 - 8 + j) * 512 + lane * 16);
        y_store<32>(acc[2 * j][0] + acc[2 * j + 1][0] + uf(s3.x), acc[2 * j][1] + acc[2 * j + 1][1] + uf(s3.y), acc[2 * j][2] + acc[2 * j + 1][2] + uf(s3.z),
                acc[2 * j][3] + acc[2 * j + 1][3] + uf(s3.w), F, pml, yp + j * 256);
      }
      TS(16);
    } else {
      if (PFW == 3 && w == 9) {
#pragma unroll 1
        for (int j = 0; j < 12; j++) { if (lane < 27) l2_line(p.wd + (b * WSH + (27 * j + lane) * 128)); wait_clk(clk(), PFP); }
      }
      if (w >= 10) bsync(14, 352);
      if (w == 10 && b < YP) {
        wait_clk(clk(), 480 * ((int)(b >> 3) - 6));
        const char* yp = gs + (G_Y + (lane >> 2) * BLK + b * 128 + (lane & 3) * 32);
        u32 t = 0;
#pragma unroll
        for (int i = 0; i < 8; i++) t |= ldr32(yp + 8 * BLK * i);
        sts32(SM_KEY + 4 * (lane & 15), t);
      }
      if (PFW < 2 && tid == 352) { mb_wait(SM_MB + 8); if (PFW) mb_wait(SM_MB + 16); l2_pre<WSH>(p.wd + b * WSH); }
      if (D0C && tid == 352 && b < 108) {
        mb_wait(SM_MB + 16);
        PROXY_FENCE();
        mb_expect(SM_MB + 24, 49152);
        tma3d(SM_TAP, &tm_down, SM_MB + 24, 64 * (b % 9), 4 * (b / 9));
      }
      TS(17);
    }
  }
  post_conv(p, &tm_down, tid2 + p.zero, b);
  TSD();
  if (s2u(smem) != SM0) __trap();
}

typedef CUresult (*EncFn)(CUtensorMap*, CUtensorMapDataType, cuuint32_t, void*, const cuuint64_t*, const cuuint64_t*, const cuuint32_t*, const cuuint32_t*,
                          CUtensorMapInterleave, CUtensorMapSwizzle, CUtensorMapL2promotion, CUtensorMapFloatOOBfill);
static void make_map(EncFn enc, CUtensorMap* tm, void* ptr, int cols, int rows, int bw, int nb, CUtensorMapSwizzle sw, int gr = 192) {
  cuuint64_t gd[3] = {(cuuint64_t)cols, (cuuint64_t)gr, (cuuint64_t)(rows / gr)}, gs[2] = {(cuuint64_t)cols * 2, (cuuint64_t)cols * 2 * gr};
  cuuint32_t bd[3] = {(cuuint32_t)bw, (cuuint32_t)gr, (cuuint32_t)nb}, es[3] = {1, 1, 1};
  enc(tm, CU_TENSOR_MAP_DATA_TYPE_BFLOAT16, 3, ptr, gd, gs, bd, es, CU_TENSOR_MAP_INTERLEAVE_NONE, sw, CU_TENSOR_MAP_L2_PROMOTION_NONE, CU_TENSOR_MAP_FLOAT_OOB_FILL_NONE);
}
extern "C" void kernel_launch(void* const* d_in, const int* in_sizes, int n_in, void* d_out, int out_size) {
  static EncFn enc = nullptr;
  static void* scratch = nullptr;
  if (!enc) {
    cudaGetSymbolAddress(&scratch, g_s);
    cudaDriverEntryPointQueryResult qr;
    cudaGetDriverEntryPoint("cuTensorMapEncodeTiled", (void**)&enc, cudaEnableDefault, &qr);
    cudaFuncSetAttribute(fused_kernel, cudaFuncAttributeMaxDynamicSharedMemorySize, SM_TOTAL);
  }
  CUtensorMap tm_mod, tm_gate, tm_gs, tm_up, tm_us, tm_down;
  make_map(enc, &tm_mod, d_in[13], 3456, 576, 32, 3, CU_TENSOR_MAP_SWIZZLE_64B);
  make_map(enc, &tm_gate, d_in[9], 4608, 576, 32, 1, CU_TENSOR_MAP_SWIZZLE_64B);
  make_map(enc, &tm_gs, d_in[9], 4608, 576, 8, 3, CU_TENSOR_MAP_SWIZZLE_NONE);
  make_map(enc, &tm_up, d_in[10], 4608, 576, 32, 3, CU_TENSOR_MAP_SWIZZLE_64B);
  make_map(enc, &tm_us, d_in[10], 4608, 576, 8, 3, CU_TENSOR_MAP_SWIZZLE_NONE);
  make_map(enc, &tm_down, d_in[11], 576, 4608, 64, 1, CU_TENSOR_MAP_SWIZZLE_128B, 96);
  Prm p;
  p.x = (const char*)d_in[0]; p.la = (const char*)d_in[1]; p.ai = (const char*)d_in[2]; p.cr = (const char*)d_in[3];
  p.ci = (const char*)d_in[4]; p.ldt = (const char*)d_in[5]; p.dsk = (const char*)d_in[6]; p.wr = (const char*)d_in[8];
  p.wg = (const char*)d_in[9]; p.wu = (const char*)d_in[10]; p.wd = (const char*)d_in[11];
  p.c = (const char*)d_in[12]; p.out = (char*)d_out; p.zero = 0; p.gs = (char*)scratch;
  fused_kernel<<<128, 384, SM_TOTAL>>>(p, tm_mod, tm_gate, tm_gs, tm_up, tm_us, tm_down);
}
```

```cpp
#include <cuda_runtime.h>
#include <cuda.h>
#include <cuda_bf16.h>
#include <cuda_fp16.h>
#include <stdint.h>
#define FUSED 1
#define DEV __device__ __forceinline__
typedef uint32_t u32;

constexpr u32 BLK = 18432, G_Z = 0, G_Y = 128 * BLK, G_MOD = 2 * G_Y, G_KEY = G_MOD + 128 * 128, G_ACT = G_KEY + 128 * 128;
constexpr u32 G_PART = G_ACT + 576 * 128, G_EP = G_PART + 128 * 2048, G_END = G_EP + 128;
__device__ __align__(128) unsigned char g_s[G_END];
#define TS(i)
#define TS0()
#define TSE()
#define TSD()
#define TSX 0
#define TSN(code, n)
#define ERRF(code)

constexpr int SM0 = 1024;
constexpr int ROW = 1168, SLV = 36864;
constexpr int SM_GATE = SM0, SM_UP = SM_GATE + 46080, SM_XST = SM_UP + 46080, SM_MODS = SM_XST + 16 * ROW, SM_W = SM_MODS + 11008;
constexpr int KTAB = 9216, WSL = 12544, W5O = 128, W3O = 3328, V2O = 6400, W9O = 8448, W7O = 10496;
constexpr int ZPS = 2192, ZSS = 2 * ZPS, ZP4 = 2368;
constexpr int SM_ZS = SM_W + 5 * WSL, SM_Z4 = SM_ZS + 4 * ZSS, SM_TAP = SM_Z4 + 2 * ZP4, TAPS = 3328;
constexpr int SM_MB = SM_TAP + 5 * TAPS;
constexpr int SM_SC = SM_MB + 32;
constexpr int SM_KV = SM_SC + 80;
constexpr int SM_THR = SM_KV + 32;
constexpr int SM_SLOT = SM_THR + 48;
constexpr int SM_KEY = SM_SLOT + 32;
constexpr int SM_ST = SM_KEY + 64;
constexpr int SM_ST2 = SM_ST + 256;
constexpr int SM_RC = SM_ST2 + 256;
constexpr int SM_SP = SM_RC + 192;
constexpr int SM_AF = SM_SP + 1152, SM_SIL = SM_AF + 1152, SM_INV = SM_SIL + 1152, SM_END = SM_SP + 5760;
constexpr int SM_ONE = SM_MODS + 9 * 1152;
constexpr int SM_WD = SM_W, SM_XS = SM_W + 36864, SM_AC = SM_ZS, SM_RED = SM_AC + 6144;
constexpr int SM_TSB = SM_END, SM_TOTAL = SM_END + TSX - SM0;
static_assert(SM_W % 1024 == 0 && SM_TAP % 1024 == 0 && SM_MODS + 8 * KTAB <= SM_ZS && SM_ZS + 2 * KTAB <= SM_TAP && SM_RED + 10240 <= SM_TAP && SM_XS + 8 * ROW <= SM_ZS, "smem map");
static_assert(SM_MB % 16 == 0 && SM_THR % 16 == 0 && SM_ST % 16 == 0 && SM_SP % 16 == 0 && SM_TOTAL <= 232448, "smem map");
constexpr int TE = 4, TO = 276, T5 = 560, T3 = 624, T9E = 680, T7E = 760, TEO = 40;
#define MT 10
#define DECL 1
#define MKT 1
#define KST 128
#define DE1 1
#define DE2 4
#define DE3 5
#define OUTA 2
#define OUTB 7
#define PFW 1
#define PFU 0
#define KD 700
#define D0C 0
#define YE 96
#define YL 104
#define YD 250
#define OPTM 1
#define YA 0
#define YB 0
#define YD8 500
#define FH 0
#define FO 0
#define KD1 1
#define AD 0
#define PD 0
#define ZD 0
#define DD 1000
#define YP 0
#define PFP 200
#define GE 0
#define NB8 8
#define DX 0
#define DMOD 1000
#define PFG 1
constexpr int SPIN = 1 << 16, NEARLY = 4;
constexpr u32 TAGM = 0x40004000u, TAGR = 0x40000000u, INVAL = 0x00004801u;

DEV u32 s2u(const void* p) { return (u32)__cvta_generic_to_shared(p); }
DEV void mma_bf(float (&c)[4], u32 a0, u32 a1, u32 a2, u32 a3, u32 b0, u32 b1) {
  asm("mma.sync.aligned.m16n8k16.row.col.f32.bf16.bf16.f32 {%0,%1,%2,%3},{%4,%5,%6,%7},{%8,%9},{%0,%1,%2,%3};"
      : "+f"(c[0]), "+f"(c[1]), "+f"(c[2]), "+f"(c[3]) : "r"(a0), "r"(a1), "r"(a2), "r"(a3), "r"(b0), "r"(b1));
}
DEV void mma_hf(float (&c)[4], u32 a0, u32 a1, u32 a2, u32 a3, u32 b0, u32 b1) {
  asm("mma.sync.aligned.m16n8k16.row.col.f32.f16.f16.f32 {%0,%1,%2,%3},{%4,%5,%6,%7},{%8,%9},{%0,%1,%2,%3};"
      : "+f"(c[0]), "+f"(c[1]), "+f"(c[2]), "+f"(c[3]) : "r"(a0), "r"(a1), "r"(a2), "r"(a3), "r"(b0), "r"(b1));
}
DEV void mma8_bf(float (&c)[4], u32 a0, u32 a1, u32 b0) {
  asm("mma.sync.aligned.m16n8k8.row.col.f32.bf16.bf16.f32 {%0,%1,%2,%3},{%4,%5},{%6},{%0,%1,%2,%3};"
      : "+f"(c[0]), "+f"(c[1]), "+f"(c[2]), "+f"(c[3]) : "r"(a0), "r"(a1), "r"(b0));
}
DEV void mma8_hf(float (&c)[4], u32 a0, u32 a1, u32 b0) {
  asm("mma.sync.aligned.m16n8k8.row.col.f32.f16.f16.f32 {%0,%1,%2,%3},{%4,%5},{%6},{%0,%1,%2,%3};"
      : "+f"(c[0]), "+f"(c[1]), "+f"(c[2]), "+f"(c[3]) : "r"(a0), "r"(a1), "r"(b0));
}
DEV u32 movm(u32 x) { u32 r; asm("movmatrix.sync.aligned.m8n8.trans.b16 %0,%1;" : "=r"(r) : "r"(x)); return r; }
DEV uint4 ldsm4(u32 a) { uint4 r; asm volatile("ldmatrix.sync.aligned.m8n8.x4.shared.b16 {%0,%1,%2,%3},[%4];" : "=r"(r.x), "=r"(r.y), "=r"(r.z), "=r"(r.w) : "r"(a)); return r; }
DEV uint4 ldsm4t(u32 a) { uint4 r; asm volatile("ldmatrix.sync.aligned.m8n8.x4.trans.shared.b16 {%0,%1,%2,%3},[%4];" : "=r"(r.x), "=r"(r.y), "=r"(r.z), "=r"(r.w) : "r"(a)); return r; }
DEV u32 lds32(u32 a) { u32 r; asm volatile("ld.volatile.shared.u32 %0,[%1];" : "=r"(r) : "r"(a)); return r; }
DEV uint2 lds64(u32 a) { uint2 r; asm volatile("ld.shared.v2.u32 {%0,%1},[%2];" : "=r"(r.x), "=r"(r.y) : "r"(a)); return r; }
DEV uint4 lds128(u32 a) { uint4 r; asm volatile("ld.shared.v4.u32 {%0,%1,%2,%3},[%4];" : "=r"(r.x), "=r"(r.y), "=r"(r.z), "=r"(r.w) : "r"(a)); return r; }
DEV void sts16(u32 a, u32 v) { asm volatile("st.shared.u16 [%0],%1;" ::"r"(a), "h"((unsigned short)v) : "memory"); }
DEV void sts32(u32 a, u32 v) { asm volatile("st.shared.u32 [%0],%1;" ::"r"(a), "r"(v) : "memory"); }
DEV void sts64(u32 a, u32 x, u32 y) { asm volatile("st.shared.v2.u32 [%0],{%1,%2};" ::"r"(a), "r"(x), "r"(y) : "memory"); }
DEV void sts128(u32 a, u32 x, u32 y, u32 z, u32 w) { asm volatile("st.shared.v4.u32 [%0],{%1,%2,%3,%4};" ::"r"(a), "r"(x), "r"(y), "r"(z), "r"(w) : "memory"); }
DEV uint4 ldr128(const void* p) { uint4 v; asm volatile("ld.relaxed.gpu.global.v4.u32 {%0,%1,%2,%3},[%4];" : "=r"(v.x), "=r"(v.y), "=r"(v.z), "=r"(v.w) : "l"(p) : "memory"); return v; }
DEV uint2 ldr64(const void* p) { uint2 v; asm volatile("ld.relaxed.gpu.global.v2.u32 {%0,%1},[%2];" : "=r"(v.x), "=r"(v.y) : "l"(p) : "memory"); return v; }
DEV u32 ldr32(const void* p) { u32 v; asm volatile("ld.relaxed.gpu.global.u32 %0,[%1];" : "=r"(v) : "l"(p) : "memory"); return v; }
DEV void str128(void* p, u32 x, u32 y, u32 z, u32 w) { asm volatile("st.relaxed.gpu.global.v4.u32 [%0],{%1,%2,%3,%4};" ::"l"(p), "r"(x), "r"(y), "r"(z), "r"(w) : "memory"); }
DEV void str64(void* p, u32 x, u32 y) { asm volatile("st.relaxed.gpu.global.v2.u32 [%0],{%1,%2};" ::"l"(p), "r"(x), "r"(y) : "memory"); }
DEV void str32(void* p, u32 x) { asm volatile("st.relaxed.gpu.global.u32 [%0],%1;" ::"l"(p), "r"(x) : "memory"); }
DEV void str16(void* p, u32 x) { asm volatile("st.relaxed.gpu.global.u16 [%0],%1;" ::"l"(p), "h"((unsigned short)x) : "memory"); }
DEV uint4 ldg128(const void* p) { uint4 v; asm volatile("ld.global.nc.v4.u32 {%0,%1,%2,%3},[%4];" : "=r"(v.x), "=r"(v.y), "=r"(v.z), "=r"(v.w) : "l"(p)); return v; }
DEV uint2 ldg64(const void* p) { uint2 v; asm volatile("ld.global.nc.v2.u32 {%0,%1},[%2];" : "=r"(v.x), "=r"(v.y) : "l"(p)); return v; }
DEV u32 ldg32(const void* p) { u32 v; asm volatile("ld.global.nc.u32 %0,[%1];" : "=r"(v) : "l"(p)); return v; }
DEV u32 ldg16(const void* p) { unsigned short v; asm volatile("ld.global.nc.u16 %0,[%1];" : "=h"(v) : "l"(p)); return v; }
#define bsync(id, n) asm volatile("bar.sync %0,%1;" ::"n"(id), "n"(n) : "memory")
#define barrive(id, n) asm volatile("bar.arrive %0,%1;" ::"n"(id), "n"(n) : "memory")
DEV void mb_init(u32 a) { asm volatile("mbarrier.init.shared.b64 [%0],1;" ::"r"(a) : "memory"); }
DEV void mb_expect(u32 a, u32 bytes) { asm volatile("mbarrier.arrive.expect_tx.shared.b64 _,[%0],%1;" ::"r"(a), "r"(bytes) : "memory"); }
DEV void mb_wait(u32 a, u32 ph = 0) {
  u32 ok; int it = 0;
  do { asm volatile("{.reg .pred p; mbarrier.try_wait.parity.shared.b64 p,[%1],%2; selp.u32 %0,1,0,p;}" : "=r"(ok) : "r"(a), "r"(ph) : "memory"); } while (!ok && ++it < SPIN);
}
template <int N> DEV void bulk_out(void* dst, u32 src) { asm volatile("cp.async.bulk.global.shared::cta.bulk_group [%0],[%1],%2;" ::"l"(dst), "r"(src), "n"(N) : "memory"); }
constexpr u32 WSH = 41472;
DEV void l2_line(const void* p) { asm volatile("prefetch.global.L2 [%0];" ::"l"(p) : "memory"); }
template <int N> DEV void l2_pre(const void* p) { asm volatile("cp.async.bulk.prefetch.L2.global [%0],%1;" ::"l"(p), "n"(N) : "memory"); }
DEV void tma3d(u32 dst, const CUtensorMap* tm, u32 mb, int c0, int c2) {
  asm volatile("cp.async.bulk.tensor.3d.shared::cluster.global.mbarrier::complete_tx::bytes [%0],[%1,{%3,0,%4}],[%2];"
               ::"r"(dst), "l"((uint64_t)tm), "r"(mb), "r"(c0), "r"(c2) : "memory");
}
DEV float blo(u32 w) { return __uint_as_float(w << 16); }
DEV float bhi(u32 w) { return __uint_as_float(w & 0xffff0000u); }
DEV u32 pk_bf(float lo, float hi) { u32 r; asm("cvt.rn.bf16x2.f32 %0,%1,%2;" : "=r"(r) : "f"(hi), "f"(lo)); return r; }
DEV u32 pk_hf(float lo, float hi) { u32 r; asm("cvt.rn.f16x2.f32 %0,%1,%2;" : "=r"(r) : "f"(hi), "f"(lo)); return r; }
DEV float rbf(float x) { return __uint_as_float(pk_bf(0.f, x) & 0xffff0000u); }
DEV u32 bfma(u32 a, u32 b, u32 c) { u32 r; asm("fma.rn.bf16x2 %0,%1,%2,%3;" : "=r"(r) : "r"(a), "r"(b), "r"(c)); return r; }
DEV u32 bmul(u32 a, u32 b) { u32 r; asm("mul.rn.bf16x2 %0,%1,%2;" : "=r"(r) : "r"(a), "r"(b)); return r; }
DEV u32 badd(u32 a, u32 b) { u32 r; asm("add.rn.bf16x2 %0,%1,%2;" : "=r"(r) : "r"(a), "r"(b)); return r; }
DEV u32 hadd(u32 a, u32 b) { u32 r; asm("add.rn.f16x2 %0,%1,%2;" : "=r"(r) : "r"(a), "r"(b)); return r; }
DEV u32 hfma(u32 a, u32 b, u32 c) { u32 r; asm("fma.rn.f16x2 %0,%1,%2,%3;" : "=r"(r) : "r"(a), "r"(b), "r"(c)); return r; }
struct C2 { u32 re, im; };
DEV C2 cm2(C2 a, C2 b) {
  const __half2 ar = *reinterpret_cast<__half2*>(&a.re), ai = *reinterpret_cast<__half2*>(&a.im), br = *reinterpret_cast<__half2*>(&b.re), bi = *reinterpret_cast<__half2*>(&b.im);
  __half2 re = __hfma2(ar, br, __hneg2(__hmul2(ai, bi))), im = __hfma2(ar, bi, __hmul2(ai, br));
  return {*reinterpret_cast<u32*>(&re), *reinterpret_cast<u32*>(&im)};
}
DEV C2 pk2(const float2 (&a)[2]) { return {pk_hf(a[0].x, a[1].x), pk_hf(a[0].y, a[1].y)}; }
DEV C2 pk2c(const float2 (&a)[2]) { return {pk_hf(a[0].x, a[1].x), pk_hf(-a[0].y, -a[1].y)}; }
DEV u32 cpy(u32 x, u32 zr, int alt) {
  u32 r;
  if (alt) asm volatile("xor.b32 %0,%1,%2;" : "=r"(r) : "r"(x), "r"(zr)); else asm volatile("mad.lo.u32 %0,%2,%2,%1;" : "=r"(r) : "r"(x), "r"(zr));
  return r;
}
DEV u32 opq(u32 x) { u32 r; asm volatile("mov.u32 %0,%1;" : "=r"(r) : "r"(x)); return r; }
DEV u32 chan(u32 b, u32 i) { return 16 * (b >> 2) + 2 * (b & 3) + (i & 1) + 4 * (i & 2); }
DEV u32 row16(u32 lane) { const u32 r0 = (lane & 7) + ((lane >> 3) & 1) + 8 * (lane >> 4) - 1; return (r0 ^ ((r0 >> 3) & 3)) * 16; }
DEV u32 clk() { u32 r; asm volatile("mov.u32 %0,%%clock;" : "=r"(r)::"memory"); return r; }
DEV void wait_clk(u32 t, int d) { while ((int)(clk() - t) < d); }
DEV float ex2(float x) { float r; asm("ex2.approx.ftz.f32 %0,%1;" : "=f"(r) : "f"(x)); return r; }
DEV float rcpf(float x) { float r; asm("rcp.approx.ftz.f32 %0,%1;" : "=f"(r) : "f"(x)); return r; }
DEV float2 cmul(float2 a, float2 b) { return make_float2(fmaf(a.x, b.x, -a.y * b.y), fmaf(a.x, b.y, a.y * b.x)); }
DEV float2 csq(float2 a) { return make_float2(fmaf(a.x, a.x, -a.y * a.y), (a.x + a.x) * a.y); }
DEV float2 cexp(float lr2, float th) {
  const float m = ex2(lr2);
  return make_float2(m * __cosf(th), m * __sinf(th));
}
DEV float silu_f(float v) { return v * rcpf(1.f + ex2(-1.4426950408889634f * v)); }
constexpr u32 B2P64 = 0x5F805F80u, B2M64 = 0x1F801F80u, BONE = 0x3F803F80u;
constexpr u32 MODJ = 18 * 128;
DEV float sqrta(float x) { float r; asm("sqrt.approx.ftz.f32 %0,%1;" : "=f"(r) : "f"(x)); return r; }
DEV u32 fu(float x) { return __float_as_uint(x); }
DEV float uf(u32 x) { return __uint_as_float(x); }
DEV void mma_hf_o(float (&d)[4], const float (&c)[4], const u32 (&a)[4], u32 b0, u32 b1) {
  asm("mma.sync.aligned.m16n8k16.row.col.f32.f16.f16.f32 {%0,%1,%2,%3},{%4,%5,%6,%7},{%8,%9},{%10,%11,%12,%13};"
      : "=f"(d[0]), "=f"(d[1]), "=f"(d[2]), "=f"(d[3]) : "r"(a[0]), "r"(a[1]), "r"(a[2]), "r"(a[3]), "r"(b0), "r"(b1), "f"(c[0]), "f"(c[1]), "f"(c[2]), "f"(c[3]));
}

DEV void mma_hf_t(float (&c)[4], const u32 (&a)[4], u32 b0, u32 b1) { mma_hf(c, a[0], a[1], a[2], a[3], b0, b1); }
DEV void cpa16(u32 dst, const void* src) { asm volatile("cp.async.cg.shared.global [%0],[%1],16;" ::"r"(dst), "l"(src) : "memory"); }
DEV void tm_pre(const CUtensorMap* tm) { asm volatile("prefetch.tensormap [%0];" ::"l"((uint64_t)tm) : "memory"); }
#define PROXY_FENCE() asm volatile("fence.proxy.async.shared::cta;" ::: "memory")
struct Prm {
  const char *la, *ai, *cr, *ci, *ldt;
  u32 zero;
  const char *x, *c;
  char* gs;
  const char *dsk, *wr, *wg, *wu, *wd;
  char* out;
};
constexpr float LOG2E = 1.4426950408889634f, F2P64 = 1.8446744073709552e19f, F2M64 = 5.421010862427522e-20f;

template <int S> DEV void y_store(float c0, float c1, float c2, float c3, u32 F, u32 pml, char* yp) {
  str32(yp, bmul(pk_bf(c0, c2), F) | pml);
  str32(yp + S, bmul(pk_bf(c1, c3), F) | pml);
}
DEV void merge4(u32 (&h)[8], uint4 a, uint4 b) {
  const u32 e1 = min(a.x, b.x), e2 = max(a.z, b.z), o1 = min(a.y, b.y), o2 = max(a.w, b.w), o0 = max(a.y, b.y), e3 = min(a.z, b.z);
  const u32 f1 = max(e1, e2), f2 = min(e1, e2), p1 = max(o1, o2), p2 = min(o1, o2);
  h[0] = max(a.x, b.x); h[1] = max(o0, f1); h[2] = min(o0, f1); h[3] = max(p1, f2); h[4] = min(p1, f2); h[5] = max(p2, e3); h[6] = min(p2, e3); h[7] = min(a.w, b.w);
}
DEV void top8(u32 (&a)[8], uint4 l, uint4 m) {
  u32 b[8];
  merge4(b, l, m);
#pragma unroll
  for (int i = 0; i < 8; i++) a[i] = max(a[i], b[7 - i]);
#pragma unroll
  for (int s = 4; s; s >>= 1)
#pragma unroll
    for (int i = 0; i < 8; i++) if (!(i & s)) { const u32 x = a[i], y = a[i + s]; a[i] = max(x, y); a[i + s] = min(x, y); }
}
#define POLL(load, cond_bad, code) { int it_ = 0; do { load; if (++it_ > SPIN) { ERRF(code); break; } } while (__any_sync(~0u, (cond_bad))); }
#define POLLW(load, cond_bad, code) { int it_ = 0; while (__any_sync(~0u, (cond_bad))) { if (++it_ > SPIN) { ERRF(code); break; } load; } TSN(code, it_); }

#define DOWN(E) if (tid == 288 && b < 108) { const u32 c0 = 64 * (b % 9), c2 = 4 * (b / 9); \
    if (!D0C && E == 1) { mb_expect(SM_MB + 24, 49152); tma3d(SM_TAP, tm_down, SM_MB + 24, c0, c2); } \
    if (DE1 == E) tma3d(SM_WD, tm_down, SM_MB + 24, c0, c2 + 1); \
    if (DE2 == E) tma3d(SM_WD + 12288, tm_down, SM_MB + 24, c0, c2 + 2); \
    if (DE3 == E) tma3d(SM_WD + 24576, tm_down, SM_MB + 24, c0, c2 + 3); }
#define OUTR(E) if (((OUTA == E) | (OUTB == E) << 1) & ot) { const u32 tl = 4 * ((lane >> 1) & 1) + ((lane >> 2) & 3) + 8 * (lane & 1); \
    bulk_out<1152>(p.out + (b * BLK + tl * 1152), SM_XST + ((lane & 2) + 4 * (lane & 1) + ((lane >> 2) & 1) + (lane & 8)) * ROW); \
    asm volatile("cp.async.bulk.commit_group;" ::: "memory"); }
DEV void ffn_tail(const Prm& p, const CUtensorMap* tm_down, uint4 (&A)[24], const u32 tid, const u32 b, const u32 par, const u32 ot) {
  const u32 w = tid >> 5, lane = tid & 31, g = lane >> 2, q = lane & 3, kq = w & 3, tg = w >> 2;
  const u32 rho = b & 1, pm = par ? TAGM : 0;
  char* const gs = p.gs;
  __syncthreads();
  TS(25);
  DOWN(5);
  {
    float c0[2][4] = {}, c1[2][4] = {};
    const u32 ba = SM_XS + (lane & 7) * ROW + (18 * kq + (lane >> 3)) * 16;
    uint4 bb[5];
#pragma unroll
    for (int s = 0; s < 5; s++) bb[s] = ldsm4(ba + s * 64);
#pragma unroll
    for (int s = 0; s < 9; s++) mma_bf(c0[s & 1], A[s].x, A[s].y, A[s].z, A[s].w, s & 1 ? bb[s >> 1].z : bb[s >> 1].x, s & 1 ? bb[s >> 1].w : bb[s >> 1].y);
    const u32 ra = SM_RED + (8 * tg + kq) * 512 + lane * 16;
    if (tg < 2) {
#pragma unroll
      for (int s = 0; s < 9; s++) mma_bf(c1[s & 1], A[9 + s].x, A[9 + s].y, A[9 + s].z, A[9 + s].w, s & 1 ? bb[s >> 1].z : bb[s >> 1].x, s & 1 ? bb[s >> 1].w : bb[s >> 1].y);
      sts128(ra + 2048, fu(c1[0][0] + c1[1][0]), fu(c1[0][1] + c1[1][1]), fu(c1[0][2] + c1[1][2]), fu(c1[0][3] + c1[1][3]));
    }
    sts128(ra, fu(c0[0][0] + c0[1][0]), fu(c0[0][1] + c0[1][1]), fu(c0[0][2] + c0[1][2]), fu(c0[0][3] + c0[1][3]));
  }
  TS(39);
  __syncthreads();
  const u32 tr = clk();
  OUTR(6);
  if (w - 3 - rho < 5 - rho) {
    const u32 t = 7 - w;
    float s[4] = {};
#pragma unroll
    for (int i = 0; i < 4; i++) { const uint4 u = lds128(SM_RED + (t * 4 + i) * 512 + lane * 16); s[0] += uf(u.x); s[1] += uf(u.y); s[2] += uf(u.z); s[3] += uf(u.w); }
    const u32 sg = pk_bf(silu_f(rbf(s[0])), silu_f(rbf(s[1])));
    const u32 act = movm(bmul(bmul(sg, pk_bf(s[2], s[3])), B2M64));
    str32(gs + (G_ACT + (t < 4 ? 4 * b + t : 512 + (b >> 1)) * 128 + lane * 4), act | (q ? 0 : pm));
  }
  TS(26);
  if (b < 108) {
    const char* src = gs + (G_ACT + (b / 9) * 6144 + tid * 16);
    uint4 a;
    if (AD) a.x = INVAL; else a = ldr128(src);
    if (AD && w >= 4) wait_clk(tr, AD);
    if (w < 4) {
      const u32 aa = SM_WD + (8 * (lane >> 4) + (lane & 7)) * 128 + (((2 * w + ((lane >> 3) & 1)) ^ (lane & 7)) << 4);
      mb_wait(SM_MB + 24);
#pragma unroll
      for (int s = 0; s < 24; s++) A[s] = ldsm4t(aa + (s < 6 ? SM_TAP - SM_WD : -12288) + s * 2048);
    }
    TS(28);
    POLLW(a = ldr128(src), (a.x ^ pm) & TAGM, 9);
    sts128(SM_AC + tid * 16, a.x & ~TAGM, a.y, a.z, a.w);
    TS(27);
    if (w < 4) {
      bsync(8, 384);
      float c[4][4] = {};
#pragma unroll
      for (int s = 0; s < 12; s++) {
        const uint4 bb = ldsm4(SM_AC + lane * 16 + s * 512);
        mma_bf(c[2 * (s & 1)], A[2 * s].x, A[2 * s].y, A[2 * s].z, A[2 * s].w, bb.x, bb.y);
        mma_bf(c[2 * (s & 1) + 1], A[2 * s + 1].x, A[2 * s + 1].y, A[2 * s + 1].z, A[2 * s + 1].w, bb.z, bb.w);
      }
      char* dst = gs + (G_PART + b * 2048 + w * 512 + lane * 8);
      u32 o[4];
#pragma unroll
      for (int i = 0; i < 4; i++) o[i] = (fu(((c[0][i] + c[1][i]) + (c[2][i] + c[3][i])) * F2P64) & ~1u) | par;
      str64(dst, o[0], o[1]); str64(dst + 256, o[2], o[3]);
      TS(29);
    } else barrive(8, 384);
  }
  OUTR(7);
  if (w == 8 && b < 72) {
    const u32 ta = clk();
    const u32 kg = lds32(SM_SLOT + 4 * g), ro = (2047 - ((kg >> 2) & 2047)) * 1152 + 16 * b;
    const char* src = gs + (G_PART + (b >> 3) * 2048 + (b & 7) * 256 + lane * 8);
    const char* xs = gs + (G_Y + ro);
    uint4 xt;
    POLL(xt = ldr128(xs), (xt.x ^ TAGR) & TAGM, 10);
    const u32 x1w = (q & 2) ? ((q & 1) ? xt.w : xt.z) : ((q & 1) ? xt.y : bmul(xt.x ^ TAGR, B2P64));
    const u32 gw = lds32(SM_MODS + 5760 + 16 * b + 4 * q);
    const u32 hw = lds32(SM_XS + g * ROW + b * 16 + q * 4);
    const float sgm = rcpf(1.f + ex2(-LOG2E * bhi(kg ^ (~((int)kg >> 31) | 0x80000000))));
    char* const dst = p.out + (ro + 4 * q);
    uint2 v[12];
#pragma unroll
    for (int j = 0; j < 12; j++) v[j] = make_uint2(1, 0);
    u32 bad;
    if (PD) wait_clk(ta, PD);
    POLL({ bad = 0; _Pragma("unroll") for (int j = 0; j < 12; j++) { if (((v[j].x ^ par) | (v[j].y ^ par)) & 1) v[j] = ldr64(src + j * 9 * 2048); }
           _Pragma("unroll") for (int j = 0; j < 12; j++) bad |= (v[j].x ^ par) | (v[j].y ^ par); }, bad & 1, 11);
    float s0[4] = {}, s1[4] = {};
#pragma unroll
    for (int j = 0; j < 12; j++) { s0[j & 3] += uf(v[j].x); s1[j & 3] += uf(v[j].y); }
    const u32 y = movm(pk_bf((s0[0] + s0[1]) + (s0[2] + s0[3]), (s1[0] + s1[1]) + (s1[2] + s1[3])));
    *(u32*)dst = badd(x1w, bmul(gw, badd(hw, bmul(y, pk_bf(sgm, sgm)))));
    if (b == 0 && lane == 0) str32(gs + G_EP, par);
    TS(30); TSE();
  }
  if (w == 10) asm volatile("cp.async.bulk.wait_group.read 0;" ::: "memory");
}

DEV u32 y_off(u32 tid, u32 b) { return G_Y + (16 * (tid >> 5) + 8 * ((tid >> 1) & 1) + ((tid >> 2) & 4)) * BLK + b * 128 + ((tid >> 2) & 3) * 32 + (tid & 1) * 16; }
DEV void post_conv(const Prm& p, const CUtensorMap* tm_down, const u32 tid, const u32 b, uint4 (&yv)[4]) {
  const u32 w = tid >> 5, lane = tid & 31;
  const u32 g = lane >> 2, q = lane & 3, e = g >> 2, h = (g >> 1) & 1, hi = g & 1;
  const u32 pm = lds32(SM_THR + 4), par = pm >> 30;
  char* const gs = p.gs;
  const u32 cho = 128 * w + 64 * e + 16 * q;
  u32 x1[4][4], h2[4][4], key[4], lt;
  char* const rowp = gs + (b * BLK + (4 * h + 8 * hi) * 1152 + cho);
  u32 ot = 0;
  uint4 A[24];
#define AROW(t) const u32 arow = 144 * ((t >> 5) & 3) + ((t >> 1) & 8) + (t & 7), ab = (t & 8) ? SM_UP : SM_GATE;
#define AFRAG9() { _Pragma("unroll") for (int s = 0; s < 9; s++) A[s] = ldsm4t(ab + SLV + arow * 16 + s * 256); }
  if (w < 9) {
    const u32 yc = 8 * (q >> 1) + 2 * (g >> 1), y1 = w < 8 ? BLK : 4 * BLK, y2 = 2 * y1;
    const char* ysrc = gs + (w < 8 ? y_off(tid, b) : G_Y + (q & 1) * 16 + (8 * yc + 2 * hi + ((b >> 4) & 1)) * BLK + 16384 + ((b >> 5) * 16 + (b & 15)) * 32);
    const char* const ys[4] = {ysrc, ysrc + y1, ysrc + y2, ysrc + (y1 + y2)};
    u32 tc = clk();
    if (w < 4 ? b - YA < YL - YA : w < 8 && b < YB) {
#pragma unroll
      for (int v = 0; v < 4; v++) yv[v] = ldr128(ys[v]);
    }
    const u32 ma = SM_MODS + cho, xa = SM_XST + (2 * h + 4 * hi) * ROW + cho;
    const uint4 sa = lds128(ma), ca = lds128(ma + 1152), ga = lds128(ma + 2304);
    const uint4 rb = lds128((g & 2) ? SM_ONE + 16 * hi : (ma ^ 64) + 8064 + 1152 * hi);
    const u32 saw[4] = {sa.x, sa.y, sa.z, sa.w}, caw[4] = {ca.x, ca.y, ca.z, ca.w}, gaw[4] = {ga.x, ga.y, ga.z, ga.w};
#pragma unroll
    for (int k = 0; k < 4; k++) {
      const uint2 st = lds64(SM_ST + 16 * (2 * h + 4 * hi + (k & 1) + 8 * (k >> 1)));
      const uint4 xv = lds128(xa + ((k & 1) + 8 * (k >> 1)) * ROW);
      x1[k][0] = xv.x; x1[k][1] = xv.y; x1[k][2] = xv.z; x1[k][3] = xv.w;
#pragma unroll
      for (int v = 0; v < 4; v++) x1[k][v] = badd(x1[k][v], bfma(bmul(badd(x1[k][v], st.x), st.y), caw[v], saw[v]));
    }
    const bool own = (q >> 1) == e;
    const u32 spw = SM_SP + (2 * w + e) * 320 + (g & 3) * 16 + (own ? ((q & 1) == h ? 4 : 12) : 8 - 8 * (q & 1));
    TS(18);
    if (w >= 4) { if (b < YE) barrive(12, 320); else bsync(12, 320); tc = clk(); }
    if (b >= YL) wait_clk(tc, YD);
    if (w == 8) { bsync(7, 160); if (b < YE) wait_clk(clk(), YD8); }
    TS(13);
    POLLW(_Pragma("unroll") for (int v = 0; v < 4; v++) if ((yv[v].x ^ pm) & TAGM) yv[v] = ldr128(ys[v]),
          ((yv[0].x ^ pm) | (yv[1].x ^ pm) | (yv[2].x ^ pm) | (yv[3].x ^ pm)) & TAGM, 5);
    TS(19);
    if (DECL && w < 4) asm volatile("setmaxnreg.dec.sync.aligned.u32 168;");
#pragma unroll
    for (int k = 0; k < 4; k += 2) {
      float X[4] = {}, Y[4] = {}, R[4] = {};
#pragma unroll
      for (int v = 0; v < 4; v++) {
        const u32 y0 = k ? yv[v].z : yv[v].x & ~TAGM, y1 = k ? yv[v].w : yv[v].y;
        x1[k][v] = bfma(movm(y0), gaw[v], x1[k][v]);
        x1[k + 1][v] = bfma(movm(y1), gaw[v], x1[k + 1][v]);
        mma8_bf(X, x1[k][v], x1[k + 1][v], x1[k][v]); mma8_bf(Y, x1[k][v], x1[k + 1][v], x1[k + 1][v]);
        if (v & 1) mma_bf(R, x1[k][v - 1], x1[k + 1][v - 1], x1[k][v], x1[k + 1][v], v & 2 ? rb.z : rb.x, v & 2 ? rb.w : rb.y);
      }
      sts32(spw + k * 64, fu(own ? (hi ? X[1] : X[0]) : R[0] + R[1]));
      sts32(spw + k * 64 + 64, fu(own ? (hi ? Y[3] : Y[2]) : R[2] + R[3]));
    }
    barrive(1, 320);
    TS(36);
    const uint4 sb = lds128(ma + 3456), cb = lds128(ma + 4608), gb = lds128(ma + 5760);
    const u32 sbw[4] = {sb.x, sb.y, sb.z, sb.w}, cbw[4] = {cb.x, cb.y, cb.z, cb.w}, gbw[4] = {gb.x, gb.y, gb.z, gb.w};
    bsync(2, 320);
    TS(37);
    lt = lds32(SM_THR);
#pragma unroll
    for (int k = 0; k < 4; k++) {
      const uint4 st = lds128(SM_ST2 + 64 * k + 16 * (g & 3));
      key[k] = st.w;
      u32 o[4];
#pragma unroll
      for (int v = 0; v < 4; v++) {
        const u32 d = badd(x1[k][v], st.x), z = bfma(d, st.y, bmul(d, st.z));
        h2[k][v] = FH ? bfma(z, cbw[v], sbw[v]) : badd(bmul(z, cbw[v]), sbw[v]);
        o[v] = FO ? bfma(gbw[v], h2[k][v], x1[k][v]) : badd(x1[k][v], bmul(gbw[v], h2[k][v]));
      }
      h2[k][0] = bmul(h2[k][0], B2M64) | TAGR;
      if (key[k] >= lt) str128(rowp + k * 1152, h2[k][0], h2[k][1], h2[k][2], h2[k][3]);
      sts128(xa + ((k & 1) + 8 * (k >> 1)) * ROW, o[0], o[1], o[2], o[3]);
    }
    barrive(3, 320);
    TS(21);
    asm volatile("setmaxnreg.inc.sync.aligned.u32 168;");
    mb_wait(SM_MB + 8); mb_wait(SM_MB + 16);
    const u32 t3 = tid ^ p.zero;
    AROW(t3);
    if (t3 < 256) {
      const u32 aa = ab + arow * 64 + ((((t3 >> 6) & 2) ^ ((t3 & 7) >> 1)) << 4);
#pragma unroll
      for (int s = 0; s < 9; s++) { A[s] = ldsm4t(aa + s * 1024); A[9 + s] = ldsm4t((aa ^ 16) + s * 1024); }
    } else AFRAG9();
    TS(22);
    bsync(6, 352);
    TS(24);
    const u32 g8 = lds32(SM_SLOT + 28);
    const u32 sk = lds32(SM_SLOT + 4 * (w & 7));
    const char* rs_ = gs + (((~sk >> 2) & 2047) * 1152 + lane * 16);
    uint4 rv[3];
    rv[0].x = rv[1].x = rv[2].x = TAGR;
    if (w < 8) { rv[0] = ldr128(rs_); rv[1] = ldr128(rs_ + 512); if (lane < 8) rv[2] = ldr128(rs_ + 1024); barrive(15, 320); }
    if (__any_sync(~0u, max(max(key[0], key[1]), max(key[2], key[3])) >= g8)) {
#pragma unroll
      for (int k = 0; k < 4; k++) if (key[k] >= g8) {
        if (key[k] < lt) str128(rowp + k * 1152, h2[k][0], h2[k][1], h2[k][2], h2[k][3]);
        str128(rowp + (G_Y + k * 1152), bmul(x1[k][0], B2M64) | TAGR, x1[k][1], x1[k][2], x1[k][3]);
      }
    }
    if (w < 8) {
      bsync(5, 320);
      const u32 sf = lds32(SM_SLOT + 4 * w);
      if (sf != sk) { rs_ = gs + (((~sf >> 2) & 2047) * 1152 + lane * 16); rv[0].x = INVAL; }
    }
    POLLW({ rv[0] = ldr128(rs_); rv[1] = ldr128(rs_ + 512); if (lane < 8) rv[2] = ldr128(rs_ + 1024); },
          ((rv[0].x ^ TAGR) | (rv[1].x ^ TAGR) | (rv[2].x ^ TAGR)) & TAGM, 8);
    TS(38);
#pragma unroll
    for (int j = 0; j < 3; j++) if (w < 8 && (j < 2 || lane < 8)) sts128(SM_XS + w * ROW + lane * 16 + j * 512, bmul(rv[j].x ^ TAGR, B2P64), rv[j].y, rv[j].z, rv[j].w);
  } else {
    u32 ok, lr;
    if (w == 10) {
      uint2 rc = lds64(SM_RC + 8 * min(lane, 17u));
      float r1 = lane < 18 ? uf(rc.x) : 0.f, r2 = lane < 18 ? uf(rc.y) : 0.f;
#pragma unroll 1
      for (int o = 16; o; o >>= 1) { r1 += __shfl_xor_sync(~0u, r1, o); r2 += __shfl_xor_sync(~0u, r2, o); }
      const u32 tl = 4 * ((lane >> 1) & 1) + ((lane >> 2) & 3) + 8 * (lane & 1), kl = (2047 - 16 * b - tl) << 2 | par * 3;
      char* const kp = gs + (G_KEY + b * KST);
      const u32 spr = SM_SP + (lane >> 4) * 9 * 320 + (lane & 15) * 16;
      TS(31);
      bsync(1, 320);
      float S1 = 0.f, S2 = 0.f, S3 = 0.f;
#pragma unroll
      for (int i = 0; i < 9; i++) { uint4 t = lds128(spr + i * 320); S1 += uf(t.x); S2 += uf(t.y); S3 += uf(t.z); }
      S1 += __shfl_xor_sync(~0u, S1, 16); S2 += __shfl_xor_sync(~0u, S2, 16); S3 += __shfl_xor_sync(~0u, S3, 16);
      const float mu = S1 * (1.f / 576.f), var = fmaxf(fmaf(-mu, mu, S2 * (1.f / 576.f)), 0.f);
      const float m = rbf(mu), rs = rcpf(rbf(sqrta(rbf(rbf(var) + 1e-5f))));
      const u32 rb = pk_bf(0.f, fmaf(fmaf(-m, r1, S3), rs, r2) + 0.f);
      ok = ((rb ^ (((int)rb >> 31) | 0x80000000)) & 0xffff0000u) | kl;
      const float rh = rbf(rs);
      sts32(SM_KEY + 4 * (lane & 15), ok);
      sts128(SM_ST2 + 16 * (lane & 15), pk_bf(-m, -m), pk_bf(rh, rh), pk_bf(rs - rh, rs - rh), ok);
      __syncwarp();
      const uint4 o0 = lds128(SM_KEY + 2 * (lane & 16)), o1 = lds128(SM_KEY + 2 * (lane & 16) + 16);
      lr = (o0.x > ok) + (o0.y > ok) + (o0.z > ok) + (o0.w > ok) + (o1.x > ok) + (o1.y > ok) + (o1.z > ok) + (o1.w > ok);
      lr += __shfl_xor_sync(~0u, lr, 16);
      if (lane < 16 && lr < 8) str32(kp + 4 * lr, ok);
      if (lr == (b < NB8 ? 7 : NEARLY - 1)) sts32(SM_THR, ok);
      barrive(2, 320);
      barrive(4, 64);
      TS(20);
    } else if (w == 9) {
      bsync(12, 320);
      wait_clk(clk(), DD);
      PROXY_FENCE();
      DOWN(1);
    }
    asm volatile("setmaxnreg.inc.sync.aligned.u32 168;");
    mb_wait(SM_MB + 8); mb_wait(SM_MB + 16);
    AROW(tid);
    AFRAG9();
    TS(22);
    if (w == 10) {
      bsync(3, 320);
      PROXY_FENCE();
      ot = lane < 16 && lr >= 8;
      OUTR(2);
      bsync(6, 352);
      bsync(15, 320);
      bsync(5, 320);
      if (lane < 16 && lr < 8 && ok < lds32(SM_SLOT + 28)) ot = 2;
      OUTR(4);
    } else if (w == 9) {
      bsync(15, 320);
      DOWN(4);
      TS(13);
    } else {
      const char* ks = gs + (G_KEY + (lane >> 1) * KST + (lane & 1) * 16);
      const u32 kt = par * 3;
      uint4 L[8];
#define KBAD(j) ((L[j].x ^ kt) & 3)
#define KLD(j) L[j] = ldr128(ks + j * 16 * KST)
      bsync(4, 64);
      if (KD) wait_clk(clk(), b < YL ? KD : KD1);
      u32 H[8];
#pragma unroll
      for (int j = 0; j < 8; j++) L[j].x = INVAL;
      POLL({ _Pragma("unroll") for (int j = 0; j < 8; j++) if (KBAD(j)) KLD(j);
             merge4(H, L[0], L[1]); top8(H, L[2], L[3]); top8(H, L[4], L[5]); }, KBAD(0) | KBAD(1) | KBAD(2) | KBAD(3) | KBAD(4) | KBAD(5), 6);
      if (KBAD(6)) KLD(6);
      if (KBAD(7)) KLD(7);
#pragma unroll 1
      for (int pass = 0;; pass++) {
        u32 G[8], m;
#pragma unroll
        for (int i = 0; i < 8; i++) G[i] = H[i];
#pragma unroll
        for (int r = 0; r < 8; r++) {
          const u32 h0 = G[0];
          m = __reduce_max_sync(~0u, h0);
          sts32(SM_SLOT + 4 * r, m);
          if (r < 7) asm("{.reg .u32 t; sub.u32 t,%1,%2; min.u32 t,t,1; mad.lo.u32 %0,t,%3,%4;}" : "=r"(G[0]) : "r"(m), "r"(h0), "r"(h0 - G[1]), "r"(G[1]));
#pragma unroll
          for (int i = 1; i < 7 - r; i++) G[i] = h0 == m ? G[i + 1] : G[i];
        }
        if (pass) break;
        barrive(6, 352);
        TS(23);
        POLLW({ if (KBAD(6)) KLD(6); if (KBAD(7)) KLD(7); }, KBAD(6) | KBAD(7), 7);
        if (!__any_sync(~0u, max(L[6].x, L[7].x) > m)) break;
        top8(H, L[6], L[7]);
      }
      barrive(5, 320);
      TS(33);
    }
  }
  ffn_tail(p, tm_down, A, tid | p.zero, b, par, ot);
}

__global__ void __launch_bounds__(384, 1)
fused_kernel(const Prm p, const __grid_constant__ CUtensorMap tm_mod, const __grid_constant__ CUtensorMap tm_gate, const __grid_constant__ CUtensorMap tm_gs,
             const __grid_constant__ CUtensorMap tm_up, const __grid_constant__ CUtensorMap tm_us, const __grid_constant__ CUtensorMap tm_down) {
  extern __shared__ __align__(1024) unsigned char smem[];
  u32 la, ai, ldt; uint2 cr, ci;
  {
    const u32 t = threadIdx.x, d = t < 256 ? chan(blockIdx.x, t >> 5) : 512 + (blockIdx.x >> 1), o = d * 256 + 8 * (t & 31), o4 = o + ((t < 256 ? t >> 5 : t >> 3) & 4);
    asm volatile("{.reg .pred p; .reg .u16 h; setp.ne.u32 p,%7,0; @p ld.global.nc.u32 %0,[%8]; @p ld.global.nc.u32 %1,[%9]; @p ld.global.nc.v2.u32 {%2,%3},[%10];"
                 "@p ld.global.nc.v2.u32 {%4,%5},[%11]; @p ld.global.nc.u16 h,[%12]; cvt.u32.u16 %6,h;}"
                 : "=r"(la), "=r"(ai), "=r"(cr.x), "=r"(cr.y), "=r"(ci.x), "=r"(ci.y), "=r"(ldt)
                 : "r"(0x6ffu >> (t >> 5) & 1), "l"(p.la + o4), "l"(p.ai + o4), "l"(p.cr + o), "l"(p.ci + o), "l"(p.ldt + 2 * d));
  }
  const u32 t0 = clk();
  const u32 tid = __shfl_sync(~0u, threadIdx.x, threadIdx.x & 31), b = blockIdx.x + p.zero;
  const u32 w = tid >> 5, lane = tid & 31;
  const u32 g = lane >> 2, q = lane & 3, hi = g & 1;
  const u32 rho = b & 1, Ps = 512 + (b >> 1);
  char* const gs = p.gs;
  TS0();
  const bool kw = w != 8 && w != 11;
  const u32 ksig = w < 8 ? (w & 3) : 4, khf = w < 8 ? (w >> 2) : (w & 1);
  if (!kw) {
    if (tid == 352) {
#pragma unroll
      for (int i = 0; i < 4; i++) mb_init(SM_MB + 8 * i);
      asm volatile("fence.mbarrier_init.release.cluster;" ::: "memory");
      tm_pre(&tm_mod);
    }
    const char* cp = p.c + (576 * (w & 1) + 24 * min(lane, 23u));
    const uint2 c0 = ldg64(cp);
    la = c0.x; ai = c0.y; cr = ldg64(cp + 8); ci = ldg64(cp + 16);
  }
  const u32 zr = tid >> 16;
  const u32 epv = ldr32(gs + (G_EP + zr));
  const u32 tp = SM_TAP + ksig * TAPS;
  if (kw && !khf) {
#pragma unroll 1
    for (u32 i = lane * 16; i < TAPS; i += 512) sts128(tp + i, 0, 0, 0, 0);
  }
  if (tid < 128) sts128(SM_INV + 16 * tid, INVAL, 0, 1, 0);
  if (tid >= 252) str128(gs + (tid >= 380 ? G_MOD + b * 128 + q * 16 : b * BLK + 16384 - 252 * 16 + tid * 16), INVAL, 0, 1, 0);
  if (tid == 352 && b < 36) { while (clk() - t0 < DMOD); mb_expect(SM_MB, 36864); tma3d(SM_UP, &tm_mod, SM_MB, 32 * b, 0); }
  if (w < 9) {
    while ((int)(clk() - t0) < DX);
    const char* xp = p.x + (b * BLK + (lane >> 3) * 1152 + 128 * w + 16 * (lane & 7));
    const u32 xd = SM_XST + (((lane >> 3) & 1) + 8 * (lane >> 4)) * ROW + 128 * w + 16 * (lane & 7);
#pragma unroll
    for (int i = 0; i < 4; i++) cpa16(xd + 2 * ROW * i, xp + 4608 * i);
  }
  const u32 ktab = w < 8 ? SM_MODS + w * KTAB : SM_ZS + (w - 9) * KTAB;
  float k2048 = 0.f;
  if (kw) {
    u32 mx = __vmaxu2(__vmaxu2(cr.x & 0x7fff7fff, cr.y & 0x7fff7fff), __vmaxu2(ci.x & 0x7fff7fff, ci.y & 0x7fff7fff));
    const u32 E = max(__reduce_max_sync(~0u, max(mx & 0xffff, mx >> 16)) >> 7, 8u);
    TS(1);
    const float dt = rbf(ex2(blo(ldt) * LOG2E)), csc = uf((257 - E) << 23 | (fu(dt) & 0x7fffff));
    sts32(SM_SC + 16 * ksig + 12, fu(uf(fu(dt) & 0x7f800000) * uf((E - 2) << 23)));
    const u32 crw = khf ? cr.y : cr.x, ciw = khf ? ci.y : ci.x;
    float2 C[2], w4[2], w8[2], w16[2], w32[2], w64[2], w128[2], w256[2], w512[2], a1[2], a2[2], a3[2], t0[2], t1[2], s3[2];
#pragma unroll
    for (int m = 0; m < 2; m++) {
      const float lr2 = rbf(ex2((m ? bhi(la) : blo(la)) * LOG2E)) * dt * -LOG2E, th = (m ? bhi(ai) : blo(ai)) * dt;
      C[m] = make_float2((m ? bhi(crw) : blo(crw)) * csc, (m ? bhi(ciw) : blo(ciw)) * csc);
      const float2 w1 = cexp(lr2, th), w2 = csq(w1);
      w64[m] = cexp(64.f * lr2, 64.f * th);
      w4[m] = csq(w2); w8[m] = csq(w4[m]); w16[m] = csq(w8[m]); w32[m] = csq(w16[m]);
      w128[m] = csq(w64[m]); w256[m] = csq(w128[m]); w512[m] = csq(w256[m]);
      const float2 w1024 = csq(w512[m]);
      a1[m] = cmul(C[m], w1); a2[m] = cmul(C[m], w2); a3[m] = cmul(a1[m], w2);
      t0[m] = cmul(C[m], w1024); t1[m] = cmul(t0[m], w128[m]); s3[m] = cmul(w8[m], w16[m]);
      k2048 += fmaf(t0[m].x, w1024.x, -t0[m].y * w1024.y);
    }
    C2 B0[8], B1[8], B2[8], S[8];
    B0[0] = pk2(C); B0[1] = pk2(a1); B0[2] = pk2(a2); B0[3] = pk2(a3);
    const C2 h4 = pk2(w4), h256 = pk2(w256), h512 = pk2(w512);
#pragma unroll
    for (int i = 0; i < 4; i++) B0[4 + i] = cm2(B0[i], h4);
#pragma unroll
    for (int i = 0; i < 4; i++) B1[i] = cm2(B0[2 * i], h256);
    B1[4] = cm2(B0[0], h512); B1[5] = cm2(B0[4], h512);
    B1[6] = cm2(B1[4], h256); B1[7] = cm2(B1[5], h256);
    const u32 ta = ktab + lane * 128, f = ((lane & 3) << 5) | ((lane & 4) << 2);
#pragma unroll
    for (int i = 0; i < 8; i++) sts128(ta + ((i << 4) ^ f), B0[i].re, B0[i].im, B1[i].re, B1[i].im);
    B2[0] = pk2(t0); B2[1] = pk2(t1);
    B2[2] = cm2(B2[0], h256); B2[3] = cm2(B2[1], h256);
#pragma unroll
    for (int i = 0; i < 4; i++) B2[4 + i] = cm2(B2[i], h512);
    S[0] = {0x3C003C00u, 0u}; S[1] = pk2c(w8); S[2] = pk2c(w16); S[3] = pk2c(s3); S[4] = pk2c(w32);
#pragma unroll
    for (int i = 1; i < 4; i++) S[4 + i] = cm2(S[i], S[4]);
#pragma unroll
    for (int i = 0; i < 8; i++) sts128(ta + 4096 + ((i << 4) ^ f), B2[i].re, B2[i].im, S[i].re, S[i].im);
    const C2 m64 = pk2c(w64), m128 = pk2c(w128);
    sts128(ktab + 8192 + lane * 16, m64.re, m64.im, m128.re, m128.im);
    __syncwarp();
  } else {
    u32 sa = SM_SIL + 576 * (w & 1) + 24 * min(lane, 23u);
#pragma unroll 1
    for (int j = 0; j < 6; j++) {
      sts32(sa, pk_bf(silu_f(blo(la)), silu_f(bhi(la))));
      la = ai; ai = cr.x; cr.x = cr.y; cr.y = ci.x; ci.x = ci.y; sa += 4;
    }
    bsync(7, 64);
  }
  TS(2);
  const u32 pm = (__reduce_or_sync(~0u, epv) & 1) ? 0 : TAGM;
  sts32(SM_THR + 4, pm);
  if (w < 9) {
    asm volatile("cp.async.wait_all;" ::: "memory");
    __syncwarp();
    TS(4);
    if (tid == 256 && b >= 36 && b < 108) { mb_expect(SM_MB, 36864); tma3d(SM_UP, &tm_mod, SM_MB, 32 * b, 0); }
    const u32 xa = SM_XST + (lane & 15) * ROW + 128 * w + 16 * (lane >> 4);
    float s[4] = {}, X[2][4] = {}, Y[2][4] = {};
#pragma unroll
    for (int j = 0; j < 4; j++) {
      const uint4 a = ldsm4(xa + 32 * j);
      mma8_bf(X[0], a.x, a.y, a.x); mma8_bf(Y[0], a.x, a.y, a.y);
      mma8_bf(X[1], a.z, a.w, a.z); mma8_bf(Y[1], a.z, a.w, a.w);
      mma_bf(s, a.x, a.y, a.z, a.w, BONE, BONE);
    }
    uint4 t[4];
#pragma unroll
    for (int j = 0; j < 4; j++) t[j] = ldsm4t(xa + 32 * j);
    const float u0 = hi ? X[0][1] + X[1][1] : X[0][0] + X[1][0], u1 = hi ? Y[0][3] + Y[1][3] : Y[0][2] + Y[1][2];
    if (q == g >> 1) sts128(SM_SP + w * 128 + g * 16, fu(s[0]), fu(u0), fu(s[2]), fu(u1));
    bsync(1, 288);
    TS(7);
    const u32 spr = SM_SP + (lane & 7) * 16 + (lane & 8);
    const uint2 t8 = lds64(spr + 1024);
    const float f8 = lane < 16 ? 1.f : 0.f;
    float S1 = uf(t8.x) * f8, S2 = uf(t8.y) * f8;
#pragma unroll
    for (int i = 0; i < 4; i++) { const uint2 u = lds64(spr + (lane & 16) * 32 + i * 128); S1 += uf(u.x); S2 += uf(u.y); }
    S1 += __shfl_xor_sync(~0u, S1, 16); S2 += __shfl_xor_sync(~0u, S2, 16);
    const float mu = S1 * (1.f / 576.f), var = fmaxf(fmaf(-mu, mu, S2 * (1.f / 576.f)), 0.f);
    const float m = rbf(mu), rs = rcpf(rbf(sqrta(rbf(rbf(var) + 1e-5f))));
    const float ra = rs * 0.0625f;
    sts64(SM_AF + w * 128 + (lane & 15) * 8, fu(ra), fu(-m * ra));
    __syncwarp();
    TS(55);
    const uint4 f0 = lds128(SM_AF + w * 128 + q * 16), f1 = lds128(SM_AF + w * 128 + 64 + q * 16);
    const u32 zdst = SM_GATE + w * 2048 + (g >> 1) * 128 + (lane & 15) * 8;
    const u32 pz = (q & 1) ? 0 : pm;
#pragma unroll
    for (int j = 0; j < 8; j++) {
      const u32 x0 = j & 1 ? t[j >> 1].z : t[j >> 1].x, x1 = j & 1 ? t[j >> 1].w : t[j >> 1].y;
      sts64((j & 1 ? zdst ^ 64 : zdst) + 512 * (j >> 1), pk_hf(fmaf(blo(x0), uf(f0.x), uf(f0.y)), fmaf(bhi(x0), uf(f0.z), uf(f0.w))) | pz,
            pk_hf(fmaf(blo(x1), uf(f1.x), uf(f1.y)), fmaf(bhi(x1), uf(f1.z), uf(f1.w))));
    }
    TS(53);
    if (w < 8) barrive(15, 288);
    else {
      bsync(15, 288);
      TS(54);
      if (lane == 0) {
        PROXY_FENCE();
        bulk_out<BLK>(gs + b * BLK, SM_GATE);
        asm volatile("cp.async.bulk.commit_group;" ::: "memory");
        if (PFG & 1) l2_pre<WSH / 2>(p.wg + b * WSH);
      }
      const float rh = rbf(rs);
      sts128(SM_ST + 16 * (lane & 15), pk_bf(-m, -m), pk_bf(rh, rh), pk_bf(rs - rh, rs - rh), 0);
    }
    TS(5);
  }
  if (kw) {
    float D[5][4] = {};
    u32 ta = ktab + q * 128 + ((g ^ (q << 1)) << 4), tm = ktab + 8192 + q * 16;
#pragma unroll 2
    for (int s = 0; s < 8; s++) {
      const uint4 ca = lds128(ta), cb = lds128(ta + 4096), ma = lds128(tm);
      ta = (ta + 512) ^ 16; tm += 64;
      k2048 += __shfl_xor_sync(~0u, k2048, 16 >> s);
      const C2 s0 = {cb.z, cb.w}, s1 = cm2(s0, {ma.x, ma.y}), s2 = cm2(s0, {ma.z, ma.w}), s3 = cm2(s1, {ma.z, ma.w});
      mma_hf(D[0], s0.re, s1.re, s0.im, s1.im, ca.x, ca.y);
      mma_hf(D[2], s0.re, s1.re, s0.im, s1.im, ca.z, ca.w);
      mma_hf(D[4], s0.re, s1.re, s0.im, s1.im, cb.x, cb.y);
      mma_hf(D[1], s2.re, s3.re, s2.im, s3.im, ca.x, ca.y);
      mma_hf(D[3], s2.re, s3.re, s2.im, s3.im, ca.z, ca.w);
    }
    TS(3);
    const u32 xa = (w < 8 ? SM_MODS + (4 + ksig) * KTAB : SM_ZS) + lane * 16;
    if (khf) {
      __syncwarp();
#pragma unroll
      for (int j = 0; j < 5; j++) sts128(xa + 512 * j, fu(D[j][0]), fu(D[j][1]), fu(D[j][2]), fu(D[j][3]));
      if (lane == 0) sts32(xa + 2560, fu(k2048));
      asm volatile("bar.arrive %0,64;" ::"r"(2 + ksig) : "memory");
    } else {
      const u32 t1 = tp + (q < 2 ? (128 + 4 * g + 2 * q) * 4 : T3 * 4 + ((32 * q - 64 + g) ^ 1) * 2);
      const u32 x = 16 * q + (g >> 1) + hi + 1, tb = tp + (hi ? T7E : T9E) * 4 - 4;
      const u32 te = tb + (x + 2 * (x & 1)) * 2, to = tb + TEO * 4 + (x ^ 1) * 2;
      asm volatile("bar.sync %0,64;" ::"r"(2 + ksig) : "memory");
#pragma unroll
      for (int j = 0; j < 5; j++) { const uint4 t = lds128(xa + 512 * j); D[j][0] += uf(t.x); D[j][1] += uf(t.y); D[j][2] += uf(t.z); D[j][3] += uf(t.w); }
      k2048 = (k2048 + uf(lds32(xa + 2560))) * 0.125f;
#pragma unroll
      for (int r = 0; r < 4; r++) {
        const u32 v = pk_hf(D[2 + (r >> 1)][2 * (r & 1)], D[2 + (r >> 1)][2 * (r & 1) + 1]);
        if (q < 2) {
          const u32 vv = __byte_perm(v, v, 0x1010);
          sts32(t1 + (TO + 32 * r) * 4, vv); sts16(t1 + (TO + 32 * r + 1) * 4 + 2, v >> 16); sts16(t1 + (TO + 32 * r - 1) * 4, v);
          sts64(t1 + (TE + 32 * r) * 4, vv, __byte_perm(v, v, 0x1032));
        } else {
          sts16(t1 + 16 * r, v >> 16);
          if (r == 0 && lane == 2) {
            const u32 vv = __byte_perm(v, v, 0x1010);
            sts32(tp + (TO + 256) * 4, vv); sts16(tp + (TO + 257) * 4 + 2, v); sts16(tp + (TO + 255) * 4, v); sts64(tp + (TE + 256) * 4, vv, vv);
          } else sts16(t1 + 16 * r - ((T3 - T5) * 4 + 6) + 8 * hi, v);
        }
      }
#pragma unroll
      for (int r = 0; r < 2; r++) {
        const u32 v = pk_hf(D[4][2 * r], D[4][2 * r + 1]);
        if (r == 0 && lane == 0) { sts16(tp + T5 * 4 + 62 * 2, v); sts32(SM_KV + 4 * ksig, v & 0xffff); sts16(tp + (T9E + TEO) * 4 + 62 * 2, pk_hf(k2048, 0.f)); }
        else { sts16(te + 8 * r, v); sts16(to + 8 * r, v); }
        sts16(te + 8 * r + 16, v >> 16); sts16(to + 8 * r + 16, v >> 16);
      }
      __syncwarp();
#pragma unroll
      for (int r = 0; r < 4; r++) {
        const u32 v = pk_hf(D[r >> 1][2 * (r & 1) + 1], D[r >> 1][2 * (r & 1)]), t2 = tp + lane * 4 + 128 * r;
        sts32(t2 + TO * 4, v); sts16(t2 + TE * 4, v >> 16); sts16(t2 + (TE + 1) * 4 + 2, v);
      }
      __syncwarp();
    }
  } else if (w == 11 && b < 108) {
    float c[4][4] = {};
    u32 aa = SM_UP + ((lane & 7) + 8 * (lane >> 4)) * 64 + ((((lane >> 3) & 1) ^ ((lane & 7) >> 1)) << 4);
    u32 ba = SM_SIL + (lane >> 3) * 16;
    uint4 a[2][10];
#define GLD(n) { _Pragma("unroll") for (int i = 0; i < 2; i++) { a[n][5 * i] = ldsm4(ba + i * 64); \
      _Pragma("unroll") for (int k = 0; k < 4; k++) a[n][5 * i + 1 + k] = ldsm4t((k & 2 ? aa ^ 32 : aa) + i * 2048 + (k & 1) * 1024); } aa += 4096; ba += 128; }
#define GMM(n) { _Pragma("unroll") for (int i = 0; i < 2; i++) _Pragma("unroll") for (int k = 0; k < 4; k++) { const uint4 f = a[n][5 * i + 1 + k], bb = a[n][5 * i]; \
      mma_bf(c[k], f.x, f.y, f.z, f.w, k & 1 ? bb.z : bb.x, k & 1 ? bb.w : bb.y); } }
    mb_wait(SM_MB);
    TS(56);
    GLD(0);
#pragma unroll 1
    for (int s = 0; s < 4; s++) { GLD(1); GMM(0); GLD(0); GMM(1); }
    GMM(0);
    const float v0 = (q & 1) ? c[0][2] + c[1][2] : c[0][0] + c[1][0], v1 = (q & 1) ? c[2][2] + c[3][2] : c[2][0] + c[3][0];
    str16(gs + (G_MOD + b * 128 + 2 * g + 16 * q), pk_bf(rbf((q & 2) ? v1 : v0) * F2M64, 0.f) | (g < 2 ? pm : 0));
    TS(57);
  }
  TS(6);
  u32 tid2 = tid;
  uint4 yv[4];
#pragma unroll
  for (int v = 0; v < 4; v++) yv[v].x = INVAL;
  if (w < 4) {
    asm volatile("setmaxnreg.inc.sync.aligned.u32 232;");
    const u32 tid = tid2 + p.zero, w = tid >> 5, lane = tid & 31, g = lane >> 2, q = lane & 3, hi = g & 1, zr = tid >> 16, tp = SM_TAP + w * TAPS;
    const u32 pml = opq((g & 3) ? 0 : pm);
    const u32 tr = tp + ((hi ? TO : TE) + (g >> 1) - q) * 4;
    u32 T[33][4], B5[5][2], B3[5][2];
#pragma unroll
    for (int d = 0; d < 33; d++) {
      T[d][0] = lds32(tr + 32 * d); T[d][1] = lds32(tr + 32 * d + 16);
      T[d][2] = cpy(d ? T[d - 1][1] : zr, zr, 0); T[d][3] = cpy(T[d][0], zr, 1);
    }
    const u32 t33 = cpy(T[32][1], zr, 0), z33 = cpy(zr, zr, 1);
    const u32 bt = tp + (T5 + g - q) * 4;
#pragma unroll
    for (int d = 0; d < 5; d++) {
      B5[d][0] = lds32(bt + 32 * d); B5[d][1] = lds32(bt + 32 * d - 16);
      B3[d][0] = lds32(bt + 32 * d + (T3 - T5) * 4); B3[d][1] = lds32(bt + 32 * d - 16 + (T3 - T5) * 4);
    }
    u32 za = opq(SM_ZS + 16 + w * ZSS + ((lane >> 3) & 1) * ZPS + ((lane & 7) + (lane >> 4)) * 16);
    u32 wa = opq(SM_W + W5O + w * WSL + row16(lane));
    u32 sa = opq(SM_W + W9O - 2048 + w * WSL + lane * 16);
    u32 yo = opq(G_Y + b * BLK + 256 * q + w * 32 + 4 * g);
    const u32 fa = opq(SM_SC + 16 * w + 8);
    TS(8);
    bsync(9, 384);
    TS(11);
    float A[4][4] = {};
    uint4 Z[4];
    Z[0] = ldsm4(za); Z[1] = ldsm4(za + 32);
    const uint2 fc = lds64(fa);
    const u32 F = __byte_perm(fu(uf(fc.x) * uf(fc.y)), 0, 0x3232);
#define STEP(s, b0, b1) { _Pragma("unroll") for (int i = 0; i < 4; i++) mma_hf_t(A[i], T[8 * i + 7 - (s)], b0, b1); }
#define PAIR(n) { Z[(n + 2) & 3] = ldsm4(za + 32 * (n + 2)); STEP(2 * n, Z[n].x, Z[n].y); STEP(2 * n + 1, Z[n].z, Z[n].w); }
#define LAST(N) mma8_hf(N, t33, z33, Z[3].y); float O[4]; mma_hf_o(O, A[0], T[0], Z[3].z, Z[3].w); \
    _Pragma("unroll") for (int i = 0; i < 3; i++) mma_hf_o(A[i], A[i + 1], T[8 * i + 8], Z[3].z, Z[3].w); \
    mma_hf_o(A[3], N, T[32], Z[3].z, Z[3].w);
#pragma unroll 1
    for (int j = 0; j < 4; j++) {
      PAIR(0); PAIR(1); PAIR(2);
      Z[1] = ldsm4(za + 160); STEP(6, Z[3].x, Z[3].y);
      float N[4] = {};
      LAST(N);
      y_store<128>(O[0], O[1], O[2], O[3], F, pml, gs + yo);
      za += 128; yo += 1024;
      TS(40 + j);
    }
    bsync(10, 352);
#pragma unroll 1
    for (int j = 4; j < 13; j++) {
      if (j == 8) bsync(14, 352);
      const uint4 a5 = ldsm4t(wa), a3 = ldsm4t(wa + (W3O - W5O));
      uint4 s3 = {0, 0, 0, 0};
      if (j >= 8) s3 = lds128(sa);
      PAIR(0);
      float N[4] = {};
#pragma unroll
      for (int i = 0; i < 4; i++) mma_hf(A[i], a5.x, a5.y, a5.z, a5.w, B5[i][0], B5[i][1]);
      mma_hf(N, a5.x, a5.y, a5.z, a5.w, B5[4][0], B5[4][1]);
      PAIR(1);
#pragma unroll
      for (int i = 0; i < 4; i++) mma_hf(A[i], a3.x, a3.y, a3.z, a3.w, B3[i][0], B3[i][1]);
      mma_hf(N, a3.x, a3.y, a3.z, a3.w, B3[4][0], B3[4][1]);
      PAIR(2);
      Z[1] = ldsm4(za + 160); STEP(6, Z[3].x, Z[3].y);
      LAST(N);
      y_store<128>(O[0] + uf(s3.x), O[1] + uf(s3.y), O[2] + uf(s3.z), O[3] + uf(s3.w), F, pml, gs + yo);
      za += 128; wa = (wa + 256) ^ 32; sa += 512; yo += 1024;
      TS(40 + j);
    }
    {
      asm volatile("mov.u32 %0,%%tid.x;" : "=r"(tid2));
      if (b < YA) {
#pragma unroll
        for (int v = 0; v < 4; v++) yv[v] = ldr128(gs + (y_off(tid2, b) + v * BLK));
      }
      const uint4 s3 = lds128(sa), s4 = lds128(sa + 512), s5 = lds128(sa + 1024);
      float X[3][4] = {{uf(s4.x), uf(s4.y), uf(s4.z), uf(s4.w)}, {}, {uf(s5.x), uf(s5.y), uf(s5.z), uf(s5.w)}};
#pragma unroll
      for (int ty = 0; ty < 2; ty++) {
        const uint4 a = ldsm4t(wa + ty * (W3O - W5O)), c = ldsm4t((wa ^ 32) + 256 + ty * (W3O - W5O)), d = ldsm4t(wa + 512 + ty * (W3O - W5O));
#pragma unroll
        for (int i = 0; i < 3; i++) mma_hf(A[i], a.x, a.y, a.z, a.w, ty ? B3[i][0] : B5[i][0], ty ? B3[i][1] : B5[i][1]);
#pragma unroll
        for (int i = 0; i < 2; i++) mma_hf(X[i], c.x, c.y, c.z, c.w, ty ? B3[i][0] : B5[i][0], ty ? B3[i][1] : B5[i][1]);
        mma_hf(X[2], d.x, d.y, d.z, d.w, ty ? B3[0][0] : B5[0][0], ty ? B3[0][1] : B5[0][1]);
      }
#pragma unroll
      for (int n = 0; n < 4; n++) {
        const uint4 f0 = n < 2 ? Z[n] : ldsm4(za + 32 * n), f1 = ldsm4(za + 32 * n + 128), f2 = ldsm4(za + 32 * n + 256);
#pragma unroll
        for (int s = 2 * n; s < 2 * n + 2; s++) {
#pragma unroll
          for (int i = 0; i < 3; i++) mma_hf_t(A[i], T[8 * i + 7 - s], s & 1 ? f0.z : f0.x, s & 1 ? f0.w : f0.y);
          mma_hf_t(X[0], T[7 - s], s & 1 ? f1.z : f1.x, s & 1 ? f1.w : f1.y); mma_hf_t(X[1], T[15 - s], s & 1 ? f1.z : f1.x, s & 1 ? f1.w : f1.y);
          mma_hf_t(X[2], T[7 - s], s & 1 ? f2.z : f2.x, s & 1 ? f2.w : f2.y);
        }
      }
      y_store<128>(A[0][0] + uf(s3.x), A[0][1] + uf(s3.y), A[0][2] + uf(s3.z), A[0][3] + uf(s3.w), F, pml, gs + yo);
      y_store<128>(A[1][0] + X[0][0], A[1][1] + X[0][1], A[1][2] + X[0][2], A[1][3] + X[0][3], F, pml, gs + yo + 1024);
      y_store<128>(A[2][0] + X[1][0] + X[2][0], A[2][1] + X[1][1] + X[2][1], A[2][2] + X[1][2] + X[2][2], A[2][3] + X[1][3] + X[2][3], F, pml, gs + yo + 2048);
    }
    barrive(12, 320);
    TS(15);
    if (!DECL) asm volatile("setmaxnreg.dec.sync.aligned.u32 168;");
  } else {
    asm volatile("setmaxnreg.dec.sync.aligned.u32 136;");
    const u32 t8 = tid - 128, pml = (g & 3) ? 0 : pm;
    {
      TS(12);
      if (PFG == 1 && tid == 288) l2_pre<WSH / 2>(p.wg + (b * WSH + WSH / 2));
      const char* zs = gs + ((16 * w - 64 + (lane >> 3)) * BLK + b * 128 + ((lane & 7) * 16 ^ rho * 64));
      const char* zs4 = gs + ((t8 >> 1) * BLK + (Ps >> 4) * 512 + (Ps & 6) * 64 + ((Ps >> 2 ^ Ps) & 2) * 32 + (Ps & 1) * 32 + (t8 & 1) * 16);
      uint4 v[5];
      v[4].x = INVAL;
      if (ZD) wait_clk(t0, ZD);
      if (w == 9) {
        const u32 d = lane < 4 ? chan(b, lane) : Ps;
        const char* mp = gs + (G_MOD + (d >> 5) * 128 + (d & 24) * 2);
        uint4 ta, tc;
        POLL({ ta = ldr128(mp); tc = ldr128(mp + MODJ); v[4] = ldr128(zs4); }, ((ta.x ^ pm) | (tc.x ^ pm)) & TAGM, 2);
        const u32 aw = (d & 4) ? ((d & 2) ? ta.w : ta.z) : ((d & 2) ? ta.y : ta.x & ~TAGM);
        const u32 cw = (d & 4) ? ((d & 2) ? tc.w : tc.z) : ((d & 2) ? tc.y : tc.x & ~TAGM);
        const float sa = ((d & 1) ? bhi(aw) : blo(aw)) * F2P64, c1 = rbf(fmaf((d & 1) ? bhi(cw) : blo(cw), F2P64, 1.f));
        const u32 EM = min(max(fu(fmaxf(32.f * fabsf(c1), fabsf(sa))) >> 23, 80u), 250u);
        const float inv = uf((264 - EM) << 23);
        if (lane < 5) { sts64(SM_SC + 16 * lane, pk_hf(16.f * c1 * inv, 16.f * c1 * inv), pk_hf(sa * inv, sa * inv)); sts32(SM_SC + 16 * lane + 8, (EM - 74) << 23); }
        TS(10);
      }
      POLLW(v[4] = ldr128(zs4), (v[4].x ^ pm) & TAGM, 1);
      TS(58);
#pragma unroll
      for (int j = 0; j < 4; j++) v[j] = ldr128(zs + j * 4 * BLK);
#define MARKERS() if (tid == 256) { \
        bulk_out<2048>(gs + (G_Y + 16384 + b * BLK), SM_INV); \
        _Pragma("unroll") for (int i = MT / 2; i < 8; i++) bulk_out<2048>(gs + (G_Y + 2048 * i + b * BLK), SM_INV); \
        bulk_out<2048>(gs + (G_PART + b * 2048), SM_INV); bulk_out<512>(gs + (G_ACT + b * 512), SM_INV); \
        bulk_out<32>(gs + (G_KEY + b * KST), SM_INV); if (!rho) bulk_out<128>(gs + (G_ACT + Ps * 128), SM_INV); \
        asm volatile("cp.async.bulk.commit_group;" ::: "memory"); }
      if (PFU == 2 && tid == 256) l2_pre<WSH>(p.wu + b * WSH);
      if (GE && tid == 256) {
        asm volatile("cp.async.bulk.wait_group.read 0;" ::: "memory");
#pragma unroll
        for (int i = 0; i < GE; i++) tma3d(SM_GATE + 12288 * i, &tm_gate, SM_MB + 8, 32 * b, i);
      }
      if (MKT == 0) MARKERS();
      if (PFG == 2 && tid == 256) l2_pre<WSH>(p.wg + b * WSH);
      if (PFG == 3 && tid == 256) l2_pre<WSH / 2>(p.wg + (b * WSH + WSH / 2));
      bsync(8, 256);
      const uint2 cc = lds64(SM_SC + 8 * (t8 & 6)), c4 = lds64(SM_SC + 64);
      POLLW(_Pragma("unroll") for (int j = 0; j < 4; j++) if ((v[j].x ^ pm) & TAGM) v[j] = ldr128(zs + j * 4 * BLK),
           ((v[0].x ^ pm) | (v[1].x ^ pm) | (v[2].x ^ pm) | (v[3].x ^ pm)) & TAGM, 1);
      TS(9);
      const u32 dst = SM_ZS + 128 + (t8 & 7) * ZPS + (16 * w - 64 + (lane >> 3)) * 16;
#pragma unroll
      for (int j = 4; j >= 0; j--) {
        const uint2 c = j < 4 ? cc : c4;
        sts128(j < 4 ? dst + j * 64 : SM_Z4 + 256 + (t8 & 1) * ZP4 + (t8 >> 1) * 16, hfma(v[j].x & ~TAGM, c.x, c.y), hfma(v[j].y, c.x, c.y), hfma(v[j].z, c.x, c.y), hfma(v[j].w, c.x, c.y));
      }
      if (t8 < 96) sts128(t8 < 64 ? SM_ZS + (t8 & 7) * ZPS + (t8 >> 3) * 16 : SM_Z4 + (t8 & 1) * ZP4 + (t8 & 30) * 8, 0, 0, 0, 0);
      if (MKT == 0) asm volatile("cp.async.bulk.wait_group.read 1;" ::: "memory");
      else asm volatile("cp.async.bulk.wait_group.read 0;" ::: "memory");
      bsync(9, 384);
      TS(11);
      if (MKT == 1) MARKERS();
      const bool lng = w < 8 || w == 9;
      const u32 ts = lane + 32 * (w == 8 ? 0 : w - 9), c = min(ts, 71u), ma = SM_MODS + 16 * c;
      const u32 sig = lng ? ksig : ts >> 4, l2 = lng ? lane : 32 + (ts & 15);
      const char* mq = gs + (G_MOD + (c >> 2) * 128 + (c & 3) * 16);
      if (!lng) {
#pragma unroll
        for (int j = 0; j < 6; j++) cpa16(ma + 1152 * j, mq + j * MODJ);
        cpa16(ma + 1152 * 6, p.dsk + 16 * c); cpa16(ma + 1152 * 7, p.wr + 16 * c);
        if (PFU == 3) {
#pragma unroll
          for (int j = 0; j < 4; j++) if (ts < 81) l2_line(p.wu + (b * WSH + (81 * j + ts) * 128));
        }
        if (tid == 352) {
          PROXY_FENCE();
          if (PFU == 1) l2_pre<WSH>(p.wu + b * WSH);
          mb_expect(SM_MB + 8, rho ? SLV : 46080);
#pragma unroll
          for (int i = GE; i < 3; i++) tma3d(SM_GATE + 12288 * i, &tm_gate, SM_MB + 8, 32 * b, i);
          if (!rho) tma3d(SM_GATE + SLV, &tm_gs, SM_MB + 8, 4096 + 4 * b, 0);
          mb_expect(SM_MB + 16, rho ? SLV : 46080);
          tma3d(SM_UP, &tm_up, SM_MB + 16, 32 * b, 0);
          if (!rho) tma3d(SM_UP + SLV, &tm_us, SM_MB + 16, 4096 + 4 * b, 0);
        }
      }
      const u32 wb = SM_W + sig * WSL;
      if (sig < 5) {
        const u32 za = (sig < 4 ? SM_ZS + 128 + sig * ZSS : SM_Z4 + 256) + l2 * 32, zb = za + (sig < 4 ? ZPS : ZP4);
        const uint4 c0 = lds128(zb - 32), c1 = lds128(za - 16), c2 = lds128(zb - 16), c3 = lds128(za), c4 = lds128(zb), c5 = lds128(za + 16), c6 = lds128(zb + 16);
        const u32 P[25] = {c0.z, c0.w, c1.x, c1.y, c1.z, c1.w, c2.x, c2.y, c2.z, c2.w, c3.x, c3.y, c3.z, c3.w, c4.x, c4.y, c4.z, c4.w, c5.x, c5.y, c5.z, c5.w, c6.x, c6.y, c6.z};
        u32 Q[25], D1[24], F4[23], W5[21], W3[17];
#pragma unroll
        for (int j = 1; j < 25; j++) Q[j] = __byte_perm(P[j - 1], P[j], 0x5432);
#pragma unroll
        for (int j = 1; j < 24; j++) D1[j] = hadd(P[j], Q[j]);
#pragma unroll
        for (int j = 2; j < 23; j++) F4[j] = hadd(D1[j], D1[j - 1]);
#pragma unroll
        for (int n = 0; n < 21; n++) W5[n] = hadd(F4[n + 2], P[n]);
#pragma unroll
        for (int n = 0; n < 17; n++) W3[n] = hadd(Q[n + 8], D1[n + 7]);
        const u32 a0 = wb + W5O + 64 * l2 + 16 * ((l2 >> 1) & 3);
#pragma unroll
        for (int i = 0; i < 4; i++) {
          sts128(a0 ^ (16 * i), W5[4 * i + 5], W5[4 * i + 6], W5[4 * i + 7], W5[4 * i + 8]);
          sts128((a0 ^ (16 * i)) + (W3O - W5O), W3[4 * i + 1], W3[4 * i + 2], W3[4 * i + 3], W3[4 * i + 4]);
        }
        if (lng) {
          if (lane < 16) sts128(wb + (lane & 7) * 16 + (lane & 8) * 400, 0, 0, 0, 0);
          const u32 a1 = wb + 32 * lane + 16 * ((lane >> 2) & 1);
#pragma unroll
          for (int i = 0; i < 4; i++) {
            const u32 a = (a1 ^ (16 * (i >> 1))) + 1024 * (i & 1), n = 4 * i;
            sts128(a + V2O, hadd(Q[n + 9], P[n + 8]), hadd(Q[n + 10], P[n + 9]), hadd(Q[n + 11], P[n + 10]), hadd(Q[n + 12], P[n + 11]));
            sts128(a + W9O, hadd(F4[n + 4], W5[n]), hadd(F4[n + 5], W5[n + 1]), hadd(F4[n + 6], W5[n + 2]), hadd(F4[n + 7], W5[n + 3]));
            sts128(a + W7O, hadd(F4[n + 6], W3[n]), hadd(F4[n + 7], W3[n + 1]), hadd(F4[n + 8], W3[n + 2]), hadd(F4[n + 9], W3[n + 3]));
          }
        }
      }
      if (w != 9) barrive(10, 352);
      __syncwarp();
      TS(32);
      if (lng) {
        const u32 wa = wb + ((lane >> 3) & 1) * 1024 + (((lane & 7) ^ (lane >> 4)) + 8 * (lane >> 4)) * 16;
        const u32 kv = lds32(SM_KV + 4 * sig), bi = (g >> 1) == q ? (hi ? kv << 16 : kv) : 0u;
        float acc[8][4] = {};
#pragma unroll
        for (int j = 0; j < 4; j++) { const uint4 a = ldsm4t(wa + V2O + j * 256); mma8_hf(acc[2 * j], a.x, a.y, bi); mma8_hf(acc[2 * j + 1], a.z, a.w, bi); }
        u32 bt = tp + (T9E + hi * TEO + (g >> 1) - q) * 4, wt = wa + W9O;
#pragma unroll 1
        for (int ty = 0; ty < 2; ty++) {
          uint4 a[4];
#pragma unroll
          for (int be = 0; be < 4; be++) a[be] = ldsm4t(wt + be * 256);
          u32 b1 = lds32(bt - 16);
#pragma unroll
          for (int d = 0; d < 8; d++) {
            const u32 b0 = lds32(bt + 16 * d);
#pragma unroll
            for (int be = 0; be < 4; be++) if (d + 2 * be < 8) mma_hf(acc[d + 2 * be], a[be].x, a[be].y, a[be].z, a[be].w, b0, b1);
            b1 = b0;
          }
          bt += (T7E - T9E) * 4; wt += W7O - W9O;
        }
        __syncwarp();
#pragma unroll
        for (int j = 0; j < 8; j++) sts128(wb + W9O + j * 512 + lane * 16, fu(acc[j][0]), fu(acc[j][1]), fu(acc[j][2]), fu(acc[j][3]));
        if (w != 9) barrive(14, 352);
        TS(34);
      }
      if (!lng) {
        asm volatile("cp.async.wait_all;" ::: "memory");
        uint4 md[6];
#pragma unroll
        for (int j = 0; j < 6; j++) md[j] = lds128(ma + 1152 * j);
        const uint4 dk = lds128(ma + 1152 * 6), wr = lds128(ma + 1152 * 7);
        POLLW(_Pragma("unroll") for (int j = 0; j < 6; j++) md[j] = ldr128(mq + j * MODJ),
              ((md[0].x ^ pm) | (md[1].x ^ pm) | (md[2].x ^ pm) | (md[3].x ^ pm) | (md[4].x ^ pm) | (md[5].x ^ pm)) & TAGM, 4);
#pragma unroll
        for (int j = 0; j < 6; j++) {
          const u32 o = (j % 3 == 1) ? BONE : 0x80008000u;
          md[j] = make_uint4(bfma(md[j].x & ~TAGM, B2P64, o), bfma(md[j].y, B2P64, o), bfma(md[j].z, B2P64, o), bfma(md[j].w, B2P64, o));
          if (j > 2) sts128(ma + 1152 * j, md[j].x, md[j].y, md[j].z, md[j].w);
        }
        const uint4 gd = make_uint4(bmul(md[2].x, dk.x), bmul(md[2].y, dk.y), bmul(md[2].z, dk.z), bmul(md[2].w, dk.w));
#pragma unroll
        for (int j = 0; j < 2; j++) sts128(ma + 1152 * j, bmul(md[j].x, gd.x), bmul(md[j].y, gd.y), bmul(md[j].z, gd.z), bmul(md[j].w, gd.w));
        sts128(ma + 2304, bmul(md[2].x, B2P64), bmul(md[2].y, B2P64), bmul(md[2].z, B2P64), bmul(md[2].w, B2P64));
        const uint4 H = make_uint4(bmul(md[4].x, wr.x), bmul(md[4].y, wr.y), bmul(md[4].z, wr.z), bmul(md[4].w, wr.w));
        sts128(ma + 1152 * 7, H.x, H.y, H.z, H.w);
        sts128(ma + 1152 * 8, bfma(md[4].x, wr.x, H.x ^ 0x80008000u), bfma(md[4].y, wr.y, H.y ^ 0x80008000u), bfma(md[4].z, wr.z, H.z ^ 0x80008000u), bfma(md[4].w, wr.w, H.w ^ 0x80008000u));
        float c4[4] = {};
        mma_bf(c4, md[4].x, md[3].x, md[4].y, md[3].y, wr.x, wr.y); mma_bf(c4, md[4].z, md[3].z, md[4].w, md[3].w, wr.z, wr.w);
        if (q == g >> 1) sts64(SM_RC + (ts >> 2) * 8, fu(hi ? c4[1] : c4[0]), fu(hi ? c4[3] : c4[2]));
        if (ts < 2) sts128(SM_ONE + 16 * ts, ts ? 0 : BONE, ts ? 0 : BONE, ts ? 0 : BONE, ts ? 0 : BONE);
        TS(14);
        if (MKT == 2) MARKERS();
        if (w == 8) asm volatile("cp.async.bulk.wait_group 0;" ::: "memory");
        if (w == 8) barrive(14, 352);
        if (PFW == 2) {
#pragma unroll
          for (int j = 0; j < 4; j++) if (ts < 81) l2_line(p.wd + (b * WSH + (81 * j + ts) * 128));
        }
        bsync(13, 96);
      }
      if (w >= 8) barrive(11, 256);
    }
    if (w < 8) {
      const int u0 = 4 * (w - 4) + 2 * rho;
      const u32 t4 = SM_TAP + 4 * TAPS;
      u32 tr = t4 + ((hi ? TO : TE) + (g >> 1) - q) * 4;
      u32 zb = SM_Z4 + 256 + ((lane >> 3) & 1) * ZP4 + u0 * 128 + (lane & 7) * 16 + (lane >> 4) * 128;
      float acc[4][4] = {};
      u32 prev = 0;
#pragma unroll 1
      for (int it = min(u0 + 2, 4); it; it--) {
#pragma unroll
        for (int s = 0; s < 8; s++) {
          const uint4 z = ldsm4(zb - 16 * s);
          const u32 t0 = lds32(tr + 32 * s), t1 = lds32(tr + 32 * s + 16);
          mma_hf(acc[s & 1], t0, t1, prev, t0, z.x, z.y);
          mma_hf(acc[2 + (s & 1)], t0, t1, prev, t0, z.z, z.w);
          prev = t1;
        }
        zb -= 128; tr += 256;
      }
      {
        const uint4 z = ldsm4(zb); const u32 t0 = lds32(tr), t1 = lds32(tr + 16);
        mma_hf(acc[0], t0, t1, prev, t0, z.x, z.y); mma_hf(acc[2], t0, t1, prev, t0, z.z, z.w);
        if (w > 4) { const uint4 y = ldsm4(zb - 16); mma8_hf(acc[1], t1, zr, y.y); mma8_hf(acc[3], t1, zr, y.w); }
      }
      bsync(11, 256);
      u32 wa = (SM_W + 4 * WSL + W5O + row16(lane) + (u0 - 3) * 256) ^ 32, bt = t4 + (T5 + g - q) * 4;
#pragma unroll 1
      for (int al = min(u0 - 2, 6); al > 0; al--) {
#pragma unroll
        for (int ty = 0; ty < 2; ty++) {
          const uint4 a = ldsm4t(wa + ty * (W3O - W5O));
          const u32 bb = bt + ty * (T3 - T5) * 4;
          mma_hf(acc[ty], a.x, a.y, a.z, a.w, lds32(bb - 32), lds32(bb - 48));
          mma_hf(acc[2 + ty], a.x, a.y, a.z, a.w, lds32(bb), lds32(bb - 16));
        }
        wa = (wa - 256) ^ 32; bt += 32;
      }
      TS(35);
      const uint2 fc = lds64(SM_SC + 16 * 4 + 8);
      const u32 F = __byte_perm(fu(uf(fc.x) * uf(fc.y)), 0, 0x3232);
      char* yp = gs + (G_Y + 16384 - 2048 + b * BLK + w * 512 + q * 64 + 4 * g);
#pragma unroll
      for (int j = 0; j < 2; j++) {
        uint4 s3 = {0, 0, 0, 0};
        if (u0 >= 8) s3 = lds128(SM_W + 4 * WSL + W9O + (u0 - 8 + j) * 512 + lane * 16);
        y_store<32>(acc[2 * j][0] + acc[2 * j + 1][0] + uf(s3.x), acc[2 * j][1] + acc[2 * j + 1][1] + uf(s3.y), acc[2 * j][2] + acc[2 * j + 1][2] + uf(s3.z),
                acc[2 * j][3] + acc[2 * j + 1][3] + uf(s3.w), F, pml, yp + j * 256);
      }
      barrive(7, 160);
      TS(16);
    } else {
      if (PFW == 3 && w == 9) {
#pragma unroll 1
        for (int j = 0; j < 12; j++) { if (lane < 27) l2_line(p.wd + (b * WSH + (27 * j + lane) * 128)); wait_clk(clk(), PFP); }
      }
      if (w >= 10) bsync(14, 352);
      if (w == 10 && b < YP) {
        wait_clk(clk(), 480 * ((int)(b >> 3) - 6));
        const char* yp = gs + (G_Y + (lane >> 2) * BLK + b * 128 + (lane & 3) * 32);
        u32 t = 0;
#pragma unroll
        for (int i = 0; i < 8; i++) t |= ldr32(yp + 8 * BLK * i);
        sts32(SM_KEY + 4 * (lane & 15), t);
      }
      if (PFW < 2 && tid == 352) { mb_wait(SM_MB + 8); if (PFW) mb_wait(SM_MB + 16); l2_pre<WSH>(p.wd + b * WSH); }
      if (D0C && tid == 352 && b < 108) {
        mb_wait(SM_MB + 16);
        PROXY_FENCE();
        mb_expect(SM_MB + 24, 49152);
        tma3d(SM_TAP, &tm_down, SM_MB + 24, 64 * (b % 9), 4 * (b / 9));
      }
      TS(17);
    }
  }
  post_conv(p, &tm_down, tid2 + p.zero, b, yv);
  TSD();
  if (s2u(smem) != SM0) __trap();
}

typedef CUresult (*EncFn)(CUtensorMap*, CUtensorMapDataType, cuuint32_t, void*, const cuuint64_t*, const cuuint64_t*, const cuuint32_t*, const cuuint32_t*,
                          CUtensorMapInterleave, CUtensorMapSwizzle, CUtensorMapL2promotion, CUtensorMapFloatOOBfill);
static void make_map(EncFn enc, CUtensorMap* tm, void* ptr, int cols, int rows, int bw, int nb, CUtensorMapSwizzle sw, int gr = 192) {
  cuuint64_t gd[3] = {(cuuint64_t)cols, (cuuint64_t)gr, (cuuint64_t)(rows / gr)}, gs[2] = {(cuuint64_t)cols * 2, (cuuint64_t)cols * 2 * gr};
  cuuint32_t bd[3] = {(cuuint32_t)bw, (cuuint32_t)gr, (cuuint32_t)nb}, es[3] = {1, 1, 1};
  enc(tm, CU_TENSOR_MAP_DATA_TYPE_BFLOAT16, 3, ptr, gd, gs, bd, es, CU_TENSOR_MAP_INTERLEAVE_NONE, sw, CU_TENSOR_MAP_L2_PROMOTION_NONE, CU_TENSOR_MAP_FLOAT_OOB_FILL_NONE);
}
extern "C" void kernel_launch(void* const* d_in, const int* in_sizes, int n_in, void* d_out, int out_size) {
  static EncFn enc = nullptr;
  static void* scratch = nullptr;
  if (!enc) {
    cudaGetSymbolAddress(&scratch, g_s);
    cudaDriverEntryPointQueryResult qr;
    cudaGetDriverEntryPoint("cuTensorMapEncodeTiled", (void**)&enc, cudaEnableDefault, &qr);
    cudaFuncSetAttribute(fused_kernel, cudaFuncAttributeMaxDynamicSharedMemorySize, SM_TOTAL);
  }
  CUtensorMap tm_mod, tm_gate, tm_gs, tm_up, tm_us, tm_down;
  make_map(enc, &tm_mod, d_in[13], 3456, 576, 32, 3, CU_TENSOR_MAP_SWIZZLE_64B);
  make_map(enc, &tm_gate, d_in[9], 4608, 576, 32, 1, CU_TENSOR_MAP_SWIZZLE_64B);
  make_map(enc, &tm_gs, d_in[9], 4608, 576, 8, 3, CU_TENSOR_MAP_SWIZZLE_NONE);
  make_map(enc, &tm_up, d_in[10], 4608, 576, 32, 3, CU_TENSOR_MAP_SWIZZLE_64B);
  make_map(enc, &tm_us, d_in[10], 4608, 576, 8, 3, CU_TENSOR_MAP_SWIZZLE_NONE);
  make_map(enc, &tm_down, d_in[11], 576, 4608, 64, 1, CU_TENSOR_MAP_SWIZZLE_128B, 96);
  Prm p;
  p.x = (const char*)d_in[0]; p.la = (const char*)d_in[1]; p.ai = (const char*)d_in[2]; p.cr = (const char*)d_in[3];
  p.ci = (const char*)d_in[4]; p.ldt = (const char*)d_in[5]; p.dsk = (const char*)d_in[6]; p.wr = (const char*)d_in[8];
  p.wg = (const char*)d_in[9]; p.wu = (const char*)d_in[10]; p.wd = (const char*)d_in[11];
  p.c = (const char*)d_in[12]; p.out = (char*)d_out; p.zero = 0; p.gs = (char*)scratch;
  fused_kernel<<<128, 384, SM_TOTAL>>>(p, tm_mod, tm_gate, tm_gs, tm_up, tm_us, tm_down);
}
```

```cpp
#include <cuda_runtime.h>
#include <cuda.h>
#include <cuda_bf16.h>
#include <cuda_fp16.h>
#include <stdint.h>
#define FUSED 1
#define DEV __device__ __forceinline__
typedef uint32_t u32;

constexpr u32 BLK = 18432, G_Z = 0, G_Y = 128 * BLK, G_MOD = 2 * G_Y, G_KEY = G_MOD + 128 * 128, G_ACT = G_KEY + 128 * 128;
constexpr u32 G_PART = G_ACT + 576 * 128, G_EP = G_PART + 128 * 2048, G_END = G_EP + 128;
__device__ __align__(128) unsigned char g_s[G_END];
#define TS(i)
#define TSJ(j)
#define TS0()
#define TSE()
#define TSD()
#define TSX 0
#define TSN(code, n)
#define ERRF(code)

constexpr int SM0 = 1024;
constexpr int ROW = 1168, SLV = 36864;
constexpr int SM_GATE = SM0, SM_UP = SM_GATE + 46080, SM_XST = SM_UP + 46080, SM_MODS = SM_XST + 16 * ROW, SM_W = SM_MODS + 11008;
constexpr int KTAB = 9216, WSL = 12544, W5O = 128, W3O = 3328, V2O = 6400, W9O = 8448, W7O = 10496;
constexpr int ZPS = 2192, ZSS = 2 * ZPS, ZP4 = 2368;
constexpr int SM_ZS = SM_W + 5 * WSL, SM_Z4 = SM_ZS + 4 * ZSS, SM_TAP = SM_Z4 + 2 * ZP4, TAPS = 3328;
constexpr int SM_MB = SM_TAP + 5 * TAPS;
constexpr int SM_SC = SM_MB + 32;
constexpr int SM_KV = SM_SC + 80;
constexpr int SM_THR = SM_KV + 32;
constexpr int SM_SLOT = SM_THR + 48;
constexpr int SM_KEY = SM_SLOT + 32;
constexpr int SM_ST = SM_KEY + 64;
constexpr int SM_ST2 = SM_ST + 256;
constexpr int SM_RC = SM_ST2 + 256;
constexpr int SM_SP = SM_RC + 192;
constexpr int SM_AF = SM_SP + 1152, SM_SIL = SM_AF + 1152, SM_INV = SM_SIL + 1152, SM_END = SM_SP + 5760;
constexpr int SM_ONE = SM_MODS + 9 * 1152;
constexpr int SM_WD = SM_W, SM_XS = SM_W + 36864, SM_AC = SM_ZS, SM_RED = SM_AC + 6144;
constexpr int SM_TSB = SM_END, SM_TOTAL = SM_END + TSX - SM0;
static_assert(SM_W % 1024 == 0 && SM_TAP % 1024 == 0 && SM_MODS + 8 * KTAB <= SM_ZS && SM_ZS + 2 * KTAB <= SM_TAP && SM_RED + 10240 <= SM_TAP && SM_XS + 8 * ROW <= SM_ZS, "smem map");
static_assert(SM_MB % 16 == 0 && SM_THR % 16 == 0 && SM_ST % 16 == 0 && SM_SP % 16 == 0 && SM_TOTAL <= 232448, "smem map");
constexpr int TE = 4, TO = 276, T5 = 560, T3 = 624, T9E = 680, T7E = 760, TEO = 40;
#define MT 10
#define DECL 1
#define MKT 1
#define KST 128
#define DE1 1
#define DE2 4
#define DE3 5
#define OUTA 2
#define OUTB 7
#define PFW 1
#define PFU 0
#define KD 750
#define D0C 0
#define YE 80
#define YL 104
#define YD 250
#define OPTM 1
#define Y8 128
#define FH 0
#define FO 0
#define DB1 1
#define KD1 150
#define AD 0
#define PD 0
#define ZD 0
#define DD 1000
#define INCV 1
#define TPIN 0
#define A5P 1
#define SWJ 1
#define TG 0
#define TU 0
#define TW 0
#define AFL 128
#define KDB 550
#define KE 80
#define PFP 200
#define GE 0
#define NB8 8
#define DX 0
#define DMOD 1000
#define PFG 1
constexpr int N1 = 320 + 32 * DB1, N12 = 288 + 32 * !DB1;
constexpr int SPIN = 1 << 16, NEARLY = 4;
constexpr u32 TAGM = 0x40004000u, TAGR = 0x40000000u, INVAL = 0x00004801u;

DEV u32 s2u(const void* p) { return (u32)__cvta_generic_to_shared(p); }
DEV void mma_bf(float (&c)[4], u32 a0, u32 a1, u32 a2, u32 a3, u32 b0, u32 b1) {
  asm("mma.sync.aligned.m16n8k16.row.col.f32.bf16.bf16.f32 {%0,%1,%2,%3},{%4,%5,%6,%7},{%8,%9},{%0,%1,%2,%3};"
      : "+f"(c[0]), "+f"(c[1]), "+f"(c[2]), "+f"(c[3]) : "r"(a0), "r"(a1), "r"(a2), "r"(a3), "r"(b0), "r"(b1));
}
DEV void mma_hf(float (&c)[4], u32 a0, u32 a1, u32 a2, u32 a3, u32 b0, u32 b1) {
  asm("mma.sync.aligned.m16n8k16.row.col.f32.f16.f16.f32 {%0,%1,%2,%3},{%4,%5,%6,%7},{%8,%9},{%0,%1,%2,%3};"
      : "+f"(c[0]), "+f"(c[1]), "+f"(c[2]), "+f"(c[3]) : "r"(a0), "r"(a1), "r"(a2), "r"(a3), "r"(b0), "r"(b1));
}
DEV void mma8_bf(float (&c)[4], u32 a0, u32 a1, u32 b0) {
  asm("mma.sync.aligned.m16n8k8.row.col.f32.bf16.bf16.f32 {%0,%1,%2,%3},{%4,%5},{%6},{%0,%1,%2,%3};"
      : "+f"(c[0]), "+f"(c[1]), "+f"(c[2]), "+f"(c[3]) : "r"(a0), "r"(a1), "r"(b0));
}
DEV void mma8_hf(float (&c)[4], u32 a0, u32 a1, u32 b0) {
  asm("mma.sync.aligned.m16n8k8.row.col.f32.f16.f16.f32 {%0,%1,%2,%3},{%4,%5},{%6},{%0,%1,%2,%3};"
      : "+f"(c[0]), "+f"(c[1]), "+f"(c[2]), "+f"(c[3]) : "r"(a0), "r"(a1), "r"(b0));
}
DEV u32 movm(u32 x) { u32 r; asm("movmatrix.sync.aligned.m8n8.trans.b16 %0,%1;" : "=r"(r) : "r"(x)); return r; }
DEV uint4 ldsm4(u32 a) { uint4 r; asm volatile("ldmatrix.sync.aligned.m8n8.x4.shared.b16 {%0,%1,%2,%3},[%4];" : "=r"(r.x), "=r"(r.y), "=r"(r.z), "=r"(r.w) : "r"(a)); return r; }
DEV uint4 ldsm4t(u32 a) { uint4 r; asm volatile("ldmatrix.sync.aligned.m8n8.x4.trans.shared.b16 {%0,%1,%2,%3},[%4];" : "=r"(r.x), "=r"(r.y), "=r"(r.z), "=r"(r.w) : "r"(a)); return r; }
DEV u32 lds32(u32 a) { u32 r; asm volatile("ld.volatile.shared.u32 %0,[%1];" : "=r"(r) : "r"(a)); return r; }
DEV uint2 lds64(u32 a) { uint2 r; asm volatile("ld.shared.v2.u32 {%0,%1},[%2];" : "=r"(r.x), "=r"(r.y) : "r"(a)); return r; }
DEV uint4 lds128(u32 a) { uint4 r; asm volatile("ld.shared.v4.u32 {%0,%1,%2,%3},[%4];" : "=r"(r.x), "=r"(r.y), "=r"(r.z), "=r"(r.w) : "r"(a)); return r; }
DEV void sts16(u32 a, u32 v) { asm volatile("st.shared.u16 [%0],%1;" ::"r"(a), "h"((unsigned short)v) : "memory"); }
DEV void sts32(u32 a, u32 v) { asm volatile("st.shared.u32 [%0],%1;" ::"r"(a), "r"(v) : "memory"); }
DEV void sts64(u32 a, u32 x, u32 y) { asm volatile("st.shared.v2.u32 [%0],{%1,%2};" ::"r"(a), "r"(x), "r"(y) : "memory"); }
DEV void sts128(u32 a, u32 x, u32 y, u32 z, u32 w) { asm volatile("st.shared.v4.u32 [%0],{%1,%2,%3,%4};" ::"r"(a), "r"(x), "r"(y), "r"(z), "r"(w) : "memory"); }
DEV uint4 ldr128(const void* p) { uint4 v; asm volatile("ld.relaxed.gpu.global.v4.u32 {%0,%1,%2,%3},[%4];" : "=r"(v.x), "=r"(v.y), "=r"(v.z), "=r"(v.w) : "l"(p) : "memory"); return v; }
DEV uint2 ldr64(const void* p) { uint2 v; asm volatile("ld.relaxed.gpu.global.v2.u32 {%0,%1},[%2];" : "=r"(v.x), "=r"(v.y) : "l"(p) : "memory"); return v; }
DEV u32 ldr32(const void* p) { u32 v; asm volatile("ld.relaxed.gpu.global.u32 %0,[%1];" : "=r"(v) : "l"(p) : "memory"); return v; }
DEV void str128(void* p, u32 x, u32 y, u32 z, u32 w) { asm volatile("st.relaxed.gpu.global.v4.u32 [%0],{%1,%2,%3,%4};" ::"l"(p), "r"(x), "r"(y), "r"(z), "r"(w) : "memory"); }
DEV void str64(void* p, u32 x, u32 y) { asm volatile("st.relaxed.gpu.global.v2.u32 [%0],{%1,%2};" ::"l"(p), "r"(x), "r"(y) : "memory"); }
DEV void str32(void* p, u32 x) { asm volatile("st.relaxed.gpu.global.u32 [%0],%1;" ::"l"(p), "r"(x) : "memory"); }
DEV void str16(void* p, u32 x) { asm volatile("st.relaxed.gpu.global.u16 [%0],%1;" ::"l"(p), "h"((unsigned short)x) : "memory"); }
DEV uint4 ldg128(const void* p) { uint4 v; asm volatile("ld.global.nc.v4.u32 {%0,%1,%2,%3},[%4];" : "=r"(v.x), "=r"(v.y), "=r"(v.z), "=r"(v.w) : "l"(p)); return v; }
DEV uint2 ldg64(const void* p) { uint2 v; asm volatile("ld.global.nc.v2.u32 {%0,%1},[%2];" : "=r"(v.x), "=r"(v.y) : "l"(p)); return v; }
DEV u32 ldg32(const void* p) { u32 v; asm volatile("ld.global.nc.u32 %0,[%1];" : "=r"(v) : "l"(p)); return v; }
DEV u32 ldg16(const void* p) { unsigned short v; asm volatile("ld.global.nc.u16 %0,[%1];" : "=h"(v) : "l"(p)); return v; }
#define bsync(id, n) asm volatile("bar.sync %0,%1;" ::"n"(id), "n"(n) : "memory")
#define barrive(id, n) asm volatile("bar.arrive %0,%1;" ::"n"(id), "n"(n) : "memory")
DEV void bsyncr(u32 id) { asm volatile("bar.sync %0,96;" ::"r"(id) : "memory"); }
DEV void barriver(u32 id) { asm volatile("bar.arrive %0,96;" ::"r"(id) : "memory"); }
constexpr u32 BW = 0x0FEA, BS = 0x6532;
DEV void mb_init(u32 a) { asm volatile("mbarrier.init.shared.b64 [%0],1;" ::"r"(a) : "memory"); }
DEV void mb_expect(u32 a, u32 bytes) { asm volatile("mbarrier.arrive.expect_tx.shared.b64 _,[%0],%1;" ::"r"(a), "r"(bytes) : "memory"); }
DEV void mb_wait(u32 a, u32 ph = 0) {
  u32 ok; int it = 0;
  do { asm volatile("{.reg .pred p; mbarrier.try_wait.parity.shared.b64 p,[%1],%2; selp.u32 %0,1,0,p;}" : "=r"(ok) : "r"(a), "r"(ph) : "memory"); } while (!ok && ++it < SPIN);
}
template <int N> DEV void bulk_out(void* dst, u32 src) { asm volatile("cp.async.bulk.global.shared::cta.bulk_group [%0],[%1],%2;" ::"l"(dst), "r"(src), "n"(N) : "memory"); }
constexpr u32 WSH = 41472;
DEV void l2_line(const void* p) { asm volatile("prefetch.global.L2 [%0];" ::"l"(p) : "memory"); }
template <int N> DEV void l2_pre(const void* p) { asm volatile("cp.async.bulk.prefetch.L2.global [%0],%1;" ::"l"(p), "n"(N) : "memory"); }
DEV void tma3d(u32 dst, const CUtensorMap* tm, u32 mb, int c0, int c2) {
  asm volatile("cp.async.bulk.tensor.3d.shared::cluster.global.mbarrier::complete_tx::bytes [%0],[%1,{%3,0,%4}],[%2];"
               ::"r"(dst), "l"((uint64_t)tm), "r"(mb), "r"(c0), "r"(c2) : "memory");
}
DEV float blo(u32 w) { return __uint_as_float(w << 16); }
DEV float bhi(u32 w) { return __uint_as_float(w & 0xffff0000u); }
DEV u32 pk_bf(float lo, float hi) { u32 r; asm("cvt.rn.bf16x2.f32 %0,%1,%2;" : "=r"(r) : "f"(hi), "f"(lo)); return r; }
DEV u32 pk_hf(float lo, float hi) { u32 r; asm("cvt.rn.f16x2.f32 %0,%1,%2;" : "=r"(r) : "f"(hi), "f"(lo)); return r; }
DEV float rbf(float x) { return __uint_as_float(pk_bf(0.f, x) & 0xffff0000u); }
DEV u32 bfma(u32 a, u32 b, u32 c) { u32 r; asm("fma.rn.bf16x2 %0,%1,%2,%3;" : "=r"(r) : "r"(a), "r"(b), "r"(c)); return r; }
DEV u32 bmul(u32 a, u32 b) { u32 r; asm("mul.rn.bf16x2 %0,%1,%2;" : "=r"(r) : "r"(a), "r"(b)); return r; }
DEV u32 badd(u32 a, u32 b) { u32 r; asm("add.rn.bf16x2 %0,%1,%2;" : "=r"(r) : "r"(a), "r"(b)); return r; }
DEV u32 hadd(u32 a, u32 b) { u32 r; asm("add.rn.f16x2 %0,%1,%2;" : "=r"(r) : "r"(a), "r"(b)); return r; }
DEV u32 hfma(u32 a, u32 b, u32 c) { u32 r; asm("fma.rn.f16x2 %0,%1,%2,%3;" : "=r"(r) : "r"(a), "r"(b), "r"(c)); return r; }
struct C2 { u32 re, im; };
DEV C2 cm2(C2 a, C2 b) {
  const __half2 ar = *reinterpret_cast<__half2*>(&a.re), ai = *reinterpret_cast<__half2*>(&a.im), br = *reinterpret_cast<__half2*>(&b.re), bi = *reinterpret_cast<__half2*>(&b.im);
  __half2 re = __hfma2(ar, br, __hneg2(__hmul2(ai, bi))), im = __hfma2(ar, bi, __hmul2(ai, br));
  return {*reinterpret_cast<u32*>(&re), *reinterpret_cast<u32*>(&im)};
}
DEV C2 pk2(const float2 (&a)[2]) { return {pk_hf(a[0].x, a[1].x), pk_hf(a[0].y, a[1].y)}; }
DEV C2 pk2c(const float2 (&a)[2]) { return {pk_hf(a[0].x, a[1].x), pk_hf(-a[0].y, -a[1].y)}; }
DEV u32 cpy(u32 x, u32 zr, int alt) {
  u32 r;
  if (alt) asm volatile("xor.b32 %0,%1,%2;" : "=r"(r) : "r"(x), "r"(zr)); else asm volatile("mad.lo.u32 %0,%2,%2,%1;" : "=r"(r) : "r"(x), "r"(zr));
  return r;
}
template <int N> DEV void inc(u32& x) { asm volatile("add.u32 %0,%0,%1;" : "+r"(x) : "n"(N)); }
DEV u32 opq(u32 x) { u32 r; asm volatile("mov.u32 %0,%1;" : "=r"(r) : "r"(x)); return r; }
DEV u32 chan(u32 b, u32 i) { return 16 * (b >> 2) + 2 * (b & 3) + (i & 1) + 4 * (i & 2); }
DEV u32 row16(u32 lane) { const u32 r0 = (lane & 7) + ((lane >> 3) & 1) + 8 * (lane >> 4) - 1; return (r0 ^ ((r0 >> 3) & 3)) * 16; }
DEV u32 clk() { u32 r; asm volatile("mov.u32 %0,%%clock;" : "=r"(r)::"memory"); return r; }
DEV void wait_clk(u32 t, int d) { while ((int)(clk() - t) < d); }
DEV float ex2(float x) { float r; asm("ex2.approx.ftz.f32 %0,%1;" : "=f"(r) : "f"(x)); return r; }
DEV float rcpf(float x) { float r; asm("rcp.approx.ftz.f32 %0,%1;" : "=f"(r) : "f"(x)); return r; }
DEV float2 cmul(float2 a, float2 b) { return make_float2(fmaf(a.x, b.x, -a.y * b.y), fmaf(a.x, b.y, a.y * b.x)); }
DEV float2 csq(float2 a) { return make_float2(fmaf(a.x, a.x, -a.y * a.y), (a.x + a.x) * a.y); }
DEV float2 cexp(float lr2, float th) {
  const float m = ex2(lr2);
  return make_float2(m * __cosf(th), m * __sinf(th));
}
DEV float silu_f(float v) { return v * rcpf(1.f + ex2(-1.4426950408889634f * v)); }
constexpr u32 B2P64 = 0x5F805F80u, B2M64 = 0x1F801F80u, BONE = 0x3F803F80u;
constexpr u32 MODJ = 18 * 128;
DEV float sqrta(float x) { float r; asm("sqrt.approx.ftz.f32 %0,%1;" : "=f"(r) : "f"(x)); return r; }
DEV u32 fu(float x) { return __float_as_uint(x); }
DEV float uf(u32 x) { return __uint_as_float(x); }
DEV void mma_hf_o(float (&d)[4], const float (&c)[4], const u32 (&a)[4], u32 b0, u32 b1) {
  asm("mma.sync.aligned.m16n8k16.row.col.f32.f16.f16.f32 {%0,%1,%2,%3},{%4,%5,%6,%7},{%8,%9},{%10,%11,%12,%13};"
      : "=f"(d[0]), "=f"(d[1]), "=f"(d[2]), "=f"(d[3]) : "r"(a[0]), "r"(a[1]), "r"(a[2]), "r"(a[3]), "r"(b0), "r"(b1), "f"(c[0]), "f"(c[1]), "f"(c[2]), "f"(c[3]));
}

DEV void mma_hf_t(float (&c)[4], const u32 (&a)[4], u32 b0, u32 b1) { mma_hf(c, a[0], a[1], a[2], a[3], b0, b1); }
DEV void cpa16(u32 dst, const void* src) { asm volatile("cp.async.cg.shared.global [%0],[%1],16;" ::"r"(dst), "l"(src) : "memory"); }
DEV void tm_pre(const CUtensorMap* tm) { asm volatile("prefetch.tensormap [%0];" ::"l"((uint64_t)tm) : "memory"); }
#define PROXY_FENCE() asm volatile("fence.proxy.async.shared::cta;" ::: "memory")
struct Prm {
  const char *la, *ai, *cr, *ci, *ldt;
  u32 zero;
  const char *x, *c;
  char* gs;
  const char *dsk, *wr, *wg, *wu, *wd;
  char* out;
};
constexpr float LOG2E = 1.4426950408889634f, F2P64 = 1.8446744073709552e19f, F2M64 = 5.421010862427522e-20f;

template <int S> DEV void y_store(float c0, float c1, float c2, float c3, u32 F, u32 pml, char* yp) {
  str32(yp, bmul(pk_bf(c0, c2), F) | pml);
  str32(yp + S, bmul(pk_bf(c1, c3), F) | pml);
}
DEV void merge4(u32 (&h)[8], uint4 a, uint4 b) {
  const u32 e1 = min(a.x, b.x), e2 = max(a.z, b.z), o1 = min(a.y, b.y), o2 = max(a.w, b.w), o0 = max(a.y, b.y), e3 = min(a.z, b.z);
  const u32 f1 = max(e1, e2), f2 = min(e1, e2), p1 = max(o1, o2), p2 = min(o1, o2);
  h[0] = max(a.x, b.x); h[1] = max(o0, f1); h[2] = min(o0, f1); h[3] = max(p1, f2); h[4] = min(p1, f2); h[5] = max(p2, e3); h[6] = min(p2, e3); h[7] = min(a.w, b.w);
}
DEV void top8(u32 (&a)[8], uint4 l, uint4 m) {
  u32 b[8];
  merge4(b, l, m);
#pragma unroll
  for (int i = 0; i < 8; i++) a[i] = max(a[i], b[7 - i]);
#pragma unroll
  for (int s = 4; s; s >>= 1)
#pragma unroll
    for (int i = 0; i < 8; i++) if (!(i & s)) { const u32 x = a[i], y = a[i + s]; a[i] = max(x, y); a[i + s] = min(x, y); }
}
#define POLL(load, cond_bad, code) { int it_ = 0; do { load; } while (__any_sync(~0u, (cond_bad)) & (++it_ <= SPIN)); if (it_ > SPIN) { ERRF(code); } TSN(code, it_); }
#define POLLW(load, cond_bad, code) { int it_ = 0; while (__any_sync(~0u, (cond_bad))) { if (++it_ > SPIN) { ERRF(code); break; } load; } TSN(code, it_); }

#define DOWN(E) if (tid == 288 && b < 108) { const u32 c0 = 64 * (b % 9), c2 = 4 * (b / 9); \
    if (!D0C && E == 1) { mb_expect(SM_MB + 24, 49152); tma3d(SM_TAP, tm_down, SM_MB + 24, c0, c2); } \
    if (DE1 == E) tma3d(SM_WD, tm_down, SM_MB + 24, c0, c2 + 1); \
    if (DE2 == E) tma3d(SM_WD + 12288, tm_down, SM_MB + 24, c0, c2 + 2); \
    if (DE3 == E) tma3d(SM_WD + 24576, tm_down, SM_MB + 24, c0, c2 + 3); }
#define OUTR(E) if (((OUTA == E) | (OUTB == E) << 1) & ot) { const u32 tl = 4 * ((lane >> 1) & 1) + ((lane >> 2) & 3) + 8 * (lane & 1); \
    bulk_out<1152>(p.out + (b * BLK + tl * 1152), SM_XST + ((lane & 2) + 4 * (lane & 1) + ((lane >> 2) & 1) + (lane & 8)) * ROW); \
    asm volatile("cp.async.bulk.commit_group;" ::: "memory"); }
DEV void ffn_tail(const Prm& p, const CUtensorMap* tm_down, uint4 (&A)[24], const u32 tid, const u32 b, const u32 par, const u32 ot) {
  const u32 w = tid >> 5, lane = tid & 31, g = lane >> 2, q = lane & 3, kq = w & 3, tg = w >> 2;
  const u32 rho = b & 1, pm = par ? TAGM : 0;
  char* const gs = p.gs;
  __syncthreads();
  TS(25);
  DOWN(5);
  {
    float c0[2][4] = {}, c1[2][4] = {};
    const u32 ba = SM_XS + (lane & 7) * ROW + (18 * kq + (lane >> 3)) * 16;
    uint4 bb[5];
#pragma unroll
    for (int s = 0; s < 5; s++) bb[s] = ldsm4(ba + s * 64);
#pragma unroll
    for (int s = 0; s < 9; s++) mma_bf(c0[s & 1], A[s].x, A[s].y, A[s].z, A[s].w, s & 1 ? bb[s >> 1].z : bb[s >> 1].x, s & 1 ? bb[s >> 1].w : bb[s >> 1].y);
    const u32 ra = SM_RED + (8 * tg + kq) * 512 + lane * 16;
    if (tg < 2) {
#pragma unroll
      for (int s = 0; s < 9; s++) mma_bf(c1[s & 1], A[9 + s].x, A[9 + s].y, A[9 + s].z, A[9 + s].w, s & 1 ? bb[s >> 1].z : bb[s >> 1].x, s & 1 ? bb[s >> 1].w : bb[s >> 1].y);
      sts128(ra + 2048, fu(c1[0][0] + c1[1][0]), fu(c1[0][1] + c1[1][1]), fu(c1[0][2] + c1[1][2]), fu(c1[0][3] + c1[1][3]));
    }
    sts128(ra, fu(c0[0][0] + c0[1][0]), fu(c0[0][1] + c0[1][1]), fu(c0[0][2] + c0[1][2]), fu(c0[0][3] + c0[1][3]));
  }
  TS(39);
  __syncthreads();
  const u32 tr = clk();
  OUTR(6);
  if (w - 3 - rho < 5 - rho) {
    const u32 t = 7 - w;
    float s[4] = {};
#pragma unroll
    for (int i = 0; i < 4; i++) { const uint4 u = lds128(SM_RED + (t * 4 + i) * 512 + lane * 16); s[0] += uf(u.x); s[1] += uf(u.y); s[2] += uf(u.z); s[3] += uf(u.w); }
    const u32 sg = pk_bf(silu_f(rbf(s[0])), silu_f(rbf(s[1])));
    const u32 act = movm(bmul(bmul(sg, pk_bf(s[2], s[3])), B2M64));
    str32(gs + (G_ACT + (t < 4 ? 4 * b + t : 512 + (b >> 1)) * 128 + lane * 4), act | (q ? 0 : pm));
  }
  TS(26);
  if (b < 108) {
    const char* src = gs + (G_ACT + (b / 9) * 6144 + tid * 16);
    uint4 a;
    if (AD) a.x = INVAL; else a = ldr128(src);
    if (AD && w >= 4) wait_clk(tr, AD);
    if (w < 4) {
      const u32 aa = SM_WD + (8 * (lane >> 4) + (lane & 7)) * 128 + (((2 * w + ((lane >> 3) & 1)) ^ (lane & 7)) << 4);
      mb_wait(SM_MB + 24);
#pragma unroll
      for (int s = 0; s < 24; s++) A[s] = ldsm4t(aa + (s < 6 ? SM_TAP - SM_WD : -12288) + s * 2048);
    }
    TS(28);
    POLLW(a = ldr128(src), (a.x ^ pm) & TAGM, 9);
    sts128(SM_AC + tid * 16, a.x & ~TAGM, a.y, a.z, a.w);
    TS(27);
    if (w < 4) {
      bsync(8, 384);
      float c[4][4] = {};
#pragma unroll
      for (int s = 0; s < 12; s++) {
        const uint4 bb = ldsm4(SM_AC + lane * 16 + s * 512);
        mma_bf(c[2 * (s & 1)], A[2 * s].x, A[2 * s].y, A[2 * s].z, A[2 * s].w, bb.x, bb.y);
        mma_bf(c[2 * (s & 1) + 1], A[2 * s + 1].x, A[2 * s + 1].y, A[2 * s + 1].z, A[2 * s + 1].w, bb.z, bb.w);
      }
      char* dst = gs + (G_PART + b * 2048 + w * 512 + lane * 8);
      u32 o[4];
#pragma unroll
      for (int i = 0; i < 4; i++) o[i] = (fu(((c[0][i] + c[1][i]) + (c[2][i] + c[3][i])) * F2P64) & ~1u) | par;
      str64(dst, o[0], o[1]); str64(dst + 256, o[2], o[3]);
      TS(29);
    } else barrive(8, 384);
  }
  OUTR(7);
  if (w == 8 && b < 72) {
    const u32 ta = clk();
    const u32 kg = lds32(SM_SLOT + 4 * g), ro = (2047 - ((kg >> 2) & 2047)) * 1152 + 16 * b;
    const char* src = gs + (G_PART + (b >> 3) * 2048 + (b & 7) * 256 + lane * 8);
    const char* xs = gs + (G_Y + ro);
    uint4 xt;
    POLL(xt = ldr128(xs), (xt.x ^ TAGR) & TAGM, 10);
    const u32 x1w = (q & 2) ? ((q & 1) ? xt.w : xt.z) : ((q & 1) ? xt.y : bmul(xt.x ^ TAGR, B2P64));
    const u32 gw = lds32(SM_MODS + 5760 + 16 * b + 4 * q);
    const u32 hw = lds32(SM_XS + g * ROW + b * 16 + q * 4);
    const float sgm = rcpf(1.f + ex2(-LOG2E * bhi(kg ^ (~((int)kg >> 31) | 0x80000000))));
    char* const dst = p.out + (ro + 4 * q);
    uint2 v[12];
#pragma unroll
    for (int j = 0; j < 12; j++) v[j] = make_uint2(1, 0);
    u32 bad;
    if (PD) wait_clk(ta, PD);
    POLL({ bad = 0; _Pragma("unroll") for (int j = 0; j < 12; j++) { if (((v[j].x ^ par) | (v[j].y ^ par)) & 1) v[j] = ldr64(src + j * 9 * 2048); }
           _Pragma("unroll") for (int j = 0; j < 12; j++) bad |= (v[j].x ^ par) | (v[j].y ^ par); }, bad & 1, 11);
    float s0[4] = {}, s1[4] = {};
#pragma unroll
    for (int j = 0; j < 12; j++) { s0[j & 3] += uf(v[j].x); s1[j & 3] += uf(v[j].y); }
    const u32 y = movm(pk_bf((s0[0] + s0[1]) + (s0[2] + s0[3]), (s1[0] + s1[1]) + (s1[2] + s1[3])));
    *(u32*)dst = badd(x1w, bmul(gw, badd(hw, bmul(y, pk_bf(sgm, sgm)))));
    if (b == 0 && lane == 0) str32(gs + G_EP, par);
    TS(30); TSE();
  }
  if (w == 10) asm volatile("cp.async.bulk.wait_group.read 0;" ::: "memory");
}

DEV u32 y_off(u32 tid, u32 b) { return G_Y + (16 * (tid >> 5) + 8 * ((tid >> 1) & 1) + ((tid >> 2) & 4)) * BLK + b * 128 + ((tid >> 2) & 3) * 32 + (tid & 1) * 16; }
DEV void post_conv(const Prm& p, const CUtensorMap* tm_down, const u32 tid, const u32 b) {
  const u32 w = tid >> 5, lane = tid & 31;
  const u32 g = lane >> 2, q = lane & 3, e = g >> 2, h = (g >> 1) & 1, hi = g & 1;
  const u32 pm = lds32(SM_THR + 4), par = pm >> 30;
  char* const gs = p.gs;
  const u32 cho = 128 * w + 64 * e + 16 * q;
  u32 x1[4][4], h2[4][4], key[4], lt;
  char* const rowp = gs + (b * BLK + (4 * h + 8 * hi) * 1152 + cho);
  u32 ot = 0;
  uint4 A[24];
#define AROW(t) const u32 arow = 144 * ((t >> 5) & 3) + ((t >> 1) & 8) + (t & 7), ab = (t & 8) ? SM_UP : SM_GATE;
#define AFRAG9() { _Pragma("unroll") for (int s = 0; s < 9; s++) A[s] = ldsm4t(ab + SLV + arow * 16 + s * 256); }
  if (w < 9) {
    const u32 yc = 8 * (q >> 1) + 2 * (g >> 1), y1 = w < 8 ? BLK : 4 * BLK, y2 = 2 * y1;
    const char* ysrc = gs + (w < 8 ? y_off(tid, b) : G_Y + (q & 1) * 16 + (8 * yc + 2 * hi + ((b >> 4) & 1)) * BLK + 16384 + ((b >> 5) * 16 + (b & 15)) * 32);
    const char* const ys[4] = {ysrc, ysrc + y1, ysrc + y2, ysrc + (y1 + y2)};
    u32 tc = clk();
    uint4 yv[4];
#pragma unroll
    for (int v = 0; v < 4; v++) yv[v].x = INVAL;
    if (w < 4 && b < YL) {
#pragma unroll
      for (int v = 0; v < 4; v++) yv[v] = ldr128(ys[v]);
    }
    if (w == 8) bsync(7, 160);
    const u32 ma = SM_MODS + cho, xa = SM_XST + (2 * h + 4 * hi) * ROW + cho;
    const uint4 sa = lds128(ma), ca = lds128(ma + 1152), ga = lds128(ma + 2304);
    const uint4 rb = lds128((g & 2) ? SM_ONE + 16 * hi : (ma ^ 64) + 8064 + 1152 * hi);
    const u32 saw[4] = {sa.x, sa.y, sa.z, sa.w}, caw[4] = {ca.x, ca.y, ca.z, ca.w}, gaw[4] = {ga.x, ga.y, ga.z, ga.w};
#pragma unroll
    for (int k = 0; k < 4; k++) {
      const uint2 st = lds64(SM_ST + 16 * (2 * h + 4 * hi + (k & 1) + 8 * (k >> 1)));
      const uint4 xv = lds128(xa + ((k & 1) + 8 * (k >> 1)) * ROW);
      x1[k][0] = xv.x; x1[k][1] = xv.y; x1[k][2] = xv.z; x1[k][3] = xv.w;
#pragma unroll
      for (int v = 0; v < 4; v++) x1[k][v] = badd(x1[k][v], bfma(bmul(badd(x1[k][v], st.x), st.y), caw[v], saw[v]));
    }
    const bool own = (q >> 1) == e;
    const u32 spw = SM_SP + (2 * w + e) * 320 + (g & 3) * 16 + (own ? ((q & 1) == h ? 4 : 12) : 8 - 8 * (q & 1));
    TS(18);
    if (w >= 4) {
      if (b < (w < 8 ? YE : Y8)) {
#pragma unroll
        for (int v = 0; v < 4; v++) yv[v] = ldr128(ys[v]);
      }
      bsync(12, N12);
      tc = clk();
    }
    if (b >= YL) wait_clk(tc, YD);
    TS(13);
    POLLW(_Pragma("unroll") for (int v = 0; v < 4; v++) if ((yv[v].x ^ pm) & TAGM) yv[v] = ldr128(ys[v]),
          ((yv[0].x ^ pm) | (yv[1].x ^ pm) | (yv[2].x ^ pm) | (yv[3].x ^ pm)) & TAGM, 5);
    TS(19);
    if (DECL && w < 4) asm volatile("setmaxnreg.dec.sync.aligned.u32 168;");
#pragma unroll
    for (int k = 0; k < 4; k += 2) {
      float X[4] = {}, Y[4] = {}, R[4] = {};
#pragma unroll
      for (int v = 0; v < 4; v++) {
        const u32 y0 = k ? yv[v].z : yv[v].x & ~TAGM, y1 = k ? yv[v].w : yv[v].y;
        x1[k][v] = bfma(movm(y0), gaw[v], x1[k][v]);
        x1[k + 1][v] = bfma(movm(y1), gaw[v], x1[k + 1][v]);
        mma8_bf(X, x1[k][v], x1[k + 1][v], x1[k][v]); mma8_bf(Y, x1[k][v], x1[k + 1][v], x1[k + 1][v]);
        if (v & 1) mma_bf(R, x1[k][v - 1], x1[k + 1][v - 1], x1[k][v], x1[k + 1][v], v & 2 ? rb.z : rb.x, v & 2 ? rb.w : rb.y);
      }
      sts32(spw + k * 64, fu(own ? (hi ? X[1] : X[0]) : R[0] + R[1]));
      sts32(spw + k * 64 + 64, fu(own ? (hi ? Y[3] : Y[2]) : R[2] + R[3]));
    }
    barrive(1, N1);
    TS(36);
    const uint4 sb = lds128(ma + 3456), cb = lds128(ma + 4608), gb = lds128(ma + 5760);
    const u32 sbw[4] = {sb.x, sb.y, sb.z, sb.w}, cbw[4] = {cb.x, cb.y, cb.z, cb.w}, gbw[4] = {gb.x, gb.y, gb.z, gb.w};
    bsync(2, 320);
    TS(37);
    lt = lds32(SM_THR);
#pragma unroll
    for (int k = 0; k < 4; k++) {
      const uint4 st = lds128(SM_ST2 + 64 * k + 16 * (g & 3));
      key[k] = st.w;
      u32 o[4];
#pragma unroll
      for (int v = 0; v < 4; v++) {
        const u32 d = badd(x1[k][v], st.x), z = bfma(d, st.y, bmul(d, st.z));
        h2[k][v] = FH ? bfma(z, cbw[v], sbw[v]) : badd(bmul(z, cbw[v]), sbw[v]);
        o[v] = FO ? bfma(gbw[v], h2[k][v], x1[k][v]) : badd(x1[k][v], bmul(gbw[v], h2[k][v]));
      }
      h2[k][0] = bmul(h2[k][0], B2M64) | TAGR;
      if (key[k] >= lt) str128(rowp + k * 1152, h2[k][0], h2[k][1], h2[k][2], h2[k][3]);
      sts128(xa + ((k & 1) + 8 * (k >> 1)) * ROW, o[0], o[1], o[2], o[3]);
    }
    barrive(3, 320);
    TS(21);
    asm volatile("setmaxnreg.inc.sync.aligned.u32 168;");
    mb_wait(SM_MB + 8); mb_wait(SM_MB + 16);
#define AFRAG18() { const u32 t3 = opq(tid); AROW(t3); if (t3 < 256) { const u32 aa = ab + arow * 64 + ((((t3 >> 6) & 2) ^ ((t3 & 7) >> 1)) << 4); \
      _Pragma("unroll") for (int s = 0; s < 9; s++) { A[s] = ldsm4t(aa + s * 1024); A[9 + s] = ldsm4t((aa ^ 16) + s * 1024); } } else AFRAG9(); }
    if (AFL >= 128 || b < AFL) AFRAG18();
    TS(22);
    bsync(6, 352);
    TS(24);
    const u32 g8 = lds32(SM_SLOT + 28);
    const u32 sk = lds32(SM_SLOT + 4 * (w & 7));
    const char* rs_ = gs + (((~sk >> 2) & 2047) * 1152 + lane * 16);
    uint4 rv[3];
    rv[0].x = rv[1].x = rv[2].x = TAGR;
    if (w < 8) { rv[0] = ldr128(rs_); rv[1] = ldr128(rs_ + 512); if (lane < 8) rv[2] = ldr128(rs_ + 1024); barrive(15, 320); }
    const u32 km = max(max(key[0], key[1]), max(key[2], key[3]));
    if (__any_sync(~0u, km >= g8 && lt > g8)) {
#pragma unroll
      for (int k = 0; k < 4; k++) if (key[k] >= g8 && key[k] < lt) str128(rowp + k * 1152, h2[k][0], h2[k][1], h2[k][2], h2[k][3]);
    }
    if (AFL < 128 && b >= AFL) AFRAG18();
    bsync(5, 352);
    const u32 sf = lds32(SM_SLOT + 4 * (w & 7)), f8 = lds32(SM_SLOT + 28);
    if (sf != sk && w < 8) { rs_ = gs + (((~sf >> 2) & 2047) * 1152 + lane * 16); rv[0].x = INVAL; }
    if (__any_sync(~0u, km >= f8)) {
#pragma unroll
      for (int k = 0; k < 4; k++) if (key[k] >= f8) str128(rowp + (G_Y + k * 1152), bmul(x1[k][0], B2M64) | TAGR, x1[k][1], x1[k][2], x1[k][3]);
    }
    POLLW({ rv[0] = ldr128(rs_); rv[1] = ldr128(rs_ + 512); if (lane < 8) rv[2] = ldr128(rs_ + 1024); },
          ((rv[0].x ^ TAGR) | (rv[1].x ^ TAGR) | (rv[2].x ^ TAGR)) & TAGM, 8);
    TS(38);
#pragma unroll
    for (int j = 0; j < 3; j++) if (w < 8 && (j < 2 || lane < 8)) sts128(SM_XS + w * ROW + lane * 16 + j * 512, bmul(rv[j].x ^ TAGR, B2P64), rv[j].y, rv[j].z, rv[j].w);
  } else {
    u32 ok, lr;
    if (w == 10) {
      uint2 rc = lds64(SM_RC + 8 * min(lane, 17u));
      float r1 = lane < 18 ? uf(rc.x) : 0.f, r2 = lane < 18 ? uf(rc.y) : 0.f;
#pragma unroll 1
      for (int o = 16; o; o >>= 1) { r1 += __shfl_xor_sync(~0u, r1, o); r2 += __shfl_xor_sync(~0u, r2, o); }
      const u32 tl = 4 * ((lane >> 1) & 1) + ((lane >> 2) & 3) + 8 * (lane & 1), kl = (2047 - 16 * b - tl) << 2 | par * 3;
      char* const kp = gs + (G_KEY + b * KST);
      const u32 spr = SM_SP + (lane >> 4) * 9 * 320 + (lane & 15) * 16;
      TS(31);
      bsync(1, N1);
      float S1 = 0.f, S2 = 0.f, S3 = 0.f;
#pragma unroll
      for (int i = 0; i < 9; i++) { uint4 t = lds128(spr + i * 320); S1 += uf(t.x); S2 += uf(t.y); S3 += uf(t.z); }
      S1 += __shfl_xor_sync(~0u, S1, 16); S2 += __shfl_xor_sync(~0u, S2, 16); S3 += __shfl_xor_sync(~0u, S3, 16);
      const float mu = S1 * (1.f / 576.f), var = fmaxf(fmaf(-mu, mu, S2 * (1.f / 576.f)), 0.f);
      const float m = rbf(mu), rs = rcpf(rbf(sqrta(rbf(rbf(var) + 1e-5f))));
      const u32 rb = pk_bf(0.f, fmaf(fmaf(-m, r1, S3), rs, r2) + 0.f);
      ok = ((rb ^ (((int)rb >> 31) | 0x80000000)) & 0xffff0000u) | kl;
      const float rh = rbf(rs);
      sts32(SM_KEY + 4 * (lane & 15), ok);
      sts128(SM_ST2 + 16 * (lane & 15), pk_bf(-m, -m), pk_bf(rh, rh), pk_bf(rs - rh, rs - rh), ok);
      __syncwarp();
      const uint4 o0 = lds128(SM_KEY + 2 * (lane & 16)), o1 = lds128(SM_KEY + 2 * (lane & 16) + 16);
      lr = (o0.x > ok) + (o0.y > ok) + (o0.z > ok) + (o0.w > ok) + (o1.x > ok) + (o1.y > ok) + (o1.z > ok) + (o1.w > ok);
      lr += __shfl_xor_sync(~0u, lr, 16);
      if (lane < 16 && lr < 8) str32(kp + 4 * lr, ok);
      if (lr == (b < NB8 ? 7 : NEARLY - 1)) sts32(SM_THR, ok);
      barrive(2, 320);
      barrive(4, 64);
      TS(20);
    } else if (w == 9) {
      if (DB1) bsync(1, N1); else { bsync(12, N12); wait_clk(clk(), DD); }
      PROXY_FENCE();
      DOWN(1);
    } else {
      const char* ks = gs + (G_KEY + (lane >> 1) * KST + (lane & 1) * 16);
      const u32 kt = par * 3;
      uint4 L[8];
      u32 H[8];
#define KBAD(j) ((L[j].x ^ kt) & 3)
#define KLD(j) L[j] = ldr128(ks + j * 16 * KST)
#pragma unroll
      for (int j = 0; j < 8; j++) L[j].x = INVAL;
      bsync(4, 64);
      wait_clk(clk(), b < KE ? KD : b < YL ? KDB : KD1);
      TS(34);
      POLL({ _Pragma("unroll") for (int j = 0; j < 8; j++) if (KBAD(j)) KLD(j);
             merge4(H, L[0], L[1]); top8(H, L[2], L[3]);
             asm volatile("" : "+r"(H[0]), "+r"(H[1]), "+r"(H[2]), "+r"(H[3]), "+r"(H[4]), "+r"(H[5]), "+r"(H[6]), "+r"(H[7])); TS(32); },
           KBAD(0) | KBAD(1) | KBAD(2) | KBAD(3) | KBAD(4) | KBAD(5), 6);
      top8(H, L[4], L[5]);
      TS(35);
#pragma unroll 1
      for (u32 pass = p.zero;; pass++) {
        u32 G[8], m[8];
#pragma unroll
        for (int i = 0; i < 8; i++) G[i] = H[i];
#pragma unroll
        for (int r = 0; r < 8; r++) {
          const u32 h0 = G[0];
          m[r] = __reduce_max_sync(~0u, h0);
          if (r == 0) { if (KBAD(6)) KLD(6); if (KBAD(7)) KLD(7); }
          if (r < 7) asm("{.reg .u32 t; sub.u32 t,%1,%2; min.u32 t,t,1; mad.lo.u32 %0,t,%3,%4;}" : "=r"(G[0]) : "r"(m[r]), "r"(h0), "r"(h0 - G[1]), "r"(G[1]));
#pragma unroll
          for (int i = 1; i < 7 - r; i++) G[i] = h0 == m[r] ? G[i + 1] : G[i];
          if ((r & 3) == 3) sts128(SM_SLOT + 4 * r - 12, m[r - 3], m[r - 2], m[r - 1], m[r]);
        }
        asm volatile("{.reg .pred p; setp.eq.u32 p,%0,0; @p bar.arrive 6,352;}" ::"r"(pass) : "memory");
        if (pass) break;
        TS(23);
        POLLW({ if (KBAD(6)) KLD(6); if (KBAD(7)) KLD(7); }, KBAD(6) | KBAD(7), 7);
        if (!__any_sync(~0u, max(L[6].x, L[7].x) > m[7])) break;
        top8(H, L[6], L[7]);
      }
      barrive(5, 352);
      TS(33);
    }
    asm volatile("setmaxnreg.inc.sync.aligned.u32 168;");
    mb_wait(SM_MB + 8); mb_wait(SM_MB + 16);
    AROW(tid);
    AFRAG9();
    TS(22);
    if (w == 10) {
      bsync(3, 320);
      PROXY_FENCE();
      ot = lane < 16 && lr >= 8;
      OUTR(2);
      bsync(6, 352);
      bsync(15, 320);
      bsync(5, 352);
      if (lane < 16 && lr < 8 && ok < lds32(SM_SLOT + 28)) ot = 2;
      OUTR(4);
    } else if (w == 9) {
      bsync(15, 320);
      DOWN(4);
      TS(13);
    }
  }
  ffn_tail(p, tm_down, A, tid | p.zero, b, par, ot);
}

__global__ void __launch_bounds__(384, 1)
fused_kernel(const Prm p, const __grid_constant__ CUtensorMap tm_mod, const __grid_constant__ CUtensorMap tm_gate, const __grid_constant__ CUtensorMap tm_gs,
             const __grid_constant__ CUtensorMap tm_up, const __grid_constant__ CUtensorMap tm_us, const __grid_constant__ CUtensorMap tm_down) {
  extern __shared__ __align__(1024) unsigned char smem[];
  u32 la, ai, ldt; uint2 cr, ci;
  {
    const u32 t = threadIdx.x, d = t < 256 ? chan(blockIdx.x, t >> 5) : 512 + (blockIdx.x >> 1), o = d * 256 + 8 * (t & 31), o4 = o + ((t < 256 ? t >> 5 : t >> 3) & 4);
    asm volatile("{.reg .pred p; .reg .u16 h; setp.ne.u32 p,%7,0; @p ld.global.nc.u32 %0,[%8]; @p ld.global.nc.u32 %1,[%9]; @p ld.global.nc.v2.u32 {%2,%3},[%10];"
                 "@p ld.global.nc.v2.u32 {%4,%5},[%11]; @p ld.global.nc.u16 h,[%12]; cvt.u32.u16 %6,h;}"
                 : "=r"(la), "=r"(ai), "=r"(cr.x), "=r"(cr.y), "=r"(ci.x), "=r"(ci.y), "=r"(ldt)
                 : "r"(0x6ffu >> (t >> 5) & 1), "l"(p.la + o4), "l"(p.ai + o4), "l"(p.cr + o), "l"(p.ci + o), "l"(p.ldt + 2 * d));
  }
  const u32 t0 = clk();
  const u32 tid = __shfl_sync(~0u, threadIdx.x, threadIdx.x & 31), b = blockIdx.x + p.zero;
  const u32 w = tid >> 5, lane = tid & 31;
  const u32 g = lane >> 2, q = lane & 3, hi = g & 1;
  const u32 rho = b & 1, Ps = 512 + (b >> 1);
  char* const gs = p.gs;
  TS0();
  const bool kw = w != 8 && w != 11;
  const u32 ksig = w < 8 ? (w & 3) : 4, khf = w < 8 ? (w >> 2) : (w & 1);
  if (!kw) {
    if (tid == 352) {
#pragma unroll
      for (int i = 0; i < 4; i++) mb_init(SM_MB + 8 * i);
      asm volatile("fence.mbarrier_init.release.cluster;" ::: "memory");
      tm_pre(&tm_mod);
    }
    const char* cp = p.c + (576 * (w & 1) + 24 * min(lane, 23u));
    const uint2 c0 = ldg64(cp);
    la = c0.x; ai = c0.y; cr = ldg64(cp + 8); ci = ldg64(cp + 16);
  }
  const u32 zr = tid >> 16;
  const u32 epv = ldr32(gs + (G_EP + zr));
  const u32 tp = SM_TAP + ksig * TAPS;
  if (kw && !khf) {
#pragma unroll 1
    for (u32 i = lane * 16; i < TAPS; i += 512) sts128(tp + i, 0, 0, 0, 0);
  }
  if (tid < 128) sts128(SM_INV + 16 * tid, INVAL, 0, 1, 0);
  if (tid >= 252) str128(gs + (tid >= 380 ? G_MOD + b * 128 + q * 16 : b * BLK + 16384 - 252 * 16 + tid * 16), INVAL, 0, 1, 0);
  if (tid == 352 && b < 36) { while (clk() - t0 < DMOD); mb_expect(SM_MB, 36864); tma3d(SM_UP, &tm_mod, SM_MB, 32 * b, 0); }
  if (w < 9) {
    while ((int)(clk() - t0) < DX);
    const char* xp = p.x + (b * BLK + (lane >> 3) * 1152 + 128 * w + 16 * (lane & 7));
    const u32 xd = SM_XST + (((lane >> 3) & 1) + 8 * (lane >> 4)) * ROW + 128 * w + 16 * (lane & 7);
#pragma unroll
    for (int i = 0; i < 4; i++) cpa16(xd + 2 * ROW * i, xp + 4608 * i);
  }
  const u32 ktab = w < 8 ? SM_MODS + w * KTAB : SM_ZS + (w - 9) * KTAB;
  float k2048 = 0.f;
  if (kw) {
    u32 mx = __vmaxu2(__vmaxu2(cr.x & 0x7fff7fff, cr.y & 0x7fff7fff), __vmaxu2(ci.x & 0x7fff7fff, ci.y & 0x7fff7fff));
    const u32 E = max(__reduce_max_sync(~0u, max(mx & 0xffff, mx >> 16)) >> 7, 8u);
    TS(1);
    const float dt = rbf(ex2(blo(ldt) * LOG2E)), csc = uf((257 - E) << 23 | (fu(dt) & 0x7fffff));
    sts32(SM_SC + 16 * ksig + 12, fu(uf(fu(dt) & 0x7f800000) * uf((E - 2) << 23)));
    const u32 crw = khf ? cr.y : cr.x, ciw = khf ? ci.y : ci.x;
    float2 C[2], w4[2], w8[2], w16[2], w32[2], w64[2], w128[2], w256[2], w512[2], a1[2], a2[2], a3[2], t0[2], t1[2], s3[2];
#pragma unroll
    for (int m = 0; m < 2; m++) {
      const float lr2 = rbf(ex2((m ? bhi(la) : blo(la)) * LOG2E)) * dt * -LOG2E, th = (m ? bhi(ai) : blo(ai)) * dt;
      C[m] = make_float2((m ? bhi(crw) : blo(crw)) * csc, (m ? bhi(ciw) : blo(ciw)) * csc);
      const float2 w1 = cexp(lr2, th), w2 = csq(w1);
      w64[m] = cexp(64.f * lr2, 64.f * th);
      w4[m] = csq(w2); w8[m] = csq(w4[m]); w16[m] = csq(w8[m]); w32[m] = csq(w16[m]);
      w128[m] = csq(w64[m]); w256[m] = csq(w128[m]); w512[m] = csq(w256[m]);
      const float2 w1024 = csq(w512[m]);
      a1[m] = cmul(C[m], w1); a2[m] = cmul(C[m], w2); a3[m] = cmul(a1[m], w2);
      t0[m] = cmul(C[m], w1024); t1[m] = cmul(t0[m], w128[m]); s3[m] = cmul(w8[m], w16[m]);
      k2048 += fmaf(t0[m].x, w1024.x, -t0[m].y * w1024.y);
    }
    C2 B0[8], B1[8], B2[8], S[8];
    B0[0] = pk2(C); B0[1] = pk2(a1); B0[2] = pk2(a2); B0[3] = pk2(a3);
    const C2 h4 = pk2(w4), h256 = pk2(w256), h512 = pk2(w512);
#pragma unroll
    for (int i = 0; i < 4; i++) B0[4 + i] = cm2(B0[i], h4);
#pragma unroll
    for (int i = 0; i < 4; i++) B1[i] = cm2(B0[2 * i], h256);
    B1[4] = cm2(B0[0], h512); B1[5] = cm2(B0[4], h512);
    B1[6] = cm2(B1[4], h256); B1[7] = cm2(B1[5], h256);
    const u32 ta = ktab + lane * 128, f = ((lane & 3) << 5) | ((lane & 4) << 2);
#pragma unroll
    for (int i = 0; i < 8; i++) sts128(ta + ((i << 4) ^ f), B0[i].re, B0[i].im, B1[i].re, B1[i].im);
    B2[0] = pk2(t0); B2[1] = pk2(t1);
    B2[2] = cm2(B2[0], h256); B2[3] = cm2(B2[1], h256);
#pragma unroll
    for (int i = 0; i < 4; i++) B2[4 + i] = cm2(B2[i], h512);
    S[0] = {0x3C003C00u, 0u}; S[1] = pk2c(w8); S[2] = pk2c(w16); S[3] = pk2c(s3); S[4] = pk2c(w32);
#pragma unroll
    for (int i = 1; i < 4; i++) S[4 + i] = cm2(S[i], S[4]);
#pragma unroll
    for (int i = 0; i < 8; i++) sts128(ta + 4096 + ((i << 4) ^ f), B2[i].re, B2[i].im, S[i].re, S[i].im);
    const C2 m64 = pk2c(w64), m128 = pk2c(w128);
    sts128(ktab + 8192 + lane * 16, m64.re, m64.im, m128.re, m128.im);
    __syncwarp();
  } else {
    u32 sa = SM_SIL + 576 * (w & 1) + 24 * min(lane, 23u);
#pragma unroll 1
    for (int j = 0; j < 6; j++) {
      sts32(sa, pk_bf(silu_f(blo(la)), silu_f(bhi(la))));
      la = ai; ai = cr.x; cr.x = cr.y; cr.y = ci.x; ci.x = ci.y; sa += 4;
    }
    bsync(7, 64);
  }
  TS(2);
  const u32 pm = (__reduce_or_sync(~0u, epv) & 1) ? 0 : TAGM;
  sts32(SM_THR + 4, pm);
  if (w < 9) {
    asm volatile("cp.async.wait_all;" ::: "memory");
    __syncwarp();
    TS(4);
    if (tid == 256 && b >= 36 && b < 108) { mb_expect(SM_MB, 36864); tma3d(SM_UP, &tm_mod, SM_MB, 32 * b, 0); }
    const u32 xa = SM_XST + (lane & 15) * ROW + 128 * w + 16 * (lane >> 4);
    float s[4] = {}, X[2][4] = {}, Y[2][4] = {};
#pragma unroll
    for (int j = 0; j < 4; j++) {
      const uint4 a = ldsm4(xa + 32 * j);
      mma8_bf(X[0], a.x, a.y, a.x); mma8_bf(Y[0], a.x, a.y, a.y);
      mma8_bf(X[1], a.z, a.w, a.z); mma8_bf(Y[1], a.z, a.w, a.w);
      mma_bf(s, a.x, a.y, a.z, a.w, BONE, BONE);
    }
    uint4 t[4];
#pragma unroll
    for (int j = 0; j < 4; j++) t[j] = ldsm4t(xa + 32 * j);
    const float u0 = hi ? X[0][1] + X[1][1] : X[0][0] + X[1][0], u1 = hi ? Y[0][3] + Y[1][3] : Y[0][2] + Y[1][2];
    if (q == g >> 1) sts128(SM_SP + w * 128 + g * 16, fu(s[0]), fu(u0), fu(s[2]), fu(u1));
    bsync(1, 288);
    TS(7);
    const u32 spr = SM_SP + (lane & 7) * 16 + (lane & 8);
    const uint2 t8 = lds64(spr + 1024);
    const float f8 = lane < 16 ? 1.f : 0.f;
    float S1 = uf(t8.x) * f8, S2 = uf(t8.y) * f8;
#pragma unroll
    for (int i = 0; i < 4; i++) { const uint2 u = lds64(spr + (lane & 16) * 32 + i * 128); S1 += uf(u.x); S2 += uf(u.y); }
    S1 += __shfl_xor_sync(~0u, S1, 16); S2 += __shfl_xor_sync(~0u, S2, 16);
    const float mu = S1 * (1.f / 576.f), var = fmaxf(fmaf(-mu, mu, S2 * (1.f / 576.f)), 0.f);
    const float m = rbf(mu), rs = rcpf(rbf(sqrta(rbf(rbf(var) + 1e-5f))));
    const float ra = rs * 0.0625f;
    sts64(SM_AF + w * 128 + (lane & 15) * 8, fu(ra), fu(-m * ra));
    __syncwarp();
    TS(55);
    const uint4 f0 = lds128(SM_AF + w * 128 + q * 16), f1 = lds128(SM_AF + w * 128 + 64 + q * 16);
    const u32 zdst = SM_GATE + w * 2048 + (g >> 1) * 128 + (lane & 15) * 8;
    const u32 pz = (q & 1) ? 0 : pm;
#pragma unroll
    for (int j = 0; j < 8; j++) {
      const u32 x0 = j & 1 ? t[j >> 1].z : t[j >> 1].x, x1 = j & 1 ? t[j >> 1].w : t[j >> 1].y;
      sts64((j & 1 ? zdst ^ 64 : zdst) + 512 * (j >> 1), pk_hf(fmaf(blo(x0), uf(f0.x), uf(f0.y)), fmaf(bhi(x0), uf(f0.z), uf(f0.w))) | pz,
            pk_hf(fmaf(blo(x1), uf(f1.x), uf(f1.y)), fmaf(bhi(x1), uf(f1.z), uf(f1.w))));
    }
    TS(53);
    if (w < 8) barrive(15, 288);
    else {
      bsync(15, 288);
      TS(54);
      if (lane == 0) {
        PROXY_FENCE();
        bulk_out<BLK>(gs + b * BLK, SM_GATE);
        asm volatile("cp.async.bulk.commit_group;" ::: "memory");
        if (PFG & 1) l2_pre<WSH / 2>(p.wg + b * WSH);
      }
      const float rh = rbf(rs);
      sts128(SM_ST + 16 * (lane & 15), pk_bf(-m, -m), pk_bf(rh, rh), pk_bf(rs - rh, rs - rh), 0);
    }
    TS(5);
  }
  if (kw) {
    float D[5][4] = {};
    u32 ta = ktab + q * 128 + ((g ^ (q << 1)) << 4), tm = ktab + 8192 + q * 16;
#pragma unroll 2
    for (int s = 0; s < 8; s++) {
      const uint4 ca = lds128(ta), cb = lds128(ta + 4096), ma = lds128(tm);
      ta = (ta + 512) ^ 16; tm += 64;
      k2048 += __shfl_xor_sync(~0u, k2048, 16 >> s);
      const C2 s0 = {cb.z, cb.w}, s1 = cm2(s0, {ma.x, ma.y}), s2 = cm2(s0, {ma.z, ma.w}), s3 = cm2(s1, {ma.z, ma.w});
      mma_hf(D[0], s0.re, s1.re, s0.im, s1.im, ca.x, ca.y);
      mma_hf(D[2], s0.re, s1.re, s0.im, s1.im, ca.z, ca.w);
      mma_hf(D[4], s0.re, s1.re, s0.im, s1.im, cb.x, cb.y);
      mma_hf(D[1], s2.re, s3.re, s2.im, s3.im, ca.x, ca.y);
      mma_hf(D[3], s2.re, s3.re, s2.im, s3.im, ca.z, ca.w);
    }
    TS(3);
    const u32 xa = (w < 8 ? SM_MODS + (4 + ksig) * KTAB : SM_ZS) + lane * 16;
    if (khf) {
      __syncwarp();
#pragma unroll
      for (int j = 0; j < 5; j++) sts128(xa + 512 * j, fu(D[j][0]), fu(D[j][1]), fu(D[j][2]), fu(D[j][3]));
      if (lane == 0) sts32(xa + 2560, fu(k2048));
      asm volatile("bar.arrive %0,64;" ::"r"(2 + ksig) : "memory");
    } else {
      const u32 t1 = tp + (q < 2 ? (128 + 4 * g + 2 * q) * 4 : T3 * 4 + ((32 * q - 64 + g) ^ 1) * 2);
      const u32 x = 16 * q + (g >> 1) + hi + 1, tb = tp + (hi ? T7E : T9E) * 4 - 4;
      const u32 te = tb + (x + 2 * (x & 1)) * 2, to = tb + TEO * 4 + (x ^ 1) * 2;
      asm volatile("bar.sync %0,64;" ::"r"(2 + ksig) : "memory");
#pragma unroll
      for (int j = 0; j < 5; j++) { const uint4 t = lds128(xa + 512 * j); D[j][0] += uf(t.x); D[j][1] += uf(t.y); D[j][2] += uf(t.z); D[j][3] += uf(t.w); }
      k2048 = (k2048 + uf(lds32(xa + 2560))) * 0.125f;
#pragma unroll
      for (int r = 0; r < 4; r++) {
        const u32 v = pk_hf(D[2 + (r >> 1)][2 * (r & 1)], D[2 + (r >> 1)][2 * (r & 1) + 1]);
        if (q < 2) {
          const u32 vv = __byte_perm(v, v, 0x1010);
          sts32(t1 + (TO + 32 * r) * 4, vv); sts16(t1 + (TO + 32 * r + 1) * 4 + 2, v >> 16); sts16(t1 + (TO + 32 * r - 1) * 4, v);
          sts64(t1 + (TE + 32 * r) * 4, vv, __byte_perm(v, v, 0x1032));
        } else {
          sts16(t1 + 16 * r, v >> 16);
          if (r == 0 && lane == 2) {
            const u32 vv = __byte_perm(v, v, 0x1010);
            sts32(tp + (TO + 256) * 4, vv); sts16(tp + (TO + 257) * 4 + 2, v); sts16(tp + (TO + 255) * 4, v); sts64(tp + (TE + 256) * 4, vv, vv);
          } else sts16(t1 + 16 * r - ((T3 - T5) * 4 + 6) + 8 * hi, v);
        }
      }
#pragma unroll
      for (int r = 0; r < 2; r++) {
        const u32 v = pk_hf(D[4][2 * r], D[4][2 * r + 1]);
        if (r == 0 && lane == 0) { sts16(tp + T5 * 4 + 62 * 2, v); sts32(SM_KV + 4 * ksig, v & 0xffff); sts16(tp + (T9E + TEO) * 4 + 62 * 2, pk_hf(k2048, 0.f)); }
        else { sts16(te + 8 * r, v); sts16(to + 8 * r, v); }
        sts16(te + 8 * r + 16, v >> 16); sts16(to + 8 * r + 16, v >> 16);
      }
      __syncwarp();
#pragma unroll
      for (int r = 0; r < 4; r++) {
        const u32 v = pk_hf(D[r >> 1][2 * (r & 1) + 1], D[r >> 1][2 * (r & 1)]), t2 = tp + lane * 4 + 128 * r;
        sts32(t2 + TO * 4, v); sts16(t2 + TE * 4, v >> 16); sts16(t2 + (TE + 1) * 4 + 2, v);
      }
      __syncwarp();
    }
  } else if (w == 11 && b < 108) {
    float c[4][4] = {};
    u32 aa = SM_UP + ((lane & 7) + 8 * (lane >> 4)) * 64 + ((((lane >> 3) & 1) ^ ((lane & 7) >> 1)) << 4);
    u32 ba = SM_SIL + (lane >> 3) * 16;
    uint4 a[2][10];
#define GLD(n) { _Pragma("unroll") for (int i = 0; i < 2; i++) { a[n][5 * i] = ldsm4(ba + i * 64); \
      _Pragma("unroll") for (int k = 0; k < 4; k++) a[n][5 * i + 1 + k] = ldsm4t((k & 2 ? aa ^ 32 : aa) + i * 2048 + (k & 1) * 1024); } aa += 4096; ba += 128; }
#define GMM(n) { _Pragma("unroll") for (int i = 0; i < 2; i++) _Pragma("unroll") for (int k = 0; k < 4; k++) { const uint4 f = a[n][5 * i + 1 + k], bb = a[n][5 * i]; \
      mma_bf(c[k], f.x, f.y, f.z, f.w, k & 1 ? bb.z : bb.x, k & 1 ? bb.w : bb.y); } }
    mb_wait(SM_MB);
    TS(56);
    GLD(0);
#pragma unroll 1
    for (int s = 0; s < 4; s++) { GLD(1); GMM(0); GLD(0); GMM(1); }
    GMM(0);
    const float v0 = (q & 1) ? c[0][2] + c[1][2] : c[0][0] + c[1][0], v1 = (q & 1) ? c[2][2] + c[3][2] : c[2][0] + c[3][0];
    str16(gs + (G_MOD + b * 128 + 2 * g + 16 * q), pk_bf(rbf((q & 2) ? v1 : v0) * F2M64, 0.f) | (g < 2 ? pm : 0));
    TS(57);
  }
  TS(6);
  u32 tid2 = tid;
  if (w < 4) {
    asm volatile("setmaxnreg.inc.sync.aligned.u32 232;");
    const u32 tid = tid2 + p.zero, w = tid >> 5, lane = tid & 31, g = lane >> 2, q = lane & 3, hi = g & 1, zr = tid >> 16, tp = SM_TAP + w * TAPS;
    const u32 pml = opq((g & 3) ? 0 : pm);
    const u32 tr = tp + ((hi ? TO : TE) + (g >> 1) - q) * 4;
    u32 T[33][4], B5[5][2], B3[5][2];
#pragma unroll
    for (int d = 0; d < 33; d++) {
      T[d][0] = lds32(tr + 32 * d); T[d][1] = lds32(tr + 32 * d + 16);
      T[d][2] = cpy(d ? T[d - 1][1] : zr, zr, 0); T[d][3] = cpy(T[d][0], zr, 1);
    }
    const u32 t33 = cpy(T[32][1], zr, 0), z33 = cpy(zr, zr, 1);
    if (TPIN) {
#pragma unroll
      for (int d = 0; d < 33; d++) asm volatile("{.reg .pred p; setp.ne.u32 p,%2,0; @p st.shared.v2.u32 [%2],{%0,%1};}" ::"r"(T[d][2]), "r"(T[d][3]), "r"(zr) : "memory");
    }
    const u32 bt = tp + (T5 + g - q) * 4;
#pragma unroll
    for (int d = 0; d < 5; d++) {
      B5[d][0] = lds32(bt + 32 * d); B5[d][1] = lds32(bt + 32 * d - 16);
      B3[d][0] = lds32(bt + 32 * d + (T3 - T5) * 4); B3[d][1] = lds32(bt + 32 * d - 16 + (T3 - T5) * 4);
    }
    u32 za = opq(SM_ZS + 16 + w * ZSS + ((lane >> 3) & 1) * ZPS + ((lane & 7) + (lane >> 4)) * 16);
    u32 wa = opq(SM_W + W5O + w * WSL + row16(lane));
    u32 sa = opq(SM_W + W9O - 2048 + w * WSL + lane * 16);
    u32 yo = opq(G_Y + b * BLK + 256 * q + w * 32 + 4 * g);
    const u32 fa = opq(SM_SC + 16 * w + 8), bw = opq((BW >> 4 * w) & 15), bs = opq((BS >> 4 * w) & 15);
    if (TPIN) asm volatile("{.reg .pred p; setp.ne.u32 p,%8,0; @p st.shared.v4.u32 [%8],{%0,%1,%2,%3}; @p st.shared.v4.u32 [%8],{%4,%5,%6,%7};}"
                           ::"r"(za), "r"(wa), "r"(sa), "r"(yo), "r"(fa), "r"(bw), "r"(bs), "r"(pml), "r"(zr) : "memory");
    TS(8);
    bsync(9, 384);
    TS(11);
    float A[4][4] = {};
    uint4 Z[4];
    Z[0] = ldsm4(za); Z[1] = ldsm4(za + 32);
    const uint2 fc = lds64(fa);
    const u32 F = __byte_perm(fu(uf(fc.x) * uf(fc.y)), 0, 0x3232);
#define STEP(s, b0, b1) { _Pragma("unroll") for (int i = 0; i < 4; i++) mma_hf_t(A[i], T[8 * i + 7 - (s)], b0, b1); }
#define PAIR(n) { Z[(n + 2) & 3] = ldsm4(za + 32 * (n + 2)); STEP(2 * n, Z[n].x, Z[n].y); STEP(2 * n + 1, Z[n].z, Z[n].w); }
#define LAST(N) mma8_hf(N, t33, z33, Z[3].y); float O[4]; mma_hf_o(O, A[0], T[0], Z[3].z, Z[3].w); \
    _Pragma("unroll") for (int i = 0; i < 3; i++) mma_hf_o(A[i], A[i + 1], T[8 * i + 8], Z[3].z, Z[3].w); \
    mma_hf_o(A[3], N, T[32], Z[3].z, Z[3].w);
#pragma unroll 1
    for (int j = 0; j < 4; j++) {
      PAIR(0); PAIR(1); PAIR(2);
      Z[1] = ldsm4(za + 160); STEP(6, Z[3].x, Z[3].y);
      float N[4] = {};
      LAST(N);
      if (INCV) inc<128>(za);
      y_store<128>(O[0], O[1], O[2], O[3], F, pml, gs + yo);
      if (!INCV) za += 128;
      yo += 1024;
      TSJ(j);
    }
    bsyncr(bw);
    uint4 a5;
    if (A5P) a5 = ldsm4t(wa);
#pragma unroll 1
    for (int j = 4; j < 13; j++) {
      if (j == 8) bsyncr(bs);
      if (!A5P) a5 = ldsm4t(wa);
      const uint4 a3 = ldsm4t(wa + (W3O - W5O));
      uint4 s3 = {0, 0, 0, 0};
      if (j >= 8) s3 = lds128(sa);
      PAIR(0);
      float N[4] = {};
#pragma unroll
      for (int i = 0; i < 4; i++) mma_hf(A[i], a5.x, a5.y, a5.z, a5.w, B5[i][0], B5[i][1]);
      mma_hf(N, a5.x, a5.y, a5.z, a5.w, B5[4][0], B5[4][1]);
      if (INCV) asm volatile("{add.u32 %0,%0,256; xor.b32 %0,%0,32;}" : "+r"(wa)); else wa = (wa + 256) ^ 32;
      if (A5P) a5 = ldsm4t(wa);
      PAIR(1);
#pragma unroll
      for (int i = 0; i < 4; i++) mma_hf(A[i], a3.x, a3.y, a3.z, a3.w, B3[i][0], B3[i][1]);
      mma_hf(N, a3.x, a3.y, a3.z, a3.w, B3[4][0], B3[4][1]);
      PAIR(2);
      Z[1] = ldsm4(za + 160); STEP(6, Z[3].x, Z[3].y);
      LAST(N);
      if (INCV) { inc<128>(za); inc<512>(sa); }
      y_store<128>(O[0] + uf(s3.x), O[1] + uf(s3.y), O[2] + uf(s3.z), O[3] + uf(s3.w), F, pml, gs + yo);
      if (!INCV) { za += 128; sa += 512; }
      yo += 1024;
      TSJ(j);
    }
    {
      asm volatile("mov.u32 %0,%%tid.x;" : "=r"(tid2));
      const uint4 s3 = lds128(sa), s4 = lds128(sa + 512), s5 = lds128(sa + 1024);
      float X[3][4] = {{uf(s4.x), uf(s4.y), uf(s4.z), uf(s4.w)}, {}, {uf(s5.x), uf(s5.y), uf(s5.z), uf(s5.w)}};
#pragma unroll
      for (int ty = 0; ty < 2; ty++) {
        const uint4 a = A5P && !ty ? a5 : ldsm4t(wa + ty * (W3O - W5O)), c = ldsm4t((wa ^ 32) + 256 + ty * (W3O - W5O)), d = ldsm4t(wa + 512 + ty * (W3O - W5O));
#pragma unroll
        for (int i = 0; i < 3; i++) mma_hf(A[i], a.x, a.y, a.z, a.w, ty ? B3[i][0] : B5[i][0], ty ? B3[i][1] : B5[i][1]);
#pragma unroll
        for (int i = 0; i < 2; i++) mma_hf(X[i], c.x, c.y, c.z, c.w, ty ? B3[i][0] : B5[i][0], ty ? B3[i][1] : B5[i][1]);
        mma_hf(X[2], d.x, d.y, d.z, d.w, ty ? B3[0][0] : B5[0][0], ty ? B3[0][1] : B5[0][1]);
      }
#pragma unroll
      for (int n = 0; n < 4; n++) {
        const uint4 f0 = n < 2 ? Z[n] : ldsm4(za + 32 * n), f1 = ldsm4(za + 32 * n + 128), f2 = ldsm4(za + 32 * n + 256);
#pragma unroll
        for (int s = 2 * n; s < 2 * n + 2; s++) {
#pragma unroll
          for (int i = 0; i < 3; i++) mma_hf_t(A[i], T[8 * i + 7 - s], s & 1 ? f0.z : f0.x, s & 1 ? f0.w : f0.y);
          mma_hf_t(X[0], T[7 - s], s & 1 ? f1.z : f1.x, s & 1 ? f1.w : f1.y); mma_hf_t(X[1], T[15 - s], s & 1 ? f1.z : f1.x, s & 1 ? f1.w : f1.y);
          mma_hf_t(X[2], T[7 - s], s & 1 ? f2.z : f2.x, s & 1 ? f2.w : f2.y);
        }
      }
      y_store<128>(A[0][0] + uf(s3.x), A[0][1] + uf(s3.y), A[0][2] + uf(s3.z), A[0][3] + uf(s3.w), F, pml, gs + yo);
      y_store<128>(A[1][0] + X[0][0], A[1][1] + X[0][1], A[1][2] + X[0][2], A[1][3] + X[0][3], F, pml, gs + yo + 1024);
      y_store<128>(A[2][0] + X[1][0] + X[2][0], A[2][1] + X[1][1] + X[2][1], A[2][2] + X[1][2] + X[2][2], A[2][3] + X[1][3] + X[2][3], F, pml, gs + yo + 2048);
    }
    barrive(12, N12);
    TS(15);
    if (!DECL) asm volatile("setmaxnreg.dec.sync.aligned.u32 168;");
  } else {
    asm volatile("setmaxnreg.dec.sync.aligned.u32 136;");
    const u32 t8 = tid - 128, pml = (g & 3) ? 0 : pm;
    {
      TS(12);
      if (PFG == 1 && tid == 288) l2_pre<WSH / 2>(p.wg + (b * WSH + WSH / 2));
      const char* zs = gs + ((16 * w - 64 + (lane >> 3)) * BLK + b * 128 + ((lane & 7) * 16 ^ rho * 64));
      const char* zs4 = gs + ((t8 >> 1) * BLK + (Ps >> 4) * 512 + (Ps & 6) * 64 + ((Ps >> 2 ^ Ps) & 2) * 32 + (Ps & 1) * 32 + (t8 & 1) * 16);
      uint4 v[5];
      v[4].x = INVAL;
      if (ZD) wait_clk(t0, ZD);
      if (w == 9) {
        const u32 d = lane < 4 ? chan(b, lane) : Ps;
        const char* mp = gs + (G_MOD + (d >> 5) * 128 + (d & 24) * 2);
        uint4 ta, tc;
        POLL({ ta = ldr128(mp); tc = ldr128(mp + MODJ); v[4] = ldr128(zs4); }, ((ta.x ^ pm) | (tc.x ^ pm)) & TAGM, 2);
        const u32 aw = (d & 4) ? ((d & 2) ? ta.w : ta.z) : ((d & 2) ? ta.y : ta.x & ~TAGM);
        const u32 cw = (d & 4) ? ((d & 2) ? tc.w : tc.z) : ((d & 2) ? tc.y : tc.x & ~TAGM);
        const float sa = ((d & 1) ? bhi(aw) : blo(aw)) * F2P64, c1 = rbf(fmaf((d & 1) ? bhi(cw) : blo(cw), F2P64, 1.f));
        const u32 EM = min(max(fu(fmaxf(32.f * fabsf(c1), fabsf(sa))) >> 23, 80u), 250u);
        const float inv = uf((264 - EM) << 23);
        if (lane < 5) { sts64(SM_SC + 16 * lane, pk_hf(16.f * c1 * inv, 16.f * c1 * inv), pk_hf(sa * inv, sa * inv)); sts32(SM_SC + 16 * lane + 8, (EM - 74) << 23); }
        TS(10);
      }
      POLLW(v[4] = ldr128(zs4), (v[4].x ^ pm) & TAGM, 1);
      TS(58);
#pragma unroll
      for (int j = 0; j < 4; j++) v[j] = ldr128(zs + j * 4 * BLK);
#define MARKERS() if (tid == 256) { \
        bulk_out<2048>(gs + (G_Y + 16384 + b * BLK), SM_INV); \
        _Pragma("unroll") for (int i = MT / 2; i < 8; i++) bulk_out<2048>(gs + (G_Y + 2048 * i + b * BLK), SM_INV); \
        bulk_out<2048>(gs + (G_PART + b * 2048), SM_INV); bulk_out<512>(gs + (G_ACT + b * 512), SM_INV); \
        bulk_out<32>(gs + (G_KEY + b * KST), SM_INV); if (!rho) bulk_out<128>(gs + (G_ACT + Ps * 128), SM_INV); \
        asm volatile("cp.async.bulk.commit_group;" ::: "memory"); }
#define GATE() { mb_expect(SM_MB + 8, rho ? SLV : 46080); \
        _Pragma("unroll") for (int i = GE; i < 3; i++) tma3d(SM_GATE + 12288 * i, &tm_gate, SM_MB + 8, 32 * b, i); \
        if (!rho) tma3d(SM_GATE + SLV, &tm_gs, SM_MB + 8, 4096 + 4 * b, 0); }
#define UP() { mb_expect(SM_MB + 16, rho ? SLV : 46080); tma3d(SM_UP, &tm_up, SM_MB + 16, 32 * b, 0); \
        if (!rho) tma3d(SM_UP + SLV, &tm_us, SM_MB + 16, 4096 + 4 * b, 0); }
      if (PFU == 2 && tid == 256) l2_pre<WSH>(p.wu + b * WSH);
      if (GE && tid == 256) {
        asm volatile("cp.async.bulk.wait_group.read 0;" ::: "memory");
#pragma unroll
        for (int i = 0; i < GE; i++) tma3d(SM_GATE + 12288 * i, &tm_gate, SM_MB + 8, 32 * b, i);
      }
      if (MKT == 0) MARKERS();
      if (PFG == 2 && tid == 256) l2_pre<WSH>(p.wg + b * WSH);
      if (PFG == 3 && tid == 256) l2_pre<WSH / 2>(p.wg + (b * WSH + WSH / 2));
      bsync(8, 256);
      const uint2 cc = lds64(SM_SC + 8 * (t8 & 6)), c4 = lds64(SM_SC + 64);
      POLLW(_Pragma("unroll") for (int j = 0; j < 4; j++) if ((v[j].x ^ pm) & TAGM) v[j] = ldr128(zs + j * 4 * BLK),
           ((v[0].x ^ pm) | (v[1].x ^ pm) | (v[2].x ^ pm) | (v[3].x ^ pm)) & TAGM, 1);
      TS(9);
      const u32 dst = SM_ZS + 128 + (t8 & 7) * ZPS + (16 * w - 64 + (lane >> 3)) * 16;
#pragma unroll
      for (int j = 4; j >= 0; j--) {
        const uint2 c = j < 4 ? cc : c4;
        sts128(j < 4 ? dst + j * 64 : SM_Z4 + 256 + (t8 & 1) * ZP4 + (t8 >> 1) * 16, hfma(v[j].x & ~TAGM, c.x, c.y), hfma(v[j].y, c.x, c.y), hfma(v[j].z, c.x, c.y), hfma(v[j].w, c.x, c.y));
      }
      if (t8 < 96) sts128(t8 < 64 ? SM_ZS + (t8 & 7) * ZPS + (t8 >> 3) * 16 : SM_Z4 + (t8 & 1) * ZP4 + (t8 & 30) * 8, 0, 0, 0, 0);
      if (MKT == 0) asm volatile("cp.async.bulk.wait_group.read 1;" ::: "memory");
      else asm volatile("cp.async.bulk.wait_group.read 0;" ::: "memory");
      bsync(9, 384);
      TS(11);
      if (MKT == 1) MARKERS();
      const bool lng = w < 8 || w == 9;
      const u32 ts = lane + 32 * (w == 8 ? 0 : w - 9), c = min(ts, 71u), ma = SM_MODS + 16 * c;
      const u32 sig = lng ? ksig : ts >> 4, l2 = lng ? lane : 32 + (ts & 15);
      const char* mq = gs + (G_MOD + (c >> 2) * 128 + (c & 3) * 16);
      if (!lng) {
#pragma unroll
        for (int j = 0; j < 6; j++) cpa16(ma + 1152 * j, mq + j * MODJ);
        cpa16(ma + 1152 * 6, p.dsk + 16 * c); cpa16(ma + 1152 * 7, p.wr + 16 * c);
        if (PFU == 3) {
#pragma unroll
          for (int j = 0; j < 4; j++) if (ts < 81) l2_line(p.wu + (b * WSH + (81 * j + ts) * 128));
        }
        if (tid == 352) {
          PROXY_FENCE();
          if (PFU == 1) l2_pre<WSH>(p.wu + b * WSH);
          if (!TG) GATE();
          if (!TU) UP();
        }
      }
      const u32 wb = SM_W + sig * WSL;
      if (sig < 5) {
        const u32 za = (sig < 4 ? SM_ZS + 128 + sig * ZSS : SM_Z4 + 256) + l2 * 32, zb = za + (sig < 4 ? ZPS : ZP4);
        const uint4 c0 = lds128(zb - 32), c1 = lds128(za - 16), c2 = lds128(zb - 16), c3 = lds128(za), c4 = lds128(zb), c5 = lds128(za + 16), c6 = lds128(zb + 16);
        const u32 P[25] = {c0.z, c0.w, c1.x, c1.y, c1.z, c1.w, c2.x, c2.y, c2.z, c2.w, c3.x, c3.y, c3.z, c3.w, c4.x, c4.y, c4.z, c4.w, c5.x, c5.y, c5.z, c5.w, c6.x, c6.y, c6.z};
        u32 Q[25], D1[24], F4[23], W5[21], W3[17];
#pragma unroll
        for (int j = 1; j < 25; j++) Q[j] = __byte_perm(P[j - 1], P[j], 0x5432);
#pragma unroll
        for (int j = 1; j < 24; j++) D1[j] = hadd(P[j], Q[j]);
#pragma unroll
        for (int j = 2; j < 23; j++) F4[j] = hadd(D1[j], D1[j - 1]);
#pragma unroll
        for (int n = 0; n < 21; n++) W5[n] = hadd(F4[n + 2], P[n]);
#pragma unroll
        for (int n = 0; n < 17; n++) W3[n] = hadd(Q[n + 8], D1[n + 7]);
        const u32 a0 = wb + W5O + 64 * l2 + 16 * ((l2 >> 1) & 3);
#pragma unroll
        for (int i = 0; i < 4; i++) {
          sts128(a0 ^ (16 * i), W5[4 * i + 5], W5[4 * i + 6], W5[4 * i + 7], W5[4 * i + 8]);
          sts128((a0 ^ (16 * i)) + (W3O - W5O), W3[4 * i + 1], W3[4 * i + 2], W3[4 * i + 3], W3[4 * i + 4]);
        }
        if (lng) {
          if (lane < 16) sts128(wb + (lane & 7) * 16 + (lane & 8) * 400, 0, 0, 0, 0);
          const u32 a1 = wb + 32 * lane + 16 * ((lane >> 2) & 1);
#pragma unroll
          for (int i = 0; i < 4; i++) {
            const u32 a = (a1 ^ (16 * (i >> 1))) + 1024 * (i & 1), n = 4 * i;
            sts128(a + V2O, hadd(Q[n + 9], P[n + 8]), hadd(Q[n + 10], P[n + 9]), hadd(Q[n + 11], P[n + 10]), hadd(Q[n + 12], P[n + 11]));
            sts128(a + W9O, hadd(F4[n + 4], W5[n]), hadd(F4[n + 5], W5[n + 1]), hadd(F4[n + 6], W5[n + 2]), hadd(F4[n + 7], W5[n + 3]));
            sts128(a + W7O, hadd(F4[n + 6], W3[n]), hadd(F4[n + 7], W3[n + 1]), hadd(F4[n + 8], W3[n + 2]), hadd(F4[n + 9], W3[n + 3]));
          }
        }
      }
      if (w < 8) barriver((BW >> (4 * w - 16)) & 15);
      else if (!(w & 1)) { barriver((BW >> (4 * w - 32)) & 15); barriver((BW >> (4 * w - 28)) & 15); }
      __syncwarp();
      TS(32);
      if (lng) {
        const u32 wa = wb + ((lane >> 3) & 1) * 1024 + (((lane & 7) ^ (lane >> 4)) + 8 * (lane >> 4)) * 16;
        const u32 kv = lds32(SM_KV + 4 * sig), bi = (g >> 1) == q ? (hi ? kv << 16 : kv) : 0u;
        float acc[8][4] = {};
#pragma unroll
        for (int j = 0; j < 4; j++) { const uint4 a = ldsm4t(wa + V2O + j * 256); mma8_hf(acc[2 * j], a.x, a.y, bi); mma8_hf(acc[2 * j + 1], a.z, a.w, bi); }
        u32 bt = tp + (T9E + hi * TEO + (g >> 1) - q) * 4, wt = wa + W9O;
#pragma unroll 1
        for (int ty = 0; ty < 2; ty++) {
          uint4 a[4];
#pragma unroll
          for (int be = 0; be < 4; be++) a[be] = ldsm4t(wt + be * 256);
          u32 b1 = lds32(bt - 16);
#pragma unroll
          for (int d = 0; d < 8; d++) {
            const u32 b0 = lds32(bt + 16 * d);
#pragma unroll
            for (int be = 0; be < 4; be++) if (d + 2 * be < 8) mma_hf(acc[d + 2 * be], a[be].x, a[be].y, a[be].z, a[be].w, b0, b1);
            b1 = b0;
          }
          bt += (T7E - T9E) * 4; wt += W7O - W9O;
        }
        __syncwarp();
#pragma unroll
        for (int j = 0; j < 8; j++) sts128(wb + W9O + j * 512 + lane * 16, fu(acc[j][0]), fu(acc[j][1]), fu(acc[j][2]), fu(acc[j][3]));
        if (w != 9) barriver((BS >> (4 * w - 16)) & 15);
        TS(34);
      }
      if (!lng) {
        asm volatile("cp.async.wait_all;" ::: "memory");
        uint4 md[6];
#pragma unroll
        for (int j = 0; j < 6; j++) md[j] = lds128(ma + 1152 * j);
        const uint4 dk = lds128(ma + 1152 * 6), wr = lds128(ma + 1152 * 7);
        POLLW(_Pragma("unroll") for (int j = 0; j < 6; j++) md[j] = ldr128(mq + j * MODJ),
              ((md[0].x ^ pm) | (md[1].x ^ pm) | (md[2].x ^ pm) | (md[3].x ^ pm) | (md[4].x ^ pm) | (md[5].x ^ pm)) & TAGM, 4);
#pragma unroll
        for (int j = 0; j < 6; j++) {
          const u32 o = (j % 3 == 1) ? BONE : 0x80008000u;
          md[j] = make_uint4(bfma(md[j].x & ~TAGM, B2P64, o), bfma(md[j].y, B2P64, o), bfma(md[j].z, B2P64, o), bfma(md[j].w, B2P64, o));
          if (j > 2) sts128(ma + 1152 * j, md[j].x, md[j].y, md[j].z, md[j].w);
        }
        const uint4 gd = make_uint4(bmul(md[2].x, dk.x), bmul(md[2].y, dk.y), bmul(md[2].z, dk.z), bmul(md[2].w, dk.w));
#pragma unroll
        for (int j = 0; j < 2; j++) sts128(ma + 1152 * j, bmul(md[j].x, gd.x), bmul(md[j].y, gd.y), bmul(md[j].z, gd.z), bmul(md[j].w, gd.w));
        sts128(ma + 2304, bmul(md[2].x, B2P64), bmul(md[2].y, B2P64), bmul(md[2].z, B2P64), bmul(md[2].w, B2P64));
        const uint4 H = make_uint4(bmul(md[4].x, wr.x), bmul(md[4].y, wr.y), bmul(md[4].z, wr.z), bmul(md[4].w, wr.w));
        sts128(ma + 1152 * 7, H.x, H.y, H.z, H.w);
        sts128(ma + 1152 * 8, bfma(md[4].x, wr.x, H.x ^ 0x80008000u), bfma(md[4].y, wr.y, H.y ^ 0x80008000u), bfma(md[4].z, wr.z, H.z ^ 0x80008000u), bfma(md[4].w, wr.w, H.w ^ 0x80008000u));
        float c4[4] = {};
        mma_bf(c4, md[4].x, md[3].x, md[4].y, md[3].y, wr.x, wr.y); mma_bf(c4, md[4].z, md[3].z, md[4].w, md[3].w, wr.z, wr.w);
        if (q == g >> 1) sts64(SM_RC + (ts >> 2) * 8, fu(hi ? c4[1] : c4[0]), fu(hi ? c4[3] : c4[2]));
        if (ts < 2) sts128(SM_ONE + 16 * ts, ts ? 0 : BONE, ts ? 0 : BONE, ts ? 0 : BONE, ts ? 0 : BONE);
        TS(14);
        if (MKT == 2) MARKERS();
        if (w == 8) asm volatile("cp.async.bulk.wait_group 0;" ::: "memory");
        if (w == 8) { barriver(2); barriver(3); barriver(5); barriver(6); }
        if (PFW == 2) {
#pragma unroll
          for (int j = 0; j < 4; j++) if (ts < 81) l2_line(p.wd + (b * WSH + (81 * j + ts) * 128));
        }
        bsync(13, 96);
      }
      if (w >= 8) barrive(11, 256);
    }
    if (w < 8) {
      const u32 jw = SWJ && w < 6 ? w ^ 1 : w;
      const int u0 = 4 * (jw - 4) + 2 * rho;
      const u32 t4 = SM_TAP + 4 * TAPS;
      u32 tr = t4 + ((hi ? TO : TE) + (g >> 1) - q) * 4;
      u32 zb = SM_Z4 + 256 + ((lane >> 3) & 1) * ZP4 + u0 * 128 + (lane & 7) * 16 + (lane >> 4) * 128;
      float acc[4][4] = {};
      u32 prev = 0;
#pragma unroll 1
      for (int it = min(u0 + 2, 4); it; it--) {
#pragma unroll
        for (int s = 0; s < 8; s++) {
          const uint4 z = ldsm4(zb - 16 * s);
          const u32 t0 = lds32(tr + 32 * s), t1 = lds32(tr + 32 * s + 16);
          mma_hf(acc[s & 1], t0, t1, prev, t0, z.x, z.y);
          mma_hf(acc[2 + (s & 1)], t0, t1, prev, t0, z.z, z.w);
          prev = t1;
        }
        zb -= 128; tr += 256;
      }
      {
        const uint4 z = ldsm4(zb); const u32 t0 = lds32(tr), t1 = lds32(tr + 16);
        mma_hf(acc[0], t0, t1, prev, t0, z.x, z.y); mma_hf(acc[2], t0, t1, prev, t0, z.z, z.w);
        if (jw > 4) { const uint4 y = ldsm4(zb - 16); mma8_hf(acc[1], t1, zr, y.y); mma8_hf(acc[3], t1, zr, y.w); }
      }
      bsync(11, 256);
      u32 wa = (SM_W + 4 * WSL + W5O + row16(lane) + (u0 - 3) * 256) ^ 32, bt = t4 + (T5 + g - q) * 4;
#pragma unroll 1
      for (int al = min(u0 - 2, 6); al > 0; al--) {
#pragma unroll
        for (int ty = 0; ty < 2; ty++) {
          const uint4 a = ldsm4t(wa + ty * (W3O - W5O));
          const u32 bb = bt + ty * (T3 - T5) * 4;
          mma_hf(acc[ty], a.x, a.y, a.z, a.w, lds32(bb - 32), lds32(bb - 48));
          mma_hf(acc[2 + ty], a.x, a.y, a.z, a.w, lds32(bb), lds32(bb - 16));
        }
        wa = (wa - 256) ^ 32; bt += 32;
      }
      TS(35);
      const uint2 fc = lds64(SM_SC + 16 * 4 + 8);
      const u32 F = __byte_perm(fu(uf(fc.x) * uf(fc.y)), 0, 0x3232);
      char* yp = gs + (G_Y + 16384 - 2048 + b * BLK + jw * 512 + q * 64 + 4 * g);
#pragma unroll
      for (int j = 0; j < 2; j++) {
        uint4 s3 = {0, 0, 0, 0};
        if (u0 >= 8) s3 = lds128(SM_W + 4 * WSL + W9O + (u0 - 8 + j) * 512 + lane * 16);
        y_store<32>(acc[2 * j][0] + acc[2 * j + 1][0] + uf(s3.x), acc[2 * j][1] + acc[2 * j + 1][1] + uf(s3.y), acc[2 * j][2] + acc[2 * j + 1][2] + uf(s3.z),
                acc[2 * j][3] + acc[2 * j + 1][3] + uf(s3.w), F, pml, yp + j * 256);
      }
      barrive(7, 160);
      TS(16);
    } else {
      if (PFW == 3 && w == 9) {
#pragma unroll 1
        for (int j = 0; j < 12; j++) { if (lane < 27) l2_line(p.wd + (b * WSH + (27 * j + lane) * 128)); wait_clk(clk(), PFP); }
      }
      if (TG | TU) {
        if (tid == 352) {
          if (TG) { wait_clk(t0, TG); GATE(); }
          if (TW < TU) { wait_clk(t0, TW); l2_pre<WSH>(p.wd + b * WSH); }
          if (TU) { wait_clk(t0, TU); UP(); }
          if (TW >= TU) { wait_clk(t0, TW); l2_pre<WSH>(p.wd + b * WSH); }
        }
      } else if (PFW < 2 && tid == 352) { mb_wait(SM_MB + 8); if (PFW) mb_wait(SM_MB + 16); l2_pre<WSH>(p.wd + b * WSH); }
      if (D0C && tid == 352 && b < 108) {
        mb_wait(SM_MB + 16);
        PROXY_FENCE();
        mb_expect(SM_MB + 24, 49152);
        tma3d(SM_TAP, &tm_down, SM_MB + 24, 64 * (b % 9), 4 * (b / 9));
      }
      TS(17);
    }
  }
  post_conv(p, &tm_down, tid2 + p.zero, b);
  TSD();
  if (s2u(smem) != SM0) __trap();
}

typedef CUresult (*EncFn)(CUtensorMap*, CUtensorMapDataType, cuuint32_t, void*, const cuuint64_t*, const cuuint64_t*, const cuuint32_t*, const cuuint32_t*,
                          CUtensorMapInterleave, CUtensorMapSwizzle, CUtensorMapL2promotion, CUtensorMapFloatOOBfill);
static void make_map(EncFn enc, CUtensorMap* tm, void* ptr, int cols, int rows, int bw, int nb, CUtensorMapSwizzle sw, int gr = 192) {
  cuuint64_t gd[3] = {(cuuint64_t)cols, (cuuint64_t)gr, (cuuint64_t)(rows / gr)}, gs[2] = {(cuuint64_t)cols * 2, (cuuint64_t)cols * 2 * gr};
  cuuint32_t bd[3] = {(cuuint32_t)bw, (cuuint32_t)gr, (cuuint32_t)nb}, es[3] = {1, 1, 1};
  enc(tm, CU_TENSOR_MAP_DATA_TYPE_BFLOAT16, 3, ptr, gd, gs, bd, es, CU_TENSOR_MAP_INTERLEAVE_NONE, sw, CU_TENSOR_MAP_L2_PROMOTION_NONE, CU_TENSOR_MAP_FLOAT_OOB_FILL_NONE);
}
extern "C" void kernel_launch(void* const* d_in, const int* in_sizes, int n_in, void* d_out, int out_size) {
  static EncFn enc = nullptr;
  static void* scratch = nullptr;
  if (!enc) {
    cudaGetSymbolAddress(&scratch, g_s);
    cudaDriverEntryPointQueryResult qr;
    cudaGetDriverEntryPoint("cuTensorMapEncodeTiled", (void**)&enc, cudaEnableDefault, &qr);
    cudaFuncSetAttribute(fused_kernel, cudaFuncAttributeMaxDynamicSharedMemorySize, SM_TOTAL);
  }
  CUtensorMap tm_mod, tm_gate, tm_gs, tm_up, tm_us, tm_down;
  make_map(enc, &tm_mod, d_in[13], 3456, 576, 32, 3, CU_TENSOR_MAP_SWIZZLE_64B);
  make_map(enc, &tm_gate, d_in[9], 4608, 576, 32, 1, CU_TENSOR_MAP_SWIZZLE_64B);
  make_map(enc, &tm_gs, d_in[9], 4608, 576, 8, 3, CU_TENSOR_MAP_SWIZZLE_NONE);
  make_map(enc, &tm_up, d_in[10], 4608, 576, 32, 3, CU_TENSOR_MAP_SWIZZLE_64B);
  make_map(enc, &tm_us, d_in[10], 4608, 576, 8, 3, CU_TENSOR_MAP_SWIZZLE_NONE);
  make_map(enc, &tm_down, d_in[11], 576, 4608, 64, 1, CU_TENSOR_MAP_SWIZZLE_128B, 96);
  Prm p;
  p.x = (const char*)d_in[0]; p.la = (const char*)d_in[1]; p.ai = (const char*)d_in[2]; p.cr = (const char*)d_in[3];
  p.ci = (const char*)d_in[4]; p.ldt = (const char*)d_in[5]; p.dsk = (const char*)d_in[6]; p.wr = (const char*)d_in[8];
  p.wg = (const char*)d_in[9]; p.wu = (const char*)d_in[10]; p.wd = (const char*)d_in[11];
  p.c = (const char*)d_in[12]; p.out = (char*)d_out; p.zero = 0; p.gs = (char*)scratch;
  fused_kernel<<<128, 384, SM_TOTAL>>>(p, tm_mod, tm_gate, tm_gs, tm_up, tm_us, tm_down);
}
```

```cpp
#include <cuda_runtime.h>
#include <cuda.h>
#include <cuda_bf16.h>
#include <cuda_fp16.h>
#include <stdint.h>
#define FUSED 1
#define DEV __device__ __forceinline__
typedef uint32_t u32;

constexpr u32 BLK = 18432, G_Z = 0, G_Y = 128 * BLK, G_MOD = 2 * G_Y, G_KEY = G_MOD + 128 * 128, G_ACT = G_KEY + 128 * 128;
constexpr u32 G_PART = G_ACT + 576 * 128, G_EP = G_PART + 128 * 2048, G_END = G_EP + 128;
__device__ __align__(128) unsigned char g_s[G_END];
#define TS(i)
#define TSJ(j)
#define TS0()
#define TSE()
#define TSD()
#define TSX 0
#define TSN(code, n)
#define ERRF(code)

constexpr int SM0 = 1024;
constexpr int ROW = 1168, SLV = 36864;
constexpr int SM_GATE = SM0, SM_UP = SM_GATE + 46080, SM_XST = SM_UP + 46080, SM_MODS = SM_XST + 16 * ROW, SM_W = SM_MODS + 11008;
constexpr int KTAB = 9216, WSL = 12544, W5O = 128, W3O = 3328, V2O = 6400, W9O = 8448, W7O = 10496;
constexpr int ZPS = 2192, ZSS = 2 * ZPS, ZP4 = 2368;
constexpr int SM_ZS = SM_W + 5 * WSL, SM_Z4 = SM_ZS + 4 * ZSS, SM_TAP = SM_Z4 + 2 * ZP4, TAPS = 3328;
constexpr int SM_MB = SM_TAP + 5 * TAPS;
constexpr int SM_SC = SM_MB + 48;
constexpr int SM_KV = SM_SC + 80;
constexpr int SM_THR = SM_KV + 32;
constexpr int SM_SLOT = SM_THR + 48;
constexpr int SM_KEY = SM_SLOT + 32;
constexpr int SM_ST = SM_KEY + 64;
constexpr int SM_ST2 = SM_ST + 256;
constexpr int SM_RC = SM_ST2 + 256;
constexpr int SM_SP = SM_RC + 192;
constexpr int SM_AF = SM_SP + 1152, SM_SIL = SM_AF + 1152, SM_INV = SM_SIL + 1152, SM_END = SM_SP + 5760;
constexpr int SM_ONE = SM_MODS + 9 * 1152;
constexpr int SM_WD = SM_W, SM_XS = SM_W + 36864, SM_AC = SM_ZS, SM_RED = SM_AC + 6144;
constexpr int SM_TSB = SM_END, SM_TOTAL = SM_END + TSX - SM0;
static_assert(SM_W % 1024 == 0 && SM_TAP % 1024 == 0 && SM_MODS + 8 * KTAB <= SM_ZS && SM_ZS + 2 * KTAB <= SM_TAP && SM_RED + 10240 <= SM_TAP && SM_XS + 8 * ROW <= SM_ZS, "smem map");
static_assert(SM_MB % 16 == 0 && SM_THR % 16 == 0 && SM_ST % 16 == 0 && SM_SP % 16 == 0 && SM_TOTAL <= 232448, "smem map");
constexpr int TE = 4, TO = 276, T5 = 560, T3 = 624, T9E = 680, T7E = 760, TEO = 40;
#define MT 10
#define MKT 1
#define KST 128
#define DE1 1
#define DE2 4
#define DE3 5
#define OUTA 2
#define OUTB 7
#define PFW 1
#define PFU 0
#define KD 700
#define D0C 0
#define YE 104
#define YL 104
#define YD 250
#define OPTM 1
#define Y8 64
#define FH 0
#define FO 0
#define DB1 1
#define KD1 50
#define AD 0
#define PD 0
#define ZD 0
#define DD 1000
#define INCV 1
#define TPIN 0
#define A5P 1
#define SWJ 1
#define TG 0
#define TU 0
#define TW 0
#define KDB 520
#define KA 0
#define MB11 0
#define W8D 0
#define KE 64
#define PFP 200
#define GE 0
#define NB8 8
#define DX 0
#define DMOD 1000
#define PFG 1
constexpr int N1 = 320 + 32 * DB1 + 32 * !!KA, N12 = 288 + 32 * !DB1;
constexpr int SPIN = 1 << 16, NEARLY = 4;
constexpr u32 TAGM = 0x40004000u, TAGR = 0x40000000u, INVAL = 0x00004801u;

DEV u32 s2u(const void* p) { return (u32)__cvta_generic_to_shared(p); }
DEV void mma_bf(float (&c)[4], u32 a0, u32 a1, u32 a2, u32 a3, u32 b0, u32 b1) {
  asm("mma.sync.aligned.m16n8k16.row.col.f32.bf16.bf16.f32 {%0,%1,%2,%3},{%4,%5,%6,%7},{%8,%9},{%0,%1,%2,%3};"
      : "+f"(c[0]), "+f"(c[1]), "+f"(c[2]), "+f"(c[3]) : "r"(a0), "r"(a1), "r"(a2), "r"(a3), "r"(b0), "r"(b1));
}
DEV void mma_hf(float (&c)[4], u32 a0, u32 a1, u32 a2, u32 a3, u32 b0, u32 b1) {
  asm("mma.sync.aligned.m16n8k16.row.col.f32.f16.f16.f32 {%0,%1,%2,%3},{%4,%5,%6,%7},{%8,%9},{%0,%1,%2,%3};"
      : "+f"(c[0]), "+f"(c[1]), "+f"(c[2]), "+f"(c[3]) : "r"(a0), "r"(a1), "r"(a2), "r"(a3), "r"(b0), "r"(b1));
}
DEV void mma8_bf(float (&c)[4], u32 a0, u32 a1, u32 b0) {
  asm("mma.sync.aligned.m16n8k8.row.col.f32.bf16.bf16.f32 {%0,%1,%2,%3},{%4,%5},{%6},{%0,%1,%2,%3};"
      : "+f"(c[0]), "+f"(c[1]), "+f"(c[2]), "+f"(c[3]) : "r"(a0), "r"(a1), "r"(b0));
}
DEV void mma8_hf(float (&c)[4], u32 a0, u32 a1, u32 b0) {
  asm("mma.sync.aligned.m16n8k8.row.col.f32.f16.f16.f32 {%0,%1,%2,%3},{%4,%5},{%6},{%0,%1,%2,%3};"
      : "+f"(c[0]), "+f"(c[1]), "+f"(c[2]), "+f"(c[3]) : "r"(a0), "r"(a1), "r"(b0));
}
DEV u32 movm(u32 x) { u32 r; asm("movmatrix.sync.aligned.m8n8.trans.b16 %0,%1;" : "=r"(r) : "r"(x)); return r; }
DEV uint4 ldsm4(u32 a) { uint4 r; asm volatile("ldmatrix.sync.aligned.m8n8.x4.shared.b16 {%0,%1,%2,%3},[%4];" : "=r"(r.x), "=r"(r.y), "=r"(r.z), "=r"(r.w) : "r"(a)); return r; }
DEV uint4 ldsm4t(u32 a) { uint4 r; asm volatile("ldmatrix.sync.aligned.m8n8.x4.trans.shared.b16 {%0,%1,%2,%3},[%4];" : "=r"(r.x), "=r"(r.y), "=r"(r.z), "=r"(r.w) : "r"(a)); return r; }
DEV u32 lds32(u32 a) { u32 r; asm volatile("ld.volatile.shared.u32 %0,[%1];" : "=r"(r) : "r"(a)); return r; }
DEV uint2 lds64(u32 a) { uint2 r; asm volatile("ld.shared.v2.u32 {%0,%1},[%2];" : "=r"(r.x), "=r"(r.y) : "r"(a)); return r; }
DEV uint4 lds128(u32 a) { uint4 r; asm volatile("ld.shared.v4.u32 {%0,%1,%2,%3},[%4];" : "=r"(r.x), "=r"(r.y), "=r"(r.z), "=r"(r.w) : "r"(a)); return r; }
DEV void sts16(u32 a, u32 v) { asm volatile("st.shared.u16 [%0],%1;" ::"r"(a), "h"((unsigned short)v) : "memory"); }
DEV void sts32(u32 a, u32 v) { asm volatile("st.shared.u32 [%0],%1;" ::"r"(a), "r"(v) : "memory"); }
DEV void sts64(u32 a, u32 x, u32 y) { asm volatile("st.shared.v2.u32 [%0],{%1,%2};" ::"r"(a), "r"(x), "r"(y) : "memory"); }
DEV void sts128(u32 a, u32 x, u32 y, u32 z, u32 w) { asm volatile("st.shared.v4.u32 [%0],{%1,%2,%3,%4};" ::"r"(a), "r"(x), "r"(y), "r"(z), "r"(w) : "memory"); }
DEV uint4 ldr128(const void* p) { uint4 v; asm volatile("ld.relaxed.gpu.global.v4.u32 {%0,%1,%2,%3},[%4];" : "=r"(v.x), "=r"(v.y), "=r"(v.z), "=r"(v.w) : "l"(p) : "memory"); return v; }
DEV uint2 ldr64(const void* p) { uint2 v; asm volatile("ld.relaxed.gpu.global.v2.u32 {%0,%1},[%2];" : "=r"(v.x), "=r"(v.y) : "l"(p) : "memory"); return v; }
DEV u32 ldr32(const void* p) { u32 v; asm volatile("ld.relaxed.gpu.global.u32 %0,[%1];" : "=r"(v) : "l"(p) : "memory"); return v; }
DEV void str128(void* p, u32 x, u32 y, u32 z, u32 w) { asm volatile("st.relaxed.gpu.global.v4.u32 [%0],{%1,%2,%3,%4};" ::"l"(p), "r"(x), "r"(y), "r"(z), "r"(w) : "memory"); }
DEV void str64(void* p, u32 x, u32 y) { asm volatile("st.relaxed.gpu.global.v2.u32 [%0],{%1,%2};" ::"l"(p), "r"(x), "r"(y) : "memory"); }
DEV void str32(void* p, u32 x) { asm volatile("st.relaxed.gpu.global.u32 [%0],%1;" ::"l"(p), "r"(x) : "memory"); }
DEV void str16(void* p, u32 x) { asm volatile("st.relaxed.gpu.global.u16 [%0],%1;" ::"l"(p), "h"((unsigned short)x) : "memory"); }
DEV uint4 ldg128(const void* p) { uint4 v; asm volatile("ld.global.nc.v4.u32 {%0,%1,%2,%3},[%4];" : "=r"(v.x), "=r"(v.y), "=r"(v.z), "=r"(v.w) : "l"(p)); return v; }
DEV uint2 ldg64(const void* p) { uint2 v; asm volatile("ld.global.nc.v2.u32 {%0,%1},[%2];" : "=r"(v.x), "=r"(v.y) : "l"(p)); return v; }
DEV u32 ldg32(const void* p) { u32 v; asm volatile("ld.global.nc.u32 %0,[%1];" : "=r"(v) : "l"(p)); return v; }
DEV u32 ldg16(const void* p) { unsigned short v; asm volatile("ld.global.nc.u16 %0,[%1];" : "=h"(v) : "l"(p)); return v; }
#define bsync(id, n) asm volatile("bar.sync %0,%1;" ::"n"(id), "n"(n) : "memory")
#define barrive(id, n) asm volatile("bar.arrive %0,%1;" ::"n"(id), "n"(n) : "memory")
DEV void bsyncr(u32 id) { asm volatile("bar.sync %0,96;" ::"r"(id) : "memory"); }
DEV void barriver(u32 id) { asm volatile("bar.arrive %0,96;" ::"r"(id) : "memory"); }
constexpr u32 BW = 0x0FEA, BS = 0x6532;
DEV void mb_init(u32 a, u32 n) { asm volatile("mbarrier.init.shared.b64 [%0],%1;" ::"r"(a), "r"(n) : "memory"); }
DEV void mb_arrive(u32 a) { asm volatile("mbarrier.arrive.shared.b64 _,[%0];" ::"r"(a) : "memory"); }
DEV void mb_expect(u32 a, u32 bytes) { asm volatile("mbarrier.arrive.expect_tx.shared.b64 _,[%0],%1;" ::"r"(a), "r"(bytes) : "memory"); }
DEV void mb_wait(u32 a, u32 ph = 0) {
  u32 ok; int it = 0;
  do { asm volatile("{.reg .pred p; mbarrier.try_wait.parity.shared.b64 p,[%1],%2; selp.u32 %0,1,0,p;}" : "=r"(ok) : "r"(a), "r"(ph) : "memory"); } while (!ok && ++it < SPIN);
}
template <int N> DEV void bulk_out(void* dst, u32 src) { asm volatile("cp.async.bulk.global.shared::cta.bulk_group [%0],[%1],%2;" ::"l"(dst), "r"(src), "n"(N) : "memory"); }
constexpr u32 WSH = 41472;
DEV void l2_line(const void* p) { asm volatile("prefetch.global.L2 [%0];" ::"l"(p) : "memory"); }
template <int N> DEV void l2_pre(const void* p) { asm volatile("cp.async.bulk.prefetch.L2.global [%0],%1;" ::"l"(p), "n"(N) : "memory"); }
DEV void tma3d(u32 dst, const CUtensorMap* tm, u32 mb, int c0, int c2) {
  asm volatile("cp.async.bulk.tensor.3d.shared::cluster.global.mbarrier::complete_tx::bytes [%0],[%1,{%3,0,%4}],[%2];"
               ::"r"(dst), "l"((uint64_t)tm), "r"(mb), "r"(c0), "r"(c2) : "memory");
}
DEV float blo(u32 w) { return __uint_as_float(w << 16); }
DEV float bhi(u32 w) { return __uint_as_float(w & 0xffff0000u); }
DEV u32 pk_bf(float lo, float hi) { u32 r; asm("cvt.rn.bf16x2.f32 %0,%1,%2;" : "=r"(r) : "f"(hi), "f"(lo)); return r; }
DEV u32 pk_hf(float lo, float hi) { u32 r; asm("cvt.rn.f16x2.f32 %0,%1,%2;" : "=r"(r) : "f"(hi), "f"(lo)); return r; }
DEV float rbf(float x) { return __uint_as_float(pk_bf(0.f, x) & 0xffff0000u); }
DEV u32 bfma(u32 a, u32 b, u32 c) { u32 r; asm("fma.rn.bf16x2 %0,%1,%2,%3;" : "=r"(r) : "r"(a), "r"(b), "r"(c)); return r; }
DEV u32 bmul(u32 a, u32 b) { u32 r; asm("mul.rn.bf16x2 %0,%1,%2;" : "=r"(r) : "r"(a), "r"(b)); return r; }
DEV u32 badd(u32 a, u32 b) { u32 r; asm("add.rn.bf16x2 %0,%1,%2;" : "=r"(r) : "r"(a), "r"(b)); return r; }
DEV u32 hadd(u32 a, u32 b) { u32 r; asm("add.rn.f16x2 %0,%1,%2;" : "=r"(r) : "r"(a), "r"(b)); return r; }
DEV u32 hfma(u32 a, u32 b, u32 c) { u32 r; asm("fma.rn.f16x2 %0,%1,%2,%3;" : "=r"(r) : "r"(a), "r"(b), "r"(c)); return r; }
struct C2 { u32 re, im; };
DEV C2 cm2(C2 a, C2 b) {
  const __half2 ar = *reinterpret_cast<__half2*>(&a.re), ai = *reinterpret_cast<__half2*>(&a.im), br = *reinterpret_cast<__half2*>(&b.re), bi = *reinterpret_cast<__half2*>(&b.im);
  __half2 re = __hfma2(ar, br, __hneg2(__hmul2(ai, bi))), im = __hfma2(ar, bi, __hmul2(ai, br));
  return {*reinterpret_cast<u32*>(&re), *reinterpret_cast<u32*>(&im)};
}
DEV C2 pk2(const float2 (&a)[2]) { return {pk_hf(a[0].x, a[1].x), pk_hf(a[0].y, a[1].y)}; }
DEV C2 pk2c(const float2 (&a)[2]) { return {pk_hf(a[0].x, a[1].x), pk_hf(-a[0].y, -a[1].y)}; }
DEV u32 cpy(u32 x, u32 zr, int alt) {
  u32 r;
  if (alt) asm volatile("xor.b32 %0,%1,%2;" : "=r"(r) : "r"(x), "r"(zr)); else asm volatile("mad.lo.u32 %0,%2,%2,%1;" : "=r"(r) : "r"(x), "r"(zr));
  return r;
}
template <int N> DEV void inc(u32& x) { asm volatile("add.u32 %0,%0,%1;" : "+r"(x) : "n"(N)); }
DEV u32 opq(u32 x) { u32 r; asm volatile("mov.u32 %0,%1;" : "=r"(r) : "r"(x)); return r; }
DEV u32 chan(u32 b, u32 i) { return 16 * (b >> 2) + 2 * (b & 3) + (i & 1) + 4 * (i & 2); }
DEV u32 row16(u32 lane) { const u32 r0 = (lane & 7) + ((lane >> 3) & 1) + 8 * (lane >> 4) - 1; return (r0 ^ ((r0 >> 3) & 3)) * 16; }
DEV u32 clk() { u32 r; asm volatile("mov.u32 %0,%%clock;" : "=r"(r)::"memory"); return r; }
DEV void wait_clk(u32 t, int d) { while ((int)(clk() - t) < d); }
DEV float ex2(float x) { float r; asm("ex2.approx.ftz.f32 %0,%1;" : "=f"(r) : "f"(x)); return r; }
DEV float rcpf(float x) { float r; asm("rcp.approx.ftz.f32 %0,%1;" : "=f"(r) : "f"(x)); return r; }
DEV float2 cmul(float2 a, float2 b) { return make_float2(fmaf(a.x, b.x, -a.y * b.y), fmaf(a.x, b.y, a.y * b.x)); }
DEV float2 csq(float2 a) { return make_float2(fmaf(a.x, a.x, -a.y * a.y), (a.x + a.x) * a.y); }
DEV float2 cexp(float lr2, float th) {
  const float m = ex2(lr2);
  return make_float2(m * __cosf(th), m * __sinf(th));
}
DEV float silu_f(float v) { return v * rcpf(1.f + ex2(-1.4426950408889634f * v)); }
constexpr u32 B2P64 = 0x5F805F80u, B2M64 = 0x1F801F80u, BONE = 0x3F803F80u;
constexpr u32 MODJ = 18 * 128;
DEV float sqrta(float x) { float r; asm("sqrt.approx.ftz.f32 %0,%1;" : "=f"(r) : "f"(x)); return r; }
DEV u32 fu(float x) { return __float_as_uint(x); }
DEV float uf(u32 x) { return __uint_as_float(x); }
DEV void mma_hf_o(float (&d)[4], const float (&c)[4], const u32 (&a)[4], u32 b0, u32 b1) {
  asm("mma.sync.aligned.m16n8k16.row.col.f32.f16.f16.f32 {%0,%1,%2,%3},{%4,%5,%6,%7},{%8,%9},{%10,%11,%12,%13};"
      : "=f"(d[0]), "=f"(d[1]), "=f"(d[2]), "=f"(d[3]) : "r"(a[0]), "r"(a[1]), "r"(a[2]), "r"(a[3]), "r"(b0), "r"(b1), "f"(c[0]), "f"(c[1]), "f"(c[2]), "f"(c[3]));
}

DEV void mma_hf_t(float (&c)[4], const u32 (&a)[4], u32 b0, u32 b1) { mma_hf(c, a[0], a[1], a[2], a[3], b0, b1); }
DEV void cpa16(u32 dst, const void* src) { asm volatile("cp.async.cg.shared.global [%0],[%1],16;" ::"r"(dst), "l"(src) : "memory"); }
DEV void tm_pre(const CUtensorMap* tm) { asm volatile("prefetch.tensormap [%0];" ::"l"((uint64_t)tm) : "memory"); }
#define PROXY_FENCE() asm volatile("fence.proxy.async.shared::cta;" ::: "memory")
struct Prm {
  const char *la, *ai, *cr, *ci, *ldt;
  u32 zero;
  const char *x, *c;
  char* gs;
  const char *dsk, *wr, *wg, *wu, *wd;
  char* out;
};
constexpr float LOG2E = 1.4426950408889634f, F2P64 = 1.8446744073709552e19f, F2M64 = 5.421010862427522e-20f;

template <int S> DEV void y_store(float c0, float c1, float c2, float c3, u32 F, u32 pml, char* yp) {
  str32(yp, bmul(pk_bf(c0, c2), F) | pml);
  str32(yp + S, bmul(pk_bf(c1, c3), F) | pml);
}
DEV void merge4(u32 (&h)[8], uint4 a, uint4 b) {
  const u32 e1 = min(a.x, b.x), e2 = max(a.z, b.z), o1 = min(a.y, b.y), o2 = max(a.w, b.w), o0 = max(a.y, b.y), e3 = min(a.z, b.z);
  const u32 f1 = max(e1, e2), f2 = min(e1, e2), p1 = max(o1, o2), p2 = min(o1, o2);
  h[0] = max(a.x, b.x); h[1] = max(o0, f1); h[2] = min(o0, f1); h[3] = max(p1, f2); h[4] = min(p1, f2); h[5] = max(p2, e3); h[6] = min(p2, e3); h[7] = min(a.w, b.w);
}
DEV void top8(u32 (&a)[8], uint4 l, uint4 m) {
  u32 b[8];
  merge4(b, l, m);
#pragma unroll
  for (int i = 0; i < 8; i++) a[i] = max(a[i], b[7 - i]);
#pragma unroll
  for (int s = 4; s; s >>= 1)
#pragma unroll
    for (int i = 0; i < 8; i++) if (!(i & s)) { const u32 x = a[i], y = a[i + s]; a[i] = max(x, y); a[i + s] = min(x, y); }
}
#define POLL(load, cond_bad, code) { int it_ = 0; do { load; } while (__any_sync(~0u, (cond_bad)) & (++it_ <= SPIN)); if (it_ > SPIN) { ERRF(code); } TSN(code, it_); }
#define POLLW(load, cond_bad, code) { int it_ = 0; while (__any_sync(~0u, (cond_bad))) { if (++it_ > SPIN) { ERRF(code); break; } load; } TSN(code, it_); }

#define DOWN(E) if (tid == 288 && b < 108) { const u32 c0 = 64 * (b % 9), c2 = 4 * (b / 9); \
    if (!D0C && E == 1) { mb_expect(SM_MB + 24, 49152); tma3d(SM_TAP, tm_down, SM_MB + 24, c0, c2); } \
    if (DE1 == E) tma3d(SM_WD, tm_down, SM_MB + 24, c0, c2 + 1); \
    if (DE2 == E) tma3d(SM_WD + 12288, tm_down, SM_MB + 24, c0, c2 + 2); \
    if (DE3 == E) tma3d(SM_WD + 24576, tm_down, SM_MB + 24, c0, c2 + 3); }
#define OUTR(E) if (((OUTA == E) | (OUTB == E) << 1) & ot) { const u32 tl = 4 * ((lane >> 1) & 1) + ((lane >> 2) & 3) + 8 * (lane & 1); \
    bulk_out<1152>(p.out + (b * BLK + tl * 1152), SM_XST + ((lane & 2) + 4 * (lane & 1) + ((lane >> 2) & 1) + (lane & 8)) * ROW); \
    asm volatile("cp.async.bulk.commit_group;" ::: "memory"); }
DEV void ffn_tail(const Prm& p, const CUtensorMap* tm_down, uint4 (&A)[24], const u32 tid, const u32 b, const u32 par, const u32 ot) {
  const u32 w = tid >> 5, lane = tid & 31, g = lane >> 2, q = lane & 3, kq = w & 3, tg = w >> 2;
  const u32 rho = b & 1, pm = par ? TAGM : 0;
  char* const gs = p.gs;
  __syncthreads();
  TS(25);
  DOWN(5);
  {
    float c0[2][4] = {}, c1[2][4] = {};
    const u32 ba = SM_XS + (lane & 7) * ROW + (18 * kq + (lane >> 3)) * 16;
    uint4 bb[5];
#pragma unroll
    for (int s = 0; s < 5; s++) bb[s] = ldsm4(ba + s * 64);
#pragma unroll
    for (int s = 0; s < 9; s++) mma_bf(c0[s & 1], A[s].x, A[s].y, A[s].z, A[s].w, s & 1 ? bb[s >> 1].z : bb[s >> 1].x, s & 1 ? bb[s >> 1].w : bb[s >> 1].y);
    const u32 ra = SM_RED + (8 * tg + kq) * 512 + lane * 16;
    if (tg < 2) {
#pragma unroll
      for (int s = 0; s < 9; s++) mma_bf(c1[s & 1], A[9 + s].x, A[9 + s].y, A[9 + s].z, A[9 + s].w, s & 1 ? bb[s >> 1].z : bb[s >> 1].x, s & 1 ? bb[s >> 1].w : bb[s >> 1].y);
      sts128(ra + 2048, fu(c1[0][0] + c1[1][0]), fu(c1[0][1] + c1[1][1]), fu(c1[0][2] + c1[1][2]), fu(c1[0][3] + c1[1][3]));
    }
    sts128(ra, fu(c0[0][0] + c0[1][0]), fu(c0[0][1] + c0[1][1]), fu(c0[0][2] + c0[1][2]), fu(c0[0][3] + c0[1][3]));
  }
  TS(39);
  __syncthreads();
  const u32 tr = clk();
  OUTR(6);
  if (w - 3 - rho < 5 - rho) {
    const u32 t = 7 - w;
    float s[4] = {};
#pragma unroll
    for (int i = 0; i < 4; i++) { const uint4 u = lds128(SM_RED + (t * 4 + i) * 512 + lane * 16); s[0] += uf(u.x); s[1] += uf(u.y); s[2] += uf(u.z); s[3] += uf(u.w); }
    const u32 sg = pk_bf(silu_f(rbf(s[0])), silu_f(rbf(s[1])));
    const u32 act = movm(bmul(bmul(sg, pk_bf(s[2], s[3])), B2M64));
    str32(gs + (G_ACT + (t < 4 ? 4 * b + t : 512 + (b >> 1)) * 128 + lane * 4), act | (q ? 0 : pm));
  }
  TS(26);
  if (b < 108) {
    const char* src = gs + (G_ACT + (b / 9) * 6144 + tid * 16);
    uint4 a;
    if (AD) a.x = INVAL; else a = ldr128(src);
    if (AD && w >= 4) wait_clk(tr, AD);
    if (w < 4) {
      const u32 aa = SM_WD + (8 * (lane >> 4) + (lane & 7)) * 128 + (((2 * w + ((lane >> 3) & 1)) ^ (lane & 7)) << 4);
      mb_wait(SM_MB + 24);
#pragma unroll
      for (int s = 0; s < 24; s++) A[s] = ldsm4t(aa + (s < 6 ? SM_TAP - SM_WD : -12288) + s * 2048);
    }
    TS(28);
    POLLW(a = ldr128(src), (a.x ^ pm) & TAGM, 9);
    sts128(SM_AC + tid * 16, a.x & ~TAGM, a.y, a.z, a.w);
    TS(27);
    if (w < 4) {
      bsync(8, 384);
      float c[4][4] = {};
#pragma unroll
      for (int s = 0; s < 12; s++) {
        const uint4 bb = ldsm4(SM_AC + lane * 16 + s * 512);
        mma_bf(c[2 * (s & 1)], A[2 * s].x, A[2 * s].y, A[2 * s].z, A[2 * s].w, bb.x, bb.y);
        mma_bf(c[2 * (s & 1) + 1], A[2 * s + 1].x, A[2 * s + 1].y, A[2 * s + 1].z, A[2 * s + 1].w, bb.z, bb.w);
      }
      char* dst = gs + (G_PART + b * 2048 + w * 512 + lane * 8);
      u32 o[4];
#pragma unroll
      for (int i = 0; i < 4; i++) o[i] = (fu(((c[0][i] + c[1][i]) + (c[2][i] + c[3][i])) * F2P64) & ~1u) | par;
      str64(dst, o[0], o[1]); str64(dst + 256, o[2], o[3]);
      TS(29);
    } else barrive(8, 384);
  }
  OUTR(7);
  if (w == 8 && b < 72) {
    const u32 ta = clk();
    const u32 kg = lds32(SM_SLOT + 4 * g), ro = (2047 - ((kg >> 2) & 2047)) * 1152 + 16 * b;
    const char* src = gs + (G_PART + (b >> 3) * 2048 + (b & 7) * 256 + lane * 8);
    const char* xs = gs + (G_Y + ro);
    uint4 xt;
    POLL(xt = ldr128(xs), (xt.x ^ TAGR) & TAGM, 10);
    const u32 x1w = (q & 2) ? ((q & 1) ? xt.w : xt.z) : ((q & 1) ? xt.y : bmul(xt.x ^ TAGR, B2P64));
    const u32 gw = lds32(SM_MODS + 5760 + 16 * b + 4 * q);
    const u32 hw = lds32(SM_XS + g * ROW + b * 16 + q * 4);
    const float sgm = rcpf(1.f + ex2(-LOG2E * bhi(kg ^ (~((int)kg >> 31) | 0x80000000))));
    char* const dst = p.out + (ro + 4 * q);
    uint2 v[12];
#pragma unroll
    for (int j = 0; j < 12; j++) v[j] = make_uint2(1, 0);
    u32 bad;
    if (PD) wait_clk(ta, PD);
    POLL({ bad = 0; _Pragma("unroll") for (int j = 0; j < 12; j++) { if (((v[j].x ^ par) | (v[j].y ^ par)) & 1) v[j] = ldr64(src + j * 9 * 2048); }
           _Pragma("unroll") for (int j = 0; j < 12; j++) bad |= (v[j].x ^ par) | (v[j].y ^ par); }, bad & 1, 11);
    float s0[4] = {}, s1[4] = {};
#pragma unroll
    for (int j = 0; j < 12; j++) { s0[j & 3] += uf(v[j].x); s1[j & 3] += uf(v[j].y); }
    const u32 y = movm(pk_bf((s0[0] + s0[1]) + (s0[2] + s0[3]), (s1[0] + s1[1]) + (s1[2] + s1[3])));
    *(u32*)dst = badd(x1w, bmul(gw, badd(hw, bmul(y, pk_bf(sgm, sgm)))));
    if (b == 0 && lane == 0) str32(gs + G_EP, par);
    TS(30); TSE();
  }
  if (w == 10) asm volatile("cp.async.bulk.wait_group.read 0;" ::: "memory");
}

DEV u32 y_off(u32 tid, u32 b) { return G_Y + (16 * (tid >> 5) + 8 * ((tid >> 1) & 1) + ((tid >> 2) & 4)) * BLK + b * 128 + ((tid >> 2) & 3) * 32 + (tid & 1) * 16; }
DEV void post_conv(const Prm& p, const CUtensorMap* tm_down, const u32 tid, const u32 b) {
  const u32 w = tid >> 5, lane = tid & 31;
  const u32 g = lane >> 2, q = lane & 3, e = g >> 2, h = (g >> 1) & 1, hi = g & 1;
  const u32 pm = lds32(SM_THR + 4), par = pm >> 30;
  char* const gs = p.gs;
  const u32 cho = 128 * w + 64 * e + 16 * q;
  u32 x1[4][4], h2[4][4], key[4], lt;
  char* const rowp = gs + (b * BLK + (4 * h + 8 * hi) * 1152 + cho);
  u32 ot = 0;
  uint4 A[24];
#define AROW(t) const u32 arow = 144 * ((t >> 5) & 3) + ((t >> 1) & 8) + (t & 7), ab = (t & 8) ? SM_UP : SM_GATE;
#define AFRAG9() { _Pragma("unroll") for (int s = 0; s < 9; s++) A[s] = ldsm4t(ab + SLV + arow * 16 + s * 256); }
#define AFRAG18() { const u32 t3 = opq(tid); AROW(t3); if (t3 < 256) { const u32 aa = ab + arow * 64 + ((((t3 >> 6) & 2) ^ ((t3 & 7) >> 1)) << 4); \
      _Pragma("unroll") for (int s = 0; s < 9; s++) { A[s] = ldsm4t(aa + s * 1024); A[9 + s] = ldsm4t((aa ^ 16) + s * 1024); } } else AFRAG9(); }
  if (w < 9) {
    const u32 yc = 8 * (q >> 1) + 2 * (g >> 1), y1 = w < 8 ? BLK : 4 * BLK, y2 = 2 * y1;
    const char* ysrc = gs + (w < 8 ? y_off(tid, b) : G_Y + (q & 1) * 16 + (8 * yc + 2 * hi + ((b >> 4) & 1)) * BLK + 16384 + ((b >> 5) * 16 + (b & 15)) * 32);
    const char* const ys[4] = {ysrc, ysrc + y1, ysrc + y2, ysrc + (y1 + y2)};
    u32 tc = clk();
    uint4 yv[4];
#pragma unroll
    for (int v = 0; v < 4; v++) yv[v].x = INVAL;
    if (w < 4 && b < YL) {
#pragma unroll
      for (int v = 0; v < 4; v++) yv[v] = ldr128(ys[v]);
    }
    if (w == 8) { bsync(7, 160); tc = clk(); }
    const u32 ma = SM_MODS + cho, xa = SM_XST + (2 * h + 4 * hi) * ROW + cho;
    const uint4 sa = lds128(ma), ca = lds128(ma + 1152), ga = lds128(ma + 2304);
    const uint4 rb = lds128((g & 2) ? SM_ONE + 16 * hi : (ma ^ 64) + 8064 + 1152 * hi);
    const u32 saw[4] = {sa.x, sa.y, sa.z, sa.w}, caw[4] = {ca.x, ca.y, ca.z, ca.w}, gaw[4] = {ga.x, ga.y, ga.z, ga.w};
#pragma unroll
    for (int k = 0; k < 4; k++) {
      const uint2 st = lds64(SM_ST + 16 * (2 * h + 4 * hi + (k & 1) + 8 * (k >> 1)));
      const uint4 xv = lds128(xa + ((k & 1) + 8 * (k >> 1)) * ROW);
      x1[k][0] = xv.x; x1[k][1] = xv.y; x1[k][2] = xv.z; x1[k][3] = xv.w;
#pragma unroll
      for (int v = 0; v < 4; v++) x1[k][v] = badd(x1[k][v], bfma(bmul(badd(x1[k][v], st.x), st.y), caw[v], saw[v]));
    }
    const bool own = (q >> 1) == e;
    const u32 spw = SM_SP + (2 * w + e) * 320 + (g & 3) * 16 + (own ? ((q & 1) == h ? 4 : 12) : 8 - 8 * (q & 1));
    if (w >= 4) {
      if (b < (w < 8 ? YE : Y8)) {
        if (W8D && w == 8 && b >= 64) wait_clk(tc, W8D);
        TS(18);
#pragma unroll
        for (int v = 0; v < 4; v++) yv[v] = ldr128(ys[v]);
      }
      bsync(12, N12);
      tc = clk();
    }
    if (b >= YL) wait_clk(tc, YD);
    TS(13);
    POLLW(_Pragma("unroll") for (int v = 0; v < 4; v++) if ((yv[v].x ^ pm) & TAGM) yv[v] = ldr128(ys[v]),
          ((yv[0].x ^ pm) | (yv[1].x ^ pm) | (yv[2].x ^ pm) | (yv[3].x ^ pm)) & TAGM, 5);
    TS(19);
    if (w < 4) asm volatile("setmaxnreg.dec.sync.aligned.u32 168;");
#pragma unroll
    for (int k = 0; k < 4; k += 2) {
      float X[4] = {}, Y[4] = {}, R[4] = {};
#pragma unroll
      for (int v = 0; v < 4; v++) {
        const u32 y0 = k ? yv[v].z : yv[v].x & ~TAGM, y1 = k ? yv[v].w : yv[v].y;
        x1[k][v] = bfma(movm(y0), gaw[v], x1[k][v]);
        x1[k + 1][v] = bfma(movm(y1), gaw[v], x1[k + 1][v]);
        mma8_bf(X, x1[k][v], x1[k + 1][v], x1[k][v]); mma8_bf(Y, x1[k][v], x1[k + 1][v], x1[k + 1][v]);
        if (v & 1) mma_bf(R, x1[k][v - 1], x1[k + 1][v - 1], x1[k][v], x1[k + 1][v], v & 2 ? rb.z : rb.x, v & 2 ? rb.w : rb.y);
      }
      sts32(spw + k * 64, fu(own ? (hi ? X[1] : X[0]) : R[0] + R[1]));
      sts32(spw + k * 64 + 64, fu(own ? (hi ? Y[3] : Y[2]) : R[2] + R[3]));
    }
    barrive(1, N1);
    TS(36);
    const uint4 sb = lds128(ma + 3456), cb = lds128(ma + 4608), gb = lds128(ma + 5760);
    const u32 sbw[4] = {sb.x, sb.y, sb.z, sb.w}, cbw[4] = {cb.x, cb.y, cb.z, cb.w}, gbw[4] = {gb.x, gb.y, gb.z, gb.w};
    bsync(2, 320);
    TS(37);
    lt = lds32(SM_THR);
#pragma unroll
    for (int k = 0; k < 4; k++) {
      const uint4 st = lds128(SM_ST2 + 64 * k + 16 * (g & 3));
      key[k] = st.w;
      u32 o[4];
#pragma unroll
      for (int v = 0; v < 4; v++) {
        const u32 d = badd(x1[k][v], st.x), z = bfma(d, st.y, bmul(d, st.z));
        h2[k][v] = FH ? bfma(z, cbw[v], sbw[v]) : badd(bmul(z, cbw[v]), sbw[v]);
        o[v] = FO ? bfma(gbw[v], h2[k][v], x1[k][v]) : badd(x1[k][v], bmul(gbw[v], h2[k][v]));
      }
      h2[k][0] = bmul(h2[k][0], B2M64) | TAGR;
      if (key[k] >= lt) str128(rowp + k * 1152, h2[k][0], h2[k][1], h2[k][2], h2[k][3]);
      sts128(xa + ((k & 1) + 8 * (k >> 1)) * ROW, o[0], o[1], o[2], o[3]);
    }
    barrive(3, 320);
    TS(21);
    asm volatile("setmaxnreg.inc.sync.aligned.u32 168;");
    mb_wait(SM_MB + 8); mb_wait(SM_MB + 16);
    AFRAG18();
    TS(22);
    bsync(6, 352);
    TS(24);
    const u32 g8 = lds32(SM_SLOT + 28);
    const u32 sk = lds32(SM_SLOT + 4 * (w & 7));
    const char* rs_ = gs + (((~sk >> 2) & 2047) * 1152 + lane * 16);
    uint4 rv[3];
    rv[0].x = rv[1].x = rv[2].x = TAGR;
    if (w < 8) { rv[0] = ldr128(rs_); rv[1] = ldr128(rs_ + 512); if (lane < 8) rv[2] = ldr128(rs_ + 1024); barrive(15, 320); }
    const u32 km = max(max(key[0], key[1]), max(key[2], key[3]));
    if (__any_sync(~0u, km >= g8 && lt > g8)) {
#pragma unroll
      for (int k = 0; k < 4; k++) if (key[k] >= g8 && key[k] < lt) str128(rowp + k * 1152, h2[k][0], h2[k][1], h2[k][2], h2[k][3]);
    }
    bsync(5, 352);
    const u32 sf = lds32(SM_SLOT + 4 * (w & 7)), f8 = lds32(SM_SLOT + 28);
    if (sf != sk && w < 8) { rs_ = gs + (((~sf >> 2) & 2047) * 1152 + lane * 16); rv[0].x = INVAL; }
    if (__any_sync(~0u, km >= f8)) {
#pragma unroll
      for (int k = 0; k < 4; k++) if (key[k] >= f8) str128(rowp + (G_Y + k * 1152), bmul(x1[k][0], B2M64) | TAGR, x1[k][1], x1[k][2], x1[k][3]);
    }
    POLLW({ rv[0] = ldr128(rs_); rv[1] = ldr128(rs_ + 512); if (lane < 8) rv[2] = ldr128(rs_ + 1024); },
          ((rv[0].x ^ TAGR) | (rv[1].x ^ TAGR) | (rv[2].x ^ TAGR)) & TAGM, 8);
    TS(38);
#pragma unroll
    for (int j = 0; j < 3; j++) if (w < 8 && (j < 2 || lane < 8)) sts128(SM_XS + w * ROW + lane * 16 + j * 512, bmul(rv[j].x ^ TAGR, B2P64), rv[j].y, rv[j].z, rv[j].w);
  } else {
    u32 ok, lr;
    if (w == 10) {
      uint2 rc = lds64(SM_RC + 8 * min(lane, 17u));
      float r1 = lane < 18 ? uf(rc.x) : 0.f, r2 = lane < 18 ? uf(rc.y) : 0.f;
#pragma unroll 1
      for (int o = 16; o; o >>= 1) { r1 += __shfl_xor_sync(~0u, r1, o); r2 += __shfl_xor_sync(~0u, r2, o); }
      const u32 tl = 4 * ((lane >> 1) & 1) + ((lane >> 2) & 3) + 8 * (lane & 1), kl = (2047 - 16 * b - tl) << 2 | par * 3;
      char* const kp = gs + (G_KEY + b * KST);
      const u32 spr = SM_SP + (lane >> 4) * 9 * 320 + (lane & 15) * 16;
      TS(31);
      bsync(1, N1);
      float S1 = 0.f, S2 = 0.f, S3 = 0.f;
#pragma unroll
      for (int i = 0; i < 9; i++) { uint4 t = lds128(spr + i * 320); S1 += uf(t.x); S2 += uf(t.y); S3 += uf(t.z); }
      S1 += __shfl_xor_sync(~0u, S1, 16); S2 += __shfl_xor_sync(~0u, S2, 16); S3 += __shfl_xor_sync(~0u, S3, 16);
      const float mu = S1 * (1.f / 576.f), var = fmaxf(fmaf(-mu, mu, S2 * (1.f / 576.f)), 0.f);
      const float m = rbf(mu), rs = rcpf(rbf(sqrta(rbf(rbf(var) + 1e-5f))));
      const u32 rb = pk_bf(0.f, fmaf(fmaf(-m, r1, S3), rs, r2) + 0.f);
      ok = ((rb ^ (((int)rb >> 31) | 0x80000000)) & 0xffff0000u) | kl;
      const float rh = rbf(rs);
      sts32(SM_KEY + 4 * (lane & 15), ok);
      sts128(SM_ST2 + 16 * (lane & 15), pk_bf(-m, -m), pk_bf(rh, rh), pk_bf(rs - rh, rs - rh), ok);
      __syncwarp();
      const uint4 o0 = lds128(SM_KEY + 2 * (lane & 16)), o1 = lds128(SM_KEY + 2 * (lane & 16) + 16);
      lr = (o0.x > ok) + (o0.y > ok) + (o0.z > ok) + (o0.w > ok) + (o1.x > ok) + (o1.y > ok) + (o1.z > ok) + (o1.w > ok);
      lr += __shfl_xor_sync(~0u, lr, 16);
      if (lane < 16 && lr < 8) str32(kp + 4 * lr, ok);
      if (lr == (b < NB8 ? 7 : NEARLY - 1)) sts32(SM_THR, ok);
      barrive(2, 320);
      if (!KA) barrive(4, 64);
      TS(20);
    } else if (w == 9) {
      if (DB1) bsync(1, N1); else { bsync(12, N12); wait_clk(clk(), DD); }
      PROXY_FENCE();
      DOWN(1);
    } else {
      const char* ks = gs + (G_KEY + (lane >> 1) * KST + (lane & 1) * 16);
      const u32 kt = par * 3;
      uint4 L[8];
      u32 H[8];
#define KBAD(j) ((L[j].x ^ kt) & 3)
#define KLD(j) L[j] = ldr128(ks + j * 16 * KST)
#pragma unroll
      for (int j = 0; j < 8; j++) L[j].x = INVAL;
      if (KA) bsync(1, N1); else bsync(4, 64);
      wait_clk(clk(), KA + (b < KE ? KD : b < YL ? KDB : KD1));
      TS(34);
      POLL({ _Pragma("unroll") for (int j = 0; j < 8; j++) if (KBAD(j)) KLD(j);
             merge4(H, L[0], L[1]); top8(H, L[2], L[3]);
             asm volatile("" : "+r"(H[0]), "+r"(H[1]), "+r"(H[2]), "+r"(H[3]), "+r"(H[4]), "+r"(H[5]), "+r"(H[6]), "+r"(H[7])); TS(32); },
           KBAD(0) | KBAD(1) | KBAD(2) | KBAD(3) | KBAD(4) | KBAD(5), 6);
      top8(H, L[4], L[5]);
      TS(35);
#pragma unroll 1
      for (u32 pass = p.zero;; pass++) {
        u32 G[8], m[8];
#pragma unroll
        for (int i = 0; i < 8; i++) G[i] = H[i];
#pragma unroll
        for (int r = 0; r < 8; r++) {
          const u32 h0 = G[0];
          m[r] = __reduce_max_sync(~0u, h0);
          if (r == 0) { if (KBAD(6)) KLD(6); if (KBAD(7)) KLD(7); }
          if (r < 7) asm("{.reg .u32 t; sub.u32 t,%1,%2; min.u32 t,t,1; mad.lo.u32 %0,t,%3,%4;}" : "=r"(G[0]) : "r"(m[r]), "r"(h0), "r"(h0 - G[1]), "r"(G[1]));
#pragma unroll
          for (int i = 1; i < 7 - r; i++) G[i] = h0 == m[r] ? G[i + 1] : G[i];
          if ((r & 3) == 3) sts128(SM_SLOT + 4 * r - 12, m[r - 3], m[r - 2], m[r - 1], m[r]);
        }
        asm volatile("{.reg .pred p; setp.eq.u32 p,%0,0; @p bar.arrive 6,352;}" ::"r"(pass) : "memory");
        if (pass) break;
        TS(23);
        POLLW({ if (KBAD(6)) KLD(6); if (KBAD(7)) KLD(7); }, KBAD(6) | KBAD(7), 7);
        if (!__any_sync(~0u, max(L[6].x, L[7].x) > m[7])) break;
        top8(H, L[6], L[7]);
      }
      barrive(5, 352);
      TS(33);
    }
    asm volatile("setmaxnreg.inc.sync.aligned.u32 168;");
    mb_wait(SM_MB + 8); mb_wait(SM_MB + 16);
    AROW(tid);
    AFRAG9();
    TS(22);
    if (w == 10) {
      bsync(3, 320);
      PROXY_FENCE();
      ot = lane < 16 && lr >= 8;
      OUTR(2);
      bsync(6, 352);
      bsync(15, 320);
      bsync(5, 352);
      if (lane < 16 && lr < 8 && ok < lds32(SM_SLOT + 28)) ot = 2;
      OUTR(4);
    } else if (w == 9) {
      bsync(15, 320);
      DOWN(4);
      TS(13);
    }
  }
  ffn_tail(p, tm_down, A, tid | p.zero, b, par, ot);
}

__global__ void __launch_bounds__(384, 1)
fused_kernel(const Prm p, const __grid_constant__ CUtensorMap tm_mod, const __grid_constant__ CUtensorMap tm_gate, const __grid_constant__ CUtensorMap tm_gs,
             const __grid_constant__ CUtensorMap tm_up, const __grid_constant__ CUtensorMap tm_us, const __grid_constant__ CUtensorMap tm_down) {
  extern __shared__ __align__(1024) unsigned char smem[];
  u32 la, ai, ldt; uint2 cr, ci;
  {
    const u32 t = threadIdx.x, d = t < 256 ? chan(blockIdx.x, t >> 5) : 512 + (blockIdx.x >> 1), o = d * 256 + 8 * (t & 31), o4 = o + ((t < 256 ? t >> 5 : t >> 3) & 4);
    asm volatile("{.reg .pred p; .reg .u16 h; setp.ne.u32 p,%7,0; @p ld.global.nc.u32 %0,[%8]; @p ld.global.nc.u32 %1,[%9]; @p ld.global.nc.v2.u32 {%2,%3},[%10];"
                 "@p ld.global.nc.v2.u32 {%4,%5},[%11]; @p ld.global.nc.u16 h,[%12]; cvt.u32.u16 %6,h;}"
                 : "=r"(la), "=r"(ai), "=r"(cr.x), "=r"(cr.y), "=r"(ci.x), "=r"(ci.y), "=r"(ldt)
                 : "r"(0x6ffu >> (t >> 5) & 1), "l"(p.la + o4), "l"(p.ai + o4), "l"(p.cr + o), "l"(p.ci + o), "l"(p.ldt + 2 * d));
  }
  const u32 t0 = clk();
  const u32 tid = __shfl_sync(~0u, threadIdx.x, threadIdx.x & 31), b = blockIdx.x + p.zero;
  const u32 w = tid >> 5, lane = tid & 31;
  const u32 g = lane >> 2, q = lane & 3, hi = g & 1;
  const u32 rho = b & 1, Ps = 512 + (b >> 1);
  char* const gs = p.gs;
  TS0();
  const bool kw = w != 8 && w != 11;
  const u32 ksig = w < 8 ? (w & 3) : 4, khf = w < 8 ? (w >> 2) : (w & 1);
  if (!kw) {
    if (tid == 352) {
#pragma unroll
      for (int i = 0; i < 5; i++) mb_init(SM_MB + 8 * i, i < 4 ? 1 : 64);
      asm volatile("fence.mbarrier_init.release.cluster;" ::: "memory");
      tm_pre(&tm_mod);
    }
    const char* cp = p.c + (576 * (w & 1) + 24 * min(lane, 23u));
    const uint2 c0 = ldg64(cp);
    la = c0.x; ai = c0.y; cr = ldg64(cp + 8); ci = ldg64(cp + 16);
  }
  const u32 zr = tid >> 16;
  const u32 epv = ldr32(gs + (G_EP + zr));
  const u32 tp = SM_TAP + ksig * TAPS;
  if (kw && !khf) {
#pragma unroll 1
    for (u32 i = lane * 16; i < TAPS; i += 512) sts128(tp + i, 0, 0, 0, 0);
  }
  if (tid < 128) sts128(SM_INV + 16 * tid, INVAL, 0, 1, 0);
  if (tid >= 252) str128(gs + (tid >= 380 ? G_MOD + b * 128 + q * 16 : b * BLK + 16384 - 252 * 16 + tid * 16), INVAL, 0, 1, 0);
  if (tid == 352 && b < 36) { while (clk() - t0 < DMOD); mb_expect(SM_MB, 36864); tma3d(SM_UP, &tm_mod, SM_MB, 32 * b, 0); }
  if (w < 9) {
    while ((int)(clk() - t0) < DX);
    const char* xp = p.x + (b * BLK + (lane >> 3) * 1152 + 128 * w + 16 * (lane & 7));
    const u32 xd = SM_XST + (((lane >> 3) & 1) + 8 * (lane >> 4)) * ROW + 128 * w + 16 * (lane & 7);
#pragma unroll
    for (int i = 0; i < 4; i++) cpa16(xd + 2 * ROW * i, xp + 4608 * i);
  }
  const u32 ktab = w < 8 ? SM_MODS + w * KTAB : SM_ZS + (w - 9) * KTAB;
  float k2048 = 0.f;
  if (kw) {
    u32 mx = __vmaxu2(__vmaxu2(cr.x & 0x7fff7fff, cr.y & 0x7fff7fff), __vmaxu2(ci.x & 0x7fff7fff, ci.y & 0x7fff7fff));
    const u32 E = max(__reduce_max_sync(~0u, max(mx & 0xffff, mx >> 16)) >> 7, 8u);
    TS(1);
    const float dt = rbf(ex2(blo(ldt) * LOG2E)), csc = uf((257 - E) << 23 | (fu(dt) & 0x7fffff));
    sts32(SM_SC + 16 * ksig + 12, fu(uf(fu(dt) & 0x7f800000) * uf((E - 2) << 23)));
    const u32 crw = khf ? cr.y : cr.x, ciw = khf ? ci.y : ci.x;
    float2 C[2], w4[2], w8[2], w16[2], w32[2], w64[2], w128[2], w256[2], w512[2], a1[2], a2[2], a3[2], t0[2], t1[2], s3[2];
#pragma unroll
    for (int m = 0; m < 2; m++) {
      const float lr2 = rbf(ex2((m ? bhi(la) : blo(la)) * LOG2E)) * dt * -LOG2E, th = (m ? bhi(ai) : blo(ai)) * dt;
      C[m] = make_float2((m ? bhi(crw) : blo(crw)) * csc, (m ? bhi(ciw) : blo(ciw)) * csc);
      const float2 w1 = cexp(lr2, th), w2 = csq(w1);
      w64[m] = cexp(64.f * lr2, 64.f * th);
      w4[m] = csq(w2); w8[m] = csq(w4[m]); w16[m] = csq(w8[m]); w32[m] = csq(w16[m]);
      w128[m] = csq(w64[m]); w256[m] = csq(w128[m]); w512[m] = csq(w256[m]);
      const float2 w1024 = csq(w512[m]);
      a1[m] = cmul(C[m], w1); a2[m] = cmul(C[m], w2); a3[m] = cmul(a1[m], w2);
      t0[m] = cmul(C[m], w1024); t1[m] = cmul(t0[m], w128[m]); s3[m] = cmul(w8[m], w16[m]);
      k2048 += fmaf(t0[m].x, w1024.x, -t0[m].y * w1024.y);
    }
    C2 B0[8], B1[8], B2[8], S[8];
    B0[0] = pk2(C); B0[1] = pk2(a1); B0[2] = pk2(a2); B0[3] = pk2(a3);
    const C2 h4 = pk2(w4), h256 = pk2(w256), h512 = pk2(w512);
#pragma unroll
    for (int i = 0; i < 4; i++) B0[4 + i] = cm2(B0[i], h4);
#pragma unroll
    for (int i = 0; i < 4; i++) B1[i] = cm2(B0[2 * i], h256);
    B1[4] = cm2(B0[0], h512); B1[5] = cm2(B0[4], h512);
    B1[6] = cm2(B1[4], h256); B1[7] = cm2(B1[5], h256);
    const u32 ta = ktab + lane * 128, f = ((lane & 3) << 5) | ((lane & 4) << 2);
#pragma unroll
    for (int i = 0; i < 8; i++) sts128(ta + ((i << 4) ^ f), B0[i].re, B0[i].im, B1[i].re, B1[i].im);
    B2[0] = pk2(t0); B2[1] = pk2(t1);
    B2[2] = cm2(B2[0], h256); B2[3] = cm2(B2[1], h256);
#pragma unroll
    for (int i = 0; i < 4; i++) B2[4 + i] = cm2(B2[i], h512);
    S[0] = {0x3C003C00u, 0u}; S[1] = pk2c(w8); S[2] = pk2c(w16); S[3] = pk2c(s3); S[4] = pk2c(w32);
#pragma unroll
    for (int i = 1; i < 4; i++) S[4 + i] = cm2(S[i], S[4]);
#pragma unroll
    for (int i = 0; i < 8; i++) sts128(ta + 4096 + ((i << 4) ^ f), B2[i].re, B2[i].im, S[i].re, S[i].im);
    const C2 m64 = pk2c(w64), m128 = pk2c(w128);
    sts128(ktab + 8192 + lane * 16, m64.re, m64.im, m128.re, m128.im);
    __syncwarp();
  } else {
    u32 sa = SM_SIL + 576 * (w & 1) + 24 * min(lane, 23u);
#pragma unroll 1
    for (int j = 0; j < 6; j++) {
      sts32(sa, pk_bf(silu_f(blo(la)), silu_f(bhi(la))));
      la = ai; ai = cr.x; cr.x = cr.y; cr.y = ci.x; ci.x = ci.y; sa += 4;
    }
    bsync(7, 64);
  }
  TS(2);
  const u32 pm = (__reduce_or_sync(~0u, epv) & 1) ? 0 : TAGM;
  sts32(SM_THR + 4, pm);
  if (w < 9) {
    asm volatile("cp.async.wait_all;" ::: "memory");
    __syncwarp();
    TS(4);
    if (tid == 256 && b >= 36 && b < 108) { mb_expect(SM_MB, 36864); tma3d(SM_UP, &tm_mod, SM_MB, 32 * b, 0); }
    const u32 xa = SM_XST + (lane & 15) * ROW + 128 * w + 16 * (lane >> 4);
    float s[4] = {}, X[2][4] = {}, Y[2][4] = {};
#pragma unroll
    for (int j = 0; j < 4; j++) {
      const uint4 a = ldsm4(xa + 32 * j);
      mma8_bf(X[0], a.x, a.y, a.x); mma8_bf(Y[0], a.x, a.y, a.y);
      mma8_bf(X[1], a.z, a.w, a.z); mma8_bf(Y[1], a.z, a.w, a.w);
      mma_bf(s, a.x, a.y, a.z, a.w, BONE, BONE);
    }
    uint4 t[4];
#pragma unroll
    for (int j = 0; j < 4; j++) t[j] = ldsm4t(xa + 32 * j);
    const float u0 = hi ? X[0][1] + X[1][1] : X[0][0] + X[1][0], u1 = hi ? Y[0][3] + Y[1][3] : Y[0][2] + Y[1][2];
    if (q == g >> 1) sts128(SM_SP + w * 128 + g * 16, fu(s[0]), fu(u0), fu(s[2]), fu(u1));
    bsync(1, 288);
    TS(7);
    const u32 spr = SM_SP + (lane & 7) * 16 + (lane & 8);
    const uint2 t8 = lds64(spr + 1024);
    const float f8 = lane < 16 ? 1.f : 0.f;
    float S1 = uf(t8.x) * f8, S2 = uf(t8.y) * f8;
#pragma unroll
    for (int i = 0; i < 4; i++) { const uint2 u = lds64(spr + (lane & 16) * 32 + i * 128); S1 += uf(u.x); S2 += uf(u.y); }
    S1 += __shfl_xor_sync(~0u, S1, 16); S2 += __shfl_xor_sync(~0u, S2, 16);
    const float mu = S1 * (1.f / 576.f), var = fmaxf(fmaf(-mu, mu, S2 * (1.f / 576.f)), 0.f);
    const float m = rbf(mu), rs = rcpf(rbf(sqrta(rbf(rbf(var) + 1e-5f))));
    const float ra = rs * 0.0625f;
    sts64(SM_AF + w * 128 + (lane & 15) * 8, fu(ra), fu(-m * ra));
    __syncwarp();
    TS(55);
    const uint4 f0 = lds128(SM_AF + w * 128 + q * 16), f1 = lds128(SM_AF + w * 128 + 64 + q * 16);
    const u32 zdst = SM_GATE + w * 2048 + (g >> 1) * 128 + (lane & 15) * 8;
    const u32 pz = (q & 1) ? 0 : pm;
#pragma unroll
    for (int j = 0; j < 8; j++) {
      const u32 x0 = j & 1 ? t[j >> 1].z : t[j >> 1].x, x1 = j & 1 ? t[j >> 1].w : t[j >> 1].y;
      sts64((j & 1 ? zdst ^ 64 : zdst) + 512 * (j >> 1), pk_hf(fmaf(blo(x0), uf(f0.x), uf(f0.y)), fmaf(bhi(x0), uf(f0.z), uf(f0.w))) | pz,
            pk_hf(fmaf(blo(x1), uf(f1.x), uf(f1.y)), fmaf(bhi(x1), uf(f1.z), uf(f1.w))));
    }
    TS(53);
    if (w < 8) barrive(15, 288);
    else {
      bsync(15, 288);
      TS(54);
      if (lane == 0) {
        PROXY_FENCE();
        bulk_out<BLK>(gs + b * BLK, SM_GATE);
        asm volatile("cp.async.bulk.commit_group;" ::: "memory");
        if (PFG & 1) l2_pre<WSH / 2>(p.wg + b * WSH);
      }
      const float rh = rbf(rs);
      sts128(SM_ST + 16 * (lane & 15), pk_bf(-m, -m), pk_bf(rh, rh), pk_bf(rs - rh, rs - rh), 0);
    }
    TS(5);
  }
  if (kw) {
    float D[5][4] = {};
    u32 ta = ktab + q * 128 + ((g ^ (q << 1)) << 4), tm = ktab + 8192 + q * 16;
#pragma unroll 2
    for (int s = 0; s < 8; s++) {
      const uint4 ca = lds128(ta), cb = lds128(ta + 4096), ma = lds128(tm);
      ta = (ta + 512) ^ 16; tm += 64;
      k2048 += __shfl_xor_sync(~0u, k2048, 16 >> s);
      const C2 s0 = {cb.z, cb.w}, s1 = cm2(s0, {ma.x, ma.y}), s2 = cm2(s0, {ma.z, ma.w}), s3 = cm2(s1, {ma.z, ma.w});
      mma_hf(D[0], s0.re, s1.re, s0.im, s1.im, ca.x, ca.y);
      mma_hf(D[2], s0.re, s1.re, s0.im, s1.im, ca.z, ca.w);
      mma_hf(D[4], s0.re, s1.re, s0.im, s1.im, cb.x, cb.y);
      mma_hf(D[1], s2.re, s3.re, s2.im, s3.im, ca.x, ca.y);
      mma_hf(D[3], s2.re, s3.re, s2.im, s3.im, ca.z, ca.w);
    }
    TS(3);
    const u32 xa = (w < 8 ? SM_MODS + (4 + ksig) * KTAB : SM_ZS) + lane * 16;
    if (khf) {
      __syncwarp();
#pragma unroll
      for (int j = 0; j < 5; j++) sts128(xa + 512 * j, fu(D[j][0]), fu(D[j][1]), fu(D[j][2]), fu(D[j][3]));
      if (lane == 0) sts32(xa + 2560, fu(k2048));
      asm volatile("bar.arrive %0,64;" ::"r"(2 + ksig) : "memory");
    } else {
      const u32 t1 = tp + (q < 2 ? (128 + 4 * g + 2 * q) * 4 : T3 * 4 + ((32 * q - 64 + g) ^ 1) * 2);
      const u32 x = 16 * q + (g >> 1) + hi + 1, tb = tp + (hi ? T7E : T9E) * 4 - 4;
      const u32 te = tb + (x + 2 * (x & 1)) * 2, to = tb + TEO * 4 + (x ^ 1) * 2;
      asm volatile("bar.sync %0,64;" ::"r"(2 + ksig) : "memory");
#pragma unroll
      for (int j = 0; j < 5; j++) { const uint4 t = lds128(xa + 512 * j); D[j][0] += uf(t.x); D[j][1] += uf(t.y); D[j][2] += uf(t.z); D[j][3] += uf(t.w); }
      k2048 = (k2048 + uf(lds32(xa + 2560))) * 0.125f;
#pragma unroll
      for (int r = 0; r < 4; r++) {
        const u32 v = pk_hf(D[2 + (r >> 1)][2 * (r & 1)], D[2 + (r >> 1)][2 * (r & 1) + 1]);
        if (q < 2) {
          const u32 vv = __byte_perm(v, v, 0x1010);
          sts32(t1 + (TO + 32 * r) * 4, vv); sts16(t1 + (TO + 32 * r + 1) * 4 + 2, v >> 16); sts16(t1 + (TO + 32 * r - 1) * 4, v);
          sts64(t1 + (TE + 32 * r) * 4, vv, __byte_perm(v, v, 0x1032));
        } else {
          sts16(t1 + 16 * r, v >> 16);
          if (r == 0 && lane == 2) {
            const u32 vv = __byte_perm(v, v, 0x1010);
            sts32(tp + (TO + 256) * 4, vv); sts16(tp + (TO + 257) * 4 + 2, v); sts16(tp + (TO + 255) * 4, v); sts64(tp + (TE + 256) * 4, vv, vv);
          } else sts16(t1 + 16 * r - ((T3 - T5) * 4 + 6) + 8 * hi, v);
        }
      }
#pragma unroll
      for (int r = 0; r < 2; r++) {
        const u32 v = pk_hf(D[4][2 * r], D[4][2 * r + 1]);
        if (r == 0 && lane == 0) { sts16(tp + T5 * 4 + 62 * 2, v); sts32(SM_KV + 4 * ksig, v & 0xffff); sts16(tp + (T9E + TEO) * 4 + 62 * 2, pk_hf(k2048, 0.f)); }
        else { sts16(te + 8 * r, v); sts16(to + 8 * r, v); }
        sts16(te + 8 * r + 16, v >> 16); sts16(to + 8 * r + 16, v >> 16);
      }
      __syncwarp();
#pragma unroll
      for (int r = 0; r < 4; r++) {
        const u32 v = pk_hf(D[r >> 1][2 * (r & 1) + 1], D[r >> 1][2 * (r & 1)]), t2 = tp + lane * 4 + 128 * r;
        sts32(t2 + TO * 4, v); sts16(t2 + TE * 4, v >> 16); sts16(t2 + (TE + 1) * 4 + 2, v);
      }
      __syncwarp();
    }
  } else if (w == 11 && b < 108) {
    float c[4][4] = {};
    u32 aa = SM_UP + ((lane & 7) + 8 * (lane >> 4)) * 64 + ((((lane >> 3) & 1) ^ ((lane & 7) >> 1)) << 4);
    u32 ba = SM_SIL + (lane >> 3) * 16;
    uint4 a[2][10];
#define GLD(n) { _Pragma("unroll") for (int i = 0; i < 2; i++) { a[n][5 * i] = ldsm4(ba + i * 64); \
      _Pragma("unroll") for (int k = 0; k < 4; k++) a[n][5 * i + 1 + k] = ldsm4t((k & 2 ? aa ^ 32 : aa) + i * 2048 + (k & 1) * 1024); } aa += 4096; ba += 128; }
#define GMM(n) { _Pragma("unroll") for (int i = 0; i < 2; i++) _Pragma("unroll") for (int k = 0; k < 4; k++) { const uint4 f = a[n][5 * i + 1 + k], bb = a[n][5 * i]; \
      mma_bf(c[k], f.x, f.y, f.z, f.w, k & 1 ? bb.z : bb.x, k & 1 ? bb.w : bb.y); } }
    mb_wait(SM_MB);
    TS(56);
    GLD(0);
#pragma unroll 1
    for (int s = 0; s < 4; s++) { GLD(1); GMM(0); GLD(0); GMM(1); }
    GMM(0);
    const float v0 = (q & 1) ? c[0][2] + c[1][2] : c[0][0] + c[1][0], v1 = (q & 1) ? c[2][2] + c[3][2] : c[2][0] + c[3][0];
    str16(gs + (G_MOD + b * 128 + 2 * g + 16 * q), pk_bf(rbf((q & 2) ? v1 : v0) * F2M64, 0.f) | (g < 2 ? pm : 0));
    TS(57);
  }
  TS(6);
  u32 tid2 = tid;
  if (w < 4) {
    asm volatile("setmaxnreg.inc.sync.aligned.u32 232;");
    const u32 tid = tid2 + p.zero, w = tid >> 5, lane = tid & 31, g = lane >> 2, q = lane & 3, hi = g & 1, zr = tid >> 16, tp = SM_TAP + w * TAPS;
    const u32 pml = opq((g & 3) ? 0 : pm);
    const u32 tr = tp + ((hi ? TO : TE) + (g >> 1) - q) * 4;
    u32 T[33][4], B5[5][2], B3[5][2];
#pragma unroll
    for (int d = 0; d < 33; d++) {
      T[d][0] = lds32(tr + 32 * d); T[d][1] = lds32(tr + 32 * d + 16);
      T[d][2] = cpy(d ? T[d - 1][1] : zr, zr, 0); T[d][3] = cpy(T[d][0], zr, 1);
    }
    const u32 t33 = cpy(T[32][1], zr, 0), z33 = cpy(zr, zr, 1);
    if (TPIN) {
#pragma unroll
      for (int d = 0; d < 33; d++) asm volatile("{.reg .pred p; setp.ne.u32 p,%2,0; @p st.shared.v2.u32 [%2],{%0,%1};}" ::"r"(T[d][2]), "r"(T[d][3]), "r"(zr) : "memory");
    }
    const u32 bt = tp + (T5 + g - q) * 4;
#pragma unroll
    for (int d = 0; d < 5; d++) {
      B5[d][0] = lds32(bt + 32 * d); B5[d][1] = lds32(bt + 32 * d - 16);
      B3[d][0] = lds32(bt + 32 * d + (T3 - T5) * 4); B3[d][1] = lds32(bt + 32 * d - 16 + (T3 - T5) * 4);
    }
    u32 za = opq(SM_ZS + 16 + w * ZSS + ((lane >> 3) & 1) * ZPS + ((lane & 7) + (lane >> 4)) * 16);
    u32 wa = opq(SM_W + W5O + w * WSL + row16(lane));
    u32 sa = opq(SM_W + W9O - 2048 + w * WSL + lane * 16);
    u32 yo = opq(G_Y + b * BLK + 256 * q + w * 32 + 4 * g);
    const u32 fa = opq(SM_SC + 16 * w + 8), bw = opq((BW >> 4 * w) & 15), bs = opq((BS >> 4 * w) & 15);
    if (TPIN) asm volatile("{.reg .pred p; setp.ne.u32 p,%8,0; @p st.shared.v4.u32 [%8],{%0,%1,%2,%3}; @p st.shared.v4.u32 [%8],{%4,%5,%6,%7};}"
                           ::"r"(za), "r"(wa), "r"(sa), "r"(yo), "r"(fa), "r"(bw), "r"(bs), "r"(pml), "r"(zr) : "memory");
    TS(8);
    bsync(9, 384);
    TS(11);
    float A[4][4] = {};
    uint4 Z[4];
    Z[0] = ldsm4(za); Z[1] = ldsm4(za + 32);
    const uint2 fc = lds64(fa);
    const u32 F = __byte_perm(fu(uf(fc.x) * uf(fc.y)), 0, 0x3232);
#define STEP(s, b0, b1) { _Pragma("unroll") for (int i = 0; i < 4; i++) mma_hf_t(A[i], T[8 * i + 7 - (s)], b0, b1); }
#define PAIR(n) { Z[(n + 2) & 3] = ldsm4(za + 32 * (n + 2)); STEP(2 * n, Z[n].x, Z[n].y); STEP(2 * n + 1, Z[n].z, Z[n].w); }
#define LAST(N) mma8_hf(N, t33, z33, Z[3].y); float O[4]; mma_hf_o(O, A[0], T[0], Z[3].z, Z[3].w); \
    _Pragma("unroll") for (int i = 0; i < 3; i++) mma_hf_o(A[i], A[i + 1], T[8 * i + 8], Z[3].z, Z[3].w); \
    mma_hf_o(A[3], N, T[32], Z[3].z, Z[3].w);
#pragma unroll 1
    for (int j = 0; j < 4; j++) {
      PAIR(0); PAIR(1); PAIR(2);
      Z[1] = ldsm4(za + 160); STEP(6, Z[3].x, Z[3].y);
      float N[4] = {};
      LAST(N);
      if (INCV) inc<128>(za);
      y_store<128>(O[0], O[1], O[2], O[3], F, pml, gs + yo);
      if (!INCV) za += 128;
      yo += 1024;
      TSJ(j);
    }
    bsyncr(bw);
    uint4 a5;
    if (A5P) a5 = ldsm4t(wa);
#pragma unroll 1
    for (int j = 4; j < 13; j++) {
      if (j == 8) bsyncr(bs);
      if (!A5P) a5 = ldsm4t(wa);
      const uint4 a3 = ldsm4t(wa + (W3O - W5O));
      uint4 s3 = {0, 0, 0, 0};
      if (j >= 8) s3 = lds128(sa);
      PAIR(0);
      float N[4] = {};
#pragma unroll
      for (int i = 0; i < 4; i++) mma_hf(A[i], a5.x, a5.y, a5.z, a5.w, B5[i][0], B5[i][1]);
      mma_hf(N, a5.x, a5.y, a5.z, a5.w, B5[4][0], B5[4][1]);
      if (INCV) asm volatile("{add.u32 %0,%0,256; xor.b32 %0,%0,32;}" : "+r"(wa)); else wa = (wa + 256) ^ 32;
      if (A5P) a5 = ldsm4t(wa);
      PAIR(1);
#pragma unroll
      for (int i = 0; i < 4; i++) mma_hf(A[i], a3.x, a3.y, a3.z, a3.w, B3[i][0], B3[i][1]);
      mma_hf(N, a3.x, a3.y, a3.z, a3.w, B3[4][0], B3[4][1]);
      PAIR(2);
      Z[1] = ldsm4(za + 160); STEP(6, Z[3].x, Z[3].y);
      LAST(N);
      if (INCV) { inc<128>(za); inc<512>(sa); }
      y_store<128>(O[0] + uf(s3.x), O[1] + uf(s3.y), O[2] + uf(s3.z), O[3] + uf(s3.w), F, pml, gs + yo);
      if (!INCV) { za += 128; sa += 512; }
      yo += 1024;
      TSJ(j);
    }
    {
      asm volatile("mov.u32 %0,%%tid.x;" : "=r"(tid2));
      const uint4 s3 = lds128(sa), s4 = lds128(sa + 512), s5 = lds128(sa + 1024);
      float X[3][4] = {{uf(s4.x), uf(s4.y), uf(s4.z), uf(s4.w)}, {}, {uf(s5.x), uf(s5.y), uf(s5.z), uf(s5.w)}};
#pragma unroll
      for (int ty = 0; ty < 2; ty++) {
        const uint4 a = A5P && !ty ? a5 : ldsm4t(wa + ty * (W3O - W5O)), c = ldsm4t((wa ^ 32) + 256 + ty * (W3O - W5O)), d = ldsm4t(wa + 512 + ty * (W3O - W5O));
#pragma unroll
        for (int i = 0; i < 3; i++) mma_hf(A[i], a.x, a.y, a.z, a.w, ty ? B3[i][0] : B5[i][0], ty ? B3[i][1] : B5[i][1]);
#pragma unroll
        for (int i = 0; i < 2; i++) mma_hf(X[i], c.x, c.y, c.z, c.w, ty ? B3[i][0] : B5[i][0], ty ? B3[i][1] : B5[i][1]);
        mma_hf(X[2], d.x, d.y, d.z, d.w, ty ? B3[0][0] : B5[0][0], ty ? B3[0][1] : B5[0][1]);
      }
#pragma unroll
      for (int n = 0; n < 4; n++) {
        const uint4 f0 = n < 2 ? Z[n] : ldsm4(za + 32 * n), f1 = ldsm4(za + 32 * n + 128), f2 = ldsm4(za + 32 * n + 256);
#pragma unroll
        for (int s = 2 * n; s < 2 * n + 2; s++) {
#pragma unroll
          for (int i = 0; i < 3; i++) mma_hf_t(A[i], T[8 * i + 7 - s], s & 1 ? f0.z : f0.x, s & 1 ? f0.w : f0.y);
          mma_hf_t(X[0], T[7 - s], s & 1 ? f1.z : f1.x, s & 1 ? f1.w : f1.y); mma_hf_t(X[1], T[15 - s], s & 1 ? f1.z : f1.x, s & 1 ? f1.w : f1.y);
          mma_hf_t(X[2], T[7 - s], s & 1 ? f2.z : f2.x, s & 1 ? f2.w : f2.y);
        }
      }
      y_store<128>(A[0][0] + uf(s3.x), A[0][1] + uf(s3.y), A[0][2] + uf(s3.z), A[0][3] + uf(s3.w), F, pml, gs + yo);
      y_store<128>(A[1][0] + X[0][0], A[1][1] + X[0][1], A[1][2] + X[0][2], A[1][3] + X[0][3], F, pml, gs + yo + 1024);
      y_store<128>(A[2][0] + X[1][0] + X[2][0], A[2][1] + X[1][1] + X[2][1], A[2][2] + X[1][2] + X[2][2], A[2][3] + X[1][3] + X[2][3], F, pml, gs + yo + 2048);
    }
    barrive(12, N12);
    TS(15);
  } else {
    asm volatile("setmaxnreg.dec.sync.aligned.u32 136;");
    const u32 t8 = tid - 128, pml = (g & 3) ? 0 : pm;
    {
      TS(12);
      if (PFG == 1 && tid == 288) l2_pre<WSH / 2>(p.wg + (b * WSH + WSH / 2));
      const char* zs = gs + ((16 * w - 64 + (lane >> 3)) * BLK + b * 128 + ((lane & 7) * 16 ^ rho * 64));
      const char* zs4 = gs + ((t8 >> 1) * BLK + (Ps >> 4) * 512 + (Ps & 6) * 64 + ((Ps >> 2 ^ Ps) & 2) * 32 + (Ps & 1) * 32 + (t8 & 1) * 16);
      uint4 v[5];
      v[4].x = INVAL;
      if (ZD) wait_clk(t0, ZD);
      if (w == 9) {
        const u32 d = lane < 4 ? chan(b, lane) : Ps;
        const char* mp = gs + (G_MOD + (d >> 5) * 128 + (d & 24) * 2);
        uint4 ta, tc;
        POLL({ ta = ldr128(mp); tc = ldr128(mp + MODJ); v[4] = ldr128(zs4); }, ((ta.x ^ pm) | (tc.x ^ pm)) & TAGM, 2);
        const u32 aw = (d & 4) ? ((d & 2) ? ta.w : ta.z) : ((d & 2) ? ta.y : ta.x & ~TAGM);
        const u32 cw = (d & 4) ? ((d & 2) ? tc.w : tc.z) : ((d & 2) ? tc.y : tc.x & ~TAGM);
        const float sa = ((d & 1) ? bhi(aw) : blo(aw)) * F2P64, c1 = rbf(fmaf((d & 1) ? bhi(cw) : blo(cw), F2P64, 1.f));
        const u32 EM = min(max(fu(fmaxf(32.f * fabsf(c1), fabsf(sa))) >> 23, 80u), 250u);
        const float inv = uf((264 - EM) << 23);
        if (lane < 5) { sts64(SM_SC + 16 * lane, pk_hf(16.f * c1 * inv, 16.f * c1 * inv), pk_hf(sa * inv, sa * inv)); sts32(SM_SC + 16 * lane + 8, (EM - 74) << 23); }
        TS(10);
      }
      POLLW(v[4] = ldr128(zs4), (v[4].x ^ pm) & TAGM, 1);
      TS(58);
#pragma unroll
      for (int j = 0; j < 4; j++) v[j] = ldr128(zs + j * 4 * BLK);
#define MARKERS() if (tid == 256) { \
        bulk_out<2048>(gs + (G_Y + 16384 + b * BLK), SM_INV); \
        _Pragma("unroll") for (int i = MT / 2; i < 8; i++) bulk_out<2048>(gs + (G_Y + 2048 * i + b * BLK), SM_INV); \
        bulk_out<2048>(gs + (G_PART + b * 2048), SM_INV); bulk_out<512>(gs + (G_ACT + b * 512), SM_INV); \
        bulk_out<32>(gs + (G_KEY + b * KST), SM_INV); if (!rho) bulk_out<128>(gs + (G_ACT + Ps * 128), SM_INV); \
        asm volatile("cp.async.bulk.commit_group;" ::: "memory"); }
#define GATE() { mb_expect(SM_MB + 8, rho ? SLV : 46080); \
        _Pragma("unroll") for (int i = GE; i < 3; i++) tma3d(SM_GATE + 12288 * i, &tm_gate, SM_MB + 8, 32 * b, i); \
        if (!rho) tma3d(SM_GATE + SLV, &tm_gs, SM_MB + 8, 4096 + 4 * b, 0); }
#define UP() { mb_expect(SM_MB + 16, rho ? SLV : 46080); tma3d(SM_UP, &tm_up, SM_MB + 16, 32 * b, 0); \
        if (!rho) tma3d(SM_UP + SLV, &tm_us, SM_MB + 16, 4096 + 4 * b, 0); }
      if (PFU == 2 && tid == 256) l2_pre<WSH>(p.wu + b * WSH);
      if (GE && tid == 256) {
        asm volatile("cp.async.bulk.wait_group.read 0;" ::: "memory");
#pragma unroll
        for (int i = 0; i < GE; i++) tma3d(SM_GATE + 12288 * i, &tm_gate, SM_MB + 8, 32 * b, i);
      }
      if (MKT == 0) MARKERS();
      if (PFG == 2 && tid == 256) l2_pre<WSH>(p.wg + b * WSH);
      if (PFG == 3 && tid == 256) l2_pre<WSH / 2>(p.wg + (b * WSH + WSH / 2));
      bsync(8, 256);
      const uint2 cc = lds64(SM_SC + 8 * (t8 & 6)), c4 = lds64(SM_SC + 64);
      POLLW(_Pragma("unroll") for (int j = 0; j < 4; j++) if ((v[j].x ^ pm) & TAGM) v[j] = ldr128(zs + j * 4 * BLK),
           ((v[0].x ^ pm) | (v[1].x ^ pm) | (v[2].x ^ pm) | (v[3].x ^ pm)) & TAGM, 1);
      TS(9);
      const u32 dst = SM_ZS + 128 + (t8 & 7) * ZPS + (16 * w - 64 + (lane >> 3)) * 16;
#pragma unroll
      for (int j = 4; j >= 0; j--) {
        const uint2 c = j < 4 ? cc : c4;
        sts128(j < 4 ? dst + j * 64 : SM_Z4 + 256 + (t8 & 1) * ZP4 + (t8 >> 1) * 16, hfma(v[j].x & ~TAGM, c.x, c.y), hfma(v[j].y, c.x, c.y), hfma(v[j].z, c.x, c.y), hfma(v[j].w, c.x, c.y));
      }
      if (t8 < 96) sts128(t8 < 64 ? SM_ZS + (t8 & 7) * ZPS + (t8 >> 3) * 16 : SM_Z4 + (t8 & 1) * ZP4 + (t8 & 30) * 8, 0, 0, 0, 0);
      if (MKT == 0) asm volatile("cp.async.bulk.wait_group.read 1;" ::: "memory");
      else asm volatile("cp.async.bulk.wait_group.read 0;" ::: "memory");
      bsync(9, 384);
      TS(11);
      if (MKT == 1) MARKERS();
      const bool lng = w < 8 || w == 9;
      const u32 ts = lane + 32 * (w == 8 ? 0 : w - 9), c = min(ts, 71u), ma = SM_MODS + 16 * c;
      const u32 sig = lng ? ksig : ts >> 4, l2 = lng ? lane : 32 + (ts & 15);
      const char* mq = gs + (G_MOD + (c >> 2) * 128 + (c & 3) * 16);
      if (!lng) {
#pragma unroll
        for (int j = 0; j < 6; j++) cpa16(ma + 1152 * j, mq + j * MODJ);
        cpa16(ma + 1152 * 6, p.dsk + 16 * c); cpa16(ma + 1152 * 7, p.wr + 16 * c);
        if (PFU == 3) {
#pragma unroll
          for (int j = 0; j < 4; j++) if (ts < 81) l2_line(p.wu + (b * WSH + (81 * j + ts) * 128));
        }
        if (tid == 352) {
          PROXY_FENCE();
          if (PFU == 1) l2_pre<WSH>(p.wu + b * WSH);
          if (!TG) GATE();
          if (!TU) UP();
        }
      }
      const u32 wb = SM_W + sig * WSL;
      if (sig < 5) {
        const u32 za = (sig < 4 ? SM_ZS + 128 + sig * ZSS : SM_Z4 + 256) + l2 * 32, zb = za + (sig < 4 ? ZPS : ZP4);
        const uint4 c0 = lds128(zb - 32), c1 = lds128(za - 16), c2 = lds128(zb - 16), c3 = lds128(za), c4 = lds128(zb), c5 = lds128(za + 16), c6 = lds128(zb + 16);
        const u32 P[25] = {c0.z, c0.w, c1.x, c1.y, c1.z, c1.w, c2.x, c2.y, c2.z, c2.w, c3.x, c3.y, c3.z, c3.w, c4.x, c4.y, c4.z, c4.w, c5.x, c5.y, c5.z, c5.w, c6.x, c6.y, c6.z};
        u32 Q[25], D1[24], F4[23], W5[21], W3[17];
#pragma unroll
        for (int j = 1; j < 25; j++) Q[j] = __byte_perm(P[j - 1], P[j], 0x5432);
#pragma unroll
        for (int j = 1; j < 24; j++) D1[j] = hadd(P[j], Q[j]);
#pragma unroll
        for (int j = 2; j < 23; j++) F4[j] = hadd(D1[j], D1[j - 1]);
#pragma unroll
        for (int n = 0; n < 21; n++) W5[n] = hadd(F4[n + 2], P[n]);
#pragma unroll
        for (int n = 0; n < 17; n++) W3[n] = hadd(Q[n + 8], D1[n + 7]);
        const u32 a0 = wb + W5O + 64 * l2 + 16 * ((l2 >> 1) & 3);
#pragma unroll
        for (int i = 0; i < 4; i++) {
          sts128(a0 ^ (16 * i), W5[4 * i + 5], W5[4 * i + 6], W5[4 * i + 7], W5[4 * i + 8]);
          sts128((a0 ^ (16 * i)) + (W3O - W5O), W3[4 * i + 1], W3[4 * i + 2], W3[4 * i + 3], W3[4 * i + 4]);
        }
        if (lng) {
          if (lane < 16) sts128(wb + (lane & 7) * 16 + (lane & 8) * 400, 0, 0, 0, 0);
          const u32 a1 = wb + 32 * lane + 16 * ((lane >> 2) & 1);
#pragma unroll
          for (int i = 0; i < 4; i++) {
            const u32 a = (a1 ^ (16 * (i >> 1))) + 1024 * (i & 1), n = 4 * i;
            sts128(a + V2O, hadd(Q[n + 9], P[n + 8]), hadd(Q[n + 10], P[n + 9]), hadd(Q[n + 11], P[n + 10]), hadd(Q[n + 12], P[n + 11]));
            sts128(a + W9O, hadd(F4[n + 4], W5[n]), hadd(F4[n + 5], W5[n + 1]), hadd(F4[n + 6], W5[n + 2]), hadd(F4[n + 7], W5[n + 3]));
            sts128(a + W7O, hadd(F4[n + 6], W3[n]), hadd(F4[n + 7], W3[n + 1]), hadd(F4[n + 8], W3[n + 2]), hadd(F4[n + 9], W3[n + 3]));
          }
        }
      }
      if (w < 8) barriver((BW >> (4 * w - 16)) & 15);
      else if (!(w & 1)) { barriver((BW >> (4 * w - 32)) & 15); barriver((BW >> (4 * w - 28)) & 15); }
      __syncwarp();
      TS(32);
      if (lng) {
        const u32 wa = wb + ((lane >> 3) & 1) * 1024 + (((lane & 7) ^ (lane >> 4)) + 8 * (lane >> 4)) * 16;
        const u32 kv = lds32(SM_KV + 4 * sig), bi = (g >> 1) == q ? (hi ? kv << 16 : kv) : 0u;
        float acc[8][4] = {};
#pragma unroll
        for (int j = 0; j < 4; j++) { const uint4 a = ldsm4t(wa + V2O + j * 256); mma8_hf(acc[2 * j], a.x, a.y, bi); mma8_hf(acc[2 * j + 1], a.z, a.w, bi); }
        u32 bt = tp + (T9E + hi * TEO + (g >> 1) - q) * 4, wt = wa + W9O;
#pragma unroll 1
        for (int ty = 0; ty < 2; ty++) {
          uint4 a[4];
#pragma unroll
          for (int be = 0; be < 4; be++) a[be] = ldsm4t(wt + be * 256);
          u32 b1 = lds32(bt - 16);
#pragma unroll
          for (int d = 0; d < 8; d++) {
            const u32 b0 = lds32(bt + 16 * d);
#pragma unroll
            for (int be = 0; be < 4; be++) if (d + 2 * be < 8) mma_hf(acc[d + 2 * be], a[be].x, a[be].y, a[be].z, a[be].w, b0, b1);
            b1 = b0;
          }
          bt += (T7E - T9E) * 4; wt += W7O - W9O;
        }
        __syncwarp();
#pragma unroll
        for (int j = 0; j < 8; j++) sts128(wb + W9O + j * 512 + lane * 16, fu(acc[j][0]), fu(acc[j][1]), fu(acc[j][2]), fu(acc[j][3]));
        if (w != 9) barriver((BS >> (4 * w - 16)) & 15);
        TS(34);
      }
      if (!lng) {
        asm volatile("cp.async.wait_all;" ::: "memory");
        uint4 md[6];
#pragma unroll
        for (int j = 0; j < 6; j++) md[j] = lds128(ma + 1152 * j);
        const uint4 dk = lds128(ma + 1152 * 6), wr = lds128(ma + 1152 * 7);
        POLLW(_Pragma("unroll") for (int j = 0; j < 6; j++) md[j] = ldr128(mq + j * MODJ),
              ((md[0].x ^ pm) | (md[1].x ^ pm) | (md[2].x ^ pm) | (md[3].x ^ pm) | (md[4].x ^ pm) | (md[5].x ^ pm)) & TAGM, 4);
#pragma unroll
        for (int j = 0; j < 6; j++) {
          const u32 o = (j % 3 == 1) ? BONE : 0x80008000u;
          md[j] = make_uint4(bfma(md[j].x & ~TAGM, B2P64, o), bfma(md[j].y, B2P64, o), bfma(md[j].z, B2P64, o), bfma(md[j].w, B2P64, o));
          if (j > 2) sts128(ma + 1152 * j, md[j].x, md[j].y, md[j].z, md[j].w);
        }
        const uint4 gd = make_uint4(bmul(md[2].x, dk.x), bmul(md[2].y, dk.y), bmul(md[2].z, dk.z), bmul(md[2].w, dk.w));
#pragma unroll
        for (int j = 0; j < 2; j++) sts128(ma + 1152 * j, bmul(md[j].x, gd.x), bmul(md[j].y, gd.y), bmul(md[j].z, gd.z), bmul(md[j].w, gd.w));
        sts128(ma + 2304, bmul(md[2].x, B2P64), bmul(md[2].y, B2P64), bmul(md[2].z, B2P64), bmul(md[2].w, B2P64));
        const uint4 H = make_uint4(bmul(md[4].x, wr.x), bmul(md[4].y, wr.y), bmul(md[4].z, wr.z), bmul(md[4].w, wr.w));
        sts128(ma + 1152 * 7, H.x, H.y, H.z, H.w);
        sts128(ma + 1152 * 8, bfma(md[4].x, wr.x, H.x ^ 0x80008000u), bfma(md[4].y, wr.y, H.y ^ 0x80008000u), bfma(md[4].z, wr.z, H.z ^ 0x80008000u), bfma(md[4].w, wr.w, H.w ^ 0x80008000u));
        float c4[4] = {};
        mma_bf(c4, md[4].x, md[3].x, md[4].y, md[3].y, wr.x, wr.y); mma_bf(c4, md[4].z, md[3].z, md[4].w, md[3].w, wr.z, wr.w);
        if (q == g >> 1) sts64(SM_RC + (ts >> 2) * 8, fu(hi ? c4[1] : c4[0]), fu(hi ? c4[3] : c4[2]));
        if (ts < 2) sts128(SM_ONE + 16 * ts, ts ? 0 : BONE, ts ? 0 : BONE, ts ? 0 : BONE, ts ? 0 : BONE);
        TS(14);
        if (MKT == 2) MARKERS();
        if (w == 8) asm volatile("cp.async.bulk.wait_group 0;" ::: "memory");
        if (PFW == 2) {
#pragma unroll
          for (int j = 0; j < 4; j++) if (ts < 81) l2_line(p.wd + (b * WSH + (81 * j + ts) * 128));
        }
        bsync(13, 96);
        if (w == 8) { barriver(2); barriver(3); barriver(5); barriver(6); }
      }
      if (MB11) { if (w == 8 || w == 9) mb_arrive(SM_MB + 32); } else if (w >= 8) barrive(11, 256);
    }
    if (w < 8) {
      const u32 jw = SWJ && w < 6 ? w ^ 1 : w;
      const int u0 = 4 * (jw - 4) + 2 * rho;
      const u32 t4 = SM_TAP + 4 * TAPS;
      u32 tr = t4 + ((hi ? TO : TE) + (g >> 1) - q) * 4;
      u32 zb = SM_Z4 + 256 + ((lane >> 3) & 1) * ZP4 + u0 * 128 + (lane & 7) * 16 + (lane >> 4) * 128;
      float acc[4][4] = {};
      u32 prev = 0;
#pragma unroll 1
      for (int it = min(u0 + 2, 4); it; it--) {
#pragma unroll
        for (int s = 0; s < 8; s++) {
          const uint4 z = ldsm4(zb - 16 * s);
          const u32 t0 = lds32(tr + 32 * s), t1 = lds32(tr + 32 * s + 16);
          mma_hf(acc[s & 1], t0, t1, prev, t0, z.x, z.y);
          mma_hf(acc[2 + (s & 1)], t0, t1, prev, t0, z.z, z.w);
          prev = t1;
        }
        zb -= 128; tr += 256;
      }
      {
        const uint4 z = ldsm4(zb); const u32 t0 = lds32(tr), t1 = lds32(tr + 16);
        mma_hf(acc[0], t0, t1, prev, t0, z.x, z.y); mma_hf(acc[2], t0, t1, prev, t0, z.z, z.w);
        if (jw > 4) { const uint4 y = ldsm4(zb - 16); mma8_hf(acc[1], t1, zr, y.y); mma8_hf(acc[3], t1, zr, y.w); }
      }
      if (MB11) mb_wait(SM_MB + 32); else bsync(11, 256);
      u32 wa = (SM_W + 4 * WSL + W5O + row16(lane) + (u0 - 3) * 256) ^ 32, bt = t4 + (T5 + g - q) * 4;
#pragma unroll 1
      for (int al = min(u0 - 2, 6); al > 0; al--) {
#pragma unroll
        for (int ty = 0; ty < 2; ty++) {
          const uint4 a = ldsm4t(wa + ty * (W3O - W5O));
          const u32 bb = bt + ty * (T3 - T5) * 4;
          mma_hf(acc[ty], a.x, a.y, a.z, a.w, lds32(bb - 32), lds32(bb - 48));
          mma_hf(acc[2 + ty], a.x, a.y, a.z, a.w, lds32(bb), lds32(bb - 16));
        }
        wa = (wa - 256) ^ 32; bt += 32;
      }
      TS(35);
      const uint2 fc = lds64(SM_SC + 16 * 4 + 8);
      const u32 F = __byte_perm(fu(uf(fc.x) * uf(fc.y)), 0, 0x3232);
      char* yp = gs + (G_Y + 16384 - 2048 + b * BLK + jw * 512 + q * 64 + 4 * g);
#pragma unroll
      for (int j = 0; j < 2; j++) {
        uint4 s3 = {0, 0, 0, 0};
        if (u0 >= 8) s3 = lds128(SM_W + 4 * WSL + W9O + (u0 - 8 + j) * 512 + lane * 16);
        y_store<32>(acc[2 * j][0] + acc[2 * j + 1][0] + uf(s3.x), acc[2 * j][1] + acc[2 * j + 1][1] + uf(s3.y), acc[2 * j][2] + acc[2 * j + 1][2] + uf(s3.z),
                acc[2 * j][3] + acc[2 * j + 1][3] + uf(s3.w), F, pml, yp + j * 256);
      }
      barrive(7, 160);
      TS(16);
    } else {
      if (PFW == 3 && w == 9) {
#pragma unroll 1
        for (int j = 0; j < 12; j++) { if (lane < 27) l2_line(p.wd + (b * WSH + (27 * j + lane) * 128)); wait_clk(clk(), PFP); }
      }
      if (TG | TU) {
        if (tid == 352) {
          if (TG) { wait_clk(t0, TG); GATE(); }
          if (TW < TU) { wait_clk(t0, TW); l2_pre<WSH>(p.wd + b * WSH); }
          if (TU) { wait_clk(t0, TU); UP(); }
          if (TW >= TU) { wait_clk(t0, TW); l2_pre<WSH>(p.wd + b * WSH); }
        }
      } else if (PFW < 2 && tid == 352) { mb_wait(SM_MB + 8); if (PFW) mb_wait(SM_MB + 16); l2_pre<WSH>(p.wd + b * WSH); }
      if (D0C && tid == 352 && b < 108) {
        mb_wait(SM_MB + 16);
        PROXY_FENCE();
        mb_expect(SM_MB + 24, 49152);
        tma3d(SM_TAP, &tm_down, SM_MB + 24, 64 * (b % 9), 4 * (b / 9));
      }
      TS(17);
    }
  }
  post_conv(p, &tm_down, tid2 + p.zero, b);
  TSD();
  if (s2u(smem) != SM0) __trap();
}

typedef CUresult (*EncFn)(CUtensorMap*, CUtensorMapDataType, cuuint32_t, void*, const cuuint64_t*, const cuuint64_t*, const cuuint32_t*, const cuuint32_t*,
                          CUtensorMapInterleave, CUtensorMapSwizzle, CUtensorMapL2promotion, CUtensorMapFloatOOBfill);
static void make_map(EncFn enc, CUtensorMap* tm, void* ptr, int cols, int rows, int bw, int nb, CUtensorMapSwizzle sw, int gr = 192) {
  cuuint64_t gd[3] = {(cuuint64_t)cols, (cuuint64_t)gr, (cuuint64_t)(rows / gr)}, gs[2] = {(cuuint64_t)cols * 2, (cuuint64_t)cols * 2 * gr};
  cuuint32_t bd[3] = {(cuuint32_t)bw, (cuuint32_t)gr, (cuuint32_t)nb}, es[3] = {1, 1, 1};
  enc(tm, CU_TENSOR_MAP_DATA_TYPE_BFLOAT16, 3, ptr, gd, gs, bd, es, CU_TENSOR_MAP_INTERLEAVE_NONE, sw, CU_TENSOR_MAP_L2_PROMOTION_NONE, CU_TENSOR_MAP_FLOAT_OOB_FILL_NONE);
}
extern "C" void kernel_launch(void* const* d_in, const int* in_sizes, int n_in, void* d_out, int out_size) {
  static EncFn enc = nullptr;
  static void* scratch = nullptr;
  if (!enc) {
    cudaGetSymbolAddress(&scratch, g_s);
    cudaDriverEntryPointQueryResult qr;
    cudaGetDriverEntryPoint("cuTensorMapEncodeTiled", (void**)&enc, cudaEnableDefault, &qr);
    cudaFuncSetAttribute(fused_kernel, cudaFuncAttributeMaxDynamicSharedMemorySize, SM_TOTAL);
  }
  CUtensorMap tm_mod, tm_gate, tm_gs, tm_up, tm_us, tm_down;
  make_map(enc, &tm_mod, d_in[13], 3456, 576, 32, 3, CU_TENSOR_MAP_SWIZZLE_64B);
  make_map(enc, &tm_gate, d_in[9], 4608, 576, 32, 1, CU_TENSOR_MAP_SWIZZLE_64B);
  make_map(enc, &tm_gs, d_in[9], 4608, 576, 8, 3, CU_TENSOR_MAP_SWIZZLE_NONE);
  make_map(enc, &tm_up, d_in[10], 4608, 576, 32, 3, CU_TENSOR_MAP_SWIZZLE_64B);
  make_map(enc, &tm_us, d_in[10], 4608, 576, 8, 3, CU_TENSOR_MAP_SWIZZLE_NONE);
  make_map(enc, &tm_down, d_in[11], 576, 4608, 64, 1, CU_TENSOR_MAP_SWIZZLE_128B, 96);
  Prm p;
  p.x = (const char*)d_in[0]; p.la = (const char*)d_in[1]; p.ai = (const char*)d_in[2]; p.cr = (const char*)d_in[3];
  p.ci = (const char*)d_in[4]; p.ldt = (const char*)d_in[5]; p.dsk = (const char*)d_in[6]; p.wr = (const char*)d_in[8];
  p.wg = (const char*)d_in[9]; p.wu = (const char*)d_in[10]; p.wd = (const char*)d_in[11];
  p.c = (const char*)d_in[12]; p.out = (char*)d_out; p.zero = 0; p.gs = (char*)scratch;
  fused_kernel<<<128, 384, SM_TOTAL>>>(p, tm_mod, tm_gate, tm_gs, tm_up, tm_us, tm_down);
}
```

```cpp
#include <cuda_runtime.h>
#include <cuda.h>
#include <cuda_bf16.h>
#include <cuda_fp16.h>
#include <stdint.h>
#define FUSED 1
#define DEV __device__ __forceinline__
typedef uint32_t u32;

constexpr u32 BLK = 18432, G_Z = 0, G_Y = 128 * BLK, G_MOD = 2 * G_Y, G_KEY = G_MOD + 128 * 128, G_ACT = G_KEY + 128 * 128;
constexpr u32 G_PART = G_ACT + 576 * 128, G_EP = G_PART + 128 * 2048, G_END = G_EP + 128;
__device__ __align__(128) unsigned char g_s[G_END];
#define TS(i)
#define TSJ(j)
#define TS0()
#define TSE()
#define TSD()
#define TSX 0
#define TSN(code, n)
#define ERRF(code)

constexpr int SM0 = 1024;
constexpr int ROW = 1168, SLV = 36864;
constexpr int SM_GATE = SM0, SM_UP = SM_GATE + 46080, SM_XST = SM_UP + 46080, SM_MODS = SM_XST + 16 * ROW, SM_W = SM_MODS + 11008;
constexpr int KTAB = 9216, WSL = 12544, W5O = 128, W3O = 3328, V2O = 6400, W9O = 8448, W7O = 10496;
constexpr int ZPS = 2192, ZSS = 2 * ZPS, ZP4 = 2368;
constexpr int SM_ZS = SM_W + 5 * WSL, SM_Z4 = SM_ZS + 4 * ZSS, SM_TAP = SM_Z4 + 2 * ZP4, TAPS = 3328;
constexpr int SM_MB = SM_TAP + 5 * TAPS;
constexpr int SM_SC = SM_MB + 48;
constexpr int SM_KV = SM_SC + 80;
constexpr int SM_THR = SM_KV + 32;
constexpr int SM_SLOT = SM_THR + 48;
constexpr int SM_KEY = SM_SLOT + 32;
constexpr int SM_ST = SM_KEY + 64;
constexpr int SM_ST2 = SM_ST + 256;
constexpr int SM_RC = SM_ST2 + 256;
constexpr int SM_SP = SM_RC + 192;
constexpr int SM_AF = SM_SP + 1152, SM_SIL = SM_AF + 1152, SM_INV = SM_SIL + 1152, SM_END = SM_SP + 5760;
constexpr int SM_ONE = SM_MODS + 9 * 1152;
constexpr int SM_WD = SM_W, SM_XS = SM_W + 36864, SM_AC = SM_ZS, SM_RED = SM_AC + 6144;
constexpr int SM_TSB = SM_END, SM_TOTAL = SM_END + TSX - SM0;
static_assert(SM_W % 1024 == 0 && SM_TAP % 1024 == 0 && SM_MODS + 8 * KTAB <= SM_ZS && SM_ZS + 2 * KTAB <= SM_TAP && SM_RED + 10240 <= SM_TAP && SM_XS + 8 * ROW <= SM_ZS, "smem map");
static_assert(SM_MB % 16 == 0 && SM_THR % 16 == 0 && SM_ST % 16 == 0 && SM_SP % 16 == 0 && SM_TOTAL <= 232448, "smem map");
constexpr int TE = 4, TO = 276, T5 = 560, T3 = 624, T9E = 680, T7E = 760, TEO = 40;
#define MT 10
#define MKT 1
#define KST 128
#define DE1 1
#define DE2 4
#define DE3 5
#define OUTA 2
#define OUTB 7
#define PFW 1
#define PFU 0
#define KD 700
#define D0C 0
#define YE 104
#define YL 104
#define YD 250
#define OPTM 1
#define Y8 64
#define FH 0
#define FO 0
#define DB1 1
#define KD1 50
#define AD 0
#define PD 0
#define ZD 0
#define DD 1000
#define INCV 1
#define TPIN 0
#define A5P 1
#define SWJ 1
#define TG 0
#define TU 0
#define TW 0
#define KDB 520
#define KA 0
#define MB11 0
#define W8D 0
#define PRM 0
#define PRG 0
#define PRU 0
#define PRS 0
#define KE 64
#define PFP 200
#define GE 0
#define NB8 8
#define DX 0
#define DMOD 1000
#define RW 3
#define AW 7
#define FW 3
#define PFG 1
constexpr int N1 = 320 + 32 * DB1 + 32 * !!KA, N12 = 288 + 32 * !DB1;
constexpr int SPIN = 1 << 16, NEARLY = 4;
constexpr u32 TAGM = 0x40004000u, TAGR = 0x40000000u, INVAL = 0x00004801u;

DEV u32 s2u(const void* p) { return (u32)__cvta_generic_to_shared(p); }
DEV void mma_bf(float (&c)[4], u32 a0, u32 a1, u32 a2, u32 a3, u32 b0, u32 b1) {
  asm("mma.sync.aligned.m16n8k16.row.col.f32.bf16.bf16.f32 {%0,%1,%2,%3},{%4,%5,%6,%7},{%8,%9},{%0,%1,%2,%3};"
      : "+f"(c[0]), "+f"(c[1]), "+f"(c[2]), "+f"(c[3]) : "r"(a0), "r"(a1), "r"(a2), "r"(a3), "r"(b0), "r"(b1));
}
DEV void mma_hf(float (&c)[4], u32 a0, u32 a1, u32 a2, u32 a3, u32 b0, u32 b1) {
  asm("mma.sync.aligned.m16n8k16.row.col.f32.f16.f16.f32 {%0,%1,%2,%3},{%4,%5,%6,%7},{%8,%9},{%0,%1,%2,%3};"
      : "+f"(c[0]), "+f"(c[1]), "+f"(c[2]), "+f"(c[3]) : "r"(a0), "r"(a1), "r"(a2), "r"(a3), "r"(b0), "r"(b1));
}
DEV void mma8_bf(float (&c)[4], u32 a0, u32 a1, u32 b0) {
  asm("mma.sync.aligned.m16n8k8.row.col.f32.bf16.bf16.f32 {%0,%1,%2,%3},{%4,%5},{%6},{%0,%1,%2,%3};"
      : "+f"(c[0]), "+f"(c[1]), "+f"(c[2]), "+f"(c[3]) : "r"(a0), "r"(a1), "r"(b0));
}
DEV void mma8_hf(float (&c)[4], u32 a0, u32 a1, u32 b0) {
  asm("mma.sync.aligned.m16n8k8.row.col.f32.f16.f16.f32 {%0,%1,%2,%3},{%4,%5},{%6},{%0,%1,%2,%3};"
      : "+f"(c[0]), "+f"(c[1]), "+f"(c[2]), "+f"(c[3]) : "r"(a0), "r"(a1), "r"(b0));
}
DEV u32 movm(u32 x) { u32 r; asm("movmatrix.sync.aligned.m8n8.trans.b16 %0,%1;" : "=r"(r) : "r"(x)); return r; }
DEV uint4 ldsm4(u32 a) { uint4 r; asm volatile("ldmatrix.sync.aligned.m8n8.x4.shared.b16 {%0,%1,%2,%3},[%4];" : "=r"(r.x), "=r"(r.y), "=r"(r.z), "=r"(r.w) : "r"(a)); return r; }
DEV uint4 ldsm4t(u32 a) { uint4 r; asm volatile("ldmatrix.sync.aligned.m8n8.x4.trans.shared.b16 {%0,%1,%2,%3},[%4];" : "=r"(r.x), "=r"(r.y), "=r"(r.z), "=r"(r.w) : "r"(a)); return r; }
DEV u32 lds32(u32 a) { u32 r; asm volatile("ld.volatile.shared.u32 %0,[%1];" : "=r"(r) : "r"(a)); return r; }
DEV uint2 lds64(u32 a) { uint2 r; asm volatile("ld.shared.v2.u32 {%0,%1},[%2];" : "=r"(r.x), "=r"(r.y) : "r"(a)); return r; }
DEV uint4 lds128(u32 a) { uint4 r; asm volatile("ld.shared.v4.u32 {%0,%1,%2,%3},[%4];" : "=r"(r.x), "=r"(r.y), "=r"(r.z), "=r"(r.w) : "r"(a)); return r; }
DEV void sts16(u32 a, u32 v) { asm volatile("st.shared.u16 [%0],%1;" ::"r"(a), "h"((unsigned short)v) : "memory"); }
DEV void sts32(u32 a, u32 v) { asm volatile("st.shared.u32 [%0],%1;" ::"r"(a), "r"(v) : "memory"); }
DEV void sts64(u32 a, u32 x, u32 y) { asm volatile("st.shared.v2.u32 [%0],{%1,%2};" ::"r"(a), "r"(x), "r"(y) : "memory"); }
DEV void sts128(u32 a, u32 x, u32 y, u32 z, u32 w) { asm volatile("st.shared.v4.u32 [%0],{%1,%2,%3,%4};" ::"r"(a), "r"(x), "r"(y), "r"(z), "r"(w) : "memory"); }
DEV uint4 ldr128(const void* p) { uint4 v; asm volatile("ld.relaxed.gpu.global.v4.u32 {%0,%1,%2,%3},[%4];" : "=r"(v.x), "=r"(v.y), "=r"(v.z), "=r"(v.w) : "l"(p) : "memory"); return v; }
DEV uint2 ldr64(const void* p) { uint2 v; asm volatile("ld.relaxed.gpu.global.v2.u32 {%0,%1},[%2];" : "=r"(v.x), "=r"(v.y) : "l"(p) : "memory"); return v; }
DEV u32 ldr32(const void* p) { u32 v; asm volatile("ld.relaxed.gpu.global.u32 %0,[%1];" : "=r"(v) : "l"(p) : "memory"); return v; }
template <u32 M> DEV void rld128(uint4& v, const void* p, u32 tag) {
  asm volatile("{.reg .pred p; .reg .u32 t; lop3.b32 t,%0,%5,%6,0x28; setp.ne.u32 p,t,0; @p ld.relaxed.gpu.global.v4.u32 {%0,%1,%2,%3},[%4];}"
               : "+r"(v.x), "+r"(v.y), "+r"(v.z), "+r"(v.w) : "l"(p), "r"(tag), "n"(M) : "memory");
}
template <u32 M> DEV void rld64(uint64_t& v, const void* p, u32 tag) {
  asm volatile("{.reg .pred p; .reg .u32 t, h; mov.b64 {t,h},%0; lop3.b32 t,t,%2,%3,0x28; setp.ne.u32 p,t,0; @p ld.relaxed.gpu.global.u64 %0,[%1];}" : "+l"(v) : "l"(p), "r"(tag), "n"(M) : "memory");
}
template <int L> DEV u32 lop3(u32 a, u32 b, u32 c) { u32 r; asm("lop3.b32 %0,%1,%2,%3,%4;" : "=r"(r) : "r"(a), "r"(b), "r"(c), "n"(L)); return r; }
DEV u32 ne3(u32 a, u32 b, u32 c) { u32 r; asm("lop3.b32 %0,%1,%2,%3,0x7e;" : "=r"(r) : "r"(a), "r"(b), "r"(c)); return r; }
DEV void pin(u32 zr, u32 a, u32 b = 0, u32 c = 0, u32 d = 0) { asm volatile("{.reg .pred p; setp.ne.u32 p,%0,0; @p st.shared.v4.u32 [%0],{%1,%2,%3,%4};}" ::"r"(zr), "r"(a), "r"(b), "r"(c), "r"(d) : "memory"); }
DEV void pin2(u32 zr, const void* a, const void* b) { asm volatile("{.reg .pred p; setp.ne.u32 p,%0,0; @p st.shared.v2.u64 [%0],{%1,%2};}" ::"r"(zr), "l"(a), "l"(b) : "memory"); }
DEV const char* rowa(const char* base, u32 key) { const char* r; asm("mad.wide.u32 %0,%1,288,%2;" : "=l"(r) : "r"(~key & 0x1ffc), "l"(base)); return r; }
DEV void str128(void* p, u32 x, u32 y, u32 z, u32 w) { asm volatile("st.relaxed.gpu.global.v4.u32 [%0],{%1,%2,%3,%4};" ::"l"(p), "r"(x), "r"(y), "r"(z), "r"(w) : "memory"); }
DEV void str64(void* p, u32 x, u32 y) { asm volatile("{.reg .u64 d; mov.b64 d,{%1,%2}; st.relaxed.gpu.global.u64 [%0],d;}" ::"l"(p), "r"(x), "r"(y) : "memory"); }
DEV void str32(void* p, u32 x) { asm volatile("st.relaxed.gpu.global.u32 [%0],%1;" ::"l"(p), "r"(x) : "memory"); }
DEV void str16(void* p, u32 x) { asm volatile("st.relaxed.gpu.global.u16 [%0],%1;" ::"l"(p), "h"((unsigned short)x) : "memory"); }
DEV uint4 ldg128(const void* p) { uint4 v; asm volatile("ld.global.nc.v4.u32 {%0,%1,%2,%3},[%4];" : "=r"(v.x), "=r"(v.y), "=r"(v.z), "=r"(v.w) : "l"(p)); return v; }
DEV uint2 ldg64(const void* p) { uint2 v; asm volatile("ld.global.nc.v2.u32 {%0,%1},[%2];" : "=r"(v.x), "=r"(v.y) : "l"(p)); return v; }
DEV u32 ldg32(const void* p) { u32 v; asm volatile("ld.global.nc.u32 %0,[%1];" : "=r"(v) : "l"(p)); return v; }
DEV u32 ldg16(const void* p) { unsigned short v; asm volatile("ld.global.nc.u16 %0,[%1];" : "=h"(v) : "l"(p)); return v; }
#define bsync(id, n) asm volatile("bar.sync %0,%1;" ::"n"(id), "n"(n) : "memory")
#define barrive(id, n) asm volatile("bar.arrive %0,%1;" ::"n"(id), "n"(n) : "memory")
DEV void bsyncr(u32 id) { asm volatile("bar.sync %0,96;" ::"r"(id) : "memory"); }
DEV void barriver(u32 id) { asm volatile("bar.arrive %0,96;" ::"r"(id) : "memory"); }
constexpr u32 BW = 0x0FEA, BS = 0x6532;
DEV void mb_init(u32 a, u32 n) { asm volatile("mbarrier.init.shared.b64 [%0],%1;" ::"r"(a), "r"(n) : "memory"); }
DEV void mb_arrive(u32 a) { asm volatile("mbarrier.arrive.shared.b64 _,[%0];" ::"r"(a) : "memory"); }
DEV void mb_expect(u32 a, u32 bytes) { asm volatile("mbarrier.arrive.expect_tx.shared.b64 _,[%0],%1;" ::"r"(a), "r"(bytes) : "memory"); }
DEV void mb_wait(u32 a, u32 ph = 0) {
  u32 ok; int it = 0;
  do { asm volatile("{.reg .pred p; mbarrier.try_wait.parity.shared.b64 p,[%1],%2; selp.u32 %0,1,0,p;}" : "=r"(ok) : "r"(a), "r"(ph) : "memory"); } while (!ok && ++it < SPIN);
}
template <int N> DEV void bulk_out(void* dst, u32 src) { asm volatile("cp.async.bulk.global.shared::cta.bulk_group [%0],[%1],%2;" ::"l"(dst), "r"(src), "n"(N) : "memory"); }
constexpr u32 WSH = 41472;
DEV void l2_line(const void* p) { asm volatile("prefetch.global.L2 [%0];" ::"l"(p) : "memory"); }
template <int N> DEV void l2_pre(const void* p) { asm volatile("cp.async.bulk.prefetch.L2.global [%0],%1;" ::"l"(p), "n"(N) : "memory"); }
DEV void tma3d(u32 dst, const CUtensorMap* tm, u32 mb, int c0, int c2) {
  asm volatile("cp.async.bulk.tensor.3d.shared::cluster.global.mbarrier::complete_tx::bytes [%0],[%1,{%3,0,%4}],[%2];"
               ::"r"(dst), "l"((uint64_t)tm), "r"(mb), "r"(c0), "r"(c2) : "memory");
}
DEV float blo(u32 w) { return __uint_as_float(w << 16); }
DEV float bhi(u32 w) { return __uint_as_float(w & 0xffff0000u); }
DEV u32 pk_bf(float lo, float hi) { u32 r; asm("cvt.rn.bf16x2.f32 %0,%1,%2;" : "=r"(r) : "f"(hi), "f"(lo)); return r; }
DEV u32 pk_hf(float lo, float hi) { u32 r; asm("cvt.rn.f16x2.f32 %0,%1,%2;" : "=r"(r) : "f"(hi), "f"(lo)); return r; }
DEV float rbf(float x) { return __uint_as_float(pk_bf(0.f, x) & 0xffff0000u); }
DEV u32 bfma(u32 a, u32 b, u32 c) { u32 r; asm("fma.rn.bf16x2 %0,%1,%2,%3;" : "=r"(r) : "r"(a), "r"(b), "r"(c)); return r; }
DEV u32 bmul(u32 a, u32 b) { u32 r; asm("mul.rn.bf16x2 %0,%1,%2;" : "=r"(r) : "r"(a), "r"(b)); return r; }
DEV u32 badd(u32 a, u32 b) { u32 r; asm("add.rn.bf16x2 %0,%1,%2;" : "=r"(r) : "r"(a), "r"(b)); return r; }
DEV u32 hadd(u32 a, u32 b) { u32 r; asm("add.rn.f16x2 %0,%1,%2;" : "=r"(r) : "r"(a), "r"(b)); return r; }
DEV u32 hfma(u32 a, u32 b, u32 c) { u32 r; asm("fma.rn.f16x2 %0,%1,%2,%3;" : "=r"(r) : "r"(a), "r"(b), "r"(c)); return r; }
struct C2 { u32 re, im; };
DEV C2 cm2(C2 a, C2 b) {
  const __half2 ar = *reinterpret_cast<__half2*>(&a.re), ai = *reinterpret_cast<__half2*>(&a.im), br = *reinterpret_cast<__half2*>(&b.re), bi = *reinterpret_cast<__half2*>(&b.im);
  __half2 re = __hfma2(ar, br, __hneg2(__hmul2(ai, bi))), im = __hfma2(ar, bi, __hmul2(ai, br));
  return {*reinterpret_cast<u32*>(&re), *reinterpret_cast<u32*>(&im)};
}
DEV C2 pk2(const float2 (&a)[2]) { return {pk_hf(a[0].x, a[1].x), pk_hf(a[0].y, a[1].y)}; }
DEV C2 pk2c(const float2 (&a)[2]) { return {pk_hf(a[0].x, a[1].x), pk_hf(-a[0].y, -a[1].y)}; }
DEV u32 cpy(u32 x, u32 zr, int alt) {
  u32 r;
  if (alt) asm volatile("xor.b32 %0,%1,%2;" : "=r"(r) : "r"(x), "r"(zr)); else asm volatile("mad.lo.u32 %0,%2,%2,%1;" : "=r"(r) : "r"(x), "r"(zr));
  return r;
}
template <int N> DEV void inc(u32& x) { asm volatile("add.u32 %0,%0,%1;" : "+r"(x) : "n"(N)); }
DEV u32 opq(u32 x) { u32 r; asm volatile("mov.u32 %0,%1;" : "=r"(r) : "r"(x)); return r; }
DEV u32 chan(u32 b, u32 i) { return 16 * (b >> 2) + 2 * (b & 3) + (i & 1) + 4 * (i & 2); }
DEV u32 row16(u32 lane) { const u32 r0 = (lane & 7) + ((lane >> 3) & 1) + 8 * (lane >> 4) - 1; return (r0 ^ ((r0 >> 3) & 3)) * 16; }
DEV u32 clk() { u32 r; asm volatile("mov.u32 %0,%%clock;" : "=r"(r)::"memory"); return r; }
DEV void wait_clk(u32 t, int d) { while ((int)(clk() - t) < d); }
DEV float ex2(float x) { float r; asm("ex2.approx.ftz.f32 %0,%1;" : "=f"(r) : "f"(x)); return r; }
DEV float rcpf(float x) { float r; asm("rcp.approx.ftz.f32 %0,%1;" : "=f"(r) : "f"(x)); return r; }
DEV float2 cmul(float2 a, float2 b) { return make_float2(fmaf(a.x, b.x, -a.y * b.y), fmaf(a.x, b.y, a.y * b.x)); }
DEV float2 csq(float2 a) { return make_float2(fmaf(a.x, a.x, -a.y * a.y), (a.x + a.x) * a.y); }
DEV float2 cexp(float lr2, float th) {
  const float m = ex2(lr2);
  return make_float2(m * __cosf(th), m * __sinf(th));
}
DEV float silu_f(float v) { return v * rcpf(1.f + ex2(-1.4426950408889634f * v)); }
constexpr u32 B2P64 = 0x5F805F80u, B2M64 = 0x1F801F80u, BONE = 0x3F803F80u;
constexpr u32 MODJ = 18 * 128;
DEV float sqrta(float x) { float r; asm("sqrt.approx.ftz.f32 %0,%1;" : "=f"(r) : "f"(x)); return r; }
DEV u32 fu(float x) { return __float_as_uint(x); }
DEV float uf(u32 x) { return __uint_as_float(x); }
DEV void mma_hf_o(float (&d)[4], const float (&c)[4], const u32 (&a)[4], u32 b0, u32 b1) {
  asm("mma.sync.aligned.m16n8k16.row.col.f32.f16.f16.f32 {%0,%1,%2,%3},{%4,%5,%6,%7},{%8,%9},{%10,%11,%12,%13};"
      : "=f"(d[0]), "=f"(d[1]), "=f"(d[2]), "=f"(d[3]) : "r"(a[0]), "r"(a[1]), "r"(a[2]), "r"(a[3]), "r"(b0), "r"(b1), "f"(c[0]), "f"(c[1]), "f"(c[2]), "f"(c[3]));
}

DEV void mma_hf_t(float (&c)[4], const u32 (&a)[4], u32 b0, u32 b1) { mma_hf(c, a[0], a[1], a[2], a[3], b0, b1); }
DEV void cpa16(u32 dst, const void* src) { asm volatile("cp.async.cg.shared.global [%0],[%1],16;" ::"r"(dst), "l"(src) : "memory"); }
DEV void tm_pre(const CUtensorMap* tm) { asm volatile("prefetch.tensormap [%0];" ::"l"((uint64_t)tm) : "memory"); }
#define PROXY_FENCE() asm volatile("fence.proxy.async.shared::cta;" ::: "memory")
struct Prm {
  const char *la, *ai, *cr, *ci, *ldt;
  u32 zero;
  const char *x, *c;
  char* gs;
  const char *dsk, *wr, *wg, *wu, *wd;
  char* out;
};
constexpr float LOG2E = 1.4426950408889634f, F2P64 = 1.8446744073709552e19f, F2M64 = 5.421010862427522e-20f;

template <int S> DEV void y_store(float c0, float c1, float c2, float c3, u32 F, u32 pml, char* yp) {
  str32(yp, bmul(pk_bf(c0, c2), F) | pml);
  str32(yp + S, bmul(pk_bf(c1, c3), F) | pml);
}
DEV void merge4(u32 (&h)[8], uint4 a, uint4 b) {
  const u32 e1 = min(a.x, b.x), e2 = max(a.z, b.z), o1 = min(a.y, b.y), o2 = max(a.w, b.w), o0 = max(a.y, b.y), e3 = min(a.z, b.z);
  const u32 f1 = max(e1, e2), f2 = min(e1, e2), p1 = max(o1, o2), p2 = min(o1, o2);
  h[0] = max(a.x, b.x); h[1] = max(o0, f1); h[2] = min(o0, f1); h[3] = max(p1, f2); h[4] = min(p1, f2); h[5] = max(p2, e3); h[6] = min(p2, e3); h[7] = min(a.w, b.w);
}
DEV void top8(u32 (&a)[8], uint4 l, uint4 m) {
  u32 b[8];
  merge4(b, l, m);
#pragma unroll
  for (int i = 0; i < 8; i++) a[i] = max(a[i], b[7 - i]);
#pragma unroll
  for (int s = 4; s; s >>= 1)
#pragma unroll
    for (int i = 0; i < 8; i++) if (!(i & s)) { const u32 x = a[i], y = a[i + s]; a[i] = max(x, y); a[i + s] = min(x, y); }
}
#define POLL(load, cond_bad, code) { int it_ = 0; do { load; } while (__any_sync(~0u, (cond_bad)) & (++it_ <= SPIN)); if (it_ > SPIN) { ERRF(code); } TSN(code, it_); }
#define POLLW(load, cond_bad, code) { int it_ = 0; while (__any_sync(~0u, (cond_bad))) { if (++it_ > SPIN) { ERRF(code); break; } load; } TSN(code, it_); }

#define DOWN(E) if (tid == 288 && b < 108) { const u32 c0 = 64 * (b % 9), c2 = 4 * (b / 9); \
    if (!D0C && E == 1) { mb_expect(SM_MB + 24, 49152); tma3d(SM_TAP, tm_down, SM_MB + 24, c0, c2); } \
    if (DE1 == E) tma3d(SM_WD, tm_down, SM_MB + 24, c0, c2 + 1); \
    if (DE2 == E) tma3d(SM_WD + 12288, tm_down, SM_MB + 24, c0, c2 + 2); \
    if (DE3 == E) tma3d(SM_WD + 24576, tm_down, SM_MB + 24, c0, c2 + 3); }
#define OUTR(E) if (((OUTA == E) | (OUTB == E) << 1) & ot) { const u32 tl = 4 * ((lane >> 1) & 1) + ((lane >> 2) & 3) + 8 * (lane & 1); \
    bulk_out<1152>(p.out + (b * BLK + tl * 1152), SM_XST + ((lane & 2) + 4 * (lane & 1) + ((lane >> 2) & 1) + (lane & 8)) * ROW); \
    asm volatile("cp.async.bulk.commit_group;" ::: "memory"); }
struct FA { u32 tid, ba, ra, sa; char *ad, *as; };
DEV FA ffn_addr(const Prm& p, u32 tid, u32 b) {
  const u32 w = tid >> 5, lane = tid & 31, kq = w & 3, tg = w >> 2, t = 7 - w;
  FA f = {tid, SM_XS + (lane & 7) * ROW + (18 * kq + (lane >> 3)) * 16, SM_RED + (8 * tg + kq) * 512 + lane * 16, SM_RED + t * 2048 + lane * 16,
          p.gs + (G_ACT + (t < 4 ? 4 * b + t : 512 + (b >> 1)) * 128 + lane * 4), p.gs + (G_ACT + (b / 9) * 6144 + tid * 16)};
  if (AW & 2) { pin(tid >> 16, f.ba, f.ra, f.sa, tid); pin2(tid >> 16, f.ad, f.as); }
  return f;
}
DEV void ffn_tail(const Prm& p, const CUtensorMap* tm_down, uint4 (&A)[24], const FA f, const u32 b, const u32 par, const u32 ot) {
  const u32 tid = f.tid, w = tid >> 5, lane = tid & 31, g = lane >> 2, q = lane & 3, tg = w >> 2, zr = tid >> 16;
  const u32 rho = b & 1, pm = par ? TAGM : 0, ba = f.ba, ra = f.ra;
  char* const gs = p.gs;
  char *const ad = f.ad, *const as = f.as;
  __syncthreads();
  TS(25);
  if (!(AW & 4)) DOWN(5);
  {
    float c0[2][4] = {}, c1[2][4] = {};
    uint4 bb[5];
#pragma unroll
    for (int s = 0; s < 5; s++) bb[s] = ldsm4(ba + s * 64);
    if (AW & 4) DOWN(5);
#pragma unroll
    for (int s = 0; s < 9; s++) mma_bf(c0[s & 1], A[s].x, A[s].y, A[s].z, A[s].w, s & 1 ? bb[s >> 1].z : bb[s >> 1].x, s & 1 ? bb[s >> 1].w : bb[s >> 1].y);
    if (tg < 2) {
#pragma unroll
      for (int s = 0; s < 9; s++) mma_bf(c1[s & 1], A[9 + s].x, A[9 + s].y, A[9 + s].z, A[9 + s].w, s & 1 ? bb[s >> 1].z : bb[s >> 1].x, s & 1 ? bb[s >> 1].w : bb[s >> 1].y);
      sts128(ra + 2048, fu(c1[0][0] + c1[1][0]), fu(c1[0][1] + c1[1][1]), fu(c1[0][2] + c1[1][2]), fu(c1[0][3] + c1[1][3]));
    }
    sts128(ra, fu(c0[0][0] + c0[1][0]), fu(c0[0][1] + c0[1][1]), fu(c0[0][2] + c0[1][2]), fu(c0[0][3] + c0[1][3]));
  }
  TS(39);
  __syncthreads();
  const u32 tr = clk();
  OUTR(6);
  if (w - 3 - rho < 5 - rho) {
    float s[4];
    const uint4 u0 = lds128(f.sa), u1 = lds128(f.sa + 512), u2 = lds128(f.sa + 1024), u3 = lds128(f.sa + 1536);
    s[0] = (uf(u0.x) + uf(u1.x)) + (uf(u2.x) + uf(u3.x)); s[1] = (uf(u0.y) + uf(u1.y)) + (uf(u2.y) + uf(u3.y));
    s[2] = (uf(u0.z) + uf(u1.z)) + (uf(u2.z) + uf(u3.z)); s[3] = (uf(u0.w) + uf(u1.w)) + (uf(u2.w) + uf(u3.w));
    const u32 sg = pk_bf(silu_f(rbf(s[0])), silu_f(rbf(s[1])));
    const u32 act = movm(bmul(bmul(sg, pk_bf(s[2], s[3])), B2M64));
    str32(ad, act | (q ? 0 : pm));
  }
  TS(26);
  const bool fin = w == 8 && b < 72;
  u32 kg;
  uint4 xt;
  const char* xs;
  if (fin) { kg = lds32(SM_SLOT + 4 * g); xs = rowa(gs + (G_Y + 16 * b), kg); xt = ldr128(xs); }
  if (b < 108) {
    uint4 a;
    if (AD) a.x = INVAL; else a = ldr128(as);
    if (AD && w >= 4) wait_clk(tr, AD);
    char* const dst = gs + (G_PART + b * 2048 + w * 512 + lane * 8);
    if (w < 4) {
      const u32 aa = SM_WD + (8 * (lane >> 4) + (lane & 7)) * 128 + (((2 * w + ((lane >> 3) & 1)) ^ (lane & 7)) << 4);
      mb_wait(SM_MB + 24);
#pragma unroll
      for (int s = 0; s < 24; s++) A[s] = ldsm4t(aa + (s < 6 ? SM_TAP - SM_WD : -12288) + s * 2048);
      if (AW & 2) pin2(zr, dst, as);
    }
    TS(28);
    POLLW(rld128<TAGM>(a, as, pm), (a.x ^ pm) & TAGM, 9);
    sts128(SM_AC + tid * 16, a.x, a.y, a.z, a.w); sts32(SM_AC + tid * 16, a.x & ~TAGM);
    TS(27);
    if (w < 4) {
      bsync(8, 384);
      float c[4][4] = {};
#pragma unroll
      for (int s = 0; s < 12; s++) {
        const uint4 bb = ldsm4(SM_AC + lane * 16 + s * 512);
        mma_bf(c[2 * (s & 1)], A[2 * s].x, A[2 * s].y, A[2 * s].z, A[2 * s].w, bb.x, bb.y);
        mma_bf(c[2 * (s & 1) + 1], A[2 * s + 1].x, A[2 * s + 1].y, A[2 * s + 1].z, A[2 * s + 1].w, bb.z, bb.w);
      }
      u32 o[4];
#pragma unroll
      for (int i = 0; i < 4; i++) o[i] = fu(((c[0][i] + c[1][i]) + (c[2][i] + c[3][i])) * F2P64);
      str64(dst, (o[0] & ~1u) | par, o[1]); str64(dst + 256, (o[2] & ~1u) | par, o[3]);
      TS(29);
    } else barrive(8, 384);
  }
  OUTR(7);
  if (fin) {
    const u32 ta = clk();
    const char* src = gs + (G_PART + (b >> 3) * 2048 + (b & 7) * 256 + lane * 8);
    const u32 gw = lds32(SM_MODS + 5760 + 16 * b + 4 * q);
    const u32 hw = lds32(SM_XS + g * ROW + b * 16 + q * 4);
    const float sgm = rcpf(1.f + ex2(-LOG2E * bhi(kg ^ (~((int)kg >> 31) | 0x80000000))));
    char* const dst = (char*)rowa(p.out + (16 * b + 4 * q), kg);
    POLLW(rld128<TAGM>(xt, xs, TAGR), (xt.x ^ TAGR) & TAGM, 10);
    const u32 x1w = (q & 2) ? ((q & 1) ? xt.w : xt.z) : ((q & 1) ? xt.y : bmul(xt.x ^ TAGR, B2P64));
    const u32 sg2 = pk_bf(sgm, sgm);
    pin(zr, x1w, gw, hw, sg2); pin2(zr, dst, src);
    uint64_t v[12];
#pragma unroll
    for (int j = 0; j < 12; j++) v[j] = par ^ 1;
    float s0, s1;
    if (PD) wait_clk(ta, PD);
#define VL(j) (u32)v[j]
#define VS(j, s) ((uf((u32)(v[j] >> s)) + uf((u32)(v[j + 1] >> s))) + (uf((u32)(v[j + 2] >> s)) + uf((u32)(v[j + 3] >> s))))
    POLL({ _Pragma("unroll") for (int j = 0; j < 12; j++) rld64<1>(v[j], src + j * 9 * 2048, par);
           s0 = VS(0, 0) + VS(4, 0) + VS(8, 0); s1 = VS(0, 32) + VS(4, 32) + VS(8, 32);
           asm volatile("" : "+f"(s0), "+f"(s1)); },
         lop3<0xa8>(lop3<0xfe>(ne3(VL(0), VL(1), par), ne3(VL(2), VL(3), par), ne3(VL(4), VL(5), par)),
                    lop3<0xfe>(ne3(VL(6), VL(7), par), ne3(VL(8), VL(9), par), ne3(VL(10), VL(11), par)), 1), 11);
    const u32 y = movm(pk_bf(s0, s1));
    asm volatile("st.global.u32 [%0],%1;" ::"l"(dst), "r"(badd(x1w, bmul(gw, badd(hw, bmul(y, sg2))))) : "memory");
    if (b == 0 && lane == 0) str32(gs + G_EP, par);
    TS(30); TSE();
  }
  if (w == 10) asm volatile("cp.async.bulk.wait_group.read 0;" ::: "memory");
}

DEV u32 y_off(u32 tid, u32 b) { return G_Y + (16 * (tid >> 5) + 8 * ((tid >> 1) & 1) + ((tid >> 2) & 4)) * BLK + b * 128 + ((tid >> 2) & 3) * 32 + (tid & 1) * 16; }
DEV void post_conv(const Prm& p, const CUtensorMap* tm_down, const u32 tid, const u32 b) {
  const u32 w = tid >> 5, lane = tid & 31;
  const u32 g = lane >> 2, q = lane & 3, e = g >> 2, h = (g >> 1) & 1, hi = g & 1;
  const u32 pm = lds32(SM_THR + 4), par = pm >> 30;
  char* const gs = p.gs;
  const u32 cho = 128 * w + 64 * e + 16 * q;
  u32 x1[4][4], h2[4][4], key[4], lt;
  char* const rowp = gs + (b * BLK + (4 * h + 8 * hi) * 1152 + cho);
  u32 ot = 0;
  FA fa;
  uint4 A[24];
#define AROW(t) const u32 arow = 144 * ((t >> 5) & 3) + ((t >> 1) & 8) + (t & 7), ab = (t & 8) ? SM_UP : SM_GATE;
#define AFRAG9() { _Pragma("unroll") for (int s = 0; s < 9; s++) A[s] = ldsm4t(ab + SLV + arow * 16 + s * 256); }
#define AFRAG18() { const u32 t3 = opq(tid); AROW(t3); if (t3 < 256) { const u32 aa = ab + arow * 64 + ((((t3 >> 6) & 2) ^ ((t3 & 7) >> 1)) << 4); \
      _Pragma("unroll") for (int s = 0; s < 9; s++) { A[s] = ldsm4t(aa + s * 1024); A[9 + s] = ldsm4t((aa ^ 16) + s * 1024); } } else AFRAG9(); }
  if (w < 9) {
    const u32 yc = 8 * (q >> 1) + 2 * (g >> 1), y1 = w < 8 ? BLK : 4 * BLK, y2 = 2 * y1;
    const char* ysrc = gs + (w < 8 ? y_off(tid, b) : G_Y + (q & 1) * 16 + (8 * yc + 2 * hi + ((b >> 4) & 1)) * BLK + 16384 + ((b >> 5) * 16 + (b & 15)) * 32);
    const char* const ys[4] = {ysrc, ysrc + y1, ysrc + y2, ysrc + (y1 + y2)};
    u32 tc = clk();
    uint4 yv[4];
#pragma unroll
    for (int v = 0; v < 4; v++) yv[v].x = INVAL;
    if (w < 4 && b < YL) {
#pragma unroll
      for (int v = 0; v < 4; v++) yv[v] = ldr128(ys[v]);
    }
    if (w == 8) { bsync(7, 160); tc = clk(); }
    const u32 ma = SM_MODS + cho, xa = SM_XST + (2 * h + 4 * hi) * ROW + cho;
    const uint4 sa = lds128(ma), ca = lds128(ma + 1152), ga = lds128(ma + 2304);
    const uint4 rb = lds128((g & 2) ? SM_ONE + 16 * hi : (ma ^ 64) + 8064 + 1152 * hi);
    const u32 saw[4] = {sa.x, sa.y, sa.z, sa.w}, caw[4] = {ca.x, ca.y, ca.z, ca.w}, gaw[4] = {ga.x, ga.y, ga.z, ga.w};
#pragma unroll
    for (int k = 0; k < 4; k++) {
      const uint2 st = lds64(SM_ST + 16 * (2 * h + 4 * hi + (k & 1) + 8 * (k >> 1)));
      const uint4 xv = lds128(xa + ((k & 1) + 8 * (k >> 1)) * ROW);
      x1[k][0] = xv.x; x1[k][1] = xv.y; x1[k][2] = xv.z; x1[k][3] = xv.w;
#pragma unroll
      for (int v = 0; v < 4; v++) x1[k][v] = badd(x1[k][v], bfma(bmul(badd(x1[k][v], st.x), st.y), caw[v], saw[v]));
    }
    const bool own = (q >> 1) == e;
    const u32 spw = SM_SP + (2 * w + e) * 320 + (g & 3) * 16 + (own ? ((q & 1) == h ? 4 : 12) : 8 - 8 * (q & 1));
    if (w >= 4) {
      if (b < (w < 8 ? YE : Y8)) {
        if (W8D && w == 8 && b >= 64) wait_clk(tc, W8D);
        TS(18);
#pragma unroll
        for (int v = 0; v < 4; v++) yv[v] = ldr128(ys[v]);
      }
      bsync(12, N12);
      tc = clk();
    }
    if (b >= YL) wait_clk(tc, YD);
    TS(13);
    POLLW(_Pragma("unroll") for (int v = 0; v < 4; v++) if ((yv[v].x ^ pm) & TAGM) yv[v] = ldr128(ys[v]),
          ((yv[0].x ^ pm) | (yv[1].x ^ pm) | (yv[2].x ^ pm) | (yv[3].x ^ pm)) & TAGM, 5);
    TS(19);
    if (w < 4) asm volatile("setmaxnreg.dec.sync.aligned.u32 168;");
#pragma unroll
    for (int k = 0; k < 4; k += 2) {
      float X[4] = {}, Y[4] = {}, R[4] = {};
#pragma unroll
      for (int v = 0; v < 4; v++) {
        const u32 y0 = k ? yv[v].z : yv[v].x & ~TAGM, y1 = k ? yv[v].w : yv[v].y;
        x1[k][v] = bfma(movm(y0), gaw[v], x1[k][v]);
        x1[k + 1][v] = bfma(movm(y1), gaw[v], x1[k + 1][v]);
        mma8_bf(X, x1[k][v], x1[k + 1][v], x1[k][v]); mma8_bf(Y, x1[k][v], x1[k + 1][v], x1[k + 1][v]);
        if (v & 1) mma_bf(R, x1[k][v - 1], x1[k + 1][v - 1], x1[k][v], x1[k + 1][v], v & 2 ? rb.z : rb.x, v & 2 ? rb.w : rb.y);
      }
      sts32(spw + k * 64, fu(own ? (hi ? X[1] : X[0]) : R[0] + R[1]));
      sts32(spw + k * 64 + 64, fu(own ? (hi ? Y[3] : Y[2]) : R[2] + R[3]));
    }
    barrive(1, N1);
    TS(36);
    const uint4 sb = lds128(ma + 3456), cb = lds128(ma + 4608), gb = lds128(ma + 5760);
    const u32 sbw[4] = {sb.x, sb.y, sb.z, sb.w}, cbw[4] = {cb.x, cb.y, cb.z, cb.w}, gbw[4] = {gb.x, gb.y, gb.z, gb.w};
    bsync(2, 320);
    TS(37);
    lt = lds32(SM_THR);
#pragma unroll
    for (int k = 0; k < 4; k++) {
      const uint4 st = lds128(SM_ST2 + 64 * k + 16 * (g & 3));
      key[k] = st.w;
      u32 o[4];
#pragma unroll
      for (int v = 0; v < 4; v++) {
        const u32 d = badd(x1[k][v], st.x), z = bfma(d, st.y, bmul(d, st.z));
        h2[k][v] = FH ? bfma(z, cbw[v], sbw[v]) : badd(bmul(z, cbw[v]), sbw[v]);
        o[v] = FO ? bfma(gbw[v], h2[k][v], x1[k][v]) : badd(x1[k][v], bmul(gbw[v], h2[k][v]));
      }
      h2[k][0] = bmul(h2[k][0], B2M64) | TAGR;
      if (key[k] >= lt) str128(rowp + k * 1152, h2[k][0], h2[k][1], h2[k][2], h2[k][3]);
      sts128(xa + ((k & 1) + 8 * (k >> 1)) * ROW, o[0], o[1], o[2], o[3]);
    }
    barrive(3, 320);
    TS(21);
    asm volatile("setmaxnreg.inc.sync.aligned.u32 168;");
    mb_wait(SM_MB + 8); mb_wait(SM_MB + 16);
    AFRAG18();
    TS(22);
    const u32 rr = tid * 57 >> 12, rc = tid * 16 - rr * 1152, sl = SM_SLOT + 8 * rr;
    const char* const rb_ = gs + rc;
    const u32 km = max(max(key[0], key[1]), max(key[2], key[3])), xd = SM_XS + rr * (2 * ROW) + rc;
    if (RW & 2) { pin(tid >> 16, sl, km, xd); pin2(tid >> 16, rb_, rowp); }
    fa = ffn_addr(p, tid | p.zero, b);
    bsync(6, 352);
    TS(24);
    const uint2 sk = lds64(sl);
    const char *r0 = rowa(rb_, sk.x), *r1 = rowa(rb_, sk.y);
    uint4 rv[2] = {ldr128(r0), ldr128(r1)};
    barrive(15, 320);
    const u32 g8 = lds32(SM_SLOT + 28);
    if (__any_sync(~0u, km >= g8 && lt > g8)) {
#pragma unroll
      for (int k = 0; k < 4; k++) if (key[k] >= g8 && key[k] < lt) str128(rowp + k * 1152, h2[k][0], h2[k][1], h2[k][2], h2[k][3]);
    }
    bsync(5, 352);
    const uint2 sf = lds64(sl);
    const u32 f8 = lds32(SM_SLOT + 28);
    if (__any_sync(~0u, km >= f8)) {
#pragma unroll
      for (int k = 0; k < 4; k++) if (key[k] >= f8) str128(rowp + (G_Y + k * 1152), bmul(x1[k][0], B2M64) | TAGR, x1[k][1], x1[k][2], x1[k][3]);
    }
    if (__any_sync(~0u, sf.x != sk.x || sf.y != sk.y)) {
      r0 = rowa(rb_, sf.x); r1 = rowa(rb_, sf.y);
      rv[0].x = rv[1].x = INVAL;
    }
    POLLW({ rld128<TAGM>(rv[0], r0, TAGR); rld128<TAGM>(rv[1], r1, TAGR); }, ne3(rv[0].x, rv[1].x, TAGR) & TAGM, 8);
    TS(38);
#pragma unroll
    for (int j = 0; j < 2; j++) sts128(xd + j * ROW, bmul(rv[j].x ^ TAGR, B2P64), rv[j].y, rv[j].z, rv[j].w);
  } else {
    u32 ok, lr;
    if (w == 10) {
      uint2 rc = lds64(SM_RC + 8 * min(lane, 17u));
      float r1 = lane < 18 ? uf(rc.x) : 0.f, r2 = lane < 18 ? uf(rc.y) : 0.f;
#pragma unroll 1
      for (int o = 16; o; o >>= 1) { r1 += __shfl_xor_sync(~0u, r1, o); r2 += __shfl_xor_sync(~0u, r2, o); }
      const u32 tl = 4 * ((lane >> 1) & 1) + ((lane >> 2) & 3) + 8 * (lane & 1), kl = (2047 - 16 * b - tl) << 2 | par * 3;
      char* const kp = gs + (G_KEY + b * KST);
      const u32 spr = SM_SP + (lane >> 4) * 9 * 320 + (lane & 15) * 16;
      TS(31);
      bsync(1, N1);
      float S1 = 0.f, S2 = 0.f, S3 = 0.f;
#pragma unroll
      for (int i = 0; i < 9; i++) { uint4 t = lds128(spr + i * 320); S1 += uf(t.x); S2 += uf(t.y); S3 += uf(t.z); }
      S1 += __shfl_xor_sync(~0u, S1, 16); S2 += __shfl_xor_sync(~0u, S2, 16); S3 += __shfl_xor_sync(~0u, S3, 16);
      const float mu = S1 * (1.f / 576.f), var = fmaxf(fmaf(-mu, mu, S2 * (1.f / 576.f)), 0.f);
      const float m = rbf(mu), rs = rcpf(rbf(sqrta(rbf(rbf(var) + 1e-5f))));
      const u32 rb = pk_bf(0.f, fmaf(fmaf(-m, r1, S3), rs, r2) + 0.f);
      ok = ((rb ^ (((int)rb >> 31) | 0x80000000)) & 0xffff0000u) | kl;
      const float rh = rbf(rs);
      sts32(SM_KEY + 4 * (lane & 15), ok);
      sts128(SM_ST2 + 16 * (lane & 15), pk_bf(-m, -m), pk_bf(rh, rh), pk_bf(rs - rh, rs - rh), ok);
      __syncwarp();
      const uint4 o0 = lds128(SM_KEY + 2 * (lane & 16)), o1 = lds128(SM_KEY + 2 * (lane & 16) + 16);
      lr = (o0.x > ok) + (o0.y > ok) + (o0.z > ok) + (o0.w > ok) + (o1.x > ok) + (o1.y > ok) + (o1.z > ok) + (o1.w > ok);
      lr += __shfl_xor_sync(~0u, lr, 16);
      if (lane < 16 && lr < 8) str32(kp + 4 * lr, ok);
      if (lr == (b < NB8 ? 7 : NEARLY - 1)) sts32(SM_THR, ok);
      barrive(2, 320);
      if (!KA) barrive(4, 64);
      TS(20);
    } else if (w == 9) {
      if (DB1) bsync(1, N1); else { bsync(12, N12); wait_clk(clk(), DD); }
      if (PFW == 4 && tid == 288) l2_pre<WSH>(p.wd + b * WSH);
      PROXY_FENCE();
      DOWN(1);
    } else {
      const char* ks = gs + (G_KEY + (lane >> 1) * KST + (lane & 1) * 16);
      const u32 kt = par * 3;
      uint4 L[8];
      u32 H[8];
#define KBAD(j) ((L[j].x ^ kt) & 3)
#define KLD(j) L[j] = ldr128(ks + j * 16 * KST)
#pragma unroll
      for (int j = 0; j < 8; j++) L[j].x = INVAL;
      if (KA) bsync(1, N1); else bsync(4, 64);
      wait_clk(clk(), KA + (b < KE ? KD : b < YL ? KDB : KD1));
      TS(34);
      POLL({ _Pragma("unroll") for (int j = 0; j < 8; j++) if (KBAD(j)) KLD(j);
             merge4(H, L[0], L[1]); top8(H, L[2], L[3]);
             asm volatile("" : "+r"(H[0]), "+r"(H[1]), "+r"(H[2]), "+r"(H[3]), "+r"(H[4]), "+r"(H[5]), "+r"(H[6]), "+r"(H[7])); TS(32); },
           KBAD(0) | KBAD(1) | KBAD(2) | KBAD(3) | KBAD(4) | KBAD(5), 6);
      top8(H, L[4], L[5]);
      TS(35);
#pragma unroll 1
      for (u32 pass = p.zero;; pass++) {
        u32 G[8], m[8];
#pragma unroll
        for (int i = 0; i < 8; i++) G[i] = H[i];
#pragma unroll
        for (int r = 0; r < 8; r++) {
          const u32 h0 = G[0];
          m[r] = __reduce_max_sync(~0u, h0);
          if (r == 0) { if (KBAD(6)) KLD(6); if (KBAD(7)) KLD(7); }
          if (r < 7) asm("{.reg .u32 t; sub.u32 t,%1,%2; min.u32 t,t,1; mad.lo.u32 %0,t,%3,%4;}" : "=r"(G[0]) : "r"(m[r]), "r"(h0), "r"(h0 - G[1]), "r"(G[1]));
#pragma unroll
          for (int i = 1; i < 7 - r; i++) G[i] = h0 == m[r] ? G[i + 1] : G[i];
          if ((r & 3) == 3) sts128(SM_SLOT + 4 * r - 12, m[r - 3], m[r - 2], m[r - 1], m[r]);
        }
        asm volatile("{.reg .pred p; setp.eq.u32 p,%0,0; @p bar.arrive 6,352;}" ::"r"(pass) : "memory");
        if (pass) break;
        TS(23);
        POLLW({ if (KBAD(6)) KLD(6); if (KBAD(7)) KLD(7); }, KBAD(6) | KBAD(7), 7);
        if (!__any_sync(~0u, max(L[6].x, L[7].x) > m[7])) break;
        top8(H, L[6], L[7]);
      }
      barrive(5, 352);
      TS(33);
    }
    asm volatile("setmaxnreg.inc.sync.aligned.u32 168;");
    mb_wait(SM_MB + 8); mb_wait(SM_MB + 16);
    AROW(tid);
    AFRAG9();
    fa = ffn_addr(p, tid | p.zero, b);
    TS(22);
    if (w == 10) {
      bsync(3, 320);
      PROXY_FENCE();
      ot = lane < 16 && lr >= 8;
      OUTR(2);
      bsync(6, 352);
      bsync(5, 352);
      if (lane < 16 && lr < 8 && ok < lds32(SM_SLOT + 28)) ot = 2;
      OUTR(4);
    } else if (w == 9) {
      bsync(15, 320);
      DOWN(4);
      TS(13);
    }
  }
  ffn_tail(p, tm_down, A, fa, b, par, ot);
}

__global__ void __launch_bounds__(384, 1)
fused_kernel(const Prm p, const __grid_constant__ CUtensorMap tm_mod, const __grid_constant__ CUtensorMap tm_gate, const __grid_constant__ CUtensorMap tm_gs,
             const __grid_constant__ CUtensorMap tm_up, const __grid_constant__ CUtensorMap tm_us, const __grid_constant__ CUtensorMap tm_down) {
  extern __shared__ __align__(1024) unsigned char smem[];
  u32 la, ai, ldt; uint2 cr, ci;
  {
    const u32 t = threadIdx.x, d = t < 256 ? chan(blockIdx.x, t >> 5) : 512 + (blockIdx.x >> 1), o = d * 256 + 8 * (t & 31), o4 = o + ((t < 256 ? t >> 5 : t >> 3) & 4);
    asm volatile("{.reg .pred p; .reg .u16 h; setp.ne.u32 p,%7,0; @p ld.global.nc.u32 %0,[%8]; @p ld.global.nc.u32 %1,[%9]; @p ld.global.nc.v2.u32 {%2,%3},[%10];"
                 "@p ld.global.nc.v2.u32 {%4,%5},[%11]; @p ld.global.nc.u16 h,[%12]; cvt.u32.u16 %6,h;}"
                 : "=r"(la), "=r"(ai), "=r"(cr.x), "=r"(cr.y), "=r"(ci.x), "=r"(ci.y), "=r"(ldt)
                 : "r"(0x6ffu >> (t >> 5) & 1), "l"(p.la + o4), "l"(p.ai + o4), "l"(p.cr + o), "l"(p.ci + o), "l"(p.ldt + 2 * d));
  }
  const u32 t0 = clk();
  const u32 tid = __shfl_sync(~0u, threadIdx.x, threadIdx.x & 31), b = blockIdx.x + p.zero;
  const u32 w = tid >> 5, lane = tid & 31;
  const u32 g = lane >> 2, q = lane & 3, hi = g & 1;
  const u32 rho = b & 1, Ps = 512 + (b >> 1);
  char* const gs = p.gs;
  TS0();
  const bool kw = w != 8 && w != 11;
  const u32 ksig = w < 8 ? (w & 3) : 4, khf = w < 8 ? (w >> 2) : (w & 1);
  if (!kw) {
    if (tid == 352) {
#pragma unroll
      for (int i = 0; i < 5; i++) mb_init(SM_MB + 8 * i, i < 4 ? 1 : 64);
      asm volatile("fence.mbarrier_init.release.cluster;" ::: "memory");
      tm_pre(&tm_mod);
    }
    const char* cp = p.c + (576 * (w & 1) + 24 * min(lane, 23u));
    const uint2 c0 = ldg64(cp);
    la = c0.x; ai = c0.y; cr = ldg64(cp + 8); ci = ldg64(cp + 16);
  }
  const u32 zr = tid >> 16;
  const u32 epv = ldr32(gs + (G_EP + zr));
  const u32 tp = SM_TAP + ksig * TAPS;
  if (kw && !khf) {
#pragma unroll 1
    for (u32 i = lane * 16; i < TAPS; i += 512) sts128(tp + i, 0, 0, 0, 0);
  }
  if (tid < 128) sts128(SM_INV + 16 * tid, INVAL, 0, 1, 0);
  if (tid >= 252) str128(gs + (tid >= 380 ? G_MOD + b * 128 + q * 16 : b * BLK + 16384 - 252 * 16 + tid * 16), INVAL, 0, 1, 0);
  if (tid == 352 && b < 36) { while (clk() - t0 < DMOD); mb_expect(SM_MB, 36864); tma3d(SM_UP, &tm_mod, SM_MB, 32 * b, 0); }
  if (w < 9) {
    while ((int)(clk() - t0) < DX);
    const char* xp = p.x + (b * BLK + (lane >> 3) * 1152 + 128 * w + 16 * (lane & 7));
    const u32 xd = SM_XST + (((lane >> 3) & 1) + 8 * (lane >> 4)) * ROW + 128 * w + 16 * (lane & 7);
#pragma unroll
    for (int i = 0; i < 4; i++) cpa16(xd + 2 * ROW * i, xp + 4608 * i);
  }
  const u32 ktab = w < 8 ? SM_MODS + w * KTAB : SM_ZS + (w - 9) * KTAB;
  float k2048 = 0.f;
  if (kw) {
    u32 mx = __vmaxu2(__vmaxu2(cr.x & 0x7fff7fff, cr.y & 0x7fff7fff), __vmaxu2(ci.x & 0x7fff7fff, ci.y & 0x7fff7fff));
    const u32 E = max(__reduce_max_sync(~0u, max(mx & 0xffff, mx >> 16)) >> 7, 8u);
    TS(1);
    const float dt = rbf(ex2(blo(ldt) * LOG2E)), csc = uf((257 - E) << 23 | (fu(dt) & 0x7fffff));
    sts32(SM_SC + 16 * ksig + 12, fu(uf(fu(dt) & 0x7f800000) * uf((E - 2) << 23)));
    const u32 crw = khf ? cr.y : cr.x, ciw = khf ? ci.y : ci.x;
    float2 C[2], w4[2], w8[2], w16[2], w32[2], w64[2], w128[2], w256[2], w512[2], a1[2], a2[2], a3[2], t0[2], t1[2], s3[2];
#pragma unroll
    for (int m = 0; m < 2; m++) {
      const float lr2 = rbf(ex2((m ? bhi(la) : blo(la)) * LOG2E)) * dt * -LOG2E, th = (m ? bhi(ai) : blo(ai)) * dt;
      C[m] = make_float2((m ? bhi(crw) : blo(crw)) * csc, (m ? bhi(ciw) : blo(ciw)) * csc);
      const float2 w1 = cexp(lr2, th), w2 = csq(w1);
      w64[m] = cexp(64.f * lr2, 64.f * th);
      w4[m] = csq(w2); w8[m] = csq(w4[m]); w16[m] = csq(w8[m]); w32[m] = csq(w16[m]);
      w128[m] = csq(w64[m]); w256[m] = csq(w128[m]); w512[m] = csq(w256[m]);
      const float2 w1024 = csq(w512[m]);
      a1[m] = cmul(C[m], w1); a2[m] = cmul(C[m], w2); a3[m] = cmul(a1[m], w2);
      t0[m] = cmul(C[m], w1024); t1[m] = cmul(t0[m], w128[m]); s3[m] = cmul(w8[m], w16[m]);
      k2048 += fmaf(t0[m].x, w1024.x, -t0[m].y * w1024.y);
    }
    C2 B0[8], B1[8], B2[8], S[8];
    B0[0] = pk2(C); B0[1] = pk2(a1); B0[2] = pk2(a2); B0[3] = pk2(a3);
    const C2 h4 = pk2(w4), h256 = pk2(w256), h512 = pk2(w512);
#pragma unroll
    for (int i = 0; i < 4; i++) B0[4 + i] = cm2(B0[i], h4);
#pragma unroll
    for (int i = 0; i < 4; i++) B1[i] = cm2(B0[2 * i], h256);
    B1[4] = cm2(B0[0], h512); B1[5] = cm2(B0[4], h512);
    B1[6] = cm2(B1[4], h256); B1[7] = cm2(B1[5], h256);
    const u32 ta = ktab + lane * 128, f = ((lane & 3) << 5) | ((lane & 4) << 2);
#pragma unroll
    for (int i = 0; i < 8; i++) sts128(ta + ((i << 4) ^ f), B0[i].re, B0[i].im, B1[i].re, B1[i].im);
    B2[0] = pk2(t0); B2[1] = pk2(t1);
    B2[2] = cm2(B2[0], h256); B2[3] = cm2(B2[1], h256);
#pragma unroll
    for (int i = 0; i < 4; i++) B2[4 + i] = cm2(B2[i], h512);
    S[0] = {0x3C003C00u, 0u}; S[1] = pk2c(w8); S[2] = pk2c(w16); S[3] = pk2c(s3); S[4] = pk2c(w32);
#pragma unroll
    for (int i = 1; i < 4; i++) S[4 + i] = cm2(S[i], S[4]);
#pragma unroll
    for (int i = 0; i < 8; i++) sts128(ta + 4096 + ((i << 4) ^ f), B2[i].re, B2[i].im, S[i].re, S[i].im);
    const C2 m64 = pk2c(w64), m128 = pk2c(w128);
    sts128(ktab + 8192 + lane * 16, m64.re, m64.im, m128.re, m128.im);
    __syncwarp();
  } else {
    u32 sa = SM_SIL + 576 * (w & 1) + 24 * min(lane, 23u);
#pragma unroll 1
    for (int j = 0; j < 6; j++) {
      sts32(sa, pk_bf(silu_f(blo(la)), silu_f(bhi(la))));
      la = ai; ai = cr.x; cr.x = cr.y; cr.y = ci.x; ci.x = ci.y; sa += 4;
    }
    bsync(7, 64);
  }
  TS(2);
  const u32 pm = (__reduce_or_sync(~0u, epv) & 1) ? 0 : TAGM;
  sts32(SM_THR + 4, pm);
  if (w < 9) {
    asm volatile("cp.async.wait_all;" ::: "memory");
    __syncwarp();
    TS(4);
    if (tid == 256 && b >= 36 && b < 108) { mb_expect(SM_MB, 36864); tma3d(SM_UP, &tm_mod, SM_MB, 32 * b, 0); }
    const u32 xa = SM_XST + (lane & 15) * ROW + 128 * w + 16 * (lane >> 4);
    float s[4] = {}, X[2][4] = {}, Y[2][4] = {};
#pragma unroll
    for (int j = 0; j < 4; j++) {
      const uint4 a = ldsm4(xa + 32 * j);
      mma8_bf(X[0], a.x, a.y, a.x); mma8_bf(Y[0], a.x, a.y, a.y);
      mma8_bf(X[1], a.z, a.w, a.z); mma8_bf(Y[1], a.z, a.w, a.w);
      mma_bf(s, a.x, a.y, a.z, a.w, BONE, BONE);
    }
    uint4 t[4];
#pragma unroll
    for (int j = 0; j < 4; j++) t[j] = ldsm4t(xa + 32 * j);
    const float u0 = hi ? X[0][1] + X[1][1] : X[0][0] + X[1][0], u1 = hi ? Y[0][3] + Y[1][3] : Y[0][2] + Y[1][2];
    if (q == g >> 1) sts128(SM_SP + w * 128 + g * 16, fu(s[0]), fu(u0), fu(s[2]), fu(u1));
    bsync(1, 288);
    TS(7);
    const u32 spr = SM_SP + (lane & 7) * 16 + (lane & 8);
    const uint2 t8 = lds64(spr + 1024);
    const float f8 = lane < 16 ? 1.f : 0.f;
    float S1 = uf(t8.x) * f8, S2 = uf(t8.y) * f8;
#pragma unroll
    for (int i = 0; i < 4; i++) { const uint2 u = lds64(spr + (lane & 16) * 32 + i * 128); S1 += uf(u.x); S2 += uf(u.y); }
    S1 += __shfl_xor_sync(~0u, S1, 16); S2 += __shfl_xor_sync(~0u, S2, 16);
    const float mu = S1 * (1.f / 576.f), var = fmaxf(fmaf(-mu, mu, S2 * (1.f / 576.f)), 0.f);
    const float m = rbf(mu), rs = rcpf(rbf(sqrta(rbf(rbf(var) + 1e-5f))));
    const float ra = rs * 0.0625f;
    sts64(SM_AF + w * 128 + (lane & 15) * 8, fu(ra), fu(-m * ra));
    __syncwarp();
    TS(55);
    const uint4 f0 = lds128(SM_AF + w * 128 + q * 16), f1 = lds128(SM_AF + w * 128 + 64 + q * 16);
    const u32 zdst = SM_GATE + w * 2048 + (g >> 1) * 128 + (lane & 15) * 8;
    const u32 pz = (q & 1) ? 0 : pm;
#pragma unroll
    for (int j = 0; j < 8; j++) {
      const u32 x0 = j & 1 ? t[j >> 1].z : t[j >> 1].x, x1 = j & 1 ? t[j >> 1].w : t[j >> 1].y;
      sts64((j & 1 ? zdst ^ 64 : zdst) + 512 * (j >> 1), pk_hf(fmaf(blo(x0), uf(f0.x), uf(f0.y)), fmaf(bhi(x0), uf(f0.z), uf(f0.w))) | pz,
            pk_hf(fmaf(blo(x1), uf(f1.x), uf(f1.y)), fmaf(bhi(x1), uf(f1.z), uf(f1.w))));
    }
    TS(53);
    if (w < 8) barrive(15, 288);
    else {
      bsync(15, 288);
      TS(54);
      if (lane == 0) {
        PROXY_FENCE();
        bulk_out<BLK>(gs + b * BLK, SM_GATE);
        asm volatile("cp.async.bulk.commit_group;" ::: "memory");
        if (PFG & 1) l2_pre<WSH / 2>(p.wg + b * WSH);
      }
      const float rh = rbf(rs);
      sts128(SM_ST + 16 * (lane & 15), pk_bf(-m, -m), pk_bf(rh, rh), pk_bf(rs - rh, rs - rh), 0);
    }
    TS(5);
  }
  if (kw) {
    float D[5][4] = {};
    u32 ta = ktab + q * 128 + ((g ^ (q << 1)) << 4), tm = ktab + 8192 + q * 16;
#pragma unroll 2
    for (int s = 0; s < 8; s++) {
      const uint4 ca = lds128(ta), cb = lds128(ta + 4096), ma = lds128(tm);
      ta = (ta + 512) ^ 16; tm += 64;
      k2048 += __shfl_xor_sync(~0u, k2048, 16 >> s);
      const C2 s0 = {cb.z, cb.w}, s1 = cm2(s0, {ma.x, ma.y}), s2 = cm2(s0, {ma.z, ma.w}), s3 = cm2(s1, {ma.z, ma.w});
      mma_hf(D[0], s0.re, s1.re, s0.im, s1.im, ca.x, ca.y);
      mma_hf(D[2], s0.re, s1.re, s0.im, s1.im, ca.z, ca.w);
      mma_hf(D[4], s0.re, s1.re, s0.im, s1.im, cb.x, cb.y);
      mma_hf(D[1], s2.re, s3.re, s2.im, s3.im, ca.x, ca.y);
      mma_hf(D[3], s2.re, s3.re, s2.im, s3.im, ca.z, ca.w);
    }
    TS(3);
    const u32 xa = (w < 8 ? SM_MODS + (4 + ksig) * KTAB : SM_ZS) + lane * 16;
    if (khf) {
      __syncwarp();
#pragma unroll
      for (int j = 0; j < 5; j++) sts128(xa + 512 * j, fu(D[j][0]), fu(D[j][1]), fu(D[j][2]), fu(D[j][3]));
      if (lane == 0) sts32(xa + 2560, fu(k2048));
      asm volatile("bar.arrive %0,64;" ::"r"(2 + ksig) : "memory");
    } else {
      const u32 t1 = tp + (q < 2 ? (128 + 4 * g + 2 * q) * 4 : T3 * 4 + ((32 * q - 64 + g) ^ 1) * 2);
      const u32 x = 16 * q + (g >> 1) + hi + 1, tb = tp + (hi ? T7E : T9E) * 4 - 4;
      const u32 te = tb + (x + 2 * (x & 1)) * 2, to = tb + TEO * 4 + (x ^ 1) * 2;
      asm volatile("bar.sync %0,64;" ::"r"(2 + ksig) : "memory");
#pragma unroll
      for (int j = 0; j < 5; j++) { const uint4 t = lds128(xa + 512 * j); D[j][0] += uf(t.x); D[j][1] += uf(t.y); D[j][2] += uf(t.z); D[j][3] += uf(t.w); }
      k2048 = (k2048 + uf(lds32(xa + 2560))) * 0.125f;
#pragma unroll
      for (int r = 0; r < 4; r++) {
        const u32 v = pk_hf(D[2 + (r >> 1)][2 * (r & 1)], D[2 + (r >> 1)][2 * (r & 1) + 1]);
        if (q < 2) {
          const u32 vv = __byte_perm(v, v, 0x1010);
          sts32(t1 + (TO + 32 * r) * 4, vv); sts16(t1 + (TO + 32 * r + 1) * 4 + 2, v >> 16); sts16(t1 + (TO + 32 * r - 1) * 4, v);
          sts64(t1 + (TE + 32 * r) * 4, vv, __byte_perm(v, v, 0x1032));
        } else {
          sts16(t1 + 16 * r, v >> 16);
          if (r == 0 && lane == 2) {
            const u32 vv = __byte_perm(v, v, 0x1010);
            sts32(tp + (TO + 256) * 4, vv); sts16(tp + (TO + 257) * 4 + 2, v); sts16(tp + (TO + 255) * 4, v); sts64(tp + (TE + 256) * 4, vv, vv);
          } else sts16(t1 + 16 * r - ((T3 - T5) * 4 + 6) + 8 * hi, v);
        }
      }
#pragma unroll
      for (int r = 0; r < 2; r++) {
        const u32 v = pk_hf(D[4][2 * r], D[4][2 * r + 1]);
        if (r == 0 && lane == 0) { sts16(tp + T5 * 4 + 62 * 2, v); sts32(SM_KV + 4 * ksig, v & 0xffff); sts16(tp + (T9E + TEO) * 4 + 62 * 2, pk_hf(k2048, 0.f)); }
        else { sts16(te + 8 * r, v); sts16(to + 8 * r, v); }
        sts16(te + 8 * r + 16, v >> 16); sts16(to + 8 * r + 16, v >> 16);
      }
      __syncwarp();
#pragma unroll
      for (int r = 0; r < 4; r++) {
        const u32 v = pk_hf(D[r >> 1][2 * (r & 1) + 1], D[r >> 1][2 * (r & 1)]), t2 = tp + lane * 4 + 128 * r;
        sts32(t2 + TO * 4, v); sts16(t2 + TE * 4, v >> 16); sts16(t2 + (TE + 1) * 4 + 2, v);
      }
      __syncwarp();
    }
  } else if (w == 11 && b < 108) {
    float c[4][4] = {};
    u32 aa = SM_UP + ((lane & 7) + 8 * (lane >> 4)) * 64 + ((((lane >> 3) & 1) ^ ((lane & 7) >> 1)) << 4);
    u32 ba = SM_SIL + (lane >> 3) * 16;
    uint4 a[2][10];
#define GLD(n) { _Pragma("unroll") for (int i = 0; i < 2; i++) { a[n][5 * i] = ldsm4(ba + i * 64); \
      _Pragma("unroll") for (int k = 0; k < 4; k++) a[n][5 * i + 1 + k] = ldsm4t((k & 2 ? aa ^ 32 : aa) + i * 2048 + (k & 1) * 1024); } aa += 4096; ba += 128; }
#define GMM(n) { _Pragma("unroll") for (int i = 0; i < 2; i++) _Pragma("unroll") for (int k = 0; k < 4; k++) { const uint4 f = a[n][5 * i + 1 + k], bb = a[n][5 * i]; \
      mma_bf(c[k], f.x, f.y, f.z, f.w, k & 1 ? bb.z : bb.x, k & 1 ? bb.w : bb.y); } }
    mb_wait(SM_MB);
    TS(56);
    GLD(0);
#pragma unroll 1
    for (int s = 0; s < 4; s++) { GLD(1); GMM(0); GLD(0); GMM(1); }
    GMM(0);
    const float v0 = (q & 1) ? c[0][2] + c[1][2] : c[0][0] + c[1][0], v1 = (q & 1) ? c[2][2] + c[3][2] : c[2][0] + c[3][0];
    str16(gs + (G_MOD + b * 128 + 2 * g + 16 * q), pk_bf(rbf((q & 2) ? v1 : v0) * F2M64, 0.f) | (g < 2 ? pm : 0));
    TS(57);
  }
  TS(6);
  u32 tid2 = tid;
  if (w < 4) {
    asm volatile("setmaxnreg.inc.sync.aligned.u32 232;");
    const u32 tid = tid2 + p.zero, w = tid >> 5, lane = tid & 31, g = lane >> 2, q = lane & 3, hi = g & 1, zr = tid >> 16, tp = SM_TAP + w * TAPS;
    const u32 pml = opq((g & 3) ? 0 : pm);
    const u32 tr = tp + ((hi ? TO : TE) + (g >> 1) - q) * 4;
    u32 T[33][4], B5[5][2], B3[5][2];
#pragma unroll
    for (int d = 0; d < 33; d++) {
      T[d][0] = lds32(tr + 32 * d); T[d][1] = lds32(tr + 32 * d + 16);
      T[d][2] = cpy(d ? T[d - 1][1] : zr, zr, 0); T[d][3] = cpy(T[d][0], zr, 1);
    }
    const u32 t33 = cpy(T[32][1], zr, 0), z33 = cpy(zr, zr, 1);
    if (TPIN) {
#pragma unroll
      for (int d = 0; d < 33; d++) asm volatile("{.reg .pred p; setp.ne.u32 p,%2,0; @p st.shared.v2.u32 [%2],{%0,%1};}" ::"r"(T[d][2]), "r"(T[d][3]), "r"(zr) : "memory");
    }
    const u32 bt = tp + (T5 + g - q) * 4;
#pragma unroll
    for (int d = 0; d < 5; d++) {
      B5[d][0] = lds32(bt + 32 * d); B5[d][1] = lds32(bt + 32 * d - 16);
      B3[d][0] = lds32(bt + 32 * d + (T3 - T5) * 4); B3[d][1] = lds32(bt + 32 * d - 16 + (T3 - T5) * 4);
    }
    u32 za = opq(SM_ZS + 16 + w * ZSS + ((lane >> 3) & 1) * ZPS + ((lane & 7) + (lane >> 4)) * 16);
    u32 wa = opq(SM_W + W5O + w * WSL + row16(lane));
    u32 sa = opq(SM_W + W9O - 2048 + w * WSL + lane * 16);
    u32 yo = opq(G_Y + b * BLK + 256 * q + w * 32 + 4 * g);
    const u32 fa = opq(SM_SC + 16 * w + 8), bw = opq((BW >> 4 * w) & 15), bs = opq((BS >> 4 * w) & 15);
    if (TPIN) asm volatile("{.reg .pred p; setp.ne.u32 p,%8,0; @p st.shared.v4.u32 [%8],{%0,%1,%2,%3}; @p st.shared.v4.u32 [%8],{%4,%5,%6,%7};}"
                           ::"r"(za), "r"(wa), "r"(sa), "r"(yo), "r"(fa), "r"(bw), "r"(bs), "r"(pml), "r"(zr) : "memory");
    TS(8);
    bsync(9, 384);
    TS(11);
    float A[4][4] = {};
    uint4 Z[4];
    Z[0] = ldsm4(za); Z[1] = ldsm4(za + 32);
    const uint2 fc = lds64(fa);
    const u32 F = __byte_perm(fu(uf(fc.x) * uf(fc.y)), 0, 0x3232);
#define STEP(s, b0, b1) { _Pragma("unroll") for (int i = 0; i < 4; i++) mma_hf_t(A[i], T[8 * i + 7 - (s)], b0, b1); }
#define PAIR(n) { Z[(n + 2) & 3] = ldsm4(za + 32 * (n + 2)); STEP(2 * n, Z[n].x, Z[n].y); STEP(2 * n + 1, Z[n].z, Z[n].w); }
#define LAST(N) mma8_hf(N, t33, z33, Z[3].y); float O[4]; mma_hf_o(O, A[0], T[0], Z[3].z, Z[3].w); \
    _Pragma("unroll") for (int i = 0; i < 3; i++) mma_hf_o(A[i], A[i + 1], T[8 * i + 8], Z[3].z, Z[3].w); \
    mma_hf_o(A[3], N, T[32], Z[3].z, Z[3].w);
#pragma unroll 1
    for (int j = 0; j < 4; j++) {
      PAIR(0); PAIR(1); PAIR(2);
      Z[1] = ldsm4(za + 160); STEP(6, Z[3].x, Z[3].y);
      float N[4] = {};
      LAST(N);
      if (INCV) inc<128>(za);
      y_store<128>(O[0], O[1], O[2], O[3], F, pml, gs + yo);
      if (!INCV) za += 128;
      yo += 1024;
      TSJ(j);
    }
    bsyncr(bw);
    uint4 a5;
    if (A5P) a5 = ldsm4t(wa);
#pragma unroll 1
    for (int j = 4; j < 13; j++) {
      if (j == 8) bsyncr(bs);
      if (!A5P) a5 = ldsm4t(wa);
      const uint4 a3 = ldsm4t(wa + (W3O - W5O));
      uint4 s3 = {0, 0, 0, 0};
      if (j >= 8) s3 = lds128(sa);
      PAIR(0);
      float N[4] = {};
#pragma unroll
      for (int i = 0; i < 4; i++) mma_hf(A[i], a5.x, a5.y, a5.z, a5.w, B5[i][0], B5[i][1]);
      mma_hf(N, a5.x, a5.y, a5.z, a5.w, B5[4][0], B5[4][1]);
      if (INCV) asm volatile("{add.u32 %0,%0,256; xor.b32 %0,%0,32;}" : "+r"(wa)); else wa = (wa + 256) ^ 32;
      if (A5P) a5 = ldsm4t(wa);
      PAIR(1);
#pragma unroll
      for (int i = 0; i < 4; i++) mma_hf(A[i], a3.x, a3.y, a3.z, a3.w, B3[i][0], B3[i][1]);
      mma_hf(N, a3.x, a3.y, a3.z, a3.w, B3[4][0], B3[4][1]);
      PAIR(2);
      Z[1] = ldsm4(za + 160); STEP(6, Z[3].x, Z[3].y);
      LAST(N);
      if (INCV) { inc<128>(za); inc<512>(sa); }
      y_store<128>(O[0] + uf(s3.x), O[1] + uf(s3.y), O[2] + uf(s3.z), O[3] + uf(s3.w), F, pml, gs + yo);
      if (!INCV) { za += 128; sa += 512; }
      yo += 1024;
      TSJ(j);
    }
    {
      asm volatile("mov.u32 %0,%%tid.x;" : "=r"(tid2));
      const uint4 s3 = lds128(sa), s4 = lds128(sa + 512), s5 = lds128(sa + 1024);
      float X[3][4] = {{uf(s4.x), uf(s4.y), uf(s4.z), uf(s4.w)}, {}, {uf(s5.x), uf(s5.y), uf(s5.z), uf(s5.w)}};
#pragma unroll
      for (int ty = 0; ty < 2; ty++) {
        const uint4 a = A5P && !ty ? a5 : ldsm4t(wa + ty * (W3O - W5O)), c = ldsm4t((wa ^ 32) + 256 + ty * (W3O - W5O)), d = ldsm4t(wa + 512 + ty * (W3O - W5O));
#pragma unroll
        for (int i = 0; i < 3; i++) mma_hf(A[i], a.x, a.y, a.z, a.w, ty ? B3[i][0] : B5[i][0], ty ? B3[i][1] : B5[i][1]);
#pragma unroll
        for (int i = 0; i < 2; i++) mma_hf(X[i], c.x, c.y, c.z, c.w, ty ? B3[i][0] : B5[i][0], ty ? B3[i][1] : B5[i][1]);
        mma_hf(X[2], d.x, d.y, d.z, d.w, ty ? B3[0][0] : B5[0][0], ty ? B3[0][1] : B5[0][1]);
      }
#pragma unroll
      for (int n = 0; n < 4; n++) {
        const uint4 f0 = n < 2 ? Z[n] : ldsm4(za + 32 * n), f1 = ldsm4(za + 32 * n + 128), f2 = ldsm4(za + 32 * n + 256);
#pragma unroll
        for (int s = 2 * n; s < 2 * n + 2; s++) {
#pragma unroll
          for (int i = 0; i < 3; i++) mma_hf_t(A[i], T[8 * i + 7 - s], s & 1 ? f0.z : f0.x, s & 1 ? f0.w : f0.y);
          mma_hf_t(X[0], T[7 - s], s & 1 ? f1.z : f1.x, s & 1 ? f1.w : f1.y); mma_hf_t(X[1], T[15 - s], s & 1 ? f1.z : f1.x, s & 1 ? f1.w : f1.y);
          mma_hf_t(X[2], T[7 - s], s & 1 ? f2.z : f2.x, s & 1 ? f2.w : f2.y);
        }
      }
      y_store<128>(A[0][0] + uf(s3.x), A[0][1] + uf(s3.y), A[0][2] + uf(s3.z), A[0][3] + uf(s3.w), F, pml, gs + yo);
      y_store<128>(A[1][0] + X[0][0], A[1][1] + X[0][1], A[1][2] + X[0][2], A[1][3] + X[0][3], F, pml, gs + yo + 1024);
      y_store<128>(A[2][0] + X[1][0] + X[2][0], A[2][1] + X[1][1] + X[2][1], A[2][2] + X[1][2] + X[2][2], A[2][3] + X[1][3] + X[2][3], F, pml, gs + yo + 2048);
    }
    barrive(12, N12);
    TS(15);
  } else {
    asm volatile("setmaxnreg.dec.sync.aligned.u32 136;");
    const u32 t8 = tid - 128, pml = (g & 3) ? 0 : pm;
    {
      TS(12);
      if (PFG == 1 && tid == 288) l2_pre<WSH / 2>(p.wg + (b * WSH + WSH / 2));
      const char* zs = gs + ((16 * w - 64 + (lane >> 3)) * BLK + b * 128 + ((lane & 7) * 16 ^ rho * 64));
      const char* zs4 = gs + ((t8 >> 1) * BLK + (Ps >> 4) * 512 + (Ps & 6) * 64 + ((Ps >> 2 ^ Ps) & 2) * 32 + (Ps & 1) * 32 + (t8 & 1) * 16);
      uint4 v[5];
      v[4].x = INVAL;
      if (ZD) wait_clk(t0, ZD);
      if (w == 9) {
        const u32 d = lane < 4 ? chan(b, lane) : Ps;
        const char* mp = gs + (G_MOD + (d >> 5) * 128 + (d & 24) * 2);
        uint4 ta, tc;
        POLL({ ta = ldr128(mp); tc = ldr128(mp + MODJ); v[4] = ldr128(zs4); }, ((ta.x ^ pm) | (tc.x ^ pm)) & TAGM, 2);
        const u32 aw = (d & 4) ? ((d & 2) ? ta.w : ta.z) : ((d & 2) ? ta.y : ta.x & ~TAGM);
        const u32 cw = (d & 4) ? ((d & 2) ? tc.w : tc.z) : ((d & 2) ? tc.y : tc.x & ~TAGM);
        const float sa = ((d & 1) ? bhi(aw) : blo(aw)) * F2P64, c1 = rbf(fmaf((d & 1) ? bhi(cw) : blo(cw), F2P64, 1.f));
        const u32 EM = min(max(fu(fmaxf(32.f * fabsf(c1), fabsf(sa))) >> 23, 80u), 250u);
        const float inv = uf((264 - EM) << 23);
        if (lane < 5) { sts64(SM_SC + 16 * lane, pk_hf(16.f * c1 * inv, 16.f * c1 * inv), pk_hf(sa * inv, sa * inv)); sts32(SM_SC + 16 * lane + 8, (EM - 74) << 23); }
        TS(10);
      }
      POLLW(v[4] = ldr128(zs4), (v[4].x ^ pm) & TAGM, 1);
      TS(58);
#pragma unroll
      for (int j = 0; j < 4; j++) v[j] = ldr128(zs + j * 4 * BLK);
#define MARKERS() if (tid == 256) { \
        bulk_out<2048>(gs + (G_Y + 16384 + b * BLK), SM_INV); \
        _Pragma("unroll") for (int i = MT / 2; i < 8; i++) bulk_out<2048>(gs + (G_Y + 2048 * i + b * BLK), SM_INV); \
        bulk_out<2048>(gs + (G_PART + b * 2048), SM_INV); bulk_out<512>(gs + (G_ACT + b * 512), SM_INV); \
        bulk_out<32>(gs + (G_KEY + b * KST), SM_INV); if (!rho) bulk_out<128>(gs + (G_ACT + Ps * 128), SM_INV); \
        asm volatile("cp.async.bulk.commit_group;" ::: "memory"); }
#define GATE() { mb_expect(SM_MB + 8, rho ? SLV : 46080); \
        _Pragma("unroll") for (int i = GE; i < 3; i++) tma3d(SM_GATE + 12288 * i, &tm_gate, SM_MB + 8, 32 * b, i); \
        if (!rho) tma3d(SM_GATE + SLV, &tm_gs, SM_MB + 8, 4096 + 4 * b, 0); }
#define UP() { mb_expect(SM_MB + 16, rho ? SLV : 46080); tma3d(SM_UP, &tm_up, SM_MB + 16, 32 * b, 0); \
        if (!rho) tma3d(SM_UP + SLV, &tm_us, SM_MB + 16, 4096 + 4 * b, 0); }
      if (PFU == 2 && tid == 256) l2_pre<WSH>(p.wu + b * WSH);
      if (GE && tid == 256) {
        asm volatile("cp.async.bulk.wait_group.read 0;" ::: "memory");
#pragma unroll
        for (int i = 0; i < GE; i++) tma3d(SM_GATE + 12288 * i, &tm_gate, SM_MB + 8, 32 * b, i);
      }
      if (MKT == 0) MARKERS();
      if (PFG == 2 && tid == 256) l2_pre<WSH>(p.wg + b * WSH);
      if (PFG == 3 && tid == 256) l2_pre<WSH / 2>(p.wg + (b * WSH + WSH / 2));
      bsync(8, 256);
      const uint2 cc = lds64(SM_SC + 8 * (t8 & 6)), c4 = lds64(SM_SC + 64);
      POLLW(_Pragma("unroll") for (int j = 0; j < 4; j++) if ((v[j].x ^ pm) & TAGM) v[j] = ldr128(zs + j * 4 * BLK),
           ((v[0].x ^ pm) | (v[1].x ^ pm) | (v[2].x ^ pm) | (v[3].x ^ pm)) & TAGM, 1);
      TS(9);
      const u32 dst = SM_ZS + 128 + (t8 & 7) * ZPS + (16 * w - 64 + (lane >> 3)) * 16;
#pragma unroll
      for (int j = 4; j >= 0; j--) {
        const uint2 c = j < 4 ? cc : c4;
        sts128(j < 4 ? dst + j * 64 : SM_Z4 + 256 + (t8 & 1) * ZP4 + (t8 >> 1) * 16, hfma(v[j].x & ~TAGM, c.x, c.y), hfma(v[j].y, c.x, c.y), hfma(v[j].z, c.x, c.y), hfma(v[j].w, c.x, c.y));
      }
      if (t8 < 96) sts128(t8 < 64 ? SM_ZS + (t8 & 7) * ZPS + (t8 >> 3) * 16 : SM_Z4 + (t8 & 1) * ZP4 + (t8 & 30) * 8, 0, 0, 0, 0);
      if (MKT == 0) asm volatile("cp.async.bulk.wait_group.read 1;" ::: "memory");
      else asm volatile("cp.async.bulk.wait_group.read 0;" ::: "memory");
      bsync(9, 384);
      TS(11);
      if (MKT == 1) MARKERS();
      const bool lng = w < 8 || w == 9;
      const u32 ts = lane + 32 * (w == 8 ? 0 : w - 9), c = min(ts, 71u), ma = SM_MODS + 16 * c;
      const u32 sig = lng ? ksig : ts >> 4, l2 = lng ? lane : 32 + (ts & 15);
      const char* mq = gs + (G_MOD + (c >> 2) * 128 + (c & 3) * 16);
      if (!lng) {
#pragma unroll
        for (int j = 0; j < 6; j++) cpa16(ma + 1152 * j, mq + j * MODJ);
        cpa16(ma + 1152 * 6, p.dsk + 16 * c); cpa16(ma + 1152 * 7, p.wr + 16 * c);
        if (PFU == 3) {
#pragma unroll
          for (int j = 0; j < 4; j++) if (ts < 81) l2_line(p.wu + (b * WSH + (81 * j + ts) * 128));
        }
        if (tid == 352) {
          PROXY_FENCE();
          if (PFU == 1) l2_pre<WSH>(p.wu + b * WSH);
          if (!TG) GATE();
          if (!TU) UP();
        }
      }
      const u32 wb = SM_W + sig * WSL;
      if (sig < 5) {
        const u32 za = (sig < 4 ? SM_ZS + 128 + sig * ZSS : SM_Z4 + 256) + l2 * 32, zb = za + (sig < 4 ? ZPS : ZP4);
        const uint4 c0 = lds128(zb - 32), c1 = lds128(za - 16), c2 = lds128(zb - 16), c3 = lds128(za), c4 = lds128(zb), c5 = lds128(za + 16), c6 = lds128(zb + 16);
        const u32 P[25] = {c0.z, c0.w, c1.x, c1.y, c1.z, c1.w, c2.x, c2.y, c2.z, c2.w, c3.x, c3.y, c3.z, c3.w, c4.x, c4.y, c4.z, c4.w, c5.x, c5.y, c5.z, c5.w, c6.x, c6.y, c6.z};
        u32 Q[25], D1[24], F4[23], W5[21], W3[17];
#pragma unroll
        for (int j = 1; j < 25; j++) Q[j] = __byte_perm(P[j - 1], P[j], 0x5432);
#pragma unroll
        for (int j = 1; j < 24; j++) D1[j] = hadd(P[j], Q[j]);
#pragma unroll
        for (int j = 2; j < 23; j++) F4[j] = hadd(D1[j], D1[j - 1]);
#pragma unroll
        for (int n = 0; n < 21; n++) W5[n] = hadd(F4[n + 2], P[n]);
#pragma unroll
        for (int n = 0; n < 17; n++) W3[n] = hadd(Q[n + 8], D1[n + 7]);
        const u32 a0 = wb + W5O + 64 * l2 + 16 * ((l2 >> 1) & 3);
#pragma unroll
        for (int i = 0; i < 4; i++) {
          sts128(a0 ^ (16 * i), W5[4 * i + 5], W5[4 * i + 6], W5[4 * i + 7], W5[4 * i + 8]);
          sts128((a0 ^ (16 * i)) + (W3O - W5O), W3[4 * i + 1], W3[4 * i + 2], W3[4 * i + 3], W3[4 * i + 4]);
        }
        if (lng) {
          if (lane < 16) sts128(wb + (lane & 7) * 16 + (lane & 8) * 400, 0, 0, 0, 0);
          const u32 a1 = wb + 32 * lane + 16 * ((lane >> 2) & 1);
#pragma unroll
          for (int i = 0; i < 4; i++) {
            const u32 a = (a1 ^ (16 * (i >> 1))) + 1024 * (i & 1), n = 4 * i;
            sts128(a + V2O, hadd(Q[n + 9], P[n + 8]), hadd(Q[n + 10], P[n + 9]), hadd(Q[n + 11], P[n + 10]), hadd(Q[n + 12], P[n + 11]));
            sts128(a + W9O, hadd(F4[n + 4], W5[n]), hadd(F4[n + 5], W5[n + 1]), hadd(F4[n + 6], W5[n + 2]), hadd(F4[n + 7], W5[n + 3]));
            sts128(a + W7O, hadd(F4[n + 6], W3[n]), hadd(F4[n + 7], W3[n + 1]), hadd(F4[n + 8], W3[n + 2]), hadd(F4[n + 9], W3[n + 3]));
          }
        }
      }
      if (w < 8) barriver((BW >> (4 * w - 16)) & 15);
      else if (!(w & 1)) { barriver((BW >> (4 * w - 32)) & 15); barriver((BW >> (4 * w - 28)) & 15); }
      __syncwarp();
      TS(32);
      if (lng) {
        const u32 wa = wb + ((lane >> 3) & 1) * 1024 + (((lane & 7) ^ (lane >> 4)) + 8 * (lane >> 4)) * 16;
        const u32 kv = lds32(SM_KV + 4 * sig), bi = (g >> 1) == q ? (hi ? kv << 16 : kv) : 0u;
        float acc[8][4] = {};
#pragma unroll
        for (int j = 0; j < 4; j++) { const uint4 a = ldsm4t(wa + V2O + j * 256); mma8_hf(acc[2 * j], a.x, a.y, bi); mma8_hf(acc[2 * j + 1], a.z, a.w, bi); }
        u32 bt = tp + (T9E + hi * TEO + (g >> 1) - q) * 4, wt = wa + W9O;
#pragma unroll 1
        for (int ty = 0; ty < 2; ty++) {
          uint4 a[4];
#pragma unroll
          for (int be = 0; be < 4; be++) a[be] = ldsm4t(wt + be * 256);
          u32 b1 = lds32(bt - 16);
#pragma unroll
          for (int d = 0; d < 8; d++) {
            const u32 b0 = lds32(bt + 16 * d);
#pragma unroll
            for (int be = 0; be < 4; be++) if (d + 2 * be < 8) mma_hf(acc[d + 2 * be], a[be].x, a[be].y, a[be].z, a[be].w, b0, b1);
            b1 = b0;
          }
          bt += (T7E - T9E) * 4; wt += W7O - W9O;
        }
        __syncwarp();
#pragma unroll
        for (int j = 0; j < 8; j++) sts128(wb + W9O + j * 512 + lane * 16, fu(acc[j][0]), fu(acc[j][1]), fu(acc[j][2]), fu(acc[j][3]));
        if (w != 9) barriver((BS >> (4 * w - 16)) & 15);
        TS(34);
      }
      if (!lng) {
        asm volatile("cp.async.wait_all;" ::: "memory");
        uint4 md[6];
#pragma unroll
        for (int j = 0; j < 6; j++) md[j] = lds128(ma + 1152 * j);
        const uint4 dk = lds128(ma + 1152 * 6), wr = lds128(ma + 1152 * 7);
        POLLW(_Pragma("unroll") for (int j = 0; j < 6; j++) md[j] = ldr128(mq + j * MODJ),
              ((md[0].x ^ pm) | (md[1].x ^ pm) | (md[2].x ^ pm) | (md[3].x ^ pm) | (md[4].x ^ pm) | (md[5].x ^ pm)) & TAGM, 4);
#pragma unroll
        for (int j = 0; j < 6; j++) {
          const u32 o = (j % 3 == 1) ? BONE : 0x80008000u;
          md[j] = make_uint4(bfma(md[j].x & ~TAGM, B2P64, o), bfma(md[j].y, B2P64, o), bfma(md[j].z, B2P64, o), bfma(md[j].w, B2P64, o));
          if (j > 2) sts128(ma + 1152 * j, md[j].x, md[j].y, md[j].z, md[j].w);
        }
        const uint4 gd = make_uint4(bmul(md[2].x, dk.x), bmul(md[2].y, dk.y), bmul(md[2].z, dk.z), bmul(md[2].w, dk.w));
#pragma unroll
        for (int j = 0; j < 2; j++) sts128(ma + 1152 * j, bmul(md[j].x, gd.x), bmul(md[j].y, gd.y), bmul(md[j].z, gd.z), bmul(md[j].w, gd.w));
        sts128(ma + 2304, bmul(md[2].x, B2P64), bmul(md[2].y, B2P64), bmul(md[2].z, B2P64), bmul(md[2].w, B2P64));
        const uint4 H = make_uint4(bmul(md[4].x, wr.x), bmul(md[4].y, wr.y), bmul(md[4].z, wr.z), bmul(md[4].w, wr.w));
        sts128(ma + 1152 * 7, H.x, H.y, H.z, H.w);
        sts128(ma + 1152 * 8, bfma(md[4].x, wr.x, H.x ^ 0x80008000u), bfma(md[4].y, wr.y, H.y ^ 0x80008000u), bfma(md[4].z, wr.z, H.z ^ 0x80008000u), bfma(md[4].w, wr.w, H.w ^ 0x80008000u));
        float c4[4] = {};
        mma_bf(c4, md[4].x, md[3].x, md[4].y, md[3].y, wr.x, wr.y); mma_bf(c4, md[4].z, md[3].z, md[4].w, md[3].w, wr.z, wr.w);
        if (q == g >> 1) sts64(SM_RC + (ts >> 2) * 8, fu(hi ? c4[1] : c4[0]), fu(hi ? c4[3] : c4[2]));
        if (ts < 2) sts128(SM_ONE + 16 * ts, ts ? 0 : BONE, ts ? 0 : BONE, ts ? 0 : BONE, ts ? 0 : BONE);
        TS(14);
        if (MKT == 2) MARKERS();
        if (w == 8) asm volatile("cp.async.bulk.wait_group 0;" ::: "memory");
        if (PFW == 2) {
#pragma unroll
          for (int j = 0; j < 4; j++) if (ts < 81) l2_line(p.wd + (b * WSH + (81 * j + ts) * 128));
        }
        bsync(13, 96);
        if (w == 8) { barriver(2); barriver(3); barriver(5); barriver(6); }
      }
      if (MB11) { if (w == 8 || w == 9) mb_arrive(SM_MB + 32); } else if (w >= 8) barrive(11, 256);
    }
    if (w < 8) {
      const u32 jw = SWJ && w < 6 ? w ^ 1 : w;
      const int u0 = 4 * (jw - 4) + 2 * rho;
      const u32 t4 = SM_TAP + 4 * TAPS;
      u32 tr = t4 + ((hi ? TO : TE) + (g >> 1) - q) * 4;
      u32 zb = SM_Z4 + 256 + ((lane >> 3) & 1) * ZP4 + u0 * 128 + (lane & 7) * 16 + (lane >> 4) * 128;
      float acc[4][4] = {};
      u32 prev = 0;
#pragma unroll 1
      for (int it = min(u0 + 2, 4); it; it--) {
#pragma unroll
        for (int s = 0; s < 8; s++) {
          const uint4 z = ldsm4(zb - 16 * s);
          const u32 t0 = lds32(tr + 32 * s), t1 = lds32(tr + 32 * s + 16);
          mma_hf(acc[s & 1], t0, t1, prev, t0, z.x, z.y);
          mma_hf(acc[2 + (s & 1)], t0, t1, prev, t0, z.z, z.w);
          prev = t1;
        }
        zb -= 128; tr += 256;
      }
      {
        const uint4 z = ldsm4(zb); const u32 t0 = lds32(tr), t1 = lds32(tr + 16);
        mma_hf(acc[0], t0, t1, prev, t0, z.x, z.y); mma_hf(acc[2], t0, t1, prev, t0, z.z, z.w);
        if (jw > 4) { const uint4 y = ldsm4(zb - 16); mma8_hf(acc[1], t1, zr, y.y); mma8_hf(acc[3], t1, zr, y.w); }
      }
      if (MB11) mb_wait(SM_MB + 32); else bsync(11, 256);
      u32 wa = (SM_W + 4 * WSL + W5O + row16(lane) + (u0 - 3) * 256) ^ 32, bt = t4 + (T5 + g - q) * 4;
#pragma unroll 1
      for (int al = min(u0 - 2, 6); al > 0; al--) {
#pragma unroll
        for (int ty = 0; ty < 2; ty++) {
          const uint4 a = ldsm4t(wa + ty * (W3O - W5O));
          const u32 bb = bt + ty * (T3 - T5) * 4;
          mma_hf(acc[ty], a.x, a.y, a.z, a.w, lds32(bb - 32), lds32(bb - 48));
          mma_hf(acc[2 + ty], a.x, a.y, a.z, a.w, lds32(bb), lds32(bb - 16));
        }
        wa = (wa - 256) ^ 32; bt += 32;
      }
      TS(35);
      const uint2 fc = lds64(SM_SC + 16 * 4 + 8);
      const u32 F = __byte_perm(fu(uf(fc.x) * uf(fc.y)), 0, 0x3232);
      char* yp = gs + (G_Y + 16384 - 2048 + b * BLK + jw * 512 + q * 64 + 4 * g);
#pragma unroll
      for (int j = 0; j < 2; j++) {
        uint4 s3 = {0, 0, 0, 0};
        if (u0 >= 8) s3 = lds128(SM_W + 4 * WSL + W9O + (u0 - 8 + j) * 512 + lane * 16);
        y_store<32>(acc[2 * j][0] + acc[2 * j + 1][0] + uf(s3.x), acc[2 * j][1] + acc[2 * j + 1][1] + uf(s3.y), acc[2 * j][2] + acc[2 * j + 1][2] + uf(s3.z),
                acc[2 * j][3] + acc[2 * j + 1][3] + uf(s3.w), F, pml, yp + j * 256);
      }
      barrive(7, 160);
      TS(16);
    } else {
      if (PFW == 3 && w == 9) {
#pragma unroll 1
        for (int j = 0; j < 12; j++) { if (lane < 27) l2_line(p.wd + (b * WSH + (27 * j + lane) * 128)); wait_clk(clk(), PFP); }
      }
      if (TG | TU | TW) {
        if (tid == 352) {
          if (TG) { wait_clk(t0, TG); GATE(); }
          if (TW < TU) { wait_clk(t0, TW); l2_pre<WSH>(p.wd + b * WSH); }
          if (TU) { wait_clk(t0, TU); UP(); }
          if (TW >= TU) { wait_clk(t0, TW); l2_pre<WSH>(p.wd + b * WSH); }
        }
      } else if (PFW < 2 && tid == 352) { mb_wait(SM_MB + 8); if (PFW) mb_wait(SM_MB + 16); l2_pre<WSH>(p.wd + b * WSH); }
      if (D0C && tid == 352 && b < 108) {
        mb_wait(SM_MB + 16);
        PROXY_FENCE();
        mb_expect(SM_MB + 24, 49152);
        tma3d(SM_TAP, &tm_down, SM_MB + 24, 64 * (b % 9), 4 * (b / 9));
      }
      TS(17);
    }
  }
  post_conv(p, &tm_down, tid2 + p.zero, b);
  TSD();
  if (s2u(smem) != SM0) __trap();
}

typedef CUresult (*EncFn)(CUtensorMap*, CUtensorMapDataType, cuuint32_t, void*, const cuuint64_t*, const cuuint64_t*, const cuuint32_t*, const cuuint32_t*,
                          CUtensorMapInterleave, CUtensorMapSwizzle, CUtensorMapL2promotion, CUtensorMapFloatOOBfill);
static void make_map(EncFn enc, CUtensorMap* tm, void* ptr, int cols, int rows, int bw, int nb, CUtensorMapSwizzle sw, int gr = 192, int prom = 0) {
  cuuint64_t gd[3] = {(cuuint64_t)cols, (cuuint64_t)gr, (cuuint64_t)(rows / gr)}, gs[2] = {(cuuint64_t)cols * 2, (cuuint64_t)cols * 2 * gr};
  cuuint32_t bd[3] = {(cuuint32_t)bw, (cuuint32_t)gr, (cuuint32_t)nb}, es[3] = {1, 1, 1};
  enc(tm, CU_TENSOR_MAP_DATA_TYPE_BFLOAT16, 3, ptr, gd, gs, bd, es, CU_TENSOR_MAP_INTERLEAVE_NONE, sw, (CUtensorMapL2promotion)prom, CU_TENSOR_MAP_FLOAT_OOB_FILL_NONE);
}
extern "C" void kernel_launch(void* const* d_in, const int* in_sizes, int n_in, void* d_out, int out_size) {
  static EncFn enc = nullptr;
  static void* scratch = nullptr;
  if (!enc) {
    cudaGetSymbolAddress(&scratch, g_s);
    cudaDriverEntryPointQueryResult qr;
    cudaGetDriverEntryPoint("cuTensorMapEncodeTiled", (void**)&enc, cudaEnableDefault, &qr);
    cudaFuncSetAttribute(fused_kernel, cudaFuncAttributeMaxDynamicSharedMemorySize, SM_TOTAL);
  }
  CUtensorMap tm_mod, tm_gate, tm_gs, tm_up, tm_us, tm_down;
  make_map(enc, &tm_mod, d_in[13], 3456, 576, 32, 3, CU_TENSOR_MAP_SWIZZLE_64B, 192, PRM);
  make_map(enc, &tm_gate, d_in[9], 4608, 576, 32, 1, CU_TENSOR_MAP_SWIZZLE_64B, 192, PRG);
  make_map(enc, &tm_gs, d_in[9], 4608, 576, 8, 3, CU_TENSOR_MAP_SWIZZLE_NONE);
  make_map(enc, &tm_up, d_in[10], 4608, 576, 32, 3, CU_TENSOR_MAP_SWIZZLE_64B, 192, PRU);
  make_map(enc, &tm_us, d_in[10], 4608, 576, 8, 3, CU_TENSOR_MAP_SWIZZLE_NONE, 192, PRS);
  make_map(enc, &tm_down, d_in[11], 576, 4608, 64, 1, CU_TENSOR_MAP_SWIZZLE_128B, 96);
  Prm p;
  p.x = (const char*)d_in[0]; p.la = (const char*)d_in[1]; p.ai = (const char*)d_in[2]; p.cr = (const char*)d_in[3];
  p.ci = (const char*)d_in[4]; p.ldt = (const char*)d_in[5]; p.dsk = (const char*)d_in[6]; p.wr = (const char*)d_in[8];
  p.wg = (const char*)d_in[9]; p.wu = (const char*)d_in[10]; p.wd = (const char*)d_in[11];
  p.c = (const char*)d_in[12]; p.out = (char*)d_out; p.zero = 0; p.gs = (char*)scratch;
  fused_kernel<<<128, 384, SM_TOTAL>>>(p, tm_mod, tm_gate, tm_gs, tm_up, tm_us, tm_down);
}
```

```cpp
#include <cuda_runtime.h>
#include <cuda.h>
#include <cuda_bf16.h>
#include <cuda_fp16.h>
#include <stdint.h>
#define FUSED 1
#define DEV __device__ __forceinline__
typedef uint32_t u32;

constexpr u32 BLK = 18432, G_Z = 0, G_Y = 128 * BLK, G_MOD = 2 * G_Y, G_KEY = G_MOD + 128 * 128, G_ACT = G_KEY + 128 * 128;
constexpr u32 G_PART = G_ACT + 576 * 128, G_EP = G_PART + 128 * 2048, G_END = G_EP + 128;
__device__ __align__(128) unsigned char g_s[G_END];
#define TS(i)
#define TSJ(j)
#define TS0()
#define TSE()
#define TSD()
#define TSX 0
#define TSN(code, n)
#define ERRF(code)

constexpr int SM0 = 1024;
constexpr int ROW = 1168, SLV = 36864;
constexpr int SM_GATE = SM0, SM_UP = SM_GATE + 46080, SM_XST = SM_UP + 46080, SM_MODS = SM_XST + 16 * ROW, SM_W = SM_MODS + 11008;
constexpr int KTAB = 9216, WSL = 12544, W5O = 128, W3O = 3328, V2O = 6400, W9O = 8448, W7O = 10496;
constexpr int ZPS = 2192, ZSS = 2 * ZPS, ZP4 = 2368;
constexpr int SM_ZS = SM_W + 5 * WSL, SM_Z4 = SM_ZS + 4 * ZSS, SM_TAP = SM_Z4 + 2 * ZP4, TAPS = 3328;
constexpr int SM_MB = SM_TAP + 5 * TAPS;
constexpr int SM_SC = SM_MB + 48;
constexpr int SM_KV = SM_SC + 80;
constexpr int SM_THR = SM_KV + 32;
constexpr int SM_SLOT = SM_THR + 48;
constexpr int SM_KEY = SM_SLOT + 32;
constexpr int SM_ST = SM_KEY + 64;
constexpr int SM_ST2 = SM_ST + 256;
constexpr int SM_RC = SM_ST2 + 256;
constexpr int SM_SP = SM_RC + 192;
constexpr int SM_AF = SM_SP + 1152, SM_SIL = SM_AF + 1152, SM_INV = SM_SIL + 1152, SM_END = SM_SP + 5760;
constexpr int SM_ONE = SM_MODS + 9 * 1152;
constexpr int SM_WD = SM_W, SM_XS = SM_W + 36864, SM_AC = SM_ZS, SM_RED = SM_AC + 6144;
constexpr int SM_TSB = SM_END, SM_TOTAL = SM_END + TSX - SM0;
static_assert(SM_W % 1024 == 0 && SM_TAP % 1024 == 0 && SM_MODS + 8 * KTAB <= SM_ZS && SM_ZS + 2 * KTAB <= SM_TAP && SM_RED + 10240 <= SM_TAP && SM_XS + 8 * ROW <= SM_ZS, "smem map");
static_assert(SM_MB % 16 == 0 && SM_THR % 16 == 0 && SM_ST % 16 == 0 && SM_SP % 16 == 0 && SM_TOTAL <= 232448, "smem map");
constexpr int TE = 4, TO = 276, T5 = 560, T3 = 624, T9E = 680, T7E = 760, TEO = 40;
#define MT 10
#define MKT 1
#define KST 128
#define DE1 1
#define DE2 4
#define DE3 5
#define OUTA 2
#define OUTB 7
#define PFW 1
#define PFU 0
#define KD 700
#define D0C 0
#define YE 104
#define YL 104
#define YD 250
#define OPTM 1
#define Y8 64
#define FH 0
#define FO 0
#define DB1 1
#define KD1 50
#define AD 0
#define PD 0
#define ZD 0
#define DD 1000
#define INCV 1
#define TPIN 0
#define A5P 1
#define SWJ 1
#define TG 0
#define TU 0
#define TW 0
#define KDB 520
#define KA 0
#define MB11 0
#define W8D 0
#define PRM 0
#define PRG 0
#define PRU 0
#define PRS 0
#define KE 64
#define PFP 200
#define GE 0
#define NB8 8
#define DX 0
#define DMOD 1000
#define RW 3
#define AW 7
#define FW 3
#define PFG 1
constexpr int N1 = 320 + 32 * DB1 + 32 * !!KA, N12 = 288 + 32 * !DB1;
constexpr int SPIN = 1 << 16, NEARLY = 4;
constexpr u32 TAGM = 0x40004000u, TAGR = 0x40000000u, INVAL = 0x00004801u;

DEV u32 s2u(const void* p) { return (u32)__cvta_generic_to_shared(p); }
DEV void mma_bf(float (&c)[4], u32 a0, u32 a1, u32 a2, u32 a3, u32 b0, u32 b1) {
  asm("mma.sync.aligned.m16n8k16.row.col.f32.bf16.bf16.f32 {%0,%1,%2,%3},{%4,%5,%6,%7},{%8,%9},{%0,%1,%2,%3};"
      : "+f"(c[0]), "+f"(c[1]), "+f"(c[2]), "+f"(c[3]) : "r"(a0), "r"(a1), "r"(a2), "r"(a3), "r"(b0), "r"(b1));
}
DEV void mma_hf(float (&c)[4], u32 a0, u32 a1, u32 a2, u32 a3, u32 b0, u32 b1) {
  asm("mma.sync.aligned.m16n8k16.row.col.f32.f16.f16.f32 {%0,%1,%2,%3},{%4,%5,%6,%7},{%8,%9},{%0,%1,%2,%3};"
      : "+f"(c[0]), "+f"(c[1]), "+f"(c[2]), "+f"(c[3]) : "r"(a0), "r"(a1), "r"(a2), "r"(a3), "r"(b0), "r"(b1));
}
DEV void mma8_bf(float (&c)[4], u32 a0, u32 a1, u32 b0) {
  asm("mma.sync.aligned.m16n8k8.row.col.f32.bf16.bf16.f32 {%0,%1,%2,%3},{%4,%5},{%6},{%0,%1,%2,%3};"
      : "+f"(c[0]), "+f"(c[1]), "+f"(c[2]), "+f"(c[3]) : "r"(a0), "r"(a1), "r"(b0));
}
DEV void mma8_hf(float (&c)[4], u32 a0, u32 a1, u32 b0) {
  asm("mma.sync.aligned.m16n8k8.row.col.f32.f16.f16.f32 {%0,%1,%2,%3},{%4,%5},{%6},{%0,%1,%2,%3};"
      : "+f"(c[0]), "+f"(c[1]), "+f"(c[2]), "+f"(c[3]) : "r"(a0), "r"(a1), "r"(b0));
}
DEV u32 movm(u32 x) { u32 r; asm("movmatrix.sync.aligned.m8n8.trans.b16 %0,%1;" : "=r"(r) : "r"(x)); return r; }
DEV uint4 ldsm4(u32 a) { uint4 r; asm volatile("ldmatrix.sync.aligned.m8n8.x4.shared.b16 {%0,%1,%2,%3},[%4];" : "=r"(r.x), "=r"(r.y), "=r"(r.z), "=r"(r.w) : "r"(a)); return r; }
DEV uint4 ldsm4t(u32 a) { uint4 r; asm volatile("ldmatrix.sync.aligned.m8n8.x4.trans.shared.b16 {%0,%1,%2,%3},[%4];" : "=r"(r.x), "=r"(r.y), "=r"(r.z), "=r"(r.w) : "r"(a)); return r; }
DEV u32 lds32(u32 a) { u32 r; asm volatile("ld.volatile.shared.u32 %0,[%1];" : "=r"(r) : "r"(a)); return r; }
DEV uint2 lds64(u32 a) { uint2 r; asm volatile("ld.shared.v2.u32 {%0,%1},[%2];" : "=r"(r.x), "=r"(r.y) : "r"(a)); return r; }
DEV uint4 lds128(u32 a) { uint4 r; asm volatile("ld.shared.v4.u32 {%0,%1,%2,%3},[%4];" : "=r"(r.x), "=r"(r.y), "=r"(r.z), "=r"(r.w) : "r"(a)); return r; }
DEV void sts16(u32 a, u32 v) { asm volatile("st.shared.u16 [%0],%1;" ::"r"(a), "h"((unsigned short)v) : "memory"); }
DEV void sts32(u32 a, u32 v) { asm volatile("st.shared.u32 [%0],%1;" ::"r"(a), "r"(v) : "memory"); }
DEV void sts64(u32 a, u32 x, u32 y) { asm volatile("st.shared.v2.u32 [%0],{%1,%2};" ::"r"(a), "r"(x), "r"(y) : "memory"); }
DEV void sts128(u32 a, u32 x, u32 y, u32 z, u32 w) { asm volatile("st.shared.v4.u32 [%0],{%1,%2,%3,%4};" ::"r"(a), "r"(x), "r"(y), "r"(z), "r"(w) : "memory"); }
DEV uint4 ldr128(const void* p) { uint4 v; asm volatile("ld.relaxed.gpu.global.v4.u32 {%0,%1,%2,%3},[%4];" : "=r"(v.x), "=r"(v.y), "=r"(v.z), "=r"(v.w) : "l"(p) : "memory"); return v; }
DEV uint2 ldr64(const void* p) { uint2 v; asm volatile("ld.relaxed.gpu.global.v2.u32 {%0,%1},[%2];" : "=r"(v.x), "=r"(v.y) : "l"(p) : "memory"); return v; }
DEV u32 ldr32(const void* p) { u32 v; asm volatile("ld.relaxed.gpu.global.u32 %0,[%1];" : "=r"(v) : "l"(p) : "memory"); return v; }
template <u32 M> DEV void rld128(uint4& v, const void* p, u32 tag) {
  asm volatile("{.reg .pred p; .reg .u32 t; lop3.b32 t,%0,%5,%6,0x28; setp.ne.u32 p,t,0; @p ld.relaxed.gpu.global.v4.u32 {%0,%1,%2,%3},[%4];}"
               : "+r"(v.x), "+r"(v.y), "+r"(v.z), "+r"(v.w) : "l"(p), "r"(tag), "n"(M) : "memory");
}
template <u32 M> DEV void rld64(uint64_t& v, const void* p, u32 tag) {
  asm volatile("{.reg .pred p; .reg .u32 t, h; mov.b64 {t,h},%0; lop3.b32 t,t,%2,%3,0x28; setp.ne.u32 p,t,0; @p ld.relaxed.gpu.global.u64 %0,[%1];}" : "+l"(v) : "l"(p), "r"(tag), "n"(M) : "memory");
}
template <int L> DEV u32 lop3(u32 a, u32 b, u32 c) { u32 r; asm("lop3.b32 %0,%1,%2,%3,%4;" : "=r"(r) : "r"(a), "r"(b), "r"(c), "n"(L)); return r; }
DEV u32 ne3(u32 a, u32 b, u32 c) { u32 r; asm("lop3.b32 %0,%1,%2,%3,0x7e;" : "=r"(r) : "r"(a), "r"(b), "r"(c)); return r; }
DEV void pin(u32 zr, u32 a, u32 b = 0, u32 c = 0, u32 d = 0) { asm volatile("{.reg .pred p; setp.ne.u32 p,%0,0; @p st.shared.v4.u32 [%0],{%1,%2,%3,%4};}" ::"r"(zr), "r"(a), "r"(b), "r"(c), "r"(d) : "memory"); }
DEV void pin2(u32 zr, const void* a, const void* b) { asm volatile("{.reg .pred p; setp.ne.u32 p,%0,0; @p st.shared.v2.u64 [%0],{%1,%2};}" ::"r"(zr), "l"(a), "l"(b) : "memory"); }
DEV const char* rowa(const char* base, u32 key) { const char* r; asm("mad.wide.u32 %0,%1,288,%2;" : "=l"(r) : "r"(~key & 0x1ffc), "l"(base)); return r; }
DEV void str128(void* p, u32 x, u32 y, u32 z, u32 w) { asm volatile("st.relaxed.gpu.global.v4.u32 [%0],{%1,%2,%3,%4};" ::"l"(p), "r"(x), "r"(y), "r"(z), "r"(w) : "memory"); }
DEV void str64(void* p, u32 x, u32 y) { asm volatile("{.reg .u64 d; mov.b64 d,{%1,%2}; st.relaxed.gpu.global.u64 [%0],d;}" ::"l"(p), "r"(x), "r"(y) : "memory"); }
DEV void str32(void* p, u32 x) { asm volatile("st.relaxed.gpu.global.u32 [%0],%1;" ::"l"(p), "r"(x) : "memory"); }
DEV void str16(void* p, u32 x) { asm volatile("st.relaxed.gpu.global.u16 [%0],%1;" ::"l"(p), "h"((unsigned short)x) : "memory"); }
DEV uint4 ldg128(const void* p) { uint4 v; asm volatile("ld.global.nc.v4.u32 {%0,%1,%2,%3},[%4];" : "=r"(v.x), "=r"(v.y), "=r"(v.z), "=r"(v.w) : "l"(p)); return v; }
DEV uint2 ldg64(const void* p) { uint2 v; asm volatile("ld.global.nc.v2.u32 {%0,%1},[%2];" : "=r"(v.x), "=r"(v.y) : "l"(p)); return v; }
DEV u32 ldg32(const void* p) { u32 v; asm volatile("ld.global.nc.u32 %0,[%1];" : "=r"(v) : "l"(p)); return v; }
DEV u32 ldg16(const void* p) { unsigned short v; asm volatile("ld.global.nc.u16 %0,[%1];" : "=h"(v) : "l"(p)); return v; }
#define bsync(id, n) asm volatile("bar.sync %0,%1;" ::"n"(id), "n"(n) : "memory")
#define barrive(id, n) asm volatile("bar.arrive %0,%1;" ::"n"(id), "n"(n) : "memory")
DEV void bsyncr(u32 id) { asm volatile("bar.sync %0,96;" ::"r"(id) : "memory"); }
DEV void barriver(u32 id) { asm volatile("bar.arrive %0,96;" ::"r"(id) : "memory"); }
constexpr u32 BW = 0x0FEA, BS = 0x6532;
DEV void mb_init(u32 a, u32 n) { asm volatile("mbarrier.init.shared.b64 [%0],%1;" ::"r"(a), "r"(n) : "memory"); }
DEV void mb_arrive(u32 a) { asm volatile("mbarrier.arrive.shared.b64 _,[%0];" ::"r"(a) : "memory"); }
DEV void mb_expect(u32 a, u32 bytes) { asm volatile("mbarrier.arrive.expect_tx.shared.b64 _,[%0],%1;" ::"r"(a), "r"(bytes) : "memory"); }
DEV void mb_wait(u32 a, u32 ph = 0) {
  u32 ok; int it = 0;
  do { asm volatile("{.reg .pred p; mbarrier.try_wait.parity.shared.b64 p,[%1],%2; selp.u32 %0,1,0,p;}" : "=r"(ok) : "r"(a), "r"(ph) : "memory"); } while (!ok && ++it < SPIN);
}
template <int N> DEV void bulk_out(void* dst, u32 src) { asm volatile("cp.async.bulk.global.shared::cta.bulk_group [%0],[%1],%2;" ::"l"(dst), "r"(src), "n"(N) : "memory"); }
constexpr u32 WSH = 41472;
DEV void l2_line(const void* p) { asm volatile("prefetch.global.L2 [%0];" ::"l"(p) : "memory"); }
template <int N> DEV void l2_pre(const void* p) { asm volatile("cp.async.bulk.prefetch.L2.global [%0],%1;" ::"l"(p), "n"(N) : "memory"); }
DEV void tma3d(u32 dst, const CUtensorMap* tm, u32 mb, int c0, int c2) {
  asm volatile("cp.async.bulk.tensor.3d.shared::cluster.global.mbarrier::complete_tx::bytes [%0],[%1,{%3,0,%4}],[%2];"
               ::"r"(dst), "l"((uint64_t)tm), "r"(mb), "r"(c0), "r"(c2) : "memory");
}
DEV float blo(u32 w) { return __uint_as_float(w << 16); }
DEV float bhi(u32 w) { return __uint_as_float(w & 0xffff0000u); }
DEV u32 pk_bf(float lo, float hi) { u32 r; asm("cvt.rn.bf16x2.f32 %0,%1,%2;" : "=r"(r) : "f"(hi), "f"(lo)); return r; }
DEV u32 pk_hf(float lo, float hi) { u32 r; asm("cvt.rn.f16x2.f32 %0,%1,%2;" : "=r"(r) : "f"(hi), "f"(lo)); return r; }
DEV float rbf(float x) { return __uint_as_float(pk_bf(0.f, x) & 0xffff0000u); }
DEV u32 bfma(u32 a, u32 b, u32 c) { u32 r; asm("fma.rn.bf16x2 %0,%1,%2,%3;" : "=r"(r) : "r"(a), "r"(b), "r"(c)); return r; }
DEV u32 bmul(u32 a, u32 b) { u32 r; asm("mul.rn.bf16x2 %0,%1,%2;" : "=r"(r) : "r"(a), "r"(b)); return r; }
DEV u32 badd(u32 a, u32 b) { u32 r; asm("add.rn.bf16x2 %0,%1,%2;" : "=r"(r) : "r"(a), "r"(b)); return r; }
DEV u32 hadd(u32 a, u32 b) { u32 r; asm("add.rn.f16x2 %0,%1,%2;" : "=r"(r) : "r"(a), "r"(b)); return r; }
DEV u32 hfma(u32 a, u32 b, u32 c) { u32 r; asm("fma.rn.f16x2 %0,%1,%2,%3;" : "=r"(r) : "r"(a), "r"(b), "r"(c)); return r; }
struct C2 { u32 re, im; };
DEV C2 cm2(C2 a, C2 b) {
  const __half2 ar = *reinterpret_cast<__half2*>(&a.re), ai = *reinterpret_cast<__half2*>(&a.im), br = *reinterpret_cast<__half2*>(&b.re), bi = *reinterpret_cast<__half2*>(&b.im);
  __half2 re = __hfma2(ar, br, __hneg2(__hmul2(ai, bi))), im = __hfma2(ar, bi, __hmul2(ai, br));
  return {*reinterpret_cast<u32*>(&re), *reinterpret_cast<u32*>(&im)};
}
DEV C2 pk2(const float2 (&a)[2]) { return {pk_hf(a[0].x, a[1].x), pk_hf(a[0].y, a[1].y)}; }
DEV C2 pk2c(const float2 (&a)[2]) { return {pk_hf(a[0].x, a[1].x), pk_hf(-a[0].y, -a[1].y)}; }
DEV u32 cpy(u32 x, u32 zr, int alt) {
  u32 r;
  if (alt) asm volatile("xor.b32 %0,%1,%2;" : "=r"(r) : "r"(x), "r"(zr)); else asm volatile("mad.lo.u32 %0,%2,%2,%1;" : "=r"(r) : "r"(x), "r"(zr));
  return r;
}
template <int N> DEV void inc(u32& x) { asm volatile("add.u32 %0,%0,%1;" : "+r"(x) : "n"(N)); }
DEV u32 opq(u32 x) { u32 r; asm volatile("mov.u32 %0,%1;" : "=r"(r) : "r"(x)); return r; }
DEV u32 chan(u32 b, u32 i) { return 16 * (b >> 2) + 2 * (b & 3) + (i & 1) + 4 * (i & 2); }
DEV u32 row16(u32 lane) { const u32 r0 = (lane & 7) + ((lane >> 3) & 1) + 8 * (lane >> 4) - 1; return (r0 ^ ((r0 >> 3) & 3)) * 16; }
DEV u32 clk() { u32 r; asm volatile("mov.u32 %0,%%clock;" : "=r"(r)::"memory"); return r; }
DEV void wait_clk(u32 t, int d) { while ((int)(clk() - t) < d); }
DEV float ex2(float x) { float r; asm("ex2.approx.ftz.f32 %0,%1;" : "=f"(r) : "f"(x)); return r; }
DEV float rcpf(float x) { float r; asm("rcp.approx.ftz.f32 %0,%1;" : "=f"(r) : "f"(x)); return r; }
DEV float2 cmul(float2 a, float2 b) { return make_float2(fmaf(a.x, b.x, -a.y * b.y), fmaf(a.x, b.y, a.y * b.x)); }
DEV float2 csq(float2 a) { return make_float2(fmaf(a.x, a.x, -a.y * a.y), (a.x + a.x) * a.y); }
DEV float2 cexp(float lr2, float th) {
  const float m = ex2(lr2);
  return make_float2(m * __cosf(th), m * __sinf(th));
}
DEV float silu_f(float v) { return v * rcpf(1.f + ex2(-1.4426950408889634f * v)); }
constexpr u32 B2P64 = 0x5F805F80u, B2M64 = 0x1F801F80u, BONE = 0x3F803F80u;
constexpr u32 MODJ = 18 * 128;
DEV float sqrta(float x) { float r; asm("sqrt.approx.ftz.f32 %0,%1;" : "=f"(r) : "f"(x)); return r; }
DEV u32 fu(float x) { return __float_as_uint(x); }
DEV float uf(u32 x) { return __uint_as_float(x); }
DEV void mma_hf_o(float (&d)[4], const float (&c)[4], const u32 (&a)[4], u32 b0, u32 b1) {
  asm("mma.sync.aligned.m16n8k16.row.col.f32.f16.f16.f32 {%0,%1,%2,%3},{%4,%5,%6,%7},{%8,%9},{%10,%11,%12,%13};"
      : "=f"(d[0]), "=f"(d[1]), "=f"(d[2]), "=f"(d[3]) : "r"(a[0]), "r"(a[1]), "r"(a[2]), "r"(a[3]), "r"(b0), "r"(b1), "f"(c[0]), "f"(c[1]), "f"(c[2]), "f"(c[3]));
}

DEV void mma_hf_t(float (&c)[4], const u32 (&a)[4], u32 b0, u32 b1) { mma_hf(c, a[0], a[1], a[2], a[3], b0, b1); }
DEV void cpa16(u32 dst, const void* src) { asm volatile("cp.async.cg.shared.global [%0],[%1],16;" ::"r"(dst), "l"(src) : "memory"); }
DEV void tm_pre(const CUtensorMap* tm) { asm volatile("prefetch.tensormap [%0];" ::"l"((uint64_t)tm) : "memory"); }
#define PROXY_FENCE() asm volatile("fence.proxy.async.shared::cta;" ::: "memory")
struct Prm {
  const char *la, *ai, *cr, *ci, *ldt;
  u32 zero;
  const char *x, *c;
  char* gs;
  const char *dsk, *wr, *wg, *wu, *wd;
  char* out;
};
constexpr float LOG2E = 1.4426950408889634f, F2P64 = 1.8446744073709552e19f, F2M64 = 5.421010862427522e-20f;

template <int S> DEV void y_store(float c0, float c1, float c2, float c3, u32 F, u32 pml, char* yp) {
  str32(yp, bmul(pk_bf(c0, c2), F) | pml);
  str32(yp + S, bmul(pk_bf(c1, c3), F) | pml);
}
DEV void merge4(u32 (&h)[8], uint4 a, uint4 b) {
  const u32 e1 = min(a.x, b.x), e2 = max(a.z, b.z), o1 = min(a.y, b.y), o2 = max(a.w, b.w), o0 = max(a.y, b.y), e3 = min(a.z, b.z);
  const u32 f1 = max(e1, e2), f2 = min(e1, e2), p1 = max(o1, o2), p2 = min(o1, o2);
  h[0] = max(a.x, b.x); h[1] = max(o0, f1); h[2] = min(o0, f1); h[3] = max(p1, f2); h[4] = min(p1, f2); h[5] = max(p2, e3); h[6] = min(p2, e3); h[7] = min(a.w, b.w);
}
DEV void top8(u32 (&a)[8], uint4 l, uint4 m) {
  u32 b[8];
  merge4(b, l, m);
#pragma unroll
  for (int i = 0; i < 8; i++) a[i] = max(a[i], b[7 - i]);
#pragma unroll
  for (int s = 4; s; s >>= 1)
#pragma unroll
    for (int i = 0; i < 8; i++) if (!(i & s)) { const u32 x = a[i], y = a[i + s]; a[i] = max(x, y); a[i + s] = min(x, y); }
}
#define POLL(load, cond_bad, code) { int it_ = 0; do { load; } while (__any_sync(~0u, (cond_bad)) & (++it_ <= SPIN)); if (it_ > SPIN) { ERRF(code); } TSN(code, it_); }
#define POLLW(load, cond_bad, code) { int it_ = 0; while (__any_sync(~0u, (cond_bad))) { if (++it_ > SPIN) { ERRF(code); break; } load; } TSN(code, it_); }

#define DOWN(E) if (tid == 288 && b < 108) { const u32 c0 = 64 * (b % 9), c2 = 4 * (b / 9); \
    if (!D0C && E == 1) { mb_expect(SM_MB + 24, 49152); tma3d(SM_TAP, tm_down, SM_MB + 24, c0, c2); } \
    if (DE1 == E) tma3d(SM_WD, tm_down, SM_MB + 24, c0, c2 + 1); \
    if (DE2 == E) tma3d(SM_WD + 12288, tm_down, SM_MB + 24, c0, c2 + 2); \
    if (DE3 == E) tma3d(SM_WD + 24576, tm_down, SM_MB + 24, c0, c2 + 3); }
#define OUTR(E) if (((OUTA == E) | (OUTB == E) << 1) & ot) { const u32 tl = 4 * ((lane >> 1) & 1) + ((lane >> 2) & 3) + 8 * (lane & 1); \
    bulk_out<1152>(p.out + (b * BLK + tl * 1152), SM_XST + ((lane & 2) + 4 * (lane & 1) + ((lane >> 2) & 1) + (lane & 8)) * ROW); \
    asm volatile("cp.async.bulk.commit_group;" ::: "memory"); }
struct FA { u32 tid, ba, ra, sa; char *ad, *as; };
DEV FA ffn_addr(const Prm& p, u32 tid, u32 b) {
  const u32 w = tid >> 5, lane = tid & 31, kq = w & 3, tg = w >> 2, t = 7 - w;
  FA f = {tid, SM_XS + (lane & 7) * ROW + (18 * kq + (lane >> 3)) * 16, SM_RED + (8 * tg + kq) * 512 + lane * 16, SM_RED + t * 2048 + lane * 16,
          p.gs + (G_ACT + (t < 4 ? 4 * b + t : 512 + (b >> 1)) * 128 + lane * 4), p.gs + (G_ACT + (b / 9) * 6144 + tid * 16)};
  if (AW & 2) { pin(tid >> 16, f.ba, f.ra, f.sa, tid); pin2(tid >> 16, f.ad, f.as); }
  return f;
}
DEV void ffn_tail(const Prm& p, const CUtensorMap* tm_down, uint4 (&A)[24], const FA f, const u32 b, const u32 par, const u32 ot) {
  const u32 tid = f.tid, w = tid >> 5, lane = tid & 31, g = lane >> 2, q = lane & 3, tg = w >> 2, zr = tid >> 16;
  const u32 rho = b & 1, pm = par ? TAGM : 0, kt = par * 3, ba = f.ba, ra = f.ra;
  char* const gs = p.gs;
  char *const ad = f.ad, *const as = f.as;
  __syncthreads();
  TS(25);
  if (!(AW & 4)) DOWN(5);
  {
    float c0[2][4] = {}, c1[2][4] = {};
    uint4 bb[5];
#pragma unroll
    for (int s = 0; s < 5; s++) bb[s] = ldsm4(ba + s * 64);
    if (AW & 4) DOWN(5);
#pragma unroll
    for (int s = 0; s < 9; s++) mma_bf(c0[s & 1], A[s].x, A[s].y, A[s].z, A[s].w, s & 1 ? bb[s >> 1].z : bb[s >> 1].x, s & 1 ? bb[s >> 1].w : bb[s >> 1].y);
    if (tg < 2) {
#pragma unroll
      for (int s = 0; s < 9; s++) mma_bf(c1[s & 1], A[9 + s].x, A[9 + s].y, A[9 + s].z, A[9 + s].w, s & 1 ? bb[s >> 1].z : bb[s >> 1].x, s & 1 ? bb[s >> 1].w : bb[s >> 1].y);
      sts128(ra + 2048, fu(c1[0][0] + c1[1][0]), fu(c1[0][1] + c1[1][1]), fu(c1[0][2] + c1[1][2]), fu(c1[0][3] + c1[1][3]));
    }
    sts128(ra, fu(c0[0][0] + c0[1][0]), fu(c0[0][1] + c0[1][1]), fu(c0[0][2] + c0[1][2]), fu(c0[0][3] + c0[1][3]));
  }
  TS(39);
  __syncthreads();
  const u32 tr = clk();
  OUTR(6);
  if (w - 3 - rho < 5 - rho) {
    float s[4];
    const uint4 u0 = lds128(f.sa), u1 = lds128(f.sa + 512), u2 = lds128(f.sa + 1024), u3 = lds128(f.sa + 1536);
    s[0] = (uf(u0.x) + uf(u1.x)) + (uf(u2.x) + uf(u3.x)); s[1] = (uf(u0.y) + uf(u1.y)) + (uf(u2.y) + uf(u3.y));
    s[2] = (uf(u0.z) + uf(u1.z)) + (uf(u2.z) + uf(u3.z)); s[3] = (uf(u0.w) + uf(u1.w)) + (uf(u2.w) + uf(u3.w));
    const u32 sg = pk_bf(silu_f(rbf(s[0])), silu_f(rbf(s[1])));
    const u32 act = movm(bmul(bmul(sg, pk_bf(s[2], s[3])), B2M64));
    str32(ad, act | (q ? 0 : pm));
  }
  TS(26);
  const bool fin = w == 8 && b < 72;
  u32 kg;
  uint4 xt;
  const char* xs;
  if (fin) { kg = lds32(SM_SLOT + 4 * g); xs = rowa(gs + (G_Y + 16 * b), kg); xt = ldr128(xs); }
  if (b < 108) {
    uint4 a;
    if (AD) a.x = INVAL; else a = ldr128(as);
    if (AD && w >= 4) wait_clk(tr, AD);
    char* const dst = gs + (G_PART + b * 2048 + w * 512 + lane * 8);
    if (w < 4) {
      const u32 aa = SM_WD + (8 * (lane >> 4) + (lane & 7)) * 128 + (((2 * w + ((lane >> 3) & 1)) ^ (lane & 7)) << 4);
      mb_wait(SM_MB + 24);
#pragma unroll
      for (int s = 0; s < 24; s++) A[s] = ldsm4t(aa + (s < 6 ? SM_TAP - SM_WD : -12288) + s * 2048);
      if (AW & 2) pin2(zr, dst, as);
    }
    TS(28);
    POLLW(rld128<TAGM>(a, as, pm), (a.x ^ pm) & TAGM, 9);
    sts128(SM_AC + tid * 16, a.x, a.y, a.z, a.w); sts32(SM_AC + tid * 16, a.x & ~TAGM);
    TS(27);
    if (w < 4) {
      bsync(8, 384);
      float c[4][4] = {};
#pragma unroll
      for (int s = 0; s < 12; s++) {
        const uint4 bb = ldsm4(SM_AC + lane * 16 + s * 512);
        mma_bf(c[2 * (s & 1)], A[2 * s].x, A[2 * s].y, A[2 * s].z, A[2 * s].w, bb.x, bb.y);
        mma_bf(c[2 * (s & 1) + 1], A[2 * s + 1].x, A[2 * s + 1].y, A[2 * s + 1].z, A[2 * s + 1].w, bb.z, bb.w);
      }
      u32 o[4];
#pragma unroll
      for (int i = 0; i < 4; i++) o[i] = fu(((c[0][i] + c[1][i]) + (c[2][i] + c[3][i])) * F2P64);
      str64(dst, (o[0] & ~3u) | kt, o[1]); str64(dst + 256, (o[2] & ~3u) | kt, o[3]);
      TS(29);
    } else barrive(8, 384);
  }
  OUTR(7);
  if (fin) {
    const u32 ta = clk();
    const char* src = gs + (G_PART + (b >> 3) * 2048 + (b & 7) * 256 + lane * 8);
    const u32 gw = lds32(SM_MODS + 5760 + 16 * b + 4 * q);
    const u32 hw = lds32(SM_XS + g * ROW + b * 16 + q * 4);
    const float sgm = rcpf(1.f + ex2(-LOG2E * bhi(kg ^ (~((int)kg >> 31) | 0x80000000))));
    char* const dst = (char*)rowa(p.out + (16 * b + 4 * q), kg);
    POLLW(rld128<TAGM>(xt, xs, TAGR), (xt.x ^ TAGR) & TAGM, 10);
    const u32 x1w = (q & 2) ? ((q & 1) ? xt.w : xt.z) : ((q & 1) ? xt.y : bmul(xt.x ^ TAGR, B2P64));
    const u32 sg2 = pk_bf(sgm, sgm);
    pin(zr, x1w, gw, hw, sg2); pin2(zr, dst, src);
    uint64_t v[12];
#pragma unroll
    for (int j = 0; j < 12; j++) v[j] = 1;
    float s0, s1;
    if (PD) wait_clk(ta, PD);
#define VL(j) (u32)v[j]
#define VS(j, s) ((uf((u32)(v[j] >> s)) + uf((u32)(v[j + 1] >> s))) + (uf((u32)(v[j + 2] >> s)) + uf((u32)(v[j + 3] >> s))))
    POLL({ _Pragma("unroll") for (int j = 0; j < 12; j++) rld64<3>(v[j], src + j * 9 * 2048, kt);
           s0 = VS(0, 0) + VS(4, 0) + VS(8, 0); s1 = VS(0, 32) + VS(4, 32) + VS(8, 32);
           asm volatile("" : "+f"(s0), "+f"(s1)); },
         lop3<0xa8>(lop3<0xfe>(ne3(VL(0), VL(1), kt), ne3(VL(2), VL(3), kt), ne3(VL(4), VL(5), kt)),
                    lop3<0xfe>(ne3(VL(6), VL(7), kt), ne3(VL(8), VL(9), kt), ne3(VL(10), VL(11), kt)), 3), 11);
    const u32 y = movm(pk_bf(s0, s1));
    asm volatile("st.global.u32 [%0],%1;" ::"l"(dst), "r"(badd(x1w, bmul(gw, badd(hw, bmul(y, sg2))))) : "memory");
    if (b == 0 && lane == 0) str32(gs + G_EP, par);
    TS(30); TSE();
  }
  if (w == 10) asm volatile("cp.async.bulk.wait_group.read 0;" ::: "memory");
}

DEV u32 y_off(u32 tid, u32 b) { return G_Y + (16 * (tid >> 5) + 8 * ((tid >> 1) & 1) + ((tid >> 2) & 4)) * BLK + b * 128 + ((tid >> 2) & 3) * 32 + (tid & 1) * 16; }
DEV void post_conv(const Prm& p, const CUtensorMap* tm_down, const u32 tid, const u32 b) {
  const u32 w = tid >> 5, lane = tid & 31;
  const u32 g = lane >> 2, q = lane & 3, e = g >> 2, h = (g >> 1) & 1, hi = g & 1;
  const u32 pm = lds32(SM_THR + 4), par = pm >> 30;
  char* const gs = p.gs;
  const u32 cho = 128 * w + 64 * e + 16 * q;
  u32 x1[4][4], h2[4][4], key[4], lt;
  char* const rowp = gs + (b * BLK + (4 * h + 8 * hi) * 1152 + cho);
  u32 ot = 0;
  FA fa;
  uint4 A[24];
#define AROW(t) const u32 arow = 144 * ((t >> 5) & 3) + ((t >> 1) & 8) + (t & 7), ab = (t & 8) ? SM_UP : SM_GATE;
#define AFRAG9() { _Pragma("unroll") for (int s = 0; s < 9; s++) A[s] = ldsm4t(ab + SLV + arow * 16 + s * 256); }
#define AFRAG18() { const u32 t3 = opq(tid); AROW(t3); if (t3 < 256) { const u32 aa = ab + arow * 64 + ((((t3 >> 6) & 2) ^ ((t3 & 7) >> 1)) << 4); \
      _Pragma("unroll") for (int s = 0; s < 9; s++) { A[s] = ldsm4t(aa + s * 1024); A[9 + s] = ldsm4t((aa ^ 16) + s * 1024); } } else AFRAG9(); }
  if (w < 9) {
    const u32 yc = 8 * (q >> 1) + 2 * (g >> 1), y1 = w < 8 ? BLK : 4 * BLK, y2 = 2 * y1;
    const char* ysrc = gs + (w < 8 ? y_off(tid, b) : G_Y + (q & 1) * 16 + (8 * yc + 2 * hi + ((b >> 4) & 1)) * BLK + 16384 + ((b >> 5) * 16 + (b & 15)) * 32);
    const char* const ys[4] = {ysrc, ysrc + y1, ysrc + y2, ysrc + (y1 + y2)};
    u32 tc = clk();
    uint4 yv[4];
#pragma unroll
    for (int v = 0; v < 4; v++) yv[v].x = INVAL;
    if (w < 4 && b < YL) {
#pragma unroll
      for (int v = 0; v < 4; v++) yv[v] = ldr128(ys[v]);
    }
    if (w == 8) { bsync(7, 160); tc = clk(); }
    const u32 ma = SM_MODS + cho, xa = SM_XST + (2 * h + 4 * hi) * ROW + cho;
    const uint4 sa = lds128(ma), ca = lds128(ma + 1152), ga = lds128(ma + 2304);
    const uint4 rb = lds128((g & 2) ? SM_ONE + 16 * hi : (ma ^ 64) + 8064 + 1152 * hi);
    const u32 saw[4] = {sa.x, sa.y, sa.z, sa.w}, caw[4] = {ca.x, ca.y, ca.z, ca.w}, gaw[4] = {ga.x, ga.y, ga.z, ga.w};
#pragma unroll
    for (int k = 0; k < 4; k++) {
      const uint2 st = lds64(SM_ST + 16 * (2 * h + 4 * hi + (k & 1) + 8 * (k >> 1)));
      const uint4 xv = lds128(xa + ((k & 1) + 8 * (k >> 1)) * ROW);
      x1[k][0] = xv.x; x1[k][1] = xv.y; x1[k][2] = xv.z; x1[k][3] = xv.w;
#pragma unroll
      for (int v = 0; v < 4; v++) x1[k][v] = badd(x1[k][v], bfma(bmul(badd(x1[k][v], st.x), st.y), caw[v], saw[v]));
    }
    const bool own = (q >> 1) == e;
    const u32 spw = SM_SP + (2 * w + e) * 320 + (g & 3) * 16 + (own ? ((q & 1) == h ? 4 : 12) : 8 - 8 * (q & 1));
    if (w >= 4) {
      if (b < (w < 8 ? YE : Y8)) {
        if (W8D && w == 8 && b >= 64) wait_clk(tc, W8D);
        TS(18);
#pragma unroll
        for (int v = 0; v < 4; v++) yv[v] = ldr128(ys[v]);
      }
      bsync(12, N12);
      tc = clk();
    }
    if (b >= YL) wait_clk(tc, YD);
    TS(13);
    POLLW(_Pragma("unroll") for (int v = 0; v < 4; v++) if ((yv[v].x ^ pm) & TAGM) yv[v] = ldr128(ys[v]),
          ((yv[0].x ^ pm) | (yv[1].x ^ pm) | (yv[2].x ^ pm) | (yv[3].x ^ pm)) & TAGM, 5);
    TS(19);
    if (w < 4) asm volatile("setmaxnreg.dec.sync.aligned.u32 168;");
#pragma unroll
    for (int k = 0; k < 4; k += 2) {
      float X[4] = {}, Y[4] = {}, R[4] = {};
#pragma unroll
      for (int v = 0; v < 4; v++) {
        const u32 y0 = k ? yv[v].z : yv[v].x & ~TAGM, y1 = k ? yv[v].w : yv[v].y;
        x1[k][v] = bfma(movm(y0), gaw[v], x1[k][v]);
        x1[k + 1][v] = bfma(movm(y1), gaw[v], x1[k + 1][v]);
        mma8_bf(X, x1[k][v], x1[k + 1][v], x1[k][v]); mma8_bf(Y, x1[k][v], x1[k + 1][v], x1[k + 1][v]);
        if (v & 1) mma_bf(R, x1[k][v - 1], x1[k + 1][v - 1], x1[k][v], x1[k + 1][v], v & 2 ? rb.z : rb.x, v & 2 ? rb.w : rb.y);
      }
      sts32(spw + k * 64, fu(own ? (hi ? X[1] : X[0]) : R[0] + R[1]));
      sts32(spw + k * 64 + 64, fu(own ? (hi ? Y[3] : Y[2]) : R[2] + R[3]));
    }
    barrive(1, N1);
    TS(36);
    const uint4 sb = lds128(ma + 3456), cb = lds128(ma + 4608), gb = lds128(ma + 5760);
    const u32 sbw[4] = {sb.x, sb.y, sb.z, sb.w}, cbw[4] = {cb.x, cb.y, cb.z, cb.w}, gbw[4] = {gb.x, gb.y, gb.z, gb.w};
    bsync(2, 320);
    TS(37);
    lt = lds32(SM_THR);
#pragma unroll
    for (int k = 0; k < 4; k++) {
      const uint4 st = lds128(SM_ST2 + 64 * k + 16 * (g & 3));
      key[k] = st.w;
      u32 o[4];
#pragma unroll
      for (int v = 0; v < 4; v++) {
        const u32 d = badd(x1[k][v], st.x), z = bfma(d, st.y, bmul(d, st.z));
        h2[k][v] = FH ? bfma(z, cbw[v], sbw[v]) : badd(bmul(z, cbw[v]), sbw[v]);
        o[v] = FO ? bfma(gbw[v], h2[k][v], x1[k][v]) : badd(x1[k][v], bmul(gbw[v], h2[k][v]));
      }
      h2[k][0] = bmul(h2[k][0], B2M64) | TAGR;
      if (key[k] >= lt) str128(rowp + k * 1152, h2[k][0], h2[k][1], h2[k][2], h2[k][3]);
      sts128(xa + ((k & 1) + 8 * (k >> 1)) * ROW, o[0], o[1], o[2], o[3]);
    }
    barrive(3, 320);
    TS(21);
    asm volatile("setmaxnreg.inc.sync.aligned.u32 168;");
    mb_wait(SM_MB + 8); mb_wait(SM_MB + 16);
    AFRAG18();
    TS(22);
    const u32 rr = tid * 57 >> 12, rc = tid * 16 - rr * 1152, sl = SM_SLOT + 8 * rr;
    const char* const rb_ = gs + rc;
    const u32 km = max(max(key[0], key[1]), max(key[2], key[3])), xd = SM_XS + rr * (2 * ROW) + rc;
    if (RW & 2) { pin(tid >> 16, sl, km, xd); pin2(tid >> 16, rb_, rowp); }
    fa = ffn_addr(p, tid | p.zero, b);
    bsync(6, 352);
    TS(24);
    const uint2 sk = lds64(sl);
    const char *r0 = rowa(rb_, sk.x), *r1 = rowa(rb_, sk.y);
    uint4 rv[2] = {ldr128(r0), ldr128(r1)};
    barrive(15, 320);
    const u32 g8 = lds32(SM_SLOT + 28);
    if (__any_sync(~0u, km >= g8 && lt > g8)) {
#pragma unroll
      for (int k = 0; k < 4; k++) if (key[k] >= g8 && key[k] < lt) str128(rowp + k * 1152, h2[k][0], h2[k][1], h2[k][2], h2[k][3]);
    }
    bsync(5, 352);
    const uint2 sf = lds64(sl);
    const u32 f8 = lds32(SM_SLOT + 28);
    if (__any_sync(~0u, km >= f8)) {
#pragma unroll
      for (int k = 0; k < 4; k++) if (key[k] >= f8) str128(rowp + (G_Y + k * 1152), bmul(x1[k][0], B2M64) | TAGR, x1[k][1], x1[k][2], x1[k][3]);
    }
    if (__any_sync(~0u, sf.x != sk.x || sf.y != sk.y)) {
      r0 = rowa(rb_, sf.x); r1 = rowa(rb_, sf.y);
      rv[0].x = rv[1].x = INVAL;
    }
    POLLW({ rld128<TAGM>(rv[0], r0, TAGR); rld128<TAGM>(rv[1], r1, TAGR); }, ne3(rv[0].x, rv[1].x, TAGR) & TAGM, 8);
    TS(38);
#pragma unroll
    for (int j = 0; j < 2; j++) sts128(xd + j * ROW, bmul(rv[j].x ^ TAGR, B2P64), rv[j].y, rv[j].z, rv[j].w);
  } else {
    u32 ok, lr;
    if (w == 10) {
      uint2 rc = lds64(SM_RC + 8 * min(lane, 17u));
      float r1 = lane < 18 ? uf(rc.x) : 0.f, r2 = lane < 18 ? uf(rc.y) : 0.f;
#pragma unroll 1
      for (int o = 16; o; o >>= 1) { r1 += __shfl_xor_sync(~0u, r1, o); r2 += __shfl_xor_sync(~0u, r2, o); }
      const u32 tl = 4 * ((lane >> 1) & 1) + ((lane >> 2) & 3) + 8 * (lane & 1), kl = (2047 - 16 * b - tl) << 2 | par * 3;
      char* const kp = gs + (G_KEY + b * KST);
      const u32 spr = SM_SP + (lane >> 4) * 9 * 320 + (lane & 15) * 16;
      TS(31);
      bsync(1, N1);
      float S1 = 0.f, S2 = 0.f, S3 = 0.f;
#pragma unroll
      for (int i = 0; i < 9; i++) { uint4 t = lds128(spr + i * 320); S1 += uf(t.x); S2 += uf(t.y); S3 += uf(t.z); }
      S1 += __shfl_xor_sync(~0u, S1, 16); S2 += __shfl_xor_sync(~0u, S2, 16); S3 += __shfl_xor_sync(~0u, S3, 16);
      const float mu = S1 * (1.f / 576.f), var = fmaxf(fmaf(-mu, mu, S2 * (1.f / 576.f)), 0.f);
      const float m = rbf(mu), rs = rcpf(rbf(sqrta(rbf(rbf(var) + 1e-5f))));
      const u32 rb = pk_bf(0.f, fmaf(fmaf(-m, r1, S3), rs, r2) + 0.f);
      ok = ((rb ^ (((int)rb >> 31) | 0x80000000)) & 0xffff0000u) | kl;
      const float rh = rbf(rs);
      sts32(SM_KEY + 4 * (lane & 15), ok);
      sts128(SM_ST2 + 16 * (lane & 15), pk_bf(-m, -m), pk_bf(rh, rh), pk_bf(rs - rh, rs - rh), ok);
      __syncwarp();
      const uint4 o0 = lds128(SM_KEY + 2 * (lane & 16)), o1 = lds128(SM_KEY + 2 * (lane & 16) + 16);
      lr = (o0.x > ok) + (o0.y > ok) + (o0.z > ok) + (o0.w > ok) + (o1.x > ok) + (o1.y > ok) + (o1.z > ok) + (o1.w > ok);
      lr += __shfl_xor_sync(~0u, lr, 16);
      if (lane < 16 && lr < 8) str32(kp + 4 * lr, ok);
      if (lr == (b < NB8 ? 7 : NEARLY - 1)) sts32(SM_THR, ok);
      barrive(2, 320);
      if (!KA) barrive(4, 64);
      TS(20);
    } else if (w == 9) {
      if (DB1) bsync(1, N1); else { bsync(12, N12); wait_clk(clk(), DD); }
      if (PFW == 4 && tid == 288) l2_pre<WSH>(p.wd + b * WSH);
      PROXY_FENCE();
      DOWN(1);
    } else {
      const char* ks = gs + (G_KEY + (lane >> 1) * KST + (lane & 1) * 16);
      const u32 kt = par * 3;
      uint4 L[8];
      u32 H[8];
#define KBAD(j) ((L[j].x ^ kt) & 3)
#define KLD(j) L[j] = ldr128(ks + j * 16 * KST)
#pragma unroll
      for (int j = 0; j < 8; j++) L[j].x = INVAL;
      if (KA) bsync(1, N1); else bsync(4, 64);
      wait_clk(clk(), KA + (b < KE ? KD : b < YL ? KDB : KD1));
      TS(34);
      POLL({ _Pragma("unroll") for (int j = 0; j < 8; j++) if (KBAD(j)) KLD(j);
             merge4(H, L[0], L[1]); top8(H, L[2], L[3]);
             asm volatile("" : "+r"(H[0]), "+r"(H[1]), "+r"(H[2]), "+r"(H[3]), "+r"(H[4]), "+r"(H[5]), "+r"(H[6]), "+r"(H[7])); TS(32); },
           KBAD(0) | KBAD(1) | KBAD(2) | KBAD(3) | KBAD(4) | KBAD(5), 6);
      top8(H, L[4], L[5]);
      TS(35);
#pragma unroll 1
      for (u32 pass = p.zero;; pass++) {
        u32 G[8], m[8];
#pragma unroll
        for (int i = 0; i < 8; i++) G[i] = H[i];
#pragma unroll
        for (int r = 0; r < 8; r++) {
          const u32 h0 = G[0];
          m[r] = __reduce_max_sync(~0u, h0);
          if (r == 0) { if (KBAD(6)) KLD(6); if (KBAD(7)) KLD(7); }
          if (r < 7) asm("{.reg .u32 t; sub.u32 t,%1,%2; min.u32 t,t,1; mad.lo.u32 %0,t,%3,%4;}" : "=r"(G[0]) : "r"(m[r]), "r"(h0), "r"(h0 - G[1]), "r"(G[1]));
#pragma unroll
          for (int i = 1; i < 7 - r; i++) G[i] = h0 == m[r] ? G[i + 1] : G[i];
          if ((r & 3) == 3) sts128(SM_SLOT + 4 * r - 12, m[r - 3], m[r - 2], m[r - 1], m[r]);
        }
        asm volatile("{.reg .pred p; setp.eq.u32 p,%0,0; @p bar.arrive 6,352;}" ::"r"(pass) : "memory");
        if (pass) break;
        TS(23);
        POLLW({ if (KBAD(6)) KLD(6); if (KBAD(7)) KLD(7); }, KBAD(6) | KBAD(7), 7);
        if (!__any_sync(~0u, max(L[6].x, L[7].x) > m[7])) break;
        top8(H, L[6], L[7]);
      }
      barrive(5, 352);
      TS(33);
    }
    asm volatile("setmaxnreg.inc.sync.aligned.u32 168;");
    mb_wait(SM_MB + 8); mb_wait(SM_MB + 16);
    AROW(tid);
    AFRAG9();
    fa = ffn_addr(p, tid | p.zero, b);
    TS(22);
    if (w == 10) {
      bsync(3, 320);
      PROXY_FENCE();
      ot = lane < 16 && lr >= 8;
      OUTR(2);
      bsync(6, 352);
      bsync(5, 352);
      if (lane < 16 && lr < 8 && ok < lds32(SM_SLOT + 28)) ot = 2;
      OUTR(4);
    } else if (w == 9) {
      bsync(15, 320);
      DOWN(4);
      TS(13);
    }
  }
  ffn_tail(p, tm_down, A, fa, b, par, ot);
}

__global__ void __launch_bounds__(384, 1)
fused_kernel(const Prm p, const __grid_constant__ CUtensorMap tm_mod, const __grid_constant__ CUtensorMap tm_gate, const __grid_constant__ CUtensorMap tm_gs,
             const __grid_constant__ CUtensorMap tm_up, const __grid_constant__ CUtensorMap tm_us, const __grid_constant__ CUtensorMap tm_down) {
  extern __shared__ __align__(1024) unsigned char smem[];
  u32 la, ai, ldt; uint2 cr, ci;
  {
    const u32 t = threadIdx.x, d = t < 256 ? chan(blockIdx.x, t >> 5) : 512 + (blockIdx.x >> 1), o = d * 256 + 8 * (t & 31), o4 = o + ((t < 256 ? t >> 5 : t >> 3) & 4);
    asm volatile("{.reg .pred p; .reg .u16 h; setp.ne.u32 p,%7,0; @p ld.global.nc.u32 %0,[%8]; @p ld.global.nc.u32 %1,[%9]; @p ld.global.nc.v2.u32 {%2,%3},[%10];"
                 "@p ld.global.nc.v2.u32 {%4,%5},[%11]; @p ld.global.nc.u16 h,[%12]; cvt.u32.u16 %6,h;}"
                 : "=r"(la), "=r"(ai), "=r"(cr.x), "=r"(cr.y), "=r"(ci.x), "=r"(ci.y), "=r"(ldt)
                 : "r"(0x6ffu >> (t >> 5) & 1), "l"(p.la + o4), "l"(p.ai + o4), "l"(p.cr + o), "l"(p.ci + o), "l"(p.ldt + 2 * d));
  }
  const u32 t0 = clk();
  const u32 tid = __shfl_sync(~0u, threadIdx.x, threadIdx.x & 31), b = blockIdx.x + p.zero;
  const u32 w = tid >> 5, lane = tid & 31;
  const u32 g = lane >> 2, q = lane & 3, hi = g & 1;
  const u32 rho = b & 1, Ps = 512 + (b >> 1);
  char* const gs = p.gs;
  TS0();
  const bool kw = w != 8 && w != 11;
  const u32 ksig = w < 8 ? (w & 3) : 4, khf = w < 8 ? (w >> 2) : (w & 1);
  if (!kw) {
    if (tid == 352) {
#pragma unroll
      for (int i = 0; i < 5; i++) mb_init(SM_MB + 8 * i, i < 4 ? 1 : 64);
      asm volatile("fence.mbarrier_init.release.cluster;" ::: "memory");
      tm_pre(&tm_mod);
    }
    const char* cp = p.c + (576 * (w & 1) + 24 * min(lane, 23u));
    const uint2 c0 = ldg64(cp);
    la = c0.x; ai = c0.y; cr = ldg64(cp + 8); ci = ldg64(cp + 16);
  }
  const u32 zr = tid >> 16;
  const u32 epv = ldr32(gs + (G_EP + zr));
  const u32 tp = SM_TAP + ksig * TAPS;
  if (kw && !khf) {
#pragma unroll 1
    for (u32 i = lane * 16; i < TAPS; i += 512) sts128(tp + i, 0, 0, 0, 0);
  }
  if (tid < 128) sts128(SM_INV + 16 * tid, INVAL, 0, 1, 0);
  if (tid >= 252) str128(gs + (tid >= 380 ? G_MOD + b * 128 + q * 16 : b * BLK + 16384 - 252 * 16 + tid * 16), INVAL, 0, 1, 0);
  if (tid == 352 && b < 36) { while (clk() - t0 < DMOD); mb_expect(SM_MB, 36864); tma3d(SM_UP, &tm_mod, SM_MB, 32 * b, 0); }
  if (w < 9) {
    while ((int)(clk() - t0) < DX);
    const char* xp = p.x + (b * BLK + (lane >> 3) * 1152 + 128 * w + 16 * (lane & 7));
    const u32 xd = SM_XST + (((lane >> 3) & 1) + 8 * (lane >> 4)) * ROW + 128 * w + 16 * (lane & 7);
#pragma unroll
    for (int i = 0; i < 4; i++) cpa16(xd + 2 * ROW * i, xp + 4608 * i);
  }
  const u32 ktab = w < 8 ? SM_MODS + w * KTAB : SM_ZS + (w - 9) * KTAB;
  float k2048 = 0.f;
  if (kw) {
    u32 mx = __vmaxu2(__vmaxu2(cr.x & 0x7fff7fff, cr.y & 0x7fff7fff), __vmaxu2(ci.x & 0x7fff7fff, ci.y & 0x7fff7fff));
    const u32 E = max(__reduce_max_sync(~0u, max(mx & 0xffff, mx >> 16)) >> 7, 8u);
    TS(1);
    const float dt = rbf(ex2(blo(ldt) * LOG2E)), csc = uf((257 - E) << 23 | (fu(dt) & 0x7fffff));
    sts32(SM_SC + 16 * ksig + 12, fu(uf(fu(dt) & 0x7f800000) * uf((E - 2) << 23)));
    const u32 crw = khf ? cr.y : cr.x, ciw = khf ? ci.y : ci.x;
    float2 C[2], w4[2], w8[2], w16[2], w32[2], w64[2], w128[2], w256[2], w512[2], a1[2], a2[2], a3[2], t0[2], t1[2], s3[2];
#pragma unroll
    for (int m = 0; m < 2; m++) {
      const float lr2 = rbf(ex2((m ? bhi(la) : blo(la)) * LOG2E)) * dt * -LOG2E, th = (m ? bhi(ai) : blo(ai)) * dt;
      C[m] = make_float2((m ? bhi(crw) : blo(crw)) * csc, (m ? bhi(ciw) : blo(ciw)) * csc);
      const float2 w1 = cexp(lr2, th), w2 = csq(w1);
      w64[m] = cexp(64.f * lr2, 64.f * th);
      w4[m] = csq(w2); w8[m] = csq(w4[m]); w16[m] = csq(w8[m]); w32[m] = csq(w16[m]);
      w128[m] = csq(w64[m]); w256[m] = csq(w128[m]); w512[m] = csq(w256[m]);
      const float2 w1024 = csq(w512[m]);
      a1[m] = cmul(C[m], w1); a2[m] = cmul(C[m], w2); a3[m] = cmul(a1[m], w2);
      t0[m] = cmul(C[m], w1024); t1[m] = cmul(t0[m], w128[m]); s3[m] = cmul(w8[m], w16[m]);
      k2048 += fmaf(t0[m].x, w1024.x, -t0[m].y * w1024.y);
    }
    C2 B0[8], B1[8], B2[8], S[8];
    B0[0] = pk2(C); B0[1] = pk2(a1); B0[2] = pk2(a2); B0[3] = pk2(a3);
    const C2 h4 = pk2(w4), h256 = pk2(w256), h512 = pk2(w512);
#pragma unroll
    for (int i = 0; i < 4; i++) B0[4 + i] = cm2(B0[i], h4);
#pragma unroll
    for (int i = 0; i < 4; i++) B1[i] = cm2(B0[2 * i], h256);
    B1[4] = cm2(B0[0], h512); B1[5] = cm2(B0[4], h512);
    B1[6] = cm2(B1[4], h256); B1[7] = cm2(B1[5], h256);
    const u32 ta = ktab + lane * 128, f = ((lane & 3) << 5) | ((lane & 4) << 2);
#pragma unroll
    for (int i = 0; i < 8; i++) sts128(ta + ((i << 4) ^ f), B0[i].re, B0[i].im, B1[i].re, B1[i].im);
    B2[0] = pk2(t0); B2[1] = pk2(t1);
    B2[2] = cm2(B2[0], h256); B2[3] = cm2(B2[1], h256);
#pragma unroll
    for (int i = 0; i < 4; i++) B2[4 + i] = cm2(B2[i], h512);
    S[0] = {0x3C003C00u, 0u}; S[1] = pk2c(w8); S[2] = pk2c(w16); S[3] = pk2c(s3); S[4] = pk2c(w32);
#pragma unroll
    for (int i = 1; i < 4; i++) S[4 + i] = cm2(S[i], S[4]);
#pragma unroll
    for (int i = 0; i < 8; i++) sts128(ta + 4096 + ((i << 4) ^ f), B2[i].re, B2[i].im, S[i].re, S[i].im);
    const C2 m64 = pk2c(w64), m128 = pk2c(w128);
    sts128(ktab + 8192 + lane * 16, m64.re, m64.im, m128.re, m128.im);
    __syncwarp();
  } else {
    u32 sa = SM_SIL + 576 * (w & 1) + 24 * min(lane, 23u);
#pragma unroll 1
    for (int j = 0; j < 6; j++) {
      sts32(sa, pk_bf(silu_f(blo(la)), silu_f(bhi(la))));
      la = ai; ai = cr.x; cr.x = cr.y; cr.y = ci.x; ci.x = ci.y; sa += 4;
    }
    bsync(7, 64);
  }
  TS(2);
  const u32 pm = (__reduce_or_sync(~0u, epv) & 1) ? 0 : TAGM;
  sts32(SM_THR + 4, pm);
  if (w < 9) {
    asm volatile("cp.async.wait_all;" ::: "memory");
    __syncwarp();
    TS(4);
    if (tid == 256 && b >= 36 && b < 108) { mb_expect(SM_MB, 36864); tma3d(SM_UP, &tm_mod, SM_MB, 32 * b, 0); }
    const u32 xa = SM_XST + (lane & 15) * ROW + 128 * w + 16 * (lane >> 4);
    float s[4] = {}, X[2][4] = {}, Y[2][4] = {};
#pragma unroll
    for (int j = 0; j < 4; j++) {
      const uint4 a = ldsm4(xa + 32 * j);
      mma8_bf(X[0], a.x, a.y, a.x); mma8_bf(Y[0], a.x, a.y, a.y);
      mma8_bf(X[1], a.z, a.w, a.z); mma8_bf(Y[1], a.z, a.w, a.w);
      mma_bf(s, a.x, a.y, a.z, a.w, BONE, BONE);
    }
    uint4 t[4];
#pragma unroll
    for (int j = 0; j < 4; j++) t[j] = ldsm4t(xa + 32 * j);
    const float u0 = hi ? X[0][1] + X[1][1] : X[0][0] + X[1][0], u1 = hi ? Y[0][3] + Y[1][3] : Y[0][2] + Y[1][2];
    if (q == g >> 1) sts128(SM_SP + w * 128 + g * 16, fu(s[0]), fu(u0), fu(s[2]), fu(u1));
    bsync(1, 288);
    TS(7);
    const u32 spr = SM_SP + (lane & 7) * 16 + (lane & 8);
    const uint2 t8 = lds64(spr + 1024);
    const float f8 = lane < 16 ? 1.f : 0.f;
    float S1 = uf(t8.x) * f8, S2 = uf(t8.y) * f8;
#pragma unroll
    for (int i = 0; i < 4; i++) { const uint2 u = lds64(spr + (lane & 16) * 32 + i * 128); S1 += uf(u.x); S2 += uf(u.y); }
    S1 += __shfl_xor_sync(~0u, S1, 16); S2 += __shfl_xor_sync(~0u, S2, 16);
    const float mu = S1 * (1.f / 576.f), var = fmaxf(fmaf(-mu, mu, S2 * (1.f / 576.f)), 0.f);
    const float m = rbf(mu), rs = rcpf(rbf(sqrta(rbf(rbf(var) + 1e-5f))));
    const float ra = rs * 0.0625f;
    sts64(SM_AF + w * 128 + (lane & 15) * 8, fu(ra), fu(-m * ra));
    __syncwarp();
    TS(55);
    const uint4 f0 = lds128(SM_AF + w * 128 + q * 16), f1 = lds128(SM_AF + w * 128 + 64 + q * 16);
    const u32 zdst = SM_GATE + w * 2048 + (g >> 1) * 128 + (lane & 15) * 8;
    const u32 pz = (q & 1) ? 0 : pm;
#pragma unroll
    for (int j = 0; j < 8; j++) {
      const u32 x0 = j & 1 ? t[j >> 1].z : t[j >> 1].x, x1 = j & 1 ? t[j >> 1].w : t[j >> 1].y;
      sts64((j & 1 ? zdst ^ 64 : zdst) + 512 * (j >> 1), pk_hf(fmaf(blo(x0), uf(f0.x), uf(f0.y)), fmaf(bhi(x0), uf(f0.z), uf(f0.w))) | pz,
            pk_hf(fmaf(blo(x1), uf(f1.x), uf(f1.y)), fmaf(bhi(x1), uf(f1.z), uf(f1.w))));
    }
    TS(53);
    if (w < 8) barrive(15, 288);
    else {
      bsync(15, 288);
      TS(54);
      if (lane == 0) {
        PROXY_FENCE();
        bulk_out<BLK>(gs + b * BLK, SM_GATE);
        asm volatile("cp.async.bulk.commit_group;" ::: "memory");
        if (PFG & 1) l2_pre<WSH / 2>(p.wg + b * WSH);
      }
      const float rh = rbf(rs);
      sts128(SM_ST + 16 * (lane & 15), pk_bf(-m, -m), pk_bf(rh, rh), pk_bf(rs - rh, rs - rh), 0);
    }
    TS(5);
  }
  if (kw) {
    float D[5][4] = {};
    u32 ta = ktab + q * 128 + ((g ^ (q << 1)) << 4), tm = ktab + 8192 + q * 16;
#pragma unroll 2
    for (int s = 0; s < 8; s++) {
      const uint4 ca = lds128(ta), cb = lds128(ta + 4096), ma = lds128(tm);
      ta = (ta + 512) ^ 16; tm += 64;
      k2048 += __shfl_xor_sync(~0u, k2048, 16 >> s);
      const C2 s0 = {cb.z, cb.w}, s1 = cm2(s0, {ma.x, ma.y}), s2 = cm2(s0, {ma.z, ma.w}), s3 = cm2(s1, {ma.z, ma.w});
      mma_hf(D[0], s0.re, s1.re, s0.im, s1.im, ca.x, ca.y);
      mma_hf(D[2], s0.re, s1.re, s0.im, s1.im, ca.z, ca.w);
      mma_hf(D[4], s0.re, s1.re, s0.im, s1.im, cb.x, cb.y);
      mma_hf(D[1], s2.re, s3.re, s2.im, s3.im, ca.x, ca.y);
      mma_hf(D[3], s2.re, s3.re, s2.im, s3.im, ca.z, ca.w);
    }
    TS(3);
    const u32 xa = (w < 8 ? SM_MODS + (4 + ksig) * KTAB : SM_ZS) + lane * 16;
    if (khf) {
      __syncwarp();
#pragma unroll
      for (int j = 0; j < 5; j++) sts128(xa + 512 * j, fu(D[j][0]), fu(D[j][1]), fu(D[j][2]), fu(D[j][3]));
      if (lane == 0) sts32(xa + 2560, fu(k2048));
      asm volatile("bar.arrive %0,64;" ::"r"(2 + ksig) : "memory");
    } else {
      const u32 t1 = tp + (q < 2 ? (128 + 4 * g + 2 * q) * 4 : T3 * 4 + ((32 * q - 64 + g) ^ 1) * 2);
      const u32 x = 16 * q + (g >> 1) + hi + 1, tb = tp + (hi ? T7E : T9E) * 4 - 4;
      const u32 te = tb + (x + 2 * (x & 1)) * 2, to = tb + TEO * 4 + (x ^ 1) * 2;
      asm volatile("bar.sync %0,64;" ::"r"(2 + ksig) : "memory");
#pragma unroll
      for (int j = 0; j < 5; j++) { const uint4 t = lds128(xa + 512 * j); D[j][0] += uf(t.x); D[j][1] += uf(t.y); D[j][2] += uf(t.z); D[j][3] += uf(t.w); }
      k2048 = (k2048 + uf(lds32(xa + 2560))) * 0.125f;
#pragma unroll
      for (int r = 0; r < 4; r++) {
        const u32 v = pk_hf(D[2 + (r >> 1)][2 * (r & 1)], D[2 + (r >> 1)][2 * (r & 1) + 1]);
        if (q < 2) {
          const u32 vv = __byte_perm(v, v, 0x1010);
          sts32(t1 + (TO + 32 * r) * 4, vv); sts16(t1 + (TO + 32 * r + 1) * 4 + 2, v >> 16); sts16(t1 + (TO + 32 * r - 1) * 4, v);
          sts64(t1 + (TE + 32 * r) * 4, vv, __byte_perm(v, v, 0x1032));
        } else {
          sts16(t1 + 16 * r, v >> 16);
          if (r == 0 && lane == 2) {
            const u32 vv = __byte_perm(v, v, 0x1010);
            sts32(tp + (TO + 256) * 4, vv); sts16(tp + (TO + 257) * 4 + 2, v); sts16(tp + (TO + 255) * 4, v); sts64(tp + (TE + 256) * 4, vv, vv);
          } else sts16(t1 + 16 * r - ((T3 - T5) * 4 + 6) + 8 * hi, v);
        }
      }
#pragma unroll
      for (int r = 0; r < 2; r++) {
        const u32 v = pk_hf(D[4][2 * r], D[4][2 * r + 1]);
        if (r == 0 && lane == 0) { sts16(tp + T5 * 4 + 62 * 2, v); sts32(SM_KV + 4 * ksig, v & 0xffff); sts16(tp + (T9E + TEO) * 4 + 62 * 2, pk_hf(k2048, 0.f)); }
        else { sts16(te + 8 * r, v); sts16(to + 8 * r, v); }
        sts16(te + 8 * r + 16, v >> 16); sts16(to + 8 * r + 16, v >> 16);
      }
      __syncwarp();
#pragma unroll
      for (int r = 0; r < 4; r++) {
        const u32 v = pk_hf(D[r >> 1][2 * (r & 1) + 1], D[r >> 1][2 * (r & 1)]), t2 = tp + lane * 4 + 128 * r;
        sts32(t2 + TO * 4, v); sts16(t2 + TE * 4, v >> 16); sts16(t2 + (TE + 1) * 4 + 2, v);
      }
      __syncwarp();
    }
  } else if (w == 11 && b < 108) {
    float c[4][4] = {};
    u32 aa = SM_UP + ((lane & 7) + 8 * (lane >> 4)) * 64 + ((((lane >> 3) & 1) ^ ((lane & 7) >> 1)) << 4);
    u32 ba = SM_SIL + (lane >> 3) * 16;
    uint4 a[2][10];
#define GLD(n) { _Pragma("unroll") for (int i = 0; i < 2; i++) { a[n][5 * i] = ldsm4(ba + i * 64); \
      _Pragma("unroll") for (int k = 0; k < 4; k++) a[n][5 * i + 1 + k] = ldsm4t((k & 2 ? aa ^ 32 : aa) + i * 2048 + (k & 1) * 1024); } aa += 4096; ba += 128; }
#define GMM(n) { _Pragma("unroll") for (int i = 0; i < 2; i++) _Pragma("unroll") for (int k = 0; k < 4; k++) { const uint4 f = a[n][5 * i + 1 + k], bb = a[n][5 * i]; \
      mma_bf(c[k], f.x, f.y, f.z, f.w, k & 1 ? bb.z : bb.x, k & 1 ? bb.w : bb.y); } }
    mb_wait(SM_MB);
    TS(56);
    GLD(0);
#pragma unroll 1
    for (int s = 0; s < 4; s++) { GLD(1); GMM(0); GLD(0); GMM(1); }
    GMM(0);
    const float v0 = (q & 1) ? c[0][2] + c[1][2] : c[0][0] + c[1][0], v1 = (q & 1) ? c[2][2] + c[3][2] : c[2][0] + c[3][0];
    str16(gs + (G_MOD + b * 128 + 2 * g + 16 * q), pk_bf(rbf((q & 2) ? v1 : v0) * F2M64, 0.f) | (g < 2 ? pm : 0));
    TS(57);
  }
  TS(6);
  u32 tid2 = tid;
  if (w < 4) {
    asm volatile("setmaxnreg.inc.sync.aligned.u32 232;");
    const u32 tid = tid2 + p.zero, w = tid >> 5, lane = tid & 31, g = lane >> 2, q = lane & 3, hi = g & 1, zr = tid >> 16, tp = SM_TAP + w * TAPS;
    const u32 pml = opq((g & 3) ? 0 : pm);
    const u32 tr = tp + ((hi ? TO : TE) + (g >> 1) - q) * 4;
    u32 T[33][4], B5[5][2], B3[5][2];
#pragma unroll
    for (int d = 0; d < 33; d++) {
      T[d][0] = lds32(tr + 32 * d); T[d][1] = lds32(tr + 32 * d + 16);
      T[d][2] = cpy(d ? T[d - 1][1] : zr, zr, 0); T[d][3] = cpy(T[d][0], zr, 1);
    }
    const u32 t33 = cpy(T[32][1], zr, 0), z33 = cpy(zr, zr, 1);
    if (TPIN) {
#pragma unroll
      for (int d = 0; d < 33; d++) asm volatile("{.reg .pred p; setp.ne.u32 p,%2,0; @p st.shared.v2.u32 [%2],{%0,%1};}" ::"r"(T[d][2]), "r"(T[d][3]), "r"(zr) : "memory");
    }
    const u32 bt = tp + (T5 + g - q) * 4;
#pragma unroll
    for (int d = 0; d < 5; d++) {
      B5[d][0] = lds32(bt + 32 * d); B5[d][1] = lds32(bt + 32 * d - 16);
      B3[d][0] = lds32(bt + 32 * d + (T3 - T5) * 4); B3[d][1] = lds32(bt + 32 * d - 16 + (T3 - T5) * 4);
    }
    u32 za = opq(SM_ZS + 16 + w * ZSS + ((lane >> 3) & 1) * ZPS + ((lane & 7) + (lane >> 4)) * 16);
    u32 wa = opq(SM_W + W5O + w * WSL + row16(lane));
    u32 sa = opq(SM_W + W9O - 2048 + w * WSL + lane * 16);
    u32 yo = opq(G_Y + b * BLK + 256 * q + w * 32 + 4 * g);
    const u32 fa = opq(SM_SC + 16 * w + 8), bw = opq((BW >> 4 * w) & 15), bs = opq((BS >> 4 * w) & 15);
    if (TPIN) asm volatile("{.reg .pred p; setp.ne.u32 p,%8,0; @p st.shared.v4.u32 [%8],{%0,%1,%2,%3}; @p st.shared.v4.u32 [%8],{%4,%5,%6,%7};}"
                           ::"r"(za), "r"(wa), "r"(sa), "r"(yo), "r"(fa), "r"(bw), "r"(bs), "r"(pml), "r"(zr) : "memory");
    TS(8);
    bsync(9, 384);
    TS(11);
    float A[4][4] = {};
    uint4 Z[4];
    Z[0] = ldsm4(za); Z[1] = ldsm4(za + 32);
    const uint2 fc = lds64(fa);
    const u32 F = __byte_perm(fu(uf(fc.x) * uf(fc.y)), 0, 0x3232);
#define STEP(s, b0, b1) { _Pragma("unroll") for (int i = 0; i < 4; i++) mma_hf_t(A[i], T[8 * i + 7 - (s)], b0, b1); }
#define PAIR(n) { Z[(n + 2) & 3] = ldsm4(za + 32 * (n + 2)); STEP(2 * n, Z[n].x, Z[n].y); STEP(2 * n + 1, Z[n].z, Z[n].w); }
#define LAST(N) mma8_hf(N, t33, z33, Z[3].y); float O[4]; mma_hf_o(O, A[0], T[0], Z[3].z, Z[3].w); \
    _Pragma("unroll") for (int i = 0; i < 3; i++) mma_hf_o(A[i], A[i + 1], T[8 * i + 8], Z[3].z, Z[3].w); \
    mma_hf_o(A[3], N, T[32], Z[3].z, Z[3].w);
#pragma unroll 1
    for (int j = 0; j < 4; j++) {
      PAIR(0); PAIR(1); PAIR(2);
      Z[1] = ldsm4(za + 160); STEP(6, Z[3].x, Z[3].y);
      float N[4] = {};
      LAST(N);
      if (INCV) inc<128>(za);
      y_store<128>(O[0], O[1], O[2], O[3], F, pml, gs + yo);
      if (!INCV) za += 128;
      yo += 1024;
      TSJ(j);
    }
    bsyncr(bw);
    uint4 a5;
    if (A5P) a5 = ldsm4t(wa);
#pragma unroll 1
    for (int j = 4; j < 13; j++) {
      if (j == 8) bsyncr(bs);
      if (!A5P) a5 = ldsm4t(wa);
      const uint4 a3 = ldsm4t(wa + (W3O - W5O));
      uint4 s3 = {0, 0, 0, 0};
      if (j >= 8) s3 = lds128(sa);
      PAIR(0);
      float N[4] = {};
#pragma unroll
      for (int i = 0; i < 4; i++) mma_hf(A[i], a5.x, a5.y, a5.z, a5.w, B5[i][0], B5[i][1]);
      mma_hf(N, a5.x, a5.y, a5.z, a5.w, B5[4][0], B5[4][1]);
      if (INCV) asm volatile("{add.u32 %0,%0,256; xor.b32 %0,%0,32;}" : "+r"(wa)); else wa = (wa + 256) ^ 32;
      if (A5P) a5 = ldsm4t(wa);
      PAIR(1);
#pragma unroll
      for (int i = 0; i < 4; i++) mma_hf(A[i], a3.x, a3.y, a3.z, a3.w, B3[i][0], B3[i][1]);
      mma_hf(N, a3.x, a3.y, a3.z, a3.w, B3[4][0], B3[4][1]);
      PAIR(2);
      Z[1] = ldsm4(za + 160); STEP(6, Z[3].x, Z[3].y);
      LAST(N);
      if (INCV) { inc<128>(za); inc<512>(sa); }
      y_store<128>(O[0] + uf(s3.x), O[1] + uf(s3.y), O[2] + uf(s3.z), O[3] + uf(s3.w), F, pml, gs + yo);
      if (!INCV) { za += 128; sa += 512; }
      yo += 1024;
      TSJ(j);
    }
    {
      asm volatile("mov.u32 %0,%%tid.x;" : "=r"(tid2));
      const uint4 s3 = lds128(sa), s4 = lds128(sa + 512), s5 = lds128(sa + 1024);
      float X[3][4] = {{uf(s4.x), uf(s4.y), uf(s4.z), uf(s4.w)}, {}, {uf(s5.x), uf(s5.y), uf(s5.z), uf(s5.w)}};
#pragma unroll
      for (int ty = 0; ty < 2; ty++) {
        const uint4 a = A5P && !ty ? a5 : ldsm4t(wa + ty * (W3O - W5O)), c = ldsm4t((wa ^ 32) + 256 + ty * (W3O - W5O)), d = ldsm4t(wa + 512 + ty * (W3O - W5O));
#pragma unroll
        for (int i = 0; i < 3; i++) mma_hf(A[i], a.x, a.y, a.z, a.w, ty ? B3[i][0] : B5[i][0], ty ? B3[i][1] : B5[i][1]);
#pragma unroll
        for (int i = 0; i < 2; i++) mma_hf(X[i], c.x, c.y, c.z, c.w, ty ? B3[i][0] : B5[i][0], ty ? B3[i][1] : B5[i][1]);
        mma_hf(X[2], d.x, d.y, d.z, d.w, ty ? B3[0][0] : B5[0][0], ty ? B3[0][1] : B5[0][1]);
      }
#pragma unroll
      for (int n = 0; n < 4; n++) {
        const uint4 f0 = n < 2 ? Z[n] : ldsm4(za + 32 * n), f1 = ldsm4(za + 32 * n + 128), f2 = ldsm4(za + 32 * n + 256);
#pragma unroll
        for (int s = 2 * n; s < 2 * n + 2; s++) {
#pragma unroll
          for (int i = 0; i < 3; i++) mma_hf_t(A[i], T[8 * i + 7 - s], s & 1 ? f0.z : f0.x, s & 1 ? f0.w : f0.y);
          mma_hf_t(X[0], T[7 - s], s & 1 ? f1.z : f1.x, s & 1 ? f1.w : f1.y); mma_hf_t(X[1], T[15 - s], s & 1 ? f1.z : f1.x, s & 1 ? f1.w : f1.y);
          mma_hf_t(X[2], T[7 - s], s & 1 ? f2.z : f2.x, s & 1 ? f2.w : f2.y);
        }
      }
      y_store<128>(A[0][0] + uf(s3.x), A[0][1] + uf(s3.y), A[0][2] + uf(s3.z), A[0][3] + uf(s3.w), F, pml, gs + yo);
      y_store<128>(A[1][0] + X[0][0], A[1][1] + X[0][1], A[1][2] + X[0][2], A[1][3] + X[0][3], F, pml, gs + yo + 1024);
      y_store<128>(A[2][0] + X[1][0] + X[2][0], A[2][1] + X[1][1] + X[2][1], A[2][2] + X[1][2] + X[2][2], A[2][3] + X[1][3] + X[2][3], F, pml, gs + yo + 2048);
    }
    barrive(12, N12);
    TS(15);
  } else {
    asm volatile("setmaxnreg.dec.sync.aligned.u32 136;");
    const u32 t8 = tid - 128, pml = (g & 3) ? 0 : pm;
    {
      TS(12);
      if (PFG == 1 && tid == 288) l2_pre<WSH / 2>(p.wg + (b * WSH + WSH / 2));
      const char* zs = gs + ((16 * w - 64 + (lane >> 3)) * BLK + b * 128 + ((lane & 7) * 16 ^ rho * 64));
      const char* zs4 = gs + ((t8 >> 1) * BLK + (Ps >> 4) * 512 + (Ps & 6) * 64 + ((Ps >> 2 ^ Ps) & 2) * 32 + (Ps & 1) * 32 + (t8 & 1) * 16);
      uint4 v[5];
      v[4].x = INVAL;
      if (ZD) wait_clk(t0, ZD);
      if (w == 9) {
        const u32 d = lane < 4 ? chan(b, lane) : Ps;
        const char* mp = gs + (G_MOD + (d >> 5) * 128 + (d & 24) * 2);
        uint4 ta, tc;
        POLL({ ta = ldr128(mp); tc = ldr128(mp + MODJ); v[4] = ldr128(zs4); }, ((ta.x ^ pm) | (tc.x ^ pm)) & TAGM, 2);
        const u32 aw = (d & 4) ? ((d & 2) ? ta.w : ta.z) : ((d & 2) ? ta.y : ta.x & ~TAGM);
        const u32 cw = (d & 4) ? ((d & 2) ? tc.w : tc.z) : ((d & 2) ? tc.y : tc.x & ~TAGM);
        const float sa = ((d & 1) ? bhi(aw) : blo(aw)) * F2P64, c1 = rbf(fmaf((d & 1) ? bhi(cw) : blo(cw), F2P64, 1.f));
        const u32 EM = min(max(fu(fmaxf(32.f * fabsf(c1), fabsf(sa))) >> 23, 80u), 250u);
        const float inv = uf((264 - EM) << 23);
        if (lane < 5) { sts64(SM_SC + 16 * lane, pk_hf(16.f * c1 * inv, 16.f * c1 * inv), pk_hf(sa * inv, sa * inv)); sts32(SM_SC + 16 * lane + 8, (EM - 74) << 23); }
        TS(10);
      }
      POLLW(v[4] = ldr128(zs4), (v[4].x ^ pm) & TAGM, 1);
      TS(58);
#pragma unroll
      for (int j = 0; j < 4; j++) v[j] = ldr128(zs + j * 4 * BLK);
#define MARKERS() if (tid == 256) { \
        bulk_out<2048>(gs + (G_Y + 16384 + b * BLK), SM_INV); \
        _Pragma("unroll") for (int i = MT / 2; i < 8; i++) bulk_out<2048>(gs + (G_Y + 2048 * i + b * BLK), SM_INV); \
        bulk_out<2048>(gs + (G_PART + b * 2048), SM_INV); bulk_out<512>(gs + (G_ACT + b * 512), SM_INV); \
        bulk_out<32>(gs + (G_KEY + b * KST), SM_INV); if (!rho) bulk_out<128>(gs + (G_ACT + Ps * 128), SM_INV); \
        asm volatile("cp.async.bulk.commit_group;" ::: "memory"); }
#define GATE() { mb_expect(SM_MB + 8, rho ? SLV : 46080); \
        _Pragma("unroll") for (int i = GE; i < 3; i++) tma3d(SM_GATE + 12288 * i, &tm_gate, SM_MB + 8, 32 * b, i); \
        if (!rho) tma3d(SM_GATE + SLV, &tm_gs, SM_MB + 8, 4096 + 4 * b, 0); }
#define UP() { mb_expect(SM_MB + 16, rho ? SLV : 46080); tma3d(SM_UP, &tm_up, SM_MB + 16, 32 * b, 0); \
        if (!rho) tma3d(SM_UP + SLV, &tm_us, SM_MB + 16, 4096 + 4 * b, 0); }
      if (PFU == 2 && tid == 256) l2_pre<WSH>(p.wu + b * WSH);
      if (GE && tid == 256) {
        asm volatile("cp.async.bulk.wait_group.read 0;" ::: "memory");
#pragma unroll
        for (int i = 0; i < GE; i++) tma3d(SM_GATE + 12288 * i, &tm_gate, SM_MB + 8, 32 * b, i);
      }
      if (MKT == 0) MARKERS();
      if (PFG == 2 && tid == 256) l2_pre<WSH>(p.wg + b * WSH);
      if (PFG == 3 && tid == 256) l2_pre<WSH / 2>(p.wg + (b * WSH + WSH / 2));
      bsync(8, 256);
      const uint2 cc = lds64(SM_SC + 8 * (t8 & 6)), c4 = lds64(SM_SC + 64);
      POLLW(_Pragma("unroll") for (int j = 0; j < 4; j++) if ((v[j].x ^ pm) & TAGM) v[j] = ldr128(zs + j * 4 * BLK),
           ((v[0].x ^ pm) | (v[1].x ^ pm) | (v[2].x ^ pm) | (v[3].x ^ pm)) & TAGM, 1);
      TS(9);
      const u32 dst = SM_ZS + 128 + (t8 & 7) * ZPS + (16 * w - 64 + (lane >> 3)) * 16;
#pragma unroll
      for (int j = 4; j >= 0; j--) {
        const uint2 c = j < 4 ? cc : c4;
        sts128(j < 4 ? dst + j * 64 : SM_Z4 + 256 + (t8 & 1) * ZP4 + (t8 >> 1) * 16, hfma(v[j].x & ~TAGM, c.x, c.y), hfma(v[j].y, c.x, c.y), hfma(v[j].z, c.x, c.y), hfma(v[j].w, c.x, c.y));
      }
      if (t8 < 96) sts128(t8 < 64 ? SM_ZS + (t8 & 7) * ZPS + (t8 >> 3) * 16 : SM_Z4 + (t8 & 1) * ZP4 + (t8 & 30) * 8, 0, 0, 0, 0);
      if (MKT == 0) asm volatile("cp.async.bulk.wait_group.read 1;" ::: "memory");
      else asm volatile("cp.async.bulk.wait_group.read 0;" ::: "memory");
      bsync(9, 384);
      TS(11);
      if (MKT == 1) MARKERS();
      const bool lng = w < 8 || w == 9;
      const u32 ts = lane + 32 * (w == 8 ? 0 : w - 9), c = min(ts, 71u), ma = SM_MODS + 16 * c;
      const u32 sig = lng ? ksig : ts >> 4, l2 = lng ? lane : 32 + (ts & 15);
      const char* mq = gs + (G_MOD + (c >> 2) * 128 + (c & 3) * 16);
      if (!lng) {
#pragma unroll
        for (int j = 0; j < 6; j++) cpa16(ma + 1152 * j, mq + j * MODJ);
        cpa16(ma + 1152 * 6, p.dsk + 16 * c); cpa16(ma + 1152 * 7, p.wr + 16 * c);
        if (PFU == 3) {
#pragma unroll
          for (int j = 0; j < 4; j++) if (ts < 81) l2_line(p.wu + (b * WSH + (81 * j + ts) * 128));
        }
        if (tid == 352) {
          PROXY_FENCE();
          if (PFU == 1) l2_pre<WSH>(p.wu + b * WSH);
          if (!TG) GATE();
          if (!TU) UP();
        }
      }
      const u32 wb = SM_W + sig * WSL;
      if (sig < 5) {
        const u32 za = (sig < 4 ? SM_ZS + 128 + sig * ZSS : SM_Z4 + 256) + l2 * 32, zb = za + (sig < 4 ? ZPS : ZP4);
        const uint4 c0 = lds128(zb - 32), c1 = lds128(za - 16), c2 = lds128(zb - 16), c3 = lds128(za), c4 = lds128(zb), c5 = lds128(za + 16), c6 = lds128(zb + 16);
        const u32 P[25] = {c0.z, c0.w, c1.x, c1.y, c1.z, c1.w, c2.x, c2.y, c2.z, c2.w, c3.x, c3.y, c3.z, c3.w, c4.x, c4.y, c4.z, c4.w, c5.x, c5.y, c5.z, c5.w, c6.x, c6.y, c6.z};
        u32 Q[25], D1[24], F4[23], W5[21], W3[17];
#pragma unroll
        for (int j = 1; j < 25; j++) Q[j] = __byte_perm(P[j - 1], P[j], 0x5432);
#pragma unroll
        for (int j = 1; j < 24; j++) D1[j] = hadd(P[j], Q[j]);
#pragma unroll
        for (int j = 2; j < 23; j++) F4[j] = hadd(D1[j], D1[j - 1]);
#pragma unroll
        for (int n = 0; n < 21; n++) W5[n] = hadd(F4[n + 2], P[n]);
#pragma unroll
        for (int n = 0; n < 17; n++) W3[n] = hadd(Q[n + 8], D1[n + 7]);
        const u32 a0 = wb + W5O + 64 * l2 + 16 * ((l2 >> 1) & 3);
#pragma unroll
        for (int i = 0; i < 4; i++) {
          sts128(a0 ^ (16 * i), W5[4 * i + 5], W5[4 * i + 6], W5[4 * i + 7], W5[4 * i + 8]);
          sts128((a0 ^ (16 * i)) + (W3O - W5O), W3[4 * i + 1], W3[4 * i + 2], W3[4 * i + 3], W3[4 * i + 4]);
        }
        if (lng) {
          if (lane < 16) sts128(wb + (lane & 7) * 16 + (lane & 8) * 400, 0, 0, 0, 0);
          const u32 a1 = wb + 32 * lane + 16 * ((lane >> 2) & 1);
#pragma unroll
          for (int i = 0; i < 4; i++) {
            const u32 a = (a1 ^ (16 * (i >> 1))) + 1024 * (i & 1), n = 4 * i;
            sts128(a + V2O, hadd(Q[n + 9], P[n + 8]), hadd(Q[n + 10], P[n + 9]), hadd(Q[n + 11], P[n + 10]), hadd(Q[n + 12], P[n + 11]));
            sts128(a + W9O, hadd(F4[n + 4], W5[n]), hadd(F4[n + 5], W5[n + 1]), hadd(F4[n + 6], W5[n + 2]), hadd(F4[n + 7], W5[n + 3]));
            sts128(a + W7O, hadd(F4[n + 6], W3[n]), hadd(F4[n + 7], W3[n + 1]), hadd(F4[n + 8], W3[n + 2]), hadd(F4[n + 9], W3[n + 3]));
          }
        }
      }
      if (w < 8) barriver((BW >> (4 * w - 16)) & 15);
      else if (!(w & 1)) { barriver((BW >> (4 * w - 32)) & 15); barriver((BW >> (4 * w - 28)) & 15); }
      __syncwarp();
      TS(32);
      if (lng) {
        const u32 wa = wb + ((lane >> 3) & 1) * 1024 + (((lane & 7) ^ (lane >> 4)) + 8 * (lane >> 4)) * 16;
        const u32 kv = lds32(SM_KV + 4 * sig), bi = (g >> 1) == q ? (hi ? kv << 16 : kv) : 0u;
        float acc[8][4] = {};
#pragma unroll
        for (int j = 0; j < 4; j++) { const uint4 a = ldsm4t(wa + V2O + j * 256); mma8_hf(acc[2 * j], a.x, a.y, bi); mma8_hf(acc[2 * j + 1], a.z, a.w, bi); }
        u32 bt = tp + (T9E + hi * TEO + (g >> 1) - q) * 4, wt = wa + W9O;
#pragma unroll 1
        for (int ty = 0; ty < 2; ty++) {
          uint4 a[4];
#pragma unroll
          for (int be = 0; be < 4; be++) a[be] = ldsm4t(wt + be * 256);
          u32 b1 = lds32(bt - 16);
#pragma unroll
          for (int d = 0; d < 8; d++) {
            const u32 b0 = lds32(bt + 16 * d);
#pragma unroll
            for (int be = 0; be < 4; be++) if (d + 2 * be < 8) mma_hf(acc[d + 2 * be], a[be].x, a[be].y, a[be].z, a[be].w, b0, b1);
            b1 = b0;
          }
          bt += (T7E - T9E) * 4; wt += W7O - W9O;
        }
        __syncwarp();
#pragma unroll
        for (int j = 0; j < 8; j++) sts128(wb + W9O + j * 512 + lane * 16, fu(acc[j][0]), fu(acc[j][1]), fu(acc[j][2]), fu(acc[j][3]));
        if (w != 9) barriver((BS >> (4 * w - 16)) & 15);
        TS(34);
      }
      if (!lng) {
        asm volatile("cp.async.wait_all;" ::: "memory");
        uint4 md[6];
#pragma unroll
        for (int j = 0; j < 6; j++) md[j] = lds128(ma + 1152 * j);
        const uint4 dk = lds128(ma + 1152 * 6), wr = lds128(ma + 1152 * 7);
        POLLW(_Pragma("unroll") for (int j = 0; j < 6; j++) md[j] = ldr128(mq + j * MODJ),
              ((md[0].x ^ pm) | (md[1].x ^ pm) | (md[2].x ^ pm) | (md[3].x ^ pm) | (md[4].x ^ pm) | (md[5].x ^ pm)) & TAGM, 4);
#pragma unroll
        for (int j = 0; j < 6; j++) {
          const u32 o = (j % 3 == 1) ? BONE : 0x80008000u;
          md[j] = make_uint4(bfma(md[j].x & ~TAGM, B2P64, o), bfma(md[j].y, B2P64, o), bfma(md[j].z, B2P64, o), bfma(md[j].w, B2P64, o));
          if (j > 2) sts128(ma + 1152 * j, md[j].x, md[j].y, md[j].z, md[j].w);
        }
        const uint4 gd = make_uint4(bmul(md[2].x, dk.x), bmul(md[2].y, dk.y), bmul(md[2].z, dk.z), bmul(md[2].w, dk.w));
#pragma unroll
        for (int j = 0; j < 2; j++) sts128(ma + 1152 * j, bmul(md[j].x, gd.x), bmul(md[j].y, gd.y), bmul(md[j].z, gd.z), bmul(md[j].w, gd.w));
        sts128(ma + 2304, bmul(md[2].x, B2P64), bmul(md[2].y, B2P64), bmul(md[2].z, B2P64), bmul(md[2].w, B2P64));
        const uint4 H = make_uint4(bmul(md[4].x, wr.x), bmul(md[4].y, wr.y), bmul(md[4].z, wr.z), bmul(md[4].w, wr.w));
        sts128(ma + 1152 * 7, H.x, H.y, H.z, H.w);
        sts128(ma + 1152 * 8, bfma(md[4].x, wr.x, H.x ^ 0x80008000u), bfma(md[4].y, wr.y, H.y ^ 0x80008000u), bfma(md[4].z, wr.z, H.z ^ 0x80008000u), bfma(md[4].w, wr.w, H.w ^ 0x80008000u));
        float c4[4] = {};
        mma_bf(c4, md[4].x, md[3].x, md[4].y, md[3].y, wr.x, wr.y); mma_bf(c4, md[4].z, md[3].z, md[4].w, md[3].w, wr.z, wr.w);
        if (q == g >> 1) sts64(SM_RC + (ts >> 2) * 8, fu(hi ? c4[1] : c4[0]), fu(hi ? c4[3] : c4[2]));
        if (ts < 2) sts128(SM_ONE + 16 * ts, ts ? 0 : BONE, ts ? 0 : BONE, ts ? 0 : BONE, ts ? 0 : BONE);
        TS(14);
        if (MKT == 2) MARKERS();
        if (w == 8) asm volatile("cp.async.bulk.wait_group 0;" ::: "memory");
        if (PFW == 2) {
#pragma unroll
          for (int j = 0; j < 4; j++) if (ts < 81) l2_line(p.wd + (b * WSH + (81 * j + ts) * 128));
        }
        bsync(13, 96);
        if (w == 8) { barriver(2); barriver(3); barriver(5); barriver(6); }
      }
      if (MB11) { if (w == 8 || w == 9) mb_arrive(SM_MB + 32); } else if (w >= 8) barrive(11, 256);
    }
    if (w < 8) {
      const u32 jw = SWJ && w < 6 ? w ^ 1 : w;
      const int u0 = 4 * (jw - 4) + 2 * rho;
      const u32 t4 = SM_TAP + 4 * TAPS;
      u32 tr = t4 + ((hi ? TO : TE) + (g >> 1) - q) * 4;
      u32 zb = SM_Z4 + 256 + ((lane >> 3) & 1) * ZP4 + u0 * 128 + (lane & 7) * 16 + (lane >> 4) * 128;
      float acc[4][4] = {};
      u32 prev = 0;
#pragma unroll 1
      for (int it = min(u0 + 2, 4); it; it--) {
#pragma unroll
        for (int s = 0; s < 8; s++) {
          const uint4 z = ldsm4(zb - 16 * s);
          const u32 t0 = lds32(tr + 32 * s), t1 = lds32(tr + 32 * s + 16);
          mma_hf(acc[s & 1], t0, t1, prev, t0, z.x, z.y);
          mma_hf(acc[2 + (s & 1)], t0, t1, prev, t0, z.z, z.w);
          prev = t1;
        }
        zb -= 128; tr += 256;
      }
      {
        const uint4 z = ldsm4(zb); const u32 t0 = lds32(tr), t1 = lds32(tr + 16);
        mma_hf(acc[0], t0, t1, prev, t0, z.x, z.y); mma_hf(acc[2], t0, t1, prev, t0, z.z, z.w);
        if (jw > 4) { const uint4 y = ldsm4(zb - 16); mma8_hf(acc[1], t1, zr, y.y); mma8_hf(acc[3], t1, zr, y.w); }
      }
      if (MB11) mb_wait(SM_MB + 32); else bsync(11, 256);
      u32 wa = (SM_W + 4 * WSL + W5O + row16(lane) + (u0 - 3) * 256) ^ 32, bt = t4 + (T5 + g - q) * 4;
#pragma unroll 1
      for (int al = min(u0 - 2, 6); al > 0; al--) {
#pragma unroll
        for (int ty = 0; ty < 2; ty++) {
          const uint4 a = ldsm4t(wa + ty * (W3O - W5O));
          const u32 bb = bt + ty * (T3 - T5) * 4;
          mma_hf(acc[ty], a.x, a.y, a.z, a.w, lds32(bb - 32), lds32(bb - 48));
          mma_hf(acc[2 + ty], a.x, a.y, a.z, a.w, lds32(bb), lds32(bb - 16));
        }
        wa = (wa - 256) ^ 32; bt += 32;
      }
      TS(35);
      const uint2 fc = lds64(SM_SC + 16 * 4 + 8);
      const u32 F = __byte_perm(fu(uf(fc.x) * uf(fc.y)), 0, 0x3232);
      char* yp = gs + (G_Y + 16384 - 2048 + b * BLK + jw * 512 + q * 64 + 4 * g);
#pragma unroll
      for (int j = 0; j < 2; j++) {
        uint4 s3 = {0, 0, 0, 0};
        if (u0 >= 8) s3 = lds128(SM_W + 4 * WSL + W9O + (u0 - 8 + j) * 512 + lane * 16);
        y_store<32>(acc[2 * j][0] + acc[2 * j + 1][0] + uf(s3.x), acc[2 * j][1] + acc[2 * j + 1][1] + uf(s3.y), acc[2 * j][2] + acc[2 * j + 1][2] + uf(s3.z),
                acc[2 * j][3] + acc[2 * j + 1][3] + uf(s3.w), F, pml, yp + j * 256);
      }
      barrive(7, 160);
      TS(16);
    } else {
      if (PFW == 3 && w == 9) {
#pragma unroll 1
        for (int j = 0; j < 12; j++) { if (lane < 27) l2_line(p.wd + (b * WSH + (27 * j + lane) * 128)); wait_clk(clk(), PFP); }
      }
      if (TG | TU | TW) {
        if (tid == 352) {
          if (TG) { wait_clk(t0, TG); GATE(); }
          if (TW < TU) { wait_clk(t0, TW); l2_pre<WSH>(p.wd + b * WSH); }
          if (TU) { wait_clk(t0, TU); UP(); }
          if (TW >= TU) { wait_clk(t0, TW); l2_pre<WSH>(p.wd + b * WSH); }
        }
      } else if (PFW < 2 && tid == 352) { mb_wait(SM_MB + 8); if (PFW) mb_wait(SM_MB + 16); l2_pre<WSH>(p.wd + b * WSH); }
      if (D0C && tid == 352 && b < 108) {
        mb_wait(SM_MB + 16);
        PROXY_FENCE();
        mb_expect(SM_MB + 24, 49152);
        tma3d(SM_TAP, &tm_down, SM_MB + 24, 64 * (b % 9), 4 * (b / 9));
      }
      TS(17);
    }
  }
  post_conv(p, &tm_down, tid2 + p.zero, b);
  TSD();
  if (s2u(smem) != SM0) __trap();
}

typedef CUresult (*EncFn)(CUtensorMap*, CUtensorMapDataType, cuuint32_t, void*, const cuuint64_t*, const cuuint64_t*, const cuuint32_t*, const cuuint32_t*,
                          CUtensorMapInterleave, CUtensorMapSwizzle, CUtensorMapL2promotion, CUtensorMapFloatOOBfill);
static void make_map(EncFn enc, CUtensorMap* tm, void* ptr, int cols, int rows, int bw, int nb, CUtensorMapSwizzle sw, int gr = 192, int prom = 0) {
  cuuint64_t gd[3] = {(cuuint64_t)cols, (cuuint64_t)gr, (cuuint64_t)(rows / gr)}, gs[2] = {(cuuint64_t)cols * 2, (cuuint64_t)cols * 2 * gr};
  cuuint32_t bd[3] = {(cuuint32_t)bw, (cuuint32_t)gr, (cuuint32_t)nb}, es[3] = {1, 1, 1};
  enc(tm, CU_TENSOR_MAP_DATA_TYPE_BFLOAT16, 3, ptr, gd, gs, bd, es, CU_TENSOR_MAP_INTERLEAVE_NONE, sw, (CUtensorMapL2promotion)prom, CU_TENSOR_MAP_FLOAT_OOB_FILL_NONE);
}
extern "C" void kernel_launch(void* const* d_in, const int* in_sizes, int n_in, void* d_out, int out_size) {
  static EncFn enc = nullptr;
  static void* scratch = nullptr;
  if (!enc) {
    cudaGetSymbolAddress(&scratch, g_s);
    cudaDriverEntryPointQueryResult qr;
    cudaGetDriverEntryPoint("cuTensorMapEncodeTiled", (void**)&enc, cudaEnableDefault, &qr);
    cudaFuncSetAttribute(fused_kernel, cudaFuncAttributeMaxDynamicSharedMemorySize, SM_TOTAL);
  }
  CUtensorMap tm_mod, tm_gate, tm_gs, tm_up, tm_us, tm_down;
  make_map(enc, &tm_mod, d_in[13], 3456, 576, 32, 3, CU_TENSOR_MAP_SWIZZLE_64B, 192, PRM);
  make_map(enc, &tm_gate, d_in[9], 4608, 576, 32, 1, CU_TENSOR_MAP_SWIZZLE_64B, 192, PRG);
  make_map(enc, &tm_gs, d_in[9], 4608, 576, 8, 3, CU_TENSOR_MAP_SWIZZLE_NONE);
  make_map(enc, &tm_up, d_in[10], 4608, 576, 32, 3, CU_TENSOR_MAP_SWIZZLE_64B, 192, PRU);
  make_map(enc, &tm_us, d_in[10], 4608, 576, 8, 3, CU_TENSOR_MAP_SWIZZLE_NONE, 192, PRS);
  make_map(enc, &tm_down, d_in[11], 576, 4608, 64, 1, CU_TENSOR_MAP_SWIZZLE_128B, 96);
  Prm p;
  p.x = (const char*)d_in[0]; p.la = (const char*)d_in[1]; p.ai = (const char*)d_in[2]; p.cr = (const char*)d_in[3];
  p.ci = (const char*)d_in[4]; p.ldt = (const char*)d_in[5]; p.dsk = (const char*)d_in[6]; p.wr = (const char*)d_in[8];
  p.wg = (const char*)d_in[9]; p.wu = (const char*)d_in[10]; p.wd = (const char*)d_in[11];
  p.c = (const char*)d_in[12]; p.out = (char*)d_out; p.zero = 0; p.gs = (char*)scratch;
  fused_kernel<<<128, 384, SM_TOTAL>>>(p, tm_mod, tm_gate, tm_gs, tm_up, tm_us, tm_down);
}
```

```cpp
#include <cuda_runtime.h>
#include <cuda.h>
#include <cuda_bf16.h>
#include <cuda_fp16.h>
#include <stdint.h>
#define FUSED 1
#define DEV __device__ __forceinline__
typedef uint32_t u32;

constexpr u32 BLK = 18432, G_Z = 0, G_Y = 128 * BLK, G_MOD = 2 * G_Y, G_KEY = G_MOD + 128 * 128, G_ACT = G_KEY + 128 * 128;
constexpr u32 G_PART = G_ACT + 576 * 128, G_EP = G_PART + 128 * 2048, G_END = G_EP + 128;
__device__ __align__(128) unsigned char g_s[G_END];
#define TS(i)
#define TSJ(j)
#define TS0()
#define TSE()
#define TSD()
#define TSX 0
#define TSRND()
#define TSN(code, n)
#define ERRF(code)

constexpr int SM0 = 1024;
constexpr int ROW = 1168, SLV = 36864;
constexpr int SM_GATE = SM0, SM_UP = SM_GATE + 46080, SM_XST = SM_UP + 46080, SM_MODS = SM_XST + 16 * ROW, SM_W = SM_MODS + 11008;
constexpr int KTAB = 9216, WSL = 12544, W5O = 128, W3O = 3328, V2O = 6400, W9O = 8448, W7O = 10496;
constexpr int ZPS = 2192, ZSS = 2 * ZPS, ZP4 = 2368;
constexpr int SM_ZS = SM_W + 5 * WSL, SM_Z4 = SM_ZS + 4 * ZSS, SM_TAP = SM_Z4 + 2 * ZP4, TAPS = 3328;
constexpr int SM_MB = SM_TAP + 5 * TAPS;
constexpr int SM_SC = SM_MB + 48;
constexpr int SM_KV = SM_SC + 80;
constexpr int SM_THR = SM_KV + 32;
constexpr int SM_SLOT = SM_THR + 48;
constexpr int SM_KEY = SM_SLOT + 32;
constexpr int SM_ST = SM_KEY + 64;
constexpr int SM_ST2 = SM_ST + 256;
constexpr int SM_RC = SM_ST2 + 256;
constexpr int SM_SP = SM_RC + 192;
constexpr int SM_AF = SM_SP + 1152, SM_SIL = SM_AF + 1152, SM_INV = SM_SIL + 1152, SM_END = SM_SP + 5760;
constexpr int SM_ONE = SM_MODS + 9 * 1152;
constexpr int SM_WD = SM_W, SM_XS = SM_W + 36864, SM_AC = SM_ZS, SM_RED = SM_AC + 6144;
constexpr int SM_TSB = SM_END, SM_TOTAL = SM_END + TSX - SM0;
static_assert(SM_W % 1024 == 0 && SM_TAP % 1024 == 0 && SM_MODS + 8 * KTAB <= SM_ZS && SM_ZS + 2 * KTAB <= SM_TAP && SM_RED + 10240 <= SM_TAP && SM_XS + 8 * ROW <= SM_ZS, "smem map");
static_assert(SM_MB % 16 == 0 && SM_THR % 16 == 0 && SM_ST % 16 == 0 && SM_SP % 16 == 0 && SM_TOTAL <= 232448, "smem map");
constexpr int TE = 4, TO = 276, T5 = 560, T3 = 624, T9E = 680, T7E = 760, TEO = 40;
#define MT 10
#define MKT 1
#define KST 128
#define DE1 1
#define DE2 4
#define DE3 5
#define OUTB 7
#define PFW 1
#define PFU 0
#define KD 700
#define D0C 0
#define YE 104
#define YL 104
#define YD 250
#define OPTM 1
#define Y8 64
#define FH 0
#define FO 0
#define DB1 1
#define KD1 50
#define AD 0
#define PD 900
#define ZD 0
#define DD 1000
#define INCV 1
#define TPIN 0
#define A5P 1
#define SWJ 1
#define TG 0
#define TU 0
#define TW 0
#define KDB 520
#define KA 0
#define MB11 0
#define W8D 0
#define PRM 0
#define PRG 0
#define PRU 0
#define PRS 0
#define KE 64
#define PFP 200
#define GE 0
#define NB8 8
#define DX 0
#define DMOD 1000
#define RW 3
#define AW 7
#define KW 900
#define KWB 400
#define KW1 200
#define AFP 1
#define AFM 0
#define PFG 1
constexpr int N1 = 320 + 32 * DB1 + 32 * !!KA, N12 = 288 + 32 * !DB1;
constexpr int SPIN = 1 << 16, NEARLY = 4;
constexpr u32 TAGM = 0x40004000u, TAGR = 0x40000000u, INVAL = 0x00004801u;

DEV u32 s2u(const void* p) { return (u32)__cvta_generic_to_shared(p); }
DEV void mma_bf(float (&c)[4], u32 a0, u32 a1, u32 a2, u32 a3, u32 b0, u32 b1) {
  asm("mma.sync.aligned.m16n8k16.row.col.f32.bf16.bf16.f32 {%0,%1,%2,%3},{%4,%5,%6,%7},{%8,%9},{%0,%1,%2,%3};"
      : "+f"(c[0]), "+f"(c[1]), "+f"(c[2]), "+f"(c[3]) : "r"(a0), "r"(a1), "r"(a2), "r"(a3), "r"(b0), "r"(b1));
}
DEV void mma_hf(float (&c)[4], u32 a0, u32 a1, u32 a2, u32 a3, u32 b0, u32 b1) {
  asm("mma.sync.aligned.m16n8k16.row.col.f32.f16.f16.f32 {%0,%1,%2,%3},{%4,%5,%6,%7},{%8,%9},{%0,%1,%2,%3};"
      : "+f"(c[0]), "+f"(c[1]), "+f"(c[2]), "+f"(c[3]) : "r"(a0), "r"(a1), "r"(a2), "r"(a3), "r"(b0), "r"(b1));
}
DEV void mma8_bf(float (&c)[4], u32 a0, u32 a1, u32 b0) {
  asm("mma.sync.aligned.m16n8k8.row.col.f32.bf16.bf16.f32 {%0,%1,%2,%3},{%4,%5},{%6},{%0,%1,%2,%3};"
      : "+f"(c[0]), "+f"(c[1]), "+f"(c[2]), "+f"(c[3]) : "r"(a0), "r"(a1), "r"(b0));
}
DEV void mma8_hf(float (&c)[4], u32 a0, u32 a1, u32 b0) {
  asm("mma.sync.aligned.m16n8k8.row.col.f32.f16.f16.f32 {%0,%1,%2,%3},{%4,%5},{%6},{%0,%1,%2,%3};"
      : "+f"(c[0]), "+f"(c[1]), "+f"(c[2]), "+f"(c[3]) : "r"(a0), "r"(a1), "r"(b0));
}
DEV u32 movm(u32 x) { u32 r; asm("movmatrix.sync.aligned.m8n8.trans.b16 %0,%1;" : "=r"(r) : "r"(x)); return r; }
DEV uint4 ldsm4(u32 a) { uint4 r; asm volatile("ldmatrix.sync.aligned.m8n8.x4.shared.b16 {%0,%1,%2,%3},[%4];" : "=r"(r.x), "=r"(r.y), "=r"(r.z), "=r"(r.w) : "r"(a)); return r; }
DEV uint4 ldsm4t(u32 a) { uint4 r; asm volatile("ldmatrix.sync.aligned.m8n8.x4.trans.shared.b16 {%0,%1,%2,%3},[%4];" : "=r"(r.x), "=r"(r.y), "=r"(r.z), "=r"(r.w) : "r"(a)); return r; }
DEV u32 lds32(u32 a) { u32 r; asm volatile("ld.volatile.shared.u32 %0,[%1];" : "=r"(r) : "r"(a)); return r; }
DEV uint2 lds64(u32 a) { uint2 r; asm volatile("ld.shared.v2.u32 {%0,%1},[%2];" : "=r"(r.x), "=r"(r.y) : "r"(a)); return r; }
DEV uint4 lds128(u32 a) { uint4 r; asm volatile("ld.shared.v4.u32 {%0,%1,%2,%3},[%4];" : "=r"(r.x), "=r"(r.y), "=r"(r.z), "=r"(r.w) : "r"(a)); return r; }
DEV void sts16(u32 a, u32 v) { asm volatile("st.shared.u16 [%0],%1;" ::"r"(a), "h"((unsigned short)v) : "memory"); }
DEV void sts32(u32 a, u32 v) { asm volatile("st.shared.u32 [%0],%1;" ::"r"(a), "r"(v) : "memory"); }
DEV void sts64(u32 a, u32 x, u32 y) { asm volatile("st.shared.v2.u32 [%0],{%1,%2};" ::"r"(a), "r"(x), "r"(y) : "memory"); }
DEV void sts128(u32 a, u32 x, u32 y, u32 z, u32 w) { asm volatile("st.shared.v4.u32 [%0],{%1,%2,%3,%4};" ::"r"(a), "r"(x), "r"(y), "r"(z), "r"(w) : "memory"); }
DEV uint4 ldr128(const void* p) { uint4 v; asm volatile("ld.relaxed.gpu.global.v4.u32 {%0,%1,%2,%3},[%4];" : "=r"(v.x), "=r"(v.y), "=r"(v.z), "=r"(v.w) : "l"(p) : "memory"); return v; }
DEV uint2 ldr64(const void* p) { uint2 v; asm volatile("ld.relaxed.gpu.global.v2.u32 {%0,%1},[%2];" : "=r"(v.x), "=r"(v.y) : "l"(p) : "memory"); return v; }
DEV u32 ldr32(const void* p) { u32 v; asm volatile("ld.relaxed.gpu.global.u32 %0,[%1];" : "=r"(v) : "l"(p) : "memory"); return v; }
template <u32 M> DEV void rld128(uint4& v, const void* p, u32 tag) {
  asm volatile("{.reg .pred p; .reg .u32 t; lop3.b32 t,%0,%5,%6,0x28; setp.ne.u32 p,t,0; @p ld.relaxed.gpu.global.v4.u32 {%0,%1,%2,%3},[%4];}"
               : "+r"(v.x), "+r"(v.y), "+r"(v.z), "+r"(v.w) : "l"(p), "r"(tag), "n"(M) : "memory");
}
template <u32 M> DEV void rld64(uint64_t& v, const void* p, u32 tag) {
  asm volatile("{.reg .pred p; .reg .u32 t, h; mov.b64 {t,h},%0; lop3.b32 t,t,%2,%3,0x28; setp.ne.u32 p,t,0; @p ld.relaxed.gpu.global.u64 %0,[%1];}" : "+l"(v) : "l"(p), "r"(tag), "n"(M) : "memory");
}
template <int L> DEV u32 lop3(u32 a, u32 b, u32 c) { u32 r; asm("lop3.b32 %0,%1,%2,%3,%4;" : "=r"(r) : "r"(a), "r"(b), "r"(c), "n"(L)); return r; }
DEV u32 ne3(u32 a, u32 b, u32 c) { u32 r; asm("lop3.b32 %0,%1,%2,%3,0x7e;" : "=r"(r) : "r"(a), "r"(b), "r"(c)); return r; }
DEV void pin(u32 zr, u32 a, u32 b = 0, u32 c = 0, u32 d = 0) { asm volatile("{.reg .pred p; setp.ne.u32 p,%0,0; @p st.shared.v4.u32 [%0],{%1,%2,%3,%4};}" ::"r"(zr), "r"(a), "r"(b), "r"(c), "r"(d) : "memory"); }
DEV void pin2(u32 zr, const void* a, const void* b) { asm volatile("{.reg .pred p; setp.ne.u32 p,%0,0; @p st.shared.v2.u64 [%0],{%1,%2};}" ::"r"(zr), "l"(a), "l"(b) : "memory"); }
DEV const char* rowa(const char* base, u32 key) { const char* r; asm("mad.wide.u32 %0,%1,288,%2;" : "=l"(r) : "r"(~key & 0x1ffc), "l"(base)); return r; }
DEV void str128(void* p, u32 x, u32 y, u32 z, u32 w) { asm volatile("st.relaxed.gpu.global.v4.u32 [%0],{%1,%2,%3,%4};" ::"l"(p), "r"(x), "r"(y), "r"(z), "r"(w) : "memory"); }
DEV void str64(void* p, u32 x, u32 y) { asm volatile("{.reg .u64 d; mov.b64 d,{%1,%2}; st.relaxed.gpu.global.u64 [%0],d;}" ::"l"(p), "r"(x), "r"(y) : "memory"); }
DEV void str32(void* p, u32 x) { asm volatile("st.relaxed.gpu.global.u32 [%0],%1;" ::"l"(p), "r"(x) : "memory"); }
DEV void str16(void* p, u32 x) { asm volatile("st.relaxed.gpu.global.u16 [%0],%1;" ::"l"(p), "h"((unsigned short)x) : "memory"); }
DEV uint4 ldg128(const void* p) { uint4 v; asm volatile("ld.global.nc.v4.u32 {%0,%1,%2,%3},[%4];" : "=r"(v.x), "=r"(v.y), "=r"(v.z), "=r"(v.w) : "l"(p)); return v; }
DEV uint2 ldg64(const void* p) { uint2 v; asm volatile("ld.global.nc.v2.u32 {%0,%1},[%2];" : "=r"(v.x), "=r"(v.y) : "l"(p)); return v; }
DEV u32 ldg32(const void* p) { u32 v; asm volatile("ld.global.nc.u32 %0,[%1];" : "=r"(v) : "l"(p)); return v; }
DEV u32 ldg16(const void* p) { unsigned short v; asm volatile("ld.global.nc.u16 %0,[%1];" : "=h"(v) : "l"(p)); return v; }
#define bsync(id, n) asm volatile("bar.sync %0,%1;" ::"n"(id), "n"(n) : "memory")
#define barrive(id, n) asm volatile("bar.arrive %0,%1;" ::"n"(id), "n"(n) : "memory")
DEV void bsyncr(u32 id) { asm volatile("bar.sync %0,96;" ::"r"(id) : "memory"); }
DEV void barriver(u32 id) { asm volatile("bar.arrive %0,96;" ::"r"(id) : "memory"); }
constexpr u32 BW = 0x0FEA, BS = 0x6532;
DEV void mb_init(u32 a, u32 n) { asm volatile("mbarrier.init.shared.b64 [%0],%1;" ::"r"(a), "r"(n) : "memory"); }
DEV void mb_arrive(u32 a) { asm volatile("mbarrier.arrive.shared.b64 _,[%0];" ::"r"(a) : "memory"); }
DEV void mb_expect(u32 a, u32 bytes) { asm volatile("mbarrier.arrive.expect_tx.shared.b64 _,[%0],%1;" ::"r"(a), "r"(bytes) : "memory"); }
DEV void mb_wait(u32 a, u32 ph = 0) {
  u32 ok; int it = 0;
  do { asm volatile("{.reg .pred p; mbarrier.try_wait.parity.shared.b64 p,[%1],%2; selp.u32 %0,1,0,p;}" : "=r"(ok) : "r"(a), "r"(ph) : "memory"); } while (!ok && ++it < SPIN);
}
template <int N> DEV void bulk_out(void* dst, u32 src) { asm volatile("cp.async.bulk.global.shared::cta.bulk_group [%0],[%1],%2;" ::"l"(dst), "r"(src), "n"(N) : "memory"); }
constexpr u32 WSH = 41472;
DEV void l2_line(const void* p) { asm volatile("prefetch.global.L2 [%0];" ::"l"(p) : "memory"); }
template <int N> DEV void l2_pre(const void* p) { asm volatile("cp.async.bulk.prefetch.L2.global [%0],%1;" ::"l"(p), "n"(N) : "memory"); }
DEV void tma3d(u32 dst, const CUtensorMap* tm, u32 mb, int c0, int c2) {
  asm volatile("cp.async.bulk.tensor.3d.shared::cluster.global.mbarrier::complete_tx::bytes [%0],[%1,{%3,0,%4}],[%2];"
               ::"r"(dst), "l"((uint64_t)tm), "r"(mb), "r"(c0), "r"(c2) : "memory");
}
DEV float blo(u32 w) { return __uint_as_float(w << 16); }
DEV float bhi(u32 w) { return __uint_as_float(w & 0xffff0000u); }
DEV u32 pk_bf(float lo, float hi) { u32 r; asm("cvt.rn.bf16x2.f32 %0,%1,%2;" : "=r"(r) : "f"(hi), "f"(lo)); return r; }
DEV u32 pk_hf(float lo, float hi) { u32 r; asm("cvt.rn.f16x2.f32 %0,%1,%2;" : "=r"(r) : "f"(hi), "f"(lo)); return r; }
DEV float rbf(float x) { return __uint_as_float(pk_bf(0.f, x) & 0xffff0000u); }
DEV u32 bfma(u32 a, u32 b, u32 c) { u32 r; asm("fma.rn.bf16x2 %0,%1,%2,%3;" : "=r"(r) : "r"(a), "r"(b), "r"(c)); return r; }
DEV u32 bmul(u32 a, u32 b) { u32 r; asm("mul.rn.bf16x2 %0,%1,%2;" : "=r"(r) : "r"(a), "r"(b)); return r; }
DEV u32 badd(u32 a, u32 b) { u32 r; asm("add.rn.bf16x2 %0,%1,%2;" : "=r"(r) : "r"(a), "r"(b)); return r; }
DEV u32 hadd(u32 a, u32 b) { u32 r; asm("add.rn.f16x2 %0,%1,%2;" : "=r"(r) : "r"(a), "r"(b)); return r; }
DEV u32 hfma(u32 a, u32 b, u32 c) { u32 r; asm("fma.rn.f16x2 %0,%1,%2,%3;" : "=r"(r) : "r"(a), "r"(b), "r"(c)); return r; }
struct C2 { u32 re, im; };
DEV C2 cm2(C2 a, C2 b) {
  const __half2 ar = *reinterpret_cast<__half2*>(&a.re), ai = *reinterpret_cast<__half2*>(&a.im), br = *reinterpret_cast<__half2*>(&b.re), bi = *reinterpret_cast<__half2*>(&b.im);
  __half2 re = __hfma2(ar, br, __hneg2(__hmul2(ai, bi))), im = __hfma2(ar, bi, __hmul2(ai, br));
  return {*reinterpret_cast<u32*>(&re), *reinterpret_cast<u32*>(&im)};
}
DEV C2 pk2(const float2 (&a)[2]) { return {pk_hf(a[0].x, a[1].x), pk_hf(a[0].y, a[1].y)}; }
DEV C2 pk2c(const float2 (&a)[2]) { return {pk_hf(a[0].x, a[1].x), pk_hf(-a[0].y, -a[1].y)}; }
DEV u32 cpy(u32 x, u32 zr, int alt) {
  u32 r;
  if (alt) asm volatile("xor.b32 %0,%1,%2;" : "=r"(r) : "r"(x), "r"(zr)); else asm volatile("mad.lo.u32 %0,%2,%2,%1;" : "=r"(r) : "r"(x), "r"(zr));
  return r;
}
template <int N> DEV void inc(u32& x) { asm volatile("add.u32 %0,%0,%1;" : "+r"(x) : "n"(N)); }
DEV u32 opq(u32 x) { u32 r; asm volatile("mov.u32 %0,%1;" : "=r"(r) : "r"(x)); return r; }
DEV u32 chan(u32 b, u32 i) { return 16 * (b >> 2) + 2 * (b & 3) + (i & 1) + 4 * (i & 2); }
DEV u32 row16(u32 lane) { const u32 r0 = (lane & 7) + ((lane >> 3) & 1) + 8 * (lane >> 4) - 1; return (r0 ^ ((r0 >> 3) & 3)) * 16; }
DEV u32 clk() { u32 r; asm volatile("mov.u32 %0,%%clock;" : "=r"(r)::"memory"); return r; }
DEV void wait_clk(u32 t, int d) { while ((int)(clk() - t) < d); }
DEV float ex2(float x) { float r; asm("ex2.approx.ftz.f32 %0,%1;" : "=f"(r) : "f"(x)); return r; }
DEV float rcpf(float x) { float r; asm("rcp.approx.ftz.f32 %0,%1;" : "=f"(r) : "f"(x)); return r; }
DEV float2 cmul(float2 a, float2 b) { return make_float2(fmaf(a.x, b.x, -a.y * b.y), fmaf(a.x, b.y, a.y * b.x)); }
DEV float2 csq(float2 a) { return make_float2(fmaf(a.x, a.x, -a.y * a.y), (a.x + a.x) * a.y); }
DEV float2 cexp(float lr2, float th) {
  const float m = ex2(lr2);
  return make_float2(m * __cosf(th), m * __sinf(th));
}
DEV float silu_f(float v) { return v * rcpf(1.f + ex2(-1.4426950408889634f * v)); }
constexpr u32 B2P64 = 0x5F805F80u, B2M64 = 0x1F801F80u, BONE = 0x3F803F80u;
constexpr u32 MODJ = 18 * 128;
DEV float sqrta(float x) { float r; asm("sqrt.approx.ftz.f32 %0,%1;" : "=f"(r) : "f"(x)); return r; }
DEV u32 fu(float x) { return __float_as_uint(x); }
DEV float uf(u32 x) { return __uint_as_float(x); }
DEV void mma_hf_o(float (&d)[4], const float (&c)[4], const u32 (&a)[4], u32 b0, u32 b1) {
  asm("mma.sync.aligned.m16n8k16.row.col.f32.f16.f16.f32 {%0,%1,%2,%3},{%4,%5,%6,%7},{%8,%9},{%10,%11,%12,%13};"
      : "=f"(d[0]), "=f"(d[1]), "=f"(d[2]), "=f"(d[3]) : "r"(a[0]), "r"(a[1]), "r"(a[2]), "r"(a[3]), "r"(b0), "r"(b1), "f"(c[0]), "f"(c[1]), "f"(c[2]), "f"(c[3]));
}

DEV void mma_hf_t(float (&c)[4], const u32 (&a)[4], u32 b0, u32 b1) { mma_hf(c, a[0], a[1], a[2], a[3], b0, b1); }
DEV void cpa16(u32 dst, const void* src) { asm volatile("cp.async.cg.shared.global [%0],[%1],16;" ::"r"(dst), "l"(src) : "memory"); }
DEV void tm_pre(const CUtensorMap* tm) { asm volatile("prefetch.tensormap [%0];" ::"l"((uint64_t)tm) : "memory"); }
#define PROXY_FENCE() asm volatile("fence.proxy.async.shared::cta;" ::: "memory")
struct Prm {
  const char *la, *ai, *cr, *ci, *ldt;
  u32 zero;
  const char *x, *c;
  char* gs;
  const char *dsk, *wr, *wg, *wu, *wd;
  char* out;
};
constexpr float LOG2E = 1.4426950408889634f, F2P64 = 1.8446744073709552e19f, F2M64 = 5.421010862427522e-20f;

template <int S> DEV void y_store(float c0, float c1, float c2, float c3, u32 F, u32 pml, char* yp) {
  str32(yp, bmul(pk_bf(c0, c2), F) | pml);
  str32(yp + S, bmul(pk_bf(c1, c3), F) | pml);
}
DEV void merge4(u32 (&h)[8], uint4 a, uint4 b) {
  const u32 e1 = min(a.x, b.x), e2 = max(a.z, b.z), o1 = min(a.y, b.y), o2 = max(a.w, b.w), o0 = max(a.y, b.y), e3 = min(a.z, b.z);
  const u32 f1 = max(e1, e2), f2 = min(e1, e2), p1 = max(o1, o2), p2 = min(o1, o2);
  h[0] = max(a.x, b.x); h[1] = max(o0, f1); h[2] = min(o0, f1); h[3] = max(p1, f2); h[4] = min(p1, f2); h[5] = max(p2, e3); h[6] = min(p2, e3); h[7] = min(a.w, b.w);
}
DEV void top8(u32 (&a)[8], uint4 l, uint4 m) {
  u32 b[8];
  merge4(b, l, m);
#pragma unroll
  for (int i = 0; i < 8; i++) a[i] = max(a[i], b[7 - i]);
#pragma unroll
  for (int s = 4; s; s >>= 1)
#pragma unroll
    for (int i = 0; i < 8; i++) if (!(i & s)) { const u32 x = a[i], y = a[i + s]; a[i] = max(x, y); a[i + s] = min(x, y); }
}
#define POLL(load, cond_bad, code) { int it_ = 0; do { load; } while (__any_sync(~0u, (cond_bad)) & (++it_ <= SPIN)); if (it_ > SPIN) { ERRF(code); } TSN(code, it_); }
#define POLLW(load, cond_bad, code) { int it_ = 0; while (__any_sync(~0u, (cond_bad))) { if (++it_ > SPIN) { ERRF(code); break; } load; } TSN(code, it_); }

#define DOWN(E) if (tid == 288 && b < 108) { const u32 c0 = 64 * (b % 9), c2 = 4 * (b / 9); \
    if (!D0C && E == 1) { mb_expect(SM_MB + 24, 49152); tma3d(SM_TAP, tm_down, SM_MB + 24, c0, c2); } \
    if (DE1 == E) tma3d(SM_WD, tm_down, SM_MB + 24, c0, c2 + 1); \
    if (DE2 == E) tma3d(SM_WD + 12288, tm_down, SM_MB + 24, c0, c2 + 2); \
    if (DE3 == E) tma3d(SM_WD + 24576, tm_down, SM_MB + 24, c0, c2 + 3); }
#define OUTR() { const u32 tl = 4 * ((lane >> 1) & 1) + ((lane >> 2) & 3) + 8 * (lane & 1); \
    bulk_out<1152>(p.out + (b * BLK + tl * 1152), SM_XST + ((lane & 2) + 4 * (lane & 1) + ((lane >> 2) & 1) + (lane & 8)) * ROW); \
    asm volatile("cp.async.bulk.commit_group;" ::: "memory"); }
struct FA { u32 tid, ba, ra, sa; char *ad, *as; };
DEV FA ffn_addr(const Prm& p, u32 tid, u32 b) {
  const u32 w = tid >> 5, lane = tid & 31, kq = w & 3, tg = w >> 2, t = 7 - w;
  FA f = {tid, SM_XS + (lane & 7) * ROW + (18 * kq + (lane >> 3)) * 16, SM_RED + (8 * tg + kq) * 512 + lane * 16, SM_RED + t * 2048 + lane * 16,
          p.gs + (G_ACT + (t < 4 ? 4 * b + t : 512 + (b >> 1)) * 128 + lane * 4), p.gs + (G_ACT + (b / 9) * 6144 + tid * 16)};
  if (AW & 2) { pin(tid >> 16, f.ba, f.ra, f.sa, tid); pin2(tid >> 16, f.ad, f.as); }
  return f;
}
DEV void ffn_tail(const Prm& p, const CUtensorMap* tm_down, uint4 (&A)[24], const FA f, const u32 b, const u32 par, const u32 okl) {
  const u32 tid = f.tid, w = tid >> 5, lane = tid & 31, g = lane >> 2, q = lane & 3, tg = w >> 2, zr = tid >> 16;
  const u32 rho = b & 1, pm = par ? TAGM : 0, kt = par * 3, ba = f.ba, ra = f.ra;
  char* const gs = p.gs;
  char *const ad = f.ad, *const as = f.as;
  __syncthreads();
  TS(25);
  if (!(AW & 4)) DOWN(5);
  {
    float c0[2][4] = {}, c1[2][4] = {};
    uint4 bb[5];
#pragma unroll
    for (int s = 0; s < 5; s++) bb[s] = ldsm4(ba + s * 64);
    if (AW & 4) DOWN(5);
#pragma unroll
    for (int s = 0; s < 9; s++) mma_bf(c0[s & 1], A[s].x, A[s].y, A[s].z, A[s].w, s & 1 ? bb[s >> 1].z : bb[s >> 1].x, s & 1 ? bb[s >> 1].w : bb[s >> 1].y);
    if (tg < 2) {
#pragma unroll
      for (int s = 0; s < 9; s++) mma_bf(c1[s & 1], A[9 + s].x, A[9 + s].y, A[9 + s].z, A[9 + s].w, s & 1 ? bb[s >> 1].z : bb[s >> 1].x, s & 1 ? bb[s >> 1].w : bb[s >> 1].y);
      sts128(ra + 2048, fu(c1[0][0] + c1[1][0]), fu(c1[0][1] + c1[1][1]), fu(c1[0][2] + c1[1][2]), fu(c1[0][3] + c1[1][3]));
    }
    sts128(ra, fu(c0[0][0] + c0[1][0]), fu(c0[0][1] + c0[1][1]), fu(c0[0][2] + c0[1][2]), fu(c0[0][3] + c0[1][3]));
  }
  TS(39);
  __syncthreads();
  const u32 tr = clk();
  if (OUTB == 6 && w == 10 && okl < lds32(SM_SLOT + 28)) OUTR();
  if (w - 3 - rho < 5 - rho) {
    float s[4];
    const uint4 u0 = lds128(f.sa), u1 = lds128(f.sa + 512), u2 = lds128(f.sa + 1024), u3 = lds128(f.sa + 1536);
    s[0] = (uf(u0.x) + uf(u1.x)) + (uf(u2.x) + uf(u3.x)); s[1] = (uf(u0.y) + uf(u1.y)) + (uf(u2.y) + uf(u3.y));
    s[2] = (uf(u0.z) + uf(u1.z)) + (uf(u2.z) + uf(u3.z)); s[3] = (uf(u0.w) + uf(u1.w)) + (uf(u2.w) + uf(u3.w));
    const u32 sg = pk_bf(silu_f(rbf(s[0])), silu_f(rbf(s[1])));
    const u32 act = movm(bmul(bmul(sg, pk_bf(s[2], s[3])), B2M64));
    str32(ad, act | (q ? 0 : pm));
  }
  TS(26);
  const bool fin = w == 8 && b < 72;
  u32 kg;
  uint4 xt;
  const char* xs;
  if (fin) { kg = lds32(SM_SLOT + 4 * g); xs = rowa(gs + (G_Y + 16 * b), kg); xt = ldr128(xs); }
  if (b < 108) {
    uint4 a;
    if (AD) a.x = INVAL; else a = ldr128(as);
    if (AD && w >= 4) wait_clk(tr, AD);
    char* const dst = gs + (G_PART + b * 2048 + w * 512 + lane * 8);
    if (w < 4) {
      const u32 aa = SM_WD + (8 * (lane >> 4) + (lane & 7)) * 128 + (((2 * w + ((lane >> 3) & 1)) ^ (lane & 7)) << 4);
      mb_wait(SM_MB + 24);
#pragma unroll
      for (int s = 0; s < 24; s++) A[s] = ldsm4t(aa + (s < 6 ? SM_TAP - SM_WD : -12288) + s * 2048);
      if (AW & 2) pin2(zr, dst, as);
    }
    TS(28);
    POLLW(rld128<TAGM>(a, as, pm), (a.x ^ pm) & TAGM, 9);
    sts128(SM_AC + tid * 16, a.x, a.y, a.z, a.w); sts32(SM_AC + tid * 16, a.x & ~TAGM);
    TS(27);
    if (w < 4) {
      bsync(8, 384);
      float c[4][4] = {};
#pragma unroll
      for (int s = 0; s < 12; s++) {
        const uint4 bb = ldsm4(SM_AC + lane * 16 + s * 512);
        mma_bf(c[2 * (s & 1)], A[2 * s].x, A[2 * s].y, A[2 * s].z, A[2 * s].w, bb.x, bb.y);
        mma_bf(c[2 * (s & 1) + 1], A[2 * s + 1].x, A[2 * s + 1].y, A[2 * s + 1].z, A[2 * s + 1].w, bb.z, bb.w);
      }
      u32 o[4];
#pragma unroll
      for (int i = 0; i < 4; i++) o[i] = fu(((c[0][i] + c[1][i]) + (c[2][i] + c[3][i])) * F2P64);
      str64(dst, (o[0] & ~3u) | kt, o[1]); str64(dst + 256, (o[2] & ~3u) | kt, o[3]);
      TS(29);
    } else barrive(8, 384);
  }
  if (OUTB == 7 && w == 10 && okl < lds32(SM_SLOT + 28)) OUTR();
  if (fin) {
    const u32 ta = clk();
    const char* src = gs + (G_PART + (b >> 3) * 2048 + (b & 7) * 256 + lane * 8);
    const u32 gw = lds32(SM_MODS + 5760 + 16 * b + 4 * q);
    const u32 hw = lds32(SM_XS + g * ROW + b * 16 + q * 4);
    const float sgm = rcpf(1.f + ex2(-LOG2E * bhi(kg ^ (~((int)kg >> 31) | 0x80000000))));
    char* const dst = (char*)rowa(p.out + (16 * b + 4 * q), kg);
    POLLW(rld128<TAGM>(xt, xs, TAGR), (xt.x ^ TAGR) & TAGM, 10);
    const u32 x1w = (q & 2) ? ((q & 1) ? xt.w : xt.z) : ((q & 1) ? xt.y : bmul(xt.x ^ TAGR, B2P64));
    const u32 sg2 = pk_bf(sgm, sgm);
    pin(zr, x1w, gw, hw, sg2); pin2(zr, dst, src);
    uint64_t v[12];
#pragma unroll
    for (int j = 0; j < 12; j++) v[j] = 1;
    float s0, s1;
    if (PD) wait_clk(ta, PD);
    TS(13);
#define VL(j) (u32)v[j]
#define VS(j, s) ((uf((u32)(v[j] >> s)) + uf((u32)(v[j + 1] >> s))) + (uf((u32)(v[j + 2] >> s)) + uf((u32)(v[j + 3] >> s))))
    POLL({ _Pragma("unroll") for (int j = 0; j < 12; j++) rld64<3>(v[j], src + j * 9 * 2048, kt);
           s0 = VS(0, 0) + VS(4, 0) + VS(8, 0); s1 = VS(0, 32) + VS(4, 32) + VS(8, 32);
           asm volatile("" : "+f"(s0), "+f"(s1)); TSRND(); },
         lop3<0xa8>(lop3<0xfe>(ne3(VL(0), VL(1), kt), ne3(VL(2), VL(3), kt), ne3(VL(4), VL(5), kt)),
                    lop3<0xfe>(ne3(VL(6), VL(7), kt), ne3(VL(8), VL(9), kt), ne3(VL(10), VL(11), kt)), 3), 11);
    const u32 y = movm(pk_bf(s0, s1));
    asm volatile("st.global.u32 [%0],%1;" ::"l"(dst), "r"(badd(x1w, bmul(gw, badd(hw, bmul(y, sg2))))) : "memory");
    if (b == 0 && lane == 0) str32(gs + G_EP, par);
    TS(30); TSE();
  }
  if (w == 10) asm volatile("cp.async.bulk.wait_group.read 0;" ::: "memory");
}

DEV u32 y_off(u32 tid, u32 b) { return G_Y + (16 * (tid >> 5) + 8 * ((tid >> 1) & 1) + ((tid >> 2) & 4)) * BLK + b * 128 + ((tid >> 2) & 3) * 32 + (tid & 1) * 16; }
DEV void post_conv(const Prm& p, const CUtensorMap* tm_down, const u32 tid, const u32 b) {
  const u32 w = tid >> 5, lane = tid & 31;
  const u32 g = lane >> 2, q = lane & 3, e = g >> 2, h = (g >> 1) & 1, hi = g & 1;
  const u32 pm = lds32(SM_THR + 4), par = pm >> 30;
  char* const gs = p.gs;
  const u32 cho = 128 * w + 64 * e + 16 * q;
  u32 x1[4][4], h2[4][4], key[4], lt;
  char* const rowp = gs + (b * BLK + (4 * h + 8 * hi) * 1152 + cho);
  u32 okl = ~0u;
  FA fa;
  uint4 A[24];
#define AROW(t) const u32 arow = 144 * ((t >> 5) & 3) + ((t >> 1) & 8) + (t & 7), ab = (t & 8) ? SM_UP : SM_GATE;
#define AFRAG9() { _Pragma("unroll") for (int s = 0; s < 9; s++) A[s] = ldsm4t(ab + SLV + arow * 16 + s * 256); }
#define AFRAG18() { const u32 t3 = opq(tid); AROW(t3); if (t3 < 256) { const u32 aa = ab + arow * 64 + ((((t3 >> 6) & 2) ^ ((t3 & 7) >> 1)) << 4); \
      _Pragma("unroll") for (int s = 0; s < 9; s++) { A[s] = ldsm4t(aa + s * 1024); A[9 + s] = ldsm4t((aa ^ 16) + s * 1024); } } else AFRAG9(); }
  if (w < 9) {
    const u32 yc = 8 * (q >> 1) + 2 * (g >> 1), y1 = w < 8 ? BLK : 4 * BLK, y2 = 2 * y1;
    const char* ysrc = gs + (w < 8 ? y_off(tid, b) : G_Y + (q & 1) * 16 + (8 * yc + 2 * hi + ((b >> 4) & 1)) * BLK + 16384 + ((b >> 5) * 16 + (b & 15)) * 32);
    const char* const ys[4] = {ysrc, ysrc + y1, ysrc + y2, ysrc + (y1 + y2)};
    u32 tc = clk();
    uint4 yv[4];
#pragma unroll
    for (int v = 0; v < 4; v++) yv[v].x = INVAL;
    if (w < 4 && b < YL) {
#pragma unroll
      for (int v = 0; v < 4; v++) yv[v] = ldr128(ys[v]);
    }
    if (w == 8) { bsync(7, 160); tc = clk(); }
    const u32 ma = SM_MODS + cho, xa = SM_XST + (2 * h + 4 * hi) * ROW + cho;
    const uint4 sa = lds128(ma), ca = lds128(ma + 1152), ga = lds128(ma + 2304);
    const uint4 rb = lds128((g & 2) ? SM_ONE + 16 * hi : (ma ^ 64) + 8064 + 1152 * hi);
    const u32 saw[4] = {sa.x, sa.y, sa.z, sa.w}, caw[4] = {ca.x, ca.y, ca.z, ca.w}, gaw[4] = {ga.x, ga.y, ga.z, ga.w};
#pragma unroll
    for (int k = 0; k < 4; k++) {
      const uint2 st = lds64(SM_ST + 16 * (2 * h + 4 * hi + (k & 1) + 8 * (k >> 1)));
      const uint4 xv = lds128(xa + ((k & 1) + 8 * (k >> 1)) * ROW);
      x1[k][0] = xv.x; x1[k][1] = xv.y; x1[k][2] = xv.z; x1[k][3] = xv.w;
#pragma unroll
      for (int v = 0; v < 4; v++) x1[k][v] = badd(x1[k][v], bfma(bmul(badd(x1[k][v], st.x), st.y), caw[v], saw[v]));
    }
    const bool own = (q >> 1) == e;
    const u32 spw = SM_SP + (2 * w + e) * 320 + (g & 3) * 16 + (own ? ((q & 1) == h ? 4 : 12) : 8 - 8 * (q & 1));
    if (w >= 4) {
      if (b < (w < 8 ? YE : Y8)) {
        if (W8D && w == 8 && b >= 64) wait_clk(tc, W8D);
        TS(18);
#pragma unroll
        for (int v = 0; v < 4; v++) yv[v] = ldr128(ys[v]);
      }
      bsync(12, N12);
      tc = clk();
    }
    if (b >= YL) wait_clk(tc, YD);
    TS(13);
    POLLW(_Pragma("unroll") for (int v = 0; v < 4; v++) if ((yv[v].x ^ pm) & TAGM) yv[v] = ldr128(ys[v]),
          ((yv[0].x ^ pm) | (yv[1].x ^ pm) | (yv[2].x ^ pm) | (yv[3].x ^ pm)) & TAGM, 5);
    TS(19);
    if (w < 4) asm volatile("setmaxnreg.dec.sync.aligned.u32 168;");
#pragma unroll
    for (int k = 0; k < 4; k += 2) {
      float X[4] = {}, Y[4] = {}, R[4] = {};
#pragma unroll
      for (int v = 0; v < 4; v++) {
        const u32 y0 = k ? yv[v].z : yv[v].x & ~TAGM, y1 = k ? yv[v].w : yv[v].y;
        x1[k][v] = bfma(movm(y0), gaw[v], x1[k][v]);
        x1[k + 1][v] = bfma(movm(y1), gaw[v], x1[k + 1][v]);
        mma8_bf(X, x1[k][v], x1[k + 1][v], x1[k][v]); mma8_bf(Y, x1[k][v], x1[k + 1][v], x1[k + 1][v]);
        if (v & 1) mma_bf(R, x1[k][v - 1], x1[k + 1][v - 1], x1[k][v], x1[k + 1][v], v & 2 ? rb.z : rb.x, v & 2 ? rb.w : rb.y);
      }
      sts32(spw + k * 64, fu(own ? (hi ? X[1] : X[0]) : R[0] + R[1]));
      sts32(spw + k * 64 + 64, fu(own ? (hi ? Y[3] : Y[2]) : R[2] + R[3]));
    }
    barrive(1, N1);
    TS(36);
    if (AFP) { asm volatile("setmaxnreg.inc.sync.aligned.u32 168;"); mb_wait(SM_MB + 8); mb_wait(SM_MB + 16); }
    const uint4 sb = lds128(ma + 3456), cb = lds128(ma + 4608), gb = lds128(ma + 5760);
    const u32 sbw[4] = {sb.x, sb.y, sb.z, sb.w}, cbw[4] = {cb.x, cb.y, cb.z, cb.w}, gbw[4] = {gb.x, gb.y, gb.z, gb.w};
    const u32 t3 = opq(tid), zr = t3 >> 16;
    AROW(t3);
    const u32 aa = ab + arow * 64 + ((((t3 >> 6) & 2) ^ ((t3 & 7) >> 1)) << 4), sta = SM_ST2 + 16 * (g & 3);
    if (AFP) pin(zr, aa, sta, xa);
    bsync(2, 320);
    TS(37);
    uint4 st[4];
#pragma unroll
    for (int k = 0; k < 4; k++) st[k] = lds128(sta + 64 * k);
    lt = lds32(SM_THR);
#define AFL() { _Pragma("unroll") for (int s = 0; s < 9; s++) { A[s] = ldsm4t(aa + s * 1024); A[9 + s] = ldsm4t((aa ^ 16) + s * 1024); } }
    if (AFP && (AFM >> w & 1)) { if (w < 8) AFL() else AFRAG9(); }
#pragma unroll
    for (int k = 0; k < 4; k++) {
      key[k] = st[k].w;
      u32 o[4];
#pragma unroll
      for (int v = 0; v < 4; v++) {
        const u32 d = badd(x1[k][v], st[k].x), z = bfma(d, st[k].y, bmul(d, st[k].z));
        h2[k][v] = FH ? bfma(z, cbw[v], sbw[v]) : badd(bmul(z, cbw[v]), sbw[v]);
        o[v] = FO ? bfma(gbw[v], h2[k][v], x1[k][v]) : badd(x1[k][v], bmul(gbw[v], h2[k][v]));
      }
      h2[k][0] = bmul(h2[k][0], B2M64) | TAGR;
      if (key[k] >= lt) str128(rowp + k * 1152, h2[k][0], h2[k][1], h2[k][2], h2[k][3]);
      sts128(xa + ((k & 1) + 8 * (k >> 1)) * ROW, o[0], o[1], o[2], o[3]);
    }
    barrive(3, 320);
    TS(21);
    if (!AFP) { asm volatile("setmaxnreg.inc.sync.aligned.u32 168;"); mb_wait(SM_MB + 8); mb_wait(SM_MB + 16); AFRAG18(); }
    else if (!(AFM >> w & 1)) { if (w < 8) AFL() else AFRAG9(); }
    TS(22);
    const u32 rr = tid * 57 >> 12, rc = tid * 16 - rr * 1152, sl = SM_SLOT + 8 * rr;
    const char* const rb_ = gs + rc;
    const u32 km = max(max(key[0], key[1]), max(key[2], key[3])), xd = SM_XS + rr * (2 * ROW) + rc;
    if (RW & 2) { pin(tid >> 16, sl, km, xd); pin2(tid >> 16, rb_, rowp); }
    fa = ffn_addr(p, tid | p.zero, b);
    bsync(6, 320);
    TS(24);
    const uint2 sk = lds64(sl);
    const char *r0 = rowa(rb_, sk.x), *r1 = rowa(rb_, sk.y);
    uint4 rv[2] = {ldr128(r0), ldr128(r1)};
    barrive(15, 320);
    const u32 g8 = lds32(SM_SLOT + 28);
    if (__any_sync(~0u, km >= g8 && lt > g8)) {
#pragma unroll
      for (int k = 0; k < 4; k++) if (key[k] >= g8 && key[k] < lt) str128(rowp + k * 1152, h2[k][0], h2[k][1], h2[k][2], h2[k][3]);
    }
    bsync(5, 320);
    const uint2 sf = lds64(sl);
    const u32 f8 = lds32(SM_SLOT + 28);
    if (__any_sync(~0u, km >= f8)) {
#pragma unroll
      for (int k = 0; k < 4; k++) if (key[k] >= f8) str128(rowp + (G_Y + k * 1152), bmul(x1[k][0], B2M64) | TAGR, x1[k][1], x1[k][2], x1[k][3]);
    }
    if (__any_sync(~0u, sf.x != sk.x || sf.y != sk.y)) {
      r0 = rowa(rb_, sf.x); r1 = rowa(rb_, sf.y);
      rv[0].x = rv[1].x = INVAL;
    }
    POLLW({ rld128<TAGM>(rv[0], r0, TAGR); rld128<TAGM>(rv[1], r1, TAGR); }, ne3(rv[0].x, rv[1].x, TAGR) & TAGM, 8);
    TS(38);
#pragma unroll
    for (int j = 0; j < 2; j++) sts128(xd + j * ROW, bmul(rv[j].x ^ TAGR, B2P64), rv[j].y, rv[j].z, rv[j].w);
  } else {
    u32 ok, lr;
    if (w == 10) {
      uint2 rc = lds64(SM_RC + 8 * min(lane, 17u));
      float r1 = lane < 18 ? uf(rc.x) : 0.f, r2 = lane < 18 ? uf(rc.y) : 0.f;
#pragma unroll 1
      for (int o = 16; o; o >>= 1) { r1 += __shfl_xor_sync(~0u, r1, o); r2 += __shfl_xor_sync(~0u, r2, o); }
      const u32 tl = 4 * ((lane >> 1) & 1) + ((lane >> 2) & 3) + 8 * (lane & 1), kl = (2047 - 16 * b - tl) << 2 | par * 3;
      char* const kp = gs + (G_KEY + b * KST);
      const u32 spr = SM_SP + (lane >> 4) * 9 * 320 + (lane & 15) * 16;
      TS(31);
      bsync(1, N1);
      float S1 = 0.f, S2 = 0.f, S3 = 0.f;
#pragma unroll
      for (int i = 0; i < 9; i++) { uint4 t = lds128(spr + i * 320); S1 += uf(t.x); S2 += uf(t.y); S3 += uf(t.z); }
      S1 += __shfl_xor_sync(~0u, S1, 16); S2 += __shfl_xor_sync(~0u, S2, 16); S3 += __shfl_xor_sync(~0u, S3, 16);
      const float mu = S1 * (1.f / 576.f), var = fmaxf(fmaf(-mu, mu, S2 * (1.f / 576.f)), 0.f);
      const float m = rbf(mu), rs = rcpf(rbf(sqrta(rbf(rbf(var) + 1e-5f))));
      const u32 rb = pk_bf(0.f, fmaf(fmaf(-m, r1, S3), rs, r2) + 0.f);
      ok = ((rb ^ (((int)rb >> 31) | 0x80000000)) & 0xffff0000u) | kl;
      const float rh = rbf(rs);
      sts32(SM_KEY + 4 * (lane & 15), ok);
      sts128(SM_ST2 + 16 * (lane & 15), pk_bf(-m, -m), pk_bf(rh, rh), pk_bf(rs - rh, rs - rh), ok);
      __syncwarp();
      const uint4 o0 = lds128(SM_KEY + 2 * (lane & 16)), o1 = lds128(SM_KEY + 2 * (lane & 16) + 16);
      lr = (o0.x > ok) + (o0.y > ok) + (o0.z > ok) + (o0.w > ok) + (o1.x > ok) + (o1.y > ok) + (o1.z > ok) + (o1.w > ok);
      lr += __shfl_xor_sync(~0u, lr, 16);
      if (lane < 16 && lr < 8) str32(kp + 4 * lr, ok);
      if (lr == (b < NB8 ? 7 : NEARLY - 1)) sts32(SM_THR, ok);
      barrive(2, 320);
      if (!KA) barrive(4, 64);
      TS(20);
    } else if (w == 9) {
      if (DB1) bsync(1, N1); else { bsync(12, N12); wait_clk(clk(), DD); }
      const u32 tb = clk();
      PROXY_FENCE();
      DOWN(1);
      if (KW) {
        __syncwarp();
        const char* ks = gs + (G_KEY + (lane >> 1) * KST + (lane & 1) * 16);
        const u32 kt = par * 3;
        uint4 L[4];
        u32 H[8];
#define KBAD(j) ((L[j].x ^ kt) & 3)
#define KLD(j) L[j] = ldr128(ks + j * 16 * KST)
#pragma unroll
        for (int j = 0; j < 4; j++) L[j].x = INVAL;
        wait_clk(tb, b < KE ? KW : b < YL ? KWB : KW1);
        POLL({ _Pragma("unroll") for (int j = 0; j < 4; j++) if (KBAD(j)) KLD(j); }, KBAD(0) | KBAD(1) | KBAD(2) | KBAD(3), 12);
        merge4(H, L[0], L[1]); top8(H, L[2], L[3]);
        sts128(SM_RED + lane * 16, H[0], H[1], H[2], H[3]); sts128(SM_RED + 512 + lane * 16, H[4], H[5], H[6], H[7]);
        barrive(13, 64);
        TS(34);
      }
    } else {
      const char* ks = gs + (G_KEY + (lane >> 1) * KST + (lane & 1) * 16);
      const u32 kt = par * 3;
      uint4 L[8];
      u32 H[8];
#define KBAD(j) ((L[j].x ^ kt) & 3)
#define KLD(j) L[j] = ldr128(ks + j * 16 * KST)
#pragma unroll
      for (int j = 0; j < 8; j++) L[j].x = INVAL;
      if (KA) bsync(1, N1); else bsync(4, 64);
      wait_clk(clk(), KA + (b < KE ? KD : b < YL ? KDB : KD1));
      TS(34);
      if (KW) {
        KLD(4); KLD(5); KLD(6); KLD(7);
        bsync(13, 64);
        const uint4 u = lds128(SM_RED + lane * 16), v = lds128(SM_RED + 512 + lane * 16);
#pragma unroll 1
        for (u32 it = SPIN;; it--) {
          const u32 mk = min(it, 3u);
          H[0] = u.x; H[1] = u.y; H[2] = u.z; H[3] = u.w; H[4] = v.x; H[5] = v.y; H[6] = v.z; H[7] = v.w;
          top8(H, L[4], L[5]);
          asm volatile("" : "+r"(H[0]), "+r"(H[1]), "+r"(H[2]), "+r"(H[3]), "+r"(H[4]), "+r"(H[5]), "+r"(H[6]), "+r"(H[7]));
          if (!__any_sync(~0u, ne3(L[4].x, L[5].x, kt) & mk)) { if (!it) { ERRF(6); } TSN(6, SPIN - it); break; }
#pragma unroll
          for (int j = 4; j < 8; j++) if (KBAD(j)) KLD(j);
        }
      } else {
      POLL({ _Pragma("unroll") for (int j = 0; j < 8; j++) if (KBAD(j)) KLD(j);
             merge4(H, L[0], L[1]); top8(H, L[2], L[3]);
             asm volatile("" : "+r"(H[0]), "+r"(H[1]), "+r"(H[2]), "+r"(H[3]), "+r"(H[4]), "+r"(H[5]), "+r"(H[6]), "+r"(H[7])); TS(32); },
           KBAD(0) | KBAD(1) | KBAD(2) | KBAD(3) | KBAD(4) | KBAD(5), 6);
      top8(H, L[4], L[5]);
      }
      TS(35);
#pragma unroll 1
      for (u32 pass = p.zero;; pass++) {
        u32 G[8], m[8];
#pragma unroll
        for (int i = 0; i < 8; i++) G[i] = H[i];
#pragma unroll
        for (int r = 0; r < 8; r++) {
          const u32 h0 = G[0];
          m[r] = __reduce_max_sync(~0u, h0);
          if (r == 0) { if (KBAD(6)) KLD(6); if (KBAD(7)) KLD(7); }
          if (r < 7) asm("{.reg .u32 t; sub.u32 t,%1,%2; min.u32 t,t,1; mad.lo.u32 %0,t,%3,%4;}" : "=r"(G[0]) : "r"(m[r]), "r"(h0), "r"(h0 - G[1]), "r"(G[1]));
#pragma unroll
          for (int i = 1; i < 7 - r; i++) G[i] = h0 == m[r] ? G[i + 1] : G[i];
          if ((r & 3) == 3) sts128(SM_SLOT + 4 * r - 12, m[r - 3], m[r - 2], m[r - 1], m[r]);
        }
        asm volatile("{.reg .pred p; setp.eq.u32 p,%0,0; @p bar.arrive 6,320;}" ::"r"(pass) : "memory");
        if (pass) break;
        TS(23);
        POLLW({ if (KBAD(6)) KLD(6); if (KBAD(7)) KLD(7); }, KBAD(6) | KBAD(7), 7);
        if (!__any_sync(~0u, max(L[6].x, L[7].x) > m[7])) break;
        top8(H, L[6], L[7]);
      }
      barrive(5, 320);
      TS(33);
    }
    asm volatile("setmaxnreg.inc.sync.aligned.u32 168;");
    mb_wait(SM_MB + 8); mb_wait(SM_MB + 16);
    AROW(tid);
    AFRAG9();
    fa = ffn_addr(p, tid | p.zero, b);
    TS(22);
    if (w == 10) {
      bsync(3, 320);
      PROXY_FENCE();
      if (lane < 16 && lr >= 8) OUTR();
      if (lane < 16 && lr < 8) okl = ok;
    } else if (w == 9) {
      bsync(15, 320);
      DOWN(4);
      TS(13);
    }
  }
  ffn_tail(p, tm_down, A, fa, b, par, okl);
}

__global__ void __launch_bounds__(384, 1)
fused_kernel(const Prm p, const __grid_constant__ CUtensorMap tm_mod, const __grid_constant__ CUtensorMap tm_gate, const __grid_constant__ CUtensorMap tm_gs,
             const __grid_constant__ CUtensorMap tm_up, const __grid_constant__ CUtensorMap tm_us, const __grid_constant__ CUtensorMap tm_down) {
  extern __shared__ __align__(1024) unsigned char smem[];
  u32 la, ai, ldt; uint2 cr, ci;
  {
    const u32 t = threadIdx.x, d = t < 256 ? chan(blockIdx.x, t >> 5) : 512 + (blockIdx.x >> 1), o = d * 256 + 8 * (t & 31), o4 = o + ((t < 256 ? t >> 5 : t >> 3) & 4);
    asm volatile("{.reg .pred p; .reg .u16 h; setp.ne.u32 p,%7,0; @p ld.global.nc.u32 %0,[%8]; @p ld.global.nc.u32 %1,[%9]; @p ld.global.nc.v2.u32 {%2,%3},[%10];"
                 "@p ld.global.nc.v2.u32 {%4,%5},[%11]; @p ld.global.nc.u16 h,[%12]; cvt.u32.u16 %6,h;}"
                 : "=r"(la), "=r"(ai), "=r"(cr.x), "=r"(cr.y), "=r"(ci.x), "=r"(ci.y), "=r"(ldt)
                 : "r"(0x6ffu >> (t >> 5) & 1), "l"(p.la + o4), "l"(p.ai + o4), "l"(p.cr + o), "l"(p.ci + o), "l"(p.ldt + 2 * d));
  }
  const u32 t0 = clk();
  const u32 tid = __shfl_sync(~0u, threadIdx.x, threadIdx.x & 31), b = blockIdx.x + p.zero;
  const u32 w = tid >> 5, lane = tid & 31;
  const u32 g = lane >> 2, q = lane & 3, hi = g & 1;
  const u32 rho = b & 1, Ps = 512 + (b >> 1);
  char* const gs = p.gs;
  TS0();
  const bool kw = w != 8 && w != 11;
  const u32 ksig = w < 8 ? (w & 3) : 4, khf = w < 8 ? (w >> 2) : (w & 1);
  if (!kw) {
    if (tid == 352) {
#pragma unroll
      for (int i = 0; i < 5; i++) mb_init(SM_MB + 8 * i, i < 4 ? 1 : 64);
      asm volatile("fence.mbarrier_init.release.cluster;" ::: "memory");
      tm_pre(&tm_mod);
    }
    const char* cp = p.c + (576 * (w & 1) + 24 * min(lane, 23u));
    const uint2 c0 = ldg64(cp);
    la = c0.x; ai = c0.y; cr = ldg64(cp + 8); ci = ldg64(cp + 16);
  }
  const u32 zr = tid >> 16;
  const u32 epv = ldr32(gs + (G_EP + zr));
  const u32 tp = SM_TAP + ksig * TAPS;
  if (kw && !khf) {
#pragma unroll 1
    for (u32 i = lane * 16; i < TAPS; i += 512) sts128(tp + i, 0, 0, 0, 0);
  }
  if (tid < 128) sts128(SM_INV + 16 * tid, INVAL, 0, 1, 0);
  if (tid >= 252) str128(gs + (tid >= 380 ? G_MOD + b * 128 + q * 16 : b * BLK + 16384 - 252 * 16 + tid * 16), INVAL, 0, 1, 0);
  if (tid == 352 && b < 36) { while (clk() - t0 < DMOD); mb_expect(SM_MB, 36864); tma3d(SM_UP, &tm_mod, SM_MB, 32 * b, 0); }
  if (w < 9) {
    while ((int)(clk() - t0) < DX);
    const char* xp = p.x + (b * BLK + (lane >> 3) * 1152 + 128 * w + 16 * (lane & 7));
    const u32 xd = SM_XST + (((lane >> 3) & 1) + 8 * (lane >> 4)) * ROW + 128 * w + 16 * (lane & 7);
#pragma unroll
    for (int i = 0; i < 4; i++) cpa16(xd + 2 * ROW * i, xp + 4608 * i);
  }
  const u32 ktab = w < 8 ? SM_MODS + w * KTAB : SM_ZS + (w - 9) * KTAB;
  float k2048 = 0.f;
  if (kw) {
    u32 mx = __vmaxu2(__vmaxu2(cr.x & 0x7fff7fff, cr.y & 0x7fff7fff), __vmaxu2(ci.x & 0x7fff7fff, ci.y & 0x7fff7fff));
    const u32 E = max(__reduce_max_sync(~0u, max(mx & 0xffff, mx >> 16)) >> 7, 8u);
    TS(1);
    const float dt = rbf(ex2(blo(ldt) * LOG2E)), csc = uf((257 - E) << 23 | (fu(dt) & 0x7fffff));
    sts32(SM_SC + 16 * ksig + 12, fu(uf(fu(dt) & 0x7f800000) * uf((E - 2) << 23)));
    const u32 crw = khf ? cr.y : cr.x, ciw = khf ? ci.y : ci.x;
    float2 C[2], w4[2], w8[2], w16[2], w32[2], w64[2], w128[2], w256[2], w512[2], a1[2], a2[2], a3[2], t0[2], t1[2], s3[2];
#pragma unroll
    for (int m = 0; m < 2; m++) {
      const float lr2 = rbf(ex2((m ? bhi(la) : blo(la)) * LOG2E)) * dt * -LOG2E, th = (m ? bhi(ai) : blo(ai)) * dt;
      C[m] = make_float2((m ? bhi(crw) : blo(crw)) * csc, (m ? bhi(ciw) : blo(ciw)) * csc);
      const float2 w1 = cexp(lr2, th), w2 = csq(w1);
      w64[m] = cexp(64.f * lr2, 64.f * th);
      w4[m] = csq(w2); w8[m] = csq(w4[m]); w16[m] = csq(w8[m]); w32[m] = csq(w16[m]);
      w128[m] = csq(w64[m]); w256[m] = csq(w128[m]); w512[m] = csq(w256[m]);
      const float2 w1024 = csq(w512[m]);
      a1[m] = cmul(C[m], w1); a2[m] = cmul(C[m], w2); a3[m] = cmul(a1[m], w2);
      t0[m] = cmul(C[m], w1024); t1[m] = cmul(t0[m], w128[m]); s3[m] = cmul(w8[m], w16[m]);
      k2048 += fmaf(t0[m].x, w1024.x, -t0[m].y * w1024.y);
    }
    C2 B0[8], B1[8], B2[8], S[8];
    B0[0] = pk2(C); B0[1] = pk2(a1); B0[2] = pk2(a2); B0[3] = pk2(a3);
    const C2 h4 = pk2(w4), h256 = pk2(w256), h512 = pk2(w512);
#pragma unroll
    for (int i = 0; i < 4; i++) B0[4 + i] = cm2(B0[i], h4);
#pragma unroll
    for (int i = 0; i < 4; i++) B1[i] = cm2(B0[2 * i], h256);
    B1[4] = cm2(B0[0], h512); B1[5] = cm2(B0[4], h512);
    B1[6] = cm2(B1[4], h256); B1[7] = cm2(B1[5], h256);
    const u32 ta = ktab + lane * 128, f = ((lane & 3) << 5) | ((lane & 4) << 2);
#pragma unroll
    for (int i = 0; i < 8; i++) sts128(ta + ((i << 4) ^ f), B0[i].re, B0[i].im, B1[i].re, B1[i].im);
    B2[0] = pk2(t0); B2[1] = pk2(t1);
    B2[2] = cm2(B2[0], h256); B2[3] = cm2(B2[1], h256);
#pragma unroll
    for (int i = 0; i < 4; i++) B2[4 + i] = cm2(B2[i], h512);
    S[0] = {0x3C003C00u, 0u}; S[1] = pk2c(w8); S[2] = pk2c(w16); S[3] = pk2c(s3); S[4] = pk2c(w32);
#pragma unroll
    for (int i = 1; i < 4; i++) S[4 + i] = cm2(S[i], S[4]);
#pragma unroll
    for (int i = 0; i < 8; i++) sts128(ta + 4096 + ((i << 4) ^ f), B2[i].re, B2[i].im, S[i].re, S[i].im);
    const C2 m64 = pk2c(w64), m128 = pk2c(w128);
    sts128(ktab + 8192 + lane * 16, m64.re, m64.im, m128.re, m128.im);
    __syncwarp();
  } else {
    u32 sa = SM_SIL + 576 * (w & 1) + 24 * min(lane, 23u);
#pragma unroll 1
    for (int j = 0; j < 6; j++) {
      sts32(sa, pk_bf(silu_f(blo(la)), silu_f(bhi(la))));
      la = ai; ai = cr.x; cr.x = cr.y; cr.y = ci.x; ci.x = ci.y; sa += 4;
    }
    bsync(7, 64);
  }
  TS(2);
  const u32 pm = (__reduce_or_sync(~0u, epv) & 1) ? 0 : TAGM;
  sts32(SM_THR + 4, pm);
  if (w < 9) {
    asm volatile("cp.async.wait_all;" ::: "memory");
    __syncwarp();
    TS(4);
    if (tid == 256 && b >= 36 && b < 108) { mb_expect(SM_MB, 36864); tma3d(SM_UP, &tm_mod, SM_MB, 32 * b, 0); }
    const u32 xa = SM_XST + (lane & 15) * ROW + 128 * w + 16 * (lane >> 4);
    float s[4] = {}, X[2][4] = {}, Y[2][4] = {};
#pragma unroll
    for (int j = 0; j < 4; j++) {
      const uint4 a = ldsm4(xa + 32 * j);
      mma8_bf(X[0], a.x, a.y, a.x); mma8_bf(Y[0], a.x, a.y, a.y);
      mma8_bf(X[1], a.z, a.w, a.z); mma8_bf(Y[1], a.z, a.w, a.w);
      mma_bf(s, a.x, a.y, a.z, a.w, BONE, BONE);
    }
    uint4 t[4];
#pragma unroll
    for (int j = 0; j < 4; j++) t[j] = ldsm4t(xa + 32 * j);
    const float u0 = hi ? X[0][1] + X[1][1] : X[0][0] + X[1][0], u1 = hi ? Y[0][3] + Y[1][3] : Y[0][2] + Y[1][2];
    if (q == g >> 1) sts128(SM_SP + w * 128 + g * 16, fu(s[0]), fu(u0), fu(s[2]), fu(u1));
    bsync(1, 288);
    TS(7);
    const u32 spr = SM_SP + (lane & 7) * 16 + (lane & 8);
    const uint2 t8 = lds64(spr + 1024);
    const float f8 = lane < 16 ? 1.f : 0.f;
    float S1 = uf(t8.x) * f8, S2 = uf(t8.y) * f8;
#pragma unroll
    for (int i = 0; i < 4; i++) { const uint2 u = lds64(spr + (lane & 16) * 32 + i * 128); S1 += uf(u.x); S2 += uf(u.y); }
    S1 += __shfl_xor_sync(~0u, S1, 16); S2 += __shfl_xor_sync(~0u, S2, 16);
    const float mu = S1 * (1.f / 576.f), var = fmaxf(fmaf(-mu, mu, S2 * (1.f / 576.f)), 0.f);
    const float m = rbf(mu), rs = rcpf(rbf(sqrta(rbf(rbf(var) + 1e-5f))));
    const float ra = rs * 0.0625f;
    sts64(SM_AF + w * 128 + (lane & 15) * 8, fu(ra), fu(-m * ra));
    __syncwarp();
    TS(55);
    const uint4 f0 = lds128(SM_AF + w * 128 + q * 16), f1 = lds128(SM_AF + w * 128 + 64 + q * 16);
    const u32 zdst = SM_GATE + w * 2048 + (g >> 1) * 128 + (lane & 15) * 8;
    const u32 pz = (q & 1) ? 0 : pm;
#pragma unroll
    for (int j = 0; j < 8; j++) {
      const u32 x0 = j & 1 ? t[j >> 1].z : t[j >> 1].x, x1 = j & 1 ? t[j >> 1].w : t[j >> 1].y;
      sts64((j & 1 ? zdst ^ 64 : zdst) + 512 * (j >> 1), pk_hf(fmaf(blo(x0), uf(f0.x), uf(f0.y)), fmaf(bhi(x0), uf(f0.z), uf(f0.w))) | pz,
            pk_hf(fmaf(blo(x1), uf(f1.x), uf(f1.y)), fmaf(bhi(x1), uf(f1.z), uf(f1.w))));
    }
    TS(53);
    if (w < 8) barrive(15, 288);
    else {
      bsync(15, 288);
      TS(54);
      if (lane == 0) {
        PROXY_FENCE();
        bulk_out<BLK>(gs + b * BLK, SM_GATE);
        asm volatile("cp.async.bulk.commit_group;" ::: "memory");
        if (PFG & 1) l2_pre<WSH / 2>(p.wg + b * WSH);
      }
      const float rh = rbf(rs);
      sts128(SM_ST + 16 * (lane & 15), pk_bf(-m, -m), pk_bf(rh, rh), pk_bf(rs - rh, rs - rh), 0);
    }
    TS(5);
  }
  if (kw) {
    float D[5][4] = {};
    u32 ta = ktab + q * 128 + ((g ^ (q << 1)) << 4), tm = ktab + 8192 + q * 16;
#pragma unroll 2
    for (int s = 0; s < 8; s++) {
      const uint4 ca = lds128(ta), cb = lds128(ta + 4096), ma = lds128(tm);
      ta = (ta + 512) ^ 16; tm += 64;
      k2048 += __shfl_xor_sync(~0u, k2048, 16 >> s);
      const C2 s0 = {cb.z, cb.w}, s1 = cm2(s0, {ma.x, ma.y}), s2 = cm2(s0, {ma.z, ma.w}), s3 = cm2(s1, {ma.z, ma.w});
      mma_hf(D[0], s0.re, s1.re, s0.im, s1.im, ca.x, ca.y);
      mma_hf(D[2], s0.re, s1.re, s0.im, s1.im, ca.z, ca.w);
      mma_hf(D[4], s0.re, s1.re, s0.im, s1.im, cb.x, cb.y);
      mma_hf(D[1], s2.re, s3.re, s2.im, s3.im, ca.x, ca.y);
      mma_hf(D[3], s2.re, s3.re, s2.im, s3.im, ca.z, ca.w);
    }
    TS(3);
    const u32 xa = (w < 8 ? SM_MODS + (4 + ksig) * KTAB : SM_ZS) + lane * 16;
    if (khf) {
      __syncwarp();
#pragma unroll
      for (int j = 0; j < 5; j++) sts128(xa + 512 * j, fu(D[j][0]), fu(D[j][1]), fu(D[j][2]), fu(D[j][3]));
      if (lane == 0) sts32(xa + 2560, fu(k2048));
      asm volatile("bar.arrive %0,64;" ::"r"(2 + ksig) : "memory");
    } else {
      const u32 t1 = tp + (q < 2 ? (128 + 4 * g + 2 * q) * 4 : T3 * 4 + ((32 * q - 64 + g) ^ 1) * 2);
      const u32 x = 16 * q + (g >> 1) + hi + 1, tb = tp + (hi ? T7E : T9E) * 4 - 4;
      const u32 te = tb + (x + 2 * (x & 1)) * 2, to = tb + TEO * 4 + (x ^ 1) * 2;
      asm volatile("bar.sync %0,64;" ::"r"(2 + ksig) : "memory");
#pragma unroll
      for (int j = 0; j < 5; j++) { const uint4 t = lds128(xa + 512 * j); D[j][0] += uf(t.x); D[j][1] += uf(t.y); D[j][2] += uf(t.z); D[j][3] += uf(t.w); }
      k2048 = (k2048 + uf(lds32(xa + 2560))) * 0.125f;
#pragma unroll
      for (int r = 0; r < 4; r++) {
        const u32 v = pk_hf(D[2 + (r >> 1)][2 * (r & 1)], D[2 + (r >> 1)][2 * (r & 1) + 1]);
        if (q < 2) {
          const u32 vv = __byte_perm(v, v, 0x1010);
          sts32(t1 + (TO + 32 * r) * 4, vv); sts16(t1 + (TO + 32 * r + 1) * 4 + 2, v >> 16); sts16(t1 + (TO + 32 * r - 1) * 4, v);
          sts64(t1 + (TE + 32 * r) * 4, vv, __byte_perm(v, v, 0x1032));
        } else {
          sts16(t1 + 16 * r, v >> 16);
          if (r == 0 && lane == 2) {
            const u32 vv = __byte_perm(v, v, 0x1010);
            sts32(tp + (TO + 256) * 4, vv); sts16(tp + (TO + 257) * 4 + 2, v); sts16(tp + (TO + 255) * 4, v); sts64(tp + (TE + 256) * 4, vv, vv);
          } else sts16(t1 + 16 * r - ((T3 - T5) * 4 + 6) + 8 * hi, v);
        }
      }
#pragma unroll
      for (int r = 0; r < 2; r++) {
        const u32 v = pk_hf(D[4][2 * r], D[4][2 * r + 1]);
        if (r == 0 && lane == 0) { sts16(tp + T5 * 4 + 62 * 2, v); sts32(SM_KV + 4 * ksig, v & 0xffff); sts16(tp + (T9E + TEO) * 4 + 62 * 2, pk_hf(k2048, 0.f)); }
        else { sts16(te + 8 * r, v); sts16(to + 8 * r, v); }
        sts16(te + 8 * r + 16, v >> 16); sts16(to + 8 * r + 16, v >> 16);
      }
      __syncwarp();
#pragma unroll
      for (int r = 0; r < 4; r++) {
        const u32 v = pk_hf(D[r >> 1][2 * (r & 1) + 1], D[r >> 1][2 * (r & 1)]), t2 = tp + lane * 4 + 128 * r;
        sts32(t2 + TO * 4, v); sts16(t2 + TE * 4, v >> 16); sts16(t2 + (TE + 1) * 4 + 2, v);
      }
      __syncwarp();
    }
  } else if (w == 11 && b < 108) {
    float c[4][4] = {};
    u32 aa = SM_UP + ((lane & 7) + 8 * (lane >> 4)) * 64 + ((((lane >> 3) & 1) ^ ((lane & 7) >> 1)) << 4);
    u32 ba = SM_SIL + (lane >> 3) * 16;
    uint4 a[2][10];
#define GLD(n) { _Pragma("unroll") for (int i = 0; i < 2; i++) { a[n][5 * i] = ldsm4(ba + i * 64); \
      _Pragma("unroll") for (int k = 0; k < 4; k++) a[n][5 * i + 1 + k] = ldsm4t((k & 2 ? aa ^ 32 : aa) + i * 2048 + (k & 1) * 1024); } aa += 4096; ba += 128; }
#define GMM(n) { _Pragma("unroll") for (int i = 0; i < 2; i++) _Pragma("unroll") for (int k = 0; k < 4; k++) { const uint4 f = a[n][5 * i + 1 + k], bb = a[n][5 * i]; \
      mma_bf(c[k], f.x, f.y, f.z, f.w, k & 1 ? bb.z : bb.x, k & 1 ? bb.w : bb.y); } }
    mb_wait(SM_MB);
    TS(56);
    GLD(0);
#pragma unroll 1
    for (int s = 0; s < 4; s++) { GLD(1); GMM(0); GLD(0); GMM(1); }
    GMM(0);
    const float v0 = (q & 1) ? c[0][2] + c[1][2] : c[0][0] + c[1][0], v1 = (q & 1) ? c[2][2] + c[3][2] : c[2][0] + c[3][0];
    str16(gs + (G_MOD + b * 128 + 2 * g + 16 * q), pk_bf(rbf((q & 2) ? v1 : v0) * F2M64, 0.f) | (g < 2 ? pm : 0));
    TS(57);
  }
  TS(6);
  u32 tid2 = tid;
  if (w < 4) {
    asm volatile("setmaxnreg.inc.sync.aligned.u32 232;");
    const u32 tid = tid2 + p.zero, w = tid >> 5, lane = tid & 31, g = lane >> 2, q = lane & 3, hi = g & 1, zr = tid >> 16, tp = SM_TAP + w * TAPS;
    const u32 pml = opq((g & 3) ? 0 : pm);
    const u32 tr = tp + ((hi ? TO : TE) + (g >> 1) - q) * 4;
    u32 T[33][4], B5[5][2], B3[5][2];
#pragma unroll
    for (int d = 0; d < 33; d++) {
      T[d][0] = lds32(tr + 32 * d); T[d][1] = lds32(tr + 32 * d + 16);
      T[d][2] = cpy(d ? T[d - 1][1] : zr, zr, 0); T[d][3] = cpy(T[d][0], zr, 1);
    }
    const u32 t33 = cpy(T[32][1], zr, 0), z33 = cpy(zr, zr, 1);
    if (TPIN) {
#pragma unroll
      for (int d = 0; d < 33; d++) asm volatile("{.reg .pred p; setp.ne.u32 p,%2,0; @p st.shared.v2.u32 [%2],{%0,%1};}" ::"r"(T[d][2]), "r"(T[d][3]), "r"(zr) : "memory");
    }
    const u32 bt = tp + (T5 + g - q) * 4;
#pragma unroll
    for (int d = 0; d < 5; d++) {
      B5[d][0] = lds32(bt + 32 * d); B5[d][1] = lds32(bt + 32 * d - 16);
      B3[d][0] = lds32(bt + 32 * d + (T3 - T5) * 4); B3[d][1] = lds32(bt + 32 * d - 16 + (T3 - T5) * 4);
    }
    u32 za = opq(SM_ZS + 16 + w * ZSS + ((lane >> 3) & 1) * ZPS + ((lane & 7) + (lane >> 4)) * 16);
    u32 wa = opq(SM_W + W5O + w * WSL + row16(lane));
    u32 sa = opq(SM_W + W9O - 2048 + w * WSL + lane * 16);
    u32 yo = opq(G_Y + b * BLK + 256 * q + w * 32 + 4 * g);
    const u32 fa = opq(SM_SC + 16 * w + 8), bw = opq((BW >> 4 * w) & 15), bs = opq((BS >> 4 * w) & 15);
    if (TPIN) asm volatile("{.reg .pred p; setp.ne.u32 p,%8,0; @p st.shared.v4.u32 [%8],{%0,%1,%2,%3}; @p st.shared.v4.u32 [%8],{%4,%5,%6,%7};}"
                           ::"r"(za), "r"(wa), "r"(sa), "r"(yo), "r"(fa), "r"(bw), "r"(bs), "r"(pml), "r"(zr) : "memory");
    TS(8);
    bsync(9, 384);
    TS(11);
    float A[4][4] = {};
    uint4 Z[4];
    Z[0] = ldsm4(za); Z[1] = ldsm4(za + 32);
    const uint2 fc = lds64(fa);
    const u32 F = __byte_perm(fu(uf(fc.x) * uf(fc.y)), 0, 0x3232);
#define STEP(s, b0, b1) { _Pragma("unroll") for (int i = 0; i < 4; i++) mma_hf_t(A[i], T[8 * i + 7 - (s)], b0, b1); }
#define PAIR(n) { Z[(n + 2) & 3] = ldsm4(za + 32 * (n + 2)); STEP(2 * n, Z[n].x, Z[n].y); STEP(2 * n + 1, Z[n].z, Z[n].w); }
#define LAST(N) mma8_hf(N, t33, z33, Z[3].y); float O[4]; mma_hf_o(O, A[0], T[0], Z[3].z, Z[3].w); \
    _Pragma("unroll") for (int i = 0; i < 3; i++) mma_hf_o(A[i], A[i + 1], T[8 * i + 8], Z[3].z, Z[3].w); \
    mma_hf_o(A[3], N, T[32], Z[3].z, Z[3].w);
#pragma unroll 1
    for (int j = 0; j < 4; j++) {
      PAIR(0); PAIR(1); PAIR(2);
      Z[1] = ldsm4(za + 160); STEP(6, Z[3].x, Z[3].y);
      float N[4] = {};
      LAST(N);
      if (INCV) inc<128>(za);
      y_store<128>(O[0], O[1], O[2], O[3], F, pml, gs + yo);
      if (!INCV) za += 128;
      yo += 1024;
      TSJ(j);
    }
    bsyncr(bw);
    uint4 a5;
    if (A5P) a5 = ldsm4t(wa);
#pragma unroll 1
    for (int j = 4; j < 13; j++) {
      if (j == 8) bsyncr(bs);
      if (!A5P) a5 = ldsm4t(wa);
      const uint4 a3 = ldsm4t(wa + (W3O - W5O));
      uint4 s3 = {0, 0, 0, 0};
      if (j >= 8) s3 = lds128(sa);
      PAIR(0);
      float N[4] = {};
#pragma unroll
      for (int i = 0; i < 4; i++) mma_hf(A[i], a5.x, a5.y, a5.z, a5.w, B5[i][0], B5[i][1]);
      mma_hf(N, a5.x, a5.y, a5.z, a5.w, B5[4][0], B5[4][1]);
      if (INCV) asm volatile("{add.u32 %0,%0,256; xor.b32 %0,%0,32;}" : "+r"(wa)); else wa = (wa + 256) ^ 32;
      if (A5P) a5 = ldsm4t(wa);
      PAIR(1);
#pragma unroll
      for (int i = 0; i < 4; i++) mma_hf(A[i], a3.x, a3.y, a3.z, a3.w, B3[i][0], B3[i][1]);
      mma_hf(N, a3.x, a3.y, a3.z, a3.w, B3[4][0], B3[4][1]);
      PAIR(2);
      Z[1] = ldsm4(za + 160); STEP(6, Z[3].x, Z[3].y);
      LAST(N);
      if (INCV) { inc<128>(za); inc<512>(sa); }
      y_store<128>(O[0] + uf(s3.x), O[1] + uf(s3.y), O[2] + uf(s3.z), O[3] + uf(s3.w), F, pml, gs + yo);
      if (!INCV) { za += 128; sa += 512; }
      yo += 1024;
      TSJ(j);
    }
    {
      asm volatile("mov.u32 %0,%%tid.x;" : "=r"(tid2));
      const uint4 s3 = lds128(sa), s4 = lds128(sa + 512), s5 = lds128(sa + 1024);
      float X[3][4] = {{uf(s4.x), uf(s4.y), uf(s4.z), uf(s4.w)}, {}, {uf(s5.x), uf(s5.y), uf(s5.z), uf(s5.w)}};
#pragma unroll
      for (int ty = 0; ty < 2; ty++) {
        const uint4 a = A5P && !ty ? a5 : ldsm4t(wa + ty * (W3O - W5O)), c = ldsm4t((wa ^ 32) + 256 + ty * (W3O - W5O)), d = ldsm4t(wa + 512 + ty * (W3O - W5O));
#pragma unroll
        for (int i = 0; i < 3; i++) mma_hf(A[i], a.x, a.y, a.z, a.w, ty ? B3[i][0] : B5[i][0], ty ? B3[i][1] : B5[i][1]);
#pragma unroll
        for (int i = 0; i < 2; i++) mma_hf(X[i], c.x, c.y, c.z, c.w, ty ? B3[i][0] : B5[i][0], ty ? B3[i][1] : B5[i][1]);
        mma_hf(X[2], d.x, d.y, d.z, d.w, ty ? B3[0][0] : B5[0][0], ty ? B3[0][1] : B5[0][1]);
      }
#pragma unroll
      for (int n = 0; n < 4; n++) {
        const uint4 f0 = n < 2 ? Z[n] : ldsm4(za + 32 * n), f1 = ldsm4(za + 32 * n + 128), f2 = ldsm4(za + 32 * n + 256);
#pragma unroll
        for (int s = 2 * n; s < 2 * n + 2; s++) {
#pragma unroll
          for (int i = 0; i < 3; i++) mma_hf_t(A[i], T[8 * i + 7 - s], s & 1 ? f0.z : f0.x, s & 1 ? f0.w : f0.y);
          mma_hf_t(X[0], T[7 - s], s & 1 ? f1.z : f1.x, s & 1 ? f1.w : f1.y); mma_hf_t(X[1], T[15 - s], s & 1 ? f1.z : f1.x, s & 1 ? f1.w : f1.y);
          mma_hf_t(X[2], T[7 - s], s & 1 ? f2.z : f2.x, s & 1 ? f2.w : f2.y);
        }
      }
      y_store<128>(A[0][0] + uf(s3.x), A[0][1] + uf(s3.y), A[0][2] + uf(s3.z), A[0][3] + uf(s3.w), F, pml, gs + yo);
      y_store<128>(A[1][0] + X[0][0], A[1][1] + X[0][1], A[1][2] + X[0][2], A[1][3] + X[0][3], F, pml, gs + yo + 1024);
      y_store<128>(A[2][0] + X[1][0] + X[2][0], A[2][1] + X[1][1] + X[2][1], A[2][2] + X[1][2] + X[2][2], A[2][3] + X[1][3] + X[2][3], F, pml, gs + yo + 2048);
    }
    barrive(12, N12);
    TS(15);
  } else {
    asm volatile("setmaxnreg.dec.sync.aligned.u32 136;");
    const u32 t8 = tid - 128, pml = (g & 3) ? 0 : pm;
    {
      TS(12);
      if (PFG == 1 && tid == 288) l2_pre<WSH / 2>(p.wg + (b * WSH + WSH / 2));
      const char* zs = gs + ((16 * w - 64 + (lane >> 3)) * BLK + b * 128 + ((lane & 7) * 16 ^ rho * 64));
      const char* zs4 = gs + ((t8 >> 1) * BLK + (Ps >> 4) * 512 + (Ps & 6) * 64 + ((Ps >> 2 ^ Ps) & 2) * 32 + (Ps & 1) * 32 + (t8 & 1) * 16);
      uint4 v[5];
      v[4].x = INVAL;
      if (ZD) wait_clk(t0, ZD);
      if (w == 9) {
        const u32 d = lane < 4 ? chan(b, lane) : Ps;
        const char* mp = gs + (G_MOD + (d >> 5) * 128 + (d & 24) * 2);
        uint4 ta, tc;
        POLL({ ta = ldr128(mp); tc = ldr128(mp + MODJ); v[4] = ldr128(zs4); }, ((ta.x ^ pm) | (tc.x ^ pm)) & TAGM, 2);
        const u32 aw = (d & 4) ? ((d & 2) ? ta.w : ta.z) : ((d & 2) ? ta.y : ta.x & ~TAGM);
        const u32 cw = (d & 4) ? ((d & 2) ? tc.w : tc.z) : ((d & 2) ? tc.y : tc.x & ~TAGM);
        const float sa = ((d & 1) ? bhi(aw) : blo(aw)) * F2P64, c1 = rbf(fmaf((d & 1) ? bhi(cw) : blo(cw), F2P64, 1.f));
        const u32 EM = min(max(fu(fmaxf(32.f * fabsf(c1), fabsf(sa))) >> 23, 80u), 250u);
        const float inv = uf((264 - EM) << 23);
        if (lane < 5) { sts64(SM_SC + 16 * lane, pk_hf(16.f * c1 * inv, 16.f * c1 * inv), pk_hf(sa * inv, sa * inv)); sts32(SM_SC + 16 * lane + 8, (EM - 74) << 23); }
        TS(10);
      }
      POLLW(v[4] = ldr128(zs4), (v[4].x ^ pm) & TAGM, 1);
      TS(58);
#pragma unroll
      for (int j = 0; j < 4; j++) v[j] = ldr128(zs + j * 4 * BLK);
#define MARKERS() if (tid == 256) { \
        bulk_out<2048>(gs + (G_Y + 16384 + b * BLK), SM_INV); \
        _Pragma("unroll") for (int i = MT / 2; i < 8; i++) bulk_out<2048>(gs + (G_Y + 2048 * i + b * BLK), SM_INV); \
        bulk_out<2048>(gs + (G_PART + b * 2048), SM_INV); bulk_out<512>(gs + (G_ACT + b * 512), SM_INV); \
        bulk_out<32>(gs + (G_KEY + b * KST), SM_INV); if (!rho) bulk_out<128>(gs + (G_ACT + Ps * 128), SM_INV); \
        asm volatile("cp.async.bulk.commit_group;" ::: "memory"); }
#define GATE() { mb_expect(SM_MB + 8, rho ? SLV : 46080); \
        _Pragma("unroll") for (int i = GE; i < 3; i++) tma3d(SM_GATE + 12288 * i, &tm_gate, SM_MB + 8, 32 * b, i); \
        if (!rho) tma3d(SM_GATE + SLV, &tm_gs, SM_MB + 8, 4096 + 4 * b, 0); }
#define UP() { mb_expect(SM_MB + 16, rho ? SLV : 46080); tma3d(SM_UP, &tm_up, SM_MB + 16, 32 * b, 0); \
        if (!rho) tma3d(SM_UP + SLV, &tm_us, SM_MB + 16, 4096 + 4 * b, 0); }
      if (PFU == 2 && tid == 256) l2_pre<WSH>(p.wu + b * WSH);
      if (GE && tid == 256) {
        asm volatile("cp.async.bulk.wait_group.read 0;" ::: "memory");
#pragma unroll
        for (int i = 0; i < GE; i++) tma3d(SM_GATE + 12288 * i, &tm_gate, SM_MB + 8, 32 * b, i);
      }
      if (MKT == 0) MARKERS();
      if (PFG == 2 && tid == 256) l2_pre<WSH>(p.wg + b * WSH);
      if (PFG == 3 && tid == 256) l2_pre<WSH / 2>(p.wg + (b * WSH + WSH / 2));
      bsync(8, 256);
      const uint2 cc = lds64(SM_SC + 8 * (t8 & 6)), c4 = lds64(SM_SC + 64);
      POLLW(_Pragma("unroll") for (int j = 0; j < 4; j++) if ((v[j].x ^ pm) & TAGM) v[j] = ldr128(zs + j * 4 * BLK),
           ((v[0].x ^ pm) | (v[1].x ^ pm) | (v[2].x ^ pm) | (v[3].x ^ pm)) & TAGM, 1);
      TS(9);
      const u32 dst = SM_ZS + 128 + (t8 & 7) * ZPS + (16 * w - 64 + (lane >> 3)) * 16;
#pragma unroll
      for (int j = 4; j >= 0; j--) {
        const uint2 c = j < 4 ? cc : c4;
        sts128(j < 4 ? dst + j * 64 : SM_Z4 + 256 + (t8 & 1) * ZP4 + (t8 >> 1) * 16, hfma(v[j].x & ~TAGM, c.x, c.y), hfma(v[j].y, c.x, c.y), hfma(v[j].z, c.x, c.y), hfma(v[j].w, c.x, c.y));
      }
      if (t8 < 96) sts128(t8 < 64 ? SM_ZS + (t8 & 7) * ZPS + (t8 >> 3) * 16 : SM_Z4 + (t8 & 1) * ZP4 + (t8 & 30) * 8, 0, 0, 0, 0);
      if (MKT == 0) asm volatile("cp.async.bulk.wait_group.read 1;" ::: "memory");
      else asm volatile("cp.async.bulk.wait_group.read 0;" ::: "memory");
      bsync(9, 384);
      TS(11);
      if (MKT == 1) MARKERS();
      const bool lng = w < 8 || w == 9;
      const u32 ts = lane + 32 * (w == 8 ? 0 : w - 9), c = min(ts, 71u), ma = SM_MODS + 16 * c;
      const u32 sig = lng ? ksig : ts >> 4, l2 = lng ? lane : 32 + (ts & 15);
      const char* mq = gs + (G_MOD + (c >> 2) * 128 + (c & 3) * 16);
      if (!lng) {
#pragma unroll
        for (int j = 0; j < 6; j++) cpa16(ma + 1152 * j, mq + j * MODJ);
        cpa16(ma + 1152 * 6, p.dsk + 16 * c); cpa16(ma + 1152 * 7, p.wr + 16 * c);
        if (PFU == 3) {
#pragma unroll
          for (int j = 0; j < 4; j++) if (ts < 81) l2_line(p.wu + (b * WSH + (81 * j + ts) * 128));
        }
        if (tid == 352) {
          PROXY_FENCE();
          if (PFU == 1) l2_pre<WSH>(p.wu + b * WSH);
          if (!TG) GATE();
          if (!TU) UP();
        }
      }
      const u32 wb = SM_W + sig * WSL;
      if (sig < 5) {
        const u32 za = (sig < 4 ? SM_ZS + 128 + sig * ZSS : SM_Z4 + 256) + l2 * 32, zb = za + (sig < 4 ? ZPS : ZP4);
        const uint4 c0 = lds128(zb - 32), c1 = lds128(za - 16), c2 = lds128(zb - 16), c3 = lds128(za), c4 = lds128(zb), c5 = lds128(za + 16), c6 = lds128(zb + 16);
        const u32 P[25] = {c0.z, c0.w, c1.x, c1.y, c1.z, c1.w, c2.x, c2.y, c2.z, c2.w, c3.x, c3.y, c3.z, c3.w, c4.x, c4.y, c4.z, c4.w, c5.x, c5.y, c5.z, c5.w, c6.x, c6.y, c6.z};
        u32 Q[25], D1[24], F4[23], W5[21], W3[17];
#pragma unroll
        for (int j = 1; j < 25; j++) Q[j] = __byte_perm(P[j - 1], P[j], 0x5432);
#pragma unroll
        for (int j = 1; j < 24; j++) D1[j] = hadd(P[j], Q[j]);
#pragma unroll
        for (int j = 2; j < 23; j++) F4[j] = hadd(D1[j], D1[j - 1]);
#pragma unroll
        for (int n = 0; n < 21; n++) W5[n] = hadd(F4[n + 2], P[n]);
#pragma unroll
        for (int n = 0; n < 17; n++) W3[n] = hadd(Q[n + 8], D1[n + 7]);
        const u32 a0 = wb + W5O + 64 * l2 + 16 * ((l2 >> 1) & 3);
#pragma unroll
        for (int i = 0; i < 4; i++) {
          sts128(a0 ^ (16 * i), W5[4 * i + 5], W5[4 * i + 6], W5[4 * i + 7], W5[4 * i + 8]);
          sts128((a0 ^ (16 * i)) + (W3O - W5O), W3[4 * i + 1], W3[4 * i + 2], W3[4 * i + 3], W3[4 * i + 4]);
        }
        if (lng) {
          if (lane < 16) sts128(wb + (lane & 7) * 16 + (lane & 8) * 400, 0, 0, 0, 0);
          const u32 a1 = wb + 32 * lane + 16 * ((lane >> 2) & 1);
#pragma unroll
          for (int i = 0; i < 4; i++) {
            const u32 a = (a1 ^ (16 * (i >> 1))) + 1024 * (i & 1), n = 4 * i;
            sts128(a + V2O, hadd(Q[n + 9], P[n + 8]), hadd(Q[n + 10], P[n + 9]), hadd(Q[n + 11], P[n + 10]), hadd(Q[n + 12], P[n + 11]));
            sts128(a + W9O, hadd(F4[n + 4], W5[n]), hadd(F4[n + 5], W5[n + 1]), hadd(F4[n + 6], W5[n + 2]), hadd(F4[n + 7], W5[n + 3]));
            sts128(a + W7O, hadd(F4[n + 6], W3[n]), hadd(F4[n + 7], W3[n + 1]), hadd(F4[n + 8], W3[n + 2]), hadd(F4[n + 9], W3[n + 3]));
          }
        }
      }
      if (w < 8) barriver((BW >> (4 * w - 16)) & 15);
      else if (!(w & 1)) { barriver((BW >> (4 * w - 32)) & 15); barriver((BW >> (4 * w - 28)) & 15); }
      __syncwarp();
      TS(32);
      if (lng) {
        const u32 wa = wb + ((lane >> 3) & 1) * 1024 + (((lane & 7) ^ (lane >> 4)) + 8 * (lane >> 4)) * 16;
        const u32 kv = lds32(SM_KV + 4 * sig), bi = (g >> 1) == q ? (hi ? kv << 16 : kv) : 0u;
        float acc[8][4] = {};
#pragma unroll
        for (int j = 0; j < 4; j++) { const uint4 a = ldsm4t(wa + V2O + j * 256); mma8_hf(acc[2 * j], a.x, a.y, bi); mma8_hf(acc[2 * j + 1], a.z, a.w, bi); }
        u32 bt = tp + (T9E + hi * TEO + (g >> 1) - q) * 4, wt = wa + W9O;
#pragma unroll 1
        for (int ty = 0; ty < 2; ty++) {
          uint4 a[4];
#pragma unroll
          for (int be = 0; be < 4; be++) a[be] = ldsm4t(wt + be * 256);
          u32 b1 = lds32(bt - 16);
#pragma unroll
          for (int d = 0; d < 8; d++) {
            const u32 b0 = lds32(bt + 16 * d);
#pragma unroll
            for (int be = 0; be < 4; be++) if (d + 2 * be < 8) mma_hf(acc[d + 2 * be], a[be].x, a[be].y, a[be].z, a[be].w, b0, b1);
            b1 = b0;
          }
          bt += (T7E - T9E) * 4; wt += W7O - W9O;
        }
        __syncwarp();
#pragma unroll
        for (int j = 0; j < 8; j++) sts128(wb + W9O + j * 512 + lane * 16, fu(acc[j][0]), fu(acc[j][1]), fu(acc[j][2]), fu(acc[j][3]));
        if (w != 9) barriver((BS >> (4 * w - 16)) & 15);
        TS(34);
      }
      if (!lng) {
        asm volatile("cp.async.wait_all;" ::: "memory");
        uint4 md[6];
#pragma unroll
        for (int j = 0; j < 6; j++) md[j] = lds128(ma + 1152 * j);
        const uint4 dk = lds128(ma + 1152 * 6), wr = lds128(ma + 1152 * 7);
        POLLW(_Pragma("unroll") for (int j = 0; j < 6; j++) md[j] = ldr128(mq + j * MODJ),
              ((md[0].x ^ pm) | (md[1].x ^ pm) | (md[2].x ^ pm) | (md[3].x ^ pm) | (md[4].x ^ pm) | (md[5].x ^ pm)) & TAGM, 4);
#pragma unroll
        for (int j = 0; j < 6; j++) {
          const u32 o = (j % 3 == 1) ? BONE : 0x80008000u;
          md[j] = make_uint4(bfma(md[j].x & ~TAGM, B2P64, o), bfma(md[j].y, B2P64, o), bfma(md[j].z, B2P64, o), bfma(md[j].w, B2P64, o));
          if (j > 2) sts128(ma + 1152 * j, md[j].x, md[j].y, md[j].z, md[j].w);
        }
        const uint4 gd = make_uint4(bmul(md[2].x, dk.x), bmul(md[2].y, dk.y), bmul(md[2].z, dk.z), bmul(md[2].w, dk.w));
#pragma unroll
        for (int j = 0; j < 2; j++) sts128(ma + 1152 * j, bmul(md[j].x, gd.x), bmul(md[j].y, gd.y), bmul(md[j].z, gd.z), bmul(md[j].w, gd.w));
        sts128(ma + 2304, bmul(md[2].x, B2P64), bmul(md[2].y, B2P64), bmul(md[2].z, B2P64), bmul(md[2].w, B2P64));
        const uint4 H = make_uint4(bmul(md[4].x, wr.x), bmul(md[4].y, wr.y), bmul(md[4].z, wr.z), bmul(md[4].w, wr.w));
        sts128(ma + 1152 * 7, H.x, H.y, H.z, H.w);
        sts128(ma + 1152 * 8, bfma(md[4].x, wr.x, H.x ^ 0x80008000u), bfma(md[4].y, wr.y, H.y ^ 0x80008000u), bfma(md[4].z, wr.z, H.z ^ 0x80008000u), bfma(md[4].w, wr.w, H.w ^ 0x80008000u));
        float c4[4] = {};
        mma_bf(c4, md[4].x, md[3].x, md[4].y, md[3].y, wr.x, wr.y); mma_bf(c4, md[4].z, md[3].z, md[4].w, md[3].w, wr.z, wr.w);
        if (q == g >> 1) sts64(SM_RC + (ts >> 2) * 8, fu(hi ? c4[1] : c4[0]), fu(hi ? c4[3] : c4[2]));
        if (ts < 2) sts128(SM_ONE + 16 * ts, ts ? 0 : BONE, ts ? 0 : BONE, ts ? 0 : BONE, ts ? 0 : BONE);
        TS(14);
        if (MKT == 2) MARKERS();
        if (w == 8) asm volatile("cp.async.bulk.wait_group 0;" ::: "memory");
        if (PFW == 2) {
#pragma unroll
          for (int j = 0; j < 4; j++) if (ts < 81) l2_line(p.wd + (b * WSH + (81 * j + ts) * 128));
        }
        bsync(13, 96);
        if (w == 8) { barriver(2); barriver(3); barriver(5); barriver(6); }
      }
      if (MB11) { if (w == 8 || w == 9) mb_arrive(SM_MB + 32); } else if (w >= 8) barrive(11, 256);
    }
    if (w < 8) {
      const u32 jw = SWJ && w < 6 ? w ^ 1 : w;
      const int u0 = 4 * (jw - 4) + 2 * rho;
      const u32 t4 = SM_TAP + 4 * TAPS;
      u32 tr = t4 + ((hi ? TO : TE) + (g >> 1) - q) * 4;
      u32 zb = SM_Z4 + 256 + ((lane >> 3) & 1) * ZP4 + u0 * 128 + (lane & 7) * 16 + (lane >> 4) * 128;
      float acc[4][4] = {};
      u32 prev = 0;
#pragma unroll 1
      for (int it = min(u0 + 2, 4); it; it--) {
#pragma unroll
        for (int s = 0; s < 8; s++) {
          const uint4 z = ldsm4(zb - 16 * s);
          const u32 t0 = lds32(tr + 32 * s), t1 = lds32(tr + 32 * s + 16);
          mma_hf(acc[s & 1], t0, t1, prev, t0, z.x, z.y);
          mma_hf(acc[2 + (s & 1)], t0, t1, prev, t0, z.z, z.w);
          prev = t1;
        }
        zb -= 128; tr += 256;
      }
      {
        const uint4 z = ldsm4(zb); const u32 t0 = lds32(tr), t1 = lds32(tr + 16);
        mma_hf(acc[0], t0, t1, prev, t0, z.x, z.y); mma_hf(acc[2], t0, t1, prev, t0, z.z, z.w);
        if (jw > 4) { const uint4 y = ldsm4(zb - 16); mma8_hf(acc[1], t1, zr, y.y); mma8_hf(acc[3], t1, zr, y.w); }
      }
      if (MB11) mb_wait(SM_MB + 32); else bsync(11, 256);
      u32 wa = (SM_W + 4 * WSL + W5O + row16(lane) + (u0 - 3) * 256) ^ 32, bt = t4 + (T5 + g - q) * 4;
#pragma unroll 1
      for (int al = min(u0 - 2, 6); al > 0; al--) {
#pragma unroll
        for (int ty = 0; ty < 2; ty++) {
          const uint4 a = ldsm4t(wa + ty * (W3O - W5O));
          const u32 bb = bt + ty * (T3 - T5) * 4;
          mma_hf(acc[ty], a.x, a.y, a.z, a.w, lds32(bb - 32), lds32(bb - 48));
          mma_hf(acc[2 + ty], a.x, a.y, a.z, a.w, lds32(bb), lds32(bb - 16));
        }
        wa = (wa - 256) ^ 32; bt += 32;
      }
      TS(35);
      const uint2 fc = lds64(SM_SC + 16 * 4 + 8);
      const u32 F = __byte_perm(fu(uf(fc.x) * uf(fc.y)), 0, 0x3232);
      char* yp = gs + (G_Y + 16384 - 2048 + b * BLK + jw * 512 + q * 64 + 4 * g);
#pragma unroll
      for (int j = 0; j < 2; j++) {
        uint4 s3 = {0, 0, 0, 0};
        if (u0 >= 8) s3 = lds128(SM_W + 4 * WSL + W9O + (u0 - 8 + j) * 512 + lane * 16);
        y_store<32>(acc[2 * j][0] + acc[2 * j + 1][0] + uf(s3.x), acc[2 * j][1] + acc[2 * j + 1][1] + uf(s3.y), acc[2 * j][2] + acc[2 * j + 1][2] + uf(s3.z),
                acc[2 * j][3] + acc[2 * j + 1][3] + uf(s3.w), F, pml, yp + j * 256);
      }
      barrive(7, 160);
      TS(16);
    } else {
      if (PFW == 3 && w == 9) {
#pragma unroll 1
        for (int j = 0; j < 12; j++) { if (lane < 27) l2_line(p.wd + (b * WSH + (27 * j + lane) * 128)); wait_clk(clk(), PFP); }
      }
      if (TG | TU | TW) {
        if (tid == 352) {
          if (TG) { wait_clk(t0, TG); GATE(); }
          if (TW < TU) { wait_clk(t0, TW); l2_pre<WSH>(p.wd + b * WSH); }
          if (TU) { wait_clk(t0, TU); UP(); }
          if (TW >= TU) { wait_clk(t0, TW); l2_pre<WSH>(p.wd + b * WSH); }
        }
      } else if (PFW < 2 && tid == 352) { mb_wait(SM_MB + 8); if (PFW) mb_wait(SM_MB + 16); l2_pre<WSH>(p.wd + b * WSH); }
      if (D0C && tid == 352 && b < 108) {
        mb_wait(SM_MB + 16);
        PROXY_FENCE();
        mb_expect(SM_MB + 24, 49152);
        tma3d(SM_TAP, &tm_down, SM_MB + 24, 64 * (b % 9), 4 * (b / 9));
      }
      TS(17);
    }
  }
  post_conv(p, &tm_down, tid2 + p.zero, b);
  TSD();
  if (s2u(smem) != SM0) __trap();
}

typedef CUresult (*EncFn)(CUtensorMap*, CUtensorMapDataType, cuuint32_t, void*, const cuuint64_t*, const cuuint64_t*, const cuuint32_t*, const cuuint32_t*,
                          CUtensorMapInterleave, CUtensorMapSwizzle, CUtensorMapL2promotion, CUtensorMapFloatOOBfill);
static void make_map(EncFn enc, CUtensorMap* tm, void* ptr, int cols, int rows, int bw, int nb, CUtensorMapSwizzle sw, int gr = 192, int prom = 0) {
  cuuint64_t gd[3] = {(cuuint64_t)cols, (cuuint64_t)gr, (cuuint64_t)(rows / gr)}, gs[2] = {(cuuint64_t)cols * 2, (cuuint64_t)cols * 2 * gr};
  cuuint32_t bd[3] = {(cuuint32_t)bw, (cuuint32_t)gr, (cuuint32_t)nb}, es[3] = {1, 1, 1};
  enc(tm, CU_TENSOR_MAP_DATA_TYPE_BFLOAT16, 3, ptr, gd, gs, bd, es, CU_TENSOR_MAP_INTERLEAVE_NONE, sw, (CUtensorMapL2promotion)prom, CU_TENSOR_MAP_FLOAT_OOB_FILL_NONE);
}
extern "C" void kernel_launch(void* const* d_in, const int* in_sizes, int n_in, void* d_out, int out_size) {
  static EncFn enc = nullptr;
  static void* scratch = nullptr;
  if (!enc) {
    cudaGetSymbolAddress(&scratch, g_s);
    cudaDriverEntryPointQueryResult qr;
    cudaGetDriverEntryPoint("cuTensorMapEncodeTiled", (void**)&enc, cudaEnableDefault, &qr);
    cudaFuncSetAttribute(fused_kernel, cudaFuncAttributeMaxDynamicSharedMemorySize, SM_TOTAL);
  }
  CUtensorMap tm_mod, tm_gate, tm_gs, tm_up, tm_us, tm_down;
  make_map(enc, &tm_mod, d_in[13], 3456, 576, 32, 3, CU_TENSOR_MAP_SWIZZLE_64B, 192, PRM);
  make_map(enc, &tm_gate, d_in[9], 4608, 576, 32, 1, CU_TENSOR_MAP_SWIZZLE_64B, 192, PRG);
  make_map(enc, &tm_gs, d_in[9], 4608, 576, 8, 3, CU_TENSOR_MAP_SWIZZLE_NONE);
  make_map(enc, &tm_up, d_in[10], 4608, 576, 32, 3, CU_TENSOR_MAP_SWIZZLE_64B, 192, PRU);
  make_map(enc, &tm_us, d_in[10], 4608, 576, 8, 3, CU_TENSOR_MAP_SWIZZLE_NONE, 192, PRS);
  make_map(enc, &tm_down, d_in[11], 576, 4608, 64, 1, CU_TENSOR_MAP_SWIZZLE_128B, 96);
  Prm p;
  p.x = (const char*)d_in[0]; p.la = (const char*)d_in[1]; p.ai = (const char*)d_in[2]; p.cr = (const char*)d_in[3];
  p.ci = (const char*)d_in[4]; p.ldt = (const char*)d_in[5]; p.dsk = (const char*)d_in[6]; p.wr = (const char*)d_in[8];
  p.wg = (const char*)d_in[9]; p.wu = (const char*)d_in[10]; p.wd = (const char*)d_in[11];
  p.c = (const char*)d_in[12]; p.out = (char*)d_out; p.zero = 0; p.gs = (char*)scratch;
  fused_kernel<<<128, 384, SM_TOTAL>>>(p, tm_mod, tm_gate, tm_gs, tm_up, tm_us, tm_down);
}
```

```cpp
#include <cuda_runtime.h>
#include <cuda.h>
#include <cuda_bf16.h>
#include <cuda_fp16.h>
#include <stdint.h>
#define FUSED 1
#define DEV __device__ __forceinline__
typedef uint32_t u32;

constexpr u32 BLK = 18432, G_Z = 0, G_Y = 128 * BLK, G_MOD = 2 * G_Y, G_KEY = G_MOD + 128 * 128, G_ACT = G_KEY + 128 * 128;
constexpr u32 G_PART = G_ACT + 576 * 128, G_EP = G_PART + 128 * 2048, G_END = G_EP + 128;
__device__ __align__(128) unsigned char g_s[G_END];
#define TS(i)
#define TSJ(j)
#define TS0()
#define TSE()
#define TSD()
#define TSX 0
#define TSRND()
#define TSN(code, n)
#define ERRF(code)

constexpr int SM0 = 1024;
constexpr int ROW = 1168, SLV = 36864;
constexpr int SM_GATE = SM0, SM_UP = SM_GATE + 46080, SM_XST = SM_UP + 46080, SM_MODS = SM_XST + 16 * ROW, SM_W = SM_MODS + 11008;
constexpr int KTAB = 9216, WSL = 12544, W5O = 128, W3O = 3328, V2O = 6400, W9O = 8448, W7O = 10496;
constexpr int ZPS = 2192, ZSS = 2 * ZPS, ZP4 = 2368;
constexpr int SM_ZS = SM_W + 5 * WSL, SM_Z4 = SM_ZS + 4 * ZSS, SM_TAP = SM_Z4 + 2 * ZP4, TAPS = 3328;
constexpr int SM_MB = SM_TAP + 5 * TAPS;
constexpr int SM_SC = SM_MB + 48;
constexpr int SM_KV = SM_SC + 80;
constexpr int SM_THR = SM_KV + 32;
constexpr int SM_SLOT = SM_THR + 48;
constexpr int SM_KEY = SM_SLOT + 32;
constexpr int SM_ST = SM_KEY + 64;
constexpr int SM_ST2 = SM_ST + 256;
constexpr int SM_RC = SM_ST2 + 256;
constexpr int SM_SP = SM_RC + 192;
constexpr int SM_AF = SM_SP + 1152, SM_SIL = SM_AF + 1152, SM_INV = SM_SIL + 1152, SM_END = SM_SP + 5760;
constexpr int SM_ONE = SM_MODS + 9 * 1152;
constexpr int SM_WD = SM_W, SM_XS = SM_W + 36864, SM_AC = SM_ZS, SM_RED = SM_AC + 6144;
constexpr int SM_TSB = SM_END, SM_TOTAL = SM_END + TSX - SM0;
static_assert(SM_W % 1024 == 0 && SM_TAP % 1024 == 0 && SM_MODS + 8 * KTAB <= SM_ZS && SM_ZS + 2 * KTAB <= SM_TAP && SM_RED + 10240 <= SM_TAP && SM_XS + 8 * ROW <= SM_ZS, "smem map");
static_assert(SM_MB % 16 == 0 && SM_THR % 16 == 0 && SM_ST % 16 == 0 && SM_SP % 16 == 0 && SM_TOTAL <= 232448, "smem map");
constexpr int TE = 4, TO = 276, T5 = 560, T3 = 624, T9E = 680, T7E = 760, TEO = 40;
#define MT 10
#define MKT 1
#define KST 128
#define DE1 1
#define DE2 4
#define DE3 5
#define OUTB 7
#define PFW 1
#define PFU 0
#define KD 700
#define D0C 0
#define YE 104
#define YL 104
#define YD 250
#define OPTM 1
#define Y8 64
#define FH 0
#define FO 0
#define DB1 1
#define KD1 50
#define AD 0
#define PD 900
#define ZD 0
#define DD 1000
#define INCV 1
#define TPIN 0
#define A5P 1
#define TG 0
#define TU 0
#define TW 0
#define KDB 520
#define W8D 0
#define PRM 0
#define PRG 0
#define PRU 0
#define PRS 0
#define KE 64
#define PFP 200
#define GE 0
#define NB8 8
#define DX 0
#define DMOD 1000
#define RW 3
#define AW 7
#define HLP 1
#define AXW 1
#define HD 0
#define W8P 1
#define KF 96
#define KDC 520
#define AFP 1
#define AFM 0
#define PFG 1
constexpr int N1 = 320 + 32 * DB1, N12 = 288 + 32 * !DB1;
static_assert(AXW || !HLP, "barrier 7");
constexpr int SPIN = 1 << 16, NEARLY = 4;
constexpr u32 TAGM = 0x40004000u, TAGR = 0x40000000u, INVAL = 0x00004801u;

DEV u32 s2u(const void* p) { return (u32)__cvta_generic_to_shared(p); }
DEV void mma_bf(float (&c)[4], u32 a0, u32 a1, u32 a2, u32 a3, u32 b0, u32 b1) {
  asm("mma.sync.aligned.m16n8k16.row.col.f32.bf16.bf16.f32 {%0,%1,%2,%3},{%4,%5,%6,%7},{%8,%9},{%0,%1,%2,%3};"
      : "+f"(c[0]), "+f"(c[1]), "+f"(c[2]), "+f"(c[3]) : "r"(a0), "r"(a1), "r"(a2), "r"(a3), "r"(b0), "r"(b1));
}
DEV void mma_hf(float (&c)[4], u32 a0, u32 a1, u32 a2, u32 a3, u32 b0, u32 b1) {
  asm("mma.sync.aligned.m16n8k16.row.col.f32.f16.f16.f32 {%0,%1,%2,%3},{%4,%5,%6,%7},{%8,%9},{%0,%1,%2,%3};"
      : "+f"(c[0]), "+f"(c[1]), "+f"(c[2]), "+f"(c[3]) : "r"(a0), "r"(a1), "r"(a2), "r"(a3), "r"(b0), "r"(b1));
}
DEV void mma8_bf(float (&c)[4], u32 a0, u32 a1, u32 b0) {
  asm("mma.sync.aligned.m16n8k8.row.col.f32.bf16.bf16.f32 {%0,%1,%2,%3},{%4,%5},{%6},{%0,%1,%2,%3};"
      : "+f"(c[0]), "+f"(c[1]), "+f"(c[2]), "+f"(c[3]) : "r"(a0), "r"(a1), "r"(b0));
}
DEV void mma8_hf(float (&c)[4], u32 a0, u32 a1, u32 b0) {
  asm("mma.sync.aligned.m16n8k8.row.col.f32.f16.f16.f32 {%0,%1,%2,%3},{%4,%5},{%6},{%0,%1,%2,%3};"
      : "+f"(c[0]), "+f"(c[1]), "+f"(c[2]), "+f"(c[3]) : "r"(a0), "r"(a1), "r"(b0));
}
DEV u32 movm(u32 x) { u32 r; asm("movmatrix.sync.aligned.m8n8.trans.b16 %0,%1;" : "=r"(r) : "r"(x)); return r; }
DEV uint4 ldsm4(u32 a) { uint4 r; asm volatile("ldmatrix.sync.aligned.m8n8.x4.shared.b16 {%0,%1,%2,%3},[%4];" : "=r"(r.x), "=r"(r.y), "=r"(r.z), "=r"(r.w) : "r"(a)); return r; }
DEV uint4 ldsm4t(u32 a) { uint4 r; asm volatile("ldmatrix.sync.aligned.m8n8.x4.trans.shared.b16 {%0,%1,%2,%3},[%4];" : "=r"(r.x), "=r"(r.y), "=r"(r.z), "=r"(r.w) : "r"(a)); return r; }
DEV u32 lds32(u32 a) { u32 r; asm volatile("ld.volatile.shared.u32 %0,[%1];" : "=r"(r) : "r"(a)); return r; }
DEV uint2 lds64(u32 a) { uint2 r; asm volatile("ld.shared.v2.u32 {%0,%1},[%2];" : "=r"(r.x), "=r"(r.y) : "r"(a)); return r; }
DEV uint4 lds128(u32 a) { uint4 r; asm volatile("ld.shared.v4.u32 {%0,%1,%2,%3},[%4];" : "=r"(r.x), "=r"(r.y), "=r"(r.z), "=r"(r.w) : "r"(a)); return r; }
DEV void sts16(u32 a, u32 v) { asm volatile("st.shared.u16 [%0],%1;" ::"r"(a), "h"((unsigned short)v) : "memory"); }
DEV void sts32(u32 a, u32 v) { asm volatile("st.shared.u32 [%0],%1;" ::"r"(a), "r"(v) : "memory"); }
DEV void sts64(u32 a, u32 x, u32 y) { asm volatile("st.shared.v2.u32 [%0],{%1,%2};" ::"r"(a), "r"(x), "r"(y) : "memory"); }
DEV void sts128(u32 a, u32 x, u32 y, u32 z, u32 w) { asm volatile("st.shared.v4.u32 [%0],{%1,%2,%3,%4};" ::"r"(a), "r"(x), "r"(y), "r"(z), "r"(w) : "memory"); }
DEV uint4 ldr128(const void* p) { uint4 v; asm volatile("ld.relaxed.gpu.global.v4.u32 {%0,%1,%2,%3},[%4];" : "=r"(v.x), "=r"(v.y), "=r"(v.z), "=r"(v.w) : "l"(p) : "memory"); return v; }
DEV uint2 ldr64(const void* p) { uint2 v; asm volatile("ld.relaxed.gpu.global.v2.u32 {%0,%1},[%2];" : "=r"(v.x), "=r"(v.y) : "l"(p) : "memory"); return v; }
DEV u32 ldr32(const void* p) { u32 v; asm volatile("ld.relaxed.gpu.global.u32 %0,[%1];" : "=r"(v) : "l"(p) : "memory"); return v; }
template <u32 M> DEV void rld128(uint4& v, const void* p, u32 tag) {
  asm volatile("{.reg .pred p; .reg .u32 t; lop3.b32 t,%0,%5,%6,0x28; setp.ne.u32 p,t,0; @p ld.relaxed.gpu.global.v4.u32 {%0,%1,%2,%3},[%4];}"
               : "+r"(v.x), "+r"(v.y), "+r"(v.z), "+r"(v.w) : "l"(p), "r"(tag), "n"(M) : "memory");
}
template <u32 M> DEV void rld64(uint64_t& v, const void* p, u32 tag) {
  asm volatile("{.reg .pred p; .reg .u32 t, h; mov.b64 {t,h},%0; lop3.b32 t,t,%2,%3,0x28; setp.ne.u32 p,t,0; @p ld.relaxed.gpu.global.u64 %0,[%1];}" : "+l"(v) : "l"(p), "r"(tag), "n"(M) : "memory");
}
template <int L> DEV u32 lop3(u32 a, u32 b, u32 c) { u32 r; asm("lop3.b32 %0,%1,%2,%3,%4;" : "=r"(r) : "r"(a), "r"(b), "r"(c), "n"(L)); return r; }
DEV u32 ne3(u32 a, u32 b, u32 c) { u32 r; asm("lop3.b32 %0,%1,%2,%3,0x7e;" : "=r"(r) : "r"(a), "r"(b), "r"(c)); return r; }
DEV void pin(u32 zr, u32 a, u32 b = 0, u32 c = 0, u32 d = 0) { asm volatile("{.reg .pred p; setp.ne.u32 p,%0,0; @p st.shared.v4.u32 [%0],{%1,%2,%3,%4};}" ::"r"(zr), "r"(a), "r"(b), "r"(c), "r"(d) : "memory"); }
DEV void pin2(u32 zr, const void* a, const void* b) { asm volatile("{.reg .pred p; setp.ne.u32 p,%0,0; @p st.shared.v2.u64 [%0],{%1,%2};}" ::"r"(zr), "l"(a), "l"(b) : "memory"); }
DEV const char* rowa(const char* base, u32 key) { const char* r; asm("mad.wide.u32 %0,%1,288,%2;" : "=l"(r) : "r"(~key & 0x1ffc), "l"(base)); return r; }
DEV void str128(void* p, u32 x, u32 y, u32 z, u32 w) { asm volatile("st.relaxed.gpu.global.v4.u32 [%0],{%1,%2,%3,%4};" ::"l"(p), "r"(x), "r"(y), "r"(z), "r"(w) : "memory"); }
DEV void str64(void* p, u32 x, u32 y) { asm volatile("{.reg .u64 d; mov.b64 d,{%1,%2}; st.relaxed.gpu.global.u64 [%0],d;}" ::"l"(p), "r"(x), "r"(y) : "memory"); }
DEV void str32(void* p, u32 x) { asm volatile("st.relaxed.gpu.global.u32 [%0],%1;" ::"l"(p), "r"(x) : "memory"); }
DEV void str16(void* p, u32 x) { asm volatile("st.relaxed.gpu.global.u16 [%0],%1;" ::"l"(p), "h"((unsigned short)x) : "memory"); }
DEV uint4 ldg128(const void* p) { uint4 v; asm volatile("ld.global.nc.v4.u32 {%0,%1,%2,%3},[%4];" : "=r"(v.x), "=r"(v.y), "=r"(v.z), "=r"(v.w) : "l"(p)); return v; }
DEV uint2 ldg64(const void* p) { uint2 v; asm volatile("ld.global.nc.v2.u32 {%0,%1},[%2];" : "=r"(v.x), "=r"(v.y) : "l"(p)); return v; }
DEV u32 ldg32(const void* p) { u32 v; asm volatile("ld.global.nc.u32 %0,[%1];" : "=r"(v) : "l"(p)); return v; }
DEV u32 ldg16(const void* p) { unsigned short v; asm volatile("ld.global.nc.u16 %0,[%1];" : "=h"(v) : "l"(p)); return v; }
#define bsync(id, n) asm volatile("bar.sync %0,%1;" ::"n"(id), "n"(n) : "memory")
#define barrive(id, n) asm volatile("bar.arrive %0,%1;" ::"n"(id), "n"(n) : "memory")
DEV void bsyncr(u32 id) { asm volatile("bar.sync %0,96;" ::"r"(id) : "memory"); }
DEV void barriver(u32 id) { asm volatile("bar.arrive %0,96;" ::"r"(id) : "memory"); }
constexpr u32 BW = 0x0FEA, BS = 0x6532;
DEV void mb_init(u32 a, u32 n) { asm volatile("mbarrier.init.shared.b64 [%0],%1;" ::"r"(a), "r"(n) : "memory"); }
DEV void mb_arrive(u32 a) { asm volatile("mbarrier.arrive.shared.b64 _,[%0];" ::"r"(a) : "memory"); }
DEV void mb_expect(u32 a, u32 bytes) { asm volatile("mbarrier.arrive.expect_tx.shared.b64 _,[%0],%1;" ::"r"(a), "r"(bytes) : "memory"); }
DEV void mb_wait(u32 a, u32 ph = 0) {
  u32 ok; int it = 0;
  do { asm volatile("{.reg .pred p; mbarrier.try_wait.parity.shared.b64 p,[%1],%2; selp.u32 %0,1,0,p;}" : "=r"(ok) : "r"(a), "r"(ph) : "memory"); } while (!ok && ++it < SPIN);
}
template <int N> DEV void bulk_out(void* dst, u32 src) { asm volatile("cp.async.bulk.global.shared::cta.bulk_group [%0],[%1],%2;" ::"l"(dst), "r"(src), "n"(N) : "memory"); }
constexpr u32 WSH = 41472;
DEV void l2_line(const void* p) { asm volatile("prefetch.global.L2 [%0];" ::"l"(p) : "memory"); }
template <int N> DEV void l2_pre(const void* p) { asm volatile("cp.async.bulk.prefetch.L2.global [%0],%1;" ::"l"(p), "n"(N) : "memory"); }
DEV void tma3d(u32 dst, const CUtensorMap* tm, u32 mb, int c0, int c2) {
  asm volatile("cp.async.bulk.tensor.3d.shared::cluster.global.mbarrier::complete_tx::bytes [%0],[%1,{%3,0,%4}],[%2];"
               ::"r"(dst), "l"((uint64_t)tm), "r"(mb), "r"(c0), "r"(c2) : "memory");
}
DEV float blo(u32 w) { return __uint_as_float(w << 16); }
DEV float bhi(u32 w) { return __uint_as_float(w & 0xffff0000u); }
DEV u32 pk_bf(float lo, float hi) { u32 r; asm("cvt.rn.bf16x2.f32 %0,%1,%2;" : "=r"(r) : "f"(hi), "f"(lo)); return r; }
DEV u32 pk_hf(float lo, float hi) { u32 r; asm("cvt.rn.f16x2.f32 %0,%1,%2;" : "=r"(r) : "f"(hi), "f"(lo)); return r; }
DEV float rbf(float x) { return __uint_as_float(pk_bf(0.f, x) & 0xffff0000u); }
DEV u32 bfma(u32 a, u32 b, u32 c) { u32 r; asm("fma.rn.bf16x2 %0,%1,%2,%3;" : "=r"(r) : "r"(a), "r"(b), "r"(c)); return r; }
DEV u32 bmul(u32 a, u32 b) { u32 r; asm("mul.rn.bf16x2 %0,%1,%2;" : "=r"(r) : "r"(a), "r"(b)); return r; }
DEV u32 badd(u32 a, u32 b) { u32 r; asm("add.rn.bf16x2 %0,%1,%2;" : "=r"(r) : "r"(a), "r"(b)); return r; }
DEV u32 hadd(u32 a, u32 b) { u32 r; asm("add.rn.f16x2 %0,%1,%2;" : "=r"(r) : "r"(a), "r"(b)); return r; }
DEV u32 hfma(u32 a, u32 b, u32 c) { u32 r; asm("fma.rn.f16x2 %0,%1,%2,%3;" : "=r"(r) : "r"(a), "r"(b), "r"(c)); return r; }
struct C2 { u32 re, im; };
DEV C2 cm2(C2 a, C2 b) {
  const __half2 ar = *reinterpret_cast<__half2*>(&a.re), ai = *reinterpret_cast<__half2*>(&a.im), br = *reinterpret_cast<__half2*>(&b.re), bi = *reinterpret_cast<__half2*>(&b.im);
  __half2 re = __hfma2(ar, br, __hneg2(__hmul2(ai, bi))), im = __hfma2(ar, bi, __hmul2(ai, br));
  return {*reinterpret_cast<u32*>(&re), *reinterpret_cast<u32*>(&im)};
}
DEV C2 pk2(const float2 (&a)[2]) { return {pk_hf(a[0].x, a[1].x), pk_hf(a[0].y, a[1].y)}; }
DEV C2 pk2c(const float2 (&a)[2]) { return {pk_hf(a[0].x, a[1].x), pk_hf(-a[0].y, -a[1].y)}; }
DEV u32 cpy(u32 x, u32 zr, int alt) {
  u32 r;
  if (alt) asm volatile("xor.b32 %0,%1,%2;" : "=r"(r) : "r"(x), "r"(zr)); else asm volatile("mad.lo.u32 %0,%2,%2,%1;" : "=r"(r) : "r"(x), "r"(zr));
  return r;
}
template <int N> DEV void inc(u32& x) { asm volatile("add.u32 %0,%0,%1;" : "+r"(x) : "n"(N)); }
DEV u32 opq(u32 x) { u32 r; asm volatile("mov.u32 %0,%1;" : "=r"(r) : "r"(x)); return r; }
DEV u32 chan(u32 b, u32 i) { return 16 * (b >> 2) + 2 * (b & 3) + (i & 1) + 4 * (i & 2); }
DEV u32 row16(u32 lane) { const u32 r0 = (lane & 7) + ((lane >> 3) & 1) + 8 * (lane >> 4) - 1; return (r0 ^ ((r0 >> 3) & 3)) * 16; }
DEV u32 clk() { u32 r; asm volatile("mov.u32 %0,%%clock;" : "=r"(r)::"memory"); return r; }
DEV void wait_clk(u32 t, int d) { while ((int)(clk() - t) < d); }
DEV float ex2(float x) { float r; asm("ex2.approx.ftz.f32 %0,%1;" : "=f"(r) : "f"(x)); return r; }
DEV float rcpf(float x) { float r; asm("rcp.approx.ftz.f32 %0,%1;" : "=f"(r) : "f"(x)); return r; }
DEV float2 cmul(float2 a, float2 b) { return make_float2(fmaf(a.x, b.x, -a.y * b.y), fmaf(a.x, b.y, a.y * b.x)); }
DEV float2 csq(float2 a) { return make_float2(fmaf(a.x, a.x, -a.y * a.y), (a.x + a.x) * a.y); }
DEV float2 cexp(float lr2, float th) {
  const float m = ex2(lr2);
  return make_float2(m * __cosf(th), m * __sinf(th));
}
DEV float silu_f(float v) { return v * rcpf(1.f + ex2(-1.4426950408889634f * v)); }
constexpr u32 B2P64 = 0x5F805F80u, B2M64 = 0x1F801F80u, BONE = 0x3F803F80u;
constexpr u32 MODJ = 18 * 128;
DEV float sqrta(float x) { float r; asm("sqrt.approx.ftz.f32 %0,%1;" : "=f"(r) : "f"(x)); return r; }
DEV u32 fu(float x) { return __float_as_uint(x); }
DEV float uf(u32 x) { return __uint_as_float(x); }
DEV void mma_hf_o(float (&d)[4], const float (&c)[4], const u32 (&a)[4], u32 b0, u32 b1) {
  asm("mma.sync.aligned.m16n8k16.row.col.f32.f16.f16.f32 {%0,%1,%2,%3},{%4,%5,%6,%7},{%8,%9},{%10,%11,%12,%13};"
      : "=f"(d[0]), "=f"(d[1]), "=f"(d[2]), "=f"(d[3]) : "r"(a[0]), "r"(a[1]), "r"(a[2]), "r"(a[3]), "r"(b0), "r"(b1), "f"(c[0]), "f"(c[1]), "f"(c[2]), "f"(c[3]));
}

DEV void mma_hf_t(float (&c)[4], const u32 (&a)[4], u32 b0, u32 b1) { mma_hf(c, a[0], a[1], a[2], a[3], b0, b1); }
DEV void cpa16(u32 dst, const void* src) { asm volatile("cp.async.cg.shared.global [%0],[%1],16;" ::"r"(dst), "l"(src) : "memory"); }
DEV void tm_pre(const CUtensorMap* tm) { asm volatile("prefetch.tensormap [%0];" ::"l"((uint64_t)tm) : "memory"); }
#define PROXY_FENCE() asm volatile("fence.proxy.async.shared::cta;" ::: "memory")
struct Prm {
  const char *la, *ai, *cr, *ci, *ldt;
  u32 zero;
  const char *x, *c;
  char* gs;
  const char *dsk, *wr, *wg, *wu, *wd;
  char* out;
};
constexpr float LOG2E = 1.4426950408889634f, F2P64 = 1.8446744073709552e19f, F2M64 = 5.421010862427522e-20f;

template <int S> DEV void y_store(float c0, float c1, float c2, float c3, u32 F, u32 pml, char* yp) {
  str32(yp, bmul(pk_bf(c0, c2), F) | pml);
  str32(yp + S, bmul(pk_bf(c1, c3), F) | pml);
}
DEV void merge4(u32 (&h)[8], uint4 a, uint4 b) {
  const u32 e1 = min(a.x, b.x), e2 = max(a.z, b.z), o1 = min(a.y, b.y), o2 = max(a.w, b.w), o0 = max(a.y, b.y), e3 = min(a.z, b.z);
  const u32 f1 = max(e1, e2), f2 = min(e1, e2), p1 = max(o1, o2), p2 = min(o1, o2);
  h[0] = max(a.x, b.x); h[1] = max(o0, f1); h[2] = min(o0, f1); h[3] = max(p1, f2); h[4] = min(p1, f2); h[5] = max(p2, e3); h[6] = min(p2, e3); h[7] = min(a.w, b.w);
}
DEV void top8(u32 (&a)[8], uint4 l, uint4 m) {
  u32 b[8];
  merge4(b, l, m);
#pragma unroll
  for (int i = 0; i < 8; i++) a[i] = max(a[i], b[7 - i]);
#pragma unroll
  for (int s = 4; s; s >>= 1)
#pragma unroll
    for (int i = 0; i < 8; i++) if (!(i & s)) { const u32 x = a[i], y = a[i + s]; a[i] = max(x, y); a[i + s] = min(x, y); }
}
#define POLL(load, cond_bad, code) { int it_ = 0; do { load; } while (__any_sync(~0u, (cond_bad)) & (++it_ <= SPIN)); if (it_ > SPIN) { ERRF(code); } TSN(code, it_); }
#define POLLW(load, cond_bad, code) { int it_ = 0; while (__any_sync(~0u, (cond_bad))) { if (++it_ > SPIN) { ERRF(code); break; } load; } TSN(code, it_); }

#define DOWN(E) if (tid == 288 && b < 108) { const u32 c0 = 64 * (b % 9), c2 = 4 * (b / 9); \
    if (!D0C && E == 1) { mb_expect(SM_MB + 24, 49152); tma3d(SM_TAP, tm_down, SM_MB + 24, c0, c2); } \
    if (DE1 == E) tma3d(SM_WD, tm_down, SM_MB + 24, c0, c2 + 1); \
    if (DE2 == E) tma3d(SM_WD + 12288, tm_down, SM_MB + 24, c0, c2 + 2); \
    if (DE3 == E) tma3d(SM_WD + 24576, tm_down, SM_MB + 24, c0, c2 + 3); }
#define OUTR() { const u32 tl = 4 * ((lane >> 1) & 1) + ((lane >> 2) & 3) + 8 * (lane & 1); \
    bulk_out<1152>(p.out + (b * BLK + tl * 1152), SM_XST + ((lane & 2) + 4 * (lane & 1) + ((lane >> 2) & 1) + (lane & 8)) * ROW); \
    asm volatile("cp.async.bulk.commit_group;" ::: "memory"); }
struct FA { u32 tid, ba, ra, sa; char *ad, *as; };
DEV FA ffn_addr(const Prm& p, u32 tid, u32 b) {
  const u32 w = tid >> 5, lane = tid & 31, kq = w & 3, tg = w >> 2, t = 7 - w;
  FA f = {tid, SM_XS + (lane & 7) * ROW + (18 * kq + (lane >> 3)) * 16, SM_RED + (8 * tg + kq) * 512 + lane * 16, SM_RED + t * 2048 + lane * 16,
          p.gs + (G_ACT + (t < 4 ? 4 * b + t : 512 + (b >> 1)) * 128 + lane * 4), p.gs + (G_ACT + (b / 9) * 6144 + tid * 16)};
  if (AW & 2) { pin(tid >> 16, f.ba, f.ra, f.sa, tid); pin2(tid >> 16, f.ad, f.as); }
  return f;
}
DEV void ffn_tail(const Prm& p, const CUtensorMap* tm_down, uint4 (&A)[24], const FA f, const u32 b, const u32 par, const u32 okl) {
  const u32 tid = f.tid, w = tid >> 5, lane = tid & 31, g = lane >> 2, q = lane & 3, tg = w >> 2, zr = tid >> 16;
  const u32 rho = b & 1, pm = par ? TAGM : 0, kt = par * 3, ba = f.ba, ra = f.ra;
  char* const gs = p.gs;
  char *const ad = f.ad, *const as = f.as;
  __syncthreads();
  TS(25);
  if (!(AW & 4)) DOWN(5);
  {
    float c0[2][4] = {}, c1[2][4] = {};
    uint4 bb[5];
#pragma unroll
    for (int s = 0; s < 5; s++) bb[s] = ldsm4(ba + s * 64);
    if (AW & 4) DOWN(5);
#pragma unroll
    for (int s = 0; s < 9; s++) mma_bf(c0[s & 1], A[s].x, A[s].y, A[s].z, A[s].w, s & 1 ? bb[s >> 1].z : bb[s >> 1].x, s & 1 ? bb[s >> 1].w : bb[s >> 1].y);
    if (tg < 2) {
#pragma unroll
      for (int s = 0; s < 9; s++) mma_bf(c1[s & 1], A[9 + s].x, A[9 + s].y, A[9 + s].z, A[9 + s].w, s & 1 ? bb[s >> 1].z : bb[s >> 1].x, s & 1 ? bb[s >> 1].w : bb[s >> 1].y);
      sts128(ra + 2048, fu(c1[0][0] + c1[1][0]), fu(c1[0][1] + c1[1][1]), fu(c1[0][2] + c1[1][2]), fu(c1[0][3] + c1[1][3]));
    }
    sts128(ra, fu(c0[0][0] + c0[1][0]), fu(c0[0][1] + c0[1][1]), fu(c0[0][2] + c0[1][2]), fu(c0[0][3] + c0[1][3]));
  }
  TS(39);
  __syncthreads();
  const u32 tr = clk();
  if (OUTB == 6 && w == 10 && okl < lds32(SM_SLOT + 28)) OUTR();
  if (w - 3 - rho < 5 - rho) {
    float s[4];
    const uint4 u0 = lds128(f.sa), u1 = lds128(f.sa + 512), u2 = lds128(f.sa + 1024), u3 = lds128(f.sa + 1536);
    s[0] = (uf(u0.x) + uf(u1.x)) + (uf(u2.x) + uf(u3.x)); s[1] = (uf(u0.y) + uf(u1.y)) + (uf(u2.y) + uf(u3.y));
    s[2] = (uf(u0.z) + uf(u1.z)) + (uf(u2.z) + uf(u3.z)); s[3] = (uf(u0.w) + uf(u1.w)) + (uf(u2.w) + uf(u3.w));
    const u32 sg = pk_bf(silu_f(rbf(s[0])), silu_f(rbf(s[1])));
    const u32 act = movm(bmul(bmul(sg, pk_bf(s[2], s[3])), B2M64));
    str32(ad, act | (q ? 0 : pm));
  }
  TS(26);
  const bool fin = w == 8 && b < 72;
  u32 kg;
  uint4 xt;
  const char* xs;
  if (fin) { kg = lds32(SM_SLOT + 4 * g); xs = rowa(gs + (G_Y + 16 * b), kg); xt = ldr128(xs); }
  if (b < 108) {
    uint4 a;
    if (AD) a.x = INVAL; else a = ldr128(as);
    if (AD && w >= 4) wait_clk(tr, AD);
    char* const dst = gs + (G_PART + b * 2048 + w * 512 + lane * 8);
    if (w < 4) {
      const u32 aa = SM_WD + (8 * (lane >> 4) + (lane & 7)) * 128 + (((2 * w + ((lane >> 3) & 1)) ^ (lane & 7)) << 4);
      mb_wait(SM_MB + 24);
#pragma unroll
      for (int s = 0; s < 24; s++) A[s] = ldsm4t(aa + (s < 6 ? SM_TAP - SM_WD : -12288) + s * 2048);
      if (AW & 2) pin2(zr, dst, as);
    }
    TS(28);
    POLLW(rld128<TAGM>(a, as, pm), (a.x ^ pm) & TAGM, 9);
    sts128(SM_AC + tid * 16, a.x, a.y, a.z, a.w); sts32(SM_AC + tid * 16, a.x & ~TAGM);
    TS(27);
    if (w < 4) {
      bsync(8, 384);
      float c[4][4] = {};
#pragma unroll
      for (int s = 0; s < 12; s++) {
        const uint4 bb = ldsm4(SM_AC + lane * 16 + s * 512);
        mma_bf(c[2 * (s & 1)], A[2 * s].x, A[2 * s].y, A[2 * s].z, A[2 * s].w, bb.x, bb.y);
        mma_bf(c[2 * (s & 1) + 1], A[2 * s + 1].x, A[2 * s + 1].y, A[2 * s + 1].z, A[2 * s + 1].w, bb.z, bb.w);
      }
      u32 o[4];
#pragma unroll
      for (int i = 0; i < 4; i++) o[i] = fu(((c[0][i] + c[1][i]) + (c[2][i] + c[3][i])) * F2P64);
      str64(dst, (o[0] & ~3u) | kt, o[1]); str64(dst + 256, (o[2] & ~3u) | kt, o[3]);
      TS(29);
    } else barrive(8, 384);
  }
  if (OUTB == 7 && w == 10 && okl < lds32(SM_SLOT + 28)) OUTR();
  if (fin) {
    const u32 ta = clk();
    const char* src = gs + (G_PART + (b >> 3) * 2048 + (b & 7) * 256 + lane * 8);
    const u32 gw = lds32(SM_MODS + 5760 + 16 * b + 4 * q);
    const u32 hw = lds32(SM_XS + g * ROW + b * 16 + q * 4);
    const float sgm = rcpf(1.f + ex2(-LOG2E * bhi(kg ^ (~((int)kg >> 31) | 0x80000000))));
    char* const dst = (char*)rowa(p.out + (16 * b + 4 * q), kg);
    POLLW(rld128<TAGM>(xt, xs, TAGR), (xt.x ^ TAGR) & TAGM, 10);
    const u32 x1w = (q & 2) ? ((q & 1) ? xt.w : xt.z) : ((q & 1) ? xt.y : bmul(xt.x ^ TAGR, B2P64));
    const u32 sg2 = pk_bf(sgm, sgm);
    pin(zr, x1w, gw, hw, sg2); pin2(zr, dst, src);
    uint64_t v[12];
#pragma unroll
    for (int j = 0; j < 12; j++) v[j] = 1;
    float s0, s1;
    if (PD) wait_clk(ta, PD);
    TS(13);
#define VL(j) (u32)v[j]
#define VS(j, s) ((uf((u32)(v[j] >> s)) + uf((u32)(v[j + 1] >> s))) + (uf((u32)(v[j + 2] >> s)) + uf((u32)(v[j + 3] >> s))))
    POLL({ _Pragma("unroll") for (int j = 0; j < 12; j++) rld64<3>(v[j], src + j * 9 * 2048, kt);
           s0 = VS(0, 0) + VS(4, 0) + VS(8, 0); s1 = VS(0, 32) + VS(4, 32) + VS(8, 32);
           asm volatile("" : "+f"(s0), "+f"(s1)); TSRND(); },
         lop3<0xa8>(lop3<0xfe>(ne3(VL(0), VL(1), kt), ne3(VL(2), VL(3), kt), ne3(VL(4), VL(5), kt)),
                    lop3<0xfe>(ne3(VL(6), VL(7), kt), ne3(VL(8), VL(9), kt), ne3(VL(10), VL(11), kt)), 3), 11);
    const u32 y = movm(pk_bf(s0, s1));
    asm volatile("st.global.u32 [%0],%1;" ::"l"(dst), "r"(badd(x1w, bmul(gw, badd(hw, bmul(y, sg2))))) : "memory");
    if (b == 0 && lane == 0) str32(gs + G_EP, par);
    TS(30); TSE();
  }
  if (w == 10) asm volatile("cp.async.bulk.wait_group.read 0;" ::: "memory");
}

DEV u32 y_off(u32 tid, u32 b) { return G_Y + (16 * (tid >> 5) + 8 * ((tid >> 1) & 1) + ((tid >> 2) & 4)) * BLK + b * 128 + ((tid >> 2) & 3) * 32 + (tid & 1) * 16; }
DEV void post_conv(const Prm& p, const CUtensorMap* tm_down, const u32 tid, const u32 b) {
  const u32 w = tid >> 5, lane = tid & 31;
  const u32 g = lane >> 2, q = lane & 3, e = g >> 2, h = (g >> 1) & 1, hi = g & 1;
  const u32 pm = lds32(SM_THR + 4), par = pm >> 30;
  char* const gs = p.gs;
  const u32 cho = 128 * w + 64 * e + 16 * q;
  u32 x1[4][4], h2[4][4], key[4], lt;
  char* const rowp = gs + (b * BLK + (4 * h + 8 * hi) * 1152 + cho);
  u32 okl = ~0u;
  FA fa;
  uint4 A[24];
#define AROW(t) const u32 arow = 144 * ((t >> 5) & 3) + ((t >> 1) & 8) + (t & 7), ab = (t & 8) ? SM_UP : SM_GATE;
#define AFRAG9() { _Pragma("unroll") for (int s = 0; s < 9; s++) A[s] = ldsm4t(ab + SLV + arow * 16 + s * 256); }
#define AFRAG18() { const u32 t3 = opq(tid); AROW(t3); if (t3 < 256) { const u32 aa = ab + arow * 64 + ((((t3 >> 6) & 2) ^ ((t3 & 7) >> 1)) << 4); \
      _Pragma("unroll") for (int s = 0; s < 9; s++) { A[s] = ldsm4t(aa + s * 1024); A[9 + s] = ldsm4t((aa ^ 16) + s * 1024); } } else AFRAG9(); }
  if (w < 9) {
    const u32 yc = 8 * (q >> 1) + 2 * (g >> 1), y1 = w < 8 ? BLK : 4 * BLK, y2 = 2 * y1;
    const char* ysrc = gs + (w < 8 ? y_off(tid, b) : G_Y + (q & 1) * 16 + (8 * yc + 2 * hi + ((b >> 4) & 1)) * BLK + 16384 + ((b >> 5) * 16 + (b & 15)) * 32);
    const char* const ys[4] = {ysrc, ysrc + y1, ysrc + y2, ysrc + (y1 + y2)};
    u32 tc = clk();
    uint4 yv[4];
#pragma unroll
    for (int v = 0; v < 4; v++) yv[v].x = INVAL;
    if (AXW && w >= 4) { bsync(12, N12); tc = clk(); TS(18); }
    if (AXW ? b < (w < 4 ? YL : w < 8 ? YE : Y8) : w < 4 && b < YL) {
#pragma unroll
      for (int v = 0; v < 4; v++) yv[v] = ldr128(ys[v]);
    }
    if (!AXW && !W8P && w == 8) { bsync(7, 160); tc = clk(); }
    const u32 ma = SM_MODS + cho, xa = SM_XST + (2 * h + 4 * hi) * ROW + cho;
    const uint4 sa = lds128(ma), ca = lds128(ma + 1152), ga = lds128(ma + 2304);
    const uint4 rb = lds128((g & 2) ? SM_ONE + 16 * hi : (ma ^ 64) + 8064 + 1152 * hi);
    const u32 saw[4] = {sa.x, sa.y, sa.z, sa.w}, caw[4] = {ca.x, ca.y, ca.z, ca.w}, gaw[4] = {ga.x, ga.y, ga.z, ga.w};
#pragma unroll
    for (int k = 0; k < 4; k++) {
      const uint2 st = lds64(SM_ST + 16 * (2 * h + 4 * hi + (k & 1) + 8 * (k >> 1)));
      const uint4 xv = lds128(xa + ((k & 1) + 8 * (k >> 1)) * ROW);
      x1[k][0] = xv.x; x1[k][1] = xv.y; x1[k][2] = xv.z; x1[k][3] = xv.w;
#pragma unroll
      for (int v = 0; v < 4; v++) x1[k][v] = badd(x1[k][v], bfma(bmul(badd(x1[k][v], st.x), st.y), caw[v], saw[v]));
    }
    const bool own = (q >> 1) == e;
    const u32 spw = SM_SP + (2 * w + e) * 320 + (g & 3) * 16 + (own ? ((q & 1) == h ? 4 : 12) : 8 - 8 * (q & 1));
    if (!AXW && w >= 4) {
      if (W8P && w == 8) {
#pragma unroll
        for (int k = 0; k < 4; k++) pin(tid >> 16, x1[k][0], x1[k][1], x1[k][2], x1[k][3]);
        bsync(7, 160); tc = clk();
      }
      if (b < (w < 8 ? YE : Y8)) {
        if (W8D && w == 8 && b >= 64) wait_clk(tc, W8D);
        TS(18);
#pragma unroll
        for (int v = 0; v < 4; v++) yv[v] = ldr128(ys[v]);
      }
      bsync(12, N12);
      tc = clk();
    }
    if (b >= YL) wait_clk(tc, YD);
    TS(13);
    POLLW(_Pragma("unroll") for (int v = 0; v < 4; v++) if ((yv[v].x ^ pm) & TAGM) yv[v] = ldr128(ys[v]),
          ((yv[0].x ^ pm) | (yv[1].x ^ pm) | (yv[2].x ^ pm) | (yv[3].x ^ pm)) & TAGM, 5);
    TS(19);
    if (w < 4) asm volatile("setmaxnreg.dec.sync.aligned.u32 168;");
#pragma unroll
    for (int k = 0; k < 4; k += 2) {
      float X[4] = {}, Y[4] = {}, R[4] = {};
#pragma unroll
      for (int v = 0; v < 4; v++) {
        const u32 y0 = k ? yv[v].z : yv[v].x & ~TAGM, y1 = k ? yv[v].w : yv[v].y;
        x1[k][v] = bfma(movm(y0), gaw[v], x1[k][v]);
        x1[k + 1][v] = bfma(movm(y1), gaw[v], x1[k + 1][v]);
        mma8_bf(X, x1[k][v], x1[k + 1][v], x1[k][v]); mma8_bf(Y, x1[k][v], x1[k + 1][v], x1[k + 1][v]);
        if (v & 1) mma_bf(R, x1[k][v - 1], x1[k + 1][v - 1], x1[k][v], x1[k + 1][v], v & 2 ? rb.z : rb.x, v & 2 ? rb.w : rb.y);
      }
      sts32(spw + k * 64, fu(own ? (hi ? X[1] : X[0]) : R[0] + R[1]));
      sts32(spw + k * 64 + 64, fu(own ? (hi ? Y[3] : Y[2]) : R[2] + R[3]));
    }
    barrive(1, N1);
    TS(36);
    if (AFP) { asm volatile("setmaxnreg.inc.sync.aligned.u32 168;"); mb_wait(SM_MB + 8); mb_wait(SM_MB + 16); }
    const uint4 sb = lds128(ma + 3456), cb = lds128(ma + 4608), gb = lds128(ma + 5760);
    const u32 sbw[4] = {sb.x, sb.y, sb.z, sb.w}, cbw[4] = {cb.x, cb.y, cb.z, cb.w}, gbw[4] = {gb.x, gb.y, gb.z, gb.w};
    const u32 t3 = opq(tid), zr = t3 >> 16;
    AROW(t3);
    const u32 aa = ab + arow * 64 + ((((t3 >> 6) & 2) ^ ((t3 & 7) >> 1)) << 4), sta = SM_ST2 + 16 * (g & 3);
    if (AFP) pin(zr, aa, sta, xa);
    bsync(2, 320);
    TS(37);
    uint4 st[4];
#pragma unroll
    for (int k = 0; k < 4; k++) st[k] = lds128(sta + 64 * k);
    lt = lds32(SM_THR);
#define AFL() { _Pragma("unroll") for (int s = 0; s < 9; s++) { A[s] = ldsm4t(aa + s * 1024); A[9 + s] = ldsm4t((aa ^ 16) + s * 1024); } }
    if (AFP && (AFM >> w & 1)) { if (w < 8) AFL() else AFRAG9(); }
#pragma unroll
    for (int k = 0; k < 4; k++) {
      key[k] = st[k].w;
      u32 o[4];
#pragma unroll
      for (int v = 0; v < 4; v++) {
        const u32 d = badd(x1[k][v], st[k].x), z = bfma(d, st[k].y, bmul(d, st[k].z));
        h2[k][v] = FH ? bfma(z, cbw[v], sbw[v]) : badd(bmul(z, cbw[v]), sbw[v]);
        o[v] = FO ? bfma(gbw[v], h2[k][v], x1[k][v]) : badd(x1[k][v], bmul(gbw[v], h2[k][v]));
      }
      h2[k][0] = bmul(h2[k][0], B2M64) | TAGR;
      if (key[k] >= lt) str128(rowp + k * 1152, h2[k][0], h2[k][1], h2[k][2], h2[k][3]);
      sts128(xa + ((k & 1) + 8 * (k >> 1)) * ROW, o[0], o[1], o[2], o[3]);
    }
    barrive(3, 320);
    TS(21);
    if (!AFP) { asm volatile("setmaxnreg.inc.sync.aligned.u32 168;"); mb_wait(SM_MB + 8); mb_wait(SM_MB + 16); AFRAG18(); }
    else if (!(AFM >> w & 1)) { if (w < 8) AFL() else AFRAG9(); }
    TS(22);
    const u32 rr = tid * 57 >> 12, rc = tid * 16 - rr * 1152, sl = SM_SLOT + 8 * rr;
    const char* const rb_ = gs + rc;
    const u32 km = max(max(key[0], key[1]), max(key[2], key[3])), xd = SM_XS + rr * (2 * ROW) + rc;
    if (RW & 2) { pin(tid >> 16, sl, km, xd); pin2(tid >> 16, rb_, rowp); }
    fa = ffn_addr(p, tid | p.zero, b);
    bsync(6, 320);
    TS(24);
    const uint2 sk = lds64(sl);
    const char *r0 = rowa(rb_, sk.x), *r1 = rowa(rb_, sk.y);
    uint4 rv[2] = {ldr128(r0), ldr128(r1)};
    barrive(15, 320);
    const u32 g8 = lds32(SM_SLOT + 28);
    if (__any_sync(~0u, km >= g8 && lt > g8)) {
#pragma unroll
      for (int k = 0; k < 4; k++) if (key[k] >= g8 && key[k] < lt) str128(rowp + k * 1152, h2[k][0], h2[k][1], h2[k][2], h2[k][3]);
    }
    bsync(5, 320);
    const uint2 sf = lds64(sl);
    const u32 f8 = lds32(SM_SLOT + 28);
    if (__any_sync(~0u, km >= f8)) {
#pragma unroll
      for (int k = 0; k < 4; k++) if (key[k] >= f8) str128(rowp + (G_Y + k * 1152), bmul(x1[k][0], B2M64) | TAGR, x1[k][1], x1[k][2], x1[k][3]);
    }
    if (__any_sync(~0u, sf.x != sk.x || sf.y != sk.y)) {
      r0 = rowa(rb_, sf.x); r1 = rowa(rb_, sf.y);
      rv[0].x = rv[1].x = INVAL;
    }
    POLLW({ rld128<TAGM>(rv[0], r0, TAGR); rld128<TAGM>(rv[1], r1, TAGR); }, ne3(rv[0].x, rv[1].x, TAGR) & TAGM, 8);
    TS(38);
#pragma unroll
    for (int j = 0; j < 2; j++) sts128(xd + j * ROW, bmul(rv[j].x ^ TAGR, B2P64), rv[j].y, rv[j].z, rv[j].w);
  } else {
    u32 ok, lr;
    if (w == 10) {
      uint2 rc = lds64(SM_RC + 8 * min(lane, 17u));
      float r1 = lane < 18 ? uf(rc.x) : 0.f, r2 = lane < 18 ? uf(rc.y) : 0.f;
#pragma unroll 1
      for (int o = 16; o; o >>= 1) { r1 += __shfl_xor_sync(~0u, r1, o); r2 += __shfl_xor_sync(~0u, r2, o); }
      const u32 tl = 4 * ((lane >> 1) & 1) + ((lane >> 2) & 3) + 8 * (lane & 1), kl = (2047 - 16 * b - tl) << 2 | par * 3;
      char* const kp = gs + (G_KEY + b * KST);
      const u32 spr = SM_SP + (lane >> 4) * 9 * 320 + (lane & 15) * 16;
      TS(31);
      bsync(1, N1);
      float S1 = 0.f, S2 = 0.f, S3 = 0.f;
#pragma unroll
      for (int i = 0; i < 9; i++) { uint4 t = lds128(spr + i * 320); S1 += uf(t.x); S2 += uf(t.y); S3 += uf(t.z); }
      S1 += __shfl_xor_sync(~0u, S1, 16); S2 += __shfl_xor_sync(~0u, S2, 16); S3 += __shfl_xor_sync(~0u, S3, 16);
      const float mu = S1 * (1.f / 576.f), var = fmaxf(fmaf(-mu, mu, S2 * (1.f / 576.f)), 0.f);
      const float m = rbf(mu), rs = rcpf(rbf(sqrta(rbf(rbf(var) + 1e-5f))));
      const u32 rb = pk_bf(0.f, fmaf(fmaf(-m, r1, S3), rs, r2) + 0.f);
      ok = ((rb ^ (((int)rb >> 31) | 0x80000000)) & 0xffff0000u) | kl;
      const float rh = rbf(rs);
      sts32(SM_KEY + 4 * (lane & 15), ok);
      sts128(SM_ST2 + 16 * (lane & 15), pk_bf(-m, -m), pk_bf(rh, rh), pk_bf(rs - rh, rs - rh), ok);
      __syncwarp();
      const uint4 o0 = lds128(SM_KEY + 2 * (lane & 16)), o1 = lds128(SM_KEY + 2 * (lane & 16) + 16);
      lr = (o0.x > ok) + (o0.y > ok) + (o0.z > ok) + (o0.w > ok) + (o1.x > ok) + (o1.y > ok) + (o1.z > ok) + (o1.w > ok);
      lr += __shfl_xor_sync(~0u, lr, 16);
      if (lane < 16 && lr < 8) str32(kp + 4 * lr, ok);
      if (lr == (b < NB8 ? 7 : NEARLY - 1)) sts32(SM_THR, ok);
      barrive(2, 320);
      barrive(13, 64);
      TS(20);
    } else if (w == 9) {
      if (DB1) bsync(1, N1); else { bsync(12, N12); wait_clk(clk(), DD); }
      PROXY_FENCE();
      DOWN(1);
    } else {
      const char* ks = gs + (G_KEY + (lane >> 1) * KST + (lane & 1) * 16);
      const u32 kt = par * 3;
      uint4 L[8];
      u32 H[8];
#define KBAD(j) ((L[j].x ^ kt) & 3)
#define KLD(j) L[j] = ldr128(ks + j * 16 * KST)
#pragma unroll
      for (int j = 0; j < 8; j++) L[j].x = INVAL;
      bsync(13, 64);
      wait_clk(clk(), b < KE ? KD : b < KF ? KDB : b < YL ? KDC : KD1);
      TS(34);
      POLL({ _Pragma("unroll") for (int j = 0; j < 8; j++) if (KBAD(j)) KLD(j);
             merge4(H, L[0], L[1]); top8(H, L[2], L[3]);
             asm volatile("" : "+r"(H[0]), "+r"(H[1]), "+r"(H[2]), "+r"(H[3]), "+r"(H[4]), "+r"(H[5]), "+r"(H[6]), "+r"(H[7])); TS(32); },
           KBAD(0) | KBAD(1) | KBAD(2) | KBAD(3) | KBAD(4) | KBAD(5), 6);
      top8(H, L[4], L[5]);
      TS(35);
#pragma unroll 1
      for (u32 pass = p.zero;; pass++) {
        u32 G[8], m[8];
#pragma unroll
        for (int i = 0; i < 8; i++) G[i] = H[i];
#pragma unroll
        for (int r = 0; r < 8; r++) {
          const u32 h0 = G[0];
          m[r] = __reduce_max_sync(~0u, h0);
          if (r == 0) { if (KBAD(6)) KLD(6); if (KBAD(7)) KLD(7); }
          if (r < 7) asm("{.reg .u32 t; sub.u32 t,%1,%2; min.u32 t,t,1; mad.lo.u32 %0,t,%3,%4;}" : "=r"(G[0]) : "r"(m[r]), "r"(h0), "r"(h0 - G[1]), "r"(G[1]));
#pragma unroll
          for (int i = 1; i < 7 - r; i++) G[i] = h0 == m[r] ? G[i + 1] : G[i];
          if ((r & 3) == 3) sts128(SM_SLOT + 4 * r - 12, m[r - 3], m[r - 2], m[r - 1], m[r]);
        }
        asm volatile("{.reg .pred p; setp.eq.u32 p,%0,0; @p bar.arrive 6,320;}" ::"r"(pass) : "memory");
        if (pass) break;
        TS(23);
        POLLW({ if (KBAD(6)) KLD(6); if (KBAD(7)) KLD(7); }, KBAD(6) | KBAD(7), 7);
        if (!__any_sync(~0u, max(L[6].x, L[7].x) > m[7])) break;
        top8(H, L[6], L[7]);
      }
      barrive(5, 320);
      TS(33);
    }
    asm volatile("setmaxnreg.inc.sync.aligned.u32 168;");
    mb_wait(SM_MB + 8); mb_wait(SM_MB + 16);
    AROW(tid);
    AFRAG9();
    fa = ffn_addr(p, tid | p.zero, b);
    TS(22);
    if (w == 10) {
      bsync(3, 320);
      PROXY_FENCE();
      if (lane < 16 && lr >= 8) OUTR();
      if (lane < 16 && lr < 8) okl = ok;
    } else if (w == 9) {
      bsync(15, 320);
      DOWN(4);
      TS(13);
    }
  }
  ffn_tail(p, tm_down, A, fa, b, par, okl);
}

__global__ void __launch_bounds__(384, 1)
fused_kernel(const Prm p, const __grid_constant__ CUtensorMap tm_mod, const __grid_constant__ CUtensorMap tm_gate, const __grid_constant__ CUtensorMap tm_gs,
             const __grid_constant__ CUtensorMap tm_up, const __grid_constant__ CUtensorMap tm_us, const __grid_constant__ CUtensorMap tm_down) {
  extern __shared__ __align__(1024) unsigned char smem[];
  u32 la, ai, ldt; uint2 cr, ci;
  {
    const u32 t = threadIdx.x, d = t < 256 ? chan(blockIdx.x, t >> 5) : 512 + (blockIdx.x >> 1), o = d * 256 + 8 * (t & 31), o4 = o + ((t < 256 ? t >> 5 : t >> 3) & 4);
    asm volatile("{.reg .pred p; .reg .u16 h; setp.ne.u32 p,%7,0; @p ld.global.nc.u32 %0,[%8]; @p ld.global.nc.u32 %1,[%9]; @p ld.global.nc.v2.u32 {%2,%3},[%10];"
                 "@p ld.global.nc.v2.u32 {%4,%5},[%11]; @p ld.global.nc.u16 h,[%12]; cvt.u32.u16 %6,h;}"
                 : "=r"(la), "=r"(ai), "=r"(cr.x), "=r"(cr.y), "=r"(ci.x), "=r"(ci.y), "=r"(ldt)
                 : "r"(0x6ffu >> (t >> 5) & 1), "l"(p.la + o4), "l"(p.ai + o4), "l"(p.cr + o), "l"(p.ci + o), "l"(p.ldt + 2 * d));
  }
  const u32 t0 = clk();
  const u32 tid = __shfl_sync(~0u, threadIdx.x, threadIdx.x & 31), b = blockIdx.x + p.zero;
  const u32 w = tid >> 5, lane = tid & 31;
  const u32 g = lane >> 2, q = lane & 3, hi = g & 1;
  const u32 rho = b & 1, Ps = 512 + (b >> 1);
  char* const gs = p.gs;
  TS0();
  const bool kw = w != 8 && w != 11;
  const u32 ksig = w < 8 ? (w & 3) : 4, khf = w < 8 ? (w >> 2) : (w & 1);
  if (!kw) {
    if (tid == 352) {
#pragma unroll
      for (int i = 0; i < 5; i++) mb_init(SM_MB + 8 * i, i < 4 ? 1 : 64);
      asm volatile("fence.mbarrier_init.release.cluster;" ::: "memory");
      tm_pre(&tm_mod);
    }
    const char* cp = p.c + (576 * (w & 1) + 24 * min(lane, 23u));
    const uint2 c0 = ldg64(cp);
    la = c0.x; ai = c0.y; cr = ldg64(cp + 8); ci = ldg64(cp + 16);
  }
  const u32 zr = tid >> 16;
  const u32 epv = ldr32(gs + (G_EP + zr));
  const u32 tp = SM_TAP + ksig * TAPS;
  if (kw && !khf) {
#pragma unroll 1
    for (u32 i = lane * 16; i < TAPS; i += 512) sts128(tp + i, 0, 0, 0, 0);
  }
  if (tid < 128) sts128(SM_INV + 16 * tid, INVAL, 0, 1, 0);
  if (tid >= 252) str128(gs + (tid >= 380 ? G_MOD + b * 128 + q * 16 : b * BLK + 16384 - 252 * 16 + tid * 16), INVAL, 0, 1, 0);
  if (tid == 352 && b < 36) { while (clk() - t0 < DMOD); mb_expect(SM_MB, 36864); tma3d(SM_UP, &tm_mod, SM_MB, 32 * b, 0); }
  if (w < 9) {
    while ((int)(clk() - t0) < DX);
    const char* xp = p.x + (b * BLK + (lane >> 3) * 1152 + 128 * w + 16 * (lane & 7));
    const u32 xd = SM_XST + (((lane >> 3) & 1) + 8 * (lane >> 4)) * ROW + 128 * w + 16 * (lane & 7);
#pragma unroll
    for (int i = 0; i < 4; i++) cpa16(xd + 2 * ROW * i, xp + 4608 * i);
  }
  const u32 ktab = w < 8 ? SM_MODS + w * KTAB : SM_ZS + (w - 9) * KTAB;
  float k2048 = 0.f;
  if (kw) {
    u32 mx = __vmaxu2(__vmaxu2(cr.x & 0x7fff7fff, cr.y & 0x7fff7fff), __vmaxu2(ci.x & 0x7fff7fff, ci.y & 0x7fff7fff));
    const u32 E = max(__reduce_max_sync(~0u, max(mx & 0xffff, mx >> 16)) >> 7, 8u);
    TS(1);
    const float dt = rbf(ex2(blo(ldt) * LOG2E)), csc = uf((257 - E) << 23 | (fu(dt) & 0x7fffff));
    sts32(SM_SC + 16 * ksig + 12, fu(uf(fu(dt) & 0x7f800000) * uf((E - 2) << 23)));
    const u32 crw = khf ? cr.y : cr.x, ciw = khf ? ci.y : ci.x;
    float2 C[2], w4[2], w8[2], w16[2], w32[2], w64[2], w128[2], w256[2], w512[2], a1[2], a2[2], a3[2], t0[2], t1[2], s3[2];
#pragma unroll
    for (int m = 0; m < 2; m++) {
      const float lr2 = rbf(ex2((m ? bhi(la) : blo(la)) * LOG2E)) * dt * -LOG2E, th = (m ? bhi(ai) : blo(ai)) * dt;
      C[m] = make_float2((m ? bhi(crw) : blo(crw)) * csc, (m ? bhi(ciw) : blo(ciw)) * csc);
      const float2 w1 = cexp(lr2, th), w2 = csq(w1);
      w64[m] = cexp(64.f * lr2, 64.f * th);
      w4[m] = csq(w2); w8[m] = csq(w4[m]); w16[m] = csq(w8[m]); w32[m] = csq(w16[m]);
      w128[m] = csq(w64[m]); w256[m] = csq(w128[m]); w512[m] = csq(w256[m]);
      const float2 w1024 = csq(w512[m]);
      a1[m] = cmul(C[m], w1); a2[m] = cmul(C[m], w2); a3[m] = cmul(a1[m], w2);
      t0[m] = cmul(C[m], w1024); t1[m] = cmul(t0[m], w128[m]); s3[m] = cmul(w8[m], w16[m]);
      k2048 += fmaf(t0[m].x, w1024.x, -t0[m].y * w1024.y);
    }
    C2 B0[8], B1[8], B2[8], S[8];
    B0[0] = pk2(C); B0[1] = pk2(a1); B0[2] = pk2(a2); B0[3] = pk2(a3);
    const C2 h4 = pk2(w4), h256 = pk2(w256), h512 = pk2(w512);
#pragma unroll
    for (int i = 0; i < 4; i++) B0[4 + i] = cm2(B0[i], h4);
#pragma unroll
    for (int i = 0; i < 4; i++) B1[i] = cm2(B0[2 * i], h256);
    B1[4] = cm2(B0[0], h512); B1[5] = cm2(B0[4], h512);
    B1[6] = cm2(B1[4], h256); B1[7] = cm2(B1[5], h256);
    const u32 ta = ktab + lane * 128, f = ((lane & 3) << 5) | ((lane & 4) << 2);
#pragma unroll
    for (int i = 0; i < 8; i++) sts128(ta + ((i << 4) ^ f), B0[i].re, B0[i].im, B1[i].re, B1[i].im);
    B2[0] = pk2(t0); B2[1] = pk2(t1);
    B2[2] = cm2(B2[0], h256); B2[3] = cm2(B2[1], h256);
#pragma unroll
    for (int i = 0; i < 4; i++) B2[4 + i] = cm2(B2[i], h512);
    S[0] = {0x3C003C00u, 0u}; S[1] = pk2c(w8); S[2] = pk2c(w16); S[3] = pk2c(s3); S[4] = pk2c(w32);
#pragma unroll
    for (int i = 1; i < 4; i++) S[4 + i] = cm2(S[i], S[4]);
#pragma unroll
    for (int i = 0; i < 8; i++) sts128(ta + 4096 + ((i << 4) ^ f), B2[i].re, B2[i].im, S[i].re, S[i].im);
    const C2 m64 = pk2c(w64), m128 = pk2c(w128);
    sts128(ktab + 8192 + lane * 16, m64.re, m64.im, m128.re, m128.im);
    __syncwarp();
  } else {
    u32 sa = SM_SIL + 576 * (w & 1) + 24 * min(lane, 23u);
#pragma unroll 1
    for (int j = 0; j < 6; j++) {
      sts32(sa, pk_bf(silu_f(blo(la)), silu_f(bhi(la))));
      la = ai; ai = cr.x; cr.x = cr.y; cr.y = ci.x; ci.x = ci.y; sa += 4;
    }
    bsync(7, 64);
  }
  TS(2);
  const u32 pm = (__reduce_or_sync(~0u, epv) & 1) ? 0 : TAGM;
  sts32(SM_THR + 4, pm);
  if (w < 9) {
    asm volatile("cp.async.wait_all;" ::: "memory");
    __syncwarp();
    TS(4);
    if (tid == 256 && b >= 36 && b < 108) { mb_expect(SM_MB, 36864); tma3d(SM_UP, &tm_mod, SM_MB, 32 * b, 0); }
    const u32 xa = SM_XST + (lane & 15) * ROW + 128 * w + 16 * (lane >> 4);
    float s[4] = {}, X[2][4] = {}, Y[2][4] = {};
#pragma unroll
    for (int j = 0; j < 4; j++) {
      const uint4 a = ldsm4(xa + 32 * j);
      mma8_bf(X[0], a.x, a.y, a.x); mma8_bf(Y[0], a.x, a.y, a.y);
      mma8_bf(X[1], a.z, a.w, a.z); mma8_bf(Y[1], a.z, a.w, a.w);
      mma_bf(s, a.x, a.y, a.z, a.w, BONE, BONE);
    }
    uint4 t[4];
#pragma unroll
    for (int j = 0; j < 4; j++) t[j] = ldsm4t(xa + 32 * j);
    const float u0 = hi ? X[0][1] + X[1][1] : X[0][0] + X[1][0], u1 = hi ? Y[0][3] + Y[1][3] : Y[0][2] + Y[1][2];
    if (q == g >> 1) sts128(SM_SP + w * 128 + g * 16, fu(s[0]), fu(u0), fu(s[2]), fu(u1));
    bsync(1, 288);
    TS(7);
    const u32 spr = SM_SP + (lane & 7) * 16 + (lane & 8);
    const uint2 t8 = lds64(spr + 1024);
    const float f8 = lane < 16 ? 1.f : 0.f;
    float S1 = uf(t8.x) * f8, S2 = uf(t8.y) * f8;
#pragma unroll
    for (int i = 0; i < 4; i++) { const uint2 u = lds64(spr + (lane & 16) * 32 + i * 128); S1 += uf(u.x); S2 += uf(u.y); }
    S1 += __shfl_xor_sync(~0u, S1, 16); S2 += __shfl_xor_sync(~0u, S2, 16);
    const float mu = S1 * (1.f / 576.f), var = fmaxf(fmaf(-mu, mu, S2 * (1.f / 576.f)), 0.f);
    const float m = rbf(mu), rs = rcpf(rbf(sqrta(rbf(rbf(var) + 1e-5f))));
    const float ra = rs * 0.0625f;
    sts64(SM_AF + w * 128 + (lane & 15) * 8, fu(ra), fu(-m * ra));
    __syncwarp();
    TS(55);
    const uint4 f0 = lds128(SM_AF + w * 128 + q * 16), f1 = lds128(SM_AF + w * 128 + 64 + q * 16);
    const u32 zdst = SM_GATE + w * 2048 + (g >> 1) * 128 + (lane & 15) * 8;
    const u32 pz = (q & 1) ? 0 : pm;
#pragma unroll
    for (int j = 0; j < 8; j++) {
      const u32 x0 = j & 1 ? t[j >> 1].z : t[j >> 1].x, x1 = j & 1 ? t[j >> 1].w : t[j >> 1].y;
      sts64((j & 1 ? zdst ^ 64 : zdst) + 512 * (j >> 1), pk_hf(fmaf(blo(x0), uf(f0.x), uf(f0.y)), fmaf(bhi(x0), uf(f0.z), uf(f0.w))) | pz,
            pk_hf(fmaf(blo(x1), uf(f1.x), uf(f1.y)), fmaf(bhi(x1), uf(f1.z), uf(f1.w))));
    }
    TS(53);
    if (w < 8) barrive(15, 288);
    else {
      bsync(15, 288);
      TS(54);
      if (lane == 0) {
        PROXY_FENCE();
        bulk_out<BLK>(gs + b * BLK, SM_GATE);
        asm volatile("cp.async.bulk.commit_group;" ::: "memory");
        if (PFG & 1) l2_pre<WSH / 2>(p.wg + b * WSH);
      }
      const float rh = rbf(rs);
      sts128(SM_ST + 16 * (lane & 15), pk_bf(-m, -m), pk_bf(rh, rh), pk_bf(rs - rh, rs - rh), 0);
    }
    TS(5);
  }
  if (kw) {
    float D[5][4] = {};
    u32 ta = ktab + q * 128 + ((g ^ (q << 1)) << 4), tm = ktab + 8192 + q * 16;
#pragma unroll 2
    for (int s = 0; s < 8; s++) {
      const uint4 ca = lds128(ta), cb = lds128(ta + 4096), ma = lds128(tm);
      ta = (ta + 512) ^ 16; tm += 64;
      k2048 += __shfl_xor_sync(~0u, k2048, 16 >> s);
      const C2 s0 = {cb.z, cb.w}, s1 = cm2(s0, {ma.x, ma.y}), s2 = cm2(s0, {ma.z, ma.w}), s3 = cm2(s1, {ma.z, ma.w});
      mma_hf(D[0], s0.re, s1.re, s0.im, s1.im, ca.x, ca.y);
      mma_hf(D[2], s0.re, s1.re, s0.im, s1.im, ca.z, ca.w);
      mma_hf(D[4], s0.re, s1.re, s0.im, s1.im, cb.x, cb.y);
      mma_hf(D[1], s2.re, s3.re, s2.im, s3.im, ca.x, ca.y);
      mma_hf(D[3], s2.re, s3.re, s2.im, s3.im, ca.z, ca.w);
    }
    TS(3);
    const u32 xa = (w < 8 ? SM_MODS + (4 + ksig) * KTAB : SM_ZS) + lane * 16;
    if (khf) {
      __syncwarp();
#pragma unroll
      for (int j = 0; j < 5; j++) sts128(xa + 512 * j, fu(D[j][0]), fu(D[j][1]), fu(D[j][2]), fu(D[j][3]));
      if (lane == 0) sts32(xa + 2560, fu(k2048));
      asm volatile("bar.arrive %0,64;" ::"r"(2 + ksig) : "memory");
    } else {
      const u32 t1 = tp + (q < 2 ? (128 + 4 * g + 2 * q) * 4 : T3 * 4 + ((32 * q - 64 + g) ^ 1) * 2);
      const u32 x = 16 * q + (g >> 1) + hi + 1, tb = tp + (hi ? T7E : T9E) * 4 - 4;
      const u32 te = tb + (x + 2 * (x & 1)) * 2, to = tb + TEO * 4 + (x ^ 1) * 2;
      asm volatile("bar.sync %0,64;" ::"r"(2 + ksig) : "memory");
#pragma unroll
      for (int j = 0; j < 5; j++) { const uint4 t = lds128(xa + 512 * j); D[j][0] += uf(t.x); D[j][1] += uf(t.y); D[j][2] += uf(t.z); D[j][3] += uf(t.w); }
      k2048 = (k2048 + uf(lds32(xa + 2560))) * 0.125f;
#pragma unroll
      for (int r = 0; r < 4; r++) {
        const u32 v = pk_hf(D[2 + (r >> 1)][2 * (r & 1)], D[2 + (r >> 1)][2 * (r & 1) + 1]);
        if (q < 2) {
          const u32 vv = __byte_perm(v, v, 0x1010);
          sts32(t1 + (TO + 32 * r) * 4, vv); sts16(t1 + (TO + 32 * r + 1) * 4 + 2, v >> 16); sts16(t1 + (TO + 32 * r - 1) * 4, v);
          sts64(t1 + (TE + 32 * r) * 4, vv, __byte_perm(v, v, 0x1032));
        } else {
          sts16(t1 + 16 * r, v >> 16);
          if (r == 0 && lane == 2) {
            const u32 vv = __byte_perm(v, v, 0x1010);
            sts32(tp + (TO + 256) * 4, vv); sts16(tp + (TO + 257) * 4 + 2, v); sts16(tp + (TO + 255) * 4, v); sts64(tp + (TE + 256) * 4, vv, vv);
          } else sts16(t1 + 16 * r - ((T3 - T5) * 4 + 6) + 8 * hi, v);
        }
      }
#pragma unroll
      for (int r = 0; r < 2; r++) {
        const u32 v = pk_hf(D[4][2 * r], D[4][2 * r + 1]);
        if (r == 0 && lane == 0) { sts16(tp + T5 * 4 + 62 * 2, v); sts32(SM_KV + 4 * ksig, v & 0xffff); sts16(tp + (T9E + TEO) * 4 + 62 * 2, pk_hf(k2048, 0.f)); }
        else { sts16(te + 8 * r, v); sts16(to + 8 * r, v); }
        sts16(te + 8 * r + 16, v >> 16); sts16(to + 8 * r + 16, v >> 16);
      }
      __syncwarp();
#pragma unroll
      for (int r = 0; r < 4; r++) {
        const u32 v = pk_hf(D[r >> 1][2 * (r & 1) + 1], D[r >> 1][2 * (r & 1)]), t2 = tp + lane * 4 + 128 * r;
        sts32(t2 + TO * 4, v); sts16(t2 + TE * 4, v >> 16); sts16(t2 + (TE + 1) * 4 + 2, v);
      }
      __syncwarp();
    }
  } else if (w == 11 && b < 108) {
    float c[4][4] = {};
    u32 aa = SM_UP + ((lane & 7) + 8 * (lane >> 4)) * 64 + ((((lane >> 3) & 1) ^ ((lane & 7) >> 1)) << 4);
    u32 ba = SM_SIL + (lane >> 3) * 16;
    uint4 a[2][10];
#define GLD(n) { _Pragma("unroll") for (int i = 0; i < 2; i++) { a[n][5 * i] = ldsm4(ba + i * 64); \
      _Pragma("unroll") for (int k = 0; k < 4; k++) a[n][5 * i + 1 + k] = ldsm4t((k & 2 ? aa ^ 32 : aa) + i * 2048 + (k & 1) * 1024); } aa += 4096; ba += 128; }
#define GMM(n) { _Pragma("unroll") for (int i = 0; i < 2; i++) _Pragma("unroll") for (int k = 0; k < 4; k++) { const uint4 f = a[n][5 * i + 1 + k], bb = a[n][5 * i]; \
      mma_bf(c[k], f.x, f.y, f.z, f.w, k & 1 ? bb.z : bb.x, k & 1 ? bb.w : bb.y); } }
    mb_wait(SM_MB);
    TS(56);
    GLD(0);
#pragma unroll 1
    for (int s = 0; s < 4; s++) { GLD(1); GMM(0); GLD(0); GMM(1); }
    GMM(0);
    const float v0 = (q & 1) ? c[0][2] + c[1][2] : c[0][0] + c[1][0], v1 = (q & 1) ? c[2][2] + c[3][2] : c[2][0] + c[3][0];
    str16(gs + (G_MOD + b * 128 + 2 * g + 16 * q), pk_bf(rbf((q & 2) ? v1 : v0) * F2M64, 0.f) | (g < 2 ? pm : 0));
    TS(57);
  }
  TS(6);
  u32 tid2 = tid;
  if (w < 4) {
    asm volatile("setmaxnreg.inc.sync.aligned.u32 232;");
    const u32 tid = tid2 + p.zero, w = tid >> 5, lane = tid & 31, g = lane >> 2, q = lane & 3, hi = g & 1, zr = tid >> 16, tp = SM_TAP + w * TAPS;
    const u32 pml = opq((g & 3) ? 0 : pm);
    const u32 tr = tp + ((hi ? TO : TE) + (g >> 1) - q) * 4;
    u32 T[33][4], B5[5][2], B3[5][2];
#pragma unroll
    for (int d = 0; d < 33; d++) {
      T[d][0] = lds32(tr + 32 * d); T[d][1] = lds32(tr + 32 * d + 16);
      T[d][2] = cpy(d ? T[d - 1][1] : zr, zr, 0); T[d][3] = cpy(T[d][0], zr, 1);
    }
    const u32 t33 = cpy(T[32][1], zr, 0), z33 = cpy(zr, zr, 1);
    if (TPIN) {
#pragma unroll
      for (int d = 0; d < 33; d++) asm volatile("{.reg .pred p; setp.ne.u32 p,%2,0; @p st.shared.v2.u32 [%2],{%0,%1};}" ::"r"(T[d][2]), "r"(T[d][3]), "r"(zr) : "memory");
    }
    const u32 bt = tp + (T5 + g - q) * 4;
#pragma unroll
    for (int d = 0; d < 5; d++) {
      B5[d][0] = lds32(bt + 32 * d); B5[d][1] = lds32(bt + 32 * d - 16);
      B3[d][0] = lds32(bt + 32 * d + (T3 - T5) * 4); B3[d][1] = lds32(bt + 32 * d - 16 + (T3 - T5) * 4);
    }
    u32 za = opq(SM_ZS + 16 + w * ZSS + ((lane >> 3) & 1) * ZPS + ((lane & 7) + (lane >> 4)) * 16);
    u32 wa = opq(SM_W + W5O + w * WSL + row16(lane));
    u32 sa = opq(SM_W + W9O - 2048 + w * WSL + lane * 16);
    u32 yo = opq(G_Y + b * BLK + 256 * q + w * 32 + 4 * g);
    const u32 fa = opq(SM_SC + 16 * w + 8), bw = opq((BW >> 4 * w) & 15), bs = opq((BS >> 4 * w) & 15);
    if (TPIN) asm volatile("{.reg .pred p; setp.ne.u32 p,%8,0; @p st.shared.v4.u32 [%8],{%0,%1,%2,%3}; @p st.shared.v4.u32 [%8],{%4,%5,%6,%7};}"
                           ::"r"(za), "r"(wa), "r"(sa), "r"(yo), "r"(fa), "r"(bw), "r"(bs), "r"(pml), "r"(zr) : "memory");
    TS(8);
    bsync(9, 384);
    TS(11);
    float A[4][4] = {};
    uint4 Z[4];
    Z[0] = ldsm4(za); Z[1] = ldsm4(za + 32);
    const uint2 fc = lds64(fa);
    const u32 F = __byte_perm(fu(uf(fc.x) * uf(fc.y)), 0, 0x3232);
#define STEP(s, b0, b1) { _Pragma("unroll") for (int i = 0; i < 4; i++) mma_hf_t(A[i], T[8 * i + 7 - (s)], b0, b1); }
#define PAIR(n) { Z[(n + 2) & 3] = ldsm4(za + 32 * (n + 2)); STEP(2 * n, Z[n].x, Z[n].y); STEP(2 * n + 1, Z[n].z, Z[n].w); }
#define LAST(N) mma8_hf(N, t33, z33, Z[3].y); float O[4]; mma_hf_o(O, A[0], T[0], Z[3].z, Z[3].w); \
    _Pragma("unroll") for (int i = 0; i < 3; i++) mma_hf_o(A[i], A[i + 1], T[8 * i + 8], Z[3].z, Z[3].w); \
    mma_hf_o(A[3], N, T[32], Z[3].z, Z[3].w);
#pragma unroll 1
    for (int j = 0; j < 4; j++) {
      PAIR(0); PAIR(1); PAIR(2);
      Z[1] = ldsm4(za + 160); STEP(6, Z[3].x, Z[3].y);
      float N[4] = {};
      LAST(N);
      if (INCV) inc<128>(za);
      y_store<128>(O[0], O[1], O[2], O[3], F, pml, gs + yo);
      if (!INCV) za += 128;
      yo += 1024;
      TSJ(j);
    }
    bsyncr(bw);
    uint4 a5;
    if (A5P) a5 = ldsm4t(wa);
#pragma unroll 1
    for (int j = 4; j < 13; j++) {
      if (j == 8) bsyncr(bs);
      if (!A5P) a5 = ldsm4t(wa);
      const uint4 a3 = ldsm4t(wa + (W3O - W5O));
      uint4 s3 = {0, 0, 0, 0};
      if (j >= 8) s3 = lds128(sa);
      PAIR(0);
      float N[4] = {};
#pragma unroll
      for (int i = 0; i < 4; i++) mma_hf(A[i], a5.x, a5.y, a5.z, a5.w, B5[i][0], B5[i][1]);
      mma_hf(N, a5.x, a5.y, a5.z, a5.w, B5[4][0], B5[4][1]);
      if (INCV) asm volatile("{add.u32 %0,%0,256; xor.b32 %0,%0,32;}" : "+r"(wa)); else wa = (wa + 256) ^ 32;
      if (A5P) a5 = ldsm4t(wa);
      PAIR(1);
#pragma unroll
      for (int i = 0; i < 4; i++) mma_hf(A[i], a3.x, a3.y, a3.z, a3.w, B3[i][0], B3[i][1]);
      mma_hf(N, a3.x, a3.y, a3.z, a3.w, B3[4][0], B3[4][1]);
      PAIR(2);
      Z[1] = ldsm4(za + 160); STEP(6, Z[3].x, Z[3].y);
      LAST(N);
      if (INCV) { inc<128>(za); inc<512>(sa); }
      y_store<128>(O[0] + uf(s3.x), O[1] + uf(s3.y), O[2] + uf(s3.z), O[3] + uf(s3.w), F, pml, gs + yo);
      if (!INCV) { za += 128; sa += 512; }
      yo += 1024;
      TSJ(j);
    }
    {
      asm volatile("mov.u32 %0,%%tid.x;" : "=r"(tid2));
      const uint4 s3 = lds128(sa), s4 = lds128(sa + 512), s5 = lds128(sa + 1024);
      float X[3][4] = {{uf(s4.x), uf(s4.y), uf(s4.z), uf(s4.w)}, {}, {uf(s5.x), uf(s5.y), uf(s5.z), uf(s5.w)}};
#pragma unroll
      for (int ty = 0; ty < 2; ty++) {
        const uint4 a = A5P && !ty ? a5 : ldsm4t(wa + ty * (W3O - W5O)), c = ldsm4t((wa ^ 32) + 256 + ty * (W3O - W5O)), d = ldsm4t(wa + 512 + ty * (W3O - W5O));
#pragma unroll
        for (int i = 0; i < 3; i++) mma_hf(A[i], a.x, a.y, a.z, a.w, ty ? B3[i][0] : B5[i][0], ty ? B3[i][1] : B5[i][1]);
#pragma unroll
        for (int i = 0; i < 2; i++) mma_hf(X[i], c.x, c.y, c.z, c.w, ty ? B3[i][0] : B5[i][0], ty ? B3[i][1] : B5[i][1]);
        mma_hf(X[2], d.x, d.y, d.z, d.w, ty ? B3[0][0] : B5[0][0], ty ? B3[0][1] : B5[0][1]);
      }
#pragma unroll
      for (int n = 0; n < 4; n++) {
        const uint4 f0 = n < 2 ? Z[n] : ldsm4(za + 32 * n), f1 = ldsm4(za + 32 * n + 128), f2 = ldsm4(za + 32 * n + 256);
#pragma unroll
        for (int s = 2 * n; s < 2 * n + 2; s++) {
#pragma unroll
          for (int i = 0; i < 3; i++) mma_hf_t(A[i], T[8 * i + 7 - s], s & 1 ? f0.z : f0.x, s & 1 ? f0.w : f0.y);
          mma_hf_t(X[0], T[7 - s], s & 1 ? f1.z : f1.x, s & 1 ? f1.w : f1.y); mma_hf_t(X[1], T[15 - s], s & 1 ? f1.z : f1.x, s & 1 ? f1.w : f1.y);
          mma_hf_t(X[2], T[7 - s], s & 1 ? f2.z : f2.x, s & 1 ? f2.w : f2.y);
        }
      }
      y_store<128>(A[0][0] + uf(s3.x), A[0][1] + uf(s3.y), A[0][2] + uf(s3.z), A[0][3] + uf(s3.w), F, pml, gs + yo);
      y_store<128>(A[1][0] + X[0][0], A[1][1] + X[0][1], A[1][2] + X[0][2], A[1][3] + X[0][3], F, pml, gs + yo + 1024);
      y_store<128>(A[2][0] + X[1][0] + X[2][0], A[2][1] + X[1][1] + X[2][1], A[2][2] + X[1][2] + X[2][2], A[2][3] + X[1][3] + X[2][3], F, pml, gs + yo + 2048);
    }
    barrive(12, N12);
    TS(15);
  } else {
    asm volatile("setmaxnreg.dec.sync.aligned.u32 136;");
    const u32 t8 = tid - 128, pml = (g & 3) ? 0 : pm;
    {
      TS(12);
      if (PFG == 1 && tid == 288) l2_pre<WSH / 2>(p.wg + (b * WSH + WSH / 2));
      const char* zs = gs + ((16 * w - 64 + (lane >> 3)) * BLK + b * 128 + ((lane & 7) * 16 ^ rho * 64));
      const char* zs4 = gs + ((t8 >> 1) * BLK + (Ps >> 4) * 512 + (Ps & 6) * 64 + ((Ps >> 2 ^ Ps) & 2) * 32 + (Ps & 1) * 32 + (t8 & 1) * 16);
      uint4 v[5];
      v[4].x = INVAL;
      if (ZD) wait_clk(t0, ZD);
      if (w == 9) {
        const u32 d = lane < 4 ? chan(b, lane) : Ps;
        const char* mp = gs + (G_MOD + (d >> 5) * 128 + (d & 24) * 2);
        uint4 ta, tc;
        POLL({ ta = ldr128(mp); tc = ldr128(mp + MODJ); v[4] = ldr128(zs4); }, ((ta.x ^ pm) | (tc.x ^ pm)) & TAGM, 2);
        const u32 aw = (d & 4) ? ((d & 2) ? ta.w : ta.z) : ((d & 2) ? ta.y : ta.x & ~TAGM);
        const u32 cw = (d & 4) ? ((d & 2) ? tc.w : tc.z) : ((d & 2) ? tc.y : tc.x & ~TAGM);
        const float sa = ((d & 1) ? bhi(aw) : blo(aw)) * F2P64, c1 = rbf(fmaf((d & 1) ? bhi(cw) : blo(cw), F2P64, 1.f));
        const u32 EM = min(max(fu(fmaxf(32.f * fabsf(c1), fabsf(sa))) >> 23, 80u), 250u);
        const float inv = uf((264 - EM) << 23);
        if (lane < 5) { sts64(SM_SC + 16 * lane, pk_hf(16.f * c1 * inv, 16.f * c1 * inv), pk_hf(sa * inv, sa * inv)); sts32(SM_SC + 16 * lane + 8, (EM - 74) << 23); }
        TS(10);
      }
      POLLW(v[4] = ldr128(zs4), (v[4].x ^ pm) & TAGM, 1);
      TS(58);
#pragma unroll
      for (int j = 0; j < 4; j++) v[j] = ldr128(zs + j * 4 * BLK);
#define MARKERS() if (tid == 256) { \
        bulk_out<2048>(gs + (G_Y + 16384 + b * BLK), SM_INV); \
        _Pragma("unroll") for (int i = MT / 2; i < 8; i++) bulk_out<2048>(gs + (G_Y + 2048 * i + b * BLK), SM_INV); \
        bulk_out<2048>(gs + (G_PART + b * 2048), SM_INV); bulk_out<512>(gs + (G_ACT + b * 512), SM_INV); \
        bulk_out<32>(gs + (G_KEY + b * KST), SM_INV); if (!rho) bulk_out<128>(gs + (G_ACT + Ps * 128), SM_INV); \
        asm volatile("cp.async.bulk.commit_group;" ::: "memory"); }
#define GATE() { mb_expect(SM_MB + 8, rho ? SLV : 46080); \
        _Pragma("unroll") for (int i = GE; i < 3; i++) tma3d(SM_GATE + 12288 * i, &tm_gate, SM_MB + 8, 32 * b, i); \
        if (!rho) tma3d(SM_GATE + SLV, &tm_gs, SM_MB + 8, 4096 + 4 * b, 0); }
#define UP() { mb_expect(SM_MB + 16, rho ? SLV : 46080); tma3d(SM_UP, &tm_up, SM_MB + 16, 32 * b, 0); \
        if (!rho) tma3d(SM_UP + SLV, &tm_us, SM_MB + 16, 4096 + 4 * b, 0); }
      if (PFU == 2 && tid == 256) l2_pre<WSH>(p.wu + b * WSH);
      if (GE && tid == 256) {
        asm volatile("cp.async.bulk.wait_group.read 0;" ::: "memory");
#pragma unroll
        for (int i = 0; i < GE; i++) tma3d(SM_GATE + 12288 * i, &tm_gate, SM_MB + 8, 32 * b, i);
      }
      if (MKT == 0) MARKERS();
      if (PFG == 2 && tid == 256) l2_pre<WSH>(p.wg + b * WSH);
      if (PFG == 3 && tid == 256) l2_pre<WSH / 2>(p.wg + (b * WSH + WSH / 2));
      bsync(8, 256);
      const uint2 cc = lds64(SM_SC + 8 * (t8 & 6)), c4 = lds64(SM_SC + 64);
      POLLW(_Pragma("unroll") for (int j = 0; j < 4; j++) if ((v[j].x ^ pm) & TAGM) v[j] = ldr128(zs + j * 4 * BLK),
           ((v[0].x ^ pm) | (v[1].x ^ pm) | (v[2].x ^ pm) | (v[3].x ^ pm)) & TAGM, 1);
      TS(9);
      const u32 dst = SM_ZS + 128 + (t8 & 7) * ZPS + (16 * w - 64 + (lane >> 3)) * 16;
#pragma unroll
      for (int j = 4; j >= 0; j--) {
        const uint2 c = j < 4 ? cc : c4;
        sts128(j < 4 ? dst + j * 64 : SM_Z4 + 256 + (t8 & 1) * ZP4 + (t8 >> 1) * 16, hfma(v[j].x & ~TAGM, c.x, c.y), hfma(v[j].y, c.x, c.y), hfma(v[j].z, c.x, c.y), hfma(v[j].w, c.x, c.y));
      }
      if (t8 < 96) sts128(t8 < 64 ? SM_ZS + (t8 & 7) * ZPS + (t8 >> 3) * 16 : SM_Z4 + (t8 & 1) * ZP4 + (t8 & 30) * 8, 0, 0, 0, 0);
      if (MKT == 0) asm volatile("cp.async.bulk.wait_group.read 1;" ::: "memory");
      else asm volatile("cp.async.bulk.wait_group.read 0;" ::: "memory");
      bsync(9, 384);
      TS(11);
      if (MKT == 1) MARKERS();
      const bool lng = w < 8 || w == 9;
      const u32 ts = lane + 32 * (w == 8 ? 0 : w - 9), c = min(ts, 71u), ma = SM_MODS + 16 * c;
      const u32 sig = lng ? ksig : ts >> 4, l2 = lng ? lane : 32 + (ts & 15);
      const char* mq = gs + (G_MOD + (c >> 2) * 128 + (c & 3) * 16);
      if (!lng) {
#pragma unroll
        for (int j = 0; j < 6; j++) cpa16(ma + 1152 * j, mq + j * MODJ);
        cpa16(ma + 1152 * 6, p.dsk + 16 * c); cpa16(ma + 1152 * 7, p.wr + 16 * c);
        if (PFU == 3) {
#pragma unroll
          for (int j = 0; j < 4; j++) if (ts < 81) l2_line(p.wu + (b * WSH + (81 * j + ts) * 128));
        }
        if (tid == 352) {
          PROXY_FENCE();
          if (PFU == 1) l2_pre<WSH>(p.wu + b * WSH);
          if (!TG) GATE();
          if (!TU) UP();
        }
      }
      const u32 wb = SM_W + sig * WSL;
      if (sig < 5) {
        const u32 za = (sig < 4 ? SM_ZS + 128 + sig * ZSS : SM_Z4 + 256) + l2 * 32, zb = za + (sig < 4 ? ZPS : ZP4);
        const uint4 c0 = lds128(zb - 32), c1 = lds128(za - 16), c2 = lds128(zb - 16), c3 = lds128(za), c4 = lds128(zb), c5 = lds128(za + 16), c6 = lds128(zb + 16);
        const u32 P[25] = {c0.z, c0.w, c1.x, c1.y, c1.z, c1.w, c2.x, c2.y, c2.z, c2.w, c3.x, c3.y, c3.z, c3.w, c4.x, c4.y, c4.z, c4.w, c5.x, c5.y, c5.z, c5.w, c6.x, c6.y, c6.z};
        u32 Q[25], D1[24], F4[23], W5[21], W3[17];
#pragma unroll
        for (int j = 1; j < 25; j++) Q[j] = __byte_perm(P[j - 1], P[j], 0x5432);
#pragma unroll
        for (int j = 1; j < 24; j++) D1[j] = hadd(P[j], Q[j]);
#pragma unroll
        for (int j = 2; j < 23; j++) F4[j] = hadd(D1[j], D1[j - 1]);
#pragma unroll
        for (int n = 0; n < 21; n++) W5[n] = hadd(F4[n + 2], P[n]);
#pragma unroll
        for (int n = 0; n < 17; n++) W3[n] = hadd(Q[n + 8], D1[n + 7]);
        const u32 a0 = wb + W5O + 64 * l2 + 16 * ((l2 >> 1) & 3);
#pragma unroll
        for (int i = 0; i < 4; i++) {
          sts128(a0 ^ (16 * i), W5[4 * i + 5], W5[4 * i + 6], W5[4 * i + 7], W5[4 * i + 8]);
          sts128((a0 ^ (16 * i)) + (W3O - W5O), W3[4 * i + 1], W3[4 * i + 2], W3[4 * i + 3], W3[4 * i + 4]);
        }
        if (lng) {
          if (lane < 16) sts128(wb + (lane & 7) * 16 + (lane & 8) * 400, 0, 0, 0, 0);
          const u32 a1 = wb + 32 * lane + 16 * ((lane >> 2) & 1);
#pragma unroll
          for (int i = 0; i < 4; i++) {
            const u32 a = (a1 ^ (16 * (i >> 1))) + 1024 * (i & 1), n = 4 * i;
            sts128(a + V2O, hadd(Q[n + 9], P[n + 8]), hadd(Q[n + 10], P[n + 9]), hadd(Q[n + 11], P[n + 10]), hadd(Q[n + 12], P[n + 11]));
            sts128(a + W9O, hadd(F4[n + 4], W5[n]), hadd(F4[n + 5], W5[n + 1]), hadd(F4[n + 6], W5[n + 2]), hadd(F4[n + 7], W5[n + 3]));
            sts128(a + W7O, hadd(F4[n + 6], W3[n]), hadd(F4[n + 7], W3[n + 1]), hadd(F4[n + 8], W3[n + 2]), hadd(F4[n + 9], W3[n + 3]));
          }
        }
      }
      if (w < 8) barriver((BW >> (4 * w - 16)) & 15);
      else if (!(w & 1)) { barriver((BW >> (4 * w - 32)) & 15); barriver((BW >> (4 * w - 28)) & 15); }
      __syncwarp();
      TS(32);
      if (lng) {
        const u32 wa = wb + ((lane >> 3) & 1) * 1024 + (((lane & 7) ^ (lane >> 4)) + 8 * (lane >> 4)) * 16;
        const u32 kv = lds32(SM_KV + 4 * sig), bi = (g >> 1) == q ? (hi ? kv << 16 : kv) : 0u;
        float acc[8][4] = {};
#pragma unroll
        for (int j = 0; j < 4; j++) { const uint4 a = ldsm4t(wa + V2O + j * 256); mma8_hf(acc[2 * j], a.x, a.y, bi); mma8_hf(acc[2 * j + 1], a.z, a.w, bi); }
        u32 bt = tp + (T9E + hi * TEO + (g >> 1) - q) * 4, wt = wa + W9O;
#pragma unroll 1
        for (int ty = 0; ty < 2; ty++) {
          uint4 a[4];
#pragma unroll
          for (int be = 0; be < 4; be++) a[be] = ldsm4t(wt + be * 256);
          u32 b1 = lds32(bt - 16);
#pragma unroll
          for (int d = 0; d < 8; d++) {
            const u32 b0 = lds32(bt + 16 * d);
#pragma unroll
            for (int be = 0; be < 4; be++) if (d + 2 * be < 8) mma_hf(acc[d + 2 * be], a[be].x, a[be].y, a[be].z, a[be].w, b0, b1);
            b1 = b0;
          }
          bt += (T7E - T9E) * 4; wt += W7O - W9O;
        }
        __syncwarp();
#pragma unroll
        for (int j = 0; j < 8; j++) sts128(wb + W9O + j * 512 + lane * 16, fu(acc[j][0]), fu(acc[j][1]), fu(acc[j][2]), fu(acc[j][3]));
        if (w != 9) barriver((BS >> (4 * w - 16)) & 15);
        TS(34);
      }
      if (!lng) {
        asm volatile("cp.async.wait_all;" ::: "memory");
        uint4 md[6];
#pragma unroll
        for (int j = 0; j < 6; j++) md[j] = lds128(ma + 1152 * j);
        const uint4 dk = lds128(ma + 1152 * 6), wr = lds128(ma + 1152 * 7);
        POLLW(_Pragma("unroll") for (int j = 0; j < 6; j++) md[j] = ldr128(mq + j * MODJ),
              ((md[0].x ^ pm) | (md[1].x ^ pm) | (md[2].x ^ pm) | (md[3].x ^ pm) | (md[4].x ^ pm) | (md[5].x ^ pm)) & TAGM, 4);
#pragma unroll
        for (int j = 0; j < 6; j++) {
          const u32 o = (j % 3 == 1) ? BONE : 0x80008000u;
          md[j] = make_uint4(bfma(md[j].x & ~TAGM, B2P64, o), bfma(md[j].y, B2P64, o), bfma(md[j].z, B2P64, o), bfma(md[j].w, B2P64, o));
          if (j > 2) sts128(ma + 1152 * j, md[j].x, md[j].y, md[j].z, md[j].w);
        }
        const uint4 gd = make_uint4(bmul(md[2].x, dk.x), bmul(md[2].y, dk.y), bmul(md[2].z, dk.z), bmul(md[2].w, dk.w));
#pragma unroll
        for (int j = 0; j < 2; j++) sts128(ma + 1152 * j, bmul(md[j].x, gd.x), bmul(md[j].y, gd.y), bmul(md[j].z, gd.z), bmul(md[j].w, gd.w));
        sts128(ma + 2304, bmul(md[2].x, B2P64), bmul(md[2].y, B2P64), bmul(md[2].z, B2P64), bmul(md[2].w, B2P64));
        const uint4 H = make_uint4(bmul(md[4].x, wr.x), bmul(md[4].y, wr.y), bmul(md[4].z, wr.z), bmul(md[4].w, wr.w));
        sts128(ma + 1152 * 7, H.x, H.y, H.z, H.w);
        sts128(ma + 1152 * 8, bfma(md[4].x, wr.x, H.x ^ 0x80008000u), bfma(md[4].y, wr.y, H.y ^ 0x80008000u), bfma(md[4].z, wr.z, H.z ^ 0x80008000u), bfma(md[4].w, wr.w, H.w ^ 0x80008000u));
        float c4[4] = {};
        mma_bf(c4, md[4].x, md[3].x, md[4].y, md[3].y, wr.x, wr.y); mma_bf(c4, md[4].z, md[3].z, md[4].w, md[3].w, wr.z, wr.w);
        if (q == g >> 1) sts64(SM_RC + (ts >> 2) * 8, fu(hi ? c4[1] : c4[0]), fu(hi ? c4[3] : c4[2]));
        if (ts < 2) sts128(SM_ONE + 16 * ts, ts ? 0 : BONE, ts ? 0 : BONE, ts ? 0 : BONE, ts ? 0 : BONE);
        TS(14);
        if (MKT == 2) MARKERS();
        if (w == 8) asm volatile("cp.async.bulk.wait_group 0;" ::: "memory");
        if (PFW == 2) {
#pragma unroll
          for (int j = 0; j < 4; j++) if (ts < 81) l2_line(p.wd + (b * WSH + (81 * j + ts) * 128));
        }
        bsync(13, 96);
        if (w == 8) { barriver(2); barriver(3); barriver(5); barriver(6); if (HLP) barrive(7, 64); }
      }
      if (!HLP) { if (w >= 8) barrive(11, 256); }
      else if (w == 9) barrive(11, 128);
    }
    const u32 jw = w < 6 ? w ^ 1 : w < 8 ? w : max(w - 4, 5u);
    const int u0 = 4 * (jw - 4) + 2 * rho;
    const u32 t4 = SM_TAP + 4 * TAPS, s3a = SM_W + 4 * WSL + (u0 >= 8 ? W9O + (u0 - 8) * 512 : V2O) + lane * 16, hb = (0x4987 >> (4 * jw - 16)) & 15;
#define FARL() { u32 wa = (SM_W + 4 * WSL + W5O + row16(lane) + (u0 - 3) * 256) ^ 32, bt = t4 + (T5 + g - q) * 4; \
      _Pragma("unroll 1") for (int al = min(u0 - 2, 6); al > 0; al--) { \
        _Pragma("unroll") for (int ty = 0; ty < 2; ty++) { \
          const uint4 a = ldsm4t(wa + ty * (W3O - W5O)); \
          const u32 bb = bt + ty * (T3 - T5) * 4; \
          mma_hf(acc[ty], a.x, a.y, a.z, a.w, lds32(bb - 32), lds32(bb - 48)); \
          mma_hf(acc[2 + ty], a.x, a.y, a.z, a.w, lds32(bb), lds32(bb - 16)); \
        } \
        wa = (wa - 256) ^ 32; bt += 32; } }
    if (w < 8) {
      u32 tr = t4 + ((hi ? TO : TE) + (g >> 1) - q) * 4;
      u32 zb = SM_Z4 + 256 + ((lane >> 3) & 1) * ZP4 + u0 * 128 + (lane & 7) * 16 + (lane >> 4) * 128;
      float acc[4][4] = {};
      u32 prev = 0;
#pragma unroll 1
      for (int it = min(u0 + 2, 4); it; it--) {
#pragma unroll
        for (int s = 0; s < 8; s++) {
          const uint4 z = ldsm4(zb - 16 * s);
          const u32 t0 = lds32(tr + 32 * s), t1 = lds32(tr + 32 * s + 16);
          mma_hf(acc[s & 1], t0, t1, prev, t0, z.x, z.y);
          mma_hf(acc[2 + (s & 1)], t0, t1, prev, t0, z.z, z.w);
          prev = t1;
        }
        zb -= 128; tr += 256;
      }
      {
        const uint4 z = ldsm4(zb); const u32 t0 = lds32(tr), t1 = lds32(tr + 16);
        mma_hf(acc[0], t0, t1, prev, t0, z.x, z.y); mma_hf(acc[2], t0, t1, prev, t0, z.z, z.w);
        if (jw > 4) { const uint4 y = ldsm4(zb - 16); mma8_hf(acc[1], t1, zr, y.y); mma8_hf(acc[3], t1, zr, y.w); }
      }
      if (!HLP) { bsync(11, 256); FARL(); }
      else asm volatile("bar.sync %0,64;" ::"r"(hb) : "memory");
      TS(35);
      const uint2 fc = lds64(SM_SC + 16 * 4 + 8);
      const u32 F = __byte_perm(fu(uf(fc.x) * uf(fc.y)), 0, 0x3232);
      char* yp = gs + (G_Y + 16384 - 2048 + b * BLK + jw * 512 + q * 64 + 4 * g);
#pragma unroll
      for (int j = 0; j < 2; j++) {
        uint4 s3 = {0, 0, 0, 0};
        if (u0 >= (HLP ? 4 : 8)) s3 = lds128(s3a + j * 512);
        y_store<32>(acc[2 * j][0] + acc[2 * j + 1][0] + uf(s3.x), acc[2 * j][1] + acc[2 * j + 1][1] + uf(s3.y), acc[2 * j][2] + acc[2 * j + 1][2] + uf(s3.z),
                acc[2 * j][3] + acc[2 * j + 1][3] + uf(s3.w), F, pml, yp + j * 256);
      }
      if (!AXW) barrive(7, 160);
      TS(16);
    } else {
      if (HLP && w != 9) {
        bsync(11, 128);
        if (HD) wait_clk(clk(), HD);
        float acc[4][4] = {};
        if (u0 >= 8) {
#pragma unroll
          for (int j = 0; j < 2; j++) { const uint4 t = lds128(s3a + j * 512); acc[2 * j][0] = uf(t.x); acc[2 * j][1] = uf(t.y); acc[2 * j][2] = uf(t.z); acc[2 * j][3] = uf(t.w); }
        }
        FARL();
#pragma unroll
        for (int j = 0; j < 2; j++)
          sts128(s3a + j * 512, fu(acc[2 * j][0] + acc[2 * j + 1][0]), fu(acc[2 * j][1] + acc[2 * j + 1][1]), fu(acc[2 * j][2] + acc[2 * j + 1][2]), fu(acc[2 * j][3] + acc[2 * j + 1][3]));
        asm volatile("bar.arrive %0,64;" ::"r"(hb) : "memory");
        TS(16);
      }
      if (PFW == 3 && w == 9) {
#pragma unroll 1
        for (int j = 0; j < 12; j++) { if (lane < 27) l2_line(p.wd + (b * WSH + (27 * j + lane) * 128)); wait_clk(clk(), PFP); }
      }
      if (TG | TU | TW) {
        if (tid == 352) {
          if (TG) { wait_clk(t0, TG); GATE(); }
          if (TW < TU) { wait_clk(t0, TW); l2_pre<WSH>(p.wd + b * WSH); }
          if (TU) { wait_clk(t0, TU); UP(); }
          if (TW >= TU) { wait_clk(t0, TW); l2_pre<WSH>(p.wd + b * WSH); }
        }
      } else if (PFW < 2 && tid == 352) { mb_wait(SM_MB + 8); if (PFW) mb_wait(SM_MB + 16); l2_pre<WSH>(p.wd + b * WSH); }
      if (D0C && tid == 352 && b < 108) {
        mb_wait(SM_MB + 16);
        PROXY_FENCE();
        mb_expect(SM_MB + 24, 49152);
        tma3d(SM_TAP, &tm_down, SM_MB + 24, 64 * (b % 9), 4 * (b / 9));
      }
      TS(17);
    }
  }
  post_conv(p, &tm_down, tid2 + p.zero, b);
  TSD();
  if (s2u(smem) != SM0) __trap();
}

typedef CUresult (*EncFn)(CUtensorMap*, CUtensorMapDataType, cuuint32_t, void*, const cuuint64_t*, const cuuint64_t*, const cuuint32_t*, const cuuint32_t*,
                          CUtensorMapInterleave, CUtensorMapSwizzle, CUtensorMapL2promotion, CUtensorMapFloatOOBfill);
static void make_map(EncFn enc, CUtensorMap* tm, void* ptr, int cols, int rows, int bw, int nb, CUtensorMapSwizzle sw, int gr = 192, int prom = 0) {
  cuuint64_t gd[3] = {(cuuint64_t)cols, (cuuint64_t)gr, (cuuint64_t)(rows / gr)}, gs[2] = {(cuuint64_t)cols * 2, (cuuint64_t)cols * 2 * gr};
  cuuint32_t bd[3] = {(cuuint32_t)bw, (cuuint32_t)gr, (cuuint32_t)nb}, es[3] = {1, 1, 1};
  enc(tm, CU_TENSOR_MAP_DATA_TYPE_BFLOAT16, 3, ptr, gd, gs, bd, es, CU_TENSOR_MAP_INTERLEAVE_NONE, sw, (CUtensorMapL2promotion)prom, CU_TENSOR_MAP_FLOAT_OOB_FILL_NONE);
}
extern "C" void kernel_launch(void* const* d_in, const int* in_sizes, int n_in, void* d_out, int out_size) {
  static EncFn enc = nullptr;
  static void* scratch = nullptr;
  if (!enc) {
    cudaGetSymbolAddress(&scratch, g_s);
    cudaDriverEntryPointQueryResult qr;
    cudaGetDriverEntryPoint("cuTensorMapEncodeTiled", (void**)&enc, cudaEnableDefault, &qr);
    cudaFuncSetAttribute(fused_kernel, cudaFuncAttributeMaxDynamicSharedMemorySize, SM_TOTAL);
  }
  CUtensorMap tm_mod, tm_gate, tm_gs, tm_up, tm_us, tm_down;
  make_map(enc, &tm_mod, d_in[13], 3456, 576, 32, 3, CU_TENSOR_MAP_SWIZZLE_64B, 192, PRM);
  make_map(enc, &tm_gate, d_in[9], 4608, 576, 32, 1, CU_TENSOR_MAP_SWIZZLE_64B, 192, PRG);
  make_map(enc, &tm_gs, d_in[9], 4608, 576, 8, 3, CU_TENSOR_MAP_SWIZZLE_NONE);
  make_map(enc, &tm_up, d_in[10], 4608, 576, 32, 3, CU_TENSOR_MAP_SWIZZLE_64B, 192, PRU);
  make_map(enc, &tm_us, d_in[10], 4608, 576, 8, 3, CU_TENSOR_MAP_SWIZZLE_NONE, 192, PRS);
  make_map(enc, &tm_down, d_in[11], 576, 4608, 64, 1, CU_TENSOR_MAP_SWIZZLE_128B, 96);
  Prm p;
  p.x = (const char*)d_in[0]; p.la = (const char*)d_in[1]; p.ai = (const char*)d_in[2]; p.cr = (const char*)d_in[3];
  p.ci = (const char*)d_in[4]; p.ldt = (const char*)d_in[5]; p.dsk = (const char*)d_in[6]; p.wr = (const char*)d_in[8];
  p.wg = (const char*)d_in[9]; p.wu = (const char*)d_in[10]; p.wd = (const char*)d_in[11];
  p.c = (const char*)d_in[12]; p.out = (char*)d_out; p.zero = 0; p.gs = (char*)scratch;
  fused_kernel<<<128, 384, SM_TOTAL>>>(p, tm_mod, tm_gate, tm_gs, tm_up, tm_us, tm_down);
}
```

```cpp
#include <cuda_runtime.h>
#include <cuda.h>
#include <cuda_bf16.h>
#include <cuda_fp16.h>
#include <stdint.h>
#define FUSED 1
#define DEV __device__ __forceinline__
typedef uint32_t u32;

constexpr u32 BLK = 18432, G_Z = 0, G_Y = 128 * BLK, G_MOD = 2 * G_Y, G_KEY = G_MOD + 128 * 128, G_ACT = G_KEY + 128 * 128;
constexpr u32 G_PART = G_ACT + 576 * 128, G_EP = G_PART + 128 * 2048, G_END = G_EP + 128;
__device__ __align__(128) unsigned char g_s[G_END];
#define TS(i)
#define TSJ(j)
#define TS0()
#define TSE()
#define TSD()
#define TSX 0
#define TSRND()
#define TSN(code, n)
#define ERRF(code)

constexpr int SM0 = 1024;
constexpr int ROW = 1168, SLV = 36864;
constexpr int SM_GATE = SM0, SM_UP = SM_GATE + 46080, SM_XST = SM_UP + 46080, SM_MODS = SM_XST + 16 * ROW, SM_W = SM_MODS + 11008;
constexpr int KTAB = 9216, WSL = 12544, W5O = 128, W3O = 3328, V2O = 6400, W9O = 8448, W7O = 10496;
constexpr int ZPS = 2192, ZSS = 2 * ZPS, ZP4 = 2368;
constexpr int SM_ZS = SM_W + 5 * WSL, SM_Z4 = SM_ZS + 4 * ZSS, SM_TAP = SM_Z4 + 2 * ZP4, TAPS = 3328;
constexpr int SM_MB = SM_TAP + 5 * TAPS;
constexpr int SM_SC = SM_MB + 48;
constexpr int SM_KV = SM_SC + 80;
constexpr int SM_THR = SM_KV + 32;
constexpr int SM_SLOT = SM_THR + 48;
constexpr int SM_KEY = SM_SLOT + 32;
constexpr int SM_ST = SM_KEY + 64;
constexpr int SM_ST2 = SM_ST + 256;
constexpr int SM_RC = SM_ST2 + 256;
constexpr int SM_SP = SM_RC + 192;
constexpr int SM_AF = SM_SP + 1152, SM_SIL = SM_AF + 1152, SM_INV = SM_SIL + 1152, SM_END = SM_SP + 5760;
constexpr int SM_ONE = SM_MODS + 9 * 1152;
constexpr int SM_WD = SM_W, SM_XS = SM_W + 36864, SM_AC = SM_ZS, SM_RED = SM_AC + 6144;
constexpr int SM_TSB = SM_END, SM_TOTAL = SM_END + TSX - SM0;
static_assert(SM_W % 1024 == 0 && SM_TAP % 1024 == 0 && SM_MODS + 8 * KTAB <= SM_ZS && SM_ZS + 2 * KTAB <= SM_TAP && SM_RED + 10240 <= SM_TAP && SM_XS + 8 * ROW <= SM_ZS, "smem map");
static_assert(SM_MB % 16 == 0 && SM_THR % 16 == 0 && SM_ST % 16 == 0 && SM_SP % 16 == 0 && SM_TOTAL <= 232448, "smem map");
constexpr int TE = 4, TO = 276, T5 = 560, T3 = 624, T9E = 680, T7E = 760, TEO = 40;
#define MT 10
#define MKT 1
#define KST 128
#define DE1 1
#define DE2 4
#define DE3 5
#define OUTB 7
#define PFW 1
#define PFU 0
#define KD 700
#define D0C 0
#define YE 104
#define YL 104
#define YD 250
#define OPTM 1
#define Y8 64
#define FH 0
#define FO 0
#define DB1 1
#define KD1 50
#define AD 0
#define PD 900
#define ZD 0
#define DD 1000
#define INCV 1
#define TPIN 0
#define A5P 1
#define TG 0
#define TU 0
#define TW 0
#define KDB 520
#define PRM 0
#define PRG 0
#define PRU 0
#define PRS 0
#define KE 64
#define PFP 200
#define GE 0
#define NB8 8
#define DX 0
#define DMOD 1000
#define RW 3
#define AW 7
#define HLP 1
#define SMD 1
#define CVG 1
#define F8 0
#define HD 0
#define KF 96
#define KDC 520
#define AFP 1
#define AFM 0
#define PFG 1
constexpr int N1 = 320 + 32 * DB1, N12 = 288 + 32 * !DB1;
constexpr int SPIN = 1 << 16, NEARLY = 4;
constexpr u32 TAGM = 0x40004000u, TAGR = 0x40000000u, INVAL = 0x00004801u;

DEV u32 s2u(const void* p) { return (u32)__cvta_generic_to_shared(p); }
DEV void mma_bf(float (&c)[4], u32 a0, u32 a1, u32 a2, u32 a3, u32 b0, u32 b1) {
  asm("mma.sync.aligned.m16n8k16.row.col.f32.bf16.bf16.f32 {%0,%1,%2,%3},{%4,%5,%6,%7},{%8,%9},{%0,%1,%2,%3};"
      : "+f"(c[0]), "+f"(c[1]), "+f"(c[2]), "+f"(c[3]) : "r"(a0), "r"(a1), "r"(a2), "r"(a3), "r"(b0), "r"(b1));
}
DEV void mma_hf(float (&c)[4], u32 a0, u32 a1, u32 a2, u32 a3, u32 b0, u32 b1) {
  asm("mma.sync.aligned.m16n8k16.row.col.f32.f16.f16.f32 {%0,%1,%2,%3},{%4,%5,%6,%7},{%8,%9},{%0,%1,%2,%3};"
      : "+f"(c[0]), "+f"(c[1]), "+f"(c[2]), "+f"(c[3]) : "r"(a0), "r"(a1), "r"(a2), "r"(a3), "r"(b0), "r"(b1));
}
DEV void mma8_bf(float (&c)[4], u32 a0, u32 a1, u32 b0) {
  asm("mma.sync.aligned.m16n8k8.row.col.f32.bf16.bf16.f32 {%0,%1,%2,%3},{%4,%5},{%6},{%0,%1,%2,%3};"
      : "+f"(c[0]), "+f"(c[1]), "+f"(c[2]), "+f"(c[3]) : "r"(a0), "r"(a1), "r"(b0));
}
DEV void mma8_hf(float (&c)[4], u32 a0, u32 a1, u32 b0) {
  asm("mma.sync.aligned.m16n8k8.row.col.f32.f16.f16.f32 {%0,%1,%2,%3},{%4,%5},{%6},{%0,%1,%2,%3};"
      : "+f"(c[0]), "+f"(c[1]), "+f"(c[2]), "+f"(c[3]) : "r"(a0), "r"(a1), "r"(b0));
}
DEV u32 movm(u32 x) { u32 r; asm("movmatrix.sync.aligned.m8n8.trans.b16 %0,%1;" : "=r"(r) : "r"(x)); return r; }
DEV void conv() { if (CVG) asm volatile("{.reg .u32 t; mov.u32 t,0; movmatrix.sync.aligned.m8n8.trans.b16 t,t;}"); }
DEV uint4 ldsm4(u32 a) { uint4 r; asm volatile("ldmatrix.sync.aligned.m8n8.x4.shared.b16 {%0,%1,%2,%3},[%4];" : "=r"(r.x), "=r"(r.y), "=r"(r.z), "=r"(r.w) : "r"(a)); return r; }
DEV uint4 ldsm4t(u32 a) { uint4 r; asm volatile("ldmatrix.sync.aligned.m8n8.x4.trans.shared.b16 {%0,%1,%2,%3},[%4];" : "=r"(r.x), "=r"(r.y), "=r"(r.z), "=r"(r.w) : "r"(a)); return r; }
DEV u32 lds32(u32 a) { u32 r; asm volatile("ld.volatile.shared.u32 %0,[%1];" : "=r"(r) : "r"(a)); return r; }
DEV uint2 lds64(u32 a) { uint2 r; asm volatile("ld.shared.v2.u32 {%0,%1},[%2];" : "=r"(r.x), "=r"(r.y) : "r"(a)); return r; }
DEV uint4 lds128(u32 a) { uint4 r; asm volatile("ld.shared.v4.u32 {%0,%1,%2,%3},[%4];" : "=r"(r.x), "=r"(r.y), "=r"(r.z), "=r"(r.w) : "r"(a)); return r; }
DEV void sts16(u32 a, u32 v) { asm volatile("st.shared.u16 [%0],%1;" ::"r"(a), "h"((unsigned short)v) : "memory"); }
DEV void sts32(u32 a, u32 v) { asm volatile("st.shared.u32 [%0],%1;" ::"r"(a), "r"(v) : "memory"); }
DEV void sts64(u32 a, u32 x, u32 y) { asm volatile("st.shared.v2.u32 [%0],{%1,%2};" ::"r"(a), "r"(x), "r"(y) : "memory"); }
DEV void sts128(u32 a, u32 x, u32 y, u32 z, u32 w) { asm volatile("st.shared.v4.u32 [%0],{%1,%2,%3,%4};" ::"r"(a), "r"(x), "r"(y), "r"(z), "r"(w) : "memory"); }
DEV uint4 ldr128(const void* p) { uint4 v; asm volatile("ld.relaxed.gpu.global.v4.u32 {%0,%1,%2,%3},[%4];" : "=r"(v.x), "=r"(v.y), "=r"(v.z), "=r"(v.w) : "l"(p) : "memory"); return v; }
DEV uint2 ldr64(const void* p) { uint2 v; asm volatile("ld.relaxed.gpu.global.v2.u32 {%0,%1},[%2];" : "=r"(v.x), "=r"(v.y) : "l"(p) : "memory"); return v; }
DEV u32 ldr32(const void* p) { u32 v; asm volatile("ld.relaxed.gpu.global.u32 %0,[%1];" : "=r"(v) : "l"(p) : "memory"); return v; }
template <u32 M> DEV void rld128(uint4& v, const void* p, u32 tag) {
  asm volatile("{.reg .pred p; .reg .u32 t; lop3.b32 t,%0,%5,%6,0x28; setp.ne.u32 p,t,0; @p ld.relaxed.gpu.global.v4.u32 {%0,%1,%2,%3},[%4];}"
               : "+r"(v.x), "+r"(v.y), "+r"(v.z), "+r"(v.w) : "l"(p), "r"(tag), "n"(M) : "memory");
}
template <u32 M> DEV void rld64(uint64_t& v, const void* p, u32 tag) {
  asm volatile("{.reg .pred p; .reg .u32 t, h; mov.b64 {t,h},%0; lop3.b32 t,t,%2,%3,0x28; setp.ne.u32 p,t,0; @p ld.relaxed.gpu.global.u64 %0,[%1];}" : "+l"(v) : "l"(p), "r"(tag), "n"(M) : "memory");
}
template <int L> DEV u32 lop3(u32 a, u32 b, u32 c) { u32 r; asm("lop3.b32 %0,%1,%2,%3,%4;" : "=r"(r) : "r"(a), "r"(b), "r"(c), "n"(L)); return r; }
DEV u32 ne3(u32 a, u32 b, u32 c) { u32 r; asm("lop3.b32 %0,%1,%2,%3,0x7e;" : "=r"(r) : "r"(a), "r"(b), "r"(c)); return r; }
DEV void pin(u32 zr, u32 a, u32 b = 0, u32 c = 0, u32 d = 0) { asm volatile("{.reg .pred p; setp.ne.u32 p,%0,0; @p st.shared.v4.u32 [%0],{%1,%2,%3,%4};}" ::"r"(zr), "r"(a), "r"(b), "r"(c), "r"(d) : "memory"); }
DEV void pin2(u32 zr, const void* a, const void* b) { asm volatile("{.reg .pred p; setp.ne.u32 p,%0,0; @p st.shared.v2.u64 [%0],{%1,%2};}" ::"r"(zr), "l"(a), "l"(b) : "memory"); }
DEV const char* rowa(const char* base, u32 key) { const char* r; asm("mad.wide.u32 %0,%1,288,%2;" : "=l"(r) : "r"(~key & 0x1ffc), "l"(base)); return r; }
DEV void str128(void* p, u32 x, u32 y, u32 z, u32 w) { asm volatile("st.relaxed.gpu.global.v4.u32 [%0],{%1,%2,%3,%4};" ::"l"(p), "r"(x), "r"(y), "r"(z), "r"(w) : "memory"); }
DEV void str64(void* p, u32 x, u32 y) { asm volatile("{.reg .u64 d; mov.b64 d,{%1,%2}; st.relaxed.gpu.global.u64 [%0],d;}" ::"l"(p), "r"(x), "r"(y) : "memory"); }
DEV void str32(void* p, u32 x) { asm volatile("st.relaxed.gpu.global.u32 [%0],%1;" ::"l"(p), "r"(x) : "memory"); }
DEV void str16(void* p, u32 x) { asm volatile("st.relaxed.gpu.global.u16 [%0],%1;" ::"l"(p), "h"((unsigned short)x) : "memory"); }
DEV uint4 ldg128(const void* p) { uint4 v; asm volatile("ld.global.nc.v4.u32 {%0,%1,%2,%3},[%4];" : "=r"(v.x), "=r"(v.y), "=r"(v.z), "=r"(v.w) : "l"(p)); return v; }
DEV uint2 ldg64(const void* p) { uint2 v; asm volatile("ld.global.nc.v2.u32 {%0,%1},[%2];" : "=r"(v.x), "=r"(v.y) : "l"(p)); return v; }
DEV u32 ldg32(const void* p) { u32 v; asm volatile("ld.global.nc.u32 %0,[%1];" : "=r"(v) : "l"(p)); return v; }
DEV u32 ldg16(const void* p) { unsigned short v; asm volatile("ld.global.nc.u16 %0,[%1];" : "=h"(v) : "l"(p)); return v; }
#define bsync(id, n) asm volatile("bar.sync %0,%1;" ::"n"(id), "n"(n) : "memory")
#define barrive(id, n) asm volatile("bar.arrive %0,%1;" ::"n"(id), "n"(n) : "memory")
DEV void bsyncr(u32 id) { asm volatile("bar.sync %0,96;" ::"r"(id) : "memory"); }
DEV void barriver(u32 id) { asm volatile("bar.arrive %0,96;" ::"r"(id) : "memory"); }
constexpr u32 BW = 0x0FEA, BS = 0x6532;
DEV void mb_init(u32 a, u32 n) { asm volatile("mbarrier.init.shared.b64 [%0],%1;" ::"r"(a), "r"(n) : "memory"); }
DEV void mb_arrive(u32 a) { asm volatile("mbarrier.arrive.shared.b64 _,[%0];" ::"r"(a) : "memory"); }
DEV void mb_expect(u32 a, u32 bytes) { asm volatile("mbarrier.arrive.expect_tx.shared.b64 _,[%0],%1;" ::"r"(a), "r"(bytes) : "memory"); }
DEV void mb_wait(u32 a, u32 ph = 0) {
  u32 ok; int it = 0;
  do { asm volatile("{.reg .pred p; mbarrier.try_wait.parity.shared.b64 p,[%1],%2; selp.u32 %0,1,0,p;}" : "=r"(ok) : "r"(a), "r"(ph) : "memory"); } while (!ok && ++it < SPIN);
}
template <int N> DEV void bulk_out(void* dst, u32 src) { asm volatile("cp.async.bulk.global.shared::cta.bulk_group [%0],[%1],%2;" ::"l"(dst), "r"(src), "n"(N) : "memory"); }
constexpr u32 WSH = 41472;
DEV void l2_line(const void* p) { asm volatile("prefetch.global.L2 [%0];" ::"l"(p) : "memory"); }
template <int N> DEV void l2_pre(const void* p) { asm volatile("cp.async.bulk.prefetch.L2.global [%0],%1;" ::"l"(p), "n"(N) : "memory"); }
DEV void tma3d(u32 dst, const CUtensorMap* tm, u32 mb, int c0, int c2) {
  asm volatile("cp.async.bulk.tensor.3d.shared::cluster.global.mbarrier::complete_tx::bytes [%0],[%1,{%3,0,%4}],[%2];"
               ::"r"(dst), "l"((uint64_t)tm), "r"(mb), "r"(c0), "r"(c2) : "memory");
}
DEV float blo(u32 w) { return __uint_as_float(w << 16); }
DEV float bhi(u32 w) { return __uint_as_float(w & 0xffff0000u); }
DEV u32 pk_bf(float lo, float hi) { u32 r; asm("cvt.rn.bf16x2.f32 %0,%1,%2;" : "=r"(r) : "f"(hi), "f"(lo)); return r; }
DEV u32 pk_hf(float lo, float hi) { u32 r; asm("cvt.rn.f16x2.f32 %0,%1,%2;" : "=r"(r) : "f"(hi), "f"(lo)); return r; }
DEV float rbf(float x) { return __uint_as_float(pk_bf(0.f, x) & 0xffff0000u); }
DEV u32 bfma(u32 a, u32 b, u32 c) { u32 r; asm("fma.rn.bf16x2 %0,%1,%2,%3;" : "=r"(r) : "r"(a), "r"(b), "r"(c)); return r; }
DEV u32 bmul(u32 a, u32 b) { u32 r; asm("mul.rn.bf16x2 %0,%1,%2;" : "=r"(r) : "r"(a), "r"(b)); return r; }
DEV u32 badd(u32 a, u32 b) { u32 r; asm("add.rn.bf16x2 %0,%1,%2;" : "=r"(r) : "r"(a), "r"(b)); return r; }
DEV u32 hadd(u32 a, u32 b) { u32 r; asm("add.rn.f16x2 %0,%1,%2;" : "=r"(r) : "r"(a), "r"(b)); return r; }
DEV u32 hfma(u32 a, u32 b, u32 c) { u32 r; asm("fma.rn.f16x2 %0,%1,%2,%3;" : "=r"(r) : "r"(a), "r"(b), "r"(c)); return r; }
struct C2 { u32 re, im; };
DEV C2 cm2(C2 a, C2 b) {
  const __half2 ar = *reinterpret_cast<__half2*>(&a.re), ai = *reinterpret_cast<__half2*>(&a.im), br = *reinterpret_cast<__half2*>(&b.re), bi = *reinterpret_cast<__half2*>(&b.im);
  __half2 re = __hfma2(ar, br, __hneg2(__hmul2(ai, bi))), im = __hfma2(ar, bi, __hmul2(ai, br));
  return {*reinterpret_cast<u32*>(&re), *reinterpret_cast<u32*>(&im)};
}
DEV C2 pk2(const float2 (&a)[2]) { return {pk_hf(a[0].x, a[1].x), pk_hf(a[0].y, a[1].y)}; }
DEV C2 pk2c(const float2 (&a)[2]) { return {pk_hf(a[0].x, a[1].x), pk_hf(-a[0].y, -a[1].y)}; }
DEV u32 cpy(u32 x, u32 zr, int alt) {
  u32 r;
  if (alt) asm volatile("xor.b32 %0,%1,%2;" : "=r"(r) : "r"(x), "r"(zr)); else asm volatile("mad.lo.u32 %0,%2,%2,%1;" : "=r"(r) : "r"(x), "r"(zr));
  return r;
}
template <int N> DEV void inc(u32& x) { asm volatile("add.u32 %0,%0,%1;" : "+r"(x) : "n"(N)); }
DEV u32 opq(u32 x) { u32 r; asm volatile("mov.u32 %0,%1;" : "=r"(r) : "r"(x)); return r; }
DEV u32 chan(u32 b, u32 i) { return 16 * (b >> 2) + 2 * (b & 3) + (i & 1) + 4 * (i & 2); }
DEV u32 row16(u32 lane) { const u32 r0 = (lane & 7) + ((lane >> 3) & 1) + 8 * (lane >> 4) - 1; return (r0 ^ ((r0 >> 3) & 3)) * 16; }
DEV u32 clk() { u32 r; asm volatile("mov.u32 %0,%%clock;" : "=r"(r)::"memory"); return r; }
DEV void wait_clk(u32 t, int d) { while ((int)(clk() - t) < d); }
DEV float ex2(float x) { float r; asm("ex2.approx.ftz.f32 %0,%1;" : "=f"(r) : "f"(x)); return r; }
DEV float rcpf(float x) { float r; asm("rcp.approx.ftz.f32 %0,%1;" : "=f"(r) : "f"(x)); return r; }
DEV float2 cmul(float2 a, float2 b) { return make_float2(fmaf(a.x, b.x, -a.y * b.y), fmaf(a.x, b.y, a.y * b.x)); }
DEV float2 csq(float2 a) { return make_float2(fmaf(a.x, a.x, -a.y * a.y), (a.x + a.x) * a.y); }
DEV float2 cexp(float lr2, float th) {
  const float m = ex2(lr2);
  return make_float2(m * __cosf(th), m * __sinf(th));
}
DEV float silu_f(float v) { return v * rcpf(1.f + ex2(-1.4426950408889634f * v)); }
constexpr u32 B2P64 = 0x5F805F80u, B2M64 = 0x1F801F80u, BONE = 0x3F803F80u;
constexpr u32 MODJ = 18 * 128;
DEV float sqrta(float x) { float r; asm("sqrt.approx.ftz.f32 %0,%1;" : "=f"(r) : "f"(x)); return r; }
DEV u32 fu(float x) { return __float_as_uint(x); }
DEV float uf(u32 x) { return __uint_as_float(x); }
DEV void mma_hf_o(float (&d)[4], const float (&c)[4], const u32 (&a)[4], u32 b0, u32 b1) {
  asm("mma.sync.aligned.m16n8k16.row.col.f32.f16.f16.f32 {%0,%1,%2,%3},{%4,%5,%6,%7},{%8,%9},{%10,%11,%12,%13};"
      : "=f"(d[0]), "=f"(d[1]), "=f"(d[2]), "=f"(d[3]) : "r"(a[0]), "r"(a[1]), "r"(a[2]), "r"(a[3]), "r"(b0), "r"(b1), "f"(c[0]), "f"(c[1]), "f"(c[2]), "f"(c[3]));
}

DEV void mma_hf_t(float (&c)[4], const u32 (&a)[4], u32 b0, u32 b1) { mma_hf(c, a[0], a[1], a[2], a[3], b0, b1); }
DEV void cpa16(u32 dst, const void* src) { asm volatile("cp.async.cg.shared.global [%0],[%1],16;" ::"r"(dst), "l"(src) : "memory"); }
DEV void tm_pre(const CUtensorMap* tm) { asm volatile("prefetch.tensormap [%0];" ::"l"((uint64_t)tm) : "memory"); }
#define PROXY_FENCE() asm volatile("fence.proxy.async.shared::cta;" ::: "memory")
struct Prm {
  const char *la, *ai, *cr, *ci, *ldt;
  u32 zero;
  const char *x, *c;
  char* gs;
  const char *dsk, *wr, *wg, *wu, *wd;
  char* out;
};
constexpr float LOG2E = 1.4426950408889634f, F2P64 = 1.8446744073709552e19f, F2M64 = 5.421010862427522e-20f;

template <int S> DEV void y_store(float c0, float c1, float c2, float c3, u32 F, u32 pml, char* yp) {
  str32(yp, bmul(pk_bf(c0, c2), F) | pml);
  str32(yp + S, bmul(pk_bf(c1, c3), F) | pml);
}
DEV void merge4(u32 (&h)[8], uint4 a, uint4 b) {
  const u32 e1 = min(a.x, b.x), e2 = max(a.z, b.z), o1 = min(a.y, b.y), o2 = max(a.w, b.w), o0 = max(a.y, b.y), e3 = min(a.z, b.z);
  const u32 f1 = max(e1, e2), f2 = min(e1, e2), p1 = max(o1, o2), p2 = min(o1, o2);
  h[0] = max(a.x, b.x); h[1] = max(o0, f1); h[2] = min(o0, f1); h[3] = max(p1, f2); h[4] = min(p1, f2); h[5] = max(p2, e3); h[6] = min(p2, e3); h[7] = min(a.w, b.w);
}
DEV void top8(u32 (&a)[8], uint4 l, uint4 m) {
  u32 b[8];
  merge4(b, l, m);
#pragma unroll
  for (int i = 0; i < 8; i++) a[i] = max(a[i], b[7 - i]);
#pragma unroll
  for (int s = 4; s; s >>= 1)
#pragma unroll
    for (int i = 0; i < 8; i++) if (!(i & s)) { const u32 x = a[i], y = a[i + s]; a[i] = max(x, y); a[i + s] = min(x, y); }
}
#define POLL(load, cond_bad, code) { int it_ = 0; do { load; } while (__any_sync(~0u, (cond_bad)) & (++it_ <= SPIN)); if (it_ > SPIN) { ERRF(code); } TSN(code, it_); }
DEV u32 tmask(u32 it, u32 m) { u32 r; asm volatile("{.reg .pred p; setp.ne.u32 p,%1,0; selp.u32 %0,%2,0,p;}" : "=r"(r) : "r"(it), "r"(m)); return r; }
#define POLLM(load, bad, M, code) { u32 it_ = SPIN + (tid >> 16), m_; do { m_ = tmask(--it_, M); load; } while (__any_sync(~0u, (bad) & m_)); if (!it_) { ERRF(code); } TSN(code, SPIN - it_); }
#define POLLS(use, load, bad, M, code) { u32 it_ = SPIN + (tid >> 16); for (;;) { const u32 m_ = tmask(--it_, M); use; if (!__any_sync(~0u, (bad) & m_)) break; load; } if (!it_) { ERRF(code); } TSN(code, SPIN - it_); }
#define POLLW(load, cond_bad, code) { int it_ = 0; while (__any_sync(~0u, (cond_bad))) { if (++it_ > SPIN) { ERRF(code); break; } load; } TSN(code, it_); }

#define DOWN(E) if (tid == (b < 108 ? 288 : ~0u)) { const u32 c0 = 64 * (b % 9), c2 = 4 * (b / 9); \
    if (!D0C && E == 1) { mb_expect(SM_MB + 24, 49152); tma3d(SM_TAP, tm_down, SM_MB + 24, c0, c2); } \
    if (DE1 == E) tma3d(SM_WD, tm_down, SM_MB + 24, c0, c2 + 1); \
    if (DE2 == E) tma3d(SM_WD + 12288, tm_down, SM_MB + 24, c0, c2 + 2); \
    if (DE3 == E) tma3d(SM_WD + 24576, tm_down, SM_MB + 24, c0, c2 + 3); }
#define OUTR() { const u32 tl = 4 * ((lane >> 1) & 1) + ((lane >> 2) & 3) + 8 * (lane & 1); \
    bulk_out<1152>(p.out + (16 * b + tl) * 1152, SM_XST + ((lane & 2) + 4 * (lane & 1) + ((lane >> 2) & 1) + (lane & 8)) * ROW); \
    asm volatile("cp.async.bulk.commit_group;" ::: "memory"); }
struct FA { u32 tid, ba, ra, sa; char *ad, *as; };
DEV FA ffn_addr(const Prm& p, u32 tid, u32 b) {
  const u32 w = tid >> 5, lane = tid & 31, kq = w & 3, tg = w >> 2, t = 7 - w;
  FA f = {tid, SM_XS + (lane & 7) * ROW + (18 * kq + (lane >> 3)) * 16, SM_RED + (8 * tg + kq) * 512 + lane * 16, SM_RED + t * 2048 + lane * 16,
          p.gs + (G_ACT + (t < 4 ? 512 * b + 128 * t : (512 + (b >> 1)) * 128) + lane * 4), p.gs + (G_ACT + (b / 9) * 6144 + tid * 16)};
  if (AW & 2) { pin(tid >> 16, f.ba, f.ra, f.sa, tid); pin2(tid >> 16, f.ad, f.as); }
  return f;
}
DEV void ffn_tail(const Prm& p, const CUtensorMap* tm_down, uint4 (&A)[24], const FA f, const u32 b, const u32 par, const u32 okl) {
  const u32 tid = f.tid, w = tid >> 5, lane = tid & 31, g = lane >> 2, q = lane & 3, tg = w >> 2, zr = tid >> 16;
  const u32 rho = b & 1, pm = par ? TAGM : 0, kt = par * 3, ba = f.ba, ra = f.ra;
  char* const gs = p.gs;
  char *const ad = f.ad, *const as = f.as;
  __syncthreads();
  TS(25);
  if (!(AW & 4)) DOWN(5);
  {
    float c0[2][4] = {}, c1[2][4] = {};
    uint4 bb[5];
#pragma unroll
    for (int s = 0; s < 5; s++) bb[s] = ldsm4(ba + s * 64);
    if (AW & 4) DOWN(5);
#pragma unroll
    for (int s = 0; s < 9; s++) mma_bf(c0[s & 1], A[s].x, A[s].y, A[s].z, A[s].w, s & 1 ? bb[s >> 1].z : bb[s >> 1].x, s & 1 ? bb[s >> 1].w : bb[s >> 1].y);
    if (tg < 2) {
#pragma unroll
      for (int s = 0; s < 9; s++) mma_bf(c1[s & 1], A[9 + s].x, A[9 + s].y, A[9 + s].z, A[9 + s].w, s & 1 ? bb[s >> 1].z : bb[s >> 1].x, s & 1 ? bb[s >> 1].w : bb[s >> 1].y);
      sts128(ra + 2048, fu(c1[0][0] + c1[1][0]), fu(c1[0][1] + c1[1][1]), fu(c1[0][2] + c1[1][2]), fu(c1[0][3] + c1[1][3]));
    }
    sts128(ra, fu(c0[0][0] + c0[1][0]), fu(c0[0][1] + c0[1][1]), fu(c0[0][2] + c0[1][2]), fu(c0[0][3] + c0[1][3]));
  }
  TS(39);
  __syncthreads();
  const u32 tr = clk();
  if (OUTB == 6 && w == 10 && okl < lds32(SM_SLOT + 28)) OUTR();
  if (w - 3 - rho < 5 - rho) {
    float s[4];
    const uint4 u0 = lds128(f.sa), u1 = lds128(f.sa + 512), u2 = lds128(f.sa + 1024), u3 = lds128(f.sa + 1536);
    s[0] = (uf(u0.x) + uf(u1.x)) + (uf(u2.x) + uf(u3.x)); s[1] = (uf(u0.y) + uf(u1.y)) + (uf(u2.y) + uf(u3.y));
    s[2] = (uf(u0.z) + uf(u1.z)) + (uf(u2.z) + uf(u3.z)); s[3] = (uf(u0.w) + uf(u1.w)) + (uf(u2.w) + uf(u3.w));
    const u32 sg = pk_bf(silu_f(rbf(s[0])), silu_f(rbf(s[1])));
    const u32 act = movm(bmul(bmul(sg, pk_bf(s[2], s[3])), B2M64));
    str32(ad, act | (q ? 0 : pm));
  }
  TS(26);
  const bool fin = w == (b < 72 ? 8 : ~0u);
  u32 kg;
  uint4 xt;
  const char* xs;
  if (fin) { kg = lds32(SM_SLOT + 4 * g); xs = rowa(gs + (G_Y + 16 * b), kg); xt = ldr128(xs); }
  if (b < 108) {
    uint4 a;
    if (AD) a.x = INVAL; else a = ldr128(as);
    if (AD && w >= 4) wait_clk(tr, AD);
    char* const dst = gs + ((G_PART + b * 2048) + (w * 512 + lane * 8));
    if (w < 4) {
      const u32 aa = SM_WD + (8 * (lane >> 4) + (lane & 7)) * 128 + (((2 * w + ((lane >> 3) & 1)) ^ (lane & 7)) << 4);
      mb_wait(SM_MB + 24);
#pragma unroll
      for (int s = 0; s < 24; s++) A[s] = ldsm4t(aa + (s < 6 ? SM_TAP - SM_WD : -12288) + s * 2048);
      if (AW & 2) pin2(zr, dst, as);
    }
    conv();
    TS(28);
    POLLW(rld128<TAGM>(a, as, pm), (a.x ^ pm) & TAGM, 9);
    sts128(SM_AC + tid * 16, a.x, a.y, a.z, a.w); sts32(SM_AC + tid * 16, a.x & ~TAGM);
    TS(27);
    if (w < 4) {
      bsync(8, 384);
      float c[4][4] = {};
#pragma unroll
      for (int s = 0; s < 12; s++) {
        const uint4 bb = ldsm4(SM_AC + lane * 16 + s * 512);
        mma_bf(c[2 * (s & 1)], A[2 * s].x, A[2 * s].y, A[2 * s].z, A[2 * s].w, bb.x, bb.y);
        mma_bf(c[2 * (s & 1) + 1], A[2 * s + 1].x, A[2 * s + 1].y, A[2 * s + 1].z, A[2 * s + 1].w, bb.z, bb.w);
      }
      u32 o[4];
#pragma unroll
      for (int i = 0; i < 4; i++) o[i] = fu(((c[0][i] + c[1][i]) + (c[2][i] + c[3][i])) * F2P64);
      str64(dst, (o[0] & ~3u) | kt, o[1]); str64(dst + 256, (o[2] & ~3u) | kt, o[3]);
      TS(29);
    } else barrive(8, 384);
  }
  if (OUTB == 7 && w == 10 && okl < lds32(SM_SLOT + 28)) OUTR();
  if (fin) {
    const u32 ta = clk();
    const char* src = gs + (G_PART + (b >> 3) * 2048 + (b & 7) * 256 + lane * 8);
    const u32 gw = lds32(SM_MODS + 5760 + 16 * b + 4 * q);
    const u32 hw = lds32(SM_XS + g * ROW + b * 16 + q * 4);
    const float sgm = rcpf(1.f + ex2(-LOG2E * bhi(kg ^ (~((int)kg >> 31) | 0x80000000))));
    char* const dst = (char*)rowa(p.out + (16 * b + 4 * q), kg);
    conv();
    POLLW(rld128<TAGM>(xt, xs, TAGR), (xt.x ^ TAGR) & TAGM, 10);
    const u32 x1w = (q & 2) ? ((q & 1) ? xt.w : xt.z) : ((q & 1) ? xt.y : bmul(xt.x ^ TAGR, B2P64));
    const u32 sg2 = pk_bf(sgm, sgm);
    pin(zr, x1w, gw, hw, sg2); pin2(zr, dst, src);
    uint64_t v[12];
#pragma unroll
    for (int j = 0; j < 12; j++) v[j] = 1;
    float s0, s1;
    if (PD) wait_clk(ta, PD);
    conv();
    TS(13);
#define VL(j) (u32)v[j]
#define VS(j, s) ((uf((u32)(v[j] >> s)) + uf((u32)(v[j + 1] >> s))) + (uf((u32)(v[j + 2] >> s)) + uf((u32)(v[j + 3] >> s))))
    POLL({ _Pragma("unroll") for (int j = 0; j < 12; j++) rld64<3>(v[j], src + j * 9 * 2048, kt);
           s0 = VS(0, 0) + VS(4, 0) + VS(8, 0); s1 = VS(0, 32) + VS(4, 32) + VS(8, 32);
           asm volatile("" : "+f"(s0), "+f"(s1)); TSRND(); },
         lop3<0xa8>(lop3<0xfe>(ne3(VL(0), VL(1), kt), ne3(VL(2), VL(3), kt), ne3(VL(4), VL(5), kt)),
                    lop3<0xfe>(ne3(VL(6), VL(7), kt), ne3(VL(8), VL(9), kt), ne3(VL(10), VL(11), kt)), 3), 11);
    const u32 y = movm(pk_bf(s0, s1));
    asm volatile("st.global.u32 [%0],%1;" ::"l"(dst), "r"(badd(x1w, bmul(gw, badd(hw, bmul(y, sg2))))) : "memory");
    if (b == 0 && lane == 0) str32(gs + G_EP, par);
    TS(30); TSE();
  }
  if (w == 10) asm volatile("cp.async.bulk.wait_group.read 0;" ::: "memory");
}

DEV u32 y_off(u32 tid, u32 b) { return G_Y + (16 * (tid >> 5) + 8 * ((tid >> 1) & 1) + ((tid >> 2) & 4)) * BLK + b * 128 + ((tid >> 2) & 3) * 32 + (tid & 1) * 16; }
DEV void post_conv(const Prm& p, const CUtensorMap* tm_down, const u32 tid, const u32 b, const u32 b3) {
  const u32 w = tid >> 5, lane = tid & 31;
  const u32 g = lane >> 2, q = lane & 3, e = g >> 2, h = (g >> 1) & 1, hi = g & 1;
  const u32 pm = lds32(SM_THR + 4), par = pm >> 30;
  char* const gs = p.gs;
  const u32 cho = 128 * w + 64 * e + 16 * q;
  u32 x1[4][4], h2[4][4], key[4], lt;
  char* const rowp = gs + (b * BLK + (4 * h + 8 * hi) * 1152 + cho);
  u32 okl = ~0u;
  FA fa;
  uint4 A[24];
#define AROW(t) const u32 arow = 144 * ((t >> 5) & 3) + ((t >> 1) & 8) + (t & 7), ab = (t & 8) ? SM_UP : SM_GATE;
#define AFRAG9() { _Pragma("unroll") for (int s = 0; s < 9; s++) A[s] = ldsm4t(ab + SLV + arow * 16 + s * 256); }
#define AFRAG18() { const u32 t3 = opq(tid); AROW(t3); if (t3 < 256) { const u32 aa = ab + arow * 64 + ((((t3 >> 6) & 2) ^ ((t3 & 7) >> 1)) << 4); \
      _Pragma("unroll") for (int s = 0; s < 9; s++) { A[s] = ldsm4t(aa + s * 1024); A[9 + s] = ldsm4t((aa ^ 16) + s * 1024); } } else AFRAG9(); }
  if (w < 9) {
    const u32 yc = 8 * (q >> 1) + 2 * (g >> 1), y1 = w < 8 ? BLK : 4 * BLK, y2 = 2 * y1;
    const char* ysrc = gs + (w < 8 ? y_off(tid, b) : G_Y + (q & 1) * 16 + (8 * yc + 2 * hi + ((b >> 4) & 1)) * BLK + 16384 + ((b >> 5) * 16 + (b & 15)) * 32);
    const char* const ys[4] = {ysrc, ysrc + y1, ysrc + y2, ysrc + (y1 + y2)};
    uint4 yv[4];
#pragma unroll
    for (int v = 0; v < 4; v++) yv[v].x = INVAL;
    const u32 tg0 = b < (w < 4 ? YL : w < 8 ? YE : Y8) ? pm : INVAL;
    if (w >= 4) { pin2(tid >> 16, ys[0], ys[1]); pin2(tid >> 16, ys[2], ys[3]); bsync(12, N12); TS(18); }
#pragma unroll
    for (int v = 0; v < 4; v++) rld128<TAGM>(yv[v], ys[v], tg0);
    const u32 tc = clk();
    const u32 ma = SM_MODS + cho, xa = SM_XST + (2 * h + 4 * hi) * ROW + cho;
    const uint4 sa = lds128(ma), ca = lds128(ma + 1152), ga = lds128(ma + 2304);
    const uint4 rb = lds128((g & 2) ? SM_ONE + 16 * hi : (ma ^ 64) + 8064 + 1152 * hi);
    const u32 saw[4] = {sa.x, sa.y, sa.z, sa.w}, caw[4] = {ca.x, ca.y, ca.z, ca.w}, gaw[4] = {ga.x, ga.y, ga.z, ga.w};
#pragma unroll
    for (int k = 0; k < 4; k++) {
      const uint2 st = lds64(SM_ST + 16 * (2 * h + 4 * hi + (k & 1) + 8 * (k >> 1)));
      const uint4 xv = lds128(xa + ((k & 1) + 8 * (k >> 1)) * ROW);
      x1[k][0] = xv.x; x1[k][1] = xv.y; x1[k][2] = xv.z; x1[k][3] = xv.w;
#pragma unroll
      for (int v = 0; v < 4; v++) x1[k][v] = badd(x1[k][v], bfma(bmul(badd(x1[k][v], st.x), st.y), caw[v], saw[v]));
    }
    const bool own = (q >> 1) == e;
    const u32 spw = SM_SP + (2 * w + e) * 320 + (g & 3) * 16 + (own ? ((q & 1) == h ? 4 : 12) : 8 - 8 * (q & 1));
    if (SMD && w < 4) asm volatile("setmaxnreg.dec.sync.aligned.u32 168;");
    if (b >= YL) wait_clk(tc, YD);
    conv();
    TS(13);
    POLLW(_Pragma("unroll") for (int v = 0; v < 4; v++) rld128<TAGM>(yv[v], ys[v], pm), lop3<0xa8>(ne3(yv[0].x, yv[1].x, pm), ne3(yv[2].x, yv[3].x, pm), TAGM), 5);
    TS(19);
    if (!SMD && w < 4) asm volatile("setmaxnreg.dec.sync.aligned.u32 168;");
#pragma unroll
    for (int k = 0; k < 4; k += 2) {
      float X[4] = {}, Y[4] = {}, R[4] = {};
#pragma unroll
      for (int v = 0; v < 4; v++) {
        const u32 y0 = k ? yv[v].z : yv[v].x & ~TAGM, y1 = k ? yv[v].w : yv[v].y;
        x1[k][v] = bfma(movm(y0), gaw[v], x1[k][v]);
        x1[k + 1][v] = bfma(movm(y1), gaw[v], x1[k + 1][v]);
        mma8_bf(X, x1[k][v], x1[k + 1][v], x1[k][v]); mma8_bf(Y, x1[k][v], x1[k + 1][v], x1[k + 1][v]);
        if (v & 1) mma_bf(R, x1[k][v - 1], x1[k + 1][v - 1], x1[k][v], x1[k + 1][v], v & 2 ? rb.z : rb.x, v & 2 ? rb.w : rb.y);
      }
      sts32(spw + k * 64, fu(own ? (hi ? X[1] : X[0]) : R[0] + R[1]));
      sts32(spw + k * 64 + 64, fu(own ? (hi ? Y[3] : Y[2]) : R[2] + R[3]));
    }
    barrive(1, N1);
    TS(36);
    if (AFP) { asm volatile("setmaxnreg.inc.sync.aligned.u32 168;"); mb_wait(SM_MB + 8); mb_wait(SM_MB + 16); }
    const uint4 sb = lds128(ma + 3456), cb = lds128(ma + 4608), gb = lds128(ma + 5760);
    const u32 sbw[4] = {sb.x, sb.y, sb.z, sb.w}, cbw[4] = {cb.x, cb.y, cb.z, cb.w}, gbw[4] = {gb.x, gb.y, gb.z, gb.w};
    const u32 t3 = opq(tid), zr = t3 >> 16;
    AROW(t3);
    const u32 aa = ab + arow * 64 + ((((t3 >> 6) & 2) ^ ((t3 & 7) >> 1)) << 4), sta = SM_ST2 + 16 * (g & 3);
    if (AFP) pin(zr, aa, sta, xa);
    bsync(2, 320);
    TS(37);
    uint4 st[4];
#pragma unroll
    for (int k = 0; k < 4; k++) st[k] = lds128(sta + 64 * k);
    lt = lds32(SM_THR);
#define AFL() { _Pragma("unroll") for (int s = 0; s < 9; s++) { A[s] = ldsm4t(aa + s * 1024); A[9 + s] = ldsm4t((aa ^ 16) + s * 1024); } }
    if (AFP && (AFM >> w & 1)) { if (w < 8) AFL() else AFRAG9(); }
#pragma unroll
    for (int k = 0; k < 4; k++) {
      key[k] = st[k].w;
      u32 o[4];
#pragma unroll
      for (int v = 0; v < 4; v++) {
        const u32 d = badd(x1[k][v], st[k].x), z = bfma(d, st[k].y, bmul(d, st[k].z));
        h2[k][v] = FH ? bfma(z, cbw[v], sbw[v]) : badd(bmul(z, cbw[v]), sbw[v]);
        o[v] = FO ? bfma(gbw[v], h2[k][v], x1[k][v]) : badd(x1[k][v], bmul(gbw[v], h2[k][v]));
      }
      h2[k][0] = bmul(h2[k][0], B2M64) | TAGR; x1[k][0] = bmul(x1[k][0], B2M64) | TAGR;
      if (key[k] >= lt) str128(rowp + k * 1152, h2[k][0], h2[k][1], h2[k][2], h2[k][3]);
      sts128(xa + ((k & 1) + 8 * (k >> 1)) * ROW, o[0], o[1], o[2], o[3]);
    }
    barrive(3, 320);
    TS(21);
    if (!AFP) { asm volatile("setmaxnreg.inc.sync.aligned.u32 168;"); mb_wait(SM_MB + 8); mb_wait(SM_MB + 16); AFRAG18(); }
    else if (!(AFM >> w & 1)) { if (w < 8) AFL() else AFRAG9(); }
    TS(22);
    const u32 rr = tid * 57 >> 12, rc = tid * 16 - rr * 1152, sl = SM_SLOT + 8 * rr;
    const char* const rb_ = gs + rc;
    const u32 km = max(max(key[0], key[1]), max(key[2], key[3])), xd = SM_XS + rr * (2 * ROW) + rc;
    if (RW & 2) { pin(tid >> 16, sl, km, xd); pin2(tid >> 16, rb_, rowp); }
    fa = ffn_addr(p, tid | p.zero, b);
    bsync(6, 320);
    TS(24);
    const uint2 sk = lds64(sl);
    const char *r0 = rowa(rb_, sk.x), *r1 = rowa(rb_, sk.y);
    uint4 rv[2] = {ldr128(r0), ldr128(r1)};
    barrive(15, 320);
    const u32 g8 = lds32(SM_SLOT + 28);
    if (__any_sync(~0u, km >= g8 && lt > g8)) {
#pragma unroll
      for (int k = 0; k < 4; k++) if (key[k] >= g8 && key[k] < lt) str128(rowp + k * 1152, h2[k][0], h2[k][1], h2[k][2], h2[k][3]);
    }
    bsync(5, 320);
    const uint2 sf = lds64(sl);
    const u32 f8 = lds32(SM_SLOT + 28);
    if (__any_sync(~0u, km >= f8)) {
#pragma unroll
      for (int k = 0; k < 4; k++) if (key[k] >= f8) str128(rowp + (G_Y + k * 1152), x1[k][0], x1[k][1], x1[k][2], x1[k][3]);
    }
    if (__any_sync(~0u, sf.x != sk.x || sf.y != sk.y)) {
      r0 = rowa(rb_, sf.x); r1 = rowa(rb_, sf.y);
      rv[0].x = rv[1].x = INVAL;
    }
    POLLW({ rld128<TAGM>(rv[0], r0, TAGR); rld128<TAGM>(rv[1], r1, TAGR); }, ne3(rv[0].x, rv[1].x, TAGR) & TAGM, 8);
    TS(38);
#pragma unroll
    for (int j = 0; j < 2; j++) sts128(xd + j * ROW, bmul(rv[j].x ^ TAGR, B2P64), rv[j].y, rv[j].z, rv[j].w);
  } else {
    u32 ok, lr;
    if (w == 10) {
      uint2 rc = lds64(SM_RC + 8 * min(lane, 17u));
      float r1 = lane < 18 ? uf(rc.x) : 0.f, r2 = lane < 18 ? uf(rc.y) : 0.f;
#pragma unroll 1
      for (int o = 16; o; o >>= 1) { r1 += __shfl_xor_sync(~0u, r1, o); r2 += __shfl_xor_sync(~0u, r2, o); }
      const u32 tl = 4 * ((lane >> 1) & 1) + ((lane >> 2) & 3) + 8 * (lane & 1), kl = (2047 - 16 * b - tl) << 2 | par * 3;
      char* const kp = gs + (G_KEY + b * KST);
      const u32 spr = SM_SP + (lane >> 4) * 9 * 320 + (lane & 15) * 16;
      TS(31);
      bsync(1, N1);
      float S1 = 0.f, S2 = 0.f, S3 = 0.f;
#pragma unroll
      for (int i = 0; i < 9; i++) { uint4 t = lds128(spr + i * 320); S1 += uf(t.x); S2 += uf(t.y); S3 += uf(t.z); }
      S1 += __shfl_xor_sync(~0u, S1, 16); S2 += __shfl_xor_sync(~0u, S2, 16); S3 += __shfl_xor_sync(~0u, S3, 16);
      const float mu = S1 * (1.f / 576.f), var = fmaxf(fmaf(-mu, mu, S2 * (1.f / 576.f)), 0.f);
      const float m = rbf(mu), rs = rcpf(rbf(sqrta(rbf(rbf(var) + 1e-5f))));
      const u32 rb = pk_bf(0.f, fmaf(fmaf(-m, r1, S3), rs, r2) + 0.f);
      ok = ((rb ^ (((int)rb >> 31) | 0x80000000)) & 0xffff0000u) | kl;
      const float rh = rbf(rs);
      sts32(SM_KEY + 4 * (lane & 15), ok);
      sts128(SM_ST2 + 16 * (lane & 15), pk_bf(-m, -m), pk_bf(rh, rh), pk_bf(rs - rh, rs - rh), ok);
      __syncwarp();
      const uint4 o0 = lds128(SM_KEY + 2 * (lane & 16)), o1 = lds128(SM_KEY + 2 * (lane & 16) + 16);
      lr = (o0.x > ok) + (o0.y > ok) + (o0.z > ok) + (o0.w > ok) + (o1.x > ok) + (o1.y > ok) + (o1.z > ok) + (o1.w > ok);
      lr += __shfl_xor_sync(~0u, lr, 16);
      if (lane < 16 && lr < 8) str32(kp + 4 * lr, ok);
      if (lr == (b < NB8 ? 7 : NEARLY - 1)) sts32(SM_THR, ok);
      barrive(2, 320);
      barrive(13, 64);
      TS(20);
    } else if (w == 9) {
      if (DB1) bsync(1, N1); else { bsync(12, N12); wait_clk(clk(), DD); }
      PROXY_FENCE();
      DOWN(1);
    } else {
      const char* ks = gs + (G_KEY + (lane >> 1) * KST + (lane & 1) * 16);
      const u32 kt = par * 3;
      uint4 L[8];
      u32 H[8];
#define KBAD(j) ((L[j].x ^ kt) & 3)
#define KLD(j) L[j] = ldr128(ks + j * 16 * KST)
#pragma unroll
      for (int j = 0; j < 8; j++) L[j].x = INVAL;
      bsync(13, 64);
      wait_clk(clk(), b < KE ? KD : b < KF ? KDB : b < YL ? KDC : KD1);
      TS(34);
      POLL({ _Pragma("unroll") for (int j = 0; j < 8; j++) if (KBAD(j)) KLD(j);
             merge4(H, L[0], L[1]); top8(H, L[2], L[3]);
             asm volatile("" : "+r"(H[0]), "+r"(H[1]), "+r"(H[2]), "+r"(H[3]), "+r"(H[4]), "+r"(H[5]), "+r"(H[6]), "+r"(H[7])); TS(32); },
           KBAD(0) | KBAD(1) | KBAD(2) | KBAD(3) | KBAD(4) | KBAD(5), 6);
      top8(H, L[4], L[5]);
      TS(35);
#pragma unroll 1
      for (u32 pass = p.zero;; pass++) {
        u32 G[8], m[8];
#pragma unroll
        for (int i = 0; i < 8; i++) G[i] = H[i];
#pragma unroll
        for (int r = 0; r < 8; r++) {
          const u32 h0 = G[0];
          m[r] = __reduce_max_sync(~0u, h0);
          if (r == 0) { if (KBAD(6)) KLD(6); if (KBAD(7)) KLD(7); }
          if (r < 7) asm("{.reg .u32 t; sub.u32 t,%1,%2; min.u32 t,t,1; mad.lo.u32 %0,t,%3,%4;}" : "=r"(G[0]) : "r"(m[r]), "r"(h0), "r"(h0 - G[1]), "r"(G[1]));
#pragma unroll
          for (int i = 1; i < 7 - r; i++) G[i] = h0 == m[r] ? G[i + 1] : G[i];
          if ((r & 3) == 3) sts128(SM_SLOT + 4 * r - 12, m[r - 3], m[r - 2], m[r - 1], m[r]);
        }
        asm volatile("{.reg .pred p; setp.eq.u32 p,%0,0; @p bar.arrive 6,320;}" ::"r"(pass) : "memory");
        if (pass) break;
        TS(23);
        POLLW({ if (KBAD(6)) KLD(6); if (KBAD(7)) KLD(7); }, KBAD(6) | KBAD(7), 7);
        if (!__any_sync(~0u, max(L[6].x, L[7].x) > m[7])) break;
        top8(H, L[6], L[7]);
      }
      barrive(5, 320);
      TS(33);
    }
    asm volatile("setmaxnreg.inc.sync.aligned.u32 168;");
    mb_wait(SM_MB + 8); mb_wait(SM_MB + 16);
    AROW(tid);
    AFRAG9();
    fa = ffn_addr(p, tid | p.zero, b);
    TS(22);
    if (w == 10) {
      bsync(3, 320);
      PROXY_FENCE();
      if (lane < 16 && lr >= 8) OUTR();
      if (lane < 16 && lr < 8) okl = ok;
    } else if (w == 9) {
      bsync(15, 320);
      DOWN(4);
      TS(13);
    }
  }
  ffn_tail(p, tm_down, A, fa, b3, par, okl);
}

__global__ void __launch_bounds__(384, 1)
fused_kernel(const Prm p, const __grid_constant__ CUtensorMap tm_mod, const __grid_constant__ CUtensorMap tm_gate, const __grid_constant__ CUtensorMap tm_gs,
             const __grid_constant__ CUtensorMap tm_up, const __grid_constant__ CUtensorMap tm_us, const __grid_constant__ CUtensorMap tm_down) {
  extern __shared__ __align__(1024) unsigned char smem[];
  u32 la, ai, ldt; uint2 cr, ci;
  {
    const u32 t = threadIdx.x, d = t < 256 ? chan(blockIdx.x, t >> 5) : 512 + (blockIdx.x >> 1), o = d * 256 + 8 * (t & 31), o4 = o + ((t < 256 ? t >> 5 : t >> 3) & 4);
    asm volatile("{.reg .pred p; .reg .u16 h; setp.ne.u32 p,%7,0; @p ld.global.nc.u32 %0,[%8]; @p ld.global.nc.u32 %1,[%9]; @p ld.global.nc.v2.u32 {%2,%3},[%10];"
                 "@p ld.global.nc.v2.u32 {%4,%5},[%11]; @p ld.global.nc.u16 h,[%12]; cvt.u32.u16 %6,h;}"
                 : "=r"(la), "=r"(ai), "=r"(cr.x), "=r"(cr.y), "=r"(ci.x), "=r"(ci.y), "=r"(ldt)
                 : "r"(0x6ffu >> (t >> 5) & 1), "l"(p.la + o4), "l"(p.ai + o4), "l"(p.cr + o), "l"(p.ci + o), "l"(p.ldt + 2 * d));
  }
  const u32 t0 = clk();
  const u32 tid = __shfl_sync(~0u, threadIdx.x, threadIdx.x & 31), b = blockIdx.x + p.zero;
  const u32 w = tid >> 5, lane = tid & 31;
  const u32 g = lane >> 2, q = lane & 3, hi = g & 1;
  const u32 rho = b & 1, Ps = 512 + (b >> 1);
  char* const gs = p.gs;
  TS0();
  const bool kw = w != 8 && w != 11;
  const u32 ksig = w < 8 ? (w & 3) : 4, khf = w < 8 ? (w >> 2) : (w & 1);
  if (!kw) {
    if (tid == 352) {
#pragma unroll
      for (int i = 0; i < 5; i++) mb_init(SM_MB + 8 * i, i < 4 ? 1 : 64);
      asm volatile("fence.mbarrier_init.release.cluster;" ::: "memory");
      tm_pre(&tm_mod);
    }
    const char* cp = p.c + (576 * (w & 1) + 24 * min(lane, 23u));
    const uint2 c0 = ldg64(cp);
    la = c0.x; ai = c0.y; cr = ldg64(cp + 8); ci = ldg64(cp + 16);
  }
  u32 b3;
  asm volatile("xor.b32 %0,%1,%2;" : "=r"(b3) : "r"(blockIdx.x), "r"(p.zero));
  const u32 zr = tid >> 16;
  const u32 epv = ldr32(gs + (G_EP + zr));
  const u32 tp = SM_TAP + ksig * TAPS;
  if (kw && !khf) {
#pragma unroll 1
    for (u32 i = lane * 16; i < TAPS; i += 512) sts128(tp + i, 0, 0, 0, 0);
  }
  if (tid < 128) sts128(SM_INV + 16 * tid, INVAL, 0, 1, 0);
  if (tid >= 252) str128(gs + (tid >= 380 ? G_MOD + b * 128 + q * 16 : b * BLK + 16384 - 252 * 16 + tid * 16), INVAL, 0, 1, 0);
  if (tid == (b < 36 ? 352 : ~0u)) { while (clk() - t0 < DMOD); mb_expect(SM_MB, 36864); tma3d(SM_UP, &tm_mod, SM_MB, 32 * b, 0); }
  if (w < 9) {
    while ((int)(clk() - t0) < DX);
    const char* xp = p.x + (b * BLK + (lane >> 3) * 1152 + 128 * w + 16 * (lane & 7));
    const u32 xd = SM_XST + (((lane >> 3) & 1) + 8 * (lane >> 4)) * ROW + 128 * w + 16 * (lane & 7);
#pragma unroll
    for (int i = 0; i < 4; i++) cpa16(xd + 2 * ROW * i, xp + 4608 * i);
  }
  const u32 ktab = w < 8 ? SM_MODS + w * KTAB : SM_ZS + (w - 9) * KTAB;
  float k2048 = 0.f;
  if (kw) {
    u32 mx = __vmaxu2(__vmaxu2(cr.x & 0x7fff7fff, cr.y & 0x7fff7fff), __vmaxu2(ci.x & 0x7fff7fff, ci.y & 0x7fff7fff));
    const u32 E = max(__reduce_max_sync(~0u, max(mx & 0xffff, mx >> 16)) >> 7, 8u);
    TS(1);
    const float dt = rbf(ex2(blo(ldt) * LOG2E)), csc = uf((257 - E) << 23 | (fu(dt) & 0x7fffff));
    sts32(SM_SC + 16 * ksig + 12, fu(uf(fu(dt) & 0x7f800000) * uf((E - 2) << 23)));
    const u32 crw = khf ? cr.y : cr.x, ciw = khf ? ci.y : ci.x;
    float2 C[2], w4[2], w8[2], w16[2], w32[2], w64[2], w128[2], w256[2], w512[2], a1[2], a2[2], a3[2], t0[2], t1[2], s3[2];
#pragma unroll
    for (int m = 0; m < 2; m++) {
      const float lr2 = rbf(ex2((m ? bhi(la) : blo(la)) * LOG2E)) * dt * -LOG2E, th = (m ? bhi(ai) : blo(ai)) * dt;
      C[m] = make_float2((m ? bhi(crw) : blo(crw)) * csc, (m ? bhi(ciw) : blo(ciw)) * csc);
      const float2 w1 = cexp(lr2, th), w2 = csq(w1);
      w64[m] = cexp(64.f * lr2, 64.f * th);
      w4[m] = csq(w2); w8[m] = csq(w4[m]); w16[m] = csq(w8[m]); w32[m] = csq(w16[m]);
      w128[m] = csq(w64[m]); w256[m] = csq(w128[m]); w512[m] = csq(w256[m]);
      const float2 w1024 = csq(w512[m]);
      a1[m] = cmul(C[m], w1); a2[m] = cmul(C[m], w2); a3[m] = cmul(a1[m], w2);
      t0[m] = cmul(C[m], w1024); t1[m] = cmul(t0[m], w128[m]); s3[m] = cmul(w8[m], w16[m]);
      k2048 += fmaf(t0[m].x, w1024.x, -t0[m].y * w1024.y);
    }
    C2 B0[8], B1[8], B2[8], S[8];
    B0[0] = pk2(C); B0[1] = pk2(a1); B0[2] = pk2(a2); B0[3] = pk2(a3);
    const C2 h4 = pk2(w4), h256 = pk2(w256), h512 = pk2(w512);
#pragma unroll
    for (int i = 0; i < 4; i++) B0[4 + i] = cm2(B0[i], h4);
#pragma unroll
    for (int i = 0; i < 4; i++) B1[i] = cm2(B0[2 * i], h256);
    B1[4] = cm2(B0[0], h512); B1[5] = cm2(B0[4], h512);
    B1[6] = cm2(B1[4], h256); B1[7] = cm2(B1[5], h256);
    const u32 ta = ktab + lane * 128, f = ((lane & 3) << 5) | ((lane & 4) << 2);
#pragma unroll
    for (int i = 0; i < 8; i++) sts128(ta + ((i << 4) ^ f), B0[i].re, B0[i].im, B1[i].re, B1[i].im);
    B2[0] = pk2(t0); B2[1] = pk2(t1);
    B2[2] = cm2(B2[0], h256); B2[3] = cm2(B2[1], h256);
#pragma unroll
    for (int i = 0; i < 4; i++) B2[4 + i] = cm2(B2[i], h512);
    S[0] = {0x3C003C00u, 0u}; S[1] = pk2c(w8); S[2] = pk2c(w16); S[3] = pk2c(s3); S[4] = pk2c(w32);
#pragma unroll
    for (int i = 1; i < 4; i++) S[4 + i] = cm2(S[i], S[4]);
#pragma unroll
    for (int i = 0; i < 8; i++) sts128(ta + 4096 + ((i << 4) ^ f), B2[i].re, B2[i].im, S[i].re, S[i].im);
    const C2 m64 = pk2c(w64), m128 = pk2c(w128);
    sts128(ktab + 8192 + lane * 16, m64.re, m64.im, m128.re, m128.im);
    __syncwarp();
  } else {
    u32 sa = SM_SIL + 576 * (w & 1) + 24 * min(lane, 23u);
#pragma unroll 1
    for (int j = 0; j < 6; j++) {
      sts32(sa, pk_bf(silu_f(blo(la)), silu_f(bhi(la))));
      la = ai; ai = cr.x; cr.x = cr.y; cr.y = ci.x; ci.x = ci.y; sa += 4;
    }
    bsync(7, 64);
  }
  TS(2);
  const u32 pm = (__reduce_or_sync(~0u, epv) & 1) ? 0 : TAGM;
  sts32(SM_THR + 4, pm);
  if (w < 9) {
    asm volatile("cp.async.wait_all;" ::: "memory");
    __syncwarp();
    TS(4);
    if (tid == (b - 36 < 72 ? 256 : ~0u)) { mb_expect(SM_MB, 36864); tma3d(SM_UP, &tm_mod, SM_MB, 32 * b, 0); }
    const u32 xa = SM_XST + (lane & 15) * ROW + 128 * w + 16 * (lane >> 4);
    float s[4] = {}, X[2][4] = {}, Y[2][4] = {};
#pragma unroll
    for (int j = 0; j < 4; j++) {
      const uint4 a = ldsm4(xa + 32 * j);
      mma8_bf(X[0], a.x, a.y, a.x); mma8_bf(Y[0], a.x, a.y, a.y);
      mma8_bf(X[1], a.z, a.w, a.z); mma8_bf(Y[1], a.z, a.w, a.w);
      mma_bf(s, a.x, a.y, a.z, a.w, BONE, BONE);
    }
    uint4 t[4];
#pragma unroll
    for (int j = 0; j < 4; j++) t[j] = ldsm4t(xa + 32 * j);
    const float u0 = hi ? X[0][1] + X[1][1] : X[0][0] + X[1][0], u1 = hi ? Y[0][3] + Y[1][3] : Y[0][2] + Y[1][2];
    if (q == g >> 1) sts128(SM_SP + w * 128 + g * 16, fu(s[0]), fu(u0), fu(s[2]), fu(u1));
    bsync(1, 288);
    TS(7);
    const u32 spr = SM_SP + (lane & 7) * 16 + (lane & 8);
    const uint2 t8 = lds64(spr + 1024);
    const float f8 = lane < 16 ? 1.f : 0.f;
    float S1 = uf(t8.x) * f8, S2 = uf(t8.y) * f8;
#pragma unroll
    for (int i = 0; i < 4; i++) { const uint2 u = lds64(spr + (lane & 16) * 32 + i * 128); S1 += uf(u.x); S2 += uf(u.y); }
    S1 += __shfl_xor_sync(~0u, S1, 16); S2 += __shfl_xor_sync(~0u, S2, 16);
    const float mu = S1 * (1.f / 576.f), var = fmaxf(fmaf(-mu, mu, S2 * (1.f / 576.f)), 0.f);
    const float m = rbf(mu), rs = rcpf(rbf(sqrta(rbf(rbf(var) + 1e-5f))));
    const float ra = rs * 0.0625f;
    sts64(SM_AF + w * 128 + (lane & 15) * 8, fu(ra), fu(-m * ra));
    __syncwarp();
    TS(55);
    const uint4 f0 = lds128(SM_AF + w * 128 + q * 16), f1 = lds128(SM_AF + w * 128 + 64 + q * 16);
    const u32 zdst = SM_GATE + w * 2048 + (g >> 1) * 128 + (lane & 15) * 8;
    const u32 pz = (q & 1) ? 0 : pm;
#pragma unroll
    for (int j = 0; j < 8; j++) {
      const u32 x0 = j & 1 ? t[j >> 1].z : t[j >> 1].x, x1 = j & 1 ? t[j >> 1].w : t[j >> 1].y;
      sts64((j & 1 ? zdst ^ 64 : zdst) + 512 * (j >> 1), pk_hf(fmaf(blo(x0), uf(f0.x), uf(f0.y)), fmaf(bhi(x0), uf(f0.z), uf(f0.w))) | pz,
            pk_hf(fmaf(blo(x1), uf(f1.x), uf(f1.y)), fmaf(bhi(x1), uf(f1.z), uf(f1.w))));
    }
    TS(53);
    if (w < 8) barrive(15, 288);
    else {
      bsync(15, 288);
      TS(54);
      if (lane == 0) {
        PROXY_FENCE();
        bulk_out<BLK>(gs + b * BLK, SM_GATE);
        asm volatile("cp.async.bulk.commit_group;" ::: "memory");
        if (PFG & 1) l2_pre<WSH / 2>(p.wg + b * WSH);
      }
      const float rh = rbf(rs);
      sts128(SM_ST + 16 * (lane & 15), pk_bf(-m, -m), pk_bf(rh, rh), pk_bf(rs - rh, rs - rh), 0);
    }
    TS(5);
  }
  if (kw) {
    float D[5][4] = {};
    u32 ta = ktab + q * 128 + ((g ^ (q << 1)) << 4), tm = ktab + 8192 + q * 16;
#pragma unroll 2
    for (int s = 0; s < 8; s++) {
      const uint4 ca = lds128(ta), cb = lds128(ta + 4096), ma = lds128(tm);
      ta = (ta + 512) ^ 16; tm += 64;
      k2048 += __shfl_xor_sync(~0u, k2048, 16 >> s);
      const C2 s0 = {cb.z, cb.w}, s1 = cm2(s0, {ma.x, ma.y}), s2 = cm2(s0, {ma.z, ma.w}), s3 = cm2(s1, {ma.z, ma.w});
      mma_hf(D[0], s0.re, s1.re, s0.im, s1.im, ca.x, ca.y);
      mma_hf(D[2], s0.re, s1.re, s0.im, s1.im, ca.z, ca.w);
      mma_hf(D[4], s0.re, s1.re, s0.im, s1.im, cb.x, cb.y);
      mma_hf(D[1], s2.re, s3.re, s2.im, s3.im, ca.x, ca.y);
      mma_hf(D[3], s2.re, s3.re, s2.im, s3.im, ca.z, ca.w);
    }
    TS(3);
    const u32 xa = (w < 8 ? SM_MODS + (4 + ksig) * KTAB : SM_ZS) + lane * 16;
    if (khf) {
      __syncwarp();
#pragma unroll
      for (int j = 0; j < 5; j++) sts128(xa + 512 * j, fu(D[j][0]), fu(D[j][1]), fu(D[j][2]), fu(D[j][3]));
      if (lane == 0) sts32(xa + 2560, fu(k2048));
      asm volatile("bar.arrive %0,64;" ::"r"(2 + ksig) : "memory");
    } else {
      const u32 t1 = tp + (q < 2 ? (128 + 4 * g + 2 * q) * 4 : T3 * 4 + ((32 * q - 64 + g) ^ 1) * 2);
      const u32 x = 16 * q + (g >> 1) + hi + 1, tb = tp + (hi ? T7E : T9E) * 4 - 4;
      const u32 te = tb + (x + 2 * (x & 1)) * 2, to = tb + TEO * 4 + (x ^ 1) * 2;
      asm volatile("bar.sync %0,64;" ::"r"(2 + ksig) : "memory");
#pragma unroll
      for (int j = 0; j < 5; j++) { const uint4 t = lds128(xa + 512 * j); D[j][0] += uf(t.x); D[j][1] += uf(t.y); D[j][2] += uf(t.z); D[j][3] += uf(t.w); }
      k2048 = (k2048 + uf(lds32(xa + 2560))) * 0.125f;
#pragma unroll
      for (int r = 0; r < 4; r++) {
        const u32 v = pk_hf(D[2 + (r >> 1)][2 * (r & 1)], D[2 + (r >> 1)][2 * (r & 1) + 1]);
        if (q < 2) {
          const u32 vv = __byte_perm(v, v, 0x1010);
          sts32(t1 + (TO + 32 * r) * 4, vv); sts16(t1 + (TO + 32 * r + 1) * 4 + 2, v >> 16); sts16(t1 + (TO + 32 * r - 1) * 4, v);
          sts64(t1 + (TE + 32 * r) * 4, vv, __byte_perm(v, v, 0x1032));
        } else {
          sts16(t1 + 16 * r, v >> 16);
          if (r == 0 && lane == 2) {
            const u32 vv = __byte_perm(v, v, 0x1010);
            sts32(tp + (TO + 256) * 4, vv); sts16(tp + (TO + 257) * 4 + 2, v); sts16(tp + (TO + 255) * 4, v); sts64(tp + (TE + 256) * 4, vv, vv);
          } else sts16(t1 + 16 * r - ((T3 - T5) * 4 + 6) + 8 * hi, v);
        }
      }
#pragma unroll
      for (int r = 0; r < 2; r++) {
        const u32 v = pk_hf(D[4][2 * r], D[4][2 * r + 1]);
        if (r == 0 && lane == 0) { sts16(tp + T5 * 4 + 62 * 2, v); sts32(SM_KV + 4 * ksig, v & 0xffff); sts16(tp + (T9E + TEO) * 4 + 62 * 2, pk_hf(k2048, 0.f)); }
        else { sts16(te + 8 * r, v); sts16(to + 8 * r, v); }
        sts16(te + 8 * r + 16, v >> 16); sts16(to + 8 * r + 16, v >> 16);
      }
      __syncwarp();
#pragma unroll
      for (int r = 0; r < 4; r++) {
        const u32 v = pk_hf(D[r >> 1][2 * (r & 1) + 1], D[r >> 1][2 * (r & 1)]), t2 = tp + lane * 4 + 128 * r;
        sts32(t2 + TO * 4, v); sts16(t2 + TE * 4, v >> 16); sts16(t2 + (TE + 1) * 4 + 2, v);
      }
      __syncwarp();
    }
  } else if (w == (b < 108 ? 11 : ~0u)) {
    float c[4][4] = {};
    u32 aa = SM_UP + ((lane & 7) + 8 * (lane >> 4)) * 64 + ((((lane >> 3) & 1) ^ ((lane & 7) >> 1)) << 4);
    u32 ba = SM_SIL + (lane >> 3) * 16;
    uint4 a[2][10];
#define GLD(n) { _Pragma("unroll") for (int i = 0; i < 2; i++) { a[n][5 * i] = ldsm4(ba + i * 64); \
      _Pragma("unroll") for (int k = 0; k < 4; k++) a[n][5 * i + 1 + k] = ldsm4t((k & 2 ? aa ^ 32 : aa) + i * 2048 + (k & 1) * 1024); } aa += 4096; ba += 128; }
#define GMM(n) { _Pragma("unroll") for (int i = 0; i < 2; i++) _Pragma("unroll") for (int k = 0; k < 4; k++) { const uint4 f = a[n][5 * i + 1 + k], bb = a[n][5 * i]; \
      mma_bf(c[k], f.x, f.y, f.z, f.w, k & 1 ? bb.z : bb.x, k & 1 ? bb.w : bb.y); } }
    mb_wait(SM_MB);
    TS(56);
    GLD(0);
#pragma unroll 1
    for (int s = 0; s < 4; s++) { GLD(1); GMM(0); GLD(0); GMM(1); }
    GMM(0);
    const float v0 = (q & 1) ? c[0][2] + c[1][2] : c[0][0] + c[1][0], v1 = (q & 1) ? c[2][2] + c[3][2] : c[2][0] + c[3][0];
    str16(gs + (G_MOD + b * 128 + 2 * g + 16 * q), pk_bf(rbf((q & 2) ? v1 : v0) * F2M64, 0.f) | (g < 2 ? pm : 0));
    TS(57);
  }
  TS(6);
  u32 tid2 = tid;
  if (w < 4) {
    asm volatile("setmaxnreg.inc.sync.aligned.u32 232;");
    const u32 tid = tid2 + p.zero, w = tid >> 5, lane = tid & 31, g = lane >> 2, q = lane & 3, hi = g & 1, zr = tid >> 16, tp = SM_TAP + w * TAPS;
    const u32 pml = opq((g & 3) ? 0 : pm);
    const u32 tr = tp + ((hi ? TO : TE) + (g >> 1) - q) * 4;
    u32 T[33][4], B5[5][2], B3[5][2];
#pragma unroll
    for (int d = 0; d < 33; d++) {
      T[d][0] = lds32(tr + 32 * d); T[d][1] = lds32(tr + 32 * d + 16);
      T[d][2] = cpy(d ? T[d - 1][1] : zr, zr, 0); T[d][3] = cpy(T[d][0], zr, 1);
    }
    const u32 t33 = cpy(T[32][1], zr, 0), z33 = cpy(zr, zr, 1);
    if (TPIN) {
#pragma unroll
      for (int d = 0; d < 33; d++) asm volatile("{.reg .pred p; setp.ne.u32 p,%2,0; @p st.shared.v2.u32 [%2],{%0,%1};}" ::"r"(T[d][2]), "r"(T[d][3]), "r"(zr) : "memory");
    }
    const u32 bt = tp + (T5 + g - q) * 4;
#pragma unroll
    for (int d = 0; d < 5; d++) {
      B5[d][0] = lds32(bt + 32 * d); B5[d][1] = lds32(bt + 32 * d - 16);
      B3[d][0] = lds32(bt + 32 * d + (T3 - T5) * 4); B3[d][1] = lds32(bt + 32 * d - 16 + (T3 - T5) * 4);
    }
    u32 za = opq(SM_ZS + 16 + w * ZSS + ((lane >> 3) & 1) * ZPS + ((lane & 7) + (lane >> 4)) * 16);
    u32 wa = opq(SM_W + W5O + w * WSL + row16(lane));
    u32 sa = opq(SM_W + W9O - 2048 + w * WSL + lane * 16);
    u32 yo = opq(G_Y + b * BLK + 256 * q + w * 32 + 4 * g);
    const u32 fa = opq(SM_SC + 16 * w + 8), bw = opq((BW >> 4 * w) & 15), bs = opq((BS >> 4 * w) & 15);
    if (TPIN) asm volatile("{.reg .pred p; setp.ne.u32 p,%8,0; @p st.shared.v4.u32 [%8],{%0,%1,%2,%3}; @p st.shared.v4.u32 [%8],{%4,%5,%6,%7};}"
                           ::"r"(za), "r"(wa), "r"(sa), "r"(yo), "r"(fa), "r"(bw), "r"(bs), "r"(pml), "r"(zr) : "memory");
    TS(8);
    uint2 fc;
    u32 F;
    if (F8) { bsync(8, 384); fc = lds64(fa); F = __byte_perm(fu(uf(fc.x) * uf(fc.y)), 0, 0x3232); pin(zr, F); }
    bsync(9, 384);
    TS(11);
    float A[4][4] = {};
    uint4 Z[4];
    Z[0] = ldsm4(za); Z[1] = ldsm4(za + 32);
    if (!F8) { fc = lds64(fa); F = __byte_perm(fu(uf(fc.x) * uf(fc.y)), 0, 0x3232); }
#define STEP(s, b0, b1) { _Pragma("unroll") for (int i = 0; i < 4; i++) mma_hf_t(A[i], T[8 * i + 7 - (s)], b0, b1); }
#define PAIR(n) { Z[(n + 2) & 3] = ldsm4(za + 32 * (n + 2)); STEP(2 * n, Z[n].x, Z[n].y); STEP(2 * n + 1, Z[n].z, Z[n].w); }
#define LAST(N) mma8_hf(N, t33, z33, Z[3].y); float O[4]; mma_hf_o(O, A[0], T[0], Z[3].z, Z[3].w); \
    _Pragma("unroll") for (int i = 0; i < 3; i++) mma_hf_o(A[i], A[i + 1], T[8 * i + 8], Z[3].z, Z[3].w); \
    mma_hf_o(A[3], N, T[32], Z[3].z, Z[3].w);
#pragma unroll 1
    for (int j = 0; j < 4; j++) {
      PAIR(0); PAIR(1); PAIR(2);
      Z[1] = ldsm4(za + 160); STEP(6, Z[3].x, Z[3].y);
      float N[4] = {};
      LAST(N);
      if (INCV) inc<128>(za);
      y_store<128>(O[0], O[1], O[2], O[3], F, pml, gs + yo);
      if (!INCV) za += 128;
      yo += 1024;
      TSJ(j);
    }
    bsyncr(bw);
    uint4 a5;
    if (A5P) a5 = ldsm4t(wa);
#pragma unroll 1
    for (int j = 4; j < 13; j++) {
      if (j == 8) bsyncr(bs);
      if (!A5P) a5 = ldsm4t(wa);
      const uint4 a3 = ldsm4t(wa + (W3O - W5O));
      uint4 s3 = {0, 0, 0, 0};
      if (j >= 8) s3 = lds128(sa);
      PAIR(0);
      float N[4] = {};
#pragma unroll
      for (int i = 0; i < 4; i++) mma_hf(A[i], a5.x, a5.y, a5.z, a5.w, B5[i][0], B5[i][1]);
      mma_hf(N, a5.x, a5.y, a5.z, a5.w, B5[4][0], B5[4][1]);
      if (INCV) asm volatile("{add.u32 %0,%0,256; xor.b32 %0,%0,32;}" : "+r"(wa)); else wa = (wa + 256) ^ 32;
      if (A5P) a5 = ldsm4t(wa);
      PAIR(1);
#pragma unroll
      for (int i = 0; i < 4; i++) mma_hf(A[i], a3.x, a3.y, a3.z, a3.w, B3[i][0], B3[i][1]);
      mma_hf(N, a3.x, a3.y, a3.z, a3.w, B3[4][0], B3[4][1]);
      PAIR(2);
      Z[1] = ldsm4(za + 160); STEP(6, Z[3].x, Z[3].y);
      LAST(N);
      if (INCV) { inc<128>(za); inc<512>(sa); }
      y_store<128>(O[0] + uf(s3.x), O[1] + uf(s3.y), O[2] + uf(s3.z), O[3] + uf(s3.w), F, pml, gs + yo);
      if (!INCV) { za += 128; sa += 512; }
      yo += 1024;
      TSJ(j);
    }
    {
      asm volatile("mov.u32 %0,%%tid.x;" : "=r"(tid2));
      const uint4 s3 = lds128(sa), s4 = lds128(sa + 512), s5 = lds128(sa + 1024);
      float X[3][4] = {{uf(s4.x), uf(s4.y), uf(s4.z), uf(s4.w)}, {}, {uf(s5.x), uf(s5.y), uf(s5.z), uf(s5.w)}};
#pragma unroll
      for (int ty = 0; ty < 2; ty++) {
        const uint4 a = A5P && !ty ? a5 : ldsm4t(wa + ty * (W3O - W5O)), c = ldsm4t((wa ^ 32) + 256 + ty * (W3O - W5O)), d = ldsm4t(wa + 512 + ty * (W3O - W5O));
#pragma unroll
        for (int i = 0; i < 3; i++) mma_hf(A[i], a.x, a.y, a.z, a.w, ty ? B3[i][0] : B5[i][0], ty ? B3[i][1] : B5[i][1]);
#pragma unroll
        for (int i = 0; i < 2; i++) mma_hf(X[i], c.x, c.y, c.z, c.w, ty ? B3[i][0] : B5[i][0], ty ? B3[i][1] : B5[i][1]);
        mma_hf(X[2], d.x, d.y, d.z, d.w, ty ? B3[0][0] : B5[0][0], ty ? B3[0][1] : B5[0][1]);
      }
#pragma unroll
      for (int n = 0; n < 4; n++) {
        const uint4 f0 = n < 2 ? Z[n] : ldsm4(za + 32 * n), f1 = ldsm4(za + 32 * n + 128), f2 = ldsm4(za + 32 * n + 256);
#pragma unroll
        for (int s = 2 * n; s < 2 * n + 2; s++) {
#pragma unroll
          for (int i = 0; i < 3; i++) mma_hf_t(A[i], T[8 * i + 7 - s], s & 1 ? f0.z : f0.x, s & 1 ? f0.w : f0.y);
          mma_hf_t(X[0], T[7 - s], s & 1 ? f1.z : f1.x, s & 1 ? f1.w : f1.y); mma_hf_t(X[1], T[15 - s], s & 1 ? f1.z : f1.x, s & 1 ? f1.w : f1.y);
          mma_hf_t(X[2], T[7 - s], s & 1 ? f2.z : f2.x, s & 1 ? f2.w : f2.y);
        }
      }
      y_store<128>(A[0][0] + uf(s3.x), A[0][1] + uf(s3.y), A[0][2] + uf(s3.z), A[0][3] + uf(s3.w), F, pml, gs + yo);
      y_store<128>(A[1][0] + X[0][0], A[1][1] + X[0][1], A[1][2] + X[0][2], A[1][3] + X[0][3], F, pml, gs + yo + 1024);
      y_store<128>(A[2][0] + X[1][0] + X[2][0], A[2][1] + X[1][1] + X[2][1], A[2][2] + X[1][2] + X[2][2], A[2][3] + X[1][3] + X[2][3], F, pml, gs + yo + 2048);
    }
    barrive(12, N12);
    TS(15);
  } else {
    asm volatile("setmaxnreg.dec.sync.aligned.u32 136;");
    const u32 t8 = tid - 128, pml = (g & 3) ? 0 : pm;
    {
      TS(12);
      if (PFG == 1 && tid == 288) l2_pre<WSH / 2>(p.wg + (b * WSH + WSH / 2));
      const char* zs = gs + ((16 * w - 64 + (lane >> 3)) * BLK + b * 128 + ((lane & 7) * 16 ^ rho * 64));
      const char* zs4 = gs + ((t8 >> 1) * BLK + (Ps >> 4) * 512 + (Ps & 6) * 64 + ((Ps >> 2 ^ Ps) & 2) * 32 + (Ps & 1) * 32 + (t8 & 1) * 16);
      uint4 v[5];
      v[4].x = INVAL;
      if (ZD) wait_clk(t0, ZD);
      const u32 d = lane < 4 ? chan(b, lane) : Ps;
      const char* mp = gs + (G_MOD + (d >> 5) * 128 + (d & 24) * 2);
      uint4 ta, tc;
      ta.x = tc.x = INVAL;
      const u32 t9 = w == 9 ? pm : INVAL;
      pin2(zr, zs, zs4);
      conv();
      POLLM({ rld128<TAGM>(ta, mp, t9); rld128<TAGM>(tc, mp + MODJ, t9); rld128<TAGM>(v[4], zs4, pm); }, lop3<0xbe>(v[4].x, pm, ne3(ta.x, tc.x, t9)), TAGM, 1);
      TS(58);
#pragma unroll
      for (int j = 0; j < 4; j++) v[j] = ldr128(zs + j * 4 * BLK);
      if (w == 9) {
        const u32 aw = (d & 4) ? ((d & 2) ? ta.w : ta.z) : ((d & 2) ? ta.y : ta.x & ~TAGM);
        const u32 cw = (d & 4) ? ((d & 2) ? tc.w : tc.z) : ((d & 2) ? tc.y : tc.x & ~TAGM);
        const float sa = ((d & 1) ? bhi(aw) : blo(aw)) * F2P64, c1 = rbf(fmaf((d & 1) ? bhi(cw) : blo(cw), F2P64, 1.f));
        const u32 EM = min(max(fu(fmaxf(32.f * fabsf(c1), fabsf(sa))) >> 23, 80u), 250u);
        const float inv = uf((264 - EM) << 23);
        if (lane < 5) { sts64(SM_SC + 16 * lane, pk_hf(16.f * c1 * inv, 16.f * c1 * inv), pk_hf(sa * inv, sa * inv)); sts32(SM_SC + 16 * lane + 8, (EM - 74) << 23); }
        TS(10);
      }
#define MARKERS() if (tid == 256) { \
        bulk_out<2048>(gs + (G_Y + 16384 + b * BLK), SM_INV); \
        _Pragma("unroll") for (int i = MT / 2; i < 8; i++) bulk_out<2048>(gs + (G_Y + 2048 * i + b * BLK), SM_INV); \
        bulk_out<2048>(gs + (G_PART + b * 2048), SM_INV); bulk_out<512>(gs + (G_ACT + b * 512), SM_INV); \
        bulk_out<32>(gs + (G_KEY + b * KST), SM_INV); if (!rho) bulk_out<128>(gs + (G_ACT + Ps * 128), SM_INV); \
        asm volatile("cp.async.bulk.commit_group;" ::: "memory"); }
#define GATE() { mb_expect(SM_MB + 8, rho ? SLV : 46080); \
        _Pragma("unroll") for (int i = GE; i < 3; i++) tma3d(SM_GATE + 12288 * i, &tm_gate, SM_MB + 8, 32 * b, i); \
        if (!rho) tma3d(SM_GATE + SLV, &tm_gs, SM_MB + 8, 4096 + 4 * b, 0); }
#define UP() { mb_expect(SM_MB + 16, rho ? SLV : 46080); tma3d(SM_UP, &tm_up, SM_MB + 16, 32 * b, 0); \
        if (!rho) tma3d(SM_UP + SLV, &tm_us, SM_MB + 16, 4096 + 4 * b, 0); }
      if (PFU == 2 && tid == 256) l2_pre<WSH>(p.wu + b * WSH);
      if (GE && tid == 256) {
        asm volatile("cp.async.bulk.wait_group.read 0;" ::: "memory");
#pragma unroll
        for (int i = 0; i < GE; i++) tma3d(SM_GATE + 12288 * i, &tm_gate, SM_MB + 8, 32 * b, i);
      }
      if (PFG == 2 && tid == 256) l2_pre<WSH>(p.wg + b * WSH);
      if (PFG == 3 && tid == 256) l2_pre<WSH / 2>(p.wg + (b * WSH + WSH / 2));
      bsync(8, F8 ? 384 : 256);
      const uint2 cc = lds64(SM_SC + 8 * (t8 & 6)), c4 = lds64(SM_SC + 64);
      sts128(SM_Z4 + 256 + (t8 & 1) * ZP4 + (t8 >> 1) * 16, hfma(v[4].x & ~TAGM, c4.x, c4.y), hfma(v[4].y, c4.x, c4.y), hfma(v[4].z, c4.x, c4.y), hfma(v[4].w, c4.x, c4.y));
      if (t8 < 96) sts128(t8 < 64 ? SM_ZS + (t8 & 7) * ZPS + (t8 >> 3) * 16 : SM_Z4 + (t8 & 1) * ZP4 + (t8 & 30) * 8, 0, 0, 0, 0);
      asm volatile("cp.async.bulk.wait_group.read 0;" ::: "memory");
      const u32 dst = SM_ZS + 128 + (t8 & 7) * ZPS + (16 * w - 64 + (lane >> 3)) * 16;
      pin(zr, dst);
      conv();
      POLLS(_Pragma("unroll") for (int j = 0; j < 4; j++) sts128(dst + j * 64, hfma(v[j].x & ~TAGM, cc.x, cc.y), hfma(v[j].y, cc.x, cc.y), hfma(v[j].z, cc.x, cc.y), hfma(v[j].w, cc.x, cc.y)),
            _Pragma("unroll") for (int j = 0; j < 4; j++) rld128<TAGM>(v[j], zs + j * 4 * BLK, pm), ne3(v[0].x, v[1].x, pm) | ne3(v[2].x, v[3].x, pm), TAGM, 1);
      TS(9);
      bsync(9, 384);
      TS(11);
      if (MKT == 1) MARKERS();
      const bool lng = w < 8 || w == 9;
      const u32 ts = lane + 32 * (w == 8 ? 0 : w - 9), c = min(ts, 71u), ma = SM_MODS + 16 * c;
      const u32 sig = lng ? ksig : ts >> 4, l2 = lng ? lane : 32 + (ts & 15);
      const char* mq = gs + (G_MOD + (c >> 2) * 128 + (c & 3) * 16);
      if (!lng) {
#pragma unroll
        for (int j = 0; j < 6; j++) cpa16(ma + 1152 * j, mq + j * MODJ);
        cpa16(ma + 1152 * 6, p.dsk + 16 * c); cpa16(ma + 1152 * 7, p.wr + 16 * c);
        if (PFU == 3) {
#pragma unroll
          for (int j = 0; j < 4; j++) if (ts < 81) l2_line(p.wu + (b * WSH + (81 * j + ts) * 128));
        }
        if (tid == 352) {
          PROXY_FENCE();
          if (PFU == 1) l2_pre<WSH>(p.wu + b * WSH);
          if (!TG) GATE();
          if (!TU) UP();
        }
      }
      const u32 wb = SM_W + sig * WSL;
      if (sig < 5) {
        const u32 za = (sig < 4 ? SM_ZS + 128 + sig * ZSS : SM_Z4 + 256) + l2 * 32, zb = za + (sig < 4 ? ZPS : ZP4);
        const uint4 c0 = lds128(zb - 32), c1 = lds128(za - 16), c2 = lds128(zb - 16), c3 = lds128(za), c4 = lds128(zb), c5 = lds128(za + 16), c6 = lds128(zb + 16);
        const u32 P[25] = {c0.z, c0.w, c1.x, c1.y, c1.z, c1.w, c2.x, c2.y, c2.z, c2.w, c3.x, c3.y, c3.z, c3.w, c4.x, c4.y, c4.z, c4.w, c5.x, c5.y, c5.z, c5.w, c6.x, c6.y, c6.z};
        u32 Q[25], D1[24], F4[23], W5[21], W3[17];
#pragma unroll
        for (int j = 1; j < 25; j++) Q[j] = __byte_perm(P[j - 1], P[j], 0x5432);
#pragma unroll
        for (int j = 1; j < 24; j++) D1[j] = hadd(P[j], Q[j]);
#pragma unroll
        for (int j = 2; j < 23; j++) F4[j] = hadd(D1[j], D1[j - 1]);
#pragma unroll
        for (int n = 0; n < 21; n++) W5[n] = hadd(F4[n + 2], P[n]);
#pragma unroll
        for (int n = 0; n < 17; n++) W3[n] = hadd(Q[n + 8], D1[n + 7]);
        const u32 a0 = wb + W5O + 64 * l2 + 16 * ((l2 >> 1) & 3);
#pragma unroll
        for (int i = 0; i < 4; i++) {
          sts128(a0 ^ (16 * i), W5[4 * i + 5], W5[4 * i + 6], W5[4 * i + 7], W5[4 * i + 8]);
          sts128((a0 ^ (16 * i)) + (W3O - W5O), W3[4 * i + 1], W3[4 * i + 2], W3[4 * i + 3], W3[4 * i + 4]);
        }
        if (lng) {
          if (lane < 16) sts128(wb + (lane & 7) * 16 + (lane & 8) * 400, 0, 0, 0, 0);
          const u32 a1 = wb + 32 * lane + 16 * ((lane >> 2) & 1);
#pragma unroll
          for (int i = 0; i < 4; i++) {
            const u32 a = (a1 ^ (16 * (i >> 1))) + 1024 * (i & 1), n = 4 * i;
            sts128(a + V2O, hadd(Q[n + 9], P[n + 8]), hadd(Q[n + 10], P[n + 9]), hadd(Q[n + 11], P[n + 10]), hadd(Q[n + 12], P[n + 11]));
            sts128(a + W9O, hadd(F4[n + 4], W5[n]), hadd(F4[n + 5], W5[n + 1]), hadd(F4[n + 6], W5[n + 2]), hadd(F4[n + 7], W5[n + 3]));
            sts128(a + W7O, hadd(F4[n + 6], W3[n]), hadd(F4[n + 7], W3[n + 1]), hadd(F4[n + 8], W3[n + 2]), hadd(F4[n + 9], W3[n + 3]));
          }
        }
      }
      if (w < 8) barriver((BW >> (4 * w - 16)) & 15);
      else if (!(w & 1)) { barriver((BW >> (4 * w - 32)) & 15); barriver((BW >> (4 * w - 28)) & 15); }
      __syncwarp();
      TS(32);
      if (lng) {
        const u32 wa = wb + ((lane >> 3) & 1) * 1024 + (((lane & 7) ^ (lane >> 4)) + 8 * (lane >> 4)) * 16;
        const u32 kv = lds32(SM_KV + 4 * sig), bi = (g >> 1) == q ? (hi ? kv << 16 : kv) : 0u;
        float acc[8][4] = {};
#pragma unroll
        for (int j = 0; j < 4; j++) { const uint4 a = ldsm4t(wa + V2O + j * 256); mma8_hf(acc[2 * j], a.x, a.y, bi); mma8_hf(acc[2 * j + 1], a.z, a.w, bi); }
        u32 bt = tp + (T9E + hi * TEO + (g >> 1) - q) * 4, wt = wa + W9O;
#pragma unroll 1
        for (int ty = 0; ty < 2; ty++) {
          uint4 a[4];
#pragma unroll
          for (int be = 0; be < 4; be++) a[be] = ldsm4t(wt + be * 256);
          u32 b1 = lds32(bt - 16);
#pragma unroll
          for (int d = 0; d < 8; d++) {
            const u32 b0 = lds32(bt + 16 * d);
#pragma unroll
            for (int be = 0; be < 4; be++) if (d + 2 * be < 8) mma_hf(acc[d + 2 * be], a[be].x, a[be].y, a[be].z, a[be].w, b0, b1);
            b1 = b0;
          }
          bt += (T7E - T9E) * 4; wt += W7O - W9O;
        }
        __syncwarp();
#pragma unroll
        for (int j = 0; j < 8; j++) sts128(wb + W9O + j * 512 + lane * 16, fu(acc[j][0]), fu(acc[j][1]), fu(acc[j][2]), fu(acc[j][3]));
        if (w != 9) barriver((BS >> (4 * w - 16)) & 15);
        TS(34);
      }
      if (!lng) {
        asm volatile("cp.async.wait_all;" ::: "memory");
        uint4 md[6];
#pragma unroll
        for (int j = 0; j < 6; j++) md[j] = lds128(ma + 1152 * j);
        const uint4 dk = lds128(ma + 1152 * 6), wr = lds128(ma + 1152 * 7);
        POLLW(_Pragma("unroll") for (int j = 0; j < 6; j++) md[j] = ldr128(mq + j * MODJ),
              ((md[0].x ^ pm) | (md[1].x ^ pm) | (md[2].x ^ pm) | (md[3].x ^ pm) | (md[4].x ^ pm) | (md[5].x ^ pm)) & TAGM, 4);
#pragma unroll
        for (int j = 0; j < 6; j++) {
          const u32 o = (j % 3 == 1) ? BONE : 0x80008000u;
          md[j] = make_uint4(bfma(md[j].x & ~TAGM, B2P64, o), bfma(md[j].y, B2P64, o), bfma(md[j].z, B2P64, o), bfma(md[j].w, B2P64, o));
          if (j > 2) sts128(ma + 1152 * j, md[j].x, md[j].y, md[j].z, md[j].w);
        }
        const uint4 gd = make_uint4(bmul(md[2].x, dk.x), bmul(md[2].y, dk.y), bmul(md[2].z, dk.z), bmul(md[2].w, dk.w));
#pragma unroll
        for (int j = 0; j < 2; j++) sts128(ma + 1152 * j, bmul(md[j].x, gd.x), bmul(md[j].y, gd.y), bmul(md[j].z, gd.z), bmul(md[j].w, gd.w));
        sts128(ma + 2304, bmul(md[2].x, B2P64), bmul(md[2].y, B2P64), bmul(md[2].z, B2P64), bmul(md[2].w, B2P64));
        const uint4 H = make_uint4(bmul(md[4].x, wr.x), bmul(md[4].y, wr.y), bmul(md[4].z, wr.z), bmul(md[4].w, wr.w));
        sts128(ma + 1152 * 7, H.x, H.y, H.z, H.w);
        sts128(ma + 1152 * 8, bfma(md[4].x, wr.x, H.x ^ 0x80008000u), bfma(md[4].y, wr.y, H.y ^ 0x80008000u), bfma(md[4].z, wr.z, H.z ^ 0x80008000u), bfma(md[4].w, wr.w, H.w ^ 0x80008000u));
        float c4[4] = {};
        mma_bf(c4, md[4].x, md[3].x, md[4].y, md[3].y, wr.x, wr.y); mma_bf(c4, md[4].z, md[3].z, md[4].w, md[3].w, wr.z, wr.w);
        if (q == g >> 1) sts64(SM_RC + (ts >> 2) * 8, fu(hi ? c4[1] : c4[0]), fu(hi ? c4[3] : c4[2]));
        if (ts < 2) sts128(SM_ONE + 16 * ts, ts ? 0 : BONE, ts ? 0 : BONE, ts ? 0 : BONE, ts ? 0 : BONE);
        TS(14);
        if (MKT == 2) MARKERS();
        if (w == 8) asm volatile("cp.async.bulk.wait_group 0;" ::: "memory");
        if (PFW == 2) {
#pragma unroll
          for (int j = 0; j < 4; j++) if (ts < 81) l2_line(p.wd + (b * WSH + (81 * j + ts) * 128));
        }
        bsync(13, 96);
        if (w == 8) { barriver(2); barriver(3); barriver(5); barriver(6); if (HLP) barrive(7, 64); }
      }
      if (!HLP) { if (w >= 8) barrive(11, 256); }
      else if (w == 9) barrive(11, 128);
    }
    const u32 jw = w < 6 ? w ^ 1 : w < 8 ? w : max(w - 4, 5u);
    const int u0 = 4 * (jw - 4) + 2 * rho;
    const u32 t4 = SM_TAP + 4 * TAPS, s3a = SM_W + 4 * WSL + (u0 >= 8 ? W9O + (u0 - 8) * 512 : V2O) + lane * 16, hb = (0x4987 >> (4 * jw - 16)) & 15;
#define FARL() { u32 wa = (SM_W + 4 * WSL + W5O + row16(lane) + (u0 - 3) * 256) ^ 32, bt = t4 + (T5 + g - q) * 4; \
      _Pragma("unroll 1") for (int al = min(u0 - 2, 6); al > 0; al--) { \
        _Pragma("unroll") for (int ty = 0; ty < 2; ty++) { \
          const uint4 a = ldsm4t(wa + ty * (W3O - W5O)); \
          const u32 bb = bt + ty * (T3 - T5) * 4; \
          mma_hf(acc[ty], a.x, a.y, a.z, a.w, lds32(bb - 32), lds32(bb - 48)); \
          mma_hf(acc[2 + ty], a.x, a.y, a.z, a.w, lds32(bb), lds32(bb - 16)); \
        } \
        wa = (wa - 256) ^ 32; bt += 32; } }
    if (w < 8) {
      u32 tr = t4 + ((hi ? TO : TE) + (g >> 1) - q) * 4;
      u32 zb = SM_Z4 + 256 + ((lane >> 3) & 1) * ZP4 + u0 * 128 + (lane & 7) * 16 + (lane >> 4) * 128;
      float acc[4][4] = {};
      u32 prev = 0;
#pragma unroll 1
      for (int it = min(u0 + 2, 4); it; it--) {
#pragma unroll
        for (int s = 0; s < 8; s++) {
          const uint4 z = ldsm4(zb - 16 * s);
          const u32 t0 = lds32(tr + 32 * s), t1 = lds32(tr + 32 * s + 16);
          mma_hf(acc[s & 1], t0, t1, prev, t0, z.x, z.y);
          mma_hf(acc[2 + (s & 1)], t0, t1, prev, t0, z.z, z.w);
          prev = t1;
        }
        zb -= 128; tr += 256;
      }
      {
        const uint4 z = ldsm4(zb); const u32 t0 = lds32(tr), t1 = lds32(tr + 16);
        mma_hf(acc[0], t0, t1, prev, t0, z.x, z.y); mma_hf(acc[2], t0, t1, prev, t0, z.z, z.w);
        if (jw > 4) { const uint4 y = ldsm4(zb - 16); mma8_hf(acc[1], t1, zr, y.y); mma8_hf(acc[3], t1, zr, y.w); }
      }
      if (!HLP) { bsync(11, 256); FARL(); }
      else asm volatile("bar.sync %0,64;" ::"r"(hb) : "memory");
      TS(35);
      const uint2 fc = lds64(SM_SC + 16 * 4 + 8);
      const u32 F = __byte_perm(fu(uf(fc.x) * uf(fc.y)), 0, 0x3232);
      char* yp = gs + (G_Y + 16384 - 2048 + b * BLK + jw * 512 + q * 64 + 4 * g);
#pragma unroll
      for (int j = 0; j < 2; j++) {
        uint4 s3 = {0, 0, 0, 0};
        if (u0 >= (HLP ? 4 : 8)) s3 = lds128(s3a + j * 512);
        y_store<32>(acc[2 * j][0] + acc[2 * j + 1][0] + uf(s3.x), acc[2 * j][1] + acc[2 * j + 1][1] + uf(s3.y), acc[2 * j][2] + acc[2 * j + 1][2] + uf(s3.z),
                acc[2 * j][3] + acc[2 * j + 1][3] + uf(s3.w), F, pml, yp + j * 256);
      }
      TS(16);
    } else {
      if (HLP && w != 9) {
        bsync(11, 128);
        if (HD) wait_clk(clk(), HD);
        float acc[4][4] = {};
        if (u0 >= 8) {
#pragma unroll
          for (int j = 0; j < 2; j++) { const uint4 t = lds128(s3a + j * 512); acc[2 * j][0] = uf(t.x); acc[2 * j][1] = uf(t.y); acc[2 * j][2] = uf(t.z); acc[2 * j][3] = uf(t.w); }
        }
        FARL();
#pragma unroll
        for (int j = 0; j < 2; j++)
          sts128(s3a + j * 512, fu(acc[2 * j][0] + acc[2 * j + 1][0]), fu(acc[2 * j][1] + acc[2 * j + 1][1]), fu(acc[2 * j][2] + acc[2 * j + 1][2]), fu(acc[2 * j][3] + acc[2 * j + 1][3]));
        asm volatile("bar.arrive %0,64;" ::"r"(hb) : "memory");
        TS(16);
      }
      if (PFW == 3 && w == 9) {
#pragma unroll 1
        for (int j = 0; j < 12; j++) { if (lane < 27) l2_line(p.wd + (b * WSH + (27 * j + lane) * 128)); wait_clk(clk(), PFP); }
      }
      if (TG | TU | TW) {
        if (tid == 352) {
          if (TG) { wait_clk(t0, TG); GATE(); }
          if (TW < TU) { wait_clk(t0, TW); l2_pre<WSH>(p.wd + b * WSH); }
          if (TU) { wait_clk(t0, TU); UP(); }
          if (TW >= TU) { wait_clk(t0, TW); l2_pre<WSH>(p.wd + b * WSH); }
        }
      } else if (PFW < 2 && tid == 352) { mb_wait(SM_MB + 8); if (PFW) mb_wait(SM_MB + 16); l2_pre<WSH>(p.wd + b * WSH); }
      if (D0C && tid == 352 && b < 108) {
        mb_wait(SM_MB + 16);
        PROXY_FENCE();
        mb_expect(SM_MB + 24, 49152);
        tma3d(SM_TAP, &tm_down, SM_MB + 24, 64 * (b % 9), 4 * (b / 9));
      }
      TS(17);
    }
  }
  post_conv(p, &tm_down, tid2 + p.zero, b, b3);
  TSD();
  if (s2u(smem) != SM0) __trap();
}

typedef CUresult (*EncFn)(CUtensorMap*, CUtensorMapDataType, cuuint32_t, void*, const cuuint64_t*, const cuuint64_t*, const cuuint32_t*, const cuuint32_t*,
                          CUtensorMapInterleave, CUtensorMapSwizzle, CUtensorMapL2promotion, CUtensorMapFloatOOBfill);
static void make_map(EncFn enc, CUtensorMap* tm, void* ptr, int cols, int rows, int bw, int nb, CUtensorMapSwizzle sw, int gr = 192, int prom = 0) {
  cuuint64_t gd[3] = {(cuuint64_t)cols, (cuuint64_t)gr, (cuuint64_t)(rows / gr)}, gs[2] = {(cuuint64_t)cols * 2, (cuuint64_t)cols * 2 * gr};
  cuuint32_t bd[3] = {(cuuint32_t)bw, (cuuint32_t)gr, (cuuint32_t)nb}, es[3] = {1, 1, 1};
  enc(tm, CU_TENSOR_MAP_DATA_TYPE_BFLOAT16, 3, ptr, gd, gs, bd, es, CU_TENSOR_MAP_INTERLEAVE_NONE, sw, (CUtensorMapL2promotion)prom, CU_TENSOR_MAP_FLOAT_OOB_FILL_NONE);
}
extern "C" void kernel_launch(void* const* d_in, const int* in_sizes, int n_in, void* d_out, int out_size) {
  static EncFn enc = nullptr;
  static void* scratch = nullptr;
  if (!enc) {
    cudaGetSymbolAddress(&scratch, g_s);
    cudaDriverEntryPointQueryResult qr;
    cudaGetDriverEntryPoint("cuTensorMapEncodeTiled", (void**)&enc, cudaEnableDefault, &qr);
    cudaFuncSetAttribute(fused_kernel, cudaFuncAttributeMaxDynamicSharedMemorySize, SM_TOTAL);
  }
  CUtensorMap tm_mod, tm_gate, tm_gs, tm_up, tm_us, tm_down;
  make_map(enc, &tm_mod, d_in[13], 3456, 576, 32, 3, CU_TENSOR_MAP_SWIZZLE_64B, 192, PRM);
  make_map(enc, &tm_gate, d_in[9], 4608, 576, 32, 1, CU_TENSOR_MAP_SWIZZLE_64B, 192, PRG);
  make_map(enc, &tm_gs, d_in[9], 4608, 576, 8, 3, CU_TENSOR_MAP_SWIZZLE_NONE);
  make_map(enc, &tm_up, d_in[10], 4608, 576, 32, 3, CU_TENSOR_MAP_SWIZZLE_64B, 192, PRU);
  make_map(enc, &tm_us, d_in[10], 4608, 576, 8, 3, CU_TENSOR_MAP_SWIZZLE_NONE, 192, PRS);
  make_map(enc, &tm_down, d_in[11], 576, 4608, 64, 1, CU_TENSOR_MAP_SWIZZLE_128B, 96);
  Prm p;
  p.x = (const char*)d_in[0]; p.la = (const char*)d_in[1]; p.ai = (const char*)d_in[2]; p.cr = (const char*)d_in[3];
  p.ci = (const char*)d_in[4]; p.ldt = (const char*)d_in[5]; p.dsk = (const char*)d_in[6]; p.wr = (const char*)d_in[8];
  p.wg = (const char*)d_in[9]; p.wu = (const char*)d_in[10]; p.wd = (const char*)d_in[11];
  p.c = (const char*)d_in[12]; p.out = (char*)d_out; p.zero = 0; p.gs = (char*)scratch;
  fused_kernel<<<128, 384, SM_TOTAL>>>(p, tm_mod, tm_gate, tm_gs, tm_up, tm_us, tm_down);
}
```

```cpp
#include <cuda_runtime.h>
#include <cuda.h>
#include <cuda_bf16.h>
#include <cuda_fp16.h>
#include <stdint.h>
#define FUSED 1
#define DEV __device__ __forceinline__
typedef uint32_t u32;

constexpr u32 BLK = 18432, G_Z = 0, G_Y = 128 * BLK, G_MOD = 2 * G_Y, G_KEY = G_MOD + 128 * 128, G_ACT = G_KEY + 128 * 128;
constexpr u32 G_PART = G_ACT + 576 * 128, G_EP = G_PART + 128 * 2048, G_END = G_EP + 128;
__device__ __align__(128) unsigned char g_s[G_END];
#define TS(i)
#define TSJ(j)
#define TS0()
#define TSE()
#define TSD()
#define TSX 0
#define TSRND()
#define TSN(code, n)
#define ERRF(code)

constexpr int SM0 = 1024;
constexpr int ROW = 1168, SLV = 36864;
constexpr int SM_GATE = SM0, SM_UP = SM_GATE + 46080, SM_XST = SM_UP + 46080, SM_MODS = SM_XST + 16 * ROW, SM_W = SM_MODS + 11008;
constexpr int KTAB = 9216, WSL = 12544, W5O = 128, W3O = 3328, V2O = 6400, W9O = 8448, W7O = 10496;
constexpr int ZPS = 2192, ZSS = 2 * ZPS, ZP4 = 2368;
constexpr int SM_ZS = SM_W + 5 * WSL, SM_Z4 = SM_ZS + 4 * ZSS, SM_TAP = SM_Z4 + 2 * ZP4, TAPS = 3328;
constexpr int SM_MB = SM_TAP + 5 * TAPS;
constexpr int SM_SC = SM_MB + 48;
constexpr int SM_KV = SM_SC + 80;
constexpr int SM_THR = SM_KV + 32;
constexpr int SM_SLOT = SM_THR + 48;
constexpr int SM_KEY = SM_SLOT + 32;
constexpr int SM_ST = SM_KEY + 64;
constexpr int SM_ST2 = SM_ST + 256;
constexpr int SM_RC = SM_ST2 + 256;
constexpr int SM_SP = SM_RC + 192;
constexpr int SM_AF = SM_SP + 1152, SM_SIL = SM_AF + 1152, SM_INV = SM_SIL + 1152, SM_END = SM_SP + 5760;
constexpr int SM_ONE = SM_MODS + 9 * 1152;
constexpr int SM_WD = SM_W, SM_XS = SM_W + 36864, SM_AC = SM_ZS, SM_RED = SM_AC + 6144;
constexpr int SM_TSB = SM_END, SM_TOTAL = SM_END + TSX - SM0;
static_assert(SM_W % 1024 == 0 && SM_TAP % 1024 == 0 && SM_MODS + 8 * KTAB <= SM_ZS && SM_ZS + 2 * KTAB <= SM_TAP && SM_RED + 10240 <= SM_TAP && SM_XS + 8 * ROW <= SM_ZS, "smem map");
static_assert(SM_MB % 16 == 0 && SM_THR % 16 == 0 && SM_ST % 16 == 0 && SM_SP % 16 == 0 && SM_TOTAL <= 232448, "smem map");
constexpr int TE = 4, TO = 276, T5 = 560, T3 = 624, T9E = 680, T7E = 760, TEO = 40;
#define MT 10
#define MKT 1
#define KST 32
#define DE1 1
#define DE2 4
#define DE3 5
#define OUTB 7
#define PFW 1
#define PFU 0
#define KD 700
#define D0C 0
#define YE 104
#define YL 104
#define YD 250
#define OPTM 1
#define Y8 104
#define FH 0
#define FO 0
#define DB1 1
#define KD1 50
#define AD 0
#define PD 900
#define ZD 0
#define DD 1000
#define INCV 1
#define TPIN 0
#define A5P 1
#define TG 0
#define TU 0
#define TW 0
#define KDB 520
#define PRM 0
#define PRG 0
#define PRU 0
#define PRS 0
#define KE 64
#define PFP 200
#define GE 0
#define NB8 8
#define DX 0
#define DMOD 1000
#define RW 3
#define AW 7
#define HLP 1
#define SMD 1
#define CVG 1
#define YS 2
#define F8 0
#define HD 0
#define KF 96
#define KDC 520
#define AFP 1
#define AFM 0
#define PFG 1
constexpr int N1 = 320 + 32 * DB1, N12 = 288 + 32 * !DB1;
constexpr int SPIN = 1 << 16, NEARLY = 4;
constexpr u32 TAGM = 0x40004000u, TAGR = 0x40000000u, INVAL = 0x00004801u;

DEV u32 s2u(const void* p) { return (u32)__cvta_generic_to_shared(p); }
DEV void mma_bf(float (&c)[4], u32 a0, u32 a1, u32 a2, u32 a3, u32 b0, u32 b1) {
  asm("mma.sync.aligned.m16n8k16.row.col.f32.bf16.bf16.f32 {%0,%1,%2,%3},{%4,%5,%6,%7},{%8,%9},{%0,%1,%2,%3};"
      : "+f"(c[0]), "+f"(c[1]), "+f"(c[2]), "+f"(c[3]) : "r"(a0), "r"(a1), "r"(a2), "r"(a3), "r"(b0), "r"(b1));
}
DEV void mma_hf(float (&c)[4], u32 a0, u32 a1, u32 a2, u32 a3, u32 b0, u32 b1) {
  asm("mma.sync.aligned.m16n8k16.row.col.f32.f16.f16.f32 {%0,%1,%2,%3},{%4,%5,%6,%7},{%8,%9},{%0,%1,%2,%3};"
      : "+f"(c[0]), "+f"(c[1]), "+f"(c[2]), "+f"(c[3]) : "r"(a0), "r"(a1), "r"(a2), "r"(a3), "r"(b0), "r"(b1));
}
DEV void mma8_bf(float (&c)[4], u32 a0, u32 a1, u32 b0) {
  asm("mma.sync.aligned.m16n8k8.row.col.f32.bf16.bf16.f32 {%0,%1,%2,%3},{%4,%5},{%6},{%0,%1,%2,%3};"
      : "+f"(c[0]), "+f"(c[1]), "+f"(c[2]), "+f"(c[3]) : "r"(a0), "r"(a1), "r"(b0));
}
DEV void mma8_hf(float (&c)[4], u32 a0, u32 a1, u32 b0) {
  asm("mma.sync.aligned.m16n8k8.row.col.f32.f16.f16.f32 {%0,%1,%2,%3},{%4,%5},{%6},{%0,%1,%2,%3};"
      : "+f"(c[0]), "+f"(c[1]), "+f"(c[2]), "+f"(c[3]) : "r"(a0), "r"(a1), "r"(b0));
}
DEV u32 movm(u32 x) { u32 r; asm("movmatrix.sync.aligned.m8n8.trans.b16 %0,%1;" : "=r"(r) : "r"(x)); return r; }
DEV void conv() { if (CVG) asm volatile("{.reg .u32 t; mov.u32 t,0; movmatrix.sync.aligned.m8n8.trans.b16 t,t;}"); }
DEV uint4 ldsm4(u32 a) { uint4 r; asm volatile("ldmatrix.sync.aligned.m8n8.x4.shared.b16 {%0,%1,%2,%3},[%4];" : "=r"(r.x), "=r"(r.y), "=r"(r.z), "=r"(r.w) : "r"(a)); return r; }
DEV uint4 ldsm4t(u32 a) { uint4 r; asm volatile("ldmatrix.sync.aligned.m8n8.x4.trans.shared.b16 {%0,%1,%2,%3},[%4];" : "=r"(r.x), "=r"(r.y), "=r"(r.z), "=r"(r.w) : "r"(a)); return r; }
DEV u32 lds32(u32 a) { u32 r; asm volatile("ld.volatile.shared.u32 %0,[%1];" : "=r"(r) : "r"(a)); return r; }
DEV uint2 lds64(u32 a) { uint2 r; asm volatile("ld.shared.v2.u32 {%0,%1},[%2];" : "=r"(r.x), "=r"(r.y) : "r"(a)); return r; }
DEV uint4 lds128(u32 a) { uint4 r; asm volatile("ld.shared.v4.u32 {%0,%1,%2,%3},[%4];" : "=r"(r.x), "=r"(r.y), "=r"(r.z), "=r"(r.w) : "r"(a)); return r; }
DEV void sts16(u32 a, u32 v) { asm volatile("st.shared.u16 [%0],%1;" ::"r"(a), "h"((unsigned short)v) : "memory"); }
DEV void sts32(u32 a, u32 v) { asm volatile("st.shared.u32 [%0],%1;" ::"r"(a), "r"(v) : "memory"); }
DEV void sts64(u32 a, u32 x, u32 y) { asm volatile("st.shared.v2.u32 [%0],{%1,%2};" ::"r"(a), "r"(x), "r"(y) : "memory"); }
DEV void sts128(u32 a, u32 x, u32 y, u32 z, u32 w) { asm volatile("st.shared.v4.u32 [%0],{%1,%2,%3,%4};" ::"r"(a), "r"(x), "r"(y), "r"(z), "r"(w) : "memory"); }
DEV uint4 ldr128(const void* p) { uint4 v; asm volatile("ld.relaxed.gpu.global.v4.u32 {%0,%1,%2,%3},[%4];" : "=r"(v.x), "=r"(v.y), "=r"(v.z), "=r"(v.w) : "l"(p) : "memory"); return v; }
DEV uint2 ldr64(const void* p) { uint2 v; asm volatile("ld.relaxed.gpu.global.v2.u32 {%0,%1},[%2];" : "=r"(v.x), "=r"(v.y) : "l"(p) : "memory"); return v; }
DEV u32 ldr32(const void* p) { u32 v; asm volatile("ld.relaxed.gpu.global.u32 %0,[%1];" : "=r"(v) : "l"(p) : "memory"); return v; }
template <u32 M> DEV void rld128(uint4& v, const void* p, u32 tag) {
  asm volatile("{.reg .pred p; .reg .u32 t; lop3.b32 t,%0,%5,%6,0x28; setp.ne.u32 p,t,0; @p ld.relaxed.gpu.global.v4.u32 {%0,%1,%2,%3},[%4];}"
               : "+r"(v.x), "+r"(v.y), "+r"(v.z), "+r"(v.w) : "l"(p), "r"(tag), "n"(M) : "memory");
}
template <u32 M> DEV void rld64(uint64_t& v, const void* p, u32 tag) {
  asm volatile("{.reg .pred p; .reg .u32 t, h; mov.b64 {t,h},%0; lop3.b32 t,t,%2,%3,0x28; setp.ne.u32 p,t,0; @p ld.relaxed.gpu.global.u64 %0,[%1];}" : "+l"(v) : "l"(p), "r"(tag), "n"(M) : "memory");
}
template <int L> DEV u32 lop3(u32 a, u32 b, u32 c) { u32 r; asm("lop3.b32 %0,%1,%2,%3,%4;" : "=r"(r) : "r"(a), "r"(b), "r"(c), "n"(L)); return r; }
DEV u32 ne3(u32 a, u32 b, u32 c) { u32 r; asm("lop3.b32 %0,%1,%2,%3,0x7e;" : "=r"(r) : "r"(a), "r"(b), "r"(c)); return r; }
DEV void pin(u32 zr, u32 a, u32 b = 0, u32 c = 0, u32 d = 0) { asm volatile("{.reg .pred p; setp.ne.u32 p,%0,0; @p st.shared.v4.u32 [%0],{%1,%2,%3,%4};}" ::"r"(zr), "r"(a), "r"(b), "r"(c), "r"(d) : "memory"); }
DEV void pin2(u32 zr, const void* a, const void* b) { asm volatile("{.reg .pred p; setp.ne.u32 p,%0,0; @p st.shared.v2.u64 [%0],{%1,%2};}" ::"r"(zr), "l"(a), "l"(b) : "memory"); }
DEV const char* rowa(const char* base, u32 key) { const char* r; asm("mad.wide.u32 %0,%1,288,%2;" : "=l"(r) : "r"(~key & 0x1ffc), "l"(base)); return r; }
DEV void str128(void* p, u32 x, u32 y, u32 z, u32 w) { asm volatile("st.relaxed.gpu.global.v4.u32 [%0],{%1,%2,%3,%4};" ::"l"(p), "r"(x), "r"(y), "r"(z), "r"(w) : "memory"); }
DEV void str64(void* p, u32 x, u32 y) { asm volatile("{.reg .u64 d; mov.b64 d,{%1,%2}; st.relaxed.gpu.global.u64 [%0],d;}" ::"l"(p), "r"(x), "r"(y) : "memory"); }
DEV void str32(void* p, u32 x) { asm volatile("st.relaxed.gpu.global.u32 [%0],%1;" ::"l"(p), "r"(x) : "memory"); }
DEV void str16(void* p, u32 x) { asm volatile("st.relaxed.gpu.global.u16 [%0],%1;" ::"l"(p), "h"((unsigned short)x) : "memory"); }
DEV uint4 ldg128(const void* p) { uint4 v; asm volatile("ld.global.nc.v4.u32 {%0,%1,%2,%3},[%4];" : "=r"(v.x), "=r"(v.y), "=r"(v.z), "=r"(v.w) : "l"(p)); return v; }
DEV uint2 ldg64(const void* p) { uint2 v; asm volatile("ld.global.nc.v2.u32 {%0,%1},[%2];" : "=r"(v.x), "=r"(v.y) : "l"(p)); return v; }
DEV u32 ldg32(const void* p) { u32 v; asm volatile("ld.global.nc.u32 %0,[%1];" : "=r"(v) : "l"(p)); return v; }
DEV u32 ldg16(const void* p) { unsigned short v; asm volatile("ld.global.nc.u16 %0,[%1];" : "=h"(v) : "l"(p)); return v; }
#define bsync(id, n) asm volatile("bar.sync %0,%1;" ::"n"(id), "n"(n) : "memory")
#define barrive(id, n) asm volatile("bar.arrive %0,%1;" ::"n"(id), "n"(n) : "memory")
DEV void bsyncr(u32 id) { asm volatile("bar.sync %0,96;" ::"r"(id) : "memory"); }
DEV void barriver(u32 id) { asm volatile("bar.arrive %0,96;" ::"r"(id) : "memory"); }
constexpr u32 BW = 0x0FEA, BS = 0x6532;
DEV void mb_init(u32 a, u32 n) { asm volatile("mbarrier.init.shared.b64 [%0],%1;" ::"r"(a), "r"(n) : "memory"); }
DEV void mb_arrive(u32 a) { asm volatile("mbarrier.arrive.shared.b64 _,[%0];" ::"r"(a) : "memory"); }
DEV void mb_expect(u32 a, u32 bytes) { asm volatile("mbarrier.arrive.expect_tx.shared.b64 _,[%0],%1;" ::"r"(a), "r"(bytes) : "memory"); }
DEV void mb_wait(u32 a, u32 ph = 0) {
  u32 ok; int it = 0;
  do { asm volatile("{.reg .pred p; mbarrier.try_wait.parity.shared.b64 p,[%1],%2; selp.u32 %0,1,0,p;}" : "=r"(ok) : "r"(a), "r"(ph) : "memory"); } while (!ok && ++it < SPIN);
}
template <int N> DEV void bulk_out(void* dst, u32 src) { asm volatile("cp.async.bulk.global.shared::cta.bulk_group [%0],[%1],%2;" ::"l"(dst), "r"(src), "n"(N) : "memory"); }
constexpr u32 WSH = 41472;
DEV void l2_line(const void* p) { asm volatile("prefetch.global.L2 [%0];" ::"l"(p) : "memory"); }
template <int N> DEV void l2_pre(const void* p) { asm volatile("cp.async.bulk.prefetch.L2.global [%0],%1;" ::"l"(p), "n"(N) : "memory"); }
DEV void tma3d(u32 dst, const CUtensorMap* tm, u32 mb, int c0, int c2) {
  asm volatile("cp.async.bulk.tensor.3d.shared::cluster.global.mbarrier::complete_tx::bytes [%0],[%1,{%3,0,%4}],[%2];"
               ::"r"(dst), "l"((uint64_t)tm), "r"(mb), "r"(c0), "r"(c2) : "memory");
}
DEV float blo(u32 w) { return __uint_as_float(w << 16); }
DEV float bhi(u32 w) { return __uint_as_float(w & 0xffff0000u); }
DEV u32 pk_bf(float lo, float hi) { u32 r; asm("cvt.rn.bf16x2.f32 %0,%1,%2;" : "=r"(r) : "f"(hi), "f"(lo)); return r; }
DEV u32 pk_hf(float lo, float hi) { u32 r; asm("cvt.rn.f16x2.f32 %0,%1,%2;" : "=r"(r) : "f"(hi), "f"(lo)); return r; }
DEV float rbf(float x) { return __uint_as_float(pk_bf(0.f, x) & 0xffff0000u); }
DEV u32 bfma(u32 a, u32 b, u32 c) { u32 r; asm("fma.rn.bf16x2 %0,%1,%2,%3;" : "=r"(r) : "r"(a), "r"(b), "r"(c)); return r; }
DEV u32 bmul(u32 a, u32 b) { u32 r; asm("mul.rn.bf16x2 %0,%1,%2;" : "=r"(r) : "r"(a), "r"(b)); return r; }
DEV u32 badd(u32 a, u32 b) { u32 r; asm("add.rn.bf16x2 %0,%1,%2;" : "=r"(r) : "r"(a), "r"(b)); return r; }
DEV u32 hadd(u32 a, u32 b) { u32 r; asm("add.rn.f16x2 %0,%1,%2;" : "=r"(r) : "r"(a), "r"(b)); return r; }
DEV u32 hfma(u32 a, u32 b, u32 c) { u32 r; asm("fma.rn.f16x2 %0,%1,%2,%3;" : "=r"(r) : "r"(a), "r"(b), "r"(c)); return r; }
struct C2 { u32 re, im; };
DEV C2 cm2(C2 a, C2 b) {
  const __half2 ar = *reinterpret_cast<__half2*>(&a.re), ai = *reinterpret_cast<__half2*>(&a.im), br = *reinterpret_cast<__half2*>(&b.re), bi = *reinterpret_cast<__half2*>(&b.im);
  __half2 re = __hfma2(ar, br, __hneg2(__hmul2(ai, bi))), im = __hfma2(ar, bi, __hmul2(ai, br));
  return {*reinterpret_cast<u32*>(&re), *reinterpret_cast<u32*>(&im)};
}
DEV C2 pk2(const float2 (&a)[2]) { return {pk_hf(a[0].x, a[1].x), pk_hf(a[0].y, a[1].y)}; }
DEV C2 pk2c(const float2 (&a)[2]) { return {pk_hf(a[0].x, a[1].x), pk_hf(-a[0].y, -a[1].y)}; }
DEV u32 cpy(u32 x, u32 zr, int alt) {
  u32 r;
  if (alt) asm volatile("xor.b32 %0,%1,%2;" : "=r"(r) : "r"(x), "r"(zr)); else asm volatile("mad.lo.u32 %0,%2,%2,%1;" : "=r"(r) : "r"(x), "r"(zr));
  return r;
}
template <int N> DEV void inc(u32& x) { asm volatile("add.u32 %0,%0,%1;" : "+r"(x) : "n"(N)); }
DEV u32 opq(u32 x) { u32 r; asm volatile("mov.u32 %0,%1;" : "=r"(r) : "r"(x)); return r; }
DEV u32 chan(u32 b, u32 i) { return 16 * (b >> 2) + 2 * (b & 3) + (i & 1) + 4 * (i & 2); }
DEV u32 row16(u32 lane) { const u32 r0 = (lane & 7) + ((lane >> 3) & 1) + 8 * (lane >> 4) - 1; return (r0 ^ ((r0 >> 3) & 3)) * 16; }
DEV u32 clk() { u32 r; asm volatile("mov.u32 %0,%%clock;" : "=r"(r)::"memory"); return r; }
DEV void wait_clk(u32 t, int d) { while ((int)(clk() - t) < d); }
DEV float ex2(float x) { float r; asm("ex2.approx.ftz.f32 %0,%1;" : "=f"(r) : "f"(x)); return r; }
DEV float rcpf(float x) { float r; asm("rcp.approx.ftz.f32 %0,%1;" : "=f"(r) : "f"(x)); return r; }
DEV float2 cmul(float2 a, float2 b) { return make_float2(fmaf(a.x, b.x, -a.y * b.y), fmaf(a.x, b.y, a.y * b.x)); }
DEV float2 csq(float2 a) { return make_float2(fmaf(a.x, a.x, -a.y * a.y), (a.x + a.x) * a.y); }
DEV float2 cexp(float lr2, float th) {
  const float m = ex2(lr2);
  return make_float2(m * __cosf(th), m * __sinf(th));
}
DEV float silu_f(float v) { return v * rcpf(1.f + ex2(-1.4426950408889634f * v)); }
constexpr u32 B2P64 = 0x5F805F80u, B2M64 = 0x1F801F80u, BONE = 0x3F803F80u;
constexpr u32 MODJ = 18 * 128;
DEV float sqrta(float x) { float r; asm("sqrt.approx.ftz.f32 %0,%1;" : "=f"(r) : "f"(x)); return r; }
DEV u32 fu(float x) { return __float_as_uint(x); }
DEV float uf(u32 x) { return __uint_as_float(x); }
DEV void mma_hf_o(float (&d)[4], const float (&c)[4], const u32 (&a)[4], u32 b0, u32 b1) {
  asm("mma.sync.aligned.m16n8k16.row.col.f32.f16.f16.f32 {%0,%1,%2,%3},{%4,%5,%6,%7},{%8,%9},{%10,%11,%12,%13};"
      : "=f"(d[0]), "=f"(d[1]), "=f"(d[2]), "=f"(d[3]) : "r"(a[0]), "r"(a[1]), "r"(a[2]), "r"(a[3]), "r"(b0), "r"(b1), "f"(c[0]), "f"(c[1]), "f"(c[2]), "f"(c[3]));
}

DEV void mma_hf_t(float (&c)[4], const u32 (&a)[4], u32 b0, u32 b1) { mma_hf(c, a[0], a[1], a[2], a[3], b0, b1); }
DEV void cpa16(u32 dst, const void* src) { asm volatile("cp.async.cg.shared.global [%0],[%1],16;" ::"r"(dst), "l"(src) : "memory"); }
DEV void tm_pre(const CUtensorMap* tm) { asm volatile("prefetch.tensormap [%0];" ::"l"((uint64_t)tm) : "memory"); }
#define PROXY_FENCE() asm volatile("fence.proxy.async.shared::cta;" ::: "memory")
struct Prm {
  const char *la, *ai, *cr, *ci, *ldt;
  u32 zero;
  const char *x, *c;
  char* gs;
  const char *dsk, *wr, *wg, *wu, *wd;
  char* out;
};
constexpr float LOG2E = 1.4426950408889634f, F2P64 = 1.8446744073709552e19f, F2M64 = 5.421010862427522e-20f;

template <int S> DEV void y_store(float c0, float c1, float c2, float c3, u32 F, u32 pml, char* yp) {
  str32(yp, bmul(pk_bf(c0, c2), F) | pml);
  str32(yp + S, bmul(pk_bf(c1, c3), F) | pml);
}
DEV void merge4(u32 (&h)[8], uint4 a, uint4 b) {
  const u32 e1 = min(a.x, b.x), e2 = max(a.z, b.z), o1 = min(a.y, b.y), o2 = max(a.w, b.w), o0 = max(a.y, b.y), e3 = min(a.z, b.z);
  const u32 f1 = max(e1, e2), f2 = min(e1, e2), p1 = max(o1, o2), p2 = min(o1, o2);
  h[0] = max(a.x, b.x); h[1] = max(o0, f1); h[2] = min(o0, f1); h[3] = max(p1, f2); h[4] = min(p1, f2); h[5] = max(p2, e3); h[6] = min(p2, e3); h[7] = min(a.w, b.w);
}
DEV void top8(u32 (&a)[8], uint4 l, uint4 m) {
  u32 b[8];
  merge4(b, l, m);
#pragma unroll
  for (int i = 0; i < 8; i++) a[i] = max(a[i], b[7 - i]);
#pragma unroll
  for (int s = 4; s; s >>= 1)
#pragma unroll
    for (int i = 0; i < 8; i++) if (!(i & s)) { const u32 x = a[i], y = a[i + s]; a[i] = max(x, y); a[i + s] = min(x, y); }
}
#define POLL(load, cond_bad, code) { int it_ = 0; do { load; } while (__any_sync(~0u, (cond_bad)) & (++it_ <= SPIN)); if (it_ > SPIN) { ERRF(code); } TSN(code, it_); }
DEV u32 tmask(u32 it, u32 m) { u32 r; asm volatile("{.reg .pred p; setp.ne.u32 p,%1,0; selp.u32 %0,%2,0,p;}" : "=r"(r) : "r"(it), "r"(m)); return r; }
#define POLLM(load, bad, M, code) { u32 it_ = SPIN + (tid >> 16), m_; do { m_ = tmask(--it_, M); load; } while (__any_sync(~0u, (bad) & m_)); if (!it_) { ERRF(code); } TSN(code, SPIN - it_); }
#define POLLS(use, load, bad, M, code) { u32 it_ = SPIN + (tid >> 16); for (;;) { const u32 m_ = tmask(--it_, M); use; if (!__any_sync(~0u, (bad) & m_)) break; load; } if (!it_) { ERRF(code); } TSN(code, SPIN - it_); }
#define POLLW(load, cond_bad, code) { int it_ = 0; while (__any_sync(~0u, (cond_bad))) { if (++it_ > SPIN) { ERRF(code); break; } load; } TSN(code, it_); }

#define DOWN(E) if (tid == (b < 108 ? 288 : ~0u)) { const u32 c0 = 64 * (b % 9), c2 = 4 * (b / 9); \
    if (!D0C && E == 1) { mb_expect(SM_MB + 24, 49152); tma3d(SM_TAP, tm_down, SM_MB + 24, c0, c2); } \
    if (DE1 == E) tma3d(SM_WD, tm_down, SM_MB + 24, c0, c2 + 1); \
    if (DE2 == E) tma3d(SM_WD + 12288, tm_down, SM_MB + 24, c0, c2 + 2); \
    if (DE3 == E) tma3d(SM_WD + 24576, tm_down, SM_MB + 24, c0, c2 + 3); }
#define OUTR() { const u32 tl = 4 * ((lane >> 1) & 1) + ((lane >> 2) & 3) + 8 * (lane & 1); \
    bulk_out<1152>(p.out + (16 * b + tl) * 1152, SM_XST + ((lane & 2) + 4 * (lane & 1) + ((lane >> 2) & 1) + (lane & 8)) * ROW); \
    asm volatile("cp.async.bulk.commit_group;" ::: "memory"); }
struct FA { u32 tid, ba, ra, sa; char *ad, *as; };
DEV FA ffn_addr(const Prm& p, u32 tid, u32 b) {
  const u32 w = tid >> 5, lane = tid & 31, kq = w & 3, tg = w >> 2, t = 7 - w;
  FA f = {tid, SM_XS + (lane & 7) * ROW + (18 * kq + (lane >> 3)) * 16, SM_RED + (8 * tg + kq) * 512 + lane * 16, SM_RED + t * 2048 + lane * 16,
          p.gs + (G_ACT + (t < 4 ? 512 * b + 128 * t : (512 + (b >> 1)) * 128) + lane * 4), p.gs + (G_ACT + (b / 9) * 6144 + tid * 16)};
  if (AW & 2) { pin(tid >> 16, f.ba, f.ra, f.sa, tid); pin2(tid >> 16, f.ad, f.as); }
  return f;
}
DEV void ffn_tail(const Prm& p, const CUtensorMap* tm_down, uint4 (&A)[24], const FA f, const u32 b, const u32 par, const u32 okl) {
  const u32 tid = f.tid, w = tid >> 5, lane = tid & 31, g = lane >> 2, q = lane & 3, tg = w >> 2, zr = tid >> 16;
  const u32 rho = b & 1, pm = par ? TAGM : 0, kt = par * 3, ba = f.ba, ra = f.ra;
  char* const gs = p.gs;
  char *const ad = f.ad, *const as = f.as;
  __syncthreads();
  TS(25);
  if (!(AW & 4)) DOWN(5);
  {
    float c0[2][4] = {}, c1[2][4] = {};
    uint4 bb[5];
#pragma unroll
    for (int s = 0; s < 5; s++) bb[s] = ldsm4(ba + s * 64);
    if (AW & 4) DOWN(5);
#pragma unroll
    for (int s = 0; s < 9; s++) mma_bf(c0[s & 1], A[s].x, A[s].y, A[s].z, A[s].w, s & 1 ? bb[s >> 1].z : bb[s >> 1].x, s & 1 ? bb[s >> 1].w : bb[s >> 1].y);
    if (tg < 2) {
#pragma unroll
      for (int s = 0; s < 9; s++) mma_bf(c1[s & 1], A[9 + s].x, A[9 + s].y, A[9 + s].z, A[9 + s].w, s & 1 ? bb[s >> 1].z : bb[s >> 1].x, s & 1 ? bb[s >> 1].w : bb[s >> 1].y);
      sts128(ra + 2048, fu(c1[0][0] + c1[1][0]), fu(c1[0][1] + c1[1][1]), fu(c1[0][2] + c1[1][2]), fu(c1[0][3] + c1[1][3]));
    }
    sts128(ra, fu(c0[0][0] + c0[1][0]), fu(c0[0][1] + c0[1][1]), fu(c0[0][2] + c0[1][2]), fu(c0[0][3] + c0[1][3]));
  }
  TS(39);
  __syncthreads();
  const u32 tr = clk();
  if (OUTB == 6 && w == 10 && okl < lds32(SM_SLOT + 28)) OUTR();
  if (w - 3 - rho < 5 - rho) {
    float s[4];
    const uint4 u0 = lds128(f.sa), u1 = lds128(f.sa + 512), u2 = lds128(f.sa + 1024), u3 = lds128(f.sa + 1536);
    s[0] = (uf(u0.x) + uf(u1.x)) + (uf(u2.x) + uf(u3.x)); s[1] = (uf(u0.y) + uf(u1.y)) + (uf(u2.y) + uf(u3.y));
    s[2] = (uf(u0.z) + uf(u1.z)) + (uf(u2.z) + uf(u3.z)); s[3] = (uf(u0.w) + uf(u1.w)) + (uf(u2.w) + uf(u3.w));
    const u32 sg = pk_bf(silu_f(rbf(s[0])), silu_f(rbf(s[1])));
    const u32 act = movm(bmul(bmul(sg, pk_bf(s[2], s[3])), B2M64));
    str32(ad, act | (q ? 0 : pm));
  }
  TS(26);
  const bool fin = w == (b < 72 ? 8 : ~0u);
  u32 kg;
  uint4 xt;
  const char* xs;
  if (fin) { kg = lds32(SM_SLOT + 4 * g); xs = rowa(gs + (G_Y + 16 * b), kg); xt = ldr128(xs); }
  if (b < 108) {
    uint4 a;
    if (AD) a.x = INVAL; else a = ldr128(as);
    if (AD && w >= 4) wait_clk(tr, AD);
    char* const dst = gs + ((G_PART + b * 2048) + (w * 512 + lane * 8));
    if (w < 4) {
      const u32 aa = SM_WD + (8 * (lane >> 4) + (lane & 7)) * 128 + (((2 * w + ((lane >> 3) & 1)) ^ (lane & 7)) << 4);
      mb_wait(SM_MB + 24);
#pragma unroll
      for (int s = 0; s < 24; s++) A[s] = ldsm4t(aa + (s < 6 ? SM_TAP - SM_WD : -12288) + s * 2048);
      if (AW & 2) pin2(zr, dst, as);
    }
    conv();
    TS(28);
    POLLW(rld128<TAGM>(a, as, pm), (a.x ^ pm) & TAGM, 9);
    sts128(SM_AC + tid * 16, a.x, a.y, a.z, a.w); sts32(SM_AC + tid * 16, a.x & ~TAGM);
    TS(27);
    if (w < 4) {
      bsync(8, 384);
      float c[4][4] = {};
#pragma unroll
      for (int s = 0; s < 12; s++) {
        const uint4 bb = ldsm4(SM_AC + lane * 16 + s * 512);
        mma_bf(c[2 * (s & 1)], A[2 * s].x, A[2 * s].y, A[2 * s].z, A[2 * s].w, bb.x, bb.y);
        mma_bf(c[2 * (s & 1) + 1], A[2 * s + 1].x, A[2 * s + 1].y, A[2 * s + 1].z, A[2 * s + 1].w, bb.z, bb.w);
      }
      u32 o[4];
#pragma unroll
      for (int i = 0; i < 4; i++) o[i] = fu(((c[0][i] + c[1][i]) + (c[2][i] + c[3][i])) * F2P64);
      str64(dst, (o[0] & ~3u) | kt, o[1]); str64(dst + 256, (o[2] & ~3u) | kt, o[3]);
      TS(29);
    } else barrive(8, 384);
  }
  if (OUTB == 7 && w == 10 && okl < lds32(SM_SLOT + 28)) OUTR();
  if (fin) {
    const u32 ta = clk();
    const char* src = gs + (G_PART + (b >> 3) * 2048 + (b & 7) * 256 + lane * 8);
    const u32 gw = lds32(SM_MODS + 5760 + 16 * b + 4 * q);
    const u32 hw = lds32(SM_XS + g * ROW + b * 16 + q * 4);
    const float sgm = rcpf(1.f + ex2(-LOG2E * bhi(kg ^ (~((int)kg >> 31) | 0x80000000))));
    char* const dst = (char*)rowa(p.out + (16 * b + 4 * q), kg);
    conv();
    POLLW(rld128<TAGM>(xt, xs, TAGR), (xt.x ^ TAGR) & TAGM, 10);
    const u32 x1w = (q & 2) ? ((q & 1) ? xt.w : xt.z) : ((q & 1) ? xt.y : bmul(xt.x ^ TAGR, B2P64));
    const u32 sg2 = pk_bf(sgm, sgm);
    pin(zr, x1w, gw, hw, sg2); pin2(zr, dst, src);
    uint64_t v[12];
#pragma unroll
    for (int j = 0; j < 12; j++) v[j] = 1;
    float s0, s1;
    if (PD) wait_clk(ta, PD);
    conv();
    TS(13);
#define VL(j) (u32)v[j]
#define VS(j, s) ((uf((u32)(v[j] >> s)) + uf((u32)(v[j + 1] >> s))) + (uf((u32)(v[j + 2] >> s)) + uf((u32)(v[j + 3] >> s))))
    POLL({ _Pragma("unroll") for (int j = 0; j < 12; j++) rld64<3>(v[j], src + j * 9 * 2048, kt);
           s0 = VS(0, 0) + VS(4, 0) + VS(8, 0); s1 = VS(0, 32) + VS(4, 32) + VS(8, 32);
           asm volatile("" : "+f"(s0), "+f"(s1)); TSRND(); },
         lop3<0xa8>(lop3<0xfe>(ne3(VL(0), VL(1), kt), ne3(VL(2), VL(3), kt), ne3(VL(4), VL(5), kt)),
                    lop3<0xfe>(ne3(VL(6), VL(7), kt), ne3(VL(8), VL(9), kt), ne3(VL(10), VL(11), kt)), 3), 11);
    const u32 y = movm(pk_bf(s0, s1));
    asm volatile("st.global.u32 [%0],%1;" ::"l"(dst), "r"(badd(x1w, bmul(gw, badd(hw, bmul(y, sg2))))) : "memory");
    if (b == 0 && lane == 0) str32(gs + G_EP, par);
    TS(30); TSE();
  }
  if (w == 10) asm volatile("cp.async.bulk.wait_group.read 0;" ::: "memory");
}

DEV u32 y_off(u32 tid, u32 b) { return G_Y + (16 * (tid >> 5) + 8 * ((tid >> 1) & 1) + ((tid >> 2) & 4)) * BLK + b * 128 + ((tid >> 2) & 3) * 32 + (tid & 1) * 16; }
DEV void post_conv(const Prm& p, const CUtensorMap* tm_down, const u32 tid, const u32 b, const u32 b3) {
  const u32 w = tid >> 5, lane = tid & 31;
  const u32 g = lane >> 2, q = lane & 3, e = g >> 2, h = (g >> 1) & 1, hi = g & 1;
  const u32 pm = lds32(SM_THR + 4), par = pm >> 30;
  char* const gs = p.gs;
  const u32 cho = 128 * w + 64 * e + 16 * q;
  u32 x1[4][4], h2[4][4], key[4], lt;
  char* const rowp = gs + (b * BLK + (4 * h + 8 * hi) * 1152 + cho);
  u32 okl = ~0u;
  FA fa;
  uint4 A[24];
#define AROW(t) const u32 arow = 144 * ((t >> 5) & 3) + ((t >> 1) & 8) + (t & 7), ab = (t & 8) ? SM_UP : SM_GATE;
#define AFRAG9() { _Pragma("unroll") for (int s = 0; s < 9; s++) A[s] = ldsm4t(ab + SLV + arow * 16 + s * 256); }
#define AFRAG18() { const u32 t3 = opq(tid); AROW(t3); if (t3 < 256) { const u32 aa = ab + arow * 64 + ((((t3 >> 6) & 2) ^ ((t3 & 7) >> 1)) << 4); \
      _Pragma("unroll") for (int s = 0; s < 9; s++) { A[s] = ldsm4t(aa + s * 1024); A[9 + s] = ldsm4t((aa ^ 16) + s * 1024); } } else AFRAG9(); }
  if (w < 9) {
    const u32 yc = 8 * (q >> 1) + 2 * (g >> 1), y1 = w < 8 ? BLK : YS ? 512 : 4 * BLK, y2 = 2 * y1;
    const char* ysrc = gs + (w < 8 ? y_off(tid, b) : YS ? G_Y + 16384 + b * BLK + (q >> 1) * 256 + g * 32 + (q & 1) * 16 : G_Y + (q & 1) * 16 + (8 * yc + 2 * hi + ((b >> 4) & 1)) * BLK + 16384 + ((b >> 5) * 16 + (b & 15)) * 32);
    const char* const ys[4] = {ysrc, ysrc + y1, ysrc + y2, ysrc + (y1 + y2)};
    uint4 yv[4];
#pragma unroll
    for (int v = 0; v < 4; v++) yv[v].x = INVAL;
    const u32 tg0 = b < (w < 4 ? YL : w < 8 ? YE : Y8) ? pm : INVAL;
    if (w >= 4) { pin2(tid >> 16, ys[0], ys[1]); pin2(tid >> 16, ys[2], ys[3]); bsync(12, N12); TS(18); }
#pragma unroll
    for (int v = 0; v < 4; v++) rld128<TAGM>(yv[v], ys[v], tg0);
    const u32 tc = clk();
    const u32 ma = SM_MODS + cho, xa = SM_XST + (2 * h + 4 * hi) * ROW + cho;
    const uint4 sa = lds128(ma), ca = lds128(ma + 1152), ga = lds128(ma + 2304);
    const uint4 rb = lds128((g & 2) ? SM_ONE + 16 * hi : (ma ^ 64) + 8064 + 1152 * hi);
    const u32 saw[4] = {sa.x, sa.y, sa.z, sa.w}, caw[4] = {ca.x, ca.y, ca.z, ca.w}, gaw[4] = {ga.x, ga.y, ga.z, ga.w};
#pragma unroll
    for (int k = 0; k < 4; k++) {
      const uint2 st = lds64(SM_ST + 16 * (2 * h + 4 * hi + (k & 1) + 8 * (k >> 1)));
      const uint4 xv = lds128(xa + ((k & 1) + 8 * (k >> 1)) * ROW);
      x1[k][0] = xv.x; x1[k][1] = xv.y; x1[k][2] = xv.z; x1[k][3] = xv.w;
#pragma unroll
      for (int v = 0; v < 4; v++) x1[k][v] = badd(x1[k][v], bfma(bmul(badd(x1[k][v], st.x), st.y), caw[v], saw[v]));
    }
    const bool own = (q >> 1) == e;
    const u32 spw = SM_SP + (2 * w + e) * 320 + (g & 3) * 16 + (own ? ((q & 1) == h ? 4 : 12) : 8 - 8 * (q & 1));
    if (SMD && w < 4) asm volatile("setmaxnreg.dec.sync.aligned.u32 168;");
    if (b >= YL) wait_clk(tc, YD);
    conv();
    TS(13);
    POLLW(_Pragma("unroll") for (int v = 0; v < 4; v++) rld128<TAGM>(yv[v], ys[v], pm), lop3<0xa8>(ne3(yv[0].x, yv[1].x, pm), ne3(yv[2].x, yv[3].x, pm), TAGM), 5);
    TS(19);
    if (!SMD && w < 4) asm volatile("setmaxnreg.dec.sync.aligned.u32 168;");
#pragma unroll
    for (int k = 0; k < 4; k += 2) {
      float X[4] = {}, Y[4] = {}, R[4] = {};
#pragma unroll
      for (int v = 0; v < 4; v++) {
        const u32 y0 = k ? yv[v].z : yv[v].x & ~TAGM, y1 = k ? yv[v].w : yv[v].y;
        x1[k][v] = bfma(movm(y0), gaw[v], x1[k][v]);
        x1[k + 1][v] = bfma(movm(y1), gaw[v], x1[k + 1][v]);
        mma8_bf(X, x1[k][v], x1[k + 1][v], x1[k][v]); mma8_bf(Y, x1[k][v], x1[k + 1][v], x1[k + 1][v]);
        if (v & 1) mma_bf(R, x1[k][v - 1], x1[k + 1][v - 1], x1[k][v], x1[k + 1][v], v & 2 ? rb.z : rb.x, v & 2 ? rb.w : rb.y);
      }
      sts32(spw + k * 64, fu(own ? (hi ? X[1] : X[0]) : R[0] + R[1]));
      sts32(spw + k * 64 + 64, fu(own ? (hi ? Y[3] : Y[2]) : R[2] + R[3]));
    }
    barrive(1, N1);
    TS(36);
    if (AFP) { asm volatile("setmaxnreg.inc.sync.aligned.u32 168;"); mb_wait(SM_MB + 8); mb_wait(SM_MB + 16); }
    const uint4 sb = lds128(ma + 3456), cb = lds128(ma + 4608), gb = lds128(ma + 5760);
    const u32 sbw[4] = {sb.x, sb.y, sb.z, sb.w}, cbw[4] = {cb.x, cb.y, cb.z, cb.w}, gbw[4] = {gb.x, gb.y, gb.z, gb.w};
    const u32 t3 = opq(tid), zr = t3 >> 16;
    AROW(t3);
    const u32 aa = ab + arow * 64 + ((((t3 >> 6) & 2) ^ ((t3 & 7) >> 1)) << 4), sta = SM_ST2 + 16 * (g & 3);
    if (AFP) pin(zr, aa, sta, xa);
    bsync(2, 320);
    TS(37);
    uint4 st[4];
#pragma unroll
    for (int k = 0; k < 4; k++) st[k] = lds128(sta + 64 * k);
    lt = lds32(SM_THR);
#define AFL() { _Pragma("unroll") for (int s = 0; s < 9; s++) { A[s] = ldsm4t(aa + s * 1024); A[9 + s] = ldsm4t((aa ^ 16) + s * 1024); } }
    if (AFP && (AFM >> w & 1)) { if (w < 8) AFL() else AFRAG9(); }
#pragma unroll
    for (int k = 0; k < 4; k++) {
      key[k] = st[k].w;
      u32 o[4];
#pragma unroll
      for (int v = 0; v < 4; v++) {
        const u32 d = badd(x1[k][v], st[k].x), z = bfma(d, st[k].y, bmul(d, st[k].z));
        h2[k][v] = FH ? bfma(z, cbw[v], sbw[v]) : badd(bmul(z, cbw[v]), sbw[v]);
        o[v] = FO ? bfma(gbw[v], h2[k][v], x1[k][v]) : badd(x1[k][v], bmul(gbw[v], h2[k][v]));
      }
      h2[k][0] = bmul(h2[k][0], B2M64) | TAGR; x1[k][0] = bmul(x1[k][0], B2M64) | TAGR;
      if (key[k] >= lt) str128(rowp + k * 1152, h2[k][0], h2[k][1], h2[k][2], h2[k][3]);
      sts128(xa + ((k & 1) + 8 * (k >> 1)) * ROW, o[0], o[1], o[2], o[3]);
    }
    barrive(3, 320);
    TS(21);
    if (!AFP) { asm volatile("setmaxnreg.inc.sync.aligned.u32 168;"); mb_wait(SM_MB + 8); mb_wait(SM_MB + 16); AFRAG18(); }
    else if (!(AFM >> w & 1)) { if (w < 8) AFL() else AFRAG9(); }
    TS(22);
    const u32 rr = tid * 57 >> 12, rc = tid * 16 - rr * 1152, sl = SM_SLOT + 8 * rr;
    const char* const rb_ = gs + rc;
    const u32 km = max(max(key[0], key[1]), max(key[2], key[3])), xd = SM_XS + rr * (2 * ROW) + rc;
    if (RW & 2) { pin(tid >> 16, sl, km, xd); pin2(tid >> 16, rb_, rowp); }
    fa = ffn_addr(p, tid | p.zero, b);
    bsync(6, 320);
    TS(24);
    const uint2 sk = lds64(sl);
    const char *r0 = rowa(rb_, sk.x), *r1 = rowa(rb_, sk.y);
    uint4 rv[2] = {ldr128(r0), ldr128(r1)};
    barrive(15, 320);
    const u32 g8 = lds32(SM_SLOT + 28);
    if (__any_sync(~0u, km >= g8 && lt > g8)) {
#pragma unroll
      for (int k = 0; k < 4; k++) if (key[k] >= g8 && key[k] < lt) str128(rowp + k * 1152, h2[k][0], h2[k][1], h2[k][2], h2[k][3]);
    }
    bsync(5, 320);
    const uint2 sf = lds64(sl);
    const u32 f8 = lds32(SM_SLOT + 28);
    if (__any_sync(~0u, km >= f8)) {
#pragma unroll
      for (int k = 0; k < 4; k++) if (key[k] >= f8) str128(rowp + (G_Y + k * 1152), x1[k][0], x1[k][1], x1[k][2], x1[k][3]);
    }
    if (__any_sync(~0u, sf.x != sk.x || sf.y != sk.y)) {
      r0 = rowa(rb_, sf.x); r1 = rowa(rb_, sf.y);
      rv[0].x = rv[1].x = INVAL;
    }
    POLLW({ rld128<TAGM>(rv[0], r0, TAGR); rld128<TAGM>(rv[1], r1, TAGR); }, ne3(rv[0].x, rv[1].x, TAGR) & TAGM, 8);
    TS(38);
#pragma unroll
    for (int j = 0; j < 2; j++) sts128(xd + j * ROW, bmul(rv[j].x ^ TAGR, B2P64), rv[j].y, rv[j].z, rv[j].w);
  } else {
    u32 ok, lr;
    if (w == 10) {
      uint2 rc = lds64(SM_RC + 8 * min(lane, 17u));
      float r1 = lane < 18 ? uf(rc.x) : 0.f, r2 = lane < 18 ? uf(rc.y) : 0.f;
#pragma unroll 1
      for (int o = 16; o; o >>= 1) { r1 += __shfl_xor_sync(~0u, r1, o); r2 += __shfl_xor_sync(~0u, r2, o); }
      const u32 tl = 4 * ((lane >> 1) & 1) + ((lane >> 2) & 3) + 8 * (lane & 1), kl = (2047 - 16 * b - tl) << 2 | par * 3;
      char* const kp = gs + (G_KEY + b * KST);
      const u32 spr = SM_SP + (lane >> 4) * 9 * 320 + (lane & 15) * 16;
      TS(31);
      bsync(1, N1);
      float S1 = 0.f, S2 = 0.f, S3 = 0.f;
#pragma unroll
      for (int i = 0; i < 9; i++) { uint4 t = lds128(spr + i * 320); S1 += uf(t.x); S2 += uf(t.y); S3 += uf(t.z); }
      S1 += __shfl_xor_sync(~0u, S1, 16); S2 += __shfl_xor_sync(~0u, S2, 16); S3 += __shfl_xor_sync(~0u, S3, 16);
      const float mu = S1 * (1.f / 576.f), var = fmaxf(fmaf(-mu, mu, S2 * (1.f / 576.f)), 0.f);
      const float m = rbf(mu), rs = rcpf(rbf(sqrta(rbf(rbf(var) + 1e-5f))));
      const u32 rb = pk_bf(0.f, fmaf(fmaf(-m, r1, S3), rs, r2) + 0.f);
      ok = ((rb ^ (((int)rb >> 31) | 0x80000000)) & 0xffff0000u) | kl;
      const float rh = rbf(rs);
      sts32(SM_KEY + 4 * (lane & 15), ok);
      sts128(SM_ST2 + 16 * (lane & 15), pk_bf(-m, -m), pk_bf(rh, rh), pk_bf(rs - rh, rs - rh), ok);
      __syncwarp();
      const uint4 o0 = lds128(SM_KEY + 2 * (lane & 16)), o1 = lds128(SM_KEY + 2 * (lane & 16) + 16);
      lr = (o0.x > ok) + (o0.y > ok) + (o0.z > ok) + (o0.w > ok) + (o1.x > ok) + (o1.y > ok) + (o1.z > ok) + (o1.w > ok);
      lr += __shfl_xor_sync(~0u, lr, 16);
      if (lane < 16 && lr < 8) str32(kp + 4 * lr, ok);
      if (lr == (b < NB8 ? 7 : NEARLY - 1)) sts32(SM_THR, ok);
      barrive(2, 320);
      barrive(13, 64);
      TS(20);
    } else if (w == 9) {
      if (DB1) bsync(1, N1); else { bsync(12, N12); wait_clk(clk(), DD); }
      PROXY_FENCE();
      DOWN(1);
    } else {
      const char* ks = gs + (G_KEY + (lane >> 1) * KST + (lane & 1) * 16);
      const u32 kt = par * 3;
      uint4 L[8];
      u32 H[8];
#define KBAD(j) ((L[j].x ^ kt) & 3)
#define KLD(j) L[j] = ldr128(ks + j * 16 * KST)
#pragma unroll
      for (int j = 0; j < 8; j++) L[j].x = INVAL;
      bsync(13, 64);
      wait_clk(clk(), b < KE ? KD : b < KF ? KDB : b < YL ? KDC : KD1);
      TS(34);
      POLL({ _Pragma("unroll") for (int j = 0; j < 8; j++) if (KBAD(j)) KLD(j);
             merge4(H, L[0], L[1]); top8(H, L[2], L[3]);
             asm volatile("" : "+r"(H[0]), "+r"(H[1]), "+r"(H[2]), "+r"(H[3]), "+r"(H[4]), "+r"(H[5]), "+r"(H[6]), "+r"(H[7])); TS(32); },
           KBAD(0) | KBAD(1) | KBAD(2) | KBAD(3) | KBAD(4) | KBAD(5), 6);
      top8(H, L[4], L[5]);
      TS(35);
#pragma unroll 1
      for (u32 pass = p.zero;; pass++) {
        u32 G[8], m[8];
#pragma unroll
        for (int i = 0; i < 8; i++) G[i] = H[i];
#pragma unroll
        for (int r = 0; r < 8; r++) {
          const u32 h0 = G[0];
          m[r] = __reduce_max_sync(~0u, h0);
          if (r == 0) { if (KBAD(6)) KLD(6); if (KBAD(7)) KLD(7); }
          if (r < 7) asm("{.reg .u32 t; sub.u32 t,%1,%2; min.u32 t,t,1; mad.lo.u32 %0,t,%3,%4;}" : "=r"(G[0]) : "r"(m[r]), "r"(h0), "r"(h0 - G[1]), "r"(G[1]));
#pragma unroll
          for (int i = 1; i < 7 - r; i++) G[i] = h0 == m[r] ? G[i + 1] : G[i];
          if ((r & 3) == 3) sts128(SM_SLOT + 4 * r - 12, m[r - 3], m[r - 2], m[r - 1], m[r]);
        }
        asm volatile("{.reg .pred p; setp.eq.u32 p,%0,0; @p bar.arrive 6,320;}" ::"r"(pass) : "memory");
        if (pass) break;
        TS(23);
        POLLW({ if (KBAD(6)) KLD(6); if (KBAD(7)) KLD(7); }, KBAD(6) | KBAD(7), 7);
        if (!__any_sync(~0u, max(L[6].x, L[7].x) > m[7])) break;
        top8(H, L[6], L[7]);
      }
      barrive(5, 320);
      TS(33);
    }
    asm volatile("setmaxnreg.inc.sync.aligned.u32 168;");
    mb_wait(SM_MB + 8); mb_wait(SM_MB + 16);
    AROW(tid);
    AFRAG9();
    fa = ffn_addr(p, tid | p.zero, b);
    TS(22);
    if (w == 10) {
      bsync(3, 320);
      PROXY_FENCE();
      if (lane < 16 && lr >= 8) OUTR();
      if (lane < 16 && lr < 8) okl = ok;
    } else if (w == 9) {
      bsync(15, 320);
      DOWN(4);
      TS(13);
    }
  }
  ffn_tail(p, tm_down, A, fa, b3, par, okl);
}

__global__ void __launch_bounds__(384, 1)
fused_kernel(const Prm p, const __grid_constant__ CUtensorMap tm_mod, const __grid_constant__ CUtensorMap tm_gate, const __grid_constant__ CUtensorMap tm_gs,
             const __grid_constant__ CUtensorMap tm_up, const __grid_constant__ CUtensorMap tm_us, const __grid_constant__ CUtensorMap tm_down) {
  extern __shared__ __align__(1024) unsigned char smem[];
  u32 la, ai, ldt; uint2 cr, ci;
  {
    const u32 t = threadIdx.x, d = t < 256 ? chan(blockIdx.x, t >> 5) : 512 + (blockIdx.x >> 1), o = d * 256 + 8 * (t & 31), o4 = o + ((t < 256 ? t >> 5 : t >> 3) & 4);
    asm volatile("{.reg .pred p; .reg .u16 h; setp.ne.u32 p,%7,0; @p ld.global.nc.u32 %0,[%8]; @p ld.global.nc.u32 %1,[%9]; @p ld.global.nc.v2.u32 {%2,%3},[%10];"
                 "@p ld.global.nc.v2.u32 {%4,%5},[%11]; @p ld.global.nc.u16 h,[%12]; cvt.u32.u16 %6,h;}"
                 : "=r"(la), "=r"(ai), "=r"(cr.x), "=r"(cr.y), "=r"(ci.x), "=r"(ci.y), "=r"(ldt)
                 : "r"(0x6ffu >> (t >> 5) & 1), "l"(p.la + o4), "l"(p.ai + o4), "l"(p.cr + o), "l"(p.ci + o), "l"(p.ldt + 2 * d));
  }
  const u32 t0 = clk();
  const u32 tid = __shfl_sync(~0u, threadIdx.x, threadIdx.x & 31), b = blockIdx.x + p.zero;
  const u32 w = tid >> 5, lane = tid & 31;
  const u32 g = lane >> 2, q = lane & 3, hi = g & 1;
  const u32 rho = b & 1, Ps = 512 + (b >> 1);
  char* const gs = p.gs;
  TS0();
  const bool kw = w != 8 && w != 11;
  const u32 ksig = w < 8 ? (w & 3) : 4, khf = w < 8 ? (w >> 2) : (w & 1);
  if (!kw) {
    if (tid == 352) {
#pragma unroll
      for (int i = 0; i < 5; i++) mb_init(SM_MB + 8 * i, i < 4 ? 1 : 64);
      asm volatile("fence.mbarrier_init.release.cluster;" ::: "memory");
      tm_pre(&tm_mod);
    }
    const char* cp = p.c + (576 * (w & 1) + 24 * min(lane, 23u));
    const uint2 c0 = ldg64(cp);
    la = c0.x; ai = c0.y; cr = ldg64(cp + 8); ci = ldg64(cp + 16);
  }
  u32 b3;
  asm volatile("xor.b32 %0,%1,%2;" : "=r"(b3) : "r"(blockIdx.x), "r"(p.zero));
  const u32 zr = tid >> 16;
  const u32 epv = ldr32(gs + (G_EP + zr));
  const u32 tp = SM_TAP + ksig * TAPS;
  if (kw && !khf) {
#pragma unroll 1
    for (u32 i = lane * 16; i < TAPS; i += 512) sts128(tp + i, 0, 0, 0, 0);
  }
  if (tid < 128) sts128(SM_INV + 16 * tid, INVAL, 0, 1, 0);
  if (tid >= (YS == 2 ? 124 : 252)) str128(gs + (tid >= 380 ? G_MOD + b * 128 + q * 16 : b * BLK + 16384 - 252 * 16 + tid * 16 + (tid < 252 ? G_Y + 2048 : 0)), INVAL, 0, 1, 0);
  if (tid == (b < 36 ? 352 : ~0u)) { while (clk() - t0 < DMOD); mb_expect(SM_MB, 36864); tma3d(SM_UP, &tm_mod, SM_MB, 32 * b, 0); }
  if (w < 9) {
    while ((int)(clk() - t0) < DX);
    const char* xp = p.x + (b * BLK + (lane >> 3) * 1152 + 128 * w + 16 * (lane & 7));
    const u32 xd = SM_XST + (((lane >> 3) & 1) + 8 * (lane >> 4)) * ROW + 128 * w + 16 * (lane & 7);
#pragma unroll
    for (int i = 0; i < 4; i++) cpa16(xd + 2 * ROW * i, xp + 4608 * i);
  }
  const u32 ktab = w < 8 ? SM_MODS + w * KTAB : SM_ZS + (w - 9) * KTAB;
  float k2048 = 0.f;
  if (kw) {
    u32 mx = __vmaxu2(__vmaxu2(cr.x & 0x7fff7fff, cr.y & 0x7fff7fff), __vmaxu2(ci.x & 0x7fff7fff, ci.y & 0x7fff7fff));
    const u32 E = max(__reduce_max_sync(~0u, max(mx & 0xffff, mx >> 16)) >> 7, 8u);
    TS(1);
    const float dt = rbf(ex2(blo(ldt) * LOG2E)), csc = uf((257 - E) << 23 | (fu(dt) & 0x7fffff));
    sts32(SM_SC + 16 * ksig + 12, fu(uf(fu(dt) & 0x7f800000) * uf((E - 2) << 23)));
    const u32 crw = khf ? cr.y : cr.x, ciw = khf ? ci.y : ci.x;
    float2 C[2], w4[2], w8[2], w16[2], w32[2], w64[2], w128[2], w256[2], w512[2], a1[2], a2[2], a3[2], t0[2], t1[2], s3[2];
#pragma unroll
    for (int m = 0; m < 2; m++) {
      const float lr2 = rbf(ex2((m ? bhi(la) : blo(la)) * LOG2E)) * dt * -LOG2E, th = (m ? bhi(ai) : blo(ai)) * dt;
      C[m] = make_float2((m ? bhi(crw) : blo(crw)) * csc, (m ? bhi(ciw) : blo(ciw)) * csc);
      const float2 w1 = cexp(lr2, th), w2 = csq(w1);
      w64[m] = cexp(64.f * lr2, 64.f * th);
      w4[m] = csq(w2); w8[m] = csq(w4[m]); w16[m] = csq(w8[m]); w32[m] = csq(w16[m]);
      w128[m] = csq(w64[m]); w256[m] = csq(w128[m]); w512[m] = csq(w256[m]);
      const float2 w1024 = csq(w512[m]);
      a1[m] = cmul(C[m], w1); a2[m] = cmul(C[m], w2); a3[m] = cmul(a1[m], w2);
      t0[m] = cmul(C[m], w1024); t1[m] = cmul(t0[m], w128[m]); s3[m] = cmul(w8[m], w16[m]);
      k2048 += fmaf(t0[m].x, w1024.x, -t0[m].y * w1024.y);
    }
    C2 B0[8], B1[8], B2[8], S[8];
    B0[0] = pk2(C); B0[1] = pk2(a1); B0[2] = pk2(a2); B0[3] = pk2(a3);
    const C2 h4 = pk2(w4), h256 = pk2(w256), h512 = pk2(w512);
#pragma unroll
    for (int i = 0; i < 4; i++) B0[4 + i] = cm2(B0[i], h4);
#pragma unroll
    for (int i = 0; i < 4; i++) B1[i] = cm2(B0[2 * i], h256);
    B1[4] = cm2(B0[0], h512); B1[5] = cm2(B0[4], h512);
    B1[6] = cm2(B1[4], h256); B1[7] = cm2(B1[5], h256);
    const u32 ta = ktab + lane * 128, f = ((lane & 3) << 5) | ((lane & 4) << 2);
#pragma unroll
    for (int i = 0; i < 8; i++) sts128(ta + ((i << 4) ^ f), B0[i].re, B0[i].im, B1[i].re, B1[i].im);
    B2[0] = pk2(t0); B2[1] = pk2(t1);
    B2[2] = cm2(B2[0], h256); B2[3] = cm2(B2[1], h256);
#pragma unroll
    for (int i = 0; i < 4; i++) B2[4 + i] = cm2(B2[i], h512);
    S[0] = {0x3C003C00u, 0u}; S[1] = pk2c(w8); S[2] = pk2c(w16); S[3] = pk2c(s3); S[4] = pk2c(w32);
#pragma unroll
    for (int i = 1; i < 4; i++) S[4 + i] = cm2(S[i], S[4]);
#pragma unroll
    for (int i = 0; i < 8; i++) sts128(ta + 4096 + ((i << 4) ^ f), B2[i].re, B2[i].im, S[i].re, S[i].im);
    const C2 m64 = pk2c(w64), m128 = pk2c(w128);
    sts128(ktab + 8192 + lane * 16, m64.re, m64.im, m128.re, m128.im);
    __syncwarp();
  } else {
    u32 sa = SM_SIL + 576 * (w & 1) + 24 * min(lane, 23u);
#pragma unroll 1
    for (int j = 0; j < 6; j++) {
      sts32(sa, pk_bf(silu_f(blo(la)), silu_f(bhi(la))));
      la = ai; ai = cr.x; cr.x = cr.y; cr.y = ci.x; ci.x = ci.y; sa += 4;
    }
    bsync(7, 64);
  }
  TS(2);
  const u32 pm = (__reduce_or_sync(~0u, epv) & 1) ? 0 : TAGM;
  sts32(SM_THR + 4, pm);
  if (w < 9) {
    asm volatile("cp.async.wait_all;" ::: "memory");
    __syncwarp();
    TS(4);
    if (tid == (b - 36 < 72 ? 256 : ~0u)) { mb_expect(SM_MB, 36864); tma3d(SM_UP, &tm_mod, SM_MB, 32 * b, 0); }
    const u32 xa = SM_XST + (lane & 15) * ROW + 128 * w + 16 * (lane >> 4);
    float s[4] = {}, X[2][4] = {}, Y[2][4] = {};
#pragma unroll
    for (int j = 0; j < 4; j++) {
      const uint4 a = ldsm4(xa + 32 * j);
      mma8_bf(X[0], a.x, a.y, a.x); mma8_bf(Y[0], a.x, a.y, a.y);
      mma8_bf(X[1], a.z, a.w, a.z); mma8_bf(Y[1], a.z, a.w, a.w);
      mma_bf(s, a.x, a.y, a.z, a.w, BONE, BONE);
    }
    uint4 t[4];
#pragma unroll
    for (int j = 0; j < 4; j++) t[j] = ldsm4t(xa + 32 * j);
    const float u0 = hi ? X[0][1] + X[1][1] : X[0][0] + X[1][0], u1 = hi ? Y[0][3] + Y[1][3] : Y[0][2] + Y[1][2];
    if (q == g >> 1) sts128(SM_SP + w * 128 + g * 16, fu(s[0]), fu(u0), fu(s[2]), fu(u1));
    bsync(1, 288);
    TS(7);
    const u32 spr = SM_SP + (lane & 7) * 16 + (lane & 8);
    const uint2 t8 = lds64(spr + 1024);
    const float f8 = lane < 16 ? 1.f : 0.f;
    float S1 = uf(t8.x) * f8, S2 = uf(t8.y) * f8;
#pragma unroll
    for (int i = 0; i < 4; i++) { const uint2 u = lds64(spr + (lane & 16) * 32 + i * 128); S1 += uf(u.x); S2 += uf(u.y); }
    S1 += __shfl_xor_sync(~0u, S1, 16); S2 += __shfl_xor_sync(~0u, S2, 16);
    const float mu = S1 * (1.f / 576.f), var = fmaxf(fmaf(-mu, mu, S2 * (1.f / 576.f)), 0.f);
    const float m = rbf(mu), rs = rcpf(rbf(sqrta(rbf(rbf(var) + 1e-5f))));
    const float ra = rs * 0.0625f;
    sts64(SM_AF + w * 128 + (lane & 15) * 8, fu(ra), fu(-m * ra));
    __syncwarp();
    TS(55);
    const uint4 f0 = lds128(SM_AF + w * 128 + q * 16), f1 = lds128(SM_AF + w * 128 + 64 + q * 16);
    const u32 zdst = SM_GATE + w * 2048 + (g >> 1) * 128 + (lane & 15) * 8;
    const u32 pz = (q & 1) ? 0 : pm;
#pragma unroll
    for (int j = 0; j < 8; j++) {
      const u32 x0 = j & 1 ? t[j >> 1].z : t[j >> 1].x, x1 = j & 1 ? t[j >> 1].w : t[j >> 1].y;
      sts64((j & 1 ? zdst ^ 64 : zdst) + 512 * (j >> 1), pk_hf(fmaf(blo(x0), uf(f0.x), uf(f0.y)), fmaf(bhi(x0), uf(f0.z), uf(f0.w))) | pz,
            pk_hf(fmaf(blo(x1), uf(f1.x), uf(f1.y)), fmaf(bhi(x1), uf(f1.z), uf(f1.w))));
    }
    TS(53);
    if (w < 8) barrive(15, 288);
    else {
      bsync(15, 288);
      TS(54);
      if (lane == 0) {
        PROXY_FENCE();
        bulk_out<BLK>(gs + b * BLK, SM_GATE);
        asm volatile("cp.async.bulk.commit_group;" ::: "memory");
        if (PFG & 1) l2_pre<WSH / 2>(p.wg + b * WSH);
      }
      const float rh = rbf(rs);
      sts128(SM_ST + 16 * (lane & 15), pk_bf(-m, -m), pk_bf(rh, rh), pk_bf(rs - rh, rs - rh), 0);
    }
    TS(5);
  }
  if (kw) {
    float D[5][4] = {};
    u32 ta = ktab + q * 128 + ((g ^ (q << 1)) << 4), tm = ktab + 8192 + q * 16;
#pragma unroll 2
    for (int s = 0; s < 8; s++) {
      const uint4 ca = lds128(ta), cb = lds128(ta + 4096), ma = lds128(tm);
      ta = (ta + 512) ^ 16; tm += 64;
      k2048 += __shfl_xor_sync(~0u, k2048, 16 >> s);
      const C2 s0 = {cb.z, cb.w}, s1 = cm2(s0, {ma.x, ma.y}), s2 = cm2(s0, {ma.z, ma.w}), s3 = cm2(s1, {ma.z, ma.w});
      mma_hf(D[0], s0.re, s1.re, s0.im, s1.im, ca.x, ca.y);
      mma_hf(D[2], s0.re, s1.re, s0.im, s1.im, ca.z, ca.w);
      mma_hf(D[4], s0.re, s1.re, s0.im, s1.im, cb.x, cb.y);
      mma_hf(D[1], s2.re, s3.re, s2.im, s3.im, ca.x, ca.y);
      mma_hf(D[3], s2.re, s3.re, s2.im, s3.im, ca.z, ca.w);
    }
    TS(3);
    const u32 xa = (w < 8 ? SM_MODS + (4 + ksig) * KTAB : SM_ZS) + lane * 16;
    if (khf) {
      __syncwarp();
#pragma unroll
      for (int j = 0; j < 5; j++) sts128(xa + 512 * j, fu(D[j][0]), fu(D[j][1]), fu(D[j][2]), fu(D[j][3]));
      if (lane == 0) sts32(xa + 2560, fu(k2048));
      asm volatile("bar.arrive %0,64;" ::"r"(2 + ksig) : "memory");
    } else {
      const u32 t1 = tp + (q < 2 ? (128 + 4 * g + 2 * q) * 4 : T3 * 4 + ((32 * q - 64 + g) ^ 1) * 2);
      const u32 x = 16 * q + (g >> 1) + hi + 1, tb = tp + (hi ? T7E : T9E) * 4 - 4;
      const u32 te = tb + (x + 2 * (x & 1)) * 2, to = tb + TEO * 4 + (x ^ 1) * 2;
      asm volatile("bar.sync %0,64;" ::"r"(2 + ksig) : "memory");
#pragma unroll
      for (int j = 0; j < 5; j++) { const uint4 t = lds128(xa + 512 * j); D[j][0] += uf(t.x); D[j][1] += uf(t.y); D[j][2] += uf(t.z); D[j][3] += uf(t.w); }
      k2048 = (k2048 + uf(lds32(xa + 2560))) * 0.125f;
#pragma unroll
      for (int r = 0; r < 4; r++) {
        const u32 v = pk_hf(D[2 + (r >> 1)][2 * (r & 1)], D[2 + (r >> 1)][2 * (r & 1) + 1]);
        if (q < 2) {
          const u32 vv = __byte_perm(v, v, 0x1010);
          sts32(t1 + (TO + 32 * r) * 4, vv); sts16(t1 + (TO + 32 * r + 1) * 4 + 2, v >> 16); sts16(t1 + (TO + 32 * r - 1) * 4, v);
          sts64(t1 + (TE + 32 * r) * 4, vv, __byte_perm(v, v, 0x1032));
        } else {
          sts16(t1 + 16 * r, v >> 16);
          if (r == 0 && lane == 2) {
            const u32 vv = __byte_perm(v, v, 0x1010);
            sts32(tp + (TO + 256) * 4, vv); sts16(tp + (TO + 257) * 4 + 2, v); sts16(tp + (TO + 255) * 4, v); sts64(tp + (TE + 256) * 4, vv, vv);
          } else sts16(t1 + 16 * r - ((T3 - T5) * 4 + 6) + 8 * hi, v);
        }
      }
#pragma unroll
      for (int r = 0; r < 2; r++) {
        const u32 v = pk_hf(D[4][2 * r], D[4][2 * r + 1]);
        if (r == 0 && lane == 0) { sts16(tp + T5 * 4 + 62 * 2, v); sts32(SM_KV + 4 * ksig, v & 0xffff); sts16(tp + (T9E + TEO) * 4 + 62 * 2, pk_hf(k2048, 0.f)); }
        else { sts16(te + 8 * r, v); sts16(to + 8 * r, v); }
        sts16(te + 8 * r + 16, v >> 16); sts16(to + 8 * r + 16, v >> 16);
      }
      __syncwarp();
#pragma unroll
      for (int r = 0; r < 4; r++) {
        const u32 v = pk_hf(D[r >> 1][2 * (r & 1) + 1], D[r >> 1][2 * (r & 1)]), t2 = tp + lane * 4 + 128 * r;
        sts32(t2 + TO * 4, v); sts16(t2 + TE * 4, v >> 16); sts16(t2 + (TE + 1) * 4 + 2, v);
      }
      __syncwarp();
    }
  } else if (w == (b < 108 ? 11 : ~0u)) {
    float c[4][4] = {};
    u32 aa = SM_UP + ((lane & 7) + 8 * (lane >> 4)) * 64 + ((((lane >> 3) & 1) ^ ((lane & 7) >> 1)) << 4);
    u32 ba = SM_SIL + (lane >> 3) * 16;
    uint4 a[2][10];
#define GLD(n) { _Pragma("unroll") for (int i = 0; i < 2; i++) { a[n][5 * i] = ldsm4(ba + i * 64); \
      _Pragma("unroll") for (int k = 0; k < 4; k++) a[n][5 * i + 1 + k] = ldsm4t((k & 2 ? aa ^ 32 : aa) + i * 2048 + (k & 1) * 1024); } aa += 4096; ba += 128; }
#define GMM(n) { _Pragma("unroll") for (int i = 0; i < 2; i++) _Pragma("unroll") for (int k = 0; k < 4; k++) { const uint4 f = a[n][5 * i + 1 + k], bb = a[n][5 * i]; \
      mma_bf(c[k], f.x, f.y, f.z, f.w, k & 1 ? bb.z : bb.x, k & 1 ? bb.w : bb.y); } }
    mb_wait(SM_MB);
    TS(56);
    GLD(0);
#pragma unroll 1
    for (int s = 0; s < 4; s++) { GLD(1); GMM(0); GLD(0); GMM(1); }
    GMM(0);
    const float v0 = (q & 1) ? c[0][2] + c[1][2] : c[0][0] + c[1][0], v1 = (q & 1) ? c[2][2] + c[3][2] : c[2][0] + c[3][0];
    str16(gs + (G_MOD + b * 128 + 2 * g + 16 * q), pk_bf(rbf((q & 2) ? v1 : v0) * F2M64, 0.f) | (g < 2 ? pm : 0));
    TS(57);
  }
  TS(6);
  u32 tid2 = tid;
  if (w < 4) {
    asm volatile("setmaxnreg.inc.sync.aligned.u32 232;");
    const u32 tid = tid2 + p.zero, w = tid >> 5, lane = tid & 31, g = lane >> 2, q = lane & 3, hi = g & 1, zr = tid >> 16, tp = SM_TAP + w * TAPS;
    const u32 pml = opq((g & 3) ? 0 : pm);
    const u32 tr = tp + ((hi ? TO : TE) + (g >> 1) - q) * 4;
    u32 T[33][4], B5[5][2], B3[5][2];
#pragma unroll
    for (int d = 0; d < 33; d++) {
      T[d][0] = lds32(tr + 32 * d); T[d][1] = lds32(tr + 32 * d + 16);
      T[d][2] = cpy(d ? T[d - 1][1] : zr, zr, 0); T[d][3] = cpy(T[d][0], zr, 1);
    }
    const u32 t33 = cpy(T[32][1], zr, 0), z33 = cpy(zr, zr, 1);
    if (TPIN) {
#pragma unroll
      for (int d = 0; d < 33; d++) asm volatile("{.reg .pred p; setp.ne.u32 p,%2,0; @p st.shared.v2.u32 [%2],{%0,%1};}" ::"r"(T[d][2]), "r"(T[d][3]), "r"(zr) : "memory");
    }
    const u32 bt = tp + (T5 + g - q) * 4;
#pragma unroll
    for (int d = 0; d < 5; d++) {
      B5[d][0] = lds32(bt + 32 * d); B5[d][1] = lds32(bt + 32 * d - 16);
      B3[d][0] = lds32(bt + 32 * d + (T3 - T5) * 4); B3[d][1] = lds32(bt + 32 * d - 16 + (T3 - T5) * 4);
    }
    u32 za = opq(SM_ZS + 16 + w * ZSS + ((lane >> 3) & 1) * ZPS + ((lane & 7) + (lane >> 4)) * 16);
    u32 wa = opq(SM_W + W5O + w * WSL + row16(lane));
    u32 sa = opq(SM_W + W9O - 2048 + w * WSL + lane * 16);
    u32 yo = opq(G_Y + b * BLK + 256 * q + w * 32 + 4 * g);
    const u32 fa = opq(SM_SC + 16 * w + 8), bw = opq((BW >> 4 * w) & 15), bs = opq((BS >> 4 * w) & 15);
    if (TPIN) asm volatile("{.reg .pred p; setp.ne.u32 p,%8,0; @p st.shared.v4.u32 [%8],{%0,%1,%2,%3}; @p st.shared.v4.u32 [%8],{%4,%5,%6,%7};}"
                           ::"r"(za), "r"(wa), "r"(sa), "r"(yo), "r"(fa), "r"(bw), "r"(bs), "r"(pml), "r"(zr) : "memory");
    TS(8);
    uint2 fc;
    u32 F;
    if (F8) { bsync(8, 384); fc = lds64(fa); F = __byte_perm(fu(uf(fc.x) * uf(fc.y)), 0, 0x3232); pin(zr, F); }
    bsync(9, 384);
    TS(11);
    float A[4][4] = {};
    uint4 Z[4];
    Z[0] = ldsm4(za); Z[1] = ldsm4(za + 32);
    if (!F8) { fc = lds64(fa); F = __byte_perm(fu(uf(fc.x) * uf(fc.y)), 0, 0x3232); }
#define STEP(s, b0, b1) { _Pragma("unroll") for (int i = 0; i < 4; i++) mma_hf_t(A[i], T[8 * i + 7 - (s)], b0, b1); }
#define PAIR(n) { Z[(n + 2) & 3] = ldsm4(za + 32 * (n + 2)); STEP(2 * n, Z[n].x, Z[n].y); STEP(2 * n + 1, Z[n].z, Z[n].w); }
#define LAST(N) mma8_hf(N, t33, z33, Z[3].y); float O[4]; mma_hf_o(O, A[0], T[0], Z[3].z, Z[3].w); \
    _Pragma("unroll") for (int i = 0; i < 3; i++) mma_hf_o(A[i], A[i + 1], T[8 * i + 8], Z[3].z, Z[3].w); \
    mma_hf_o(A[3], N, T[32], Z[3].z, Z[3].w);
#pragma unroll 1
    for (int j = 0; j < 4; j++) {
      PAIR(0); PAIR(1); PAIR(2);
      Z[1] = ldsm4(za + 160); STEP(6, Z[3].x, Z[3].y);
      float N[4] = {};
      LAST(N);
      if (INCV) inc<128>(za);
      y_store<128>(O[0], O[1], O[2], O[3], F, pml, gs + yo);
      if (!INCV) za += 128;
      yo += 1024;
      TSJ(j);
    }
    bsyncr(bw);
    uint4 a5;
    if (A5P) a5 = ldsm4t(wa);
#pragma unroll 1
    for (int j = 4; j < 13; j++) {
      if (j == 8) bsyncr(bs);
      if (!A5P) a5 = ldsm4t(wa);
      const uint4 a3 = ldsm4t(wa + (W3O - W5O));
      uint4 s3 = {0, 0, 0, 0};
      if (j >= 8) s3 = lds128(sa);
      PAIR(0);
      float N[4] = {};
#pragma unroll
      for (int i = 0; i < 4; i++) mma_hf(A[i], a5.x, a5.y, a5.z, a5.w, B5[i][0], B5[i][1]);
      mma_hf(N, a5.x, a5.y, a5.z, a5.w, B5[4][0], B5[4][1]);
      if (INCV) asm volatile("{add.u32 %0,%0,256; xor.b32 %0,%0,32;}" : "+r"(wa)); else wa = (wa + 256) ^ 32;
      if (A5P) a5 = ldsm4t(wa);
      PAIR(1);
#pragma unroll
      for (int i = 0; i < 4; i++) mma_hf(A[i], a3.x, a3.y, a3.z, a3.w, B3[i][0], B3[i][1]);
      mma_hf(N, a3.x, a3.y, a3.z, a3.w, B3[4][0], B3[4][1]);
      PAIR(2);
      Z[1] = ldsm4(za + 160); STEP(6, Z[3].x, Z[3].y);
      LAST(N);
      if (INCV) { inc<128>(za); inc<512>(sa); }
      y_store<128>(O[0] + uf(s3.x), O[1] + uf(s3.y), O[2] + uf(s3.z), O[3] + uf(s3.w), F, pml, gs + yo);
      if (!INCV) { za += 128; sa += 512; }
      yo += 1024;
      TSJ(j);
    }
    {
      asm volatile("mov.u32 %0,%%tid.x;" : "=r"(tid2));
      const uint4 s3 = lds128(sa), s4 = lds128(sa + 512), s5 = lds128(sa + 1024);
      float X[3][4] = {{uf(s4.x), uf(s4.y), uf(s4.z), uf(s4.w)}, {}, {uf(s5.x), uf(s5.y), uf(s5.z), uf(s5.w)}};
#pragma unroll
      for (int ty = 0; ty < 2; ty++) {
        const uint4 a = A5P && !ty ? a5 : ldsm4t(wa + ty * (W3O - W5O)), c = ldsm4t((wa ^ 32) + 256 + ty * (W3O - W5O)), d = ldsm4t(wa + 512 + ty * (W3O - W5O));
#pragma unroll
        for (int i = 0; i < 3; i++) mma_hf(A[i], a.x, a.y, a.z, a.w, ty ? B3[i][0] : B5[i][0], ty ? B3[i][1] : B5[i][1]);
#pragma unroll
        for (int i = 0; i < 2; i++) mma_hf(X[i], c.x, c.y, c.z, c.w, ty ? B3[i][0] : B5[i][0], ty ? B3[i][1] : B5[i][1]);
        mma_hf(X[2], d.x, d.y, d.z, d.w, ty ? B3[0][0] : B5[0][0], ty ? B3[0][1] : B5[0][1]);
      }
#pragma unroll
      for (int n = 0; n < 4; n++) {
        const uint4 f0 = n < 2 ? Z[n] : ldsm4(za + 32 * n), f1 = ldsm4(za + 32 * n + 128), f2 = ldsm4(za + 32 * n + 256);
#pragma unroll
        for (int s = 2 * n; s < 2 * n + 2; s++) {
#pragma unroll
          for (int i = 0; i < 3; i++) mma_hf_t(A[i], T[8 * i + 7 - s], s & 1 ? f0.z : f0.x, s & 1 ? f0.w : f0.y);
          mma_hf_t(X[0], T[7 - s], s & 1 ? f1.z : f1.x, s & 1 ? f1.w : f1.y); mma_hf_t(X[1], T[15 - s], s & 1 ? f1.z : f1.x, s & 1 ? f1.w : f1.y);
          mma_hf_t(X[2], T[7 - s], s & 1 ? f2.z : f2.x, s & 1 ? f2.w : f2.y);
        }
      }
      y_store<128>(A[0][0] + uf(s3.x), A[0][1] + uf(s3.y), A[0][2] + uf(s3.z), A[0][3] + uf(s3.w), F, pml, gs + yo);
      y_store<128>(A[1][0] + X[0][0], A[1][1] + X[0][1], A[1][2] + X[0][2], A[1][3] + X[0][3], F, pml, gs + yo + 1024);
      y_store<128>(A[2][0] + X[1][0] + X[2][0], A[2][1] + X[1][1] + X[2][1], A[2][2] + X[1][2] + X[2][2], A[2][3] + X[1][3] + X[2][3], F, pml, gs + yo + 2048);
    }
    barrive(12, N12);
    TS(15);
  } else {
    asm volatile("setmaxnreg.dec.sync.aligned.u32 136;");
    const u32 t8 = tid - 128, pml = (g & 3) ? 0 : pm;
    {
      TS(12);
      if (PFG == 1 && tid == 288) l2_pre<WSH / 2>(p.wg + (b * WSH + WSH / 2));
      const char* zs = gs + ((16 * w - 64 + (lane >> 3)) * BLK + b * 128 + ((lane & 7) * 16 ^ rho * 64));
      const char* zs4 = gs + ((t8 >> 1) * BLK + (Ps >> 4) * 512 + (Ps & 6) * 64 + ((Ps >> 2 ^ Ps) & 2) * 32 + (Ps & 1) * 32 + (t8 & 1) * 16);
      uint4 v[5];
      v[4].x = INVAL;
      if (ZD) wait_clk(t0, ZD);
      const u32 d = lane < 4 ? chan(b, lane) : Ps;
      const char* mp = gs + (G_MOD + (d >> 5) * 128 + (d & 24) * 2);
      uint4 ta, tc;
      ta.x = tc.x = INVAL;
      const u32 t9 = w == 9 ? pm : INVAL;
      pin2(zr, zs, zs4);
      conv();
      POLLM({ rld128<TAGM>(ta, mp, t9); rld128<TAGM>(tc, mp + MODJ, t9); rld128<TAGM>(v[4], zs4, pm); }, lop3<0xbe>(v[4].x, pm, ne3(ta.x, tc.x, t9)), TAGM, 1);
      TS(58);
#pragma unroll
      for (int j = 0; j < 4; j++) v[j] = ldr128(zs + j * 4 * BLK);
      if (w == 9) {
        const u32 aw = (d & 4) ? ((d & 2) ? ta.w : ta.z) : ((d & 2) ? ta.y : ta.x & ~TAGM);
        const u32 cw = (d & 4) ? ((d & 2) ? tc.w : tc.z) : ((d & 2) ? tc.y : tc.x & ~TAGM);
        const float sa = ((d & 1) ? bhi(aw) : blo(aw)) * F2P64, c1 = rbf(fmaf((d & 1) ? bhi(cw) : blo(cw), F2P64, 1.f));
        const u32 EM = min(max(fu(fmaxf(32.f * fabsf(c1), fabsf(sa))) >> 23, 80u), 250u);
        const float inv = uf((264 - EM) << 23);
        if (lane < 5) { sts64(SM_SC + 16 * lane, pk_hf(16.f * c1 * inv, 16.f * c1 * inv), pk_hf(sa * inv, sa * inv)); sts32(SM_SC + 16 * lane + 8, (EM - 74) << 23); }
        TS(10);
      }
#define MARKERS() if (tid == 256) { \
        if (!YS) bulk_out<2048>(gs + (G_Y + 16384 + b * BLK), SM_INV); \
        _Pragma("unroll") for (int i = MT / 2; i < 8; i++) bulk_out<2048>(gs + (G_Y + 2048 * i + b * BLK), SM_INV); \
        bulk_out<2048>(gs + (G_PART + b * 2048), SM_INV); bulk_out<512>(gs + (G_ACT + b * 512), SM_INV); \
        bulk_out<32>(gs + (G_KEY + b * KST), SM_INV); if (!rho) bulk_out<128>(gs + (G_ACT + Ps * 128), SM_INV); \
        asm volatile("cp.async.bulk.commit_group;" ::: "memory"); }
#define GATE() { mb_expect(SM_MB + 8, rho ? SLV : 46080); \
        _Pragma("unroll") for (int i = GE; i < 3; i++) tma3d(SM_GATE + 12288 * i, &tm_gate, SM_MB + 8, 32 * b, i); \
        if (!rho) tma3d(SM_GATE + SLV, &tm_gs, SM_MB + 8, 4096 + 4 * b, 0); }
#define UP() { mb_expect(SM_MB + 16, rho ? SLV : 46080); tma3d(SM_UP, &tm_up, SM_MB + 16, 32 * b, 0); \
        if (!rho) tma3d(SM_UP + SLV, &tm_us, SM_MB + 16, 4096 + 4 * b, 0); }
      if (PFU == 2 && tid == 256) l2_pre<WSH>(p.wu + b * WSH);
      if (GE && tid == 256) {
        asm volatile("cp.async.bulk.wait_group.read 0;" ::: "memory");
#pragma unroll
        for (int i = 0; i < GE; i++) tma3d(SM_GATE + 12288 * i, &tm_gate, SM_MB + 8, 32 * b, i);
      }
      if (PFG == 2 && tid == 256) l2_pre<WSH>(p.wg + b * WSH);
      if (PFG == 3 && tid == 256) l2_pre<WSH / 2>(p.wg + (b * WSH + WSH / 2));
      bsync(8, F8 ? 384 : 256);
      const uint2 cc = lds64(SM_SC + 8 * (t8 & 6)), c4 = lds64(SM_SC + 64);
      sts128(SM_Z4 + 256 + (t8 & 1) * ZP4 + (t8 >> 1) * 16, hfma(v[4].x & ~TAGM, c4.x, c4.y), hfma(v[4].y, c4.x, c4.y), hfma(v[4].z, c4.x, c4.y), hfma(v[4].w, c4.x, c4.y));
      if (t8 < 96) sts128(t8 < 64 ? SM_ZS + (t8 & 7) * ZPS + (t8 >> 3) * 16 : SM_Z4 + (t8 & 1) * ZP4 + (t8 & 30) * 8, 0, 0, 0, 0);
      asm volatile("cp.async.bulk.wait_group.read 0;" ::: "memory");
      const u32 dst = SM_ZS + 128 + (t8 & 7) * ZPS + (16 * w - 64 + (lane >> 3)) * 16;
      pin(zr, dst);
      conv();
      POLLS(_Pragma("unroll") for (int j = 0; j < 4; j++) sts128(dst + j * 64, hfma(v[j].x & ~TAGM, cc.x, cc.y), hfma(v[j].y, cc.x, cc.y), hfma(v[j].z, cc.x, cc.y), hfma(v[j].w, cc.x, cc.y)),
            _Pragma("unroll") for (int j = 0; j < 4; j++) rld128<TAGM>(v[j], zs + j * 4 * BLK, pm), ne3(v[0].x, v[1].x, pm) | ne3(v[2].x, v[3].x, pm), TAGM, 1);
      TS(9);
      bsync(9, 384);
      TS(11);
      if (MKT == 1) MARKERS();
      const bool lng = w < 8 || w == 9;
      const u32 ts = lane + 32 * (w == 8 ? 0 : w - 9), c = min(ts, 71u), ma = SM_MODS + 16 * c;
      const u32 sig = lng ? ksig : ts >> 4, l2 = lng ? lane : 32 + (ts & 15);
      const char* mq = gs + (G_MOD + (c >> 2) * 128 + (c & 3) * 16);
      if (!lng) {
#pragma unroll
        for (int j = 0; j < 6; j++) cpa16(ma + 1152 * j, mq + j * MODJ);
        cpa16(ma + 1152 * 6, p.dsk + 16 * c); cpa16(ma + 1152 * 7, p.wr + 16 * c);
        if (PFU == 3) {
#pragma unroll
          for (int j = 0; j < 4; j++) if (ts < 81) l2_line(p.wu + (b * WSH + (81 * j + ts) * 128));
        }
        if (tid == 352) {
          PROXY_FENCE();
          if (PFU == 1) l2_pre<WSH>(p.wu + b * WSH);
          if (!TG) GATE();
          if (!TU) UP();
        }
      }
      const u32 wb = SM_W + sig * WSL;
      if (sig < 5) {
        const u32 za = (sig < 4 ? SM_ZS + 128 + sig * ZSS : SM_Z4 + 256) + l2 * 32, zb = za + (sig < 4 ? ZPS : ZP4);
        const uint4 c0 = lds128(zb - 32), c1 = lds128(za - 16), c2 = lds128(zb - 16), c3 = lds128(za), c4 = lds128(zb), c5 = lds128(za + 16), c6 = lds128(zb + 16);
        const u32 P[25] = {c0.z, c0.w, c1.x, c1.y, c1.z, c1.w, c2.x, c2.y, c2.z, c2.w, c3.x, c3.y, c3.z, c3.w, c4.x, c4.y, c4.z, c4.w, c5.x, c5.y, c5.z, c5.w, c6.x, c6.y, c6.z};
        u32 Q[25], D1[24], F4[23], W5[21], W3[17];
#pragma unroll
        for (int j = 1; j < 25; j++) Q[j] = __byte_perm(P[j - 1], P[j], 0x5432);
#pragma unroll
        for (int j = 1; j < 24; j++) D1[j] = hadd(P[j], Q[j]);
#pragma unroll
        for (int j = 2; j < 23; j++) F4[j] = hadd(D1[j], D1[j - 1]);
#pragma unroll
        for (int n = 0; n < 21; n++) W5[n] = hadd(F4[n + 2], P[n]);
#pragma unroll
        for (int n = 0; n < 17; n++) W3[n] = hadd(Q[n + 8], D1[n + 7]);
        const u32 a0 = wb + W5O + 64 * l2 + 16 * ((l2 >> 1) & 3);
#pragma unroll
        for (int i = 0; i < 4; i++) {
          sts128(a0 ^ (16 * i), W5[4 * i + 5], W5[4 * i + 6], W5[4 * i + 7], W5[4 * i + 8]);
          sts128((a0 ^ (16 * i)) + (W3O - W5O), W3[4 * i + 1], W3[4 * i + 2], W3[4 * i + 3], W3[4 * i + 4]);
        }
        if (lng) {
          if (lane < 16) sts128(wb + (lane & 7) * 16 + (lane & 8) * 400, 0, 0, 0, 0);
          const u32 a1 = wb + 32 * lane + 16 * ((lane >> 2) & 1);
#pragma unroll
          for (int i = 0; i < 4; i++) {
            const u32 a = (a1 ^ (16 * (i >> 1))) + 1024 * (i & 1), n = 4 * i;
            sts128(a + V2O, hadd(Q[n + 9], P[n + 8]), hadd(Q[n + 10], P[n + 9]), hadd(Q[n + 11], P[n + 10]), hadd(Q[n + 12], P[n + 11]));
            sts128(a + W9O, hadd(F4[n + 4], W5[n]), hadd(F4[n + 5], W5[n + 1]), hadd(F4[n + 6], W5[n + 2]), hadd(F4[n + 7], W5[n + 3]));
            sts128(a + W7O, hadd(F4[n + 6], W3[n]), hadd(F4[n + 7], W3[n + 1]), hadd(F4[n + 8], W3[n + 2]), hadd(F4[n + 9], W3[n + 3]));
          }
        }
      }
      if (w < 8) barriver((BW >> (4 * w - 16)) & 15);
      else if (!(w & 1)) { barriver((BW >> (4 * w - 32)) & 15); barriver((BW >> (4 * w - 28)) & 15); }
      __syncwarp();
      TS(32);
      if (lng) {
        const u32 wa = wb + ((lane >> 3) & 1) * 1024 + (((lane & 7) ^ (lane >> 4)) + 8 * (lane >> 4)) * 16;
        const u32 kv = lds32(SM_KV + 4 * sig), bi = (g >> 1) == q ? (hi ? kv << 16 : kv) : 0u;
        float acc[8][4] = {};
#pragma unroll
        for (int j = 0; j < 4; j++) { const uint4 a = ldsm4t(wa + V2O + j * 256); mma8_hf(acc[2 * j], a.x, a.y, bi); mma8_hf(acc[2 * j + 1], a.z, a.w, bi); }
        u32 bt = tp + (T9E + hi * TEO + (g >> 1) - q) * 4, wt = wa + W9O;
#pragma unroll 1
        for (int ty = 0; ty < 2; ty++) {
          uint4 a[4];
#pragma unroll
          for (int be = 0; be < 4; be++) a[be] = ldsm4t(wt + be * 256);
          u32 b1 = lds32(bt - 16);
#pragma unroll
          for (int d = 0; d < 8; d++) {
            const u32 b0 = lds32(bt + 16 * d);
#pragma unroll
            for (int be = 0; be < 4; be++) if (d + 2 * be < 8) mma_hf(acc[d + 2 * be], a[be].x, a[be].y, a[be].z, a[be].w, b0, b1);
            b1 = b0;
          }
          bt += (T7E - T9E) * 4; wt += W7O - W9O;
        }
        __syncwarp();
#pragma unroll
        for (int j = 0; j < 8; j++) sts128(wb + W9O + j * 512 + lane * 16, fu(acc[j][0]), fu(acc[j][1]), fu(acc[j][2]), fu(acc[j][3]));
        if (w != 9) barriver((BS >> (4 * w - 16)) & 15);
        TS(34);
      }
      if (!lng) {
        asm volatile("cp.async.wait_all;" ::: "memory");
        uint4 md[6];
#pragma unroll
        for (int j = 0; j < 6; j++) md[j] = lds128(ma + 1152 * j);
        const uint4 dk = lds128(ma + 1152 * 6), wr = lds128(ma + 1152 * 7);
        POLLW(_Pragma("unroll") for (int j = 0; j < 6; j++) md[j] = ldr128(mq + j * MODJ),
              ((md[0].x ^ pm) | (md[1].x ^ pm) | (md[2].x ^ pm) | (md[3].x ^ pm) | (md[4].x ^ pm) | (md[5].x ^ pm)) & TAGM, 4);
#pragma unroll
        for (int j = 0; j < 6; j++) {
          const u32 o = (j % 3 == 1) ? BONE : 0x80008000u;
          md[j] = make_uint4(bfma(md[j].x & ~TAGM, B2P64, o), bfma(md[j].y, B2P64, o), bfma(md[j].z, B2P64, o), bfma(md[j].w, B2P64, o));
          if (j > 2) sts128(ma + 1152 * j, md[j].x, md[j].y, md[j].z, md[j].w);
        }
        const uint4 gd = make_uint4(bmul(md[2].x, dk.x), bmul(md[2].y, dk.y), bmul(md[2].z, dk.z), bmul(md[2].w, dk.w));
#pragma unroll
        for (int j = 0; j < 2; j++) sts128(ma + 1152 * j, bmul(md[j].x, gd.x), bmul(md[j].y, gd.y), bmul(md[j].z, gd.z), bmul(md[j].w, gd.w));
        sts128(ma + 2304, bmul(md[2].x, B2P64), bmul(md[2].y, B2P64), bmul(md[2].z, B2P64), bmul(md[2].w, B2P64));
        const uint4 H = make_uint4(bmul(md[4].x, wr.x), bmul(md[4].y, wr.y), bmul(md[4].z, wr.z), bmul(md[4].w, wr.w));
        sts128(ma + 1152 * 7, H.x, H.y, H.z, H.w);
        sts128(ma + 1152 * 8, bfma(md[4].x, wr.x, H.x ^ 0x80008000u), bfma(md[4].y, wr.y, H.y ^ 0x80008000u), bfma(md[4].z, wr.z, H.z ^ 0x80008000u), bfma(md[4].w, wr.w, H.w ^ 0x80008000u));
        float c4[4] = {};
        mma_bf(c4, md[4].x, md[3].x, md[4].y, md[3].y, wr.x, wr.y); mma_bf(c4, md[4].z, md[3].z, md[4].w, md[3].w, wr.z, wr.w);
        if (q == g >> 1) sts64(SM_RC + (ts >> 2) * 8, fu(hi ? c4[1] : c4[0]), fu(hi ? c4[3] : c4[2]));
        if (ts < 2) sts128(SM_ONE + 16 * ts, ts ? 0 : BONE, ts ? 0 : BONE, ts ? 0 : BONE, ts ? 0 : BONE);
        TS(14);
        if (MKT == 2) MARKERS();
        if (w == 8) asm volatile("cp.async.bulk.wait_group 0;" ::: "memory");
        if (PFW == 2) {
#pragma unroll
          for (int j = 0; j < 4; j++) if (ts < 81) l2_line(p.wd + (b * WSH + (81 * j + ts) * 128));
        }
        bsync(13, 96);
        if (w == 8) { barriver(2); barriver(3); barriver(5); barriver(6); if (HLP) barrive(7, 64); }
      }
      if (!HLP) { if (w >= 8) barrive(11, 256); }
      else if (w == 9) barrive(11, 128);
    }
    const u32 jw = w < 6 ? w ^ 1 : w < 8 ? w : max(w - 4, 5u);
    const int u0 = 4 * (jw - 4) + 2 * rho;
    const u32 t4 = SM_TAP + 4 * TAPS, s3a = SM_W + 4 * WSL + (u0 >= 8 ? W9O + (u0 - 8) * 512 : V2O) + lane * 16, hb = (0x4987 >> (4 * jw - 16)) & 15;
#define FARL() { u32 wa = (SM_W + 4 * WSL + W5O + row16(lane) + (u0 - 3) * 256) ^ 32, bt = t4 + (T5 + g - q) * 4; \
      _Pragma("unroll 1") for (int al = min(u0 - 2, 6); al > 0; al--) { \
        _Pragma("unroll") for (int ty = 0; ty < 2; ty++) { \
          const uint4 a = ldsm4t(wa + ty * (W3O - W5O)); \
          const u32 bb = bt + ty * (T3 - T5) * 4; \
          mma_hf(acc[ty], a.x, a.y, a.z, a.w, lds32(bb - 32), lds32(bb - 48)); \
          mma_hf(acc[2 + ty], a.x, a.y, a.z, a.w, lds32(bb), lds32(bb - 16)); \
        } \
        wa = (wa - 256) ^ 32; bt += 32; } }
    if (w < 8) {
      u32 tr = t4 + ((hi ? TO : TE) + (g >> 1) - q) * 4;
      u32 zb = SM_Z4 + 256 + ((lane >> 3) & 1) * ZP4 + u0 * 128 + (lane & 7) * 16 + (lane >> 4) * 128;
      float acc[4][4] = {};
      u32 prev = 0;
#pragma unroll 1
      for (int it = min(u0 + 2, 4); it; it--) {
#pragma unroll
        for (int s = 0; s < 8; s++) {
          const uint4 z = ldsm4(zb - 16 * s);
          const u32 t0 = lds32(tr + 32 * s), t1 = lds32(tr + 32 * s + 16);
          mma_hf(acc[s & 1], t0, t1, prev, t0, z.x, z.y);
          mma_hf(acc[2 + (s & 1)], t0, t1, prev, t0, z.z, z.w);
          prev = t1;
        }
        zb -= 128; tr += 256;
      }
      {
        const uint4 z = ldsm4(zb); const u32 t0 = lds32(tr), t1 = lds32(tr + 16);
        mma_hf(acc[0], t0, t1, prev, t0, z.x, z.y); mma_hf(acc[2], t0, t1, prev, t0, z.z, z.w);
        if (jw > 4) { const uint4 y = ldsm4(zb - 16); mma8_hf(acc[1], t1, zr, y.y); mma8_hf(acc[3], t1, zr, y.w); }
      }
      if (!HLP) { bsync(11, 256); FARL(); }
      else asm volatile("bar.sync %0,64;" ::"r"(hb) : "memory");
      TS(35);
      const uint2 fc = lds64(SM_SC + 16 * 4 + 8);
      const u32 F = __byte_perm(fu(uf(fc.x) * uf(fc.y)), 0, 0x3232);
      char* yp = gs + (YS ? G_Y + 16384 + (32 * jw - 128 + 16 * rho + 2 * q) * BLK + (b & 12) * 128 + (b & 64) * 4 + (b & 48) * 4 + (b & 2) * 16 + 4 * g : G_Y + 16384 - 2048 + b * BLK + jw * 512 + q * 64 + 4 * g);
#pragma unroll
      for (int j = 0; j < 2; j++) {
        uint4 s3 = {0, 0, 0, 0};
        if (u0 >= (HLP ? 4 : 8)) s3 = lds128(s3a + j * 512);
        y_store<YS ? BLK : 32>(acc[2 * j][0] + acc[2 * j + 1][0] + uf(s3.x), acc[2 * j][1] + acc[2 * j + 1][1] + uf(s3.y), acc[2 * j][2] + acc[2 * j + 1][2] + uf(s3.z),
                acc[2 * j][3] + acc[2 * j + 1][3] + uf(s3.w), F, pml, yp + j * (YS ? 8 * BLK : 256));
      }
      TS(16);
    } else {
      if (HLP && w != 9) {
        bsync(11, 128);
        if (HD) wait_clk(clk(), HD);
        float acc[4][4] = {};
        if (u0 >= 8) {
#pragma unroll
          for (int j = 0; j < 2; j++) { const uint4 t = lds128(s3a + j * 512); acc[2 * j][0] = uf(t.x); acc[2 * j][1] = uf(t.y); acc[2 * j][2] = uf(t.z); acc[2 * j][3] = uf(t.w); }
        }
        FARL();
#pragma unroll
        for (int j = 0; j < 2; j++)
          sts128(s3a + j * 512, fu(acc[2 * j][0] + acc[2 * j + 1][0]), fu(acc[2 * j][1] + acc[2 * j + 1][1]), fu(acc[2 * j][2] + acc[2 * j + 1][2]), fu(acc[2 * j][3] + acc[2 * j + 1][3]));
        asm volatile("bar.arrive %0,64;" ::"r"(hb) : "memory");
        TS(16);
      }
      if (PFW == 3 && w == 9) {
#pragma unroll 1
        for (int j = 0; j < 12; j++) { if (lane < 27) l2_line(p.wd + (b * WSH + (27 * j + lane) * 128)); wait_clk(clk(), PFP); }
      }
      if (TG | TU | TW) {
        if (tid == 352) {
          if (TG) { wait_clk(t0, TG); GATE(); }
          if (TW < TU) { wait_clk(t0, TW); l2_pre<WSH>(p.wd + b * WSH); }
          if (TU) { wait_clk(t0, TU); UP(); }
          if (TW >= TU) { wait_clk(t0, TW); l2_pre<WSH>(p.wd + b * WSH); }
        }
      } else if (PFW < 2 && tid == 352) { mb_wait(SM_MB + 8); if (PFW) mb_wait(SM_MB + 16); l2_pre<WSH>(p.wd + b * WSH); }
      if (D0C && tid == 352 && b < 108) {
        mb_wait(SM_MB + 16);
        PROXY_FENCE();
        mb_expect(SM_MB + 24, 49152);
        tma3d(SM_TAP, &tm_down, SM_MB + 24, 64 * (b % 9), 4 * (b / 9));
      }
      TS(17);
    }
  }
  post_conv(p, &tm_down, tid2 + p.zero, b, b3);
  TSD();
  if (s2u(smem) != SM0) __trap();
}

typedef CUresult (*EncFn)(CUtensorMap*, CUtensorMapDataType, cuuint32_t, void*, const cuuint64_t*, const cuuint64_t*, const cuuint32_t*, const cuuint32_t*,
                          CUtensorMapInterleave, CUtensorMapSwizzle, CUtensorMapL2promotion, CUtensorMapFloatOOBfill);
static void make_map(EncFn enc, CUtensorMap* tm, void* ptr, int cols, int rows, int bw, int nb, CUtensorMapSwizzle sw, int gr = 192, int prom = 0) {
  cuuint64_t gd[3] = {(cuuint64_t)cols, (cuuint64_t)gr, (cuuint64_t)(rows / gr)}, gs[2] = {(cuuint64_t)cols * 2, (cuuint64_t)cols * 2 * gr};
  cuuint32_t bd[3] = {(cuuint32_t)bw, (cuuint32_t)gr, (cuuint32_t)nb}, es[3] = {1, 1, 1};
  enc(tm, CU_TENSOR_MAP_DATA_TYPE_BFLOAT16, 3, ptr, gd, gs, bd, es, CU_TENSOR_MAP_INTERLEAVE_NONE, sw, (CUtensorMapL2promotion)prom, CU_TENSOR_MAP_FLOAT_OOB_FILL_NONE);
}
extern "C" void kernel_launch(void* const* d_in, const int* in_sizes, int n_in, void* d_out, int out_size) {
  static EncFn enc = nullptr;
  static void* scratch = nullptr;
  if (!enc) {
    cudaGetSymbolAddress(&scratch, g_s);
    cudaDriverEntryPointQueryResult qr;
    cudaGetDriverEntryPoint("cuTensorMapEncodeTiled", (void**)&enc, cudaEnableDefault, &qr);
    cudaFuncSetAttribute(fused_kernel, cudaFuncAttributeMaxDynamicSharedMemorySize, SM_TOTAL);
  }
  CUtensorMap tm_mod, tm_gate, tm_gs, tm_up, tm_us, tm_down;
  make_map(enc, &tm_mod, d_in[13], 3456, 576, 32, 3, CU_TENSOR_MAP_SWIZZLE_64B, 192, PRM);
  make_map(enc, &tm_gate, d_in[9], 4608, 576, 32, 1, CU_TENSOR_MAP_SWIZZLE_64B, 192, PRG);
  make_map(enc, &tm_gs, d_in[9], 4608, 576, 8, 3, CU_TENSOR_MAP_SWIZZLE_NONE);
  make_map(enc, &tm_up, d_in[10], 4608, 576, 32, 3, CU_TENSOR_MAP_SWIZZLE_64B, 192, PRU);
  make_map(enc, &tm_us, d_in[10], 4608, 576, 8, 3, CU_TENSOR_MAP_SWIZZLE_NONE, 192, PRS);
  make_map(enc, &tm_down, d_in[11], 576, 4608, 64, 1, CU_TENSOR_MAP_SWIZZLE_128B, 96);
  Prm p;
  p.x = (const char*)d_in[0]; p.la = (const char*)d_in[1]; p.ai = (const char*)d_in[2]; p.cr = (const char*)d_in[3];
  p.ci = (const char*)d_in[4]; p.ldt = (const char*)d_in[5]; p.dsk = (const char*)d_in[6]; p.wr = (const char*)d_in[8];
  p.wg = (const char*)d_in[9]; p.wu = (const char*)d_in[10]; p.wd = (const char*)d_in[11];
  p.c = (const char*)d_in[12]; p.out = (char*)d_out; p.zero = 0; p.gs = (char*)scratch;
  fused_kernel<<<128, 384, SM_TOTAL>>>(p, tm_mod, tm_gate, tm_gs, tm_up, tm_us, tm_down);
}
```

```cpp
#include <cuda_runtime.h>
#include <cuda.h>
#include <cuda_bf16.h>
#include <cuda_fp16.h>
#include <stdint.h>
#define FUSED 1
#define DEV __device__ __forceinline__
typedef uint32_t u32;

constexpr u32 BLK = 18432, G_Z = 0, G_Y = 128 * BLK, G_MOD = 2 * G_Y, G_KEY = G_MOD + 128 * 128, G_ACT = G_KEY + 128 * 128;
constexpr u32 G_PART = G_ACT + 576 * 128, G_EP = G_PART + 128 * 2048, G_END = G_EP + 128;
__device__ __align__(128) unsigned char g_s[G_END];
#define TS(i)
#define TSJ(j)
#define TS0()
#define TSE()
#define TSD()
#define TSX 0
#define TSRND()
#define TSN(code, n)
#define ERRF(code)

constexpr int SM0 = 1024;
constexpr int ROW = 1168, SLV = 36864;
constexpr int SM_GATE = SM0, SM_UP = SM_GATE + 46080, SM_XST = SM_UP + 46080, SM_MODS = SM_XST + 16 * ROW, SM_W = SM_MODS + 11008;
constexpr int KTAB = 9216, WSL = 12544, W5O = 128, W3O = 3328, V2O = 6400, W9O = 8448, W7O = 10496;
constexpr int ZPS = 2192, ZSS = 2 * ZPS, ZP4 = 2368;
constexpr int SM_ZS = SM_W + 5 * WSL, SM_Z4 = SM_ZS + 4 * ZSS, SM_TAP = SM_Z4 + 2 * ZP4, TAPS = 3328;
constexpr int SM_MB = SM_TAP + 5 * TAPS;
constexpr int SM_SC = SM_MB + 48;
constexpr int SM_KV = SM_SC + 80;
constexpr int SM_THR = SM_KV + 32;
constexpr int SM_SLOT = SM_THR + 48;
constexpr int SM_KEY = SM_SLOT + 32;
constexpr int SM_ST = SM_KEY + 64;
constexpr int SM_ST2 = SM_ST + 256;
constexpr int SM_RC = SM_ST2 + 256;
constexpr int SM_SP = SM_RC + 192;
constexpr int SM_AF = SM_SP + 1152, SM_SIL = SM_AF + 1152, SM_INV = SM_SIL + 1152, SM_END = SM_SP + 5760;
constexpr int SM_ONE = SM_MODS + 9 * 1152;
constexpr int SM_WD = SM_W, SM_XS = SM_W + 36864, SM_AC = SM_ZS, SM_RED = SM_AC + 6144;
constexpr int SM_TSB = SM_END, SM_TOTAL = SM_END + TSX - SM0;
static_assert(SM_W % 1024 == 0 && SM_TAP % 1024 == 0 && SM_MODS + 8 * KTAB <= SM_ZS && SM_ZS + 2 * KTAB <= SM_TAP && SM_RED + 10240 <= SM_TAP && SM_XS + 8 * ROW <= SM_ZS, "smem map");
static_assert(SM_MB % 16 == 0 && SM_THR % 16 == 0 && SM_ST % 16 == 0 && SM_SP % 16 == 0 && SM_TOTAL <= 232448, "smem map");
constexpr int TE = 4, TO = 276, T5 = 560, T3 = 624, T9E = 680, T7E = 760, TEO = 40;
#define MT 10
#define MKT 1
#define KST 32
#define DE1 1
#define DE2 4
#define DE3 5
#define OUTB 7
#define PFW 1
#define PFU 0
#define KD 700
#define D0C 0
#define YE 104
#define YL 104
#define YD 250
#define OPTM 1
#define Y8 104
#define FH 0
#define FO 0
#define DB1 1
#define KD1 50
#define AD 0
#define PD 900
#define ZD 0
#define DD 1000
#define INCV 1
#define TPIN 0
#define A5P 1
#define TG 0
#define TU 0
#define TW 0
#define KDB 520
#define PRM 0
#define PRG 0
#define PRU 0
#define PRS 0
#define KE 64
#define PFP 200
#define GE 0
#define NB8 8
#define DX 0
#define DMOD 1000
#define RW 3
#define AW 7
#define HLP 1
#define SMD 1
#define CVG 1
#define YS 2
#define F8 0
#define HD 0
#define KF 96
#define KDC 520
#define AFP 1
#define AFM 0
#define PFG 1
constexpr int N1 = 320 + 32 * DB1, N12 = 288 + 32 * !DB1;
constexpr int SPIN = 1 << 16, NEARLY = 4;
constexpr u32 TAGM = 0x40004000u, TAGR = 0x40000000u, INVAL = 0x00004801u;

DEV u32 s2u(const void* p) { return (u32)__cvta_generic_to_shared(p); }
DEV void mma_bf(float (&c)[4], u32 a0, u32 a1, u32 a2, u32 a3, u32 b0, u32 b1) {
  asm("mma.sync.aligned.m16n8k16.row.col.f32.bf16.bf16.f32 {%0,%1,%2,%3},{%4,%5,%6,%7},{%8,%9},{%0,%1,%2,%3};"
      : "+f"(c[0]), "+f"(c[1]), "+f"(c[2]), "+f"(c[3]) : "r"(a0), "r"(a1), "r"(a2), "r"(a3), "r"(b0), "r"(b1));
}
DEV void mma_hf(float (&c)[4], u32 a0, u32 a1, u32 a2, u32 a3, u32 b0, u32 b1) {
  asm("mma.sync.aligned.m16n8k16.row.col.f32.f16.f16.f32 {%0,%1,%2,%3},{%4,%5,%6,%7},{%8,%9},{%0,%1,%2,%3};"
      : "+f"(c[0]), "+f"(c[1]), "+f"(c[2]), "+f"(c[3]) : "r"(a0), "r"(a1), "r"(a2), "r"(a3), "r"(b0), "r"(b1));
}
DEV void mma8_bf(float (&c)[4], u32 a0, u32 a1, u32 b0) {
  asm("mma.sync.aligned.m16n8k8.row.col.f32.bf16.bf16.f32 {%0,%1,%2,%3},{%4,%5},{%6},{%0,%1,%2,%3};"
      : "+f"(c[0]), "+f"(c[1]), "+f"(c[2]), "+f"(c[3]) : "r"(a0), "r"(a1), "r"(b0));
}
DEV void mma8_hf(float (&c)[4], u32 a0, u32 a1, u32 b0) {
  asm("mma.sync.aligned.m16n8k8.row.col.f32.f16.f16.f32 {%0,%1,%2,%3},{%4,%5},{%6},{%0,%1,%2,%3};"
      : "+f"(c[0]), "+f"(c[1]), "+f"(c[2]), "+f"(c[3]) : "r"(a0), "r"(a1), "r"(b0));
}
DEV u32 movm(u32 x) { u32 r; asm("movmatrix.sync.aligned.m8n8.trans.b16 %0,%1;" : "=r"(r) : "r"(x)); return r; }
DEV void conv() { if (CVG) asm volatile("{.reg .u32 t; mov.u32 t,0; movmatrix.sync.aligned.m8n8.trans.b16 t,t;}"); }
DEV uint4 ldsm4(u32 a) { uint4 r; asm volatile("ldmatrix.sync.aligned.m8n8.x4.shared.b16 {%0,%1,%2,%3},[%4];" : "=r"(r.x), "=r"(r.y), "=r"(r.z), "=r"(r.w) : "r"(a)); return r; }
DEV uint4 ldsm4t(u32 a) { uint4 r; asm volatile("ldmatrix.sync.aligned.m8n8.x4.trans.shared.b16 {%0,%1,%2,%3},[%4];" : "=r"(r.x), "=r"(r.y), "=r"(r.z), "=r"(r.w) : "r"(a)); return r; }
DEV u32 lds32(u32 a) { u32 r; asm volatile("ld.volatile.shared.u32 %0,[%1];" : "=r"(r) : "r"(a)); return r; }
DEV uint2 lds64(u32 a) { uint2 r; asm volatile("ld.shared.v2.u32 {%0,%1},[%2];" : "=r"(r.x), "=r"(r.y) : "r"(a)); return r; }
DEV uint4 lds128(u32 a) { uint4 r; asm volatile("ld.shared.v4.u32 {%0,%1,%2,%3},[%4];" : "=r"(r.x), "=r"(r.y), "=r"(r.z), "=r"(r.w) : "r"(a)); return r; }
DEV void sts16(u32 a, u32 v) { asm volatile("st.shared.u16 [%0],%1;" ::"r"(a), "h"((unsigned short)v) : "memory"); }
DEV void sts32(u32 a, u32 v) { asm volatile("st.shared.u32 [%0],%1;" ::"r"(a), "r"(v) : "memory"); }
DEV void sts64(u32 a, u32 x, u32 y) { asm volatile("st.shared.v2.u32 [%0],{%1,%2};" ::"r"(a), "r"(x), "r"(y) : "memory"); }
DEV void sts128(u32 a, u32 x, u32 y, u32 z, u32 w) { asm volatile("st.shared.v4.u32 [%0],{%1,%2,%3,%4};" ::"r"(a), "r"(x), "r"(y), "r"(z), "r"(w) : "memory"); }
DEV uint4 ldr128(const void* p) { uint4 v; asm volatile("ld.relaxed.gpu.global.v4.u32 {%0,%1,%2,%3},[%4];" : "=r"(v.x), "=r"(v.y), "=r"(v.z), "=r"(v.w) : "l"(p) : "memory"); return v; }
DEV uint2 ldr64(const void* p) { uint2 v; asm volatile("ld.relaxed.gpu.global.v2.u32 {%0,%1},[%2];" : "=r"(v.x), "=r"(v.y) : "l"(p) : "memory"); return v; }
DEV u32 ldr32(const void* p) { u32 v; asm volatile("ld.relaxed.gpu.global.u32 %0,[%1];" : "=r"(v) : "l"(p) : "memory"); return v; }
template <u32 M> DEV void rld128(uint4& v, const void* p, u32 tag) {
  asm volatile("{.reg .pred p; .reg .u32 t; lop3.b32 t,%0,%5,%6,0x28; setp.ne.u32 p,t,0; @p ld.relaxed.gpu.global.v4.u32 {%0,%1,%2,%3},[%4];}"
               : "+r"(v.x), "+r"(v.y), "+r"(v.z), "+r"(v.w) : "l"(p), "r"(tag), "n"(M) : "memory");
}
template <u32 M> DEV void rld64(uint64_t& v, const void* p, u32 tag) {
  asm volatile("{.reg .pred p; .reg .u32 t, h; mov.b64 {t,h},%0; lop3.b32 t,t,%2,%3,0x28; setp.ne.u32 p,t,0; @p ld.relaxed.gpu.global.u64 %0,[%1];}" : "+l"(v) : "l"(p), "r"(tag), "n"(M) : "memory");
}
template <int L> DEV u32 lop3(u32 a, u32 b, u32 c) { u32 r; asm("lop3.b32 %0,%1,%2,%3,%4;" : "=r"(r) : "r"(a), "r"(b), "r"(c), "n"(L)); return r; }
DEV u32 ne3(u32 a, u32 b, u32 c) { u32 r; asm("lop3.b32 %0,%1,%2,%3,0x7e;" : "=r"(r) : "r"(a), "r"(b), "r"(c)); return r; }
DEV void pin(u32 zr, u32 a, u32 b = 0, u32 c = 0, u32 d = 0) { asm volatile("{.reg .pred p; setp.ne.u32 p,%0,0; @p st.shared.v4.u32 [%0],{%1,%2,%3,%4};}" ::"r"(zr), "r"(a), "r"(b), "r"(c), "r"(d) : "memory"); }
DEV void pin2(u32 zr, const void* a, const void* b) { asm volatile("{.reg .pred p; setp.ne.u32 p,%0,0; @p st.shared.v2.u64 [%0],{%1,%2};}" ::"r"(zr), "l"(a), "l"(b) : "memory"); }
DEV const char* rowa(const char* base, u32 key) { const char* r; asm("mad.wide.u32 %0,%1,288,%2;" : "=l"(r) : "r"(~key & 0x1ffc), "l"(base)); return r; }
DEV void str128(void* p, u32 x, u32 y, u32 z, u32 w) { asm volatile("st.relaxed.gpu.global.v4.u32 [%0],{%1,%2,%3,%4};" ::"l"(p), "r"(x), "r"(y), "r"(z), "r"(w) : "memory"); }
DEV void str64(void* p, u32 x, u32 y) { asm volatile("{.reg .u64 d; mov.b64 d,{%1,%2}; st.relaxed.gpu.global.u64 [%0],d;}" ::"l"(p), "r"(x), "r"(y) : "memory"); }
DEV void str32(void* p, u32 x) { asm volatile("st.relaxed.gpu.global.u32 [%0],%1;" ::"l"(p), "r"(x) : "memory"); }
DEV void str16(void* p, u32 x) { asm volatile("st.relaxed.gpu.global.u16 [%0],%1;" ::"l"(p), "h"((unsigned short)x) : "memory"); }
DEV uint4 ldg128(const void* p) { uint4 v; asm volatile("ld.global.nc.v4.u32 {%0,%1,%2,%3},[%4];" : "=r"(v.x), "=r"(v.y), "=r"(v.z), "=r"(v.w) : "l"(p)); return v; }
DEV uint2 ldg64(const void* p) { uint2 v; asm volatile("ld.global.nc.v2.u32 {%0,%1},[%2];" : "=r"(v.x), "=r"(v.y) : "l"(p)); return v; }
DEV u32 ldg32(const void* p) { u32 v; asm volatile("ld.global.nc.u32 %0,[%1];" : "=r"(v) : "l"(p)); return v; }
DEV u32 ldg16(const void* p) { unsigned short v; asm volatile("ld.global.nc.u16 %0,[%1];" : "=h"(v) : "l"(p)); return v; }
#define bsync(id, n) asm volatile("bar.sync %0,%1;" ::"n"(id), "n"(n) : "memory")
#define barrive(id, n) asm volatile("bar.arrive %0,%1;" ::"n"(id), "n"(n) : "memory")
DEV void bsyncr(u32 id) { asm volatile("bar.sync %0,96;" ::"r"(id) : "memory"); }
DEV void barriver(u32 id) { asm volatile("bar.arrive %0,96;" ::"r"(id) : "memory"); }
constexpr u32 BW = 0x0FEA, BS = 0x6532;
DEV void mb_init(u32 a, u32 n) { asm volatile("mbarrier.init.shared.b64 [%0],%1;" ::"r"(a), "r"(n) : "memory"); }
DEV void mb_arrive(u32 a) { asm volatile("mbarrier.arrive.shared.b64 _,[%0];" ::"r"(a) : "memory"); }
DEV void mb_expect(u32 a, u32 bytes) { asm volatile("mbarrier.arrive.expect_tx.shared.b64 _,[%0],%1;" ::"r"(a), "r"(bytes) : "memory"); }
DEV void mb_wait(u32 a, u32 ph = 0) {
  u32 ok; int it = 0;
  do { asm volatile("{.reg .pred p; mbarrier.try_wait.parity.shared.b64 p,[%1],%2; selp.u32 %0,1,0,p;}" : "=r"(ok) : "r"(a), "r"(ph) : "memory"); } while (!ok && ++it < SPIN);
}
template <int N> DEV void bulk_out(void* dst, u32 src) { asm volatile("cp.async.bulk.global.shared::cta.bulk_group [%0],[%1],%2;" ::"l"(dst), "r"(src), "n"(N) : "memory"); }
constexpr u32 WSH = 41472;
DEV void l2_line(const void* p) { asm volatile("prefetch.global.L2 [%0];" ::"l"(p) : "memory"); }
template <int N> DEV void l2_pre(const void* p) { asm volatile("cp.async.bulk.prefetch.L2.global [%0],%1;" ::"l"(p), "n"(N) : "memory"); }
DEV void tma3d(u32 dst, const CUtensorMap* tm, u32 mb, int c0, int c2) {
  asm volatile("cp.async.bulk.tensor.3d.shared::cluster.global.mbarrier::complete_tx::bytes [%0],[%1,{%3,0,%4}],[%2];"
               ::"r"(dst), "l"((uint64_t)tm), "r"(mb), "r"(c0), "r"(c2) : "memory");
}
DEV float blo(u32 w) { return __uint_as_float(w << 16); }
DEV float bhi(u32 w) { return __uint_as_float(w & 0xffff0000u); }
DEV u32 pk_bf(float lo, float hi) { u32 r; asm("cvt.rn.bf16x2.f32 %0,%1,%2;" : "=r"(r) : "f"(hi), "f"(lo)); return r; }
DEV u32 pk_hf(float lo, float hi) { u32 r; asm("cvt.rn.f16x2.f32 %0,%1,%2;" : "=r"(r) : "f"(hi), "f"(lo)); return r; }
DEV float rbf(float x) { return __uint_as_float(pk_bf(0.f, x) & 0xffff0000u); }
DEV u32 bfma(u32 a, u32 b, u32 c) { u32 r; asm("fma.rn.bf16x2 %0,%1,%2,%3;" : "=r"(r) : "r"(a), "r"(b), "r"(c)); return r; }
DEV u32 bmul(u32 a, u32 b) { u32 r; asm("mul.rn.bf16x2 %0,%1,%2;" : "=r"(r) : "r"(a), "r"(b)); return r; }
DEV u32 badd(u32 a, u32 b) { u32 r; asm("add.rn.bf16x2 %0,%1,%2;" : "=r"(r) : "r"(a), "r"(b)); return r; }
DEV u32 hadd(u32 a, u32 b) { u32 r; asm("add.rn.f16x2 %0,%1,%2;" : "=r"(r) : "r"(a), "r"(b)); return r; }
DEV u32 hfma(u32 a, u32 b, u32 c) { u32 r; asm("fma.rn.f16x2 %0,%1,%2,%3;" : "=r"(r) : "r"(a), "r"(b), "r"(c)); return r; }
struct C2 { u32 re, im; };
DEV C2 cm2(C2 a, C2 b) {
  const __half2 ar = *reinterpret_cast<__half2*>(&a.re), ai = *reinterpret_cast<__half2*>(&a.im), br = *reinterpret_cast<__half2*>(&b.re), bi = *reinterpret_cast<__half2*>(&b.im);
  __half2 re = __hfma2(ar, br, __hneg2(__hmul2(ai, bi))), im = __hfma2(ar, bi, __hmul2(ai, br));
  return {*reinterpret_cast<u32*>(&re), *reinterpret_cast<u32*>(&im)};
}
DEV C2 pk2(const float2 (&a)[2]) { return {pk_hf(a[0].x, a[1].x), pk_hf(a[0].y, a[1].y)}; }
DEV C2 pk2c(const float2 (&a)[2]) { return {pk_hf(a[0].x, a[1].x), pk_hf(-a[0].y, -a[1].y)}; }
DEV u32 cpy(u32 x, u32 zr, int alt) {
  u32 r;
  if (alt) asm volatile("xor.b32 %0,%1,%2;" : "=r"(r) : "r"(x), "r"(zr)); else asm volatile("mad.lo.u32 %0,%2,%2,%1;" : "=r"(r) : "r"(x), "r"(zr));
  return r;
}
template <int N> DEV void inc(u32& x) { asm volatile("add.u32 %0,%0,%1;" : "+r"(x) : "n"(N)); }
DEV u32 opq(u32 x) { u32 r; asm volatile("mov.u32 %0,%1;" : "=r"(r) : "r"(x)); return r; }
DEV u32 chan(u32 b, u32 i) { return 16 * (b >> 2) + 2 * (b & 3) + (i & 1) + 4 * (i & 2); }
DEV u32 row16(u32 lane) { const u32 r0 = (lane & 7) + ((lane >> 3) & 1) + 8 * (lane >> 4) - 1; return (r0 ^ ((r0 >> 3) & 3)) * 16; }
DEV u32 clk() { u32 r; asm volatile("mov.u32 %0,%%clock;" : "=r"(r)::"memory"); return r; }
DEV void wait_clk(u32 t, int d) { while ((int)(clk() - t) < d); }
DEV float ex2(float x) { float r; asm("ex2.approx.ftz.f32 %0,%1;" : "=f"(r) : "f"(x)); return r; }
DEV float rcpf(float x) { float r; asm("rcp.approx.ftz.f32 %0,%1;" : "=f"(r) : "f"(x)); return r; }
DEV float2 cmul(float2 a, float2 b) { return make_float2(fmaf(a.x, b.x, -a.y * b.y), fmaf(a.x, b.y, a.y * b.x)); }
DEV float2 csq(float2 a) { return make_float2(fmaf(a.x, a.x, -a.y * a.y), (a.x + a.x) * a.y); }
DEV float2 cexp(float lr2, float th) {
  const float m = ex2(lr2);
  return make_float2(m * __cosf(th), m * __sinf(th));
}
DEV float silu_f(float v) { return v * rcpf(1.f + ex2(-1.4426950408889634f * v)); }
constexpr u32 B2P64 = 0x5F805F80u, B2M64 = 0x1F801F80u, BONE = 0x3F803F80u;
constexpr u32 MODJ = 18 * 128;
DEV float sqrta(float x) { float r; asm("sqrt.approx.ftz.f32 %0,%1;" : "=f"(r) : "f"(x)); return r; }
DEV u32 fu(float x) { return __float_as_uint(x); }
DEV float uf(u32 x) { return __uint_as_float(x); }
DEV void mma_hf_o(float (&d)[4], const float (&c)[4], const u32 (&a)[4], u32 b0, u32 b1) {
  asm("mma.sync.aligned.m16n8k16.row.col.f32.f16.f16.f32 {%0,%1,%2,%3},{%4,%5,%6,%7},{%8,%9},{%10,%11,%12,%13};"
      : "=f"(d[0]), "=f"(d[1]), "=f"(d[2]), "=f"(d[3]) : "r"(a[0]), "r"(a[1]), "r"(a[2]), "r"(a[3]), "r"(b0), "r"(b1), "f"(c[0]), "f"(c[1]), "f"(c[2]), "f"(c[3]));
}

DEV void mma_hf_t(float (&c)[4], const u32 (&a)[4], u32 b0, u32 b1) { mma_hf(c, a[0], a[1], a[2], a[3], b0, b1); }
DEV void cpa16(u32 dst, const void* src) { asm volatile("cp.async.cg.shared.global [%0],[%1],16;" ::"r"(dst), "l"(src) : "memory"); }
DEV void tm_pre(const CUtensorMap* tm) { asm volatile("prefetch.tensormap [%0];" ::"l"((uint64_t)tm) : "memory"); }
#define PROXY_FENCE() asm volatile("fence.proxy.async.shared::cta;" ::: "memory")
struct Prm {
  const char *la, *ai, *cr, *ci, *ldt;
  u32 zero;
  const char *x, *c;
  char* gs;
  const char *dsk, *wr, *wg, *wu, *wd;
  char* out;
};
constexpr float LOG2E = 1.4426950408889634f, F2P64 = 1.8446744073709552e19f, F2M64 = 5.421010862427522e-20f;

template <int S> DEV void y_store(float c0, float c1, float c2, float c3, u32 F, u32 pml, char* yp) {
  str32(yp, bmul(pk_bf(c0, c2), F) | pml);
  str32(yp + S, bmul(pk_bf(c1, c3), F) | pml);
}
DEV u32 sgn2(u32 a, u32 x, u32 y) { return opq(((a - x) >> 31) + ((a - y) >> 31)); }
DEV void merge4(u32 (&h)[8], uint4 a, uint4 b) {
  const u32 e1 = min(a.x, b.x), e2 = max(a.z, b.z), o1 = min(a.y, b.y), o2 = max(a.w, b.w), o0 = max(a.y, b.y), e3 = min(a.z, b.z);
  const u32 f1 = max(e1, e2), f2 = min(e1, e2), p1 = max(o1, o2), p2 = min(o1, o2);
  h[0] = max(a.x, b.x); h[1] = max(o0, f1); h[2] = min(o0, f1); h[3] = max(p1, f2); h[4] = min(p1, f2); h[5] = max(p2, e3); h[6] = min(p2, e3); h[7] = min(a.w, b.w);
}
DEV void top8(u32 (&a)[8], uint4 l, uint4 m) {
  u32 b[8];
  merge4(b, l, m);
#pragma unroll
  for (int i = 0; i < 8; i++) a[i] = max(a[i], b[7 - i]);
#pragma unroll
  for (int s = 4; s; s >>= 1)
#pragma unroll
    for (int i = 0; i < 8; i++) if (!(i & s)) { const u32 x = a[i], y = a[i + s]; a[i] = max(x, y); a[i + s] = min(x, y); }
}
#define POLL(load, cond_bad, code) { int it_ = 0; do { load; } while (__any_sync(~0u, (cond_bad)) & (++it_ <= SPIN)); if (it_ > SPIN) { ERRF(code); } TSN(code, it_); }
DEV u32 tmask(u32 it, u32 m) { u32 r; asm volatile("{.reg .pred p; setp.ne.u32 p,%1,0; selp.u32 %0,%2,0,p;}" : "=r"(r) : "r"(it), "r"(m)); return r; }
#define POLLM(load, bad, M, code) { u32 it_ = SPIN + (tid >> 16), m_; do { m_ = tmask(--it_, M); load; } while (__any_sync(~0u, (bad) & m_)); if (!it_) { ERRF(code); } TSN(code, SPIN - it_); }
#define POLLS(use, load, bad, M, code) { u32 it_ = SPIN + (tid >> 16); for (;;) { const u32 m_ = tmask(--it_, M); use; if (!__any_sync(~0u, (bad) & m_)) break; load; } if (!it_) { ERRF(code); } TSN(code, SPIN - it_); }
#define POLLW(load, cond_bad, code) { int it_ = 0; while (__any_sync(~0u, (cond_bad))) { if (++it_ > SPIN) { ERRF(code); break; } load; } TSN(code, it_); }

#define DOWN(E) if (tid == (b < 108 ? 288 : ~0u)) { const u32 c0 = 64 * (b % 9), c2 = 4 * (b / 9); \
    if (!D0C && E == 1) { mb_expect(SM_MB + 24, 49152); tma3d(SM_TAP, tm_down, SM_MB + 24, c0, c2); } \
    if (DE1 == E) tma3d(SM_WD, tm_down, SM_MB + 24, c0, c2 + 1); \
    if (DE2 == E) tma3d(SM_WD + 12288, tm_down, SM_MB + 24, c0, c2 + 2); \
    if (DE3 == E) tma3d(SM_WD + 24576, tm_down, SM_MB + 24, c0, c2 + 3); }
#define OUTR() { const u32 tl = 4 * ((lane >> 1) & 1) + ((lane >> 2) & 3) + 8 * (lane & 1); \
    bulk_out<1152>(p.out + (16 * b + tl) * 1152, SM_XST + ((lane & 2) + 4 * (lane & 1) + ((lane >> 2) & 1) + (lane & 8)) * ROW); \
    asm volatile("cp.async.bulk.commit_group;" ::: "memory"); }
struct FA { u32 tid, ba, ra, sa; char *ad, *as; };
DEV FA ffn_addr(const Prm& p, u32 tid, u32 b) {
  const u32 w = tid >> 5, lane = tid & 31, kq = w & 3, tg = w >> 2, t = 7 - w;
  FA f = {tid, SM_XS + (lane & 7) * ROW + (18 * kq + (lane >> 3)) * 16, SM_RED + (8 * tg + kq) * 512 + lane * 16, SM_RED + t * 2048 + lane * 16,
          p.gs + (G_ACT + (t < 4 ? 512 * b + 128 * t : (512 + (b >> 1)) * 128) + lane * 4), p.gs + (G_ACT + (b / 9) * 6144 + tid * 16)};
  if (AW & 2) { pin(tid >> 16, f.ba, f.ra, f.sa, tid); pin2(tid >> 16, f.ad, f.as); }
  return f;
}
DEV void ffn_tail(const Prm& p, const CUtensorMap* tm_down, uint4 (&A)[24], const FA f, const u32 b, const u32 par, const u32 okl) {
  const u32 tid = f.tid, w = tid >> 5, lane = tid & 31, g = lane >> 2, q = lane & 3, tg = w >> 2, zr = tid >> 16;
  const u32 rho = b & 1, pm = par ? TAGM : 0, kt = par * 3, ba = f.ba, ra = f.ra;
  char* const gs = p.gs;
  char *const ad = f.ad, *const as = f.as;
  __syncthreads();
  TS(25);
  if (!(AW & 4)) DOWN(5);
  {
    float c0[2][4] = {}, c1[2][4] = {};
    uint4 bb[5];
#pragma unroll
    for (int s = 0; s < 5; s++) bb[s] = ldsm4(ba + s * 64);
    if (AW & 4) DOWN(5);
#pragma unroll
    for (int s = 0; s < 9; s++) mma_bf(c0[s & 1], A[s].x, A[s].y, A[s].z, A[s].w, s & 1 ? bb[s >> 1].z : bb[s >> 1].x, s & 1 ? bb[s >> 1].w : bb[s >> 1].y);
    if (tg < 2) {
#pragma unroll
      for (int s = 0; s < 9; s++) mma_bf(c1[s & 1], A[9 + s].x, A[9 + s].y, A[9 + s].z, A[9 + s].w, s & 1 ? bb[s >> 1].z : bb[s >> 1].x, s & 1 ? bb[s >> 1].w : bb[s >> 1].y);
      sts128(ra + 2048, fu(c1[0][0] + c1[1][0]), fu(c1[0][1] + c1[1][1]), fu(c1[0][2] + c1[1][2]), fu(c1[0][3] + c1[1][3]));
    }
    sts128(ra, fu(c0[0][0] + c0[1][0]), fu(c0[0][1] + c0[1][1]), fu(c0[0][2] + c0[1][2]), fu(c0[0][3] + c0[1][3]));
  }
  TS(39);
  __syncthreads();
  const u32 tr = clk();
  if (OUTB == 6 && w == 10 && okl < lds32(SM_SLOT + 28)) OUTR();
  if (w - 3 - rho < 5 - rho) {
    float s[4];
    const uint4 u0 = lds128(f.sa), u1 = lds128(f.sa + 512), u2 = lds128(f.sa + 1024), u3 = lds128(f.sa + 1536);
    s[0] = (uf(u0.x) + uf(u1.x)) + (uf(u2.x) + uf(u3.x)); s[1] = (uf(u0.y) + uf(u1.y)) + (uf(u2.y) + uf(u3.y));
    s[2] = (uf(u0.z) + uf(u1.z)) + (uf(u2.z) + uf(u3.z)); s[3] = (uf(u0.w) + uf(u1.w)) + (uf(u2.w) + uf(u3.w));
    const u32 sg = pk_bf(silu_f(rbf(s[0])), silu_f(rbf(s[1])));
    const u32 act = movm(bmul(bmul(sg, pk_bf(s[2], s[3])), B2M64));
    str32(ad, act | (q ? 0 : pm));
  }
  TS(26);
  const bool fin = w == (b < 72 ? 8 : ~0u);
  u32 kg;
  uint4 xt;
  const char* xs;
  if (fin) { kg = lds32(SM_SLOT + 4 * g); xs = rowa(gs + (G_Y + 16 * b), kg); xt = ldr128(xs); }
  if (b < 108) {
    uint4 a;
    if (AD) a.x = INVAL; else a = ldr128(as);
    if (AD && w >= 4) wait_clk(tr, AD);
    char* const dst = gs + ((G_PART + b * 2048) + (w * 512 + lane * 8));
    if (w < 4) {
      const u32 aa = SM_WD + (8 * (lane >> 4) + (lane & 7)) * 128 + (((2 * w + ((lane >> 3) & 1)) ^ (lane & 7)) << 4);
      mb_wait(SM_MB + 24);
#pragma unroll
      for (int s = 0; s < 24; s++) A[s] = ldsm4t(aa + (s < 6 ? SM_TAP - SM_WD : -12288) + s * 2048);
      if (AW & 2) pin2(zr, dst, as);
    }
    conv();
    TS(28);
    POLLW(rld128<TAGM>(a, as, pm), (a.x ^ pm) & TAGM, 9);
    sts128(SM_AC + tid * 16, a.x, a.y, a.z, a.w); sts32(SM_AC + tid * 16, a.x & ~TAGM);
    TS(27);
    if (w < 4) {
      bsync(8, 384);
      float c[4][4] = {};
#pragma unroll
      for (int s = 0; s < 12; s++) {
        const uint4 bb = ldsm4(SM_AC + lane * 16 + s * 512);
        mma_bf(c[2 * (s & 1)], A[2 * s].x, A[2 * s].y, A[2 * s].z, A[2 * s].w, bb.x, bb.y);
        mma_bf(c[2 * (s & 1) + 1], A[2 * s + 1].x, A[2 * s + 1].y, A[2 * s + 1].z, A[2 * s + 1].w, bb.z, bb.w);
      }
      u32 o[4];
#pragma unroll
      for (int i = 0; i < 4; i++) o[i] = fu(((c[0][i] + c[1][i]) + (c[2][i] + c[3][i])) * F2P64);
      str64(dst, (o[0] & ~3u) | kt, o[1]); str64(dst + 256, (o[2] & ~3u) | kt, o[3]);
      TS(29);
    } else barrive(8, 384);
  }
  if (OUTB == 7 && w == 10 && okl < lds32(SM_SLOT + 28)) OUTR();
  if (fin) {
    const u32 ta = clk();
    const char* src = gs + (G_PART + (b >> 3) * 2048 + (b & 7) * 256 + lane * 8);
    const u32 gw = lds32(SM_MODS + 5760 + 16 * b + 4 * q);
    const u32 hw = lds32(SM_XS + g * ROW + b * 16 + q * 4);
    const float sgm = rcpf(1.f + ex2(-LOG2E * bhi(kg ^ (~((int)kg >> 31) | 0x80000000))));
    char* const dst = (char*)rowa(p.out + (16 * b + 4 * q), kg);
    conv();
    POLLW(rld128<TAGM>(xt, xs, TAGR), (xt.x ^ TAGR) & TAGM, 10);
    const u32 x1w = (q & 2) ? ((q & 1) ? xt.w : xt.z) : ((q & 1) ? xt.y : bmul(xt.x ^ TAGR, B2P64));
    const u32 sg2 = pk_bf(sgm, sgm);
    pin(zr, x1w, gw, hw, sg2); pin2(zr, dst, src);
    uint64_t v[12];
#pragma unroll
    for (int j = 0; j < 12; j++) v[j] = 1;
    float s0, s1;
    if (PD) wait_clk(ta, PD);
    conv();
    TS(13);
#define VL(j) (u32)v[j]
#define VS(j, s) ((uf((u32)(v[j] >> s)) + uf((u32)(v[j + 1] >> s))) + (uf((u32)(v[j + 2] >> s)) + uf((u32)(v[j + 3] >> s))))
    u32 res;
    POLLM({ _Pragma("unroll") for (int j = 0; j < 12; j++) rld64<3>(v[j], src + j * 9 * 2048, kt);
            s0 = VS(0, 0) + VS(4, 0) + VS(8, 0); s1 = VS(0, 32) + VS(4, 32) + VS(8, 32);
            res = opq(badd(x1w, bmul(gw, badd(hw, bmul(movm(pk_bf(s0, s1)), sg2))))); TSRND(); },
          lop3<0xfe>(ne3(VL(0), VL(1), kt), ne3(VL(2), VL(3), kt), ne3(VL(4), VL(5), kt)) |
          lop3<0xfe>(ne3(VL(6), VL(7), kt), ne3(VL(8), VL(9), kt), ne3(VL(10), VL(11), kt)), 3, 11);
    asm volatile("st.global.u32 [%0],%1;" ::"l"(dst), "r"(res) : "memory");
    if (b == 0 && lane == 0) str32(gs + G_EP, par);
    TS(30); TSE();
  }
  if (w == 10) asm volatile("cp.async.bulk.wait_group.read 0;" ::: "memory");
}

DEV u32 y_off(u32 tid, u32 b) { return G_Y + (16 * (tid >> 5) + 8 * ((tid >> 1) & 1) + ((tid >> 2) & 4)) * BLK + b * 128 + ((tid >> 2) & 3) * 32 + (tid & 1) * 16; }
DEV void post_conv(const Prm& p, const CUtensorMap* tm_down, const u32 tid, const u32 b, const u32 b3) {
  const u32 w = tid >> 5, lane = tid & 31;
  const u32 g = lane >> 2, q = lane & 3, e = g >> 2, h = (g >> 1) & 1, hi = g & 1;
  const u32 pm = lds32(SM_THR + 4), par = pm >> 30;
  char* const gs = p.gs;
  const u32 cho = 128 * w + 64 * e + 16 * q;
  u32 x1[4][4], h2[4][4], key[4], lt;
  char* const rowp = gs + (b * BLK + (4 * h + 8 * hi) * 1152 + cho);
  u32 okl = ~0u;
  FA fa;
  uint4 A[24];
#define AROW(t) const u32 arow = 144 * ((t >> 5) & 3) + ((t >> 1) & 8) + (t & 7), ab = (t & 8) ? SM_UP : SM_GATE;
#define AFRAG9() { _Pragma("unroll") for (int s = 0; s < 9; s++) A[s] = ldsm4t(ab + SLV + arow * 16 + s * 256); }
#define AFRAG18() { const u32 t3 = opq(tid); AROW(t3); if (t3 < 256) { const u32 aa = ab + arow * 64 + ((((t3 >> 6) & 2) ^ ((t3 & 7) >> 1)) << 4); \
      _Pragma("unroll") for (int s = 0; s < 9; s++) { A[s] = ldsm4t(aa + s * 1024); A[9 + s] = ldsm4t((aa ^ 16) + s * 1024); } } else AFRAG9(); }
  if (w < 9) {
    const u32 yc = 8 * (q >> 1) + 2 * (g >> 1), y1 = w < 8 ? BLK : YS ? 512 : 4 * BLK, y2 = 2 * y1;
    const char* ysrc = gs + (w < 8 ? y_off(tid, b) : YS ? G_Y + 16384 + b * BLK + (q >> 1) * 256 + g * 32 + (q & 1) * 16 : G_Y + (q & 1) * 16 + (8 * yc + 2 * hi + ((b >> 4) & 1)) * BLK + 16384 + ((b >> 5) * 16 + (b & 15)) * 32);
    const char* const ys[4] = {ysrc, ysrc + y1, ysrc + y2, ysrc + (y1 + y2)};
    uint4 yv[4];
#pragma unroll
    for (int v = 0; v < 4; v++) yv[v].x = INVAL;
    const u32 tg0 = b < (w < 4 ? YL : w < 8 ? YE : Y8) ? pm : INVAL;
    if (w >= 4) { pin2(tid >> 16, ys[0], ys[1]); pin2(tid >> 16, ys[2], ys[3]); bsync(12, N12); TS(18); }
#pragma unroll
    for (int v = 0; v < 4; v++) rld128<TAGM>(yv[v], ys[v], tg0);
    const u32 tc = clk();
    const u32 ma = SM_MODS + cho, xa = SM_XST + (2 * h + 4 * hi) * ROW + cho;
    const uint4 sa = lds128(ma), ca = lds128(ma + 1152), ga = lds128(ma + 2304);
    const uint4 rb = lds128((g & 2) ? SM_ONE + 16 * hi : (ma ^ 64) + 8064 + 1152 * hi);
    const u32 saw[4] = {sa.x, sa.y, sa.z, sa.w}, caw[4] = {ca.x, ca.y, ca.z, ca.w}, gaw[4] = {ga.x, ga.y, ga.z, ga.w};
#pragma unroll
    for (int k = 0; k < 4; k++) {
      const uint2 st = lds64(SM_ST + 16 * (2 * h + 4 * hi + (k & 1) + 8 * (k >> 1)));
      const uint4 xv = lds128(xa + ((k & 1) + 8 * (k >> 1)) * ROW);
      x1[k][0] = xv.x; x1[k][1] = xv.y; x1[k][2] = xv.z; x1[k][3] = xv.w;
#pragma unroll
      for (int v = 0; v < 4; v++) x1[k][v] = badd(x1[k][v], bfma(bmul(badd(x1[k][v], st.x), st.y), caw[v], saw[v]));
    }
    const bool own = (q >> 1) == e;
    const u32 spw = SM_SP + (2 * w + e) * 320 + (g & 3) * 16 + (own ? ((q & 1) == h ? 4 : 12) : 8 - 8 * (q & 1));
    if (SMD && w < 4) asm volatile("setmaxnreg.dec.sync.aligned.u32 168;");
    if (b >= YL) wait_clk(tc, YD);
    conv();
    TS(13);
    POLLW(_Pragma("unroll") for (int v = 0; v < 4; v++) rld128<TAGM>(yv[v], ys[v], pm), lop3<0xa8>(ne3(yv[0].x, yv[1].x, pm), ne3(yv[2].x, yv[3].x, pm), TAGM), 5);
    TS(19);
    if (!SMD && w < 4) asm volatile("setmaxnreg.dec.sync.aligned.u32 168;");
#pragma unroll
    for (int k = 0; k < 4; k += 2) {
      float X[4] = {}, Y[4] = {}, R[4] = {};
#pragma unroll
      for (int v = 0; v < 4; v++) {
        const u32 y0 = k ? yv[v].z : yv[v].x & ~TAGM, y1 = k ? yv[v].w : yv[v].y;
        x1[k][v] = bfma(movm(y0), gaw[v], x1[k][v]);
        x1[k + 1][v] = bfma(movm(y1), gaw[v], x1[k + 1][v]);
        mma8_bf(X, x1[k][v], x1[k + 1][v], x1[k][v]); mma8_bf(Y, x1[k][v], x1[k + 1][v], x1[k + 1][v]);
        if (v & 1) mma_bf(R, x1[k][v - 1], x1[k + 1][v - 1], x1[k][v], x1[k + 1][v], v & 2 ? rb.z : rb.x, v & 2 ? rb.w : rb.y);
      }
      sts32(spw + k * 64, fu(own ? (hi ? X[1] : X[0]) : R[0] + R[1]));
      sts32(spw + k * 64 + 64, fu(own ? (hi ? Y[3] : Y[2]) : R[2] + R[3]));
    }
    barrive(1, N1);
    TS(36);
    if (AFP) { asm volatile("setmaxnreg.inc.sync.aligned.u32 168;"); mb_wait(SM_MB + 8); mb_wait(SM_MB + 16); }
    const uint4 sb = lds128(ma + 3456), cb = lds128(ma + 4608), gb = lds128(ma + 5760);
    const u32 sbw[4] = {sb.x, sb.y, sb.z, sb.w}, cbw[4] = {cb.x, cb.y, cb.z, cb.w}, gbw[4] = {gb.x, gb.y, gb.z, gb.w};
    const u32 t3 = opq(tid), zr = t3 >> 16;
    AROW(t3);
    const u32 aa = ab + arow * 64 + ((((t3 >> 6) & 2) ^ ((t3 & 7) >> 1)) << 4), sta = SM_ST2 + 16 * (g & 3);
    if (AFP) pin(zr, aa, sta, xa);
    bsync(2, 320);
    TS(37);
    uint4 st[4];
#pragma unroll
    for (int k = 0; k < 4; k++) st[k] = lds128(sta + 64 * k);
    lt = lds32(SM_THR);
#define AFL() { _Pragma("unroll") for (int s = 0; s < 9; s++) { A[s] = ldsm4t(aa + s * 1024); A[9 + s] = ldsm4t((aa ^ 16) + s * 1024); } }
    if (AFP && (AFM >> w & 1)) { if (w < 8) AFL() else AFRAG9(); }
#pragma unroll
    for (int k = 0; k < 4; k++) {
      key[k] = st[k].w;
      u32 o[4];
#pragma unroll
      for (int v = 0; v < 4; v++) {
        const u32 d = badd(x1[k][v], st[k].x), z = bfma(d, st[k].y, bmul(d, st[k].z));
        h2[k][v] = FH ? bfma(z, cbw[v], sbw[v]) : badd(bmul(z, cbw[v]), sbw[v]);
        o[v] = FO ? bfma(gbw[v], h2[k][v], x1[k][v]) : badd(x1[k][v], bmul(gbw[v], h2[k][v]));
      }
      h2[k][0] = bmul(h2[k][0], B2M64) | TAGR; x1[k][0] = bmul(x1[k][0], B2M64) | TAGR;
      if (key[k] >= lt) str128(rowp + k * 1152, h2[k][0], h2[k][1], h2[k][2], h2[k][3]);
      sts128(xa + ((k & 1) + 8 * (k >> 1)) * ROW, o[0], o[1], o[2], o[3]);
    }
    barrive(3, 320);
    TS(21);
    if (!AFP) { asm volatile("setmaxnreg.inc.sync.aligned.u32 168;"); mb_wait(SM_MB + 8); mb_wait(SM_MB + 16); AFRAG18(); }
    else if (!(AFM >> w & 1)) { if (w < 8) AFL() else AFRAG9(); }
    TS(22);
    const u32 rr = tid * 57 >> 12, rc = tid * 16 - rr * 1152, sl = SM_SLOT + 8 * rr;
    const char* const rb_ = gs + rc;
    const u32 km = max(max(key[0], key[1]), max(key[2], key[3])), xd = SM_XS + rr * (2 * ROW) + rc;
    if (RW & 2) { pin(tid >> 16, sl, km, xd); pin2(tid >> 16, rb_, rowp); }
    fa = ffn_addr(p, tid | p.zero, b);
    bsync(6, 320);
    TS(24);
    const uint2 sk = lds64(sl);
    const char *r0 = rowa(rb_, sk.x), *r1 = rowa(rb_, sk.y);
    uint4 rv[2] = {ldr128(r0), ldr128(r1)};
    barrive(15, 320);
    const u32 g8 = lds32(SM_SLOT + 28);
    if (__any_sync(~0u, km >= g8 && lt > g8)) {
#pragma unroll
      for (int k = 0; k < 4; k++) if (key[k] >= g8 && key[k] < lt) str128(rowp + k * 1152, h2[k][0], h2[k][1], h2[k][2], h2[k][3]);
    }
    bsync(5, 320);
    const uint2 sf = lds64(sl);
    const u32 f8 = lds32(SM_SLOT + 28);
    if (__any_sync(~0u, km >= f8)) {
#pragma unroll
      for (int k = 0; k < 4; k++) if (key[k] >= f8) str128(rowp + (G_Y + k * 1152), x1[k][0], x1[k][1], x1[k][2], x1[k][3]);
    }
    if (__any_sync(~0u, sf.x != sk.x || sf.y != sk.y)) {
      r0 = rowa(rb_, sf.x); r1 = rowa(rb_, sf.y);
      rv[0].x = rv[1].x = INVAL;
    }
    POLLW({ rld128<TAGM>(rv[0], r0, TAGR); rld128<TAGM>(rv[1], r1, TAGR); }, ne3(rv[0].x, rv[1].x, TAGR) & TAGM, 8);
    TS(38);
#pragma unroll
    for (int j = 0; j < 2; j++) sts128(xd + j * ROW, bmul(rv[j].x ^ TAGR, B2P64), rv[j].y, rv[j].z, rv[j].w);
  } else {
    u32 ok, lr;
    if (w == 10) {
      uint2 rc = lds64(SM_RC + 8 * min(lane, 17u));
      float r1 = lane < 18 ? uf(rc.x) : 0.f, r2 = lane < 18 ? uf(rc.y) : 0.f;
#pragma unroll 1
      for (int o = 16; o; o >>= 1) { r1 += __shfl_xor_sync(~0u, r1, o); r2 += __shfl_xor_sync(~0u, r2, o); }
      const u32 tl = 4 * ((lane >> 1) & 1) + ((lane >> 2) & 3) + 8 * (lane & 1), kl = (2047 - 16 * b - tl) << 2 | par * 3;
      char* const kp = gs + (G_KEY + b * KST + (tid >> 16));
      const u32 spr = SM_SP + (lane >> 4) * 9 * 320 + (lane & 15) * 16;
      TS(31);
      r2 += 0.f;
      const u32 nth = b < NB8 ? 7 : NEARLY - 1, ka = SM_KEY + 4 * (lane & 15), kb = SM_KEY + 2 * (lane & 16), lim = lane < 16 ? 8 : 0;
      pin(tid >> 16, kl, ka, kb, lim); pin2(tid >> 16, kp, kp);
      conv();
      bsync(1, N1);
      uint4 t = lds128(spr);
      float S1 = uf(t.x), S2 = uf(t.y), S3 = uf(t.z);
#pragma unroll
      for (int i = 1; i < 9; i++) { t = lds128(spr + i * 320); S1 += uf(t.x); S2 += uf(t.y); S3 += uf(t.z); }
      S1 += __shfl_xor_sync(~0u, S1, 16); S2 += __shfl_xor_sync(~0u, S2, 16); S3 += __shfl_xor_sync(~0u, S3, 16);
      const float mu = S1 * (1.f / 576.f), var = fmaxf(fmaf(-mu, mu, S2 * (1.f / 576.f)), 0.f);
      const float m = rbf(mu), rs = rcpf(rbf(sqrta(rbf(rbf(var) + 1e-5f))));
      const u32 rb = pk_bf(0.f, fmaf(fmaf(-m, r1, S3), rs, r2));
      ok = ((rb ^ (((int)rb >> 31) | 0x80000000)) & 0xffff0000u) | kl;
      const float rh = rbf(rs);
      const u32 oh = ok >> 1;
      sts32(ka, oh);
      __syncwarp();
      const uint4 o0 = lds128(kb), o1 = lds128(kb + 16);
      sts128(SM_ST2 + 16 * (lane & 15), pk_bf(-m, -m), pk_bf(rh, rh), pk_bf(rs - rh, rs - rh), ok);
      lr = opq(sgn2(oh, o0.x, o0.y) + sgn2(oh, o0.z, o0.w)) +
           opq(sgn2(oh, o1.x, o1.y) + sgn2(oh, o1.z, o1.w));
      lr += __shfl_xor_sync(~0u, lr, 16);
      asm volatile("{.reg .pred p; .reg .u64 a; setp.lt.u32 p,%0,%1; mad.wide.u32 a,%0,4,%2; @p st.relaxed.gpu.global.u32 [a],%3;}" ::"r"(lr), "r"(lim), "l"(kp), "r"(ok) : "memory");
      if (lr == nth) sts32(SM_THR, ok);
      barrive(2, 320);
      barrive(13, 64);
      TS(20);
    } else if (w == 9) {
      if (DB1) bsync(1, N1); else { bsync(12, N12); wait_clk(clk(), DD); }
      PROXY_FENCE();
      DOWN(1);
    } else {
      const char* ks = gs + (G_KEY + (lane >> 1) * KST + (lane & 1) * 16);
      const u32 kt = par * 3;
      uint4 L[8];
      u32 H[8];
#define KBAD(j) ((L[j].x ^ kt) & 3)
#define KLD(j) L[j] = ldr128(ks + j * 16 * KST)
#pragma unroll
      for (int j = 0; j < 8; j++) L[j].x = INVAL;
      bsync(13, 64);
      wait_clk(clk(), b < KE ? KD : b < KF ? KDB : b < YL ? KDC : KD1);
      TS(34);
      POLL({ _Pragma("unroll") for (int j = 0; j < 8; j++) if (KBAD(j)) KLD(j);
             merge4(H, L[0], L[1]); top8(H, L[2], L[3]);
             asm volatile("" : "+r"(H[0]), "+r"(H[1]), "+r"(H[2]), "+r"(H[3]), "+r"(H[4]), "+r"(H[5]), "+r"(H[6]), "+r"(H[7])); TS(32); },
           KBAD(0) | KBAD(1) | KBAD(2) | KBAD(3) | KBAD(4) | KBAD(5), 6);
      top8(H, L[4], L[5]);
      TS(35);
#pragma unroll 1
      for (u32 pass = p.zero;; pass++) {
        u32 G[8], m[8];
        conv();
#pragma unroll
        for (int i = 0; i < 8; i++) G[i] = H[i];
#pragma unroll
        for (int r = 0; r < 8; r++) {
          const u32 h0 = G[0];
          m[r] = __reduce_max_sync(~0u, h0);
          if (r == 0) { if (KBAD(6)) KLD(6); if (KBAD(7)) KLD(7); }
          if (r < 7) asm("{.reg .u32 t; sub.u32 t,%1,%2; min.u32 t,t,1; mad.lo.u32 %0,t,%3,%4;}" : "=r"(G[0]) : "r"(m[r]), "r"(h0), "r"(h0 - G[1]), "r"(G[1]));
#pragma unroll
          for (int i = 1; i < 7 - r; i++) G[i] = h0 == m[r] ? G[i + 1] : G[i];
          if ((r & 3) == 3) sts128(SM_SLOT + 4 * r - 12, m[r - 3], m[r - 2], m[r - 1], m[r]);
        }
        asm volatile("{.reg .pred p; setp.eq.u32 p,%0,0; @p bar.arrive 6,320;}" ::"r"(pass) : "memory");
        if (pass) break;
        TS(23);
        conv();
        POLLW({ if (KBAD(6)) KLD(6); if (KBAD(7)) KLD(7); }, KBAD(6) | KBAD(7), 7);
        if (!__any_sync(~0u, max(L[6].x, L[7].x) > m[7])) break;
        top8(H, L[6], L[7]);
      }
      barrive(5, 320);
      TS(33);
    }
    asm volatile("setmaxnreg.inc.sync.aligned.u32 168;");
    mb_wait(SM_MB + 8); mb_wait(SM_MB + 16);
    AROW(tid);
    AFRAG9();
    fa = ffn_addr(p, tid | p.zero, b);
    TS(22);
    if (w == 10) {
      bsync(3, 320);
      PROXY_FENCE();
      if (lane < 16 && lr >= 8) OUTR();
      if (lane < 16 && lr < 8) okl = ok;
    } else if (w == 9) {
      bsync(15, 320);
      DOWN(4);
      TS(13);
    }
  }
  ffn_tail(p, tm_down, A, fa, b3, par, okl);
}

__global__ void __launch_bounds__(384, 1)
fused_kernel(const Prm p, const __grid_constant__ CUtensorMap tm_mod, const __grid_constant__ CUtensorMap tm_gate, const __grid_constant__ CUtensorMap tm_gs,
             const __grid_constant__ CUtensorMap tm_up, const __grid_constant__ CUtensorMap tm_us, const __grid_constant__ CUtensorMap tm_down) {
  extern __shared__ __align__(1024) unsigned char smem[];
  u32 la, ai, ldt; uint2 cr, ci;
  {
    const u32 t = threadIdx.x, d = t < 256 ? chan(blockIdx.x, t >> 5) : 512 + (blockIdx.x >> 1), o = d * 256 + 8 * (t & 31), o4 = o + ((t < 256 ? t >> 5 : t >> 3) & 4);
    asm volatile("{.reg .pred p; .reg .u16 h; setp.ne.u32 p,%7,0; @p ld.global.nc.u32 %0,[%8]; @p ld.global.nc.u32 %1,[%9]; @p ld.global.nc.v2.u32 {%2,%3},[%10];"
                 "@p ld.global.nc.v2.u32 {%4,%5},[%11]; @p ld.global.nc.u16 h,[%12]; cvt.u32.u16 %6,h;}"
                 : "=r"(la), "=r"(ai), "=r"(cr.x), "=r"(cr.y), "=r"(ci.x), "=r"(ci.y), "=r"(ldt)
                 : "r"(0x6ffu >> (t >> 5) & 1), "l"(p.la + o4), "l"(p.ai + o4), "l"(p.cr + o), "l"(p.ci + o), "l"(p.ldt + 2 * d));
  }
  const u32 t0 = clk();
  const u32 tid = __shfl_sync(~0u, threadIdx.x, threadIdx.x & 31), b = blockIdx.x + p.zero;
  const u32 w = tid >> 5, lane = tid & 31;
  const u32 g = lane >> 2, q = lane & 3, hi = g & 1;
  const u32 rho = b & 1, Ps = 512 + (b >> 1);
  char* const gs = p.gs;
  TS0();
  const bool kw = w != 8 && w != 11;
  const u32 ksig = w < 8 ? (w & 3) : 4, khf = w < 8 ? (w >> 2) : (w & 1);
  if (!kw) {
    if (tid == 352) {
#pragma unroll
      for (int i = 0; i < 5; i++) mb_init(SM_MB + 8 * i, i < 4 ? 1 : 64);
      asm volatile("fence.mbarrier_init.release.cluster;" ::: "memory");
      tm_pre(&tm_mod);
    }
    const char* cp = p.c + (576 * (w & 1) + 24 * min(lane, 23u));
    const uint2 c0 = ldg64(cp);
    la = c0.x; ai = c0.y; cr = ldg64(cp + 8); ci = ldg64(cp + 16);
  }
  u32 b3;
  asm volatile("xor.b32 %0,%1,%2;" : "=r"(b3) : "r"(blockIdx.x), "r"(p.zero));
  const u32 zr = tid >> 16;
  const u32 epv = ldr32(gs + (G_EP + zr));
  const u32 tp = SM_TAP + ksig * TAPS;
  if (kw && !khf) {
#pragma unroll 1
    for (u32 i = lane * 16; i < TAPS; i += 512) sts128(tp + i, 0, 0, 0, 0);
  }
  if (tid < 128) sts128(SM_INV + 16 * tid, INVAL, 0, 1, 0);
  if (tid >= (YS == 2 ? 124 : 252)) str128(gs + (tid >= 380 ? G_MOD + b * 128 + q * 16 : b * BLK + 16384 - 252 * 16 + tid * 16 + (tid < 252 ? G_Y + 2048 : 0)), INVAL, 0, 1, 0);
  if (tid == (b < 36 ? 352 : ~0u)) { while (clk() - t0 < DMOD); mb_expect(SM_MB, 36864); tma3d(SM_UP, &tm_mod, SM_MB, 32 * b, 0); }
  if (w < 9) {
    while ((int)(clk() - t0) < DX);
    const char* xp = p.x + (b * BLK + (lane >> 3) * 1152 + 128 * w + 16 * (lane & 7));
    const u32 xd = SM_XST + (((lane >> 3) & 1) + 8 * (lane >> 4)) * ROW + 128 * w + 16 * (lane & 7);
#pragma unroll
    for (int i = 0; i < 4; i++) cpa16(xd + 2 * ROW * i, xp + 4608 * i);
  }
  const u32 ktab = w < 8 ? SM_MODS + w * KTAB : SM_ZS + (w - 9) * KTAB;
  float k2048 = 0.f;
  if (kw) {
    u32 mx = __vmaxu2(__vmaxu2(cr.x & 0x7fff7fff, cr.y & 0x7fff7fff), __vmaxu2(ci.x & 0x7fff7fff, ci.y & 0x7fff7fff));
    const u32 E = max(__reduce_max_sync(~0u, max(mx & 0xffff, mx >> 16)) >> 7, 8u);
    TS(1);
    const float dt = rbf(ex2(blo(ldt) * LOG2E)), csc = uf((257 - E) << 23 | (fu(dt) & 0x7fffff));
    sts32(SM_SC + 16 * ksig + 12, fu(uf(fu(dt) & 0x7f800000) * uf((E - 2) << 23)));
    const u32 crw = khf ? cr.y : cr.x, ciw = khf ? ci.y : ci.x;
    float2 C[2], w4[2], w8[2], w16[2], w32[2], w64[2], w128[2], w256[2], w512[2], a1[2], a2[2], a3[2], t0[2], t1[2], s3[2];
#pragma unroll
    for (int m = 0; m < 2; m++) {
      const float lr2 = rbf(ex2((m ? bhi(la) : blo(la)) * LOG2E)) * dt * -LOG2E, th = (m ? bhi(ai) : blo(ai)) * dt;
      C[m] = make_float2((m ? bhi(crw) : blo(crw)) * csc, (m ? bhi(ciw) : blo(ciw)) * csc);
      const float2 w1 = cexp(lr2, th), w2 = csq(w1);
      w64[m] = cexp(64.f * lr2, 64.f * th);
      w4[m] = csq(w2); w8[m] = csq(w4[m]); w16[m] = csq(w8[m]); w32[m] = csq(w16[m]);
      w128[m] = csq(w64[m]); w256[m] = csq(w128[m]); w512[m] = csq(w256[m]);
      const float2 w1024 = csq(w512[m]);
      a1[m] = cmul(C[m], w1); a2[m] = cmul(C[m], w2); a3[m] = cmul(a1[m], w2);
      t0[m] = cmul(C[m], w1024); t1[m] = cmul(t0[m], w128[m]); s3[m] = cmul(w8[m], w16[m]);
      k2048 += fmaf(t0[m].x, w1024.x, -t0[m].y * w1024.y);
    }
    C2 B0[8], B1[8], B2[8], S[8];
    B0[0] = pk2(C); B0[1] = pk2(a1); B0[2] = pk2(a2); B0[3] = pk2(a3);
    const C2 h4 = pk2(w4), h256 = pk2(w256), h512 = pk2(w512);
#pragma unroll
    for (int i = 0; i < 4; i++) B0[4 + i] = cm2(B0[i], h4);
#pragma unroll
    for (int i = 0; i < 4; i++) B1[i] = cm2(B0[2 * i], h256);
    B1[4] = cm2(B0[0], h512); B1[5] = cm2(B0[4], h512);
    B1[6] = cm2(B1[4], h256); B1[7] = cm2(B1[5], h256);
    const u32 ta = ktab + lane * 128, f = ((lane & 3) << 5) | ((lane & 4) << 2);
#pragma unroll
    for (int i = 0; i < 8; i++) sts128(ta + ((i << 4) ^ f), B0[i].re, B0[i].im, B1[i].re, B1[i].im);
    B2[0] = pk2(t0); B2[1] = pk2(t1);
    B2[2] = cm2(B2[0], h256); B2[3] = cm2(B2[1], h256);
#pragma unroll
    for (int i = 0; i < 4; i++) B2[4 + i] = cm2(B2[i], h512);
    S[0] = {0x3C003C00u, 0u}; S[1] = pk2c(w8); S[2] = pk2c(w16); S[3] = pk2c(s3); S[4] = pk2c(w32);
#pragma unroll
    for (int i = 1; i < 4; i++) S[4 + i] = cm2(S[i], S[4]);
#pragma unroll
    for (int i = 0; i < 8; i++) sts128(ta + 4096 + ((i << 4) ^ f), B2[i].re, B2[i].im, S[i].re, S[i].im);
    const C2 m64 = pk2c(w64), m128 = pk2c(w128);
    sts128(ktab + 8192 + lane * 16, m64.re, m64.im, m128.re, m128.im);
    __syncwarp();
  } else {
    u32 sa = SM_SIL + 576 * (w & 1) + 24 * min(lane, 23u);
#pragma unroll 1
    for (int j = 0; j < 6; j++) {
      sts32(sa, pk_bf(silu_f(blo(la)), silu_f(bhi(la))));
      la = ai; ai = cr.x; cr.x = cr.y; cr.y = ci.x; ci.x = ci.y; sa += 4;
    }
    bsync(7, 64);
  }
  TS(2);
  const u32 pm = (__reduce_or_sync(~0u, epv) & 1) ? 0 : TAGM;
  sts32(SM_THR + 4, pm);
  if (w < 9) {
    asm volatile("cp.async.wait_all;" ::: "memory");
    __syncwarp();
    TS(4);
    if (tid == (b - 36 < 72 ? 256 : ~0u)) { mb_expect(SM_MB, 36864); tma3d(SM_UP, &tm_mod, SM_MB, 32 * b, 0); }
    const u32 xa = SM_XST + (lane & 15) * ROW + 128 * w + 16 * (lane >> 4);
    float s[4] = {}, X[2][4] = {}, Y[2][4] = {};
#pragma unroll
    for (int j = 0; j < 4; j++) {
      const uint4 a = ldsm4(xa + 32 * j);
      mma8_bf(X[0], a.x, a.y, a.x); mma8_bf(Y[0], a.x, a.y, a.y);
      mma8_bf(X[1], a.z, a.w, a.z); mma8_bf(Y[1], a.z, a.w, a.w);
      mma_bf(s, a.x, a.y, a.z, a.w, BONE, BONE);
    }
    uint4 t[4];
#pragma unroll
    for (int j = 0; j < 4; j++) t[j] = ldsm4t(xa + 32 * j);
    const float u0 = hi ? X[0][1] + X[1][1] : X[0][0] + X[1][0], u1 = hi ? Y[0][3] + Y[1][3] : Y[0][2] + Y[1][2];
    if (q == g >> 1) sts128(SM_SP + w * 128 + g * 16, fu(s[0]), fu(u0), fu(s[2]), fu(u1));
    bsync(1, 288);
    TS(7);
    const u32 spr = SM_SP + (lane & 7) * 16 + (lane & 8);
    const uint2 t8 = lds64(spr + 1024);
    const float f8 = lane < 16 ? 1.f : 0.f;
    float S1 = uf(t8.x) * f8, S2 = uf(t8.y) * f8;
#pragma unroll
    for (int i = 0; i < 4; i++) { const uint2 u = lds64(spr + (lane & 16) * 32 + i * 128); S1 += uf(u.x); S2 += uf(u.y); }
    S1 += __shfl_xor_sync(~0u, S1, 16); S2 += __shfl_xor_sync(~0u, S2, 16);
    const float mu = S1 * (1.f / 576.f), var = fmaxf(fmaf(-mu, mu, S2 * (1.f / 576.f)), 0.f);
    const float m = rbf(mu), rs = rcpf(rbf(sqrta(rbf(rbf(var) + 1e-5f))));
    const float ra = rs * 0.0625f;
    sts64(SM_AF + w * 128 + (lane & 15) * 8, fu(ra), fu(-m * ra));
    __syncwarp();
    TS(55);
    const uint4 f0 = lds128(SM_AF + w * 128 + q * 16), f1 = lds128(SM_AF + w * 128 + 64 + q * 16);
    const u32 zdst = SM_GATE + w * 2048 + (g >> 1) * 128 + (lane & 15) * 8;
    const u32 pz = (q & 1) ? 0 : pm;
#pragma unroll
    for (int j = 0; j < 8; j++) {
      const u32 x0 = j & 1 ? t[j >> 1].z : t[j >> 1].x, x1 = j & 1 ? t[j >> 1].w : t[j >> 1].y;
      sts64((j & 1 ? zdst ^ 64 : zdst) + 512 * (j >> 1), pk_hf(fmaf(blo(x0), uf(f0.x), uf(f0.y)), fmaf(bhi(x0), uf(f0.z), uf(f0.w))) | pz,
            pk_hf(fmaf(blo(x1), uf(f1.x), uf(f1.y)), fmaf(bhi(x1), uf(f1.z), uf(f1.w))));
    }
    TS(53);
    if (w < 8) barrive(15, 288);
    else {
      bsync(15, 288);
      TS(54);
      if (lane == 0) {
        PROXY_FENCE();
        bulk_out<BLK>(gs + b * BLK, SM_GATE);
        asm volatile("cp.async.bulk.commit_group;" ::: "memory");
        if (PFG & 1) l2_pre<WSH / 2>(p.wg + b * WSH);
      }
      const float rh = rbf(rs);
      sts128(SM_ST + 16 * (lane & 15), pk_bf(-m, -m), pk_bf(rh, rh), pk_bf(rs - rh, rs - rh), 0);
    }
    TS(5);
  }
  if (kw) {
    float D[5][4] = {};
    u32 ta = ktab + q * 128 + ((g ^ (q << 1)) << 4), tm = ktab + 8192 + q * 16;
#pragma unroll 2
    for (int s = 0; s < 8; s++) {
      const uint4 ca = lds128(ta), cb = lds128(ta + 4096), ma = lds128(tm);
      ta = (ta + 512) ^ 16; tm += 64;
      k2048 += __shfl_xor_sync(~0u, k2048, 16 >> s);
      const C2 s0 = {cb.z, cb.w}, s1 = cm2(s0, {ma.x, ma.y}), s2 = cm2(s0, {ma.z, ma.w}), s3 = cm2(s1, {ma.z, ma.w});
      mma_hf(D[0], s0.re, s1.re, s0.im, s1.im, ca.x, ca.y);
      mma_hf(D[2], s0.re, s1.re, s0.im, s1.im, ca.z, ca.w);
      mma_hf(D[4], s0.re, s1.re, s0.im, s1.im, cb.x, cb.y);
      mma_hf(D[1], s2.re, s3.re, s2.im, s3.im, ca.x, ca.y);
      mma_hf(D[3], s2.re, s3.re, s2.im, s3.im, ca.z, ca.w);
    }
    TS(3);
    const u32 xa = (w < 8 ? SM_MODS + (4 + ksig) * KTAB : SM_ZS) + lane * 16;
    if (khf) {
      __syncwarp();
#pragma unroll
      for (int j = 0; j < 5; j++) sts128(xa + 512 * j, fu(D[j][0]), fu(D[j][1]), fu(D[j][2]), fu(D[j][3]));
      if (lane == 0) sts32(xa + 2560, fu(k2048));
      asm volatile("bar.arrive %0,64;" ::"r"(2 + ksig) : "memory");
    } else {
      const u32 t1 = tp + (q < 2 ? (128 + 4 * g + 2 * q) * 4 : T3 * 4 + ((32 * q - 64 + g) ^ 1) * 2);
      const u32 x = 16 * q + (g >> 1) + hi + 1, tb = tp + (hi ? T7E : T9E) * 4 - 4;
      const u32 te = tb + (x + 2 * (x & 1)) * 2, to = tb + TEO * 4 + (x ^ 1) * 2;
      asm volatile("bar.sync %0,64;" ::"r"(2 + ksig) : "memory");
#pragma unroll
      for (int j = 0; j < 5; j++) { const uint4 t = lds128(xa + 512 * j); D[j][0] += uf(t.x); D[j][1] += uf(t.y); D[j][2] += uf(t.z); D[j][3] += uf(t.w); }
      k2048 = (k2048 + uf(lds32(xa + 2560))) * 0.125f;
#pragma unroll
      for (int r = 0; r < 4; r++) {
        const u32 v = pk_hf(D[2 + (r >> 1)][2 * (r & 1)], D[2 + (r >> 1)][2 * (r & 1) + 1]);
        if (q < 2) {
          const u32 vv = __byte_perm(v, v, 0x1010);
          sts32(t1 + (TO + 32 * r) * 4, vv); sts16(t1 + (TO + 32 * r + 1) * 4 + 2, v >> 16); sts16(t1 + (TO + 32 * r - 1) * 4, v);
          sts64(t1 + (TE + 32 * r) * 4, vv, __byte_perm(v, v, 0x1032));
        } else {
          sts16(t1 + 16 * r, v >> 16);
          if (r == 0 && lane == 2) {
            const u32 vv = __byte_perm(v, v, 0x1010);
            sts32(tp + (TO + 256) * 4, vv); sts16(tp + (TO + 257) * 4 + 2, v); sts16(tp + (TO + 255) * 4, v); sts64(tp + (TE + 256) * 4, vv, vv);
          } else sts16(t1 + 16 * r - ((T3 - T5) * 4 + 6) + 8 * hi, v);
        }
      }
#pragma unroll
      for (int r = 0; r < 2; r++) {
        const u32 v = pk_hf(D[4][2 * r], D[4][2 * r + 1]);
        if (r == 0 && lane == 0) { sts16(tp + T5 * 4 + 62 * 2, v); sts32(SM_KV + 4 * ksig, v & 0xffff); sts16(tp + (T9E + TEO) * 4 + 62 * 2, pk_hf(k2048, 0.f)); }
        else { sts16(te + 8 * r, v); sts16(to + 8 * r, v); }
        sts16(te + 8 * r + 16, v >> 16); sts16(to + 8 * r + 16, v >> 16);
      }
      __syncwarp();
#pragma unroll
      for (int r = 0; r < 4; r++) {
        const u32 v = pk_hf(D[r >> 1][2 * (r & 1) + 1], D[r >> 1][2 * (r & 1)]), t2 = tp + lane * 4 + 128 * r;
        sts32(t2 + TO * 4, v); sts16(t2 + TE * 4, v >> 16); sts16(t2 + (TE + 1) * 4 + 2, v);
      }
      __syncwarp();
    }
  } else if (w == (b < 108 ? 11 : ~0u)) {
    float c[4][4] = {};
    u32 aa = SM_UP + ((lane & 7) + 8 * (lane >> 4)) * 64 + ((((lane >> 3) & 1) ^ ((lane & 7) >> 1)) << 4);
    u32 ba = SM_SIL + (lane >> 3) * 16;
    uint4 a[2][10];
#define GLD(n) { _Pragma("unroll") for (int i = 0; i < 2; i++) { a[n][5 * i] = ldsm4(ba + i * 64); \
      _Pragma("unroll") for (int k = 0; k < 4; k++) a[n][5 * i + 1 + k] = ldsm4t((k & 2 ? aa ^ 32 : aa) + i * 2048 + (k & 1) * 1024); } aa += 4096; ba += 128; }
#define GMM(n) { _Pragma("unroll") for (int i = 0; i < 2; i++) _Pragma("unroll") for (int k = 0; k < 4; k++) { const uint4 f = a[n][5 * i + 1 + k], bb = a[n][5 * i]; \
      mma_bf(c[k], f.x, f.y, f.z, f.w, k & 1 ? bb.z : bb.x, k & 1 ? bb.w : bb.y); } }
    mb_wait(SM_MB);
    TS(56);
    GLD(0);
#pragma unroll 1
    for (int s = 0; s < 4; s++) { GLD(1); GMM(0); GLD(0); GMM(1); }
    GMM(0);
    const float v0 = (q & 1) ? c[0][2] + c[1][2] : c[0][0] + c[1][0], v1 = (q & 1) ? c[2][2] + c[3][2] : c[2][0] + c[3][0];
    str16(gs + (G_MOD + b * 128 + 2 * g + 16 * q), pk_bf(rbf((q & 2) ? v1 : v0) * F2M64, 0.f) | (g < 2 ? pm : 0));
    TS(57);
  }
  TS(6);
  u32 tid2 = tid;
  if (w < 4) {
    asm volatile("setmaxnreg.inc.sync.aligned.u32 232;");
    const u32 tid = tid2 + p.zero, w = tid >> 5, lane = tid & 31, g = lane >> 2, q = lane & 3, hi = g & 1, zr = tid >> 16, tp = SM_TAP + w * TAPS;
    const u32 pml = opq((g & 3) ? 0 : pm);
    const u32 tr = tp + ((hi ? TO : TE) + (g >> 1) - q) * 4;
    u32 T[33][4], B5[5][2], B3[5][2];
#pragma unroll
    for (int d = 0; d < 33; d++) {
      T[d][0] = lds32(tr + 32 * d); T[d][1] = lds32(tr + 32 * d + 16);
      T[d][2] = cpy(d ? T[d - 1][1] : zr, zr, 0); T[d][3] = cpy(T[d][0], zr, 1);
    }
    const u32 t33 = cpy(T[32][1], zr, 0), z33 = cpy(zr, zr, 1);
    if (TPIN) {
#pragma unroll
      for (int d = 0; d < 33; d++) asm volatile("{.reg .pred p; setp.ne.u32 p,%2,0; @p st.shared.v2.u32 [%2],{%0,%1};}" ::"r"(T[d][2]), "r"(T[d][3]), "r"(zr) : "memory");
    }
    const u32 bt = tp + (T5 + g - q) * 4;
#pragma unroll
    for (int d = 0; d < 5; d++) {
      B5[d][0] = lds32(bt + 32 * d); B5[d][1] = lds32(bt + 32 * d - 16);
      B3[d][0] = lds32(bt + 32 * d + (T3 - T5) * 4); B3[d][1] = lds32(bt + 32 * d - 16 + (T3 - T5) * 4);
    }
    u32 za = opq(SM_ZS + 16 + w * ZSS + ((lane >> 3) & 1) * ZPS + ((lane & 7) + (lane >> 4)) * 16);
    u32 wa = opq(SM_W + W5O + w * WSL + row16(lane));
    u32 sa = opq(SM_W + W9O - 2048 + w * WSL + lane * 16);
    u32 yo = opq(G_Y + b * BLK + 256 * q + w * 32 + 4 * g);
    const u32 fa = opq(SM_SC + 16 * w + 8), bw = opq((BW >> 4 * w) & 15), bs = opq((BS >> 4 * w) & 15);
    if (TPIN) asm volatile("{.reg .pred p; setp.ne.u32 p,%8,0; @p st.shared.v4.u32 [%8],{%0,%1,%2,%3}; @p st.shared.v4.u32 [%8],{%4,%5,%6,%7};}"
                           ::"r"(za), "r"(wa), "r"(sa), "r"(yo), "r"(fa), "r"(bw), "r"(bs), "r"(pml), "r"(zr) : "memory");
    TS(8);
    uint2 fc;
    u32 F;
    if (F8) { bsync(8, 384); fc = lds64(fa); F = __byte_perm(fu(uf(fc.x) * uf(fc.y)), 0, 0x3232); pin(zr, F); }
    bsync(9, 384);
    TS(11);
    float A[4][4] = {};
    uint4 Z[4];
    Z[0] = ldsm4(za); Z[1] = ldsm4(za + 32);
    if (!F8) { fc = lds64(fa); F = __byte_perm(fu(uf(fc.x) * uf(fc.y)), 0, 0x3232); }
#define STEP(s, b0, b1) { _Pragma("unroll") for (int i = 0; i < 4; i++) mma_hf_t(A[i], T[8 * i + 7 - (s)], b0, b1); }
#define PAIR(n) { Z[(n + 2) & 3] = ldsm4(za + 32 * (n + 2)); STEP(2 * n, Z[n].x, Z[n].y); STEP(2 * n + 1, Z[n].z, Z[n].w); }
#define LAST(N) mma8_hf(N, t33, z33, Z[3].y); float O[4]; mma_hf_o(O, A[0], T[0], Z[3].z, Z[3].w); \
    _Pragma("unroll") for (int i = 0; i < 3; i++) mma_hf_o(A[i], A[i + 1], T[8 * i + 8], Z[3].z, Z[3].w); \
    mma_hf_o(A[3], N, T[32], Z[3].z, Z[3].w);
#pragma unroll 1
    for (int j = 0; j < 4; j++) {
      PAIR(0); PAIR(1); PAIR(2);
      Z[1] = ldsm4(za + 160); STEP(6, Z[3].x, Z[3].y);
      float N[4] = {};
      LAST(N);
      if (INCV) inc<128>(za);
      y_store<128>(O[0], O[1], O[2], O[3], F, pml, gs + yo);
      if (!INCV) za += 128;
      yo += 1024;
      TSJ(j);
    }
    bsyncr(bw);
    uint4 a5;
    if (A5P) a5 = ldsm4t(wa);
#pragma unroll 1
    for (int j = 4; j < 13; j++) {
      if (j == 8) bsyncr(bs);
      if (!A5P) a5 = ldsm4t(wa);
      const uint4 a3 = ldsm4t(wa + (W3O - W5O));
      uint4 s3 = {0, 0, 0, 0};
      if (j >= 8) s3 = lds128(sa);
      PAIR(0);
      float N[4] = {};
#pragma unroll
      for (int i = 0; i < 4; i++) mma_hf(A[i], a5.x, a5.y, a5.z, a5.w, B5[i][0], B5[i][1]);
      mma_hf(N, a5.x, a5.y, a5.z, a5.w, B5[4][0], B5[4][1]);
      if (INCV) asm volatile("{add.u32 %0,%0,256; xor.b32 %0,%0,32;}" : "+r"(wa)); else wa = (wa + 256) ^ 32;
      if (A5P) a5 = ldsm4t(wa);
      PAIR(1);
#pragma unroll
      for (int i = 0; i < 4; i++) mma_hf(A[i], a3.x, a3.y, a3.z, a3.w, B3[i][0], B3[i][1]);
      mma_hf(N, a3.x, a3.y, a3.z, a3.w, B3[4][0], B3[4][1]);
      PAIR(2);
      Z[1] = ldsm4(za + 160); STEP(6, Z[3].x, Z[3].y);
      LAST(N);
      if (INCV) { inc<128>(za); inc<512>(sa); }
      y_store<128>(O[0] + uf(s3.x), O[1] + uf(s3.y), O[2] + uf(s3.z), O[3] + uf(s3.w), F, pml, gs + yo);
      if (!INCV) { za += 128; sa += 512; }
      yo += 1024;
      TSJ(j);
    }
    {
      asm volatile("mov.u32 %0,%%tid.x;" : "=r"(tid2));
      const uint4 s3 = lds128(sa), s4 = lds128(sa + 512), s5 = lds128(sa + 1024);
      float X[3][4] = {{uf(s4.x), uf(s4.y), uf(s4.z), uf(s4.w)}, {}, {uf(s5.x), uf(s5.y), uf(s5.z), uf(s5.w)}};
#pragma unroll
      for (int ty = 0; ty < 2; ty++) {
        const uint4 a = A5P && !ty ? a5 : ldsm4t(wa + ty * (W3O - W5O)), c = ldsm4t((wa ^ 32) + 256 + ty * (W3O - W5O)), d = ldsm4t(wa + 512 + ty * (W3O - W5O));
#pragma unroll
        for (int i = 0; i < 3; i++) mma_hf(A[i], a.x, a.y, a.z, a.w, ty ? B3[i][0] : B5[i][0], ty ? B3[i][1] : B5[i][1]);
#pragma unroll
        for (int i = 0; i < 2; i++) mma_hf(X[i], c.x, c.y, c.z, c.w, ty ? B3[i][0] : B5[i][0], ty ? B3[i][1] : B5[i][1]);
        mma_hf(X[2], d.x, d.y, d.z, d.w, ty ? B3[0][0] : B5[0][0], ty ? B3[0][1] : B5[0][1]);
      }
#pragma unroll
      for (int n = 0; n < 4; n++) {
        const uint4 f0 = n < 2 ? Z[n] : ldsm4(za + 32 * n), f1 = ldsm4(za + 32 * n + 128), f2 = ldsm4(za + 32 * n + 256);
#pragma unroll
        for (int s = 2 * n; s < 2 * n + 2; s++) {
#pragma unroll
          for (int i = 0; i < 3; i++) mma_hf_t(A[i], T[8 * i + 7 - s], s & 1 ? f0.z : f0.x, s & 1 ? f0.w : f0.y);
          mma_hf_t(X[0], T[7 - s], s & 1 ? f1.z : f1.x, s & 1 ? f1.w : f1.y); mma_hf_t(X[1], T[15 - s], s & 1 ? f1.z : f1.x, s & 1 ? f1.w : f1.y);
          mma_hf_t(X[2], T[7 - s], s & 1 ? f2.z : f2.x, s & 1 ? f2.w : f2.y);
        }
      }
      y_store<128>(A[0][0] + uf(s3.x), A[0][1] + uf(s3.y), A[0][2] + uf(s3.z), A[0][3] + uf(s3.w), F, pml, gs + yo);
      y_store<128>(A[1][0] + X[0][0], A[1][1] + X[0][1], A[1][2] + X[0][2], A[1][3] + X[0][3], F, pml, gs + yo + 1024);
      y_store<128>(A[2][0] + X[1][0] + X[2][0], A[2][1] + X[1][1] + X[2][1], A[2][2] + X[1][2] + X[2][2], A[2][3] + X[1][3] + X[2][3], F, pml, gs + yo + 2048);
    }
    barrive(12, N12);
    TS(15);
  } else {
    asm volatile("setmaxnreg.dec.sync.aligned.u32 136;");
    const u32 t8 = tid - 128, pml = (g & 3) ? 0 : pm;
    {
      TS(12);
      if (PFG == 1 && tid == 288) l2_pre<WSH / 2>(p.wg + (b * WSH + WSH / 2));
      const char* zs = gs + ((16 * w - 64 + (lane >> 3)) * BLK + b * 128 + ((lane & 7) * 16 ^ rho * 64));
      const char* zs4 = gs + ((t8 >> 1) * BLK + (Ps >> 4) * 512 + (Ps & 6) * 64 + ((Ps >> 2 ^ Ps) & 2) * 32 + (Ps & 1) * 32 + (t8 & 1) * 16);
      uint4 v[5];
      v[4].x = INVAL;
      if (ZD) wait_clk(t0, ZD);
      const u32 d = lane < 4 ? chan(b, lane) : Ps;
      const char* mp = gs + (G_MOD + (d >> 5) * 128 + (d & 24) * 2);
      uint4 ta, tc;
      ta.x = tc.x = INVAL;
      const u32 t9 = w == 9 ? pm : INVAL;
      pin2(zr, zs, zs4);
      conv();
      POLLM({ rld128<TAGM>(ta, mp, t9); rld128<TAGM>(tc, mp + MODJ, t9); rld128<TAGM>(v[4], zs4, pm); }, lop3<0xbe>(v[4].x, pm, ne3(ta.x, tc.x, t9)), TAGM, 1);
      TS(58);
#pragma unroll
      for (int j = 0; j < 4; j++) v[j] = ldr128(zs + j * 4 * BLK);
      if (w == 9) {
        const u32 aw = (d & 4) ? ((d & 2) ? ta.w : ta.z) : ((d & 2) ? ta.y : ta.x & ~TAGM);
        const u32 cw = (d & 4) ? ((d & 2) ? tc.w : tc.z) : ((d & 2) ? tc.y : tc.x & ~TAGM);
        const float sa = ((d & 1) ? bhi(aw) : blo(aw)) * F2P64, c1 = rbf(fmaf((d & 1) ? bhi(cw) : blo(cw), F2P64, 1.f));
        const u32 EM = min(max(fu(fmaxf(32.f * fabsf(c1), fabsf(sa))) >> 23, 80u), 250u);
        const float inv = uf((264 - EM) << 23);
        if (lane < 5) { sts64(SM_SC + 16 * lane, pk_hf(16.f * c1 * inv, 16.f * c1 * inv), pk_hf(sa * inv, sa * inv)); sts32(SM_SC + 16 * lane + 8, (EM - 74) << 23); }
        TS(10);
      }
#define MARKERS() if (tid == 256) { \
        if (!YS) bulk_out<2048>(gs + (G_Y + 16384 + b * BLK), SM_INV); \
        _Pragma("unroll") for (int i = MT / 2; i < 8; i++) bulk_out<2048>(gs + (G_Y + 2048 * i + b * BLK), SM_INV); \
        bulk_out<2048>(gs + (G_PART + b * 2048), SM_INV); bulk_out<512>(gs + (G_ACT + b * 512), SM_INV); \
        bulk_out<32>(gs + (G_KEY + b * KST), SM_INV); if (!rho) bulk_out<128>(gs + (G_ACT + Ps * 128), SM_INV); \
        asm volatile("cp.async.bulk.commit_group;" ::: "memory"); }
#define GATE() { mb_expect(SM_MB + 8, rho ? SLV : 46080); \
        _Pragma("unroll") for (int i = GE; i < 3; i++) tma3d(SM_GATE + 12288 * i, &tm_gate, SM_MB + 8, 32 * b, i); \
        if (!rho) tma3d(SM_GATE + SLV, &tm_gs, SM_MB + 8, 4096 + 4 * b, 0); }
#define UP() { mb_expect(SM_MB + 16, rho ? SLV : 46080); tma3d(SM_UP, &tm_up, SM_MB + 16, 32 * b, 0); \
        if (!rho) tma3d(SM_UP + SLV, &tm_us, SM_MB + 16, 4096 + 4 * b, 0); }
      if (PFU == 2 && tid == 256) l2_pre<WSH>(p.wu + b * WSH);
      if (GE && tid == 256) {
        asm volatile("cp.async.bulk.wait_group.read 0;" ::: "memory");
#pragma unroll
        for (int i = 0; i < GE; i++) tma3d(SM_GATE + 12288 * i, &tm_gate, SM_MB + 8, 32 * b, i);
      }
      if (PFG == 2 && tid == 256) l2_pre<WSH>(p.wg + b * WSH);
      if (PFG == 3 && tid == 256) l2_pre<WSH / 2>(p.wg + (b * WSH + WSH / 2));
      bsync(8, F8 ? 384 : 256);
      const uint2 cc = lds64(SM_SC + 8 * (t8 & 6)), c4 = lds64(SM_SC + 64);
      sts128(SM_Z4 + 256 + (t8 & 1) * ZP4 + (t8 >> 1) * 16, hfma(v[4].x & ~TAGM, c4.x, c4.y), hfma(v[4].y, c4.x, c4.y), hfma(v[4].z, c4.x, c4.y), hfma(v[4].w, c4.x, c4.y));
      if (t8 < 96) sts128(t8 < 64 ? SM_ZS + (t8 & 7) * ZPS + (t8 >> 3) * 16 : SM_Z4 + (t8 & 1) * ZP4 + (t8 & 30) * 8, 0, 0, 0, 0);
      asm volatile("cp.async.bulk.wait_group.read 0;" ::: "memory");
      const u32 dst = SM_ZS + 128 + (t8 & 7) * ZPS + (16 * w - 64 + (lane >> 3)) * 16;
      pin(zr, dst);
      conv();
      POLLS(_Pragma("unroll") for (int j = 0; j < 4; j++) sts128(dst + j * 64, hfma(v[j].x & ~TAGM, cc.x, cc.y), hfma(v[j].y, cc.x, cc.y), hfma(v[j].z, cc.x, cc.y), hfma(v[j].w, cc.x, cc.y)),
            _Pragma("unroll") for (int j = 0; j < 4; j++) rld128<TAGM>(v[j], zs + j * 4 * BLK, pm), ne3(v[0].x, v[1].x, pm) | ne3(v[2].x, v[3].x, pm), TAGM, 1);
      TS(9);
      bsync(9, 384);
      TS(11);
      if (MKT == 1) MARKERS();
      if (w == 10 && s2u(smem) != SM0) __trap();
      const bool lng = w < 8 || w == 9;
      const u32 ts = lane + 32 * (w == 8 ? 0 : w - 9), c = min(ts, 71u), ma = SM_MODS + 16 * c;
      const u32 sig = lng ? ksig : ts >> 4, l2 = lng ? lane : 32 + (ts & 15);
      const char* mq = gs + (G_MOD + (c >> 2) * 128 + (c & 3) * 16);
      if (!lng) {
#pragma unroll
        for (int j = 0; j < 6; j++) cpa16(ma + 1152 * j, mq + j * MODJ);
        cpa16(ma + 1152 * 6, p.dsk + 16 * c); cpa16(ma + 1152 * 7, p.wr + 16 * c);
        if (PFU == 3) {
#pragma unroll
          for (int j = 0; j < 4; j++) if (ts < 81) l2_line(p.wu + (b * WSH + (81 * j + ts) * 128));
        }
        if (tid == 352) {
          PROXY_FENCE();
          if (PFU == 1) l2_pre<WSH>(p.wu + b * WSH);
          if (!TG) GATE();
          if (!TU) UP();
        }
      }
      const u32 wb = SM_W + sig * WSL;
      if (sig < 5) {
        const u32 za = (sig < 4 ? SM_ZS + 128 + sig * ZSS : SM_Z4 + 256) + l2 * 32, zb = za + (sig < 4 ? ZPS : ZP4);
        const uint4 c0 = lds128(zb - 32), c1 = lds128(za - 16), c2 = lds128(zb - 16), c3 = lds128(za), c4 = lds128(zb), c5 = lds128(za + 16), c6 = lds128(zb + 16);
        const u32 P[25] = {c0.z, c0.w, c1.x, c1.y, c1.z, c1.w, c2.x, c2.y, c2.z, c2.w, c3.x, c3.y, c3.z, c3.w, c4.x, c4.y, c4.z, c4.w, c5.x, c5.y, c5.z, c5.w, c6.x, c6.y, c6.z};
        u32 Q[25], D1[24], F4[23], W5[21], W3[17];
#pragma unroll
        for (int j = 1; j < 25; j++) Q[j] = __byte_perm(P[j - 1], P[j], 0x5432);
#pragma unroll
        for (int j = 1; j < 24; j++) D1[j] = hadd(P[j], Q[j]);
#pragma unroll
        for (int j = 2; j < 23; j++) F4[j] = hadd(D1[j], D1[j - 1]);
#pragma unroll
        for (int n = 0; n < 21; n++) W5[n] = hadd(F4[n + 2], P[n]);
#pragma unroll
        for (int n = 0; n < 17; n++) W3[n] = hadd(Q[n + 8], D1[n + 7]);
        const u32 a0 = wb + W5O + 64 * l2 + 16 * ((l2 >> 1) & 3);
#pragma unroll
        for (int i = 0; i < 4; i++) {
          sts128(a0 ^ (16 * i), W5[4 * i + 5], W5[4 * i + 6], W5[4 * i + 7], W5[4 * i + 8]);
          sts128((a0 ^ (16 * i)) + (W3O - W5O), W3[4 * i + 1], W3[4 * i + 2], W3[4 * i + 3], W3[4 * i + 4]);
        }
        if (lng) {
          if (lane < 16) sts128(wb + (lane & 7) * 16 + (lane & 8) * 400, 0, 0, 0, 0);
          const u32 a1 = wb + 32 * lane + 16 * ((lane >> 2) & 1);
#pragma unroll
          for (int i = 0; i < 4; i++) {
            const u32 a = (a1 ^ (16 * (i >> 1))) + 1024 * (i & 1), n = 4 * i;
            sts128(a + V2O, hadd(Q[n + 9], P[n + 8]), hadd(Q[n + 10], P[n + 9]), hadd(Q[n + 11], P[n + 10]), hadd(Q[n + 12], P[n + 11]));
            sts128(a + W9O, hadd(F4[n + 4], W5[n]), hadd(F4[n + 5], W5[n + 1]), hadd(F4[n + 6], W5[n + 2]), hadd(F4[n + 7], W5[n + 3]));
            sts128(a + W7O, hadd(F4[n + 6], W3[n]), hadd(F4[n + 7], W3[n + 1]), hadd(F4[n + 8], W3[n + 2]), hadd(F4[n + 9], W3[n + 3]));
          }
        }
      }
      if (w < 8) barriver((BW >> (4 * w - 16)) & 15);
      else if (!(w & 1)) { barriver((BW >> (4 * w - 32)) & 15); barriver((BW >> (4 * w - 28)) & 15); }
      __syncwarp();
      TS(32);
      if (lng) {
        const u32 wa = wb + ((lane >> 3) & 1) * 1024 + (((lane & 7) ^ (lane >> 4)) + 8 * (lane >> 4)) * 16;
        const u32 kv = lds32(SM_KV + 4 * sig), bi = (g >> 1) == q ? (hi ? kv << 16 : kv) : 0u;
        float acc[8][4] = {};
#pragma unroll
        for (int j = 0; j < 4; j++) { const uint4 a = ldsm4t(wa + V2O + j * 256); mma8_hf(acc[2 * j], a.x, a.y, bi); mma8_hf(acc[2 * j + 1], a.z, a.w, bi); }
        u32 bt = tp + (T9E + hi * TEO + (g >> 1) - q) * 4, wt = wa + W9O;
#pragma unroll 1
        for (int ty = 0; ty < 2; ty++) {
          uint4 a[4];
#pragma unroll
          for (int be = 0; be < 4; be++) a[be] = ldsm4t(wt + be * 256);
          u32 b1 = lds32(bt - 16);
#pragma unroll
          for (int d = 0; d < 8; d++) {
            const u32 b0 = lds32(bt + 16 * d);
#pragma unroll
            for (int be = 0; be < 4; be++) if (d + 2 * be < 8) mma_hf(acc[d + 2 * be], a[be].x, a[be].y, a[be].z, a[be].w, b0, b1);
            b1 = b0;
          }
          bt += (T7E - T9E) * 4; wt += W7O - W9O;
        }
        __syncwarp();
#pragma unroll
        for (int j = 0; j < 8; j++) sts128(wb + W9O + j * 512 + lane * 16, fu(acc[j][0]), fu(acc[j][1]), fu(acc[j][2]), fu(acc[j][3]));
        if (w != 9) barriver((BS >> (4 * w - 16)) & 15);
        TS(34);
      }
      if (!lng) {
        asm volatile("cp.async.wait_all;" ::: "memory");
        uint4 md[6];
#pragma unroll
        for (int j = 0; j < 6; j++) md[j] = lds128(ma + 1152 * j);
        const uint4 dk = lds128(ma + 1152 * 6), wr = lds128(ma + 1152 * 7);
        POLLW(_Pragma("unroll") for (int j = 0; j < 6; j++) md[j] = ldr128(mq + j * MODJ),
              ((md[0].x ^ pm) | (md[1].x ^ pm) | (md[2].x ^ pm) | (md[3].x ^ pm) | (md[4].x ^ pm) | (md[5].x ^ pm)) & TAGM, 4);
#pragma unroll
        for (int j = 0; j < 6; j++) {
          const u32 o = (j % 3 == 1) ? BONE : 0x80008000u;
          md[j] = make_uint4(bfma(md[j].x & ~TAGM, B2P64, o), bfma(md[j].y, B2P64, o), bfma(md[j].z, B2P64, o), bfma(md[j].w, B2P64, o));
          if (j > 2) sts128(ma + 1152 * j, md[j].x, md[j].y, md[j].z, md[j].w);
        }
        const uint4 gd = make_uint4(bmul(md[2].x, dk.x), bmul(md[2].y, dk.y), bmul(md[2].z, dk.z), bmul(md[2].w, dk.w));
#pragma unroll
        for (int j = 0; j < 2; j++) sts128(ma + 1152 * j, bmul(md[j].x, gd.x), bmul(md[j].y, gd.y), bmul(md[j].z, gd.z), bmul(md[j].w, gd.w));
        sts128(ma + 2304, bmul(md[2].x, B2P64), bmul(md[2].y, B2P64), bmul(md[2].z, B2P64), bmul(md[2].w, B2P64));
        const uint4 H = make_uint4(bmul(md[4].x, wr.x), bmul(md[4].y, wr.y), bmul(md[4].z, wr.z), bmul(md[4].w, wr.w));
        sts128(ma + 1152 * 7, H.x, H.y, H.z, H.w);
        sts128(ma + 1152 * 8, bfma(md[4].x, wr.x, H.x ^ 0x80008000u), bfma(md[4].y, wr.y, H.y ^ 0x80008000u), bfma(md[4].z, wr.z, H.z ^ 0x80008000u), bfma(md[4].w, wr.w, H.w ^ 0x80008000u));
        float c4[4] = {};
        mma_bf(c4, md[4].x, md[3].x, md[4].y, md[3].y, wr.x, wr.y); mma_bf(c4, md[4].z, md[3].z, md[4].w, md[3].w, wr.z, wr.w);
        if (q == g >> 1) sts64(SM_RC + (ts >> 2) * 8, fu(hi ? c4[1] : c4[0]), fu(hi ? c4[3] : c4[2]));
        if (ts < 2) sts128(SM_ONE + 16 * ts, ts ? 0 : BONE, ts ? 0 : BONE, ts ? 0 : BONE, ts ? 0 : BONE);
        TS(14);
        if (MKT == 2) MARKERS();
        if (w == 8) asm volatile("cp.async.bulk.wait_group 0;" ::: "memory");
        if (PFW == 2) {
#pragma unroll
          for (int j = 0; j < 4; j++) if (ts < 81) l2_line(p.wd + (b * WSH + (81 * j + ts) * 128));
        }
        bsync(13, 96);
        if (w == 8) { barriver(2); barriver(3); barriver(5); barriver(6); if (HLP) barrive(7, 64); }
      }
      if (!HLP) { if (w >= 8) barrive(11, 256); }
      else if (w == 9) barrive(11, 128);
    }
    const u32 jw = w < 6 ? w ^ 1 : w < 8 ? w : max(w - 4, 5u);
    const int u0 = 4 * (jw - 4) + 2 * rho;
    const u32 t4 = SM_TAP + 4 * TAPS, s3a = SM_W + 4 * WSL + (u0 >= 8 ? W9O + (u0 - 8) * 512 : V2O) + lane * 16, hb = (0x4987 >> (4 * jw - 16)) & 15;
#define FARL() { u32 wa = (SM_W + 4 * WSL + W5O + row16(lane) + (u0 - 3) * 256) ^ 32, bt = t4 + (T5 + g - q) * 4; \
      _Pragma("unroll 1") for (int al = min(u0 - 2, 6); al > 0; al--) { \
        _Pragma("unroll") for (int ty = 0; ty < 2; ty++) { \
          const uint4 a = ldsm4t(wa + ty * (W3O - W5O)); \
          const u32 bb = bt + ty * (T3 - T5) * 4; \
          mma_hf(acc[ty], a.x, a.y, a.z, a.w, lds32(bb - 32), lds32(bb - 48)); \
          mma_hf(acc[2 + ty], a.x, a.y, a.z, a.w, lds32(bb), lds32(bb - 16)); \
        } \
        wa = (wa - 256) ^ 32; bt += 32; } }
    if (w < 8) {
      u32 tr = t4 + ((hi ? TO : TE) + (g >> 1) - q) * 4;
      u32 zb = SM_Z4 + 256 + ((lane >> 3) & 1) * ZP4 + u0 * 128 + (lane & 7) * 16 + (lane >> 4) * 128;
      float acc[4][4] = {};
      u32 prev = 0;
#pragma unroll 1
      for (int it = min(u0 + 2, 4); it; it--) {
#pragma unroll
        for (int s = 0; s < 8; s++) {
          const uint4 z = ldsm4(zb - 16 * s);
          const u32 t0 = lds32(tr + 32 * s), t1 = lds32(tr + 32 * s + 16);
          mma_hf(acc[s & 1], t0, t1, prev, t0, z.x, z.y);
          mma_hf(acc[2 + (s & 1)], t0, t1, prev, t0, z.z, z.w);
          prev = t1;
        }
        zb -= 128; tr += 256;
      }
      {
        const uint4 z = ldsm4(zb); const u32 t0 = lds32(tr), t1 = lds32(tr + 16);
        mma_hf(acc[0], t0, t1, prev, t0, z.x, z.y); mma_hf(acc[2], t0, t1, prev, t0, z.z, z.w);
        if (jw > 4) { const uint4 y = ldsm4(zb - 16); mma8_hf(acc[1], t1, zr, y.y); mma8_hf(acc[3], t1, zr, y.w); }
      }
      if (!HLP) { bsync(11, 256); FARL(); }
      else asm volatile("bar.sync %0,64;" ::"r"(hb) : "memory");
      TS(35);
      const uint2 fc = lds64(SM_SC + 16 * 4 + 8);
      const u32 F = __byte_perm(fu(uf(fc.x) * uf(fc.y)), 0, 0x3232);
      char* yp = gs + (YS ? G_Y + 16384 + (32 * jw - 128 + 16 * rho + 2 * q) * BLK + (b & 12) * 128 + (b & 64) * 4 + (b & 48) * 4 + (b & 2) * 16 + 4 * g : G_Y + 16384 - 2048 + b * BLK + jw * 512 + q * 64 + 4 * g);
#pragma unroll
      for (int j = 0; j < 2; j++) {
        uint4 s3 = {0, 0, 0, 0};
        if (u0 >= (HLP ? 4 : 8)) s3 = lds128(s3a + j * 512);
        y_store<YS ? BLK : 32>(acc[2 * j][0] + acc[2 * j + 1][0] + uf(s3.x), acc[2 * j][1] + acc[2 * j + 1][1] + uf(s3.y), acc[2 * j][2] + acc[2 * j + 1][2] + uf(s3.z),
                acc[2 * j][3] + acc[2 * j + 1][3] + uf(s3.w), F, pml, yp + j * (YS ? 8 * BLK : 256));
      }
      TS(16);
    } else {
      if (HLP && w != 9) {
        bsync(11, 128);
        if (HD) wait_clk(clk(), HD);
        float acc[4][4] = {};
        if (u0 >= 8) {
#pragma unroll
          for (int j = 0; j < 2; j++) { const uint4 t = lds128(s3a + j * 512); acc[2 * j][0] = uf(t.x); acc[2 * j][1] = uf(t.y); acc[2 * j][2] = uf(t.z); acc[2 * j][3] = uf(t.w); }
        }
        FARL();
#pragma unroll
        for (int j = 0; j < 2; j++)
          sts128(s3a + j * 512, fu(acc[2 * j][0] + acc[2 * j + 1][0]), fu(acc[2 * j][1] + acc[2 * j + 1][1]), fu(acc[2 * j][2] + acc[2 * j + 1][2]), fu(acc[2 * j][3] + acc[2 * j + 1][3]));
        asm volatile("bar.arrive %0,64;" ::"r"(hb) : "memory");
        TS(16);
      }
      if (PFW == 3 && w == 9) {
#pragma unroll 1
        for (int j = 0; j < 12; j++) { if (lane < 27) l2_line(p.wd + (b * WSH + (27 * j + lane) * 128)); wait_clk(clk(), PFP); }
      }
      if (TG | TU | TW) {
        if (tid == 352) {
          if (TG) { wait_clk(t0, TG); GATE(); }
          if (TW < TU) { wait_clk(t0, TW); l2_pre<WSH>(p.wd + b * WSH); }
          if (TU) { wait_clk(t0, TU); UP(); }
          if (TW >= TU) { wait_clk(t0, TW); l2_pre<WSH>(p.wd + b * WSH); }
        }
      } else if (PFW < 2 && tid == 352) { mb_wait(SM_MB + 8); if (PFW) mb_wait(SM_MB + 16); l2_pre<WSH>(p.wd + b * WSH); }
      if (D0C && tid == 352 && b < 108) {
        mb_wait(SM_MB + 16);
        PROXY_FENCE();
        mb_expect(SM_MB + 24, 49152);
        tma3d(SM_TAP, &tm_down, SM_MB + 24, 64 * (b % 9), 4 * (b / 9));
      }
      TS(17);
    }
  }
  post_conv(p, &tm_down, tid2 + p.zero, b, b3);
  TSD();
}

typedef CUresult (*EncFn)(CUtensorMap*, CUtensorMapDataType, cuuint32_t, void*, const cuuint64_t*, const cuuint64_t*, const cuuint32_t*, const cuuint32_t*,
                          CUtensorMapInterleave, CUtensorMapSwizzle, CUtensorMapL2promotion, CUtensorMapFloatOOBfill);
static void make_map(EncFn enc, CUtensorMap* tm, void* ptr, int cols, int rows, int bw, int nb, CUtensorMapSwizzle sw, int gr = 192, int prom = 0) {
  cuuint64_t gd[3] = {(cuuint64_t)cols, (cuuint64_t)gr, (cuuint64_t)(rows / gr)}, gs[2] = {(cuuint64_t)cols * 2, (cuuint64_t)cols * 2 * gr};
  cuuint32_t bd[3] = {(cuuint32_t)bw, (cuuint32_t)gr, (cuuint32_t)nb}, es[3] = {1, 1, 1};
  enc(tm, CU_TENSOR_MAP_DATA_TYPE_BFLOAT16, 3, ptr, gd, gs, bd, es, CU_TENSOR_MAP_INTERLEAVE_NONE, sw, (CUtensorMapL2promotion)prom, CU_TENSOR_MAP_FLOAT_OOB_FILL_NONE);
}
extern "C" void kernel_launch(void* const* d_in, const int* in_sizes, int n_in, void* d_out, int out_size) {
  static EncFn enc = nullptr;
  static void* scratch = nullptr;
  if (!enc) {
    cudaGetSymbolAddress(&scratch, g_s);
    cudaDriverEntryPointQueryResult qr;
    cudaGetDriverEntryPoint("cuTensorMapEncodeTiled", (void**)&enc, cudaEnableDefault, &qr);
    cudaFuncSetAttribute(fused_kernel, cudaFuncAttributeMaxDynamicSharedMemorySize, SM_TOTAL);
  }
  CUtensorMap tm_mod, tm_gate, tm_gs, tm_up, tm_us, tm_down;
  make_map(enc, &tm_mod, d_in[13], 3456, 576, 32, 3, CU_TENSOR_MAP_SWIZZLE_64B, 192, PRM);
  make_map(enc, &tm_gate, d_in[9], 4608, 576, 32, 1, CU_TENSOR_MAP_SWIZZLE_64B, 192, PRG);
  make_map(enc, &tm_gs, d_in[9], 4608, 576, 8, 3, CU_TENSOR_MAP_SWIZZLE_NONE);
  make_map(enc, &tm_up, d_in[10], 4608, 576, 32, 3, CU_TENSOR_MAP_SWIZZLE_64B, 192, PRU);
  make_map(enc, &tm_us, d_in[10], 4608, 576, 8, 3, CU_TENSOR_MAP_SWIZZLE_NONE, 192, PRS);
  make_map(enc, &tm_down, d_in[11], 576, 4608, 64, 1, CU_TENSOR_MAP_SWIZZLE_128B, 96);
  Prm p;
  p.x = (const char*)d_in[0]; p.la = (const char*)d_in[1]; p.ai = (const char*)d_in[2]; p.cr = (const char*)d_in[3];
  p.ci = (const char*)d_in[4]; p.ldt = (const char*)d_in[5]; p.dsk = (const char*)d_in[6]; p.wr = (const char*)d_in[8];
  p.wg = (const char*)d_in[9]; p.wu = (const char*)d_in[10]; p.wd = (const char*)d_in[11];
  p.c = (const char*)d_in[12]; p.out = (char*)d_out; p.zero = 0; p.gs = (char*)scratch;
  fused_kernel<<<128, 384, SM_TOTAL>>>(p, tm_mod, tm_gate, tm_gs, tm_up, tm_us, tm_down);
}
```

```cpp
#include <cuda_runtime.h>
#include <cuda.h>
#include <cuda_bf16.h>
#include <cuda_fp16.h>
#include <stdint.h>
#define FUSED 1
#define DEV __device__ __forceinline__
typedef uint32_t u32;

constexpr u32 BLK = 18432, G_Z = 0, G_Y = 128 * BLK, G_MOD = 2 * G_Y, G_KEY = G_MOD + 128 * 128, G_ACT = G_KEY + 128 * 128;
constexpr u32 G_PART = G_ACT + 576 * 128, G_EP = G_PART + 128 * 2048, G_END = G_EP + 128;
__device__ __align__(128) unsigned char g_s[2 * G_END];
#define TS(i)
#define TSJ(j)
#define TS0()
#define TSE()
#define TSD()
#define TSX 0
#define TSRND()
#define TSN(code, n)
#define ERRF(code)

constexpr int SM0 = 1024;
constexpr int ROW = 1168, SLV = 36864;
constexpr int SM_GATE = SM0, SM_UP = SM_GATE + 46080, SM_XST = SM_UP + 46080, SM_MODS = SM_XST + 16 * ROW, SM_W = SM_MODS + 11008;
constexpr int KTAB = 9216, WSL = 12544, W5O = 128, W3O = 3328, V2O = 6400, W9O = 8448, W7O = 10496;
constexpr int ZPS = 2192, ZSS = 2 * ZPS, ZP4 = 2368;
constexpr int SM_ZS = SM_W + 5 * WSL, SM_Z4 = SM_ZS + 4 * ZSS, SM_TAP = SM_Z4 + 2 * ZP4, TAPS = 3328;
constexpr int SM_MB = SM_TAP + 5 * TAPS;
constexpr int SM_SC = SM_MB + 48;
constexpr int SM_KV = SM_SC + 80;
constexpr int SM_THR = SM_KV + 32;
constexpr int SM_SLOT = SM_THR + 48;
constexpr int SM_KEY = SM_SLOT + 32;
constexpr int SM_ST = SM_KEY + 64;
constexpr int SM_ST2 = SM_ST + 256;
constexpr int SM_RC = SM_ST2 + 256;
constexpr int SM_SP = SM_RC + 192;
constexpr int SM_AF = SM_SP + 1152, SM_SIL = SM_AF + 1152, SM_INV = SM_SIL + 1152, SM_END = SM_SP + 5760;
constexpr int SM_ONE = SM_MODS + 9 * 1152;
constexpr int SM_WD = SM_W, SM_XS = SM_W + 36864, SM_AC = SM_ZS, SM_RED = SM_AC + 6144;
constexpr int SM_TSB = SM_END, SM_TOTAL = SM_END + TSX - SM0;
static_assert(SM_W % 1024 == 0 && SM_TAP % 1024 == 0 && SM_MODS + 8 * KTAB <= SM_ZS && SM_ZS + 2 * KTAB <= SM_TAP && SM_RED + 10240 <= SM_TAP && SM_XS + 8 * ROW <= SM_ZS, "smem map");
static_assert(SM_MB % 16 == 0 && SM_THR % 16 == 0 && SM_ST % 16 == 0 && SM_SP % 16 == 0 && SM_TOTAL <= 232448, "smem map");
constexpr int TE = 4, TO = 276, T5 = 560, T3 = 624, T9E = 680, T7E = 760, TEO = 40;
#define MT 10
#define MKT 1
#define KST 32
#define DE1 1
#define DE2 4
#define DE3 5
#define OUTB 7
#define PFW 1
#define PFU 0
#define KD 700
#define D0C 0
#define YE 104
#define YL 104
#define YD 250
#define OPTM 1
#define Y8 104
#define FH 0
#define FO 0
#define DB1 1
#define KD1 50
#define AD 0
#define PD 900
#define ZD 0
#define DD 1000
#define INCV 1
#define TPIN 0
#define A5P 1
#define TG 0
#define TU 0
#define TW 0
#define KDB 520
#define PRM 0
#define PRG 0
#define PRU 0
#define PRS 0
#define KE 64
#define PFP 200
#define GE 0
#define NB8 8
#define DX 0
#define DMOD 1000
#define RW 3
#define AW 7
#define HLP 1
#define SMD 1
#define CVG 1
#define GX 15
#define HD 0
#define KF 96
#define KDC 520
#define AFP 1
#define AFM 0
#define PFG 1
constexpr int N1 = 320 + 32 * DB1, N12 = 288 + 32 * !DB1;
constexpr int SPIN = 1 << 16, NEARLY = 4;
constexpr u32 TAGM = 0x40004000u, TAGR = 0x40000000u, INVAL = 0x00004801u;

DEV u32 s2u(const void* p) { return (u32)__cvta_generic_to_shared(p); }
DEV void mma_bf(float (&c)[4], u32 a0, u32 a1, u32 a2, u32 a3, u32 b0, u32 b1) {
  asm("mma.sync.aligned.m16n8k16.row.col.f32.bf16.bf16.f32 {%0,%1,%2,%3},{%4,%5,%6,%7},{%8,%9},{%0,%1,%2,%3};"
      : "+f"(c[0]), "+f"(c[1]), "+f"(c[2]), "+f"(c[3]) : "r"(a0), "r"(a1), "r"(a2), "r"(a3), "r"(b0), "r"(b1));
}
DEV void mma_hf(float (&c)[4], u32 a0, u32 a1, u32 a2, u32 a3, u32 b0, u32 b1) {
  asm("mma.sync.aligned.m16n8k16.row.col.f32.f16.f16.f32 {%0,%1,%2,%3},{%4,%5,%6,%7},{%8,%9},{%0,%1,%2,%3};"
      : "+f"(c[0]), "+f"(c[1]), "+f"(c[2]), "+f"(c[3]) : "r"(a0), "r"(a1), "r"(a2), "r"(a3), "r"(b0), "r"(b1));
}
DEV void mma8_bf(float (&c)[4], u32 a0, u32 a1, u32 b0) {
  asm("mma.sync.aligned.m16n8k8.row.col.f32.bf16.bf16.f32 {%0,%1,%2,%3},{%4,%5},{%6},{%0,%1,%2,%3};"
      : "+f"(c[0]), "+f"(c[1]), "+f"(c[2]), "+f"(c[3]) : "r"(a0), "r"(a1), "r"(b0));
}
DEV void mma8_hf(float (&c)[4], u32 a0, u32 a1, u32 b0) {
  asm("mma.sync.aligned.m16n8k8.row.col.f32.f16.f16.f32 {%0,%1,%2,%3},{%4,%5},{%6},{%0,%1,%2,%3};"
      : "+f"(c[0]), "+f"(c[1]), "+f"(c[2]), "+f"(c[3]) : "r"(a0), "r"(a1), "r"(b0));
}
DEV u32 movm(u32 x) { u32 r; asm("movmatrix.sync.aligned.m8n8.trans.b16 %0,%1;" : "=r"(r) : "r"(x)); return r; }
DEV void conv() { if (CVG) asm volatile("{.reg .u32 t; mov.u32 t,0; movmatrix.sync.aligned.m8n8.trans.b16 t,t;}"); }
DEV uint4 ldsm4(u32 a) { uint4 r; asm volatile("ldmatrix.sync.aligned.m8n8.x4.shared.b16 {%0,%1,%2,%3},[%4];" : "=r"(r.x), "=r"(r.y), "=r"(r.z), "=r"(r.w) : "r"(a)); return r; }
DEV uint4 ldsm4t(u32 a) { uint4 r; asm volatile("ldmatrix.sync.aligned.m8n8.x4.trans.shared.b16 {%0,%1,%2,%3},[%4];" : "=r"(r.x), "=r"(r.y), "=r"(r.z), "=r"(r.w) : "r"(a)); return r; }
DEV u32 lds32(u32 a) { u32 r; asm volatile("ld.volatile.shared.u32 %0,[%1];" : "=r"(r) : "r"(a)); return r; }
DEV uint2 lds64(u32 a) { uint2 r; asm volatile("ld.shared.v2.u32 {%0,%1},[%2];" : "=r"(r.x), "=r"(r.y) : "r"(a)); return r; }
DEV uint4 lds128(u32 a) { uint4 r; asm volatile("ld.shared.v4.u32 {%0,%1,%2,%3},[%4];" : "=r"(r.x), "=r"(r.y), "=r"(r.z), "=r"(r.w) : "r"(a)); return r; }
DEV void sts16(u32 a, u32 v) { asm volatile("st.shared.u16 [%0],%1;" ::"r"(a), "h"((unsigned short)v) : "memory"); }
DEV void sts32(u32 a, u32 v) { asm volatile("st.shared.u32 [%0],%1;" ::"r"(a), "r"(v) : "memory"); }
DEV void sts64(u32 a, u32 x, u32 y) { asm volatile("st.shared.v2.u32 [%0],{%1,%2};" ::"r"(a), "r"(x), "r"(y) : "memory"); }
DEV void sts128(u32 a, u32 x, u32 y, u32 z, u32 w) { asm volatile("st.shared.v4.u32 [%0],{%1,%2,%3,%4};" ::"r"(a), "r"(x), "r"(y), "r"(z), "r"(w) : "memory"); }
DEV uint4 ldr128(const void* p) { uint4 v; asm volatile("ld.relaxed.gpu.global.v4.u32 {%0,%1,%2,%3},[%4];" : "=r"(v.x), "=r"(v.y), "=r"(v.z), "=r"(v.w) : "l"(p) : "memory"); return v; }
DEV uint2 ldr64(const void* p) { uint2 v; asm volatile("ld.relaxed.gpu.global.v2.u32 {%0,%1},[%2];" : "=r"(v.x), "=r"(v.y) : "l"(p) : "memory"); return v; }
DEV u32 ldr32(const void* p) { u32 v; asm volatile("ld.relaxed.gpu.global.u32 %0,[%1];" : "=r"(v) : "l"(p) : "memory"); return v; }
template <u32 M> DEV void rld128(uint4& v, const void* p, u32 tag) {
  asm volatile("{.reg .pred p; .reg .u32 t; lop3.b32 t,%0,%5,%6,0x28; setp.ne.u32 p,t,0; @p ld.relaxed.gpu.global.v4.u32 {%0,%1,%2,%3},[%4];}"
               : "+r"(v.x), "+r"(v.y), "+r"(v.z), "+r"(v.w) : "l"(p), "r"(tag), "n"(M) : "memory");
}
template <u32 M> DEV void rld64(uint64_t& v, const void* p, u32 tag) {
  asm volatile("{.reg .pred p; .reg .u32 t, h; mov.b64 {t,h},%0; lop3.b32 t,t,%2,%3,0x28; setp.ne.u32 p,t,0; @p ld.relaxed.gpu.global.u64 %0,[%1];}" : "+l"(v) : "l"(p), "r"(tag), "n"(M) : "memory");
}
template <int L> DEV u32 lop3(u32 a, u32 b, u32 c) { u32 r; asm("lop3.b32 %0,%1,%2,%3,%4;" : "=r"(r) : "r"(a), "r"(b), "r"(c), "n"(L)); return r; }
DEV u32 ne3(u32 a, u32 b, u32 c) { u32 r; asm("lop3.b32 %0,%1,%2,%3,0x7e;" : "=r"(r) : "r"(a), "r"(b), "r"(c)); return r; }
DEV void pin(u32 zr, u32 a, u32 b = 0, u32 c = 0, u32 d = 0) { asm volatile("{.reg .pred p; setp.ne.u32 p,%0,0; @p st.shared.v4.u32 [%0],{%1,%2,%3,%4};}" ::"r"(zr), "r"(a), "r"(b), "r"(c), "r"(d) : "memory"); }
DEV void pin2(u32 zr, const void* a, const void* b) { asm volatile("{.reg .pred p; setp.ne.u32 p,%0,0; @p st.shared.v2.u64 [%0],{%1,%2};}" ::"r"(zr), "l"(a), "l"(b) : "memory"); }
DEV const char* rowa(const char* base, u32 key) { const char* r; asm("mad.wide.u32 %0,%1,288,%2;" : "=l"(r) : "r"(~key & 0x1ffc), "l"(base)); return r; }
DEV void str128(void* p, u32 x, u32 y, u32 z, u32 w) { asm volatile("st.relaxed.gpu.global.v4.u32 [%0],{%1,%2,%3,%4};" ::"l"(p), "r"(x), "r"(y), "r"(z), "r"(w) : "memory"); }
DEV void str64(void* p, u32 x, u32 y) { asm volatile("{.reg .u64 d; mov.b64 d,{%1,%2}; st.relaxed.gpu.global.u64 [%0],d;}" ::"l"(p), "r"(x), "r"(y) : "memory"); }
DEV void str32(void* p, u32 x) { asm volatile("st.relaxed.gpu.global.u32 [%0],%1;" ::"l"(p), "r"(x) : "memory"); }
DEV void str16(void* p, u32 x) { asm volatile("st.relaxed.gpu.global.u16 [%0],%1;" ::"l"(p), "h"((unsigned short)x) : "memory"); }
DEV uint4 ldg128(const void* p) { uint4 v; asm volatile("ld.global.nc.v4.u32 {%0,%1,%2,%3},[%4];" : "=r"(v.x), "=r"(v.y), "=r"(v.z), "=r"(v.w) : "l"(p)); return v; }
DEV uint2 ldg64(const void* p) { uint2 v; asm volatile("ld.global.nc.v2.u32 {%0,%1},[%2];" : "=r"(v.x), "=r"(v.y) : "l"(p)); return v; }
DEV u32 ldg32(const void* p) { u32 v; asm volatile("ld.global.nc.u32 %0,[%1];" : "=r"(v) : "l"(p)); return v; }
DEV u32 ldg16(const void* p) { unsigned short v; asm volatile("ld.global.nc.u16 %0,[%1];" : "=h"(v) : "l"(p)); return v; }
#define bsync(id, n) asm volatile("bar.sync %0,%1;" ::"n"(id), "n"(n) : "memory")
#define barrive(id, n) asm volatile("bar.arrive %0,%1;" ::"n"(id), "n"(n) : "memory")
DEV void bsyncr(u32 id) { asm volatile("bar.sync %0,96;" ::"r"(id) : "memory"); }
DEV void barriver(u32 id) { asm volatile("bar.arrive %0,96;" ::"r"(id) : "memory"); }
constexpr u32 BW = 0x0FEA, BS = 0x6532;
DEV void mb_init(u32 a, u32 n) { asm volatile("mbarrier.init.shared.b64 [%0],%1;" ::"r"(a), "r"(n) : "memory"); }
DEV void mb_arrive(u32 a) { asm volatile("mbarrier.arrive.shared.b64 _,[%0];" ::"r"(a) : "memory"); }
DEV void mb_expect(u32 a, u32 bytes) { asm volatile("mbarrier.arrive.expect_tx.shared.b64 _,[%0],%1;" ::"r"(a), "r"(bytes) : "memory"); }
DEV void mb_wait(u32 a, u32 ph = 0) {
  u32 ok; int it = 0;
  do { asm volatile("{.reg .pred p; mbarrier.try_wait.parity.shared.b64 p,[%1],%2; selp.u32 %0,1,0,p;}" : "=r"(ok) : "r"(a), "r"(ph) : "memory"); } while (!ok && ++it < SPIN);
}
template <int N> DEV void bulk_out(void* dst, u32 src) { asm volatile("cp.async.bulk.global.shared::cta.bulk_group [%0],[%1],%2;" ::"l"(dst), "r"(src), "n"(N) : "memory"); }
constexpr u32 WSH = 41472;
DEV void l2_line(const void* p) { asm volatile("prefetch.global.L2 [%0];" ::"l"(p) : "memory"); }
template <int N> DEV void l2_pre(const void* p) { asm volatile("cp.async.bulk.prefetch.L2.global [%0],%1;" ::"l"(p), "n"(N) : "memory"); }
DEV void tma3d(u32 dst, const CUtensorMap* tm, u32 mb, int c0, int c2) {
  asm volatile("cp.async.bulk.tensor.3d.shared::cluster.global.mbarrier::complete_tx::bytes [%0],[%1,{%3,0,%4}],[%2];"
               ::"r"(dst), "l"((uint64_t)tm), "r"(mb), "r"(c0), "r"(c2) : "memory");
}
DEV float blo(u32 w) { return __uint_as_float(w << 16); }
DEV float bhi(u32 w) { return __uint_as_float(w & 0xffff0000u); }
DEV u32 pk_bf(float lo, float hi) { u32 r; asm("cvt.rn.bf16x2.f32 %0,%1,%2;" : "=r"(r) : "f"(hi), "f"(lo)); return r; }
DEV u32 pk_hf(float lo, float hi) { u32 r; asm("cvt.rn.f16x2.f32 %0,%1,%2;" : "=r"(r) : "f"(hi), "f"(lo)); return r; }
DEV float rbf(float x) { return __uint_as_float(pk_bf(0.f, x) & 0xffff0000u); }
DEV u32 bfma(u32 a, u32 b, u32 c) { u32 r; asm("fma.rn.bf16x2 %0,%1,%2,%3;" : "=r"(r) : "r"(a), "r"(b), "r"(c)); return r; }
DEV u32 bmul(u32 a, u32 b) { u32 r; asm("mul.rn.bf16x2 %0,%1,%2;" : "=r"(r) : "r"(a), "r"(b)); return r; }
DEV u32 badd(u32 a, u32 b) { u32 r; asm("add.rn.bf16x2 %0,%1,%2;" : "=r"(r) : "r"(a), "r"(b)); return r; }
DEV u32 hadd(u32 a, u32 b) { u32 r; asm("add.rn.f16x2 %0,%1,%2;" : "=r"(r) : "r"(a), "r"(b)); return r; }
DEV u32 hfma(u32 a, u32 b, u32 c) { u32 r; asm("fma.rn.f16x2 %0,%1,%2,%3;" : "=r"(r) : "r"(a), "r"(b), "r"(c)); return r; }
struct C2 { u32 re, im; };
DEV C2 cm2(C2 a, C2 b) {
  const __half2 ar = *reinterpret_cast<__half2*>(&a.re), ai = *reinterpret_cast<__half2*>(&a.im), br = *reinterpret_cast<__half2*>(&b.re), bi = *reinterpret_cast<__half2*>(&b.im);
  __half2 re = __hfma2(ar, br, __hneg2(__hmul2(ai, bi))), im = __hfma2(ar, bi, __hmul2(ai, br));
  return {*reinterpret_cast<u32*>(&re), *reinterpret_cast<u32*>(&im)};
}
DEV C2 pk2(const float2 (&a)[2]) { return {pk_hf(a[0].x, a[1].x), pk_hf(a[0].y, a[1].y)}; }
DEV C2 pk2c(const float2 (&a)[2]) { return {pk_hf(a[0].x, a[1].x), pk_hf(-a[0].y, -a[1].y)}; }
DEV u32 cpy(u32 x, u32 zr, int alt) {
  u32 r;
  if (alt) asm volatile("xor.b32 %0,%1,%2;" : "=r"(r) : "r"(x), "r"(zr)); else asm volatile("mad.lo.u32 %0,%2,%2,%1;" : "=r"(r) : "r"(x), "r"(zr));
  return r;
}
template <int N> DEV void inc(u32& x) { asm volatile("add.u32 %0,%0,%1;" : "+r"(x) : "n"(N)); }
DEV u32 opq(u32 x) { u32 r; asm volatile("mov.u32 %0,%1;" : "=r"(r) : "r"(x)); return r; }
DEV u32 chan(u32 b, u32 i) { return 16 * (b >> 2) + 2 * (b & 3) + (i & 1) + 4 * (i & 2); }
DEV u32 row16(u32 lane) { const u32 r0 = (lane & 7) + ((lane >> 3) & 1) + 8 * (lane >> 4) - 1; return (r0 ^ ((r0 >> 3) & 3)) * 16; }
DEV u32 clk() { u32 r; asm volatile("mov.u32 %0,%%clock;" : "=r"(r)::"memory"); return r; }
DEV void wait_clk(u32 t, int d) { while ((int)(clk() - t) < d); }
DEV float ex2(float x) { float r; asm("ex2.approx.ftz.f32 %0,%1;" : "=f"(r) : "f"(x)); return r; }
DEV float rcpf(float x) { float r; asm("rcp.approx.ftz.f32 %0,%1;" : "=f"(r) : "f"(x)); return r; }
DEV float2 cmul(float2 a, float2 b) { return make_float2(fmaf(a.x, b.x, -a.y * b.y), fmaf(a.x, b.y, a.y * b.x)); }
DEV float2 csq(float2 a) { return make_float2(fmaf(a.x, a.x, -a.y * a.y), (a.x + a.x) * a.y); }
DEV float2 cexp(float lr2, float th) {
  const float m = ex2(lr2);
  return make_float2(m * __cosf(th), m * __sinf(th));
}
DEV float silu_f(float v) { return v * rcpf(1.f + ex2(-1.4426950408889634f * v)); }
constexpr u32 B2P64 = 0x5F805F80u, B2M64 = 0x1F801F80u, BONE = 0x3F803F80u;
constexpr u32 MODJ = 18 * 128;
DEV float sqrta(float x) { float r; asm("sqrt.approx.ftz.f32 %0,%1;" : "=f"(r) : "f"(x)); return r; }
DEV u32 fu(float x) { return __float_as_uint(x); }
DEV float uf(u32 x) { return __uint_as_float(x); }
DEV void mma_hf_o(float (&d)[4], const float (&c)[4], const u32 (&a)[4], u32 b0, u32 b1) {
  asm("mma.sync.aligned.m16n8k16.row.col.f32.f16.f16.f32 {%0,%1,%2,%3},{%4,%5,%6,%7},{%8,%9},{%10,%11,%12,%13};"
      : "=f"(d[0]), "=f"(d[1]), "=f"(d[2]), "=f"(d[3]) : "r"(a[0]), "r"(a[1]), "r"(a[2]), "r"(a[3]), "r"(b0), "r"(b1), "f"(c[0]), "f"(c[1]), "f"(c[2]), "f"(c[3]));
}

DEV void mma_hf_t(float (&c)[4], const u32 (&a)[4], u32 b0, u32 b1) { mma_hf(c, a[0], a[1], a[2], a[3], b0, b1); }
DEV void cpa16(u32 dst, const void* src) { asm volatile("cp.async.cg.shared.global [%0],[%1],16;" ::"r"(dst), "l"(src) : "memory"); }
DEV void tm_pre(const CUtensorMap* tm) { asm volatile("prefetch.tensormap [%0];" ::"l"((uint64_t)tm) : "memory"); }
#define PROXY_FENCE() asm volatile("fence.proxy.async.shared::cta;" ::: "memory")
struct Prm {
  const char *la, *ai, *cr, *ci, *ldt;
  u32 zero, glo, ghi;
  const char *x, *c;
  char* gs;
  const char *dsk, *wr, *wg, *wu, *wd;
  char* out;
};
DEV char* gptr(const Prm& p, u32 lo) { char* r; asm("mov.b64 %0,{%1,%2};" : "=l"(r) : "r"(lo), "r"(p.ghi)); return r; }
DEV u32 uni(const Prm& p, u32 x) { return x >> p.zero; }
DEV u32 rowo(u32 base, u32 key) { return (~key & 0x1ffc) * 288 + base; }
constexpr float LOG2E = 1.4426950408889634f, F2P64 = 1.8446744073709552e19f, F2M64 = 5.421010862427522e-20f;

template <int S> DEV void y_store(float c0, float c1, float c2, float c3, u32 F, u32 pml, char* yp) {
  str32(yp, bmul(pk_bf(c0, c2), F) | pml);
  str32(yp + S, bmul(pk_bf(c1, c3), F) | pml);
}
DEV u32 sgn2(u32 a, u32 x, u32 y) { return opq(((a - x) >> 31) + ((a - y) >> 31)); }
DEV void merge4(u32 (&h)[8], uint4 a, uint4 b) {
  const u32 e1 = min(a.x, b.x), e2 = max(a.z, b.z), o1 = min(a.y, b.y), o2 = max(a.w, b.w), o0 = max(a.y, b.y), e3 = min(a.z, b.z);
  const u32 f1 = max(e1, e2), f2 = min(e1, e2), p1 = max(o1, o2), p2 = min(o1, o2);
  h[0] = max(a.x, b.x); h[1] = max(o0, f1); h[2] = min(o0, f1); h[3] = max(p1, f2); h[4] = min(p1, f2); h[5] = max(p2, e3); h[6] = min(p2, e3); h[7] = min(a.w, b.w);
}
DEV void top8(u32 (&a)[8], uint4 l, uint4 m) {
  u32 b[8];
  merge4(b, l, m);
#pragma unroll
  for (int i = 0; i < 8; i++) a[i] = max(a[i], b[7 - i]);
#pragma unroll
  for (int s = 4; s; s >>= 1)
#pragma unroll
    for (int i = 0; i < 8; i++) if (!(i & s)) { const u32 x = a[i], y = a[i + s]; a[i] = max(x, y); a[i + s] = min(x, y); }
}
#define POLL(load, cond_bad, code) { int it_ = 0; do { load; } while (__any_sync(~0u, (cond_bad)) & (++it_ <= SPIN)); if (it_ > SPIN) { ERRF(code); } TSN(code, it_); }
DEV u32 tmask(u32 it, u32 m) { u32 r; asm volatile("{.reg .pred p; setp.ne.u32 p,%1,0; selp.u32 %0,%2,0,p;}" : "=r"(r) : "r"(it), "r"(m)); return r; }
#define POLLM(load, bad, M, code) { u32 it_ = SPIN + (tid >> 16), m_; do { m_ = tmask(--it_, M); load; } while (__any_sync(~0u, (bad) & m_)); if (!it_) { ERRF(code); } TSN(code, SPIN - it_); }
#define POLLS(use, load, bad, M, code) { u32 it_ = SPIN + (tid >> 16); for (;;) { const u32 m_ = tmask(--it_, M); use; if (!__any_sync(~0u, (bad) & m_)) break; load; } if (!it_) { ERRF(code); } TSN(code, SPIN - it_); }
#define POLLW(load, cond_bad, code) { int it_ = 0; while (__any_sync(~0u, (cond_bad))) { if (++it_ > SPIN) { ERRF(code); break; } load; } TSN(code, it_); }

#define DOWN(E) if (tid == (b < 108 ? 288 : ~0u)) { const u32 c0 = 64 * (b % 9), c2 = 4 * (b / 9); \
    if (!D0C && E == 1) { mb_expect(SM_MB + 24, 49152); tma3d(SM_TAP, tm_down, SM_MB + 24, c0, c2); } \
    if (DE1 == E) tma3d(SM_WD, tm_down, SM_MB + 24, c0, c2 + 1); \
    if (DE2 == E) tma3d(SM_WD + 12288, tm_down, SM_MB + 24, c0, c2 + 2); \
    if (DE3 == E) tma3d(SM_WD + 24576, tm_down, SM_MB + 24, c0, c2 + 3); }
#define OUTR() { const u32 tl = 4 * ((lane >> 1) & 1) + ((lane >> 2) & 3) + 8 * (lane & 1); \
    bulk_out<1152>(p.out + (uni(p, b * BLK) + tl * 1152), SM_XST + ((lane & 2) + 4 * (lane & 1) + ((lane >> 2) & 1) + (lane & 8)) * ROW); \
    asm volatile("cp.async.bulk.commit_group;" ::: "memory"); }
struct FA { u32 tid, ba, ra, sa, ad, as; };
DEV FA ffn_addr(const Prm& p, u32 tid, u32 b) {
  const u32 w = tid >> 5, lane = tid & 31, kq = w & 3, tg = w >> 2, t = 7 - w;
  FA f = {tid, SM_XS + (lane & 7) * ROW + (18 * kq + (lane >> 3)) * 16, SM_RED + (8 * tg + kq) * 512 + lane * 16, w >= uni(p, 3 + (b & 1)) && w < 8 ? SM_RED + t * 2048 + lane * 16 : 0,
          (t < 4 ? uni(p, p.glo + G_ACT + 512 * b) + 128 * t : uni(p, p.glo + G_ACT + (512 + (b >> 1)) * 128)) + lane * 4, uni(p, p.glo + G_ACT + (b / 9) * 6144) + tid * 16};
  if (AW & 2) { pin(tid >> 16, f.ba, f.ra, f.sa, tid); pin(tid >> 16, f.ad, f.as); }
  return f;
}
DEV void ffn_tail(const Prm& p, const CUtensorMap* tm_down, uint4 (&A)[24], const FA f, const u32 b, const u32 par, const u32 okl) {
  const u32 tid = f.tid, w = tid >> 5, lane = tid & 31, g = lane >> 2, q = lane & 3, tg = w >> 2, zr = tid >> 16;
  const u32 pm = par ? TAGM : 0, kt = par * 3, ba = f.ba, ra = f.ra;
  char* const gs = p.gs;
  __syncthreads();
  TS(25);
  {
    float c0[2][4] = {}, c1[2][4] = {};
    uint4 bb[5];
#pragma unroll
    for (int s = 0; s < 5; s++) bb[s] = ldsm4(ba + s * 64);
#define BX(s) (s & 1 ? bb[s >> 1].z : bb[s >> 1].x), (s & 1 ? bb[s >> 1].w : bb[s >> 1].y)
    if (!(GX & 2)) {
      DOWN(5);
#pragma unroll
      for (int s = 0; s < 9; s++) mma_bf(c0[s & 1], A[s].x, A[s].y, A[s].z, A[s].w, BX(s));
      if (tg < 2) {
#pragma unroll
        for (int s = 0; s < 9; s++) mma_bf(c1[s & 1], A[9 + s].x, A[9 + s].y, A[9 + s].z, A[9 + s].w, BX(s));
        sts128(ra + 2048, fu(c1[0][0] + c1[1][0]), fu(c1[0][1] + c1[1][1]), fu(c1[0][2] + c1[1][2]), fu(c1[0][3] + c1[1][3]));
      }
    } else if (tg < 2) {
#pragma unroll
      for (int s = 0; s < 9; s++) {
        mma_bf(c0[s & 1], A[s].x, A[s].y, A[s].z, A[s].w, BX(s));
        mma_bf(c1[s & 1], A[9 + s].x, A[9 + s].y, A[9 + s].z, A[9 + s].w, BX(s));
      }
      sts128(ra + 2048, fu(c1[0][0] + c1[1][0]), fu(c1[0][1] + c1[1][1]), fu(c1[0][2] + c1[1][2]), fu(c1[0][3] + c1[1][3]));
    } else {
      DOWN(5);
#pragma unroll
      for (int s = 0; s < 9; s++) mma_bf(s & 2 ? c1[s & 1] : c0[s & 1], A[s].x, A[s].y, A[s].z, A[s].w, BX(s));
#pragma unroll
      for (int i = 0; i < 4; i++) c0[1][i] += c1[0][i] + c1[1][i];
    }
    sts128(ra, fu(c0[0][0] + c0[1][0]), fu(c0[0][1] + c0[1][1]), fu(c0[0][2] + c0[1][2]), fu(c0[0][3] + c0[1][3]));
  }
  const u32 atag = q ? 0 : pm, acs = SM_AC + tid * 16, acl = SM_AC + lane * 16;
  if (GX & 4) pin(zr, atag, acs, acl, kt);
  TS(39);
  if (!(GX & 1)) __syncthreads();
  if (!f.sa) { if (GX & 1) bsync(0, 384); }
  else {
    if (GX & 1) bsync(0, 384);
    float s[4];
    const uint4 u0 = lds128(f.sa), u1 = lds128(f.sa + 512), u2 = lds128(f.sa + 1024), u3 = lds128(f.sa + 1536);
    s[0] = (uf(u0.x) + uf(u1.x)) + (uf(u2.x) + uf(u3.x)); s[1] = (uf(u0.y) + uf(u1.y)) + (uf(u2.y) + uf(u3.y));
    s[2] = (uf(u0.z) + uf(u1.z)) + (uf(u2.z) + uf(u3.z)); s[3] = (uf(u0.w) + uf(u1.w)) + (uf(u2.w) + uf(u3.w));
    const u32 sg = pk_bf(silu_f(rbf(s[0])), silu_f(rbf(s[1])));
    str32(gptr(p, f.ad), bmul(sg, bmul(pk_bf(s[2], s[3]), B2M64)) | atag);
  }
  TS(26);
  const bool fin = w == (b < 72 ? 8 : ~0u);
  u32 kg;
  uint4 xt;
  const char* xs;
  if (fin) { kg = lds32(SM_SLOT + 4 * g); xs = gptr(p, rowo(uni(p, p.glo + G_Y + 16 * b), kg)); xt = ldr128(xs); }
  if (b < 108) {
    const char* const as = gptr(p, f.as);
    uint4 a = ldr128(as);
    char* const dst = gptr(p, uni(p, p.glo + G_PART + b * 2048) + w * 512 + lane * 8);
    if (w < 4) {
      const u32 aa = SM_WD + (8 * (lane >> 4) + (lane & 7)) * 128 + (((2 * w + ((lane >> 3) & 1)) ^ (lane & 7)) << 4);
      mb_wait(SM_MB + 24);
#pragma unroll
      for (int s = 0; s < 24; s++) A[s] = ldsm4t(aa + (s < 6 ? SM_TAP - SM_WD : -12288) + s * 2048);
      if (AW & 2) pin2(zr, dst, as);
    }
    conv();
    TS(28);
    if (!(GX & 16)) {
      POLLW(rld128<TAGM>(a, as, pm), (a.x ^ pm) & TAGM, 9);
      sts128(acs, a.x, a.y, a.z, a.w); sts32(acs, a.x & ~TAGM);
    } else
    POLLS({ sts128(acs, a.x, a.y, a.z, a.w); sts32(acs, a.x & ~TAGM); }, rld128<TAGM>(a, as, pm), a.x ^ pm, TAGM, 9);
    TS(27);
    if (w < 4) {
      bsync(8, 384);
      float c[4][4] = {};
#pragma unroll
      for (int s = 0; s < 12; s++) {
        const uint4 bb = ldsm4t(acl + s * 512);
        mma_bf(c[2 * (s & 1)], A[2 * s].x, A[2 * s].y, A[2 * s].z, A[2 * s].w, bb.x, bb.y);
        mma_bf(c[2 * (s & 1) + 1], A[2 * s + 1].x, A[2 * s + 1].y, A[2 * s + 1].z, A[2 * s + 1].w, bb.z, bb.w);
      }
      u32 o[4];
#pragma unroll
      for (int i = 0; i < 4; i++) o[i] = fu((c[0][i] + c[1][i]) + (c[2][i] + c[3][i]));
      str64(dst, (o[0] & ~3u) | kt, o[1]); str64(dst + 256, (o[2] & ~3u) | kt, o[3]);
      TS(29);
    } else barrive(8, 384);
  }
  if (OUTB == 7 && w == 10 && okl < lds32(SM_SLOT + 28)) OUTR();
  if (fin) {
    const u32 ta = clk();
    const char* src = gptr(p, uni(p, p.glo + G_PART + b * 256) + lane * 8);
    const u32 co = uni(p, 16 * b) + 4 * q, gw = lds32(SM_MODS + 5760 + co), hw = lds32(SM_XS + g * ROW + co);
    const float sgm = rcpf(1.f + ex2(-LOG2E * bhi(kg ^ (~((int)kg >> 31) | 0x80000000))));
    char* const dst = p.out + rowo(co, kg);
    conv();
    POLLW(rld128<TAGM>(xt, xs, TAGR), (xt.x ^ TAGR) & TAGM, 10);
    const u32 x1w = (q & 2) ? ((q & 1) ? xt.w : xt.z) : ((q & 1) ? xt.y : bmul(xt.x ^ TAGR, B2P64));
    const u32 sg2 = bmul(pk_bf(sgm, sgm), B2P64);
    pin(zr, x1w, gw, hw, sg2); pin2(zr, dst, src);
    uint64_t v[12];
#pragma unroll
    for (int j = 0; j < 12; j++) v[j] = 1;
    float s0, s1;
    if (PD) wait_clk(ta, PD);
    conv();
    TS(13);
#define VL(j) (u32)v[j]
#define VS(j, s) ((uf((u32)(v[j] >> s)) + uf((u32)(v[j + 1] >> s))) + (uf((u32)(v[j + 2] >> s)) + uf((u32)(v[j + 3] >> s))))
    u32 res;
    POLLM({ _Pragma("unroll") for (int j = 0; j < 12; j++) rld64<3>(v[j], src + j * 9 * 2048, kt);
            s0 = VS(0, 0) + VS(4, 0) + VS(8, 0); s1 = VS(0, 32) + VS(4, 32) + VS(8, 32);
            res = opq(badd(x1w, bmul(gw, badd(hw, bmul(movm(pk_bf(s0, s1)), sg2))))); TSRND(); },
          lop3<0xfe>(ne3(VL(0), VL(1), kt), ne3(VL(2), VL(3), kt), ne3(VL(4), VL(5), kt)) |
          lop3<0xfe>(ne3(VL(6), VL(7), kt), ne3(VL(8), VL(9), kt), ne3(VL(10), VL(11), kt)), 3, 11);
    asm volatile("st.global.u32 [%0],%1;" ::"l"(dst), "r"(res) : "memory");
    if (b == 0 && lane == 0) str32(gs + G_EP, par);
    TS(30); TSE();
  }
  if (w == 10) asm volatile("cp.async.bulk.wait_group.read 0;" ::: "memory");
}

DEV u32 y_lo(const Prm& p, u32 tid, u32 b) {
  const u32 ua = uni(p, p.glo + G_Y + b * 128), ub = uni(p, p.glo + 16384 + (b & ~3) * BLK + (b & 3) * 512);
  return (tid < 256 ? ua : ub) + (((tid & 2) * 4) | ((tid >> 2) & 4)) * (tid < 256 ? BLK : 32) + (tid >> 5) * (16 * BLK) + ((tid >> 2) & 3) * 32 + (tid & 1) * 16;
}
DEV void post_conv(const Prm& p, const CUtensorMap* tm_down, const u32 tid, const u32 b, const u32 b3) {
  const u32 w = tid >> 5, lane = tid & 31;
  const u32 g = lane >> 2, q = lane & 3, e = g >> 2, h = (g >> 1) & 1, hi = g & 1;
  const u32 pm = lds32(SM_THR + 4), par = pm >> 30;
  char* const gs = p.gs;
  const u32 cho = 128 * w + 64 * e + 16 * q;
  u32 x1[4][4], h2[4][4], key[4], lt;
  u32 okl = ~0u;
  FA fa;
  uint4 A[24];
#define AROW(t) const u32 arow = 144 * ((t >> 5) & 3) + ((t >> 1) & 8) + (t & 7), ab = (t & 8) ? SM_UP : SM_GATE;
#define AFRAG9() { _Pragma("unroll") for (int s = 0; s < 9; s++) A[s] = ldsm4t(ab + SLV + arow * 16 + s * 256); }
#define AFRAG18() { const u32 t3 = opq(tid); AROW(t3); if (t3 < 256) { const u32 aa = ab + arow * 64 + ((((t3 >> 6) & 2) ^ ((t3 & 7) >> 1)) << 4); \
      _Pragma("unroll") for (int s = 0; s < 9; s++) { A[s] = ldsm4t(aa + s * 1024); A[9 + s] = ldsm4t((aa ^ 16) + s * 1024); } } else AFRAG9(); }
  if (w < 9) {
    const char* const ys = gptr(p, y_lo(p, tid, b));
    uint4 yv[4];
#pragma unroll
    for (int v = 0; v < 4; v++) yv[v].x = INVAL;
    const u32 tg0 = b < YL ? pm : INVAL;
    if (w >= 4) { pin2(tid >> 16, ys, ys); bsync(12, N12); TS(18); }
#pragma unroll
    for (int v = 0; v < 4; v++) rld128<TAGM>(yv[v], ys + v * BLK, tg0);
    const u32 tc = clk();
    const u32 ma = SM_MODS + cho, xa = SM_XST + (2 * h + 4 * hi) * ROW + cho;
    const uint4 sa = lds128(ma), ca = lds128(ma + 1152), ga = lds128(ma + 2304);
    const uint4 rb = lds128((g & 2) ? SM_ONE + 16 * hi : (ma ^ 64) + 8064 + 1152 * hi);
    const u32 saw[4] = {sa.x, sa.y, sa.z, sa.w}, caw[4] = {ca.x, ca.y, ca.z, ca.w}, gaw[4] = {ga.x, ga.y, ga.z, ga.w};
#pragma unroll
    for (int k = 0; k < 4; k++) {
      const uint2 st = lds64(SM_ST + 16 * (2 * h + 4 * hi + (k & 1) + 8 * (k >> 1)));
      const uint4 xv = lds128(xa + ((k & 1) + 8 * (k >> 1)) * ROW);
      x1[k][0] = xv.x; x1[k][1] = xv.y; x1[k][2] = xv.z; x1[k][3] = xv.w;
#pragma unroll
      for (int v = 0; v < 4; v++) x1[k][v] = badd(x1[k][v], bfma(bmul(badd(x1[k][v], st.x), st.y), caw[v], saw[v]));
    }
    const bool own = (q >> 1) == e;
    const u32 spw = SM_SP + (2 * w + e) * 320 + (g & 3) * 16 + (own ? ((q & 1) == h ? 4 : 12) : 8 - 8 * (q & 1));
    if (SMD && w < 4) asm volatile("setmaxnreg.dec.sync.aligned.u32 168;");
    if (b >= YL) wait_clk(tc, YD);
    conv();
    TS(13);
    POLLW(_Pragma("unroll") for (int v = 0; v < 4; v++) rld128<TAGM>(yv[v], ys + v * BLK, pm), lop3<0xa8>(ne3(yv[0].x, yv[1].x, pm), ne3(yv[2].x, yv[3].x, pm), TAGM), 5);
    TS(19);
    if (!SMD && w < 4) asm volatile("setmaxnreg.dec.sync.aligned.u32 168;");
#pragma unroll
    for (int k = 0; k < 4; k += 2) {
      float X[4] = {}, Y[4] = {}, R[4] = {};
#pragma unroll
      for (int v = 0; v < 4; v++) {
        const u32 y0 = k ? yv[v].z : yv[v].x & ~TAGM, y1 = k ? yv[v].w : yv[v].y;
        x1[k][v] = bfma(movm(y0), gaw[v], x1[k][v]);
        x1[k + 1][v] = bfma(movm(y1), gaw[v], x1[k + 1][v]);
        mma8_bf(X, x1[k][v], x1[k + 1][v], x1[k][v]); mma8_bf(Y, x1[k][v], x1[k + 1][v], x1[k + 1][v]);
        if (v & 1) mma_bf(R, x1[k][v - 1], x1[k + 1][v - 1], x1[k][v], x1[k + 1][v], v & 2 ? rb.z : rb.x, v & 2 ? rb.w : rb.y);
      }
      sts32(spw + k * 64, fu(own ? (hi ? X[1] : X[0]) : R[0] + R[1]));
      sts32(spw + k * 64 + 64, fu(own ? (hi ? Y[3] : Y[2]) : R[2] + R[3]));
    }
    barrive(1, N1);
    TS(36);
    if (AFP) { asm volatile("setmaxnreg.inc.sync.aligned.u32 168;"); mb_wait(SM_MB + 8); mb_wait(SM_MB + 16); }
    const uint4 sb = lds128(ma + 3456), cb = lds128(ma + 4608), gb = lds128(ma + 5760);
    const u32 sbw[4] = {sb.x, sb.y, sb.z, sb.w}, cbw[4] = {cb.x, cb.y, cb.z, cb.w}, gbw[4] = {gb.x, gb.y, gb.z, gb.w};
    const u32 t3 = opq(tid), zr = t3 >> 16;
    AROW(t3);
    const u32 aa = ab + arow * 64 + ((((t3 >> 6) & 2) ^ ((t3 & 7) >> 1)) << 4), sta = SM_ST2 + 16 * (g & 3);
    const u32 rowl = uni(p, p.glo + b * BLK) + (4 * h + 8 * hi) * 1152 + cho;
    char* const rowp = gptr(p, rowl);
    if (AFP) { pin(zr, aa, sta, xa); pin2(zr, rowp, rowp); }
    bsync(2, 320);
    TS(37);
    uint4 st[4];
#pragma unroll
    for (int k = 0; k < 4; k++) st[k] = lds128(sta + 64 * k);
    lt = lds32(SM_THR);
#define AFL() { _Pragma("unroll") for (int s = 0; s < 9; s++) { A[s] = ldsm4t(aa + s * 1024); A[9 + s] = ldsm4t((aa ^ 16) + s * 1024); } }
    if (AFP && (AFM >> w & 1)) { if (w < 8) AFL() else AFRAG9(); }
#pragma unroll
    for (int k = 0; k < 4; k++) {
      key[k] = st[k].w;
      u32 o[4];
#pragma unroll
      for (int v = 0; v < 4; v++) {
        const u32 d = badd(x1[k][v], st[k].x), z = bfma(d, st[k].y, bmul(d, st[k].z));
        h2[k][v] = FH ? bfma(z, cbw[v], sbw[v]) : badd(bmul(z, cbw[v]), sbw[v]);
        o[v] = FO ? bfma(gbw[v], h2[k][v], x1[k][v]) : badd(x1[k][v], bmul(gbw[v], h2[k][v]));
      }
      h2[k][0] = bmul(h2[k][0], B2M64) | TAGR; x1[k][0] = bmul(x1[k][0], B2M64) | TAGR;
      if (key[k] >= lt) str128(rowp + k * 1152, h2[k][0], h2[k][1], h2[k][2], h2[k][3]);
      sts128(xa + ((k & 1) + 8 * (k >> 1)) * ROW, o[0], o[1], o[2], o[3]);
    }
    barrive(3, 320);
    TS(21);
    if (!AFP) { asm volatile("setmaxnreg.inc.sync.aligned.u32 168;"); mb_wait(SM_MB + 8); mb_wait(SM_MB + 16); AFRAG18(); }
    else if (!(AFM >> w & 1)) { if (w < 8) AFL() else AFRAG9(); }
    TS(22);
    const u32 rr = tid * 57 >> 12, rc = tid * 16 - rr * 1152, sl = SM_SLOT + 8 * rr;
    const u32 rb_ = p.glo + rc;
    const u32 km = max(max(key[0], key[1]), max(key[2], key[3])), xd = SM_XS + rr * (2 * ROW) + rc;
    if (RW & 2) { pin(tid >> 16, sl, km, xd); pin(tid >> 16, rb_, rowl); }
    fa = ffn_addr(p, tid | p.zero, b);
    bsync(6, 320);
    TS(24);
    const uint2 sk = lds64(sl);
    const char *r0 = gptr(p, rowo(rb_, sk.x)), *r1 = gptr(p, rowo(rb_, sk.y));
    uint4 rv[2] = {ldr128(r0), ldr128(r1)};
    barrive(15, 320);
    const u32 g8 = lds32(SM_SLOT + 28);
    if (__any_sync(~0u, km >= g8 && lt > g8)) {
      char* const rowq = gptr(p, opq(rowl));
#pragma unroll
      for (int k = 0; k < 4; k++) if (key[k] >= g8 && key[k] < lt) str128(rowq + k * 1152, h2[k][0], h2[k][1], h2[k][2], h2[k][3]);
    }
    bsync(5, 320);
    const uint2 sf = lds64(sl);
    const u32 f8 = lds32(SM_SLOT + 28);
    if (__any_sync(~0u, km >= f8)) {
      char* const rowq = gptr(p, opq(rowl));
#pragma unroll
      for (int k = 0; k < 4; k++) if (key[k] >= f8) str128(rowq + (G_Y + k * 1152), x1[k][0], x1[k][1], x1[k][2], x1[k][3]);
    }
    if (__any_sync(~0u, sf.x != sk.x || sf.y != sk.y)) {
      r0 = gptr(p, rowo(rb_, sf.x)); r1 = gptr(p, rowo(rb_, sf.y));
      rv[0].x = rv[1].x = INVAL;
    }
    if (!(GX & 8)) {
      POLLW({ rld128<TAGM>(rv[0], r0, TAGR); rld128<TAGM>(rv[1], r1, TAGR); }, ne3(rv[0].x, rv[1].x, TAGR) & TAGM, 8);
#pragma unroll
      for (int j = 0; j < 2; j++) sts128(xd + j * ROW, bmul(rv[j].x ^ TAGR, B2P64), rv[j].y, rv[j].z, rv[j].w);
    } else
    POLLS(_Pragma("unroll") for (int j = 0; j < 2; j++) { sts128(xd + j * ROW, rv[j].x, rv[j].y, rv[j].z, rv[j].w); sts32(xd + j * ROW, bmul(rv[j].x ^ TAGR, B2P64)); },
          { rld128<TAGM>(rv[0], r0, TAGR); rld128<TAGM>(rv[1], r1, TAGR); }, ne3(rv[0].x, rv[1].x, TAGR), TAGM, 8);
    TS(38);
  } else {
    u32 ok, lr;
    if (w == 10) {
      uint2 rc = lds64(SM_RC + 8 * min(lane, 17u));
      float r1 = lane < 18 ? uf(rc.x) : 0.f, r2 = lane < 18 ? uf(rc.y) : 0.f;
#pragma unroll 1
      for (int o = 16; o; o >>= 1) { r1 += __shfl_xor_sync(~0u, r1, o); r2 += __shfl_xor_sync(~0u, r2, o); }
      const u32 tl = 4 * ((lane >> 1) & 1) + ((lane >> 2) & 3) + 8 * (lane & 1), kl = (2047 - 16 * b - tl) << 2 | par * 3;
      const u32 kp = uni(p, p.glo + G_KEY + b * KST) + (tid >> 16);
      const u32 spr = SM_SP + (lane >> 4) * 9 * 320 + (lane & 15) * 16;
      TS(31);
      r2 += 0.f;
      const u32 nth = b < NB8 ? 7 : NEARLY - 1, ka = SM_KEY + 4 * (lane & 15), kb = SM_KEY + 2 * (lane & 16), lim = lane < 16 ? 8 : 0;
      pin(tid >> 16, kl, ka, kb, lim); pin(tid >> 16, kp);
      conv();
      bsync(1, N1);
      uint4 t = lds128(spr);
      float S1 = uf(t.x), S2 = uf(t.y), S3 = uf(t.z);
#pragma unroll
      for (int i = 1; i < 9; i++) { t = lds128(spr + i * 320); S1 += uf(t.x); S2 += uf(t.y); S3 += uf(t.z); }
      S1 += __shfl_xor_sync(~0u, S1, 16); S2 += __shfl_xor_sync(~0u, S2, 16); S3 += __shfl_xor_sync(~0u, S3, 16);
      const float mu = S1 * (1.f / 576.f), var = fmaxf(fmaf(-mu, mu, S2 * (1.f / 576.f)), 0.f);
      const float m = rbf(mu), rs = rcpf(rbf(sqrta(rbf(rbf(var) + 1e-5f))));
      const u32 rb = pk_bf(0.f, fmaf(fmaf(-m, r1, S3), rs, r2));
      ok = ((rb ^ (((int)rb >> 31) | 0x80000000)) & 0xffff0000u) | kl;
      const float rh = rbf(rs);
      const u32 oh = ok >> 1;
      sts32(ka, oh);
      __syncwarp();
      const uint4 o0 = lds128(kb), o1 = lds128(kb + 16);
      sts128(SM_ST2 + 16 * (lane & 15), pk_bf(-m, -m), pk_bf(rh, rh), pk_bf(rs - rh, rs - rh), ok);
      lr = opq(sgn2(oh, o0.x, o0.y) + sgn2(oh, o0.z, o0.w)) +
           opq(sgn2(oh, o1.x, o1.y) + sgn2(oh, o1.z, o1.w));
      lr += __shfl_xor_sync(~0u, lr, 16);
      asm volatile("{.reg .pred p; setp.lt.u32 p,%0,%1; @p st.relaxed.gpu.global.u32 [%2],%3;}" ::"r"(lr), "r"(lim), "l"(gptr(p, kp + 4 * lr)), "r"(ok) : "memory");
      if (lr == nth) sts32(SM_THR, ok);
      barrive(2, 320);
      barrive(13, 64);
      TS(20);
    } else if (w == 9) {
      if (DB1) bsync(1, N1); else { bsync(12, N12); wait_clk(clk(), DD); }
      PROXY_FENCE();
      DOWN(1);
    } else {
      const char* ks = gs + (G_KEY + (lane >> 1) * KST + (lane & 1) * 16);
      const u32 kt = par * 3;
      uint4 L[8];
      u32 H[8];
#define KBAD(j) ((L[j].x ^ kt) & 3)
#define KLD(j) L[j] = ldr128(ks + j * 16 * KST)
#pragma unroll
      for (int j = 0; j < 8; j++) L[j].x = INVAL;
      bsync(13, 64);
      wait_clk(clk(), b < KE ? KD : b < KF ? KDB : b < YL ? KDC : KD1);
      TS(34);
      POLL({ _Pragma("unroll") for (int j = 0; j < 8; j++) if (KBAD(j)) KLD(j);
             merge4(H, L[0], L[1]); top8(H, L[2], L[3]);
             asm volatile("" : "+r"(H[0]), "+r"(H[1]), "+r"(H[2]), "+r"(H[3]), "+r"(H[4]), "+r"(H[5]), "+r"(H[6]), "+r"(H[7])); TS(32); },
           KBAD(0) | KBAD(1) | KBAD(2) | KBAD(3) | KBAD(4) | KBAD(5), 6);
      u32 u = __reduce_max_sync(~0u, max(H[0], max(L[4].x, L[5].x)));
      top8(H, L[4], L[5]);
      TS(35);
#pragma unroll 1
      for (u32 pass = p.zero;; pass++) {
        u32 G[8], m[8];
        conv();
#pragma unroll
        for (int i = 0; i < 8; i++) G[i] = H[i];
        u32 x0 = G[0], x1 = G[1];
#pragma unroll
        for (int r = 0; r < 8; r++) {
          const u32 ur = u;
          const bool win = x0 == ur;
          if (r < 7) { x0 = max(x0 - ur, x1 - ur); u = __reduce_max_sync(~0u, x0); }
          m[r] = r ? m[r - 1] + ur : ur;
          if (r == 0) { if (KBAD(6)) KLD(6); if (KBAD(7)) KLD(7); }
#pragma unroll
          for (int i = 1; i < 7 - r; i++) G[i] = win ? G[i + 1] : G[i];
          x1 = G[1] - m[r];
          if ((r & 3) == 3) sts128(SM_SLOT + 4 * r - 12, m[r - 3], m[r - 2], m[r - 1], m[r]);
        }
        asm volatile("{.reg .pred p; setp.eq.u32 p,%0,0; @p bar.arrive 6,320;}" ::"r"(pass) : "memory");
        if (pass) break;
        TS(23);
        conv();
        POLLW({ if (KBAD(6)) KLD(6); if (KBAD(7)) KLD(7); }, KBAD(6) | KBAD(7), 7);
        if (!__any_sync(~0u, max(L[6].x, L[7].x) > m[7])) break;
        u = __reduce_max_sync(~0u, max(H[0], max(L[6].x, L[7].x)));
        top8(H, L[6], L[7]);
      }
      barrive(5, 320);
      TS(33);
    }
    asm volatile("setmaxnreg.inc.sync.aligned.u32 168;");
    mb_wait(SM_MB + 8); mb_wait(SM_MB + 16);
    AROW(tid);
    AFRAG9();
    fa = ffn_addr(p, tid | p.zero, b);
    TS(22);
    if (w == 10) {
      bsync(3, 320);
      PROXY_FENCE();
      if (lane < 16 && lr >= 8) OUTR();
      if (lane < 16 && lr < 8) okl = ok;
    } else if (w == 9) {
      bsync(15, 320);
      DOWN(4);
      TS(13);
    }
  }
  ffn_tail(p, tm_down, A, fa, b3, par, okl);
}

__global__ void __launch_bounds__(384, 1)
fused_kernel(const Prm p, const __grid_constant__ CUtensorMap tm_mod, const __grid_constant__ CUtensorMap tm_gate, const __grid_constant__ CUtensorMap tm_gs,
             const __grid_constant__ CUtensorMap tm_up, const __grid_constant__ CUtensorMap tm_us, const __grid_constant__ CUtensorMap tm_down) {
  extern __shared__ __align__(1024) unsigned char smem[];
  u32 la, ai, ldt; uint2 cr, ci;
  {
    const u32 t = threadIdx.x, d = t < 256 ? chan(blockIdx.x, t >> 5) : 512 + (blockIdx.x >> 1), o = d * 256 + 8 * (t & 31), o4 = o + ((t < 256 ? t >> 5 : t >> 3) & 4);
    asm volatile("{.reg .pred p; .reg .u16 h; setp.ne.u32 p,%7,0; @p ld.global.nc.u32 %0,[%8]; @p ld.global.nc.u32 %1,[%9]; @p ld.global.nc.v2.u32 {%2,%3},[%10];"
                 "@p ld.global.nc.v2.u32 {%4,%5},[%11]; @p ld.global.nc.u16 h,[%12]; cvt.u32.u16 %6,h;}"
                 : "=r"(la), "=r"(ai), "=r"(cr.x), "=r"(cr.y), "=r"(ci.x), "=r"(ci.y), "=r"(ldt)
                 : "r"(0x6ffu >> (t >> 5) & 1), "l"(p.la + o4), "l"(p.ai + o4), "l"(p.cr + o), "l"(p.ci + o), "l"(p.ldt + 2 * d));
  }
  const u32 t0 = clk();
  const u32 tid = __shfl_sync(~0u, threadIdx.x, threadIdx.x & 31), b = blockIdx.x + p.zero;
  const u32 w = tid >> 5, lane = tid & 31;
  const u32 g = lane >> 2, q = lane & 3, hi = g & 1;
  const u32 rho = b & 1, Ps = 512 + (b >> 1);
  char* const gs = p.gs;
  TS0();
  const bool kw = w != 8 && w != 11;
  const u32 ksig = w < 8 ? (w & 3) : 4, khf = w < 8 ? (w >> 2) : (w & 1);
  if (!kw) {
    if (tid == 352) {
#pragma unroll
      for (int i = 0; i < 5; i++) mb_init(SM_MB + 8 * i, i < 4 ? 1 : 64);
      asm volatile("fence.mbarrier_init.release.cluster;" ::: "memory");
      tm_pre(&tm_mod);
    }
    const char* cp = p.c + (576 * (w & 1) + 24 * min(lane, 23u));
    const uint2 c0 = ldg64(cp);
    la = c0.x; ai = c0.y; cr = ldg64(cp + 8); ci = ldg64(cp + 16);
  }
  u32 b3;
  asm volatile("shr.u32 %0,%1,%2;" : "=r"(b3) : "r"(blockIdx.x), "r"(p.zero));
  const u32 zr = tid >> 16;
  const u32 epv = ldr32(gs + (G_EP + zr));
  const u32 tp = SM_TAP + ksig * TAPS;
  if (kw && !khf) {
#pragma unroll 1
    for (u32 i = lane * 16; i < TAPS; i += 512) sts128(tp + i, 0, 0, 0, 0);
  }
  if (tid < 128) sts128(SM_INV + 16 * tid, INVAL, 0, 1, 0);
  if (tid >= 124) str128(gs + (tid >= 380 ? G_MOD + b * 128 + q * 16 : b * BLK + 16384 - 252 * 16 + tid * 16 + (tid < 252 ? G_Y + 2048 : 0)), INVAL, 0, 1, 0);
  if (tid == (b < 36 ? 352 : ~0u)) { while (clk() - t0 < DMOD); mb_expect(SM_MB, 36864); tma3d(SM_UP, &tm_mod, SM_MB, 32 * b, 0); }
  if (w < 9) {
    while ((int)(clk() - t0) < DX);
    const char* xp = p.x + (b * BLK + (lane >> 3) * 1152 + 128 * w + 16 * (lane & 7));
    const u32 xd = SM_XST + (((lane >> 3) & 1) + 8 * (lane >> 4)) * ROW + 128 * w + 16 * (lane & 7);
#pragma unroll
    for (int i = 0; i < 4; i++) cpa16(xd + 2 * ROW * i, xp + 4608 * i);
  }
  const u32 ktab = w < 8 ? SM_MODS + w * KTAB : SM_ZS + (w - 9) * KTAB;
  float k2048 = 0.f;
  if (kw) {
    u32 mx = __vmaxu2(__vmaxu2(cr.x & 0x7fff7fff, cr.y & 0x7fff7fff), __vmaxu2(ci.x & 0x7fff7fff, ci.y & 0x7fff7fff));
    const u32 E = max(__reduce_max_sync(~0u, max(mx & 0xffff, mx >> 16)) >> 7, 8u);
    TS(1);
    const float dt = rbf(ex2(blo(ldt) * LOG2E)), csc = uf((257 - E) << 23 | (fu(dt) & 0x7fffff));
    sts32(SM_SC + 16 * ksig + 12, fu(uf(fu(dt) & 0x7f800000) * uf((E - 2) << 23)));
    const u32 crw = khf ? cr.y : cr.x, ciw = khf ? ci.y : ci.x;
    float2 C[2], w4[2], w8[2], w16[2], w32[2], w64[2], w128[2], w256[2], w512[2], a1[2], a2[2], a3[2], t0[2], t1[2], s3[2];
#pragma unroll
    for (int m = 0; m < 2; m++) {
      const float lr2 = rbf(ex2((m ? bhi(la) : blo(la)) * LOG2E)) * dt * -LOG2E, th = (m ? bhi(ai) : blo(ai)) * dt;
      C[m] = make_float2((m ? bhi(crw) : blo(crw)) * csc, (m ? bhi(ciw) : blo(ciw)) * csc);
      const float2 w1 = cexp(lr2, th), w2 = csq(w1);
      w64[m] = cexp(64.f * lr2, 64.f * th);
      w4[m] = csq(w2); w8[m] = csq(w4[m]); w16[m] = csq(w8[m]); w32[m] = csq(w16[m]);
      w128[m] = csq(w64[m]); w256[m] = csq(w128[m]); w512[m] = csq(w256[m]);
      const float2 w1024 = csq(w512[m]);
      a1[m] = cmul(C[m], w1); a2[m] = cmul(C[m], w2); a3[m] = cmul(a1[m], w2);
      t0[m] = cmul(C[m], w1024); t1[m] = cmul(t0[m], w128[m]); s3[m] = cmul(w8[m], w16[m]);
      k2048 += fmaf(t0[m].x, w1024.x, -t0[m].y * w1024.y);
    }
    C2 B0[8], B1[8], B2[8], S[8];
    B0[0] = pk2(C); B0[1] = pk2(a1); B0[2] = pk2(a2); B0[3] = pk2(a3);
    const C2 h4 = pk2(w4), h256 = pk2(w256), h512 = pk2(w512);
#pragma unroll
    for (int i = 0; i < 4; i++) B0[4 + i] = cm2(B0[i], h4);
#pragma unroll
    for (int i = 0; i < 4; i++) B1[i] = cm2(B0[2 * i], h256);
    B1[4] = cm2(B0[0], h512); B1[5] = cm2(B0[4], h512);
    B1[6] = cm2(B1[4], h256); B1[7] = cm2(B1[5], h256);
    const u32 ta = ktab + lane * 128, f = ((lane & 3) << 5) | ((lane & 4) << 2);
#pragma unroll
    for (int i = 0; i < 8; i++) sts128(ta + ((i << 4) ^ f), B0[i].re, B0[i].im, B1[i].re, B1[i].im);
    B2[0] = pk2(t0); B2[1] = pk2(t1);
    B2[2] = cm2(B2[0], h256); B2[3] = cm2(B2[1], h256);
#pragma unroll
    for (int i = 0; i < 4; i++) B2[4 + i] = cm2(B2[i], h512);
    S[0] = {0x3C003C00u, 0u}; S[1] = pk2c(w8); S[2] = pk2c(w16); S[3] = pk2c(s3); S[4] = pk2c(w32);
#pragma unroll
    for (int i = 1; i < 4; i++) S[4 + i] = cm2(S[i], S[4]);
#pragma unroll
    for (int i = 0; i < 8; i++) sts128(ta + 4096 + ((i << 4) ^ f), B2[i].re, B2[i].im, S[i].re, S[i].im);
    const C2 m64 = pk2c(w64), m128 = pk2c(w128);
    sts128(ktab + 8192 + lane * 16, m64.re, m64.im, m128.re, m128.im);
    __syncwarp();
  } else {
    u32 sa = SM_SIL + 576 * (w & 1) + 24 * min(lane, 23u);
#pragma unroll 1
    for (int j = 0; j < 6; j++) {
      sts32(sa, pk_bf(silu_f(blo(la)), silu_f(bhi(la))));
      la = ai; ai = cr.x; cr.x = cr.y; cr.y = ci.x; ci.x = ci.y; sa += 4;
    }
    bsync(7, 64);
  }
  TS(2);
  const u32 pm = (__reduce_or_sync(~0u, epv) & 1) ? 0 : TAGM;
  sts32(SM_THR + 4, pm);
  if (w < 9) {
    asm volatile("cp.async.wait_all;" ::: "memory");
    __syncwarp();
    TS(4);
    if (tid == (b - 36 < 72 ? 256 : ~0u)) { mb_expect(SM_MB, 36864); tma3d(SM_UP, &tm_mod, SM_MB, 32 * b, 0); }
    const u32 xa = SM_XST + (lane & 15) * ROW + 128 * w + 16 * (lane >> 4);
    float s[4] = {}, X[2][4] = {}, Y[2][4] = {};
#pragma unroll
    for (int j = 0; j < 4; j++) {
      const uint4 a = ldsm4(xa + 32 * j);
      mma8_bf(X[0], a.x, a.y, a.x); mma8_bf(Y[0], a.x, a.y, a.y);
      mma8_bf(X[1], a.z, a.w, a.z); mma8_bf(Y[1], a.z, a.w, a.w);
      mma_bf(s, a.x, a.y, a.z, a.w, BONE, BONE);
    }
    uint4 t[4];
#pragma unroll
    for (int j = 0; j < 4; j++) t[j] = ldsm4t(xa + 32 * j);
    const float u0 = hi ? X[0][1] + X[1][1] : X[0][0] + X[1][0], u1 = hi ? Y[0][3] + Y[1][3] : Y[0][2] + Y[1][2];
    if (q == g >> 1) sts128(SM_SP + w * 128 + g * 16, fu(s[0]), fu(u0), fu(s[2]), fu(u1));
    bsync(1, 288);
    TS(7);
    const u32 spr = SM_SP + (lane & 7) * 16 + (lane & 8);
    const uint2 t8 = lds64(spr + 1024);
    const float f8 = lane < 16 ? 1.f : 0.f;
    float S1 = uf(t8.x) * f8, S2 = uf(t8.y) * f8;
#pragma unroll
    for (int i = 0; i < 4; i++) { const uint2 u = lds64(spr + (lane & 16) * 32 + i * 128); S1 += uf(u.x); S2 += uf(u.y); }
    S1 += __shfl_xor_sync(~0u, S1, 16); S2 += __shfl_xor_sync(~0u, S2, 16);
    const float mu = S1 * (1.f / 576.f), var = fmaxf(fmaf(-mu, mu, S2 * (1.f / 576.f)), 0.f);
    const float m = rbf(mu), rs = rcpf(rbf(sqrta(rbf(rbf(var) + 1e-5f))));
    const float ra = rs * 0.0625f;
    sts64(SM_AF + w * 128 + (lane & 15) * 8, fu(ra), fu(-m * ra));
    __syncwarp();
    TS(55);
    const uint4 f0 = lds128(SM_AF + w * 128 + q * 16), f1 = lds128(SM_AF + w * 128 + 64 + q * 16);
    const u32 zdst = SM_GATE + w * 2048 + (g >> 1) * 128 + (lane & 15) * 8;
    const u32 pz = (q & 1) ? 0 : pm;
#pragma unroll
    for (int j = 0; j < 8; j++) {
      const u32 x0 = j & 1 ? t[j >> 1].z : t[j >> 1].x, x1 = j & 1 ? t[j >> 1].w : t[j >> 1].y;
      sts64((j & 1 ? zdst ^ 64 : zdst) + 512 * (j >> 1), pk_hf(fmaf(blo(x0), uf(f0.x), uf(f0.y)), fmaf(bhi(x0), uf(f0.z), uf(f0.w))) | pz,
            pk_hf(fmaf(blo(x1), uf(f1.x), uf(f1.y)), fmaf(bhi(x1), uf(f1.z), uf(f1.w))));
    }
    TS(53);
    if (w < 8) barrive(15, 288);
    else {
      bsync(15, 288);
      TS(54);
      if (lane == 0) {
        PROXY_FENCE();
        bulk_out<BLK>(gs + b * BLK, SM_GATE);
        asm volatile("cp.async.bulk.commit_group;" ::: "memory");
        if (PFG & 1) l2_pre<WSH / 2>(p.wg + b * WSH);
      }
      const float rh = rbf(rs);
      sts128(SM_ST + 16 * (lane & 15), pk_bf(-m, -m), pk_bf(rh, rh), pk_bf(rs - rh, rs - rh), 0);
    }
    TS(5);
  }
  if (kw) {
    float D[5][4] = {};
    u32 ta = ktab + q * 128 + ((g ^ (q << 1)) << 4), tm = ktab + 8192 + q * 16;
#pragma unroll 2
    for (int s = 0; s < 8; s++) {
      const uint4 ca = lds128(ta), cb = lds128(ta + 4096), ma = lds128(tm);
      ta = (ta + 512) ^ 16; tm += 64;
      k2048 += __shfl_xor_sync(~0u, k2048, 16 >> s);
      const C2 s0 = {cb.z, cb.w}, s1 = cm2(s0, {ma.x, ma.y}), s2 = cm2(s0, {ma.z, ma.w}), s3 = cm2(s1, {ma.z, ma.w});
      mma_hf(D[0], s0.re, s1.re, s0.im, s1.im, ca.x, ca.y);
      mma_hf(D[2], s0.re, s1.re, s0.im, s1.im, ca.z, ca.w);
      mma_hf(D[4], s0.re, s1.re, s0.im, s1.im, cb.x, cb.y);
      mma_hf(D[1], s2.re, s3.re, s2.im, s3.im, ca.x, ca.y);
      mma_hf(D[3], s2.re, s3.re, s2.im, s3.im, ca.z, ca.w);
    }
    TS(3);
    const u32 xa = (w < 8 ? SM_MODS + (4 + ksig) * KTAB : SM_ZS) + lane * 16;
    if (khf) {
      __syncwarp();
#pragma unroll
      for (int j = 0; j < 5; j++) sts128(xa + 512 * j, fu(D[j][0]), fu(D[j][1]), fu(D[j][2]), fu(D[j][3]));
      if (lane == 0) sts32(xa + 2560, fu(k2048));
      asm volatile("bar.arrive %0,64;" ::"r"(2 + ksig) : "memory");
    } else {
      const u32 t1 = tp + (q < 2 ? (128 + 4 * g + 2 * q) * 4 : T3 * 4 + ((32 * q - 64 + g) ^ 1) * 2);
      const u32 x = 16 * q + (g >> 1) + hi + 1, tb = tp + (hi ? T7E : T9E) * 4 - 4;
      const u32 te = tb + (x + 2 * (x & 1)) * 2, to = tb + TEO * 4 + (x ^ 1) * 2;
      asm volatile("bar.sync %0,64;" ::"r"(2 + ksig) : "memory");
#pragma unroll
      for (int j = 0; j < 5; j++) { const uint4 t = lds128(xa + 512 * j); D[j][0] += uf(t.x); D[j][1] += uf(t.y); D[j][2] += uf(t.z); D[j][3] += uf(t.w); }
      k2048 = (k2048 + uf(lds32(xa + 2560))) * 0.125f;
#pragma unroll
      for (int r = 0; r < 4; r++) {
        const u32 v = pk_hf(D[2 + (r >> 1)][2 * (r & 1)], D[2 + (r >> 1)][2 * (r & 1) + 1]);
        if (q < 2) {
          const u32 vv = __byte_perm(v, v, 0x1010);
          sts32(t1 + (TO + 32 * r) * 4, vv); sts16(t1 + (TO + 32 * r + 1) * 4 + 2, v >> 16); sts16(t1 + (TO + 32 * r - 1) * 4, v);
          sts64(t1 + (TE + 32 * r) * 4, vv, __byte_perm(v, v, 0x1032));
        } else {
          sts16(t1 + 16 * r, v >> 16);
          if (r == 0 && lane == 2) {
            const u32 vv = __byte_perm(v, v, 0x1010);
            sts32(tp + (TO + 256) * 4, vv); sts16(tp + (TO + 257) * 4 + 2, v); sts16(tp + (TO + 255) * 4, v); sts64(tp + (TE + 256) * 4, vv, vv);
          } else sts16(t1 + 16 * r - ((T3 - T5) * 4 + 6) + 8 * hi, v);
        }
      }
#pragma unroll
      for (int r = 0; r < 2; r++) {
        const u32 v = pk_hf(D[4][2 * r], D[4][2 * r + 1]);
        if (r == 0 && lane == 0) { sts16(tp + T5 * 4 + 62 * 2, v); sts32(SM_KV + 4 * ksig, v & 0xffff); sts16(tp + (T9E + TEO) * 4 + 62 * 2, pk_hf(k2048, 0.f)); }
        else { sts16(te + 8 * r, v); sts16(to + 8 * r, v); }
        sts16(te + 8 * r + 16, v >> 16); sts16(to + 8 * r + 16, v >> 16);
      }
      __syncwarp();
#pragma unroll
      for (int r = 0; r < 4; r++) {
        const u32 v = pk_hf(D[r >> 1][2 * (r & 1) + 1], D[r >> 1][2 * (r & 1)]), t2 = tp + lane * 4 + 128 * r;
        sts32(t2 + TO * 4, v); sts16(t2 + TE * 4, v >> 16); sts16(t2 + (TE + 1) * 4 + 2, v);
      }
      __syncwarp();
    }
  } else if (w == (b < 108 ? 11 : ~0u)) {
    float c[4][4] = {};
    u32 aa = SM_UP + ((lane & 7) + 8 * (lane >> 4)) * 64 + ((((lane >> 3) & 1) ^ ((lane & 7) >> 1)) << 4);
    u32 ba = SM_SIL + (lane >> 3) * 16;
    uint4 a[2][10];
#define GLD(n) { _Pragma("unroll") for (int i = 0; i < 2; i++) { a[n][5 * i] = ldsm4(ba + i * 64); \
      _Pragma("unroll") for (int k = 0; k < 4; k++) a[n][5 * i + 1 + k] = ldsm4t((k & 2 ? aa ^ 32 : aa) + i * 2048 + (k & 1) * 1024); } aa += 4096; ba += 128; }
#define GMM(n) { _Pragma("unroll") for (int i = 0; i < 2; i++) _Pragma("unroll") for (int k = 0; k < 4; k++) { const uint4 f = a[n][5 * i + 1 + k], bb = a[n][5 * i]; \
      mma_bf(c[k], f.x, f.y, f.z, f.w, k & 1 ? bb.z : bb.x, k & 1 ? bb.w : bb.y); } }
    mb_wait(SM_MB);
    TS(56);
    GLD(0);
#pragma unroll 1
    for (int s = 0; s < 4; s++) { GLD(1); GMM(0); GLD(0); GMM(1); }
    GMM(0);
    const float v0 = (q & 1) ? c[0][2] + c[1][2] : c[0][0] + c[1][0], v1 = (q & 1) ? c[2][2] + c[3][2] : c[2][0] + c[3][0];
    str16(gs + (G_MOD + b * 128 + 2 * g + 16 * q), pk_bf(rbf((q & 2) ? v1 : v0) * F2M64, 0.f) | (g < 2 ? pm : 0));
    TS(57);
  }
  TS(6);
  u32 tid2 = tid;
  if (w < 4) {
    asm volatile("setmaxnreg.inc.sync.aligned.u32 232;");
    const u32 tid = tid2 + p.zero, w = tid >> 5, lane = tid & 31, g = lane >> 2, q = lane & 3, hi = g & 1, zr = tid >> 16, tp = SM_TAP + w * TAPS;
    const u32 pml = opq((g & 3) ? 0 : pm);
    const u32 tr = tp + ((hi ? TO : TE) + (g >> 1) - q) * 4;
    u32 T[33][4], B5[5][2], B3[5][2];
#pragma unroll
    for (int d = 0; d < 33; d++) {
      T[d][0] = lds32(tr + 32 * d); T[d][1] = lds32(tr + 32 * d + 16);
      T[d][2] = cpy(d ? T[d - 1][1] : zr, zr, 0); T[d][3] = cpy(T[d][0], zr, 1);
    }
    const u32 t33 = cpy(T[32][1], zr, 0), z33 = cpy(zr, zr, 1);
    if (TPIN) {
#pragma unroll
      for (int d = 0; d < 33; d++) asm volatile("{.reg .pred p; setp.ne.u32 p,%2,0; @p st.shared.v2.u32 [%2],{%0,%1};}" ::"r"(T[d][2]), "r"(T[d][3]), "r"(zr) : "memory");
    }
    const u32 bt = tp + (T5 + g - q) * 4;
#pragma unroll
    for (int d = 0; d < 5; d++) {
      B5[d][0] = lds32(bt + 32 * d); B5[d][1] = lds32(bt + 32 * d - 16);
      B3[d][0] = lds32(bt + 32 * d + (T3 - T5) * 4); B3[d][1] = lds32(bt + 32 * d - 16 + (T3 - T5) * 4);
    }
    u32 za = opq(SM_ZS + 16 + w * ZSS + ((lane >> 3) & 1) * ZPS + ((lane & 7) + (lane >> 4)) * 16);
    u32 wa = opq(SM_W + W5O + w * WSL + row16(lane));
    u32 sa = opq(SM_W + W9O - 2048 + w * WSL + lane * 16);
    const u32 yo = opq(p.glo + G_Y - 1024 + b * BLK + 256 * q + w * 32 + 4 * g);
    char* yp = gptr(p, yo);
#define YINC() asm volatile("{.reg .u32 l, h; mov.b64 {l,h},%0; add.u32 l,l,1024; mov.b64 %0,{l,h};}" : "+l"(yp))
    const u32 fa = opq(SM_SC + 16 * w + 8), bw = opq((BW >> 4 * w) & 15), bs = opq((BS >> 4 * w) & 15);
    if (TPIN) asm volatile("{.reg .pred p; setp.ne.u32 p,%8,0; @p st.shared.v4.u32 [%8],{%0,%1,%2,%3}; @p st.shared.v4.u32 [%8],{%4,%5,%6,%7};}"
                           ::"r"(za), "r"(wa), "r"(sa), "r"(yo), "r"(fa), "r"(bw), "r"(bs), "r"(pml), "r"(zr) : "memory");
    TS(8);
    u32 F;
    bsync(9, 384);
    TS(11);
    float A[4][4] = {};
    uint4 Z[4];
    Z[0] = ldsm4(za); Z[1] = ldsm4(za + 32);
#define STEP(s, b0, b1) { _Pragma("unroll") for (int i = 0; i < 4; i++) mma_hf_t(A[i], T[8 * i + 7 - (s)], b0, b1); }
#define PAIR(n) { Z[(n + 2) & 3] = ldsm4(za + 32 * (n + 2)); STEP(2 * n, Z[n].x, Z[n].y); STEP(2 * n + 1, Z[n].z, Z[n].w); }
#define LAST(N) mma8_hf(N, t33, z33, Z[3].y); float O[4]; mma_hf_o(O, A[0], T[0], Z[3].z, Z[3].w); \
    _Pragma("unroll") for (int i = 0; i < 3; i++) mma_hf_o(A[i], A[i + 1], T[8 * i + 8], Z[3].z, Z[3].w); \
    mma_hf_o(A[3], N, T[32], Z[3].z, Z[3].w);
#pragma unroll 1
    for (int j = 0; j < 4; j++) {
      PAIR(0);
      const uint2 fc = lds64(fa);
      PAIR(1);
      F = __byte_perm(fu(uf(fc.x) * uf(fc.y)), 0, 0x3232);
      PAIR(2);
      Z[1] = ldsm4(za + 160); STEP(6, Z[3].x, Z[3].y);
      float N[4] = {};
      LAST(N);
      if (INCV) inc<128>(za);
      YINC();
      y_store<128>(O[0], O[1], O[2], O[3], F, pml, yp);
      if (!INCV) za += 128;
      TSJ(j);
    }
    bsyncr(bw);
    uint4 a5;
    if (A5P) a5 = ldsm4t(wa);
#pragma unroll 1
    for (int j = 4; j < 13; j++) {
      if (j == 8) bsyncr(bs);
      if (!A5P) a5 = ldsm4t(wa);
      const uint4 a3 = ldsm4t(wa + (W3O - W5O));
      uint4 s3 = {0, 0, 0, 0};
      if (j >= 8) s3 = lds128(sa);
      PAIR(0);
      float N[4] = {};
#pragma unroll
      for (int i = 0; i < 4; i++) mma_hf(A[i], a5.x, a5.y, a5.z, a5.w, B5[i][0], B5[i][1]);
      mma_hf(N, a5.x, a5.y, a5.z, a5.w, B5[4][0], B5[4][1]);
      if (INCV) asm volatile("{add.u32 %0,%0,256; xor.b32 %0,%0,32;}" : "+r"(wa)); else wa = (wa + 256) ^ 32;
      if (A5P) a5 = ldsm4t(wa);
      PAIR(1);
#pragma unroll
      for (int i = 0; i < 4; i++) mma_hf(A[i], a3.x, a3.y, a3.z, a3.w, B3[i][0], B3[i][1]);
      mma_hf(N, a3.x, a3.y, a3.z, a3.w, B3[4][0], B3[4][1]);
      PAIR(2);
      Z[1] = ldsm4(za + 160); STEP(6, Z[3].x, Z[3].y);
      LAST(N);
      if (INCV) { inc<128>(za); inc<512>(sa); }
      YINC();
      y_store<128>(O[0] + uf(s3.x), O[1] + uf(s3.y), O[2] + uf(s3.z), O[3] + uf(s3.w), F, pml, yp);
      if (!INCV) { za += 128; sa += 512; }
      TSJ(j);
    }
    {
      asm volatile("mov.u32 %0,%%tid.x;" : "=r"(tid2));
      const uint4 s3 = lds128(sa), s4 = lds128(sa + 512), s5 = lds128(sa + 1024);
      float X[3][4] = {{uf(s4.x), uf(s4.y), uf(s4.z), uf(s4.w)}, {}, {uf(s5.x), uf(s5.y), uf(s5.z), uf(s5.w)}};
#pragma unroll
      for (int ty = 0; ty < 2; ty++) {
        const uint4 a = A5P && !ty ? a5 : ldsm4t(wa + ty * (W3O - W5O)), c = ldsm4t((wa ^ 32) + 256 + ty * (W3O - W5O)), d = ldsm4t(wa + 512 + ty * (W3O - W5O));
#pragma unroll
        for (int i = 0; i < 3; i++) mma_hf(A[i], a.x, a.y, a.z, a.w, ty ? B3[i][0] : B5[i][0], ty ? B3[i][1] : B5[i][1]);
#pragma unroll
        for (int i = 0; i < 2; i++) mma_hf(X[i], c.x, c.y, c.z, c.w, ty ? B3[i][0] : B5[i][0], ty ? B3[i][1] : B5[i][1]);
        mma_hf(X[2], d.x, d.y, d.z, d.w, ty ? B3[0][0] : B5[0][0], ty ? B3[0][1] : B5[0][1]);
      }
#pragma unroll
      for (int n = 0; n < 4; n++) {
        const uint4 f0 = n < 2 ? Z[n] : ldsm4(za + 32 * n), f1 = ldsm4(za + 32 * n + 128), f2 = ldsm4(za + 32 * n + 256);
#pragma unroll
        for (int s = 2 * n; s < 2 * n + 2; s++) {
#pragma unroll
          for (int i = 0; i < 3; i++) mma_hf_t(A[i], T[8 * i + 7 - s], s & 1 ? f0.z : f0.x, s & 1 ? f0.w : f0.y);
          mma_hf_t(X[0], T[7 - s], s & 1 ? f1.z : f1.x, s & 1 ? f1.w : f1.y); mma_hf_t(X[1], T[15 - s], s & 1 ? f1.z : f1.x, s & 1 ? f1.w : f1.y);
          mma_hf_t(X[2], T[7 - s], s & 1 ? f2.z : f2.x, s & 1 ? f2.w : f2.y);
        }
      }
      y_store<128>(A[0][0] + uf(s3.x), A[0][1] + uf(s3.y), A[0][2] + uf(s3.z), A[0][3] + uf(s3.w), F, pml, yp + 1024);
      y_store<128>(A[1][0] + X[0][0], A[1][1] + X[0][1], A[1][2] + X[0][2], A[1][3] + X[0][3], F, pml, yp + 2048);
      y_store<128>(A[2][0] + X[1][0] + X[2][0], A[2][1] + X[1][1] + X[2][1], A[2][2] + X[1][2] + X[2][2], A[2][3] + X[1][3] + X[2][3], F, pml, yp + 3072);
    }
    barrive(12, N12);
    TS(15);
  } else {
    asm volatile("setmaxnreg.dec.sync.aligned.u32 136;");
    const u32 t8 = tid - 128, pml = (g & 3) ? 0 : pm;
    {
      TS(12);
      if (PFG == 1 && tid == 288) l2_pre<WSH / 2>(p.wg + (b * WSH + WSH / 2));
      const char* zs = gs + ((16 * w - 64 + (lane >> 3)) * BLK + b * 128 + ((lane & 7) * 16 ^ rho * 64));
      const char* zs4 = gs + ((t8 >> 1) * BLK + (Ps >> 4) * 512 + (Ps & 6) * 64 + ((Ps >> 2 ^ Ps) & 2) * 32 + (Ps & 1) * 32 + (t8 & 1) * 16);
      uint4 v[5];
      v[4].x = INVAL;
      if (ZD) wait_clk(t0, ZD);
      const u32 d = lane < 4 ? chan(b, lane) : Ps;
      const char* mp = gs + (G_MOD + (d >> 5) * 128 + (d & 24) * 2);
      uint4 ta, tc;
      ta.x = tc.x = INVAL;
      const u32 t9 = w == 9 ? pm : INVAL;
      pin2(zr, zs, zs4);
      conv();
      POLLM({ rld128<TAGM>(ta, mp, t9); rld128<TAGM>(tc, mp + MODJ, t9); rld128<TAGM>(v[4], zs4, pm); }, lop3<0xbe>(v[4].x, pm, ne3(ta.x, tc.x, t9)), TAGM, 1);
      TS(58);
#pragma unroll
      for (int j = 0; j < 4; j++) v[j] = ldr128(zs + j * 4 * BLK);
      if (w == 9) {
        const u32 aw = (d & 4) ? ((d & 2) ? ta.w : ta.z) : ((d & 2) ? ta.y : ta.x & ~TAGM);
        const u32 cw = (d & 4) ? ((d & 2) ? tc.w : tc.z) : ((d & 2) ? tc.y : tc.x & ~TAGM);
        const float sa = ((d & 1) ? bhi(aw) : blo(aw)) * F2P64, c1 = rbf(fmaf((d & 1) ? bhi(cw) : blo(cw), F2P64, 1.f));
        const u32 EM = min(max(fu(fmaxf(32.f * fabsf(c1), fabsf(sa))) >> 23, 80u), 250u);
        const float inv = uf((264 - EM) << 23);
        if (lane < 5) { sts64(SM_SC + 16 * lane, pk_hf(16.f * c1 * inv, 16.f * c1 * inv), pk_hf(sa * inv, sa * inv)); sts32(SM_SC + 16 * lane + 8, (EM - 74) << 23); }
        TS(10);
      }
#define MARKERS() if (tid == 256) { \
        _Pragma("unroll") for (int i = MT / 2; i < 8; i++) bulk_out<2048>(gs + (G_Y + 2048 * i + b * BLK), SM_INV); \
        bulk_out<2048>(gs + (G_PART + b * 2048), SM_INV); bulk_out<512>(gs + (G_ACT + b * 512), SM_INV); \
        bulk_out<32>(gs + (G_KEY + b * KST), SM_INV); if (!rho) bulk_out<128>(gs + (G_ACT + Ps * 128), SM_INV); \
        asm volatile("cp.async.bulk.commit_group;" ::: "memory"); }
#define GATE() { mb_expect(SM_MB + 8, rho ? SLV : 46080); \
        _Pragma("unroll") for (int i = GE; i < 3; i++) tma3d(SM_GATE + 12288 * i, &tm_gate, SM_MB + 8, 32 * b, i); \
        if (!rho) tma3d(SM_GATE + SLV, &tm_gs, SM_MB + 8, 4096 + 4 * b, 0); }
#define UP() { mb_expect(SM_MB + 16, rho ? SLV : 46080); tma3d(SM_UP, &tm_up, SM_MB + 16, 32 * b, 0); \
        if (!rho) tma3d(SM_UP + SLV, &tm_us, SM_MB + 16, 4096 + 4 * b, 0); }
      if (PFU == 2 && tid == 256) l2_pre<WSH>(p.wu + b * WSH);
      if (GE && tid == 256) {
        asm volatile("cp.async.bulk.wait_group.read 0;" ::: "memory");
#pragma unroll
        for (int i = 0; i < GE; i++) tma3d(SM_GATE + 12288 * i, &tm_gate, SM_MB + 8, 32 * b, i);
      }
      if (PFG == 2 && tid == 256) l2_pre<WSH>(p.wg + b * WSH);
      if (PFG == 3 && tid == 256) l2_pre<WSH / 2>(p.wg + (b * WSH + WSH / 2));
      bsync(8, 256);
      const uint2 cc = lds64(SM_SC + 8 * (t8 & 6)), c4 = lds64(SM_SC + 64);
      sts128(SM_Z4 + 256 + (t8 & 1) * ZP4 + (t8 >> 1) * 16, hfma(v[4].x & ~TAGM, c4.x, c4.y), hfma(v[4].y, c4.x, c4.y), hfma(v[4].z, c4.x, c4.y), hfma(v[4].w, c4.x, c4.y));
      if (t8 < 96) sts128(t8 < 64 ? SM_ZS + (t8 & 7) * ZPS + (t8 >> 3) * 16 : SM_Z4 + (t8 & 1) * ZP4 + (t8 & 30) * 8, 0, 0, 0, 0);
      asm volatile("cp.async.bulk.wait_group.read 0;" ::: "memory");
      const u32 dst = SM_ZS + 128 + (t8 & 7) * ZPS + (16 * w - 64 + (lane >> 3)) * 16;
      pin(zr, dst);
      conv();
      POLLS(_Pragma("unroll") for (int j = 0; j < 4; j++) sts128(dst + j * 64, hfma(v[j].x & ~TAGM, cc.x, cc.y), hfma(v[j].y, cc.x, cc.y), hfma(v[j].z, cc.x, cc.y), hfma(v[j].w, cc.x, cc.y)),
            _Pragma("unroll") for (int j = 0; j < 4; j++) rld128<TAGM>(v[j], zs + j * 4 * BLK, pm), ne3(v[0].x, v[1].x, pm) | ne3(v[2].x, v[3].x, pm), TAGM, 1);
      TS(9);
      bsync(9, 384);
      TS(11);
      if (MKT == 1) MARKERS();
      if (w == 10 && s2u(smem) != SM0) __trap();
      const bool lng = w < 8 || w == 9;
      const u32 ts = lane + 32 * (w == 8 ? 0 : w - 9), c = min(ts, 71u), ma = SM_MODS + 16 * c;
      const u32 sig = lng ? ksig : ts >> 4, l2 = lng ? lane : 32 + (ts & 15);
      const char* mq = gs + (G_MOD + (c >> 2) * 128 + (c & 3) * 16);
      if (!lng) {
#pragma unroll
        for (int j = 0; j < 6; j++) cpa16(ma + 1152 * j, mq + j * MODJ);
        cpa16(ma + 1152 * 6, p.dsk + 16 * c); cpa16(ma + 1152 * 7, p.wr + 16 * c);
        if (PFU == 3) {
#pragma unroll
          for (int j = 0; j < 4; j++) if (ts < 81) l2_line(p.wu + (b * WSH + (81 * j + ts) * 128));
        }
        if (tid == 352) {
          PROXY_FENCE();
          if (PFU == 1) l2_pre<WSH>(p.wu + b * WSH);
          if (!TG) GATE();
          if (!TU) UP();
        }
      }
      const u32 wb = SM_W + sig * WSL;
      if (sig < 5) {
        const u32 za = (sig < 4 ? SM_ZS + 128 + sig * ZSS : SM_Z4 + 256) + l2 * 32, zb = za + (sig < 4 ? ZPS : ZP4);
        const uint4 c0 = lds128(zb - 32), c1 = lds128(za - 16), c2 = lds128(zb - 16), c3 = lds128(za), c4 = lds128(zb), c5 = lds128(za + 16), c6 = lds128(zb + 16);
        const u32 P[25] = {c0.z, c0.w, c1.x, c1.y, c1.z, c1.w, c2.x, c2.y, c2.z, c2.w, c3.x, c3.y, c3.z, c3.w, c4.x, c4.y, c4.z, c4.w, c5.x, c5.y, c5.z, c5.w, c6.x, c6.y, c6.z};
        u32 Q[25], D1[24], F4[23], W5[21], W3[17];
#pragma unroll
        for (int j = 1; j < 25; j++) Q[j] = __byte_perm(P[j - 1], P[j], 0x5432);
#pragma unroll
        for (int j = 1; j < 24; j++) D1[j] = hadd(P[j], Q[j]);
#pragma unroll
        for (int j = 2; j < 23; j++) F4[j] = hadd(D1[j], D1[j - 1]);
#pragma unroll
        for (int n = 0; n < 21; n++) W5[n] = hadd(F4[n + 2], P[n]);
#pragma unroll
        for (int n = 0; n < 17; n++) W3[n] = hadd(Q[n + 8], D1[n + 7]);
        const u32 a0 = wb + W5O + 64 * l2 + 16 * ((l2 >> 1) & 3);
#pragma unroll
        for (int i = 0; i < 4; i++) {
          sts128(a0 ^ (16 * i), W5[4 * i + 5], W5[4 * i + 6], W5[4 * i + 7], W5[4 * i + 8]);
          sts128((a0 ^ (16 * i)) + (W3O - W5O), W3[4 * i + 1], W3[4 * i + 2], W3[4 * i + 3], W3[4 * i + 4]);
        }
        if (lng) {
          if (lane < 16) sts128(wb + (lane & 7) * 16 + (lane & 8) * 400, 0, 0, 0, 0);
          const u32 a1 = wb + 32 * lane + 16 * ((lane >> 2) & 1);
#pragma unroll
          for (int i = 0; i < 4; i++) {
            const u32 a = (a1 ^ (16 * (i >> 1))) + 1024 * (i & 1), n = 4 * i;
            sts128(a + V2O, hadd(Q[n + 9], P[n + 8]), hadd(Q[n + 10], P[n + 9]), hadd(Q[n + 11], P[n + 10]), hadd(Q[n + 12], P[n + 11]));
            sts128(a + W9O, hadd(F4[n + 4], W5[n]), hadd(F4[n + 5], W5[n + 1]), hadd(F4[n + 6], W5[n + 2]), hadd(F4[n + 7], W5[n + 3]));
            sts128(a + W7O, hadd(F4[n + 6], W3[n]), hadd(F4[n + 7], W3[n + 1]), hadd(F4[n + 8], W3[n + 2]), hadd(F4[n + 9], W3[n + 3]));
          }
        }
      }
      if (w < 8) barriver((BW >> (4 * w - 16)) & 15);
      else if (!(w & 1)) { barriver((BW >> (4 * w - 32)) & 15); barriver((BW >> (4 * w - 28)) & 15); }
      __syncwarp();
      TS(32);
      if (lng) {
        const u32 wa = wb + ((lane >> 3) & 1) * 1024 + (((lane & 7) ^ (lane >> 4)) + 8 * (lane >> 4)) * 16;
        const u32 kv = lds32(SM_KV + 4 * sig), bi = (g >> 1) == q ? (hi ? kv << 16 : kv) : 0u;
        float acc[8][4] = {};
#pragma unroll
        for (int j = 0; j < 4; j++) { const uint4 a = ldsm4t(wa + V2O + j * 256); mma8_hf(acc[2 * j], a.x, a.y, bi); mma8_hf(acc[2 * j + 1], a.z, a.w, bi); }
        u32 bt = tp + (T9E + hi * TEO + (g >> 1) - q) * 4, wt = wa + W9O;
#pragma unroll 1
        for (int ty = 0; ty < 2; ty++) {
          uint4 a[4];
#pragma unroll
          for (int be = 0; be < 4; be++) a[be] = ldsm4t(wt + be * 256);
          u32 b1 = lds32(bt - 16);
#pragma unroll
          for (int d = 0; d < 8; d++) {
            const u32 b0 = lds32(bt + 16 * d);
#pragma unroll
            for (int be = 0; be < 4; be++) if (d + 2 * be < 8) mma_hf(acc[d + 2 * be], a[be].x, a[be].y, a[be].z, a[be].w, b0, b1);
            b1 = b0;
          }
          bt += (T7E - T9E) * 4; wt += W7O - W9O;
        }
        __syncwarp();
#pragma unroll
        for (int j = 0; j < 8; j++) sts128(wb + W9O + j * 512 + lane * 16, fu(acc[j][0]), fu(acc[j][1]), fu(acc[j][2]), fu(acc[j][3]));
        if (w != 9) barriver((BS >> (4 * w - 16)) & 15);
        TS(34);
      }
      if (!lng) {
        asm volatile("cp.async.wait_all;" ::: "memory");
        uint4 md[6];
#pragma unroll
        for (int j = 0; j < 6; j++) md[j] = lds128(ma + 1152 * j);
        const uint4 dk = lds128(ma + 1152 * 6), wr = lds128(ma + 1152 * 7);
        POLLW(_Pragma("unroll") for (int j = 0; j < 6; j++) md[j] = ldr128(mq + j * MODJ),
              ((md[0].x ^ pm) | (md[1].x ^ pm) | (md[2].x ^ pm) | (md[3].x ^ pm) | (md[4].x ^ pm) | (md[5].x ^ pm)) & TAGM, 4);
#pragma unroll
        for (int j = 0; j < 6; j++) {
          const u32 o = (j % 3 == 1) ? BONE : 0x80008000u;
          md[j] = make_uint4(bfma(md[j].x & ~TAGM, B2P64, o), bfma(md[j].y, B2P64, o), bfma(md[j].z, B2P64, o), bfma(md[j].w, B2P64, o));
          if (j > 2) sts128(ma + 1152 * j, md[j].x, md[j].y, md[j].z, md[j].w);
        }
        const uint4 gd = make_uint4(bmul(md[2].x, dk.x), bmul(md[2].y, dk.y), bmul(md[2].z, dk.z), bmul(md[2].w, dk.w));
#pragma unroll
        for (int j = 0; j < 2; j++) sts128(ma + 1152 * j, bmul(md[j].x, gd.x), bmul(md[j].y, gd.y), bmul(md[j].z, gd.z), bmul(md[j].w, gd.w));
        sts128(ma + 2304, bmul(md[2].x, B2P64), bmul(md[2].y, B2P64), bmul(md[2].z, B2P64), bmul(md[2].w, B2P64));
        const uint4 H = make_uint4(bmul(md[4].x, wr.x), bmul(md[4].y, wr.y), bmul(md[4].z, wr.z), bmul(md[4].w, wr.w));
        sts128(ma + 1152 * 7, H.x, H.y, H.z, H.w);
        sts128(ma + 1152 * 8, bfma(md[4].x, wr.x, H.x ^ 0x80008000u), bfma(md[4].y, wr.y, H.y ^ 0x80008000u), bfma(md[4].z, wr.z, H.z ^ 0x80008000u), bfma(md[4].w, wr.w, H.w ^ 0x80008000u));
        float c4[4] = {};
        mma_bf(c4, md[4].x, md[3].x, md[4].y, md[3].y, wr.x, wr.y); mma_bf(c4, md[4].z, md[3].z, md[4].w, md[3].w, wr.z, wr.w);
        if (q == g >> 1) sts64(SM_RC + (ts >> 2) * 8, fu(hi ? c4[1] : c4[0]), fu(hi ? c4[3] : c4[2]));
        if (ts < 2) sts128(SM_ONE + 16 * ts, ts ? 0 : BONE, ts ? 0 : BONE, ts ? 0 : BONE, ts ? 0 : BONE);
        TS(14);
        if (MKT == 2) MARKERS();
        if (w == 8) asm volatile("cp.async.bulk.wait_group 0;" ::: "memory");
        if (PFW == 2) {
#pragma unroll
          for (int j = 0; j < 4; j++) if (ts < 81) l2_line(p.wd + (b * WSH + (81 * j + ts) * 128));
        }
        bsync(13, 96);
        if (w == 8) { barriver(2); barriver(3); barriver(5); barriver(6); if (HLP) barrive(7, 64); }
      }
      if (!HLP) { if (w >= 8) barrive(11, 256); }
      else if (w == 9) barrive(11, 128);
    }
    const u32 jw = w < 6 ? w ^ 1 : w < 8 ? w : max(w - 4, 5u);
    const int u0 = 4 * (jw - 4) + 2 * rho;
    const u32 t4 = SM_TAP + 4 * TAPS, s3a = SM_W + 4 * WSL + (u0 >= 8 ? W9O + (u0 - 8) * 512 : V2O) + lane * 16, hb = (0x4987 >> (4 * jw - 16)) & 15;
#define FARL() { u32 wa = (SM_W + 4 * WSL + W5O + row16(lane) + (u0 - 3) * 256) ^ 32, bt = t4 + (T5 + g - q) * 4; \
      _Pragma("unroll 1") for (int al = min(u0 - 2, 6); al > 0; al--) { \
        _Pragma("unroll") for (int ty = 0; ty < 2; ty++) { \
          const uint4 a = ldsm4t(wa + ty * (W3O - W5O)); \
          const u32 bb = bt + ty * (T3 - T5) * 4; \
          mma_hf(acc[ty], a.x, a.y, a.z, a.w, lds32(bb - 32), lds32(bb - 48)); \
          mma_hf(acc[2 + ty], a.x, a.y, a.z, a.w, lds32(bb), lds32(bb - 16)); \
        } \
        wa = (wa - 256) ^ 32; bt += 32; } }
    if (w < 8) {
      u32 tr = t4 + ((hi ? TO : TE) + (g >> 1) - q) * 4;
      u32 zb = SM_Z4 + 256 + ((lane >> 3) & 1) * ZP4 + u0 * 128 + (lane & 7) * 16 + (lane >> 4) * 128;
      float acc[4][4] = {};
      u32 prev = 0;
#pragma unroll 1
      for (int it = min(u0 + 2, 4); it; it--) {
#pragma unroll
        for (int s = 0; s < 8; s++) {
          const uint4 z = ldsm4(zb - 16 * s);
          const u32 t0 = lds32(tr + 32 * s), t1 = lds32(tr + 32 * s + 16);
          mma_hf(acc[s & 1], t0, t1, prev, t0, z.x, z.y);
          mma_hf(acc[2 + (s & 1)], t0, t1, prev, t0, z.z, z.w);
          prev = t1;
        }
        zb -= 128; tr += 256;
      }
      {
        const uint4 z = ldsm4(zb); const u32 t0 = lds32(tr), t1 = lds32(tr + 16);
        mma_hf(acc[0], t0, t1, prev, t0, z.x, z.y); mma_hf(acc[2], t0, t1, prev, t0, z.z, z.w);
        if (jw > 4) { const uint4 y = ldsm4(zb - 16); mma8_hf(acc[1], t1, zr, y.y); mma8_hf(acc[3], t1, zr, y.w); }
      }
      if (!HLP) { bsync(11, 256); FARL(); }
      else asm volatile("bar.sync %0,64;" ::"r"(hb) : "memory");
      TS(35);
      const uint2 fc = lds64(SM_SC + 16 * 4 + 8);
      const u32 F = __byte_perm(fu(uf(fc.x) * uf(fc.y)), 0, 0x3232);
      char* yp = gs + (G_Y + 16384 + (32 * jw - 128 + 16 * rho + 4 * (q >> 1) + ((b >> 2) & 3)) * BLK + (q & 1) * 1024 + (b & 112) * 4 + (b & 2) * 16 + 4 * g);
#pragma unroll
      for (int j = 0; j < 2; j++) {
        uint4 s3 = {0, 0, 0, 0};
        if (u0 >= (HLP ? 4 : 8)) s3 = lds128(s3a + j * 512);
        y_store<512>(acc[2 * j][0] + acc[2 * j + 1][0] + uf(s3.x), acc[2 * j][1] + acc[2 * j + 1][1] + uf(s3.y), acc[2 * j][2] + acc[2 * j + 1][2] + uf(s3.z),
                acc[2 * j][3] + acc[2 * j + 1][3] + uf(s3.w), F, pml, yp + j * 8 * BLK);
      }
      TS(16);
    } else {
      if (HLP && w != 9) {
        bsync(11, 128);
        if (HD) wait_clk(clk(), HD);
        float acc[4][4] = {};
        if (u0 >= 8) {
#pragma unroll
          for (int j = 0; j < 2; j++) { const uint4 t = lds128(s3a + j * 512); acc[2 * j][0] = uf(t.x); acc[2 * j][1] = uf(t.y); acc[2 * j][2] = uf(t.z); acc[2 * j][3] = uf(t.w); }
        }
        FARL();
#pragma unroll
        for (int j = 0; j < 2; j++)
          sts128(s3a + j * 512, fu(acc[2 * j][0] + acc[2 * j + 1][0]), fu(acc[2 * j][1] + acc[2 * j + 1][1]), fu(acc[2 * j][2] + acc[2 * j + 1][2]), fu(acc[2 * j][3] + acc[2 * j + 1][3]));
        asm volatile("bar.arrive %0,64;" ::"r"(hb) : "memory");
        TS(16);
      }
      if (PFW == 3 && w == 9) {
#pragma unroll 1
        for (int j = 0; j < 12; j++) { if (lane < 27) l2_line(p.wd + (b * WSH + (27 * j + lane) * 128)); wait_clk(clk(), PFP); }
      }
      if (TG | TU | TW) {
        if (tid == 352) {
          if (TG) { wait_clk(t0, TG); GATE(); }
          if (TW < TU) { wait_clk(t0, TW); l2_pre<WSH>(p.wd + b * WSH); }
          if (TU) { wait_clk(t0, TU); UP(); }
          if (TW >= TU) { wait_clk(t0, TW); l2_pre<WSH>(p.wd + b * WSH); }
        }
      } else if (PFW < 2 && tid == 352) { mb_wait(SM_MB + 8); if (PFW) mb_wait(SM_MB + 16); l2_pre<WSH>(p.wd + b * WSH); }
      if (D0C && tid == 352 && b < 108) {
        mb_wait(SM_MB + 16);
        PROXY_FENCE();
        mb_expect(SM_MB + 24, 49152);
        tma3d(SM_TAP, &tm_down, SM_MB + 24, 64 * (b % 9), 4 * (b / 9));
      }
      TS(17);
    }
  }
  post_conv(p, &tm_down, tid2 + p.zero, b, b3);
  TSD();
}

typedef CUresult (*EncFn)(CUtensorMap*, CUtensorMapDataType, cuuint32_t, void*, const cuuint64_t*, const cuuint64_t*, const cuuint32_t*, const cuuint32_t*,
                          CUtensorMapInterleave, CUtensorMapSwizzle, CUtensorMapL2promotion, CUtensorMapFloatOOBfill);
static void make_map(EncFn enc, CUtensorMap* tm, void* ptr, int cols, int rows, int bw, int nb, CUtensorMapSwizzle sw, int gr = 192, int prom = 0) {
  cuuint64_t gd[3] = {(cuuint64_t)cols, (cuuint64_t)gr, (cuuint64_t)(rows / gr)}, gs[2] = {(cuuint64_t)cols * 2, (cuuint64_t)cols * 2 * gr};
  cuuint32_t bd[3] = {(cuuint32_t)bw, (cuuint32_t)gr, (cuuint32_t)nb}, es[3] = {1, 1, 1};
  enc(tm, CU_TENSOR_MAP_DATA_TYPE_BFLOAT16, 3, ptr, gd, gs, bd, es, CU_TENSOR_MAP_INTERLEAVE_NONE, sw, (CUtensorMapL2promotion)prom, CU_TENSOR_MAP_FLOAT_OOB_FILL_NONE);
}
extern "C" void kernel_launch(void* const* d_in, const int* in_sizes, int n_in, void* d_out, int out_size) {
  static EncFn enc = nullptr;
  static void* scratch = nullptr;
  if (!enc) {
    cudaGetSymbolAddress(&scratch, g_s);
    const uintptr_t last = (uintptr_t)scratch + G_END;
    if ((u32)last < G_END) scratch = (void*)(last - (u32)last);
    cudaDriverEntryPointQueryResult qr;
    cudaGetDriverEntryPoint("cuTensorMapEncodeTiled", (void**)&enc, cudaEnableDefault, &qr);
    cudaFuncSetAttribute(fused_kernel, cudaFuncAttributeMaxDynamicSharedMemorySize, SM_TOTAL);
  }
  CUtensorMap tm_mod, tm_gate, tm_gs, tm_up, tm_us, tm_down;
  make_map(enc, &tm_mod, d_in[13], 3456, 576, 32, 3, CU_TENSOR_MAP_SWIZZLE_64B, 192, PRM);
  make_map(enc, &tm_gate, d_in[9], 4608, 576, 32, 1, CU_TENSOR_MAP_SWIZZLE_64B, 192, PRG);
  make_map(enc, &tm_gs, d_in[9], 4608, 576, 8, 3, CU_TENSOR_MAP_SWIZZLE_NONE);
  make_map(enc, &tm_up, d_in[10], 4608, 576, 32, 3, CU_TENSOR_MAP_SWIZZLE_64B, 192, PRU);
  make_map(enc, &tm_us, d_in[10], 4608, 576, 8, 3, CU_TENSOR_MAP_SWIZZLE_NONE, 192, PRS);
  make_map(enc, &tm_down, d_in[11], 576, 4608, 64, 1, CU_TENSOR_MAP_SWIZZLE_128B, 96);
  Prm p;
  p.x = (const char*)d_in[0]; p.la = (const char*)d_in[1]; p.ai = (const char*)d_in[2]; p.cr = (const char*)d_in[3];
  p.ci = (const char*)d_in[4]; p.ldt = (const char*)d_in[5]; p.dsk = (const char*)d_in[6]; p.wr = (const char*)d_in[8];
  p.wg = (const char*)d_in[9]; p.wu = (const char*)d_in[10]; p.wd = (const char*)d_in[11];
  p.c = (const char*)d_in[12]; p.out = (char*)d_out; p.zero = 0; p.gs = (char*)scratch; p.glo = (u32)(uintptr_t)scratch; p.ghi = (u32)((uintptr_t)scratch >> 32);
  fused_kernel<<<128, 384, SM_TOTAL>>>(p, tm_mod, tm_gate, tm_gs, tm_up, tm_us, tm_down);
}
```

```cpp
#include <cuda_runtime.h>
#include <cuda.h>
#include <cuda_bf16.h>
#include <cuda_fp16.h>
#include <stdint.h>
#define FUSED 1
#define DEV __device__ __forceinline__
typedef uint32_t u32;

constexpr u32 BLK = 18432, G_Z = 0, G_Y = 128 * BLK, G_MOD = 2 * G_Y, G_KEY = G_MOD + 128 * 128, G_ACT = G_KEY + 128 * 128;
constexpr u32 G_PART = G_ACT + 576 * 128, G_EP = G_PART + 128 * 2048, G_END = G_EP + 128;
__device__ __align__(128) unsigned char g_s[2 * G_END];
#define TS(i)
#define TSJ(j)
#define TS0()
#define TSE()
#define TSD()
#define TSX 0
#define TSRND()
#define TSN(code, n)
#define ERRF(code)

constexpr int SM0 = 1024;
constexpr int ROW = 1168, SLV = 36864;
constexpr int SM_GATE = SM0, SM_UP = SM_GATE + 46080, SM_XST = SM_UP + 46080, SM_MODS = SM_XST + 16 * ROW, SM_W = SM_MODS + 11008;
constexpr int KTAB = 9216, WSL = 12544, W5O = 128, W3O = 3328, V2O = 6400, W9O = 8448, W7O = 10496;
constexpr int ZPS = 2192, ZSS = 2 * ZPS, ZP4 = 2368;
constexpr int SM_ZS = SM_W + 5 * WSL, SM_Z4 = SM_ZS + 4 * ZSS, SM_TAP = SM_Z4 + 2 * ZP4, TAPS = 3328;
constexpr int SM_MB = SM_TAP + 5 * TAPS;
constexpr int SM_SC = SM_MB + 48;
constexpr int SM_KV = SM_SC + 80;
constexpr int SM_THR = SM_KV + 32;
constexpr int SM_SLOT = SM_THR + 48;
constexpr int SM_KEY = SM_SLOT + 32;
constexpr int SM_ST = SM_KEY + 64;
constexpr int SM_ST2 = SM_ST + 256;
constexpr int SM_RC = SM_ST2 + 256;
constexpr int SM_SP = SM_RC + 192;
constexpr int SM_AF = SM_SP + 1152, SM_SIL = SM_AF + 1152, SM_INV = SM_SIL + 1152, SM_END = SM_SP + 5760;
constexpr int SM_ONE = SM_MODS + 9 * 1152;
constexpr int SM_WD = SM_W, SM_XS = SM_W + 36864, SM_AC = SM_ZS, SM_RED = SM_AC + 6144;
constexpr int SM_TSB = SM_END, SM_TOTAL = SM_END + TSX - SM0;
static_assert(SM_W % 1024 == 0 && SM_TAP % 1024 == 0 && SM_MODS + 8 * KTAB <= SM_ZS && SM_ZS + 2 * KTAB <= SM_TAP && SM_RED + 10240 <= SM_TAP && SM_XS + 8 * ROW <= SM_ZS, "smem map");
static_assert(SM_MB % 16 == 0 && SM_THR % 16 == 0 && SM_ST % 16 == 0 && SM_SP % 16 == 0 && SM_TOTAL <= 232448, "smem map");
constexpr int TE = 4, TO = 276, T5 = 560, T3 = 624, T9E = 680, T7E = 760, TEO = 40;
#define MT 10
#define MKT 1
#define KST 32
#define DE1 1
#define DE2 4
#define DE3 5
#define OUTB 7
#define PFW 1
#define PFU 0
#define KD 700
#define D0C 0
#define YE 104
#define YL 104
#define YD 250
#define OPTM 1
#define Y8 104
#define FH 0
#define FO 0
#define DB1 1
#define KD1 50
#define AD 0
#define PD 900
#define ZD 0
#define DD 1000
#define INCV 1
#define TPIN 0
#define A5P 1
#define TG 0
#define TU 0
#define TW 0
#define KDB 520
#define PRM 0
#define PRG 0
#define PRU 0
#define PRS 0
#define KE 64
#define PFP 200
#define GE 0
#define NB8 8
#define DX 0
#define DMOD 1000
#define RW 3
#define AW 7
#define HLP 1
#define SMD 1
#define CVG 1
#define SPL 1
#define GX 15
#define HD 0
#define KF 96
#define KDC 520
#define AFP 1
#define AFM 0
#define PFG 1
constexpr int N1 = 320 + 32 * DB1, N12 = 288 + 32 * !DB1;
constexpr int SPIN = 1 << 16, NEARLY = 4;
constexpr u32 TAGM = 0x40004000u, TAGR = 0x40000000u, INVAL = 0x00004801u;

DEV u32 s2u(const void* p) { return (u32)__cvta_generic_to_shared(p); }
DEV void mma_bf(float (&c)[4], u32 a0, u32 a1, u32 a2, u32 a3, u32 b0, u32 b1) {
  asm("mma.sync.aligned.m16n8k16.row.col.f32.bf16.bf16.f32 {%0,%1,%2,%3},{%4,%5,%6,%7},{%8,%9},{%0,%1,%2,%3};"
      : "+f"(c[0]), "+f"(c[1]), "+f"(c[2]), "+f"(c[3]) : "r"(a0), "r"(a1), "r"(a2), "r"(a3), "r"(b0), "r"(b1));
}
DEV void mma_hf(float (&c)[4], u32 a0, u32 a1, u32 a2, u32 a3, u32 b0, u32 b1) {
  asm("mma.sync.aligned.m16n8k16.row.col.f32.f16.f16.f32 {%0,%1,%2,%3},{%4,%5,%6,%7},{%8,%9},{%0,%1,%2,%3};"
      : "+f"(c[0]), "+f"(c[1]), "+f"(c[2]), "+f"(c[3]) : "r"(a0), "r"(a1), "r"(a2), "r"(a3), "r"(b0), "r"(b1));
}
DEV void mma8_bf(float (&c)[4], u32 a0, u32 a1, u32 b0) {
  asm("mma.sync.aligned.m16n8k8.row.col.f32.bf16.bf16.f32 {%0,%1,%2,%3},{%4,%5},{%6},{%0,%1,%2,%3};"
      : "+f"(c[0]), "+f"(c[1]), "+f"(c[2]), "+f"(c[3]) : "r"(a0), "r"(a1), "r"(b0));
}
DEV void mma8_hf(float (&c)[4], u32 a0, u32 a1, u32 b0) {
  asm("mma.sync.aligned.m16n8k8.row.col.f32.f16.f16.f32 {%0,%1,%2,%3},{%4,%5},{%6},{%0,%1,%2,%3};"
      : "+f"(c[0]), "+f"(c[1]), "+f"(c[2]), "+f"(c[3]) : "r"(a0), "r"(a1), "r"(b0));
}
DEV u32 movm(u32 x) { u32 r; asm("movmatrix.sync.aligned.m8n8.trans.b16 %0,%1;" : "=r"(r) : "r"(x)); return r; }
DEV void conv() { if (CVG) asm volatile("{.reg .u32 t; mov.u32 t,0; movmatrix.sync.aligned.m8n8.trans.b16 t,t;}"); }
DEV uint4 ldsm4(u32 a) { uint4 r; asm volatile("ldmatrix.sync.aligned.m8n8.x4.shared.b16 {%0,%1,%2,%3},[%4];" : "=r"(r.x), "=r"(r.y), "=r"(r.z), "=r"(r.w) : "r"(a)); return r; }
DEV uint4 ldsm4t(u32 a) { uint4 r; asm volatile("ldmatrix.sync.aligned.m8n8.x4.trans.shared.b16 {%0,%1,%2,%3},[%4];" : "=r"(r.x), "=r"(r.y), "=r"(r.z), "=r"(r.w) : "r"(a)); return r; }
DEV u32 lds32(u32 a) { u32 r; asm volatile("ld.volatile.shared.u32 %0,[%1];" : "=r"(r) : "r"(a)); return r; }
DEV uint2 lds64(u32 a) { uint2 r; asm volatile("ld.shared.v2.u32 {%0,%1},[%2];" : "=r"(r.x), "=r"(r.y) : "r"(a)); return r; }
DEV uint4 lds128(u32 a) { uint4 r; asm volatile("ld.shared.v4.u32 {%0,%1,%2,%3},[%4];" : "=r"(r.x), "=r"(r.y), "=r"(r.z), "=r"(r.w) : "r"(a)); return r; }
DEV void sts16(u32 a, u32 v) { asm volatile("st.shared.u16 [%0],%1;" ::"r"(a), "h"((unsigned short)v) : "memory"); }
DEV void sts32(u32 a, u32 v) { asm volatile("st.shared.u32 [%0],%1;" ::"r"(a), "r"(v) : "memory"); }
DEV void sts64(u32 a, u32 x, u32 y) { asm volatile("st.shared.v2.u32 [%0],{%1,%2};" ::"r"(a), "r"(x), "r"(y) : "memory"); }
DEV void sts128(u32 a, u32 x, u32 y, u32 z, u32 w) { asm volatile("st.shared.v4.u32 [%0],{%1,%2,%3,%4};" ::"r"(a), "r"(x), "r"(y), "r"(z), "r"(w) : "memory"); }
DEV uint4 ldr128(const void* p) { uint4 v; asm volatile("ld.relaxed.gpu.global.v4.u32 {%0,%1,%2,%3},[%4];" : "=r"(v.x), "=r"(v.y), "=r"(v.z), "=r"(v.w) : "l"(p) : "memory"); return v; }
DEV uint2 ldr64(const void* p) { uint2 v; asm volatile("ld.relaxed.gpu.global.v2.u32 {%0,%1},[%2];" : "=r"(v.x), "=r"(v.y) : "l"(p) : "memory"); return v; }
DEV u32 ldr32(const void* p) { u32 v; asm volatile("ld.relaxed.gpu.global.u32 %0,[%1];" : "=r"(v) : "l"(p) : "memory"); return v; }
template <u32 M> DEV void rld128(uint4& v, const void* p, u32 tag) {
  asm volatile("{.reg .pred p; .reg .u32 t; lop3.b32 t,%0,%5,%6,0x28; setp.ne.u32 p,t,0; @p ld.relaxed.gpu.global.v4.u32 {%0,%1,%2,%3},[%4];}"
               : "+r"(v.x), "+r"(v.y), "+r"(v.z), "+r"(v.w) : "l"(p), "r"(tag), "n"(M) : "memory");
}
template <u32 M> DEV void rld64(uint64_t& v, const void* p, u32 tag) {
  asm volatile("{.reg .pred p; .reg .u32 t, h; mov.b64 {t,h},%0; lop3.b32 t,t,%2,%3,0x28; setp.ne.u32 p,t,0; @p ld.relaxed.gpu.global.u64 %0,[%1];}" : "+l"(v) : "l"(p), "r"(tag), "n"(M) : "memory");
}
template <int L> DEV u32 lop3(u32 a, u32 b, u32 c) { u32 r; asm("lop3.b32 %0,%1,%2,%3,%4;" : "=r"(r) : "r"(a), "r"(b), "r"(c), "n"(L)); return r; }
DEV u32 ne3(u32 a, u32 b, u32 c) { u32 r; asm("lop3.b32 %0,%1,%2,%3,0x7e;" : "=r"(r) : "r"(a), "r"(b), "r"(c)); return r; }
DEV void pin(u32 zr, u32 a, u32 b = 0, u32 c = 0, u32 d = 0) { asm volatile("{.reg .pred p; setp.ne.u32 p,%0,0; @p st.shared.v4.u32 [%0],{%1,%2,%3,%4};}" ::"r"(zr), "r"(a), "r"(b), "r"(c), "r"(d) : "memory"); }
DEV void pin2(u32 zr, const void* a, const void* b) { asm volatile("{.reg .pred p; setp.ne.u32 p,%0,0; @p st.shared.v2.u64 [%0],{%1,%2};}" ::"r"(zr), "l"(a), "l"(b) : "memory"); }
DEV const char* rowa(const char* base, u32 key) { const char* r; asm("mad.wide.u32 %0,%1,288,%2;" : "=l"(r) : "r"(~key & 0x1ffc), "l"(base)); return r; }
DEV void str128(void* p, u32 x, u32 y, u32 z, u32 w) { asm volatile("st.relaxed.gpu.global.v4.u32 [%0],{%1,%2,%3,%4};" ::"l"(p), "r"(x), "r"(y), "r"(z), "r"(w) : "memory"); }
DEV void str64(void* p, u32 x, u32 y) { asm volatile("{.reg .u64 d; mov.b64 d,{%1,%2}; st.relaxed.gpu.global.u64 [%0],d;}" ::"l"(p), "r"(x), "r"(y) : "memory"); }
DEV void str32(void* p, u32 x) { asm volatile("st.relaxed.gpu.global.u32 [%0],%1;" ::"l"(p), "r"(x) : "memory"); }
DEV void str16(void* p, u32 x) { asm volatile("st.relaxed.gpu.global.u16 [%0],%1;" ::"l"(p), "h"((unsigned short)x) : "memory"); }
DEV uint4 ldg128(const void* p) { uint4 v; asm volatile("ld.global.nc.v4.u32 {%0,%1,%2,%3},[%4];" : "=r"(v.x), "=r"(v.y), "=r"(v.z), "=r"(v.w) : "l"(p)); return v; }
DEV uint2 ldg64(const void* p) { uint2 v; asm volatile("ld.global.nc.v2.u32 {%0,%1},[%2];" : "=r"(v.x), "=r"(v.y) : "l"(p)); return v; }
DEV u32 ldg32(const void* p) { u32 v; asm volatile("ld.global.nc.u32 %0,[%1];" : "=r"(v) : "l"(p)); return v; }
DEV u32 ldg16(const void* p) { unsigned short v; asm volatile("ld.global.nc.u16 %0,[%1];" : "=h"(v) : "l"(p)); return v; }
#define bsync(id, n) asm volatile("bar.sync %0,%1;" ::"n"(id), "n"(n) : "memory")
#define barrive(id, n) asm volatile("bar.arrive %0,%1;" ::"n"(id), "n"(n) : "memory")
DEV void bsyncr(u32 id) { asm volatile("bar.sync %0,96;" ::"r"(id) : "memory"); }
DEV void barriver(u32 id) { asm volatile("bar.arrive %0,96;" ::"r"(id) : "memory"); }
constexpr u32 BW = 0x0FEA, BS = 0x6532;
DEV void mb_init(u32 a, u32 n) { asm volatile("mbarrier.init.shared.b64 [%0],%1;" ::"r"(a), "r"(n) : "memory"); }
DEV void mb_arrive(u32 a) { asm volatile("mbarrier.arrive.shared.b64 _,[%0];" ::"r"(a) : "memory"); }
DEV void mb_expect(u32 a, u32 bytes) { asm volatile("mbarrier.arrive.expect_tx.shared.b64 _,[%0],%1;" ::"r"(a), "r"(bytes) : "memory"); }
DEV void mb_wait(u32 a, u32 ph = 0) {
  u32 ok; int it = 0;
  do { asm volatile("{.reg .pred p; mbarrier.try_wait.parity.shared.b64 p,[%1],%2; selp.u32 %0,1,0,p;}" : "=r"(ok) : "r"(a), "r"(ph) : "memory"); } while (!ok && ++it < SPIN);
}
template <int N> DEV void bulk_out(void* dst, u32 src) { asm volatile("cp.async.bulk.global.shared::cta.bulk_group [%0],[%1],%2;" ::"l"(dst), "r"(src), "n"(N) : "memory"); }
constexpr u32 WSH = 41472;
DEV void l2_line(const void* p) { asm volatile("prefetch.global.L2 [%0];" ::"l"(p) : "memory"); }
template <int N> DEV void l2_pre(const void* p) { asm volatile("cp.async.bulk.prefetch.L2.global [%0],%1;" ::"l"(p), "n"(N) : "memory"); }
DEV void tma3d(u32 dst, const CUtensorMap* tm, u32 mb, int c0, int c2) {
  asm volatile("cp.async.bulk.tensor.3d.shared::cluster.global.mbarrier::complete_tx::bytes [%0],[%1,{%3,0,%4}],[%2];"
               ::"r"(dst), "l"((uint64_t)tm), "r"(mb), "r"(c0), "r"(c2) : "memory");
}
DEV float blo(u32 w) { return __uint_as_float(w << 16); }
DEV float bhi(u32 w) { return __uint_as_float(w & 0xffff0000u); }
DEV u32 pk_bf(float lo, float hi) { u32 r; asm("cvt.rn.bf16x2.f32 %0,%1,%2;" : "=r"(r) : "f"(hi), "f"(lo)); return r; }
DEV u32 pk_hf(float lo, float hi) { u32 r; asm("cvt.rn.f16x2.f32 %0,%1,%2;" : "=r"(r) : "f"(hi), "f"(lo)); return r; }
DEV float rbf(float x) { return __uint_as_float(pk_bf(0.f, x) & 0xffff0000u); }
DEV u32 bfma(u32 a, u32 b, u32 c) { u32 r; asm("fma.rn.bf16x2 %0,%1,%2,%3;" : "=r"(r) : "r"(a), "r"(b), "r"(c)); return r; }
DEV u32 bmul(u32 a, u32 b) { u32 r; asm("mul.rn.bf16x2 %0,%1,%2;" : "=r"(r) : "r"(a), "r"(b)); return r; }
DEV u32 badd(u32 a, u32 b) { u32 r; asm("add.rn.bf16x2 %0,%1,%2;" : "=r"(r) : "r"(a), "r"(b)); return r; }
DEV u32 hadd(u32 a, u32 b) { u32 r; asm("add.rn.f16x2 %0,%1,%2;" : "=r"(r) : "r"(a), "r"(b)); return r; }
DEV u32 hfma(u32 a, u32 b, u32 c) { u32 r; asm("fma.rn.f16x2 %0,%1,%2,%3;" : "=r"(r) : "r"(a), "r"(b), "r"(c)); return r; }
struct C2 { u32 re, im; };
DEV C2 cm2(C2 a, C2 b) {
  const __half2 ar = *reinterpret_cast<__half2*>(&a.re), ai = *reinterpret_cast<__half2*>(&a.im), br = *reinterpret_cast<__half2*>(&b.re), bi = *reinterpret_cast<__half2*>(&b.im);
  __half2 re = __hfma2(ar, br, __hneg2(__hmul2(ai, bi))), im = __hfma2(ar, bi, __hmul2(ai, br));
  return {*reinterpret_cast<u32*>(&re), *reinterpret_cast<u32*>(&im)};
}
DEV C2 pk2(const float2 (&a)[2]) { return {pk_hf(a[0].x, a[1].x), pk_hf(a[0].y, a[1].y)}; }
DEV C2 pk2c(const float2 (&a)[2]) { return {pk_hf(a[0].x, a[1].x), pk_hf(-a[0].y, -a[1].y)}; }
DEV u32 cpy(u32 x, u32 zr, int alt) {
  u32 r;
  if (alt) asm volatile("xor.b32 %0,%1,%2;" : "=r"(r) : "r"(x), "r"(zr)); else asm volatile("mad.lo.u32 %0,%2,%2,%1;" : "=r"(r) : "r"(x), "r"(zr));
  return r;
}
template <int N> DEV void inc(u32& x) { asm volatile("add.u32 %0,%0,%1;" : "+r"(x) : "n"(N)); }
DEV u32 opq(u32 x) { u32 r; asm volatile("mov.u32 %0,%1;" : "=r"(r) : "r"(x)); return r; }
DEV u32 chan(u32 b, u32 i) { return 16 * (b >> 2) + 2 * (b & 3) + (i & 1) + 4 * (i & 2); }
DEV u32 row16(u32 lane) { const u32 r0 = (lane & 7) + ((lane >> 3) & 1) + 8 * (lane >> 4) - 1; return (r0 ^ ((r0 >> 3) & 3)) * 16; }
DEV u32 clk() { u32 r; asm volatile("mov.u32 %0,%%clock;" : "=r"(r)::"memory"); return r; }
DEV void wait_clk(u32 t, int d) { while ((int)(clk() - t) < d); }
DEV float ex2(float x) { float r; asm("ex2.approx.ftz.f32 %0,%1;" : "=f"(r) : "f"(x)); return r; }
DEV float rcpf(float x) { float r; asm("rcp.approx.ftz.f32 %0,%1;" : "=f"(r) : "f"(x)); return r; }
DEV float2 cmul(float2 a, float2 b) { return make_float2(fmaf(a.x, b.x, -a.y * b.y), fmaf(a.x, b.y, a.y * b.x)); }
DEV float2 csq(float2 a) { return make_float2(fmaf(a.x, a.x, -a.y * a.y), (a.x + a.x) * a.y); }
DEV float2 cexp(float lr2, float th) {
  const float m = ex2(lr2);
  return make_float2(m * __cosf(th), m * __sinf(th));
}
DEV float silu_f(float v) { return v * rcpf(1.f + ex2(-1.4426950408889634f * v)); }
constexpr u32 B2P64 = 0x5F805F80u, B2M64 = 0x1F801F80u, BONE = 0x3F803F80u;
constexpr u32 MODJ = 18 * 128;
DEV float sqrta(float x) { float r; asm("sqrt.approx.ftz.f32 %0,%1;" : "=f"(r) : "f"(x)); return r; }
DEV u32 fu(float x) { return __float_as_uint(x); }
DEV float uf(u32 x) { return __uint_as_float(x); }
DEV void mma_hf_o(float (&d)[4], const float (&c)[4], const u32 (&a)[4], u32 b0, u32 b1) {
  asm("mma.sync.aligned.m16n8k16.row.col.f32.f16.f16.f32 {%0,%1,%2,%3},{%4,%5,%6,%7},{%8,%9},{%10,%11,%12,%13};"
      : "=f"(d[0]), "=f"(d[1]), "=f"(d[2]), "=f"(d[3]) : "r"(a[0]), "r"(a[1]), "r"(a[2]), "r"(a[3]), "r"(b0), "r"(b1), "f"(c[0]), "f"(c[1]), "f"(c[2]), "f"(c[3]));
}

DEV void mma_hf_t(float (&c)[4], const u32 (&a)[4], u32 b0, u32 b1) { mma_hf(c, a[0], a[1], a[2], a[3], b0, b1); }
DEV void cpa16(u32 dst, const void* src) { asm volatile("cp.async.cg.shared.global [%0],[%1],16;" ::"r"(dst), "l"(src) : "memory"); }
DEV void tm_pre(const CUtensorMap* tm) { asm volatile("prefetch.tensormap [%0];" ::"l"((uint64_t)tm) : "memory"); }
#define PROXY_FENCE() asm volatile("fence.proxy.async.shared::cta;" ::: "memory")
struct Prm {
  const char *la, *ai, *cr, *ci, *ldt;
  u32 zero, glo, ghi;
  const char *x, *c;
  char* gs;
  const char *dsk, *wr, *wg, *wu, *wd;
  char* out;
};
DEV char* gptr(const Prm& p, u32 lo) { char* r; asm("mov.b64 %0,{%1,%2};" : "=l"(r) : "r"(lo), "r"(p.ghi)); return r; }
DEV u32 uni(const Prm& p, u32 x) { return x >> p.zero; }
DEV u32 rowo(u32 base, u32 key) { return (~key & 0x1ffc) * 288 + base; }
constexpr float LOG2E = 1.4426950408889634f, F2P64 = 1.8446744073709552e19f, F2M64 = 5.421010862427522e-20f;

template <int S> DEV void y_store(float c0, float c1, float c2, float c3, u32 F, u32 pml, char* yp) {
  str32(yp, bmul(pk_bf(c0, c2), F) | pml);
  str32(yp + S, bmul(pk_bf(c1, c3), F) | pml);
}
DEV u32 sgn2(u32 a, u32 x, u32 y) { return opq(((a - x) >> 31) + ((a - y) >> 31)); }
DEV void merge4(u32 (&h)[8], uint4 a, uint4 b) {
  const u32 e1 = min(a.x, b.x), e2 = max(a.z, b.z), o1 = min(a.y, b.y), o2 = max(a.w, b.w), o0 = max(a.y, b.y), e3 = min(a.z, b.z);
  const u32 f1 = max(e1, e2), f2 = min(e1, e2), p1 = max(o1, o2), p2 = min(o1, o2);
  h[0] = max(a.x, b.x); h[1] = max(o0, f1); h[2] = min(o0, f1); h[3] = max(p1, f2); h[4] = min(p1, f2); h[5] = max(p2, e3); h[6] = min(p2, e3); h[7] = min(a.w, b.w);
}
DEV void top8(u32 (&a)[8], uint4 l, uint4 m) {
  u32 b[8];
  merge4(b, l, m);
#pragma unroll
  for (int i = 0; i < 8; i++) a[i] = max(a[i], b[7 - i]);
#pragma unroll
  for (int s = 4; s; s >>= 1)
#pragma unroll
    for (int i = 0; i < 8; i++) if (!(i & s)) { const u32 x = a[i], y = a[i + s]; a[i] = max(x, y); a[i + s] = min(x, y); }
}
#define POLL(load, cond_bad, code) { int it_ = 0; do { load; } while (__any_sync(~0u, (cond_bad)) & (++it_ <= SPIN)); if (it_ > SPIN) { ERRF(code); } TSN(code, it_); }
DEV u32 tmask(u32 it, u32 m) { u32 r; asm volatile("{.reg .pred p; setp.ne.u32 p,%1,0; selp.u32 %0,%2,0,p;}" : "=r"(r) : "r"(it), "r"(m)); return r; }
#define POLLM(load, bad, M, code) { u32 it_ = SPIN + (tid >> 16), m_; do { m_ = tmask(--it_, M); load; } while (__any_sync(~0u, (bad) & m_)); if (!it_) { ERRF(code); } TSN(code, SPIN - it_); }
#define POLLS(use, load, bad, M, code) { u32 it_ = SPIN + (tid >> 16); for (;;) { const u32 m_ = tmask(--it_, M); use; if (!__any_sync(~0u, (bad) & m_)) break; load; } if (!it_) { ERRF(code); } TSN(code, SPIN - it_); }
#define POLLW(load, cond_bad, code) { int it_ = 0; while (__any_sync(~0u, (cond_bad))) { if (++it_ > SPIN) { ERRF(code); break; } load; } TSN(code, it_); }

#define DOWN(E) if (tid == (b < 108 ? 288 : ~0u)) { const u32 c0 = 64 * (b % 9), c2 = 4 * (b / 9); \
    if (!D0C && E == 1) { mb_expect(SM_MB + 24, 49152); tma3d(SM_TAP, tm_down, SM_MB + 24, c0, c2); } \
    if (DE1 == E) tma3d(SM_WD, tm_down, SM_MB + 24, c0, c2 + 1); \
    if (DE2 == E) tma3d(SM_WD + 12288, tm_down, SM_MB + 24, c0, c2 + 2); \
    if (DE3 == E) tma3d(SM_WD + 24576, tm_down, SM_MB + 24, c0, c2 + 3); }
#define OUTR() { const u32 tl = 4 * ((lane >> 1) & 1) + ((lane >> 2) & 3) + 8 * (lane & 1); \
    bulk_out<1152>(p.out + (uni(p, b * BLK) + tl * 1152), SM_XST + ((lane & 2) + 4 * (lane & 1) + ((lane >> 2) & 1) + (lane & 8)) * ROW); \
    asm volatile("cp.async.bulk.commit_group;" ::: "memory"); }
struct FA { u32 tid, ba, ra, sa, ad, as; };
DEV FA ffn_addr(const Prm& p, u32 tid, u32 b) {
  const u32 w = tid >> 5, lane = tid & 31, kq = w & 3, tg = w >> 2, t = 7 - w;
  FA f = {tid, SM_XS + (lane & 7) * ROW + (18 * kq + (lane >> 3)) * 16, SM_RED + (8 * tg + kq) * 512 + lane * 16, w >= uni(p, 3 + (b & 1)) && w < 8 ? SM_RED + t * 2048 + lane * 16 : 0,
          (t < 4 ? uni(p, p.glo + G_ACT + 512 * b) + 128 * t : uni(p, p.glo + G_ACT + (512 + (b >> 1)) * 128)) + lane * 4, uni(p, p.glo + G_ACT + (b / 9) * 6144) + tid * 16};
  if (AW & 2) { pin(tid >> 16, f.ba, f.ra, f.sa, tid); pin(tid >> 16, f.ad, f.as); }
  return f;
}
DEV void ffn_tail(const Prm& p, const CUtensorMap* tm_down, uint4 (&A)[24], const FA f, const u32 b, const u32 par, const u32 okl) {
  const u32 tid = f.tid, w = tid >> 5, lane = tid & 31, g = lane >> 2, q = lane & 3, tg = w >> 2, zr = tid >> 16;
  const u32 pm = par ? TAGM : 0, kt = par * 3, ba = f.ba, ra = f.ra;
  char* const gs = p.gs;
  __syncthreads();
  TS(25);
  {
    float c0[2][4] = {}, c1[2][4] = {};
    uint4 bb[5];
#pragma unroll
    for (int s = 0; s < 5; s++) bb[s] = ldsm4(ba + s * 64);
#define BX(s) (s & 1 ? bb[s >> 1].z : bb[s >> 1].x), (s & 1 ? bb[s >> 1].w : bb[s >> 1].y)
    if (!(GX & 2)) {
      DOWN(5);
#pragma unroll
      for (int s = 0; s < 9; s++) mma_bf(c0[s & 1], A[s].x, A[s].y, A[s].z, A[s].w, BX(s));
      if (tg < 2) {
#pragma unroll
        for (int s = 0; s < 9; s++) mma_bf(c1[s & 1], A[9 + s].x, A[9 + s].y, A[9 + s].z, A[9 + s].w, BX(s));
        sts128(ra + 2048, fu(c1[0][0] + c1[1][0]), fu(c1[0][1] + c1[1][1]), fu(c1[0][2] + c1[1][2]), fu(c1[0][3] + c1[1][3]));
      }
    } else if (tg < 2) {
#pragma unroll
      for (int s = 0; s < 9; s++) {
        mma_bf(c0[s & 1], A[s].x, A[s].y, A[s].z, A[s].w, BX(s));
        mma_bf(c1[s & 1], A[9 + s].x, A[9 + s].y, A[9 + s].z, A[9 + s].w, BX(s));
      }
      sts128(ra + 2048, fu(c1[0][0] + c1[1][0]), fu(c1[0][1] + c1[1][1]), fu(c1[0][2] + c1[1][2]), fu(c1[0][3] + c1[1][3]));
    } else {
      DOWN(5);
#pragma unroll
      for (int s = 0; s < 9; s++) mma_bf(s & 2 ? c1[s & 1] : c0[s & 1], A[s].x, A[s].y, A[s].z, A[s].w, BX(s));
#pragma unroll
      for (int i = 0; i < 4; i++) c0[1][i] += c1[0][i] + c1[1][i];
    }
    sts128(ra, fu(c0[0][0] + c0[1][0]), fu(c0[0][1] + c0[1][1]), fu(c0[0][2] + c0[1][2]), fu(c0[0][3] + c0[1][3]));
  }
  const u32 atag = q ? 0 : pm, acs = SM_AC + tid * 16, acl = SM_AC + lane * 16;
  if (GX & 4) pin(zr, atag, acs, acl, kt);
  TS(39);
  if (!(GX & 1)) __syncthreads();
  if (!f.sa) { if (GX & 1) bsync(0, 384); }
  else {
    if (GX & 1) bsync(0, 384);
    float s[4];
    const uint4 u0 = lds128(f.sa), u1 = lds128(f.sa + 512), u2 = lds128(f.sa + 1024), u3 = lds128(f.sa + 1536);
    s[0] = (uf(u0.x) + uf(u1.x)) + (uf(u2.x) + uf(u3.x)); s[1] = (uf(u0.y) + uf(u1.y)) + (uf(u2.y) + uf(u3.y));
    s[2] = (uf(u0.z) + uf(u1.z)) + (uf(u2.z) + uf(u3.z)); s[3] = (uf(u0.w) + uf(u1.w)) + (uf(u2.w) + uf(u3.w));
    const u32 sg = pk_bf(silu_f(rbf(s[0])), silu_f(rbf(s[1])));
    str32(gptr(p, f.ad), bmul(sg, bmul(pk_bf(s[2], s[3]), B2M64)) | atag);
  }
  TS(26);
  const bool fin = w == (b < 72 ? 8 : ~0u);
  u32 kg;
  uint4 xt;
  const char* xs;
  if (fin) { kg = lds32(SM_SLOT + 4 * g); xs = gptr(p, rowo(uni(p, p.glo + G_Y + 16 * b), kg)); xt = ldr128(xs); }
  if (b < 108) {
    const char* const as = gptr(p, f.as);
    uint4 a = ldr128(as);
    char* const dst = gptr(p, uni(p, p.glo + G_PART + b * 2048) + w * 512 + lane * 8);
    if (w < 4) {
      const u32 aa = SM_WD + (8 * (lane >> 4) + (lane & 7)) * 128 + (((2 * w + ((lane >> 3) & 1)) ^ (lane & 7)) << 4);
      mb_wait(SM_MB + 24);
#pragma unroll
      for (int s = 0; s < 24; s++) A[s] = ldsm4t(aa + (s < 6 ? SM_TAP - SM_WD : -12288) + s * 2048);
      if (AW & 2) pin2(zr, dst, as);
    }
    conv();
    TS(28);
    if (!(GX & 16)) {
      POLLW(rld128<TAGM>(a, as, pm), (a.x ^ pm) & TAGM, 9);
      sts128(acs, a.x, a.y, a.z, a.w); sts32(acs, a.x & ~TAGM);
    } else
    POLLS({ sts128(acs, a.x, a.y, a.z, a.w); sts32(acs, a.x & ~TAGM); }, rld128<TAGM>(a, as, pm), a.x ^ pm, TAGM, 9);
    TS(27);
    if (w < 4) {
      bsync(8, 384);
      float c[4][4] = {};
#pragma unroll
      for (int s = 0; s < 12; s++) {
        const uint4 bb = ldsm4t(acl + s * 512);
        mma_bf(c[2 * (s & 1)], A[2 * s].x, A[2 * s].y, A[2 * s].z, A[2 * s].w, bb.x, bb.y);
        mma_bf(c[2 * (s & 1) + 1], A[2 * s + 1].x, A[2 * s + 1].y, A[2 * s + 1].z, A[2 * s + 1].w, bb.z, bb.w);
      }
      u32 o[4];
#pragma unroll
      for (int i = 0; i < 4; i++) o[i] = fu((c[0][i] + c[1][i]) + (c[2][i] + c[3][i]));
      str64(dst, (o[0] & ~3u) | kt, o[1]); str64(dst + 256, (o[2] & ~3u) | kt, o[3]);
      TS(29);
    } else barrive(8, 384);
  }
  if (OUTB == 7 && w == 10 && okl < lds32(SM_SLOT + 28)) OUTR();
  if (fin) {
    const u32 ta = clk();
    const char* src = gptr(p, uni(p, p.glo + G_PART + b * 256) + lane * 8);
    const u32 co = uni(p, 16 * b) + 4 * q, gw = lds32(SM_MODS + 5760 + co), hw = lds32(SM_XS + g * ROW + co);
    const float sgm = rcpf(1.f + ex2(-LOG2E * bhi(kg ^ (~((int)kg >> 31) | 0x80000000))));
    char* const dst = p.out + rowo(co, kg);
    conv();
    POLLW(rld128<TAGM>(xt, xs, TAGR), (xt.x ^ TAGR) & TAGM, 10);
    const u32 x1w = (q & 2) ? ((q & 1) ? xt.w : xt.z) : ((q & 1) ? xt.y : bmul(xt.x ^ TAGR, B2P64));
    const u32 sg2 = bmul(pk_bf(sgm, sgm), B2P64);
    pin(zr, x1w, gw, hw, sg2); pin2(zr, dst, src);
    uint64_t v[12];
#pragma unroll
    for (int j = 0; j < 12; j++) v[j] = 1;
    float s0, s1;
    if (PD) wait_clk(ta, PD);
    conv();
    TS(13);
#define VL(j) (u32)v[j]
#define VS(j, s) ((uf((u32)(v[j] >> s)) + uf((u32)(v[j + 1] >> s))) + (uf((u32)(v[j + 2] >> s)) + uf((u32)(v[j + 3] >> s))))
    u32 res;
    POLLM({ _Pragma("unroll") for (int j = 0; j < 12; j++) rld64<3>(v[j], src + j * 9 * 2048, kt);
            s0 = VS(0, 0) + VS(4, 0) + VS(8, 0); s1 = VS(0, 32) + VS(4, 32) + VS(8, 32);
            res = opq(badd(x1w, bmul(gw, badd(hw, bmul(movm(pk_bf(s0, s1)), sg2))))); TSRND(); },
          lop3<0xfe>(ne3(VL(0), VL(1), kt), ne3(VL(2), VL(3), kt), ne3(VL(4), VL(5), kt)) |
          lop3<0xfe>(ne3(VL(6), VL(7), kt), ne3(VL(8), VL(9), kt), ne3(VL(10), VL(11), kt)), 3, 11);
    asm volatile("st.global.u32 [%0],%1;" ::"l"(dst), "r"(res) : "memory");
    if (b == 0 && lane == 0) str32(gs + G_EP, par);
    TS(30); TSE();
  }
  if (w == 10) asm volatile("cp.async.bulk.wait_group.read 0;" ::: "memory");
}

DEV u32 y_lo(const Prm& p, u32 tid, u32 b) {
  const u32 ua = uni(p, p.glo + G_Y + b * 128), ub = uni(p, p.glo + 16384 + (b & ~3) * BLK + (b & 3) * 512);
  return (tid < 256 ? ua : ub) + (((tid & 2) * 4) | ((tid >> 2) & 4)) * (tid < 256 ? BLK : 32) + (tid >> 5) * (16 * BLK) + ((tid >> 2) & 3) * 32 + (tid & 1) * 16;
}
DEV void post_conv(const Prm& p, const CUtensorMap* tm_down, const u32 tid, const u32 b, const u32 b3) {
  const u32 w = tid >> 5, lane = tid & 31;
  const u32 g = lane >> 2, q = lane & 3, e = g >> 2, h = (g >> 1) & 1, hi = g & 1;
  const u32 pm = lds32(SM_THR + 4), par = pm >> 30;
  char* const gs = p.gs;
  const u32 cho = 128 * w + 64 * e + 16 * q;
  u32 x1[4][4], h2[4][4], key[4], lt;
  u32 okl = ~0u;
  FA fa;
  uint4 A[24];
#define AROW(t) const u32 arow = 144 * ((t >> 5) & 3) + ((t >> 1) & 8) + (t & 7), ab = (t & 8) ? SM_UP : SM_GATE;
#define AFRAG9() { _Pragma("unroll") for (int s = 0; s < 9; s++) A[s] = ldsm4t(ab + SLV + arow * 16 + s * 256); }
#define AFRAG18() { const u32 t3 = opq(tid); AROW(t3); if (t3 < 256) { const u32 aa = ab + arow * 64 + ((((t3 >> 6) & 2) ^ ((t3 & 7) >> 1)) << 4); \
      _Pragma("unroll") for (int s = 0; s < 9; s++) { A[s] = ldsm4t(aa + s * 1024); A[9 + s] = ldsm4t((aa ^ 16) + s * 1024); } } else AFRAG9(); }
  if (w < 9) {
    const char* const ys = gptr(p, y_lo(p, tid, b));
    uint4 yv[4];
#pragma unroll
    for (int v = 0; v < 4; v++) yv[v].x = INVAL;
    const u32 tg0 = b < YL ? pm : INVAL;
    if (w >= 4) { pin2(tid >> 16, ys, ys); bsync(12, N12); TS(18); }
#pragma unroll
    for (int v = 0; v < 4; v++) rld128<TAGM>(yv[v], ys + v * BLK, tg0);
    const u32 tc = clk();
    const u32 ma = SM_MODS + cho, xa = SM_XST + (2 * h + 4 * hi) * ROW + cho;
    const uint4 sa = lds128(ma), ca = lds128(ma + 1152), ga = lds128(ma + 2304);
    const uint4 rb = lds128((g & 2) ? SM_ONE + 16 * hi : (ma ^ 64) + 8064 + 1152 * hi);
    const u32 saw[4] = {sa.x, sa.y, sa.z, sa.w}, caw[4] = {ca.x, ca.y, ca.z, ca.w}, gaw[4] = {ga.x, ga.y, ga.z, ga.w};
#pragma unroll
    for (int k = 0; k < 4; k++) {
      const uint2 st = lds64(SM_ST + 16 * (2 * h + 4 * hi + (k & 1) + 8 * (k >> 1)));
      const uint4 xv = lds128(xa + ((k & 1) + 8 * (k >> 1)) * ROW);
      x1[k][0] = xv.x; x1[k][1] = xv.y; x1[k][2] = xv.z; x1[k][3] = xv.w;
#pragma unroll
      for (int v = 0; v < 4; v++) x1[k][v] = badd(x1[k][v], bfma(bmul(badd(x1[k][v], st.x), st.y), caw[v], saw[v]));
    }
    const bool own = (q >> 1) == e;
    const u32 spw = SM_SP + (2 * w + e) * 320 + (g & 3) * 16 + (own ? ((q & 1) == h ? 4 : 12) : 8 - 8 * (q & 1));
    if (SMD && w < 4) asm volatile("setmaxnreg.dec.sync.aligned.u32 168;");
    if (b >= YL) wait_clk(tc, YD);
    conv();
    TS(13);
    POLLW(_Pragma("unroll") for (int v = 0; v < 4; v++) rld128<TAGM>(yv[v], ys + v * BLK, pm), lop3<0xa8>(ne3(yv[0].x, yv[1].x, pm), ne3(yv[2].x, yv[3].x, pm), TAGM), 5);
    TS(19);
    if (!SMD && w < 4) asm volatile("setmaxnreg.dec.sync.aligned.u32 168;");
#pragma unroll
    for (int k = 0; k < 4; k += 2) {
      float X[4] = {}, Y[4] = {}, R[4] = {};
#pragma unroll
      for (int v = 0; v < 4; v++) {
        const u32 y0 = k ? yv[v].z : yv[v].x & ~TAGM, y1 = k ? yv[v].w : yv[v].y;
        x1[k][v] = bfma(movm(y0), gaw[v], x1[k][v]);
        x1[k + 1][v] = bfma(movm(y1), gaw[v], x1[k + 1][v]);
        mma8_bf(X, x1[k][v], x1[k + 1][v], x1[k][v]); mma8_bf(Y, x1[k][v], x1[k + 1][v], x1[k + 1][v]);
        if (v & 1) mma_bf(R, x1[k][v - 1], x1[k + 1][v - 1], x1[k][v], x1[k + 1][v], v & 2 ? rb.z : rb.x, v & 2 ? rb.w : rb.y);
      }
      sts32(spw + k * 64, fu(own ? (hi ? X[1] : X[0]) : R[0] + R[1]));
      sts32(spw + k * 64 + 64, fu(own ? (hi ? Y[3] : Y[2]) : R[2] + R[3]));
    }
    barrive(1, N1);
    TS(36);
    if (AFP) { asm volatile("setmaxnreg.inc.sync.aligned.u32 168;"); mb_wait(SM_MB + 8); mb_wait(SM_MB + 16); }
    const uint4 sb = lds128(ma + 3456), cb = lds128(ma + 4608), gb = lds128(ma + 5760);
    const u32 sbw[4] = {sb.x, sb.y, sb.z, sb.w}, cbw[4] = {cb.x, cb.y, cb.z, cb.w}, gbw[4] = {gb.x, gb.y, gb.z, gb.w};
    const u32 t3 = opq(tid), zr = t3 >> 16;
    AROW(t3);
    const u32 aa = ab + arow * 64 + ((((t3 >> 6) & 2) ^ ((t3 & 7) >> 1)) << 4), sta = SM_ST2 + 16 * (g & 3);
    const u32 rowl = uni(p, p.glo + b * BLK) + (4 * h + 8 * hi) * 1152 + cho;
    char* const rowp = gptr(p, rowl);
    if (AFP) { pin(zr, aa, sta, xa); pin2(zr, rowp, rowp); }
    bsync(2, 320);
    TS(37);
    uint4 st[4];
#pragma unroll
    for (int k = 0; k < 4; k++) st[k] = lds128(sta + 64 * k);
    lt = lds32(SM_THR);
#define AFL() { _Pragma("unroll") for (int s = 0; s < 9; s++) { A[s] = ldsm4t(aa + s * 1024); A[9 + s] = ldsm4t((aa ^ 16) + s * 1024); } }
    if (AFP && (AFM >> w & 1)) { if (w < 8) AFL() else AFRAG9(); }
#pragma unroll
    for (int k = 0; k < 4; k++) {
      key[k] = st[k].w;
      u32 o[4];
#pragma unroll
      for (int v = 0; v < 4; v++) {
        const u32 d = badd(x1[k][v], st[k].x), z = bfma(d, st[k].y, bmul(d, st[k].z));
        h2[k][v] = FH ? bfma(z, cbw[v], sbw[v]) : badd(bmul(z, cbw[v]), sbw[v]);
        o[v] = FO ? bfma(gbw[v], h2[k][v], x1[k][v]) : badd(x1[k][v], bmul(gbw[v], h2[k][v]));
      }
      h2[k][0] = bmul(h2[k][0], B2M64) | TAGR; x1[k][0] = bmul(x1[k][0], B2M64) | TAGR;
      if (key[k] >= lt) str128(rowp + k * 1152, h2[k][0], h2[k][1], h2[k][2], h2[k][3]);
      sts128(xa + ((k & 1) + 8 * (k >> 1)) * ROW, o[0], o[1], o[2], o[3]);
    }
    barrive(3, 320);
    TS(21);
    if (!AFP) { asm volatile("setmaxnreg.inc.sync.aligned.u32 168;"); mb_wait(SM_MB + 8); mb_wait(SM_MB + 16); AFRAG18(); }
    else if (!(AFM >> w & 1)) { if (w < 8) AFL() else AFRAG9(); }
    TS(22);
    const u32 rr = tid * 57 >> 12, rc = tid * 16 - rr * 1152, sl = SM_SLOT + 8 * rr;
    const u32 rb_ = p.glo + rc;
    const u32 km = max(max(key[0], key[1]), max(key[2], key[3])), xd = SM_XS + rr * (2 * ROW) + rc;
    if (RW & 2) { pin(tid >> 16, sl, km, xd); pin(tid >> 16, rb_, rowl); }
    fa = ffn_addr(p, tid | p.zero, b);
    bsync(6, 320);
    TS(24);
    const uint2 sk = lds64(sl);
    const char *r0 = gptr(p, rowo(rb_, sk.x)), *r1 = gptr(p, rowo(rb_, sk.y));
    uint4 rv[2] = {ldr128(r0), ldr128(r1)};
    barrive(15, 320);
    const u32 g8 = lds32(SM_SLOT + 28);
    if (__any_sync(~0u, km >= g8 && lt > g8)) {
      char* const rowq = gptr(p, opq(rowl));
#pragma unroll
      for (int k = 0; k < 4; k++) if (key[k] >= g8 && key[k] < lt) str128(rowq + k * 1152, h2[k][0], h2[k][1], h2[k][2], h2[k][3]);
    }
    bsync(5, 320);
    const uint2 sf = lds64(sl);
    const u32 f8 = lds32(SM_SLOT + 28);
    if (__any_sync(~0u, km >= f8)) {
      char* const rowq = gptr(p, opq(rowl));
#pragma unroll
      for (int k = 0; k < 4; k++) if (key[k] >= f8) str128(rowq + (G_Y + k * 1152), x1[k][0], x1[k][1], x1[k][2], x1[k][3]);
    }
    if (__any_sync(~0u, sf.x != sk.x || sf.y != sk.y)) {
      r0 = gptr(p, rowo(rb_, sf.x)); r1 = gptr(p, rowo(rb_, sf.y));
      rv[0].x = rv[1].x = INVAL;
    }
    if (!(GX & 8)) {
      POLLW({ rld128<TAGM>(rv[0], r0, TAGR); rld128<TAGM>(rv[1], r1, TAGR); }, ne3(rv[0].x, rv[1].x, TAGR) & TAGM, 8);
#pragma unroll
      for (int j = 0; j < 2; j++) sts128(xd + j * ROW, bmul(rv[j].x ^ TAGR, B2P64), rv[j].y, rv[j].z, rv[j].w);
    } else
    POLLS(_Pragma("unroll") for (int j = 0; j < 2; j++) { sts128(xd + j * ROW, rv[j].x, rv[j].y, rv[j].z, rv[j].w); sts32(xd + j * ROW, bmul(rv[j].x ^ TAGR, B2P64)); },
          { rld128<TAGM>(rv[0], r0, TAGR); rld128<TAGM>(rv[1], r1, TAGR); }, ne3(rv[0].x, rv[1].x, TAGR), TAGM, 8);
    TS(38);
  } else {
    u32 ok, lr;
    if (w == 10) {
      uint2 rc = lds64(SM_RC + 8 * min(lane, 17u));
      float r1 = lane < 18 ? uf(rc.x) : 0.f, r2 = lane < 18 ? uf(rc.y) : 0.f;
#pragma unroll 1
      for (int o = 16; o; o >>= 1) { r1 += __shfl_xor_sync(~0u, r1, o); r2 += __shfl_xor_sync(~0u, r2, o); }
      const u32 tl = 4 * ((lane >> 1) & 1) + ((lane >> 2) & 3) + 8 * (lane & 1), kl = (2047 - 16 * b - tl) << 2 | par * 3;
      const u32 kp = uni(p, p.glo + G_KEY + b * KST) + (tid >> 16);
      const u32 spr = SM_SP + (lane >> 4) * 9 * 320 + (lane & 15) * 16;
      TS(31);
      r2 += 0.f;
      const u32 nth = b < NB8 ? 7 : NEARLY - 1, ka = SM_KEY + 4 * (lane & 15), kb = SM_KEY + 2 * (lane & 16), lim = lane < 16 ? 8 : 0;
      pin(tid >> 16, kl, ka, kb, lim); pin(tid >> 16, kp);
      conv();
      bsync(1, N1);
      uint4 t = lds128(spr);
      float S1 = uf(t.x), S2 = uf(t.y), S3 = uf(t.z);
#pragma unroll
      for (int i = 1; i < 9; i++) { t = lds128(spr + i * 320); S1 += uf(t.x); S2 += uf(t.y); S3 += uf(t.z); }
      S1 += __shfl_xor_sync(~0u, S1, 16); S2 += __shfl_xor_sync(~0u, S2, 16); S3 += __shfl_xor_sync(~0u, S3, 16);
      const float mu = S1 * (1.f / 576.f), var = fmaxf(fmaf(-mu, mu, S2 * (1.f / 576.f)), 0.f);
      const float m = rbf(mu), rs = rcpf(rbf(sqrta(rbf(rbf(var) + 1e-5f))));
      const u32 rb = pk_bf(0.f, fmaf(fmaf(-m, r1, S3), rs, r2));
      ok = ((rb ^ (((int)rb >> 31) | 0x80000000)) & 0xffff0000u) | kl;
      const float rh = rbf(rs);
      const u32 oh = ok >> 1;
      sts32(ka, oh);
      __syncwarp();
      const uint4 o0 = lds128(kb), o1 = lds128(kb + 16);
      sts128(SM_ST2 + 16 * (lane & 15), pk_bf(-m, -m), pk_bf(rh, rh), pk_bf(rs - rh, rs - rh), ok);
      lr = opq(sgn2(oh, o0.x, o0.y) + sgn2(oh, o0.z, o0.w)) +
           opq(sgn2(oh, o1.x, o1.y) + sgn2(oh, o1.z, o1.w));
      lr += __shfl_xor_sync(~0u, lr, 16);
      asm volatile("{.reg .pred p; setp.lt.u32 p,%0,%1; @p st.relaxed.gpu.global.u32 [%2],%3;}" ::"r"(lr), "r"(lim), "l"(gptr(p, kp + 4 * lr)), "r"(ok) : "memory");
      if (lr == nth) sts32(SM_THR, ok);
      barrive(2, 320);
      barrive(13, 64);
      TS(20);
    } else if (w == 9) {
      if (DB1) bsync(1, N1); else { bsync(12, N12); wait_clk(clk(), DD); }
      PROXY_FENCE();
      DOWN(1);
    } else {
      const char* ks = gs + (G_KEY + (lane >> 1) * KST + (lane & 1) * 16);
      const u32 kt = par * 3;
      uint4 L[8];
      u32 H[8];
#define KBAD(j) ((L[j].x ^ kt) & 3)
#define KLD(j) L[j] = ldr128(ks + j * 16 * KST)
#pragma unroll
      for (int j = 0; j < 8; j++) L[j].x = INVAL;
      bsync(13, 64);
      wait_clk(clk(), b < KE ? KD : b < KF ? KDB : b < YL ? KDC : KD1);
      TS(34);
      POLL({ _Pragma("unroll") for (int j = 0; j < 8; j++) if (KBAD(j)) KLD(j);
             merge4(H, L[0], L[1]); top8(H, L[2], L[3]);
             asm volatile("" : "+r"(H[0]), "+r"(H[1]), "+r"(H[2]), "+r"(H[3]), "+r"(H[4]), "+r"(H[5]), "+r"(H[6]), "+r"(H[7])); TS(32); },
           KBAD(0) | KBAD(1) | KBAD(2) | KBAD(3) | KBAD(4) | KBAD(5), 6);
      u32 u = __reduce_max_sync(~0u, max(H[0], max(L[4].x, L[5].x)));
      top8(H, L[4], L[5]);
      TS(35);
#pragma unroll 1
      for (u32 pass = p.zero;; pass++) {
        u32 G[8], m[8];
        conv();
#pragma unroll
        for (int i = 0; i < 8; i++) G[i] = H[i];
        u32 x0 = G[0], x1 = G[1];
#pragma unroll
        for (int r = 0; r < 8; r++) {
          const u32 ur = u;
          const bool win = x0 == ur;
          if (r < 7) { x0 = max(x0 - ur, x1 - ur); u = __reduce_max_sync(~0u, x0); }
          m[r] = r ? m[r - 1] + ur : ur;
          if (r == 0) { if (KBAD(6)) KLD(6); if (KBAD(7)) KLD(7); }
#pragma unroll
          for (int i = 1; i < 7 - r; i++) G[i] = win ? G[i + 1] : G[i];
          x1 = G[1] - m[r];
          if ((r & 3) == 3) sts128(SM_SLOT + 4 * r - 12, m[r - 3], m[r - 2], m[r - 1], m[r]);
        }
        asm volatile("{.reg .pred p; setp.eq.u32 p,%0,0; @p bar.arrive 6,320;}" ::"r"(pass) : "memory");
        if (pass) break;
        TS(23);
        conv();
        POLLW({ if (KBAD(6)) KLD(6); if (KBAD(7)) KLD(7); }, KBAD(6) | KBAD(7), 7);
        if (!__any_sync(~0u, max(L[6].x, L[7].x) > m[7])) break;
        u = __reduce_max_sync(~0u, max(H[0], max(L[6].x, L[7].x)));
        top8(H, L[6], L[7]);
      }
      barrive(5, 320);
      TS(33);
    }
    asm volatile("setmaxnreg.inc.sync.aligned.u32 168;");
    mb_wait(SM_MB + 8); mb_wait(SM_MB + 16);
    AROW(tid);
    AFRAG9();
    fa = ffn_addr(p, tid | p.zero, b);
    TS(22);
    if (w == 10) {
      bsync(3, 320);
      PROXY_FENCE();
      if (lane < 16 && lr >= 8) OUTR();
      if (lane < 16 && lr < 8) okl = ok;
    } else if (w == 9) {
      bsync(15, 320);
      DOWN(4);
      TS(13);
    }
  }
  ffn_tail(p, tm_down, A, fa, b3, par, okl);
}

__global__ void __launch_bounds__(384, 1)
fused_kernel(const Prm p, const __grid_constant__ CUtensorMap tm_mod, const __grid_constant__ CUtensorMap tm_gate, const __grid_constant__ CUtensorMap tm_gs,
             const __grid_constant__ CUtensorMap tm_up, const __grid_constant__ CUtensorMap tm_us, const __grid_constant__ CUtensorMap tm_down) {
  extern __shared__ __align__(1024) unsigned char smem[];
  u32 la, ai, ldt; uint2 cr, ci;
  {
    const u32 t = threadIdx.x, d = t < 256 ? chan(blockIdx.x, t >> 5) : 512 + (blockIdx.x >> 1), o = d * 256 + 8 * (t & 31), o4 = o + ((t < 256 ? t >> 5 : t >> 3) & 4);
    asm volatile("{.reg .pred p; .reg .u16 h; setp.ne.u32 p,%7,0; @p ld.global.nc.u32 %0,[%8]; @p ld.global.nc.u32 %1,[%9]; @p ld.global.nc.v2.u32 {%2,%3},[%10];"
                 "@p ld.global.nc.v2.u32 {%4,%5},[%11]; @p ld.global.nc.u16 h,[%12]; cvt.u32.u16 %6,h;}"
                 : "=r"(la), "=r"(ai), "=r"(cr.x), "=r"(cr.y), "=r"(ci.x), "=r"(ci.y), "=r"(ldt)
                 : "r"(0x6ffu >> (t >> 5) & 1), "l"(p.la + o4), "l"(p.ai + o4), "l"(p.cr + o), "l"(p.ci + o), "l"(p.ldt + 2 * d));
  }
  const u32 t0 = clk();
  const u32 tid = __shfl_sync(~0u, threadIdx.x, threadIdx.x & 31), b = blockIdx.x + p.zero;
  const u32 w = tid >> 5, lane = tid & 31;
  const u32 g = lane >> 2, q = lane & 3, hi = g & 1;
  const u32 rho = b & 1, Ps = 512 + (b >> 1);
  char* const gs = p.gs;
  TS0();
  const bool kw = w != 8 && w != 11;
  const u32 ksig = w < 8 ? (w & 3) : 4, khf = w < 8 ? (w >> 2) : (w & 1);
  if (!kw) {
    if (tid == 352) {
#pragma unroll
      for (int i = 0; i < 5; i++) mb_init(SM_MB + 8 * i, i < 4 ? 1 : 64);
      asm volatile("fence.mbarrier_init.release.cluster;" ::: "memory");
      tm_pre(&tm_mod);
    }
    const char* cp = p.c + (576 * (w & 1) + 24 * min(lane, 23u));
    const uint2 c0 = ldg64(cp);
    la = c0.x; ai = c0.y; cr = ldg64(cp + 8); ci = ldg64(cp + 16);
  }
  u32 b3;
  asm volatile("shr.u32 %0,%1,%2;" : "=r"(b3) : "r"(blockIdx.x), "r"(p.zero));
  const u32 zr = tid >> 16;
  const u32 epv = ldr32(gs + (G_EP + zr));
  const u32 tp = SM_TAP + ksig * TAPS;
  if (kw && !khf) {
#pragma unroll 1
    for (u32 i = lane * 16; i < TAPS; i += 512) sts128(tp + i, 0, 0, 0, 0);
  }
  if (tid < 128) sts128(SM_INV + 16 * tid, INVAL, 0, 1, 0);
  if (tid >= 124) str128(gs + (tid >= 380 ? G_MOD + b * 128 + q * 16 : b * BLK + 16384 - 252 * 16 + tid * 16 + (tid < 252 ? G_Y + 2048 : 0)), INVAL, 0, 1, 0);
  if (tid == (b < 36 ? 352 : ~0u)) { while (clk() - t0 < DMOD); mb_expect(SM_MB, 36864); tma3d(SM_UP, &tm_mod, SM_MB, 32 * b, 0); }
  if (w < 9) {
    while ((int)(clk() - t0) < DX);
    const char* xp = p.x + (b * BLK + (lane >> 3) * 1152 + 128 * w + 16 * (lane & 7));
    const u32 xd = SM_XST + (((lane >> 3) & 1) + 8 * (lane >> 4)) * ROW + 128 * w + 16 * (lane & 7);
#pragma unroll
    for (int i = 0; i < 4; i++) cpa16(xd + 2 * ROW * i, xp + 4608 * i);
  }
  const u32 ktab = w < 8 ? SM_MODS + w * KTAB : SM_ZS + (w - 9) * KTAB;
  float k2048 = 0.f;
  if (kw) {
    u32 mx = __vmaxu2(__vmaxu2(cr.x & 0x7fff7fff, cr.y & 0x7fff7fff), __vmaxu2(ci.x & 0x7fff7fff, ci.y & 0x7fff7fff));
    const u32 E = max(__reduce_max_sync(~0u, max(mx & 0xffff, mx >> 16)) >> 7, 8u);
    TS(1);
    const float dt = rbf(ex2(blo(ldt) * LOG2E)), csc = uf((257 - E) << 23 | (fu(dt) & 0x7fffff));
    sts32(SM_SC + 16 * ksig + 12, fu(uf(fu(dt) & 0x7f800000) * uf((E - 2) << 23)));
    const u32 crw = khf ? cr.y : cr.x, ciw = khf ? ci.y : ci.x;
    float2 C[2], w4[2], w8[2], w16[2], w32[2], w64[2], w128[2], w256[2], w512[2], a1[2], a2[2], a3[2], t0[2], t1[2], s3[2];
#pragma unroll
    for (int m = 0; m < 2; m++) {
      const float lr2 = rbf(ex2((m ? bhi(la) : blo(la)) * LOG2E)) * dt * -LOG2E, th = (m ? bhi(ai) : blo(ai)) * dt;
      C[m] = make_float2((m ? bhi(crw) : blo(crw)) * csc, (m ? bhi(ciw) : blo(ciw)) * csc);
      const float2 w1 = cexp(lr2, th), w2 = csq(w1);
      w64[m] = cexp(64.f * lr2, 64.f * th);
      w4[m] = csq(w2); w8[m] = csq(w4[m]); w16[m] = csq(w8[m]); w32[m] = csq(w16[m]);
      w128[m] = csq(w64[m]); w256[m] = csq(w128[m]); w512[m] = csq(w256[m]);
      const float2 w1024 = csq(w512[m]);
      a1[m] = cmul(C[m], w1); a2[m] = cmul(C[m], w2); a3[m] = cmul(a1[m], w2);
      t0[m] = cmul(C[m], w1024); t1[m] = cmul(t0[m], w128[m]); s3[m] = cmul(w8[m], w16[m]);
      k2048 += fmaf(t0[m].x, w1024.x, -t0[m].y * w1024.y);
    }
    C2 B0[8], B1[8], B2[8], S[8];
    B0[0] = pk2(C); B0[1] = pk2(a1); B0[2] = pk2(a2); B0[3] = pk2(a3);
    const C2 h4 = pk2(w4), h256 = pk2(w256), h512 = pk2(w512);
#pragma unroll
    for (int i = 0; i < 4; i++) B0[4 + i] = cm2(B0[i], h4);
#pragma unroll
    for (int i = 0; i < 4; i++) B1[i] = cm2(B0[2 * i], h256);
    B1[4] = cm2(B0[0], h512); B1[5] = cm2(B0[4], h512);
    B1[6] = cm2(B1[4], h256); B1[7] = cm2(B1[5], h256);
    const u32 ta = ktab + lane * 128, f = ((lane & 3) << 5) | ((lane & 4) << 2);
#pragma unroll
    for (int i = 0; i < 8; i++) sts128(ta + ((i << 4) ^ f), B0[i].re, B0[i].im, B1[i].re, B1[i].im);
    B2[0] = pk2(t0); B2[1] = pk2(t1);
    B2[2] = cm2(B2[0], h256); B2[3] = cm2(B2[1], h256);
#pragma unroll
    for (int i = 0; i < 4; i++) B2[4 + i] = cm2(B2[i], h512);
    S[0] = {0x3C003C00u, 0u}; S[1] = pk2c(w8); S[2] = pk2c(w16); S[3] = pk2c(s3); S[4] = pk2c(w32);
#pragma unroll
    for (int i = 1; i < 4; i++) S[4 + i] = cm2(S[i], S[4]);
#pragma unroll
    for (int i = 0; i < 8; i++) sts128(ta + 4096 + ((i << 4) ^ f), B2[i].re, B2[i].im, S[i].re, S[i].im);
    const C2 m64 = pk2c(w64), m128 = pk2c(w128);
    sts128(ktab + 8192 + lane * 16, m64.re, m64.im, m128.re, m128.im);
    __syncwarp();
  } else {
    u32 sa = SM_SIL + 576 * (w & 1) + 24 * min(lane, 23u);
#pragma unroll 1
    for (int j = 0; j < 6; j++) {
      sts32(sa, pk_bf(silu_f(blo(la)), silu_f(bhi(la))));
      la = ai; ai = cr.x; cr.x = cr.y; cr.y = ci.x; ci.x = ci.y; sa += 4;
    }
    bsync(7, 64);
  }
  TS(2);
  const u32 pm = (__reduce_or_sync(~0u, epv) & 1) ? 0 : TAGM;
  sts32(SM_THR + 4, pm);
  if (w < 9) {
    asm volatile("cp.async.wait_all;" ::: "memory");
    __syncwarp();
    TS(4);
    if (tid == (b - 36 < 72 ? 256 : ~0u)) { mb_expect(SM_MB, 36864); tma3d(SM_UP, &tm_mod, SM_MB, 32 * b, 0); }
    const u32 xa = SM_XST + (lane & 15) * ROW + 128 * w + 16 * (lane >> 4);
    float s[4] = {}, X[2][4] = {}, Y[2][4] = {};
#pragma unroll
    for (int j = 0; j < 4; j++) {
      const uint4 a = ldsm4(xa + 32 * j);
      mma8_bf(X[0], a.x, a.y, a.x); mma8_bf(Y[0], a.x, a.y, a.y);
      mma8_bf(X[1], a.z, a.w, a.z); mma8_bf(Y[1], a.z, a.w, a.w);
      mma_bf(s, a.x, a.y, a.z, a.w, BONE, BONE);
    }
    uint4 t[4];
#pragma unroll
    for (int j = 0; j < 4; j++) t[j] = ldsm4t(xa + 32 * j);
    const float u0 = hi ? X[0][1] + X[1][1] : X[0][0] + X[1][0], u1 = hi ? Y[0][3] + Y[1][3] : Y[0][2] + Y[1][2];
    if (q == g >> 1) sts128(SM_SP + w * 128 + g * 16, fu(s[0]), fu(u0), fu(s[2]), fu(u1));
    bsync(1, 288);
    TS(7);
    const u32 spr = SM_SP + (lane & 7) * 16 + (lane & 8);
    const uint2 t8 = lds64(spr + 1024);
    const float f8 = lane < 16 ? 1.f : 0.f;
    float S1 = uf(t8.x) * f8, S2 = uf(t8.y) * f8;
#pragma unroll
    for (int i = 0; i < 4; i++) { const uint2 u = lds64(spr + (lane & 16) * 32 + i * 128); S1 += uf(u.x); S2 += uf(u.y); }
    S1 += __shfl_xor_sync(~0u, S1, 16); S2 += __shfl_xor_sync(~0u, S2, 16);
    const float mu = S1 * (1.f / 576.f), var = fmaxf(fmaf(-mu, mu, S2 * (1.f / 576.f)), 0.f);
    const float m = rbf(mu), rs = rcpf(rbf(sqrta(rbf(rbf(var) + 1e-5f))));
    const float ra = rs * 0.0625f;
    sts64(SM_AF + w * 128 + (lane & 15) * 8, fu(ra), fu(-m * ra));
    __syncwarp();
    TS(55);
    const uint4 f0 = lds128(SM_AF + w * 128 + q * 16), f1 = lds128(SM_AF + w * 128 + 64 + q * 16);
    const u32 zdst = SM_GATE + w * 2048 + (g >> 1) * 128 + (lane & 15) * 8;
    const u32 pz = (q & 1) ? 0 : pm;
#pragma unroll
    for (int j = 0; j < 8; j++) {
      const u32 x0 = j & 1 ? t[j >> 1].z : t[j >> 1].x, x1 = j & 1 ? t[j >> 1].w : t[j >> 1].y;
      sts64((j & 1 ? zdst ^ 64 : zdst) + 512 * (j >> 1), pk_hf(fmaf(blo(x0), uf(f0.x), uf(f0.y)), fmaf(bhi(x0), uf(f0.z), uf(f0.w))) | pz,
            pk_hf(fmaf(blo(x1), uf(f1.x), uf(f1.y)), fmaf(bhi(x1), uf(f1.z), uf(f1.w))));
    }
    TS(53);
    if (w < 8) barrive(15, 288);
    else {
      bsync(15, 288);
      TS(54);
      if (lane == 0) {
        PROXY_FENCE();
        bulk_out<BLK>(gs + b * BLK, SM_GATE);
        asm volatile("cp.async.bulk.commit_group;" ::: "memory");
        if (PFG & 1) l2_pre<WSH / 2>(p.wg + b * WSH);
      }
      const float rh = rbf(rs);
      sts128(SM_ST + 16 * (lane & 15), pk_bf(-m, -m), pk_bf(rh, rh), pk_bf(rs - rh, rs - rh), 0);
    }
    TS(5);
  }
  if (kw) {
    float D[5][4] = {};
    u32 ta = ktab + q * 128 + ((g ^ (q << 1)) << 4), tm = ktab + 8192 + q * 16;
#pragma unroll 2
    for (int s = 0; s < 8; s++) {
      const uint4 ca = lds128(ta), cb = lds128(ta + 4096), ma = lds128(tm);
      ta = (ta + 512) ^ 16; tm += 64;
      k2048 += __shfl_xor_sync(~0u, k2048, 16 >> s);
      const C2 s0 = {cb.z, cb.w}, s1 = cm2(s0, {ma.x, ma.y}), s2 = cm2(s0, {ma.z, ma.w}), s3 = cm2(s1, {ma.z, ma.w});
      mma_hf(D[0], s0.re, s1.re, s0.im, s1.im, ca.x, ca.y);
      mma_hf(D[2], s0.re, s1.re, s0.im, s1.im, ca.z, ca.w);
      mma_hf(D[4], s0.re, s1.re, s0.im, s1.im, cb.x, cb.y);
      mma_hf(D[1], s2.re, s3.re, s2.im, s3.im, ca.x, ca.y);
      mma_hf(D[3], s2.re, s3.re, s2.im, s3.im, ca.z, ca.w);
    }
    TS(3);
    const u32 xa = (w < 8 ? SM_MODS + (4 + ksig) * KTAB : SM_ZS) + lane * 16;
    if (khf) {
      __syncwarp();
#pragma unroll
      for (int j = 0; j < 5; j++) sts128(xa + 512 * j, fu(D[j][0]), fu(D[j][1]), fu(D[j][2]), fu(D[j][3]));
      if (lane == 0) sts32(xa + 2560, fu(k2048));
      asm volatile("bar.arrive %0,64;" ::"r"(2 + ksig) : "memory");
    } else {
      const u32 t1 = tp + (q < 2 ? (128 + 4 * g + 2 * q) * 4 : T3 * 4 + ((32 * q - 64 + g) ^ 1) * 2);
      const u32 x = 16 * q + (g >> 1) + hi + 1, tb = tp + (hi ? T7E : T9E) * 4 - 4;
      const u32 te = tb + (x + 2 * (x & 1)) * 2, to = tb + TEO * 4 + (x ^ 1) * 2;
      asm volatile("bar.sync %0,64;" ::"r"(2 + ksig) : "memory");
#pragma unroll
      for (int j = 0; j < 5; j++) { const uint4 t = lds128(xa + 512 * j); D[j][0] += uf(t.x); D[j][1] += uf(t.y); D[j][2] += uf(t.z); D[j][3] += uf(t.w); }
      k2048 = (k2048 + uf(lds32(xa + 2560))) * 0.125f;
#pragma unroll
      for (int r = 0; r < 4; r++) {
        const u32 v = pk_hf(D[2 + (r >> 1)][2 * (r & 1)], D[2 + (r >> 1)][2 * (r & 1) + 1]);
        if (q < 2) {
          const u32 vv = __byte_perm(v, v, 0x1010);
          sts32(t1 + (TO + 32 * r) * 4, vv); sts16(t1 + (TO + 32 * r + 1) * 4 + 2, v >> 16); sts16(t1 + (TO + 32 * r - 1) * 4, v);
          sts64(t1 + (TE + 32 * r) * 4, vv, __byte_perm(v, v, 0x1032));
        } else {
          sts16(t1 + 16 * r, v >> 16);
          if (r == 0 && lane == 2) {
            const u32 vv = __byte_perm(v, v, 0x1010);
            sts32(tp + (TO + 256) * 4, vv); sts16(tp + (TO + 257) * 4 + 2, v); sts16(tp + (TO + 255) * 4, v); sts64(tp + (TE + 256) * 4, vv, vv);
          } else sts16(t1 + 16 * r - ((T3 - T5) * 4 + 6) + 8 * hi, v);
        }
      }
#pragma unroll
      for (int r = 0; r < 2; r++) {
        const u32 v = pk_hf(D[4][2 * r], D[4][2 * r + 1]);
        if (r == 0 && lane == 0) { sts16(tp + T5 * 4 + 62 * 2, v); sts32(SM_KV + 4 * ksig, v & 0xffff); sts16(tp + (T9E + TEO) * 4 + 62 * 2, pk_hf(k2048, 0.f)); }
        else { sts16(te + 8 * r, v); sts16(to + 8 * r, v); }
        sts16(te + 8 * r + 16, v >> 16); sts16(to + 8 * r + 16, v >> 16);
      }
      __syncwarp();
#pragma unroll
      for (int r = 0; r < 4; r++) {
        const u32 v = pk_hf(D[r >> 1][2 * (r & 1) + 1], D[r >> 1][2 * (r & 1)]), t2 = tp + lane * 4 + 128 * r;
        sts32(t2 + TO * 4, v); sts16(t2 + TE * 4, v >> 16); sts16(t2 + (TE + 1) * 4 + 2, v);
      }
      __syncwarp();
    }
  } else if (w == (b < 108 ? 11 : ~0u)) {
    float c[4][4] = {};
    u32 aa = SM_UP + ((lane & 7) + 8 * (lane >> 4)) * 64 + ((((lane >> 3) & 1) ^ ((lane & 7) >> 1)) << 4);
    u32 ba = SM_SIL + (lane >> 3) * 16;
    uint4 a[2][10];
#define GLD(n) { _Pragma("unroll") for (int i = 0; i < 2; i++) { a[n][5 * i] = ldsm4(ba + i * 64); \
      _Pragma("unroll") for (int k = 0; k < 4; k++) a[n][5 * i + 1 + k] = ldsm4t((k & 2 ? aa ^ 32 : aa) + i * 2048 + (k & 1) * 1024); } aa += 4096; ba += 128; }
#define GMM(n) { _Pragma("unroll") for (int i = 0; i < 2; i++) _Pragma("unroll") for (int k = 0; k < 4; k++) { const uint4 f = a[n][5 * i + 1 + k], bb = a[n][5 * i]; \
      mma_bf(c[k], f.x, f.y, f.z, f.w, k & 1 ? bb.z : bb.x, k & 1 ? bb.w : bb.y); } }
    mb_wait(SM_MB);
    TS(56);
    GLD(0);
#pragma unroll 1
    for (int s = 0; s < 4; s++) { GLD(1); GMM(0); GLD(0); GMM(1); }
    GMM(0);
    const float v0 = (q & 1) ? c[0][2] + c[1][2] : c[0][0] + c[1][0], v1 = (q & 1) ? c[2][2] + c[3][2] : c[2][0] + c[3][0];
    str16(gs + (G_MOD + b * 128 + 2 * g + 16 * q), pk_bf(rbf((q & 2) ? v1 : v0) * F2M64, 0.f) | (g < 2 ? pm : 0));
    TS(57);
  }
  TS(6);
  u32 tid2 = tid;
  if (w < 4) {
    asm volatile("setmaxnreg.inc.sync.aligned.u32 232;");
    const u32 tid = tid2 + p.zero, w = tid >> 5, lane = tid & 31, g = lane >> 2, q = lane & 3, hi = g & 1, zr = tid >> 16, tp = SM_TAP + w * TAPS;
    const u32 pml = opq((g & 3) ? 0 : pm);
    const u32 tr = tp + ((hi ? TO : TE) + (g >> 1) - q) * 4;
    u32 T[33][4], B5[5][2], B3[5][2];
#pragma unroll
    for (int d = 0; d < 33; d++) {
      T[d][0] = lds32(tr + 32 * d); T[d][1] = lds32(tr + 32 * d + 16);
      T[d][2] = cpy(d ? T[d - 1][1] : zr, zr, 0); T[d][3] = cpy(T[d][0], zr, 1);
    }
    const u32 t33 = cpy(T[32][1], zr, 0), z33 = cpy(zr, zr, 1);
    if (TPIN) {
#pragma unroll
      for (int d = 0; d < 33; d++) asm volatile("{.reg .pred p; setp.ne.u32 p,%2,0; @p st.shared.v2.u32 [%2],{%0,%1};}" ::"r"(T[d][2]), "r"(T[d][3]), "r"(zr) : "memory");
    }
    const u32 bt = tp + (T5 + g - q) * 4;
#pragma unroll
    for (int d = 0; d < 5; d++) {
      B5[d][0] = lds32(bt + 32 * d); B5[d][1] = lds32(bt + 32 * d - 16);
      B3[d][0] = lds32(bt + 32 * d + (T3 - T5) * 4); B3[d][1] = lds32(bt + 32 * d - 16 + (T3 - T5) * 4);
    }
    u32 za = opq(SM_ZS + 16 + w * ZSS + ((lane >> 3) & 1) * ZPS + ((lane & 7) + (lane >> 4)) * 16);
    u32 wa = opq(SM_W + W5O + w * WSL + row16(lane));
    u32 sa = opq(SM_W + W9O - (SPL ? 0 : 2048) + w * WSL + lane * 16);
    const u32 yo = opq(p.glo + G_Y - 1024 + b * BLK + 256 * q + w * 32 + 4 * g);
    char* yp = gptr(p, yo);
#define YINC() asm volatile("{.reg .u32 l, h; mov.b64 {l,h},%0; add.u32 l,l,1024; mov.b64 %0,{l,h};}" : "+l"(yp))
    const u32 fa = opq(SM_SC + 16 * w + 8), bw = opq((BW >> 4 * w) & 15), bs = opq((BS >> 4 * w) & 15);
    if (TPIN) asm volatile("{.reg .pred p; setp.ne.u32 p,%8,0; @p st.shared.v4.u32 [%8],{%0,%1,%2,%3}; @p st.shared.v4.u32 [%8],{%4,%5,%6,%7};}"
                           ::"r"(za), "r"(wa), "r"(sa), "r"(yo), "r"(fa), "r"(bw), "r"(bs), "r"(pml), "r"(zr) : "memory");
    TS(8);
    u32 F;
    bsync(9, 384);
    TS(11);
    float A[4][4] = {};
    uint4 Z[4];
    Z[0] = ldsm4(za); Z[1] = ldsm4(za + 32);
#define STEP(s, b0, b1) { _Pragma("unroll") for (int i = 0; i < 4; i++) mma_hf_t(A[i], T[8 * i + 7 - (s)], b0, b1); }
#define PAIR(n) { Z[(n + 2) & 3] = ldsm4(za + 32 * (n + 2)); STEP(2 * n, Z[n].x, Z[n].y); STEP(2 * n + 1, Z[n].z, Z[n].w); }
#define LAST(N) mma8_hf(N, t33, z33, Z[3].y); float O[4]; mma_hf_o(O, A[0], T[0], Z[3].z, Z[3].w); \
    _Pragma("unroll") for (int i = 0; i < 3; i++) mma_hf_o(A[i], A[i + 1], T[8 * i + 8], Z[3].z, Z[3].w); \
    mma_hf_o(A[3], N, T[32], Z[3].z, Z[3].w);
#pragma unroll 1
    for (int j = 0; j < 4; j++) {
      PAIR(0);
      uint2 fc;
      asm volatile("ld.volatile.shared.v2.u32 {%0,%1},[%2];" : "=r"(fc.x), "=r"(fc.y) : "r"(fa));
      PAIR(1);
      F = __byte_perm(fu(uf(fc.x) * uf(fc.y)), 0, 0x3232);
      PAIR(2);
      Z[1] = ldsm4(za + 160); STEP(6, Z[3].x, Z[3].y);
      float N[4] = {};
      LAST(N);
      if (INCV) inc<128>(za);
      YINC();
      y_store<128>(O[0], O[1], O[2], O[3], F, pml, yp);
      if (!INCV) za += 128;
      TSJ(j);
    }
    bsyncr(bw);
    uint4 a5;
    if (A5P) a5 = ldsm4t(wa);
#pragma unroll
    for (int half = 0; half < (SPL ? 2 : 1); half++) {
    if (half) bsyncr(bs);
#pragma unroll 1
    for (int j = half ? 8 : 4; j < (SPL && !half ? 8 : 13); j++) {
      if (!SPL && j == 8) bsyncr(bs);
      if (!A5P) a5 = ldsm4t(wa);
      const uint4 a3 = ldsm4t(wa + (W3O - W5O));
      uint4 s3 = {0, 0, 0, 0};
      if (SPL ? half : j >= 8) s3 = lds128(sa);
      PAIR(0);
      float N[4] = {};
#pragma unroll
      for (int i = 0; i < 4; i++) mma_hf(A[i], a5.x, a5.y, a5.z, a5.w, B5[i][0], B5[i][1]);
      mma_hf(N, a5.x, a5.y, a5.z, a5.w, B5[4][0], B5[4][1]);
      if (INCV) asm volatile("{add.u32 %0,%0,256; xor.b32 %0,%0,32;}" : "+r"(wa)); else wa = (wa + 256) ^ 32;
      if (A5P) a5 = ldsm4t(wa);
      PAIR(1);
#pragma unroll
      for (int i = 0; i < 4; i++) mma_hf(A[i], a3.x, a3.y, a3.z, a3.w, B3[i][0], B3[i][1]);
      mma_hf(N, a3.x, a3.y, a3.z, a3.w, B3[4][0], B3[4][1]);
      PAIR(2);
      Z[1] = ldsm4(za + 160); STEP(6, Z[3].x, Z[3].y);
      LAST(N);
      if (INCV) { inc<128>(za); if (!SPL || half) inc<512>(sa); }
      YINC();
      if (SPL && !half) y_store<128>(O[0], O[1], O[2], O[3], F, pml, yp);
      else y_store<128>(O[0] + uf(s3.x), O[1] + uf(s3.y), O[2] + uf(s3.z), O[3] + uf(s3.w), F, pml, yp);
      if (!INCV) { za += 128; if (!SPL || half) sa += 512; }
      TSJ(j);
    }
    }
    {
      asm volatile("mov.u32 %0,%%tid.x;" : "=r"(tid2));
      const uint4 s3 = lds128(sa), s4 = lds128(sa + 512), s5 = lds128(sa + 1024);
      float X[3][4] = {{uf(s4.x), uf(s4.y), uf(s4.z), uf(s4.w)}, {}, {uf(s5.x), uf(s5.y), uf(s5.z), uf(s5.w)}};
#pragma unroll
      for (int ty = 0; ty < 2; ty++) {
        const uint4 a = A5P && !ty ? a5 : ldsm4t(wa + ty * (W3O - W5O)), c = ldsm4t((wa ^ 32) + 256 + ty * (W3O - W5O)), d = ldsm4t(wa + 512 + ty * (W3O - W5O));
#pragma unroll
        for (int i = 0; i < 3; i++) mma_hf(A[i], a.x, a.y, a.z, a.w, ty ? B3[i][0] : B5[i][0], ty ? B3[i][1] : B5[i][1]);
#pragma unroll
        for (int i = 0; i < 2; i++) mma_hf(X[i], c.x, c.y, c.z, c.w, ty ? B3[i][0] : B5[i][0], ty ? B3[i][1] : B5[i][1]);
        mma_hf(X[2], d.x, d.y, d.z, d.w, ty ? B3[0][0] : B5[0][0], ty ? B3[0][1] : B5[0][1]);
      }
#pragma unroll
      for (int n = 0; n < 4; n++) {
        const uint4 f0 = n < 2 ? Z[n] : ldsm4(za + 32 * n), f1 = ldsm4(za + 32 * n + 128), f2 = ldsm4(za + 32 * n + 256);
#pragma unroll
        for (int s = 2 * n; s < 2 * n + 2; s++) {
#pragma unroll
          for (int i = 0; i < 3; i++) mma_hf_t(A[i], T[8 * i + 7 - s], s & 1 ? f0.z : f0.x, s & 1 ? f0.w : f0.y);
          mma_hf_t(X[0], T[7 - s], s & 1 ? f1.z : f1.x, s & 1 ? f1.w : f1.y); mma_hf_t(X[1], T[15 - s], s & 1 ? f1.z : f1.x, s & 1 ? f1.w : f1.y);
          mma_hf_t(X[2], T[7 - s], s & 1 ? f2.z : f2.x, s & 1 ? f2.w : f2.y);
        }
      }
      y_store<128>(A[0][0] + uf(s3.x), A[0][1] + uf(s3.y), A[0][2] + uf(s3.z), A[0][3] + uf(s3.w), F, pml, yp + 1024);
      y_store<128>(A[1][0] + X[0][0], A[1][1] + X[0][1], A[1][2] + X[0][2], A[1][3] + X[0][3], F, pml, yp + 2048);
      y_store<128>(A[2][0] + X[1][0] + X[2][0], A[2][1] + X[1][1] + X[2][1], A[2][2] + X[1][2] + X[2][2], A[2][3] + X[1][3] + X[2][3], F, pml, yp + 3072);
    }
    barrive(12, N12);
    TS(15);
  } else {
    asm volatile("setmaxnreg.dec.sync.aligned.u32 136;");
    const u32 t8 = tid - 128, pml = (g & 3) ? 0 : pm;
    {
      TS(12);
      if (PFG == 1 && tid == 288) l2_pre<WSH / 2>(p.wg + (b * WSH + WSH / 2));
      const char* zs = gs + ((16 * w - 64 + (lane >> 3)) * BLK + b * 128 + ((lane & 7) * 16 ^ rho * 64));
      const char* zs4 = gs + ((t8 >> 1) * BLK + (Ps >> 4) * 512 + (Ps & 6) * 64 + ((Ps >> 2 ^ Ps) & 2) * 32 + (Ps & 1) * 32 + (t8 & 1) * 16);
      uint4 v[5];
      v[4].x = INVAL;
      if (ZD) wait_clk(t0, ZD);
      const u32 d = lane < 4 ? chan(b, lane) : Ps;
      const char* mp = gs + (G_MOD + (d >> 5) * 128 + (d & 24) * 2);
      uint4 ta, tc;
      ta.x = tc.x = INVAL;
      const u32 t9 = w == 9 ? pm : INVAL;
      pin2(zr, zs, zs4);
      conv();
      POLLM({ rld128<TAGM>(ta, mp, t9); rld128<TAGM>(tc, mp + MODJ, t9); rld128<TAGM>(v[4], zs4, pm); }, lop3<0xbe>(v[4].x, pm, ne3(ta.x, tc.x, t9)), TAGM, 1);
      TS(58);
#pragma unroll
      for (int j = 0; j < 4; j++) v[j] = ldr128(zs + j * 4 * BLK);
      if (w == 9) {
        const u32 aw = (d & 4) ? ((d & 2) ? ta.w : ta.z) : ((d & 2) ? ta.y : ta.x & ~TAGM);
        const u32 cw = (d & 4) ? ((d & 2) ? tc.w : tc.z) : ((d & 2) ? tc.y : tc.x & ~TAGM);
        const float sa = ((d & 1) ? bhi(aw) : blo(aw)) * F2P64, c1 = rbf(fmaf((d & 1) ? bhi(cw) : blo(cw), F2P64, 1.f));
        const u32 EM = min(max(fu(fmaxf(32.f * fabsf(c1), fabsf(sa))) >> 23, 80u), 250u);
        const float inv = uf((264 - EM) << 23);
        if (lane < 5) { sts64(SM_SC + 16 * lane, pk_hf(16.f * c1 * inv, 16.f * c1 * inv), pk_hf(sa * inv, sa * inv)); sts32(SM_SC + 16 * lane + 8, (EM - 74) << 23); }
        TS(10);
      }
#define MARKERS() if (tid == 256) { \
        _Pragma("unroll") for (int i = MT / 2; i < 8; i++) bulk_out<2048>(gs + (G_Y + 2048 * i + b * BLK), SM_INV); \
        bulk_out<2048>(gs + (G_PART + b * 2048), SM_INV); bulk_out<512>(gs + (G_ACT + b * 512), SM_INV); \
        bulk_out<32>(gs + (G_KEY + b * KST), SM_INV); if (!rho) bulk_out<128>(gs + (G_ACT + Ps * 128), SM_INV); \
        asm volatile("cp.async.bulk.commit_group;" ::: "memory"); }
#define GATE() { mb_expect(SM_MB + 8, rho ? SLV : 46080); \
        _Pragma("unroll") for (int i = GE; i < 3; i++) tma3d(SM_GATE + 12288 * i, &tm_gate, SM_MB + 8, 32 * b, i); \
        if (!rho) tma3d(SM_GATE + SLV, &tm_gs, SM_MB + 8, 4096 + 4 * b, 0); }
#define UP() { mb_expect(SM_MB + 16, rho ? SLV : 46080); tma3d(SM_UP, &tm_up, SM_MB + 16, 32 * b, 0); \
        if (!rho) tma3d(SM_UP + SLV, &tm_us, SM_MB + 16, 4096 + 4 * b, 0); }
      if (PFU == 2 && tid == 256) l2_pre<WSH>(p.wu + b * WSH);
      if (GE && tid == 256) {
        asm volatile("cp.async.bulk.wait_group.read 0;" ::: "memory");
#pragma unroll
        for (int i = 0; i < GE; i++) tma3d(SM_GATE + 12288 * i, &tm_gate, SM_MB + 8, 32 * b, i);
      }
      if (PFG == 2 && tid == 256) l2_pre<WSH>(p.wg + b * WSH);
      if (PFG == 3 && tid == 256) l2_pre<WSH / 2>(p.wg + (b * WSH + WSH / 2));
      bsync(8, 256);
      const uint2 cc = lds64(SM_SC + 8 * (t8 & 6)), c4 = lds64(SM_SC + 64);
      sts128(SM_Z4 + 256 + (t8 & 1) * ZP4 + (t8 >> 1) * 16, hfma(v[4].x & ~TAGM, c4.x, c4.y), hfma(v[4].y, c4.x, c4.y), hfma(v[4].z, c4.x, c4.y), hfma(v[4].w, c4.x, c4.y));
      if (t8 < 96) sts128(t8 < 64 ? SM_ZS + (t8 & 7) * ZPS + (t8 >> 3) * 16 : SM_Z4 + (t8 & 1) * ZP4 + (t8 & 30) * 8, 0, 0, 0, 0);
      asm volatile("cp.async.bulk.wait_group.read 0;" ::: "memory");
      const u32 dst = SM_ZS + 128 + (t8 & 7) * ZPS + (16 * w - 64 + (lane >> 3)) * 16;
      pin(zr, dst);
      conv();
      POLLS(_Pragma("unroll") for (int j = 0; j < 4; j++) sts128(dst + j * 64, hfma(v[j].x & ~TAGM, cc.x, cc.y), hfma(v[j].y, cc.x, cc.y), hfma(v[j].z, cc.x, cc.y), hfma(v[j].w, cc.x, cc.y)),
            _Pragma("unroll") for (int j = 0; j < 4; j++) rld128<TAGM>(v[j], zs + j * 4 * BLK, pm), ne3(v[0].x, v[1].x, pm) | ne3(v[2].x, v[3].x, pm), TAGM, 1);
      TS(9);
      bsync(9, 384);
      TS(11);
      if (MKT == 1) MARKERS();
      if (w == 10 && s2u(smem) != SM0) __trap();
      const bool lng = w < 8 || w == 9;
      const u32 ts = lane + 32 * (w == 8 ? 0 : w - 9), c = min(ts, 71u), ma = SM_MODS + 16 * c;
      const u32 sig = lng ? ksig : ts >> 4, l2 = lng ? lane : 32 + (ts & 15);
      const char* mq = gs + (G_MOD + (c >> 2) * 128 + (c & 3) * 16);
      if (!lng) {
#pragma unroll
        for (int j = 0; j < 6; j++) cpa16(ma + 1152 * j, mq + j * MODJ);
        cpa16(ma + 1152 * 6, p.dsk + 16 * c); cpa16(ma + 1152 * 7, p.wr + 16 * c);
        if (PFU == 3) {
#pragma unroll
          for (int j = 0; j < 4; j++) if (ts < 81) l2_line(p.wu + (b * WSH + (81 * j + ts) * 128));
        }
        if (tid == 352) {
          PROXY_FENCE();
          if (PFU == 1) l2_pre<WSH>(p.wu + b * WSH);
          if (!TG) GATE();
          if (!TU) UP();
        }
      }
      const u32 wb = SM_W + sig * WSL;
      if (sig < 5) {
        const u32 za = (sig < 4 ? SM_ZS + 128 + sig * ZSS : SM_Z4 + 256) + l2 * 32, zb = za + (sig < 4 ? ZPS : ZP4);
        const uint4 c0 = lds128(zb - 32), c1 = lds128(za - 16), c2 = lds128(zb - 16), c3 = lds128(za), c4 = lds128(zb), c5 = lds128(za + 16), c6 = lds128(zb + 16);
        const u32 P[25] = {c0.z, c0.w, c1.x, c1.y, c1.z, c1.w, c2.x, c2.y, c2.z, c2.w, c3.x, c3.y, c3.z, c3.w, c4.x, c4.y, c4.z, c4.w, c5.x, c5.y, c5.z, c5.w, c6.x, c6.y, c6.z};
        u32 Q[25], D1[24], F4[23], W5[21], W3[17];
#pragma unroll
        for (int j = 1; j < 25; j++) Q[j] = __byte_perm(P[j - 1], P[j], 0x5432);
#pragma unroll
        for (int j = 1; j < 24; j++) D1[j] = hadd(P[j], Q[j]);
#pragma unroll
        for (int j = 2; j < 23; j++) F4[j] = hadd(D1[j], D1[j - 1]);
#pragma unroll
        for (int n = 0; n < 21; n++) W5[n] = hadd(F4[n + 2], P[n]);
#pragma unroll
        for (int n = 0; n < 17; n++) W3[n] = hadd(Q[n + 8], D1[n + 7]);
        const u32 a0 = wb + W5O + 64 * l2 + 16 * ((l2 >> 1) & 3);
#pragma unroll
        for (int i = 0; i < 4; i++) {
          sts128(a0 ^ (16 * i), W5[4 * i + 5], W5[4 * i + 6], W5[4 * i + 7], W5[4 * i + 8]);
          sts128((a0 ^ (16 * i)) + (W3O - W5O), W3[4 * i + 1], W3[4 * i + 2], W3[4 * i + 3], W3[4 * i + 4]);
        }
        if (lng) {
          if (lane < 16) sts128(wb + (lane & 7) * 16 + (lane & 8) * 400, 0, 0, 0, 0);
          const u32 a1 = wb + 32 * lane + 16 * ((lane >> 2) & 1);
#pragma unroll
          for (int i = 0; i < 4; i++) {
            const u32 a = (a1 ^ (16 * (i >> 1))) + 1024 * (i & 1), n = 4 * i;
            sts128(a + V2O, hadd(Q[n + 9], P[n + 8]), hadd(Q[n + 10], P[n + 9]), hadd(Q[n + 11], P[n + 10]), hadd(Q[n + 12], P[n + 11]));
            sts128(a + W9O, hadd(F4[n + 4], W5[n]), hadd(F4[n + 5], W5[n + 1]), hadd(F4[n + 6], W5[n + 2]), hadd(F4[n + 7], W5[n + 3]));
            sts128(a + W7O, hadd(F4[n + 6], W3[n]), hadd(F4[n + 7], W3[n + 1]), hadd(F4[n + 8], W3[n + 2]), hadd(F4[n + 9], W3[n + 3]));
          }
        }
      }
      if (w < 8) barriver((BW >> (4 * w - 16)) & 15);
      else if (!(w & 1)) { barriver((BW >> (4 * w - 32)) & 15); barriver((BW >> (4 * w - 28)) & 15); }
      __syncwarp();
      TS(32);
      if (lng) {
        const u32 wa = wb + ((lane >> 3) & 1) * 1024 + (((lane & 7) ^ (lane >> 4)) + 8 * (lane >> 4)) * 16;
        const u32 kv = lds32(SM_KV + 4 * sig), bi = (g >> 1) == q ? (hi ? kv << 16 : kv) : 0u;
        float acc[8][4] = {};
#pragma unroll
        for (int j = 0; j < 4; j++) { const uint4 a = ldsm4t(wa + V2O + j * 256); mma8_hf(acc[2 * j], a.x, a.y, bi); mma8_hf(acc[2 * j + 1], a.z, a.w, bi); }
        u32 bt = tp + (T9E + hi * TEO + (g >> 1) - q) * 4, wt = wa + W9O;
#pragma unroll 1
        for (int ty = 0; ty < 2; ty++) {
          uint4 a[4];
#pragma unroll
          for (int be = 0; be < 4; be++) a[be] = ldsm4t(wt + be * 256);
          u32 b1 = lds32(bt - 16);
#pragma unroll
          for (int d = 0; d < 8; d++) {
            const u32 b0 = lds32(bt + 16 * d);
#pragma unroll
            for (int be = 0; be < 4; be++) if (d + 2 * be < 8) mma_hf(acc[d + 2 * be], a[be].x, a[be].y, a[be].z, a[be].w, b0, b1);
            b1 = b0;
          }
          bt += (T7E - T9E) * 4; wt += W7O - W9O;
        }
        __syncwarp();
#pragma unroll
        for (int j = 0; j < 8; j++) sts128(wb + W9O + j * 512 + lane * 16, fu(acc[j][0]), fu(acc[j][1]), fu(acc[j][2]), fu(acc[j][3]));
        if (w != 9) barriver((BS >> (4 * w - 16)) & 15);
        TS(34);
      }
      if (!lng) {
        asm volatile("cp.async.wait_all;" ::: "memory");
        uint4 md[6];
#pragma unroll
        for (int j = 0; j < 6; j++) md[j] = lds128(ma + 1152 * j);
        const uint4 dk = lds128(ma + 1152 * 6), wr = lds128(ma + 1152 * 7);
        POLLW(_Pragma("unroll") for (int j = 0; j < 6; j++) md[j] = ldr128(mq + j * MODJ),
              ((md[0].x ^ pm) | (md[1].x ^ pm) | (md[2].x ^ pm) | (md[3].x ^ pm) | (md[4].x ^ pm) | (md[5].x ^ pm)) & TAGM, 4);
#pragma unroll
        for (int j = 0; j < 6; j++) {
          const u32 o = (j % 3 == 1) ? BONE : 0x80008000u;
          md[j] = make_uint4(bfma(md[j].x & ~TAGM, B2P64, o), bfma(md[j].y, B2P64, o), bfma(md[j].z, B2P64, o), bfma(md[j].w, B2P64, o));
          if (j > 2) sts128(ma + 1152 * j, md[j].x, md[j].y, md[j].z, md[j].w);
        }
        const uint4 gd = make_uint4(bmul(md[2].x, dk.x), bmul(md[2].y, dk.y), bmul(md[2].z, dk.z), bmul(md[2].w, dk.w));
#pragma unroll
        for (int j = 0; j < 2; j++) sts128(ma + 1152 * j, bmul(md[j].x, gd.x), bmul(md[j].y, gd.y), bmul(md[j].z, gd.z), bmul(md[j].w, gd.w));
        sts128(ma + 2304, bmul(md[2].x, B2P64), bmul(md[2].y, B2P64), bmul(md[2].z, B2P64), bmul(md[2].w, B2P64));
        const uint4 H = make_uint4(bmul(md[4].x, wr.x), bmul(md[4].y, wr.y), bmul(md[4].z, wr.z), bmul(md[4].w, wr.w));
        sts128(ma + 1152 * 7, H.x, H.y, H.z, H.w);
        sts128(ma + 1152 * 8, bfma(md[4].x, wr.x, H.x ^ 0x80008000u), bfma(md[4].y, wr.y, H.y ^ 0x80008000u), bfma(md[4].z, wr.z, H.z ^ 0x80008000u), bfma(md[4].w, wr.w, H.w ^ 0x80008000u));
        float c4[4] = {};
        mma_bf(c4, md[4].x, md[3].x, md[4].y, md[3].y, wr.x, wr.y); mma_bf(c4, md[4].z, md[3].z, md[4].w, md[3].w, wr.z, wr.w);
        if (q == g >> 1) sts64(SM_RC + (ts >> 2) * 8, fu(hi ? c4[1] : c4[0]), fu(hi ? c4[3] : c4[2]));
        if (ts < 2) sts128(SM_ONE + 16 * ts, ts ? 0 : BONE, ts ? 0 : BONE, ts ? 0 : BONE, ts ? 0 : BONE);
        TS(14);
        if (MKT == 2) MARKERS();
        if (w == 8) asm volatile("cp.async.bulk.wait_group 0;" ::: "memory");
        if (PFW == 2) {
#pragma unroll
          for (int j = 0; j < 4; j++) if (ts < 81) l2_line(p.wd + (b * WSH + (81 * j + ts) * 128));
        }
        bsync(13, 96);
        if (w == 8) { barriver(2); barriver(3); barriver(5); barriver(6); if (HLP) barrive(7, 64); }
      }
      if (!HLP) { if (w >= 8) barrive(11, 256); }
      else if (w == 9) barrive(11, 128);
    }
    const u32 jw = w < 6 ? w ^ 1 : w < 8 ? w : max(w - 4, 5u);
    const int u0 = 4 * (jw - 4) + 2 * rho;
    const u32 t4 = SM_TAP + 4 * TAPS, s3a = SM_W + 4 * WSL + (u0 >= 8 ? W9O + (u0 - 8) * 512 : V2O) + lane * 16, hb = (0x4987 >> (4 * jw - 16)) & 15;
#define FARL() { u32 wa = (SM_W + 4 * WSL + W5O + row16(lane) + (u0 - 3) * 256) ^ 32, bt = t4 + (T5 + g - q) * 4; \
      _Pragma("unroll 1") for (int al = min(u0 - 2, 6); al > 0; al--) { \
        _Pragma("unroll") for (int ty = 0; ty < 2; ty++) { \
          const uint4 a = ldsm4t(wa + ty * (W3O - W5O)); \
          const u32 bb = bt + ty * (T3 - T5) * 4; \
          mma_hf(acc[ty], a.x, a.y, a.z, a.w, lds32(bb - 32), lds32(bb - 48)); \
          mma_hf(acc[2 + ty], a.x, a.y, a.z, a.w, lds32(bb), lds32(bb - 16)); \
        } \
        wa = (wa - 256) ^ 32; bt += 32; } }
    if (w < 8) {
      u32 tr = t4 + ((hi ? TO : TE) + (g >> 1) - q) * 4;
      u32 zb = SM_Z4 + 256 + ((lane >> 3) & 1) * ZP4 + u0 * 128 + (lane & 7) * 16 + (lane >> 4) * 128;
      float acc[4][4] = {};
      u32 prev = 0;
#pragma unroll 1
      for (int it = min(u0 + 2, 4); it; it--) {
#pragma unroll
        for (int s = 0; s < 8; s++) {
          const uint4 z = ldsm4(zb - 16 * s);
          const u32 t0 = lds32(tr + 32 * s), t1 = lds32(tr + 32 * s + 16);
          mma_hf(acc[s & 1], t0, t1, prev, t0, z.x, z.y);
          mma_hf(acc[2 + (s & 1)], t0, t1, prev, t0, z.z, z.w);
          prev = t1;
        }
        zb -= 128; tr += 256;
      }
      {
        const uint4 z = ldsm4(zb); const u32 t0 = lds32(tr), t1 = lds32(tr + 16);
        mma_hf(acc[0], t0, t1, prev, t0, z.x, z.y); mma_hf(acc[2], t0, t1, prev, t0, z.z, z.w);
        if (jw > 4) { const uint4 y = ldsm4(zb - 16); mma8_hf(acc[1], t1, zr, y.y); mma8_hf(acc[3], t1, zr, y.w); }
      }
      if (!HLP) { bsync(11, 256); FARL(); }
      else asm volatile("bar.sync %0,64;" ::"r"(hb) : "memory");
      TS(35);
      const uint2 fc = lds64(SM_SC + 16 * 4 + 8);
      const u32 F = __byte_perm(fu(uf(fc.x) * uf(fc.y)), 0, 0x3232);
      char* yp = gs + (G_Y + 16384 + (32 * jw - 128 + 16 * rho + 4 * (q >> 1) + ((b >> 2) & 3)) * BLK + (q & 1) * 1024 + (b & 112) * 4 + (b & 2) * 16 + 4 * g);
#pragma unroll
      for (int j = 0; j < 2; j++) {
        uint4 s3 = {0, 0, 0, 0};
        if (u0 >= (HLP ? 4 : 8)) s3 = lds128(s3a + j * 512);
        y_store<512>(acc[2 * j][0] + acc[2 * j + 1][0] + uf(s3.x), acc[2 * j][1] + acc[2 * j + 1][1] + uf(s3.y), acc[2 * j][2] + acc[2 * j + 1][2] + uf(s3.z),
                acc[2 * j][3] + acc[2 * j + 1][3] + uf(s3.w), F, pml, yp + j * 8 * BLK);
      }
      TS(16);
    } else {
      if (HLP && w != 9) {
        bsync(11, 128);
        if (HD) wait_clk(clk(), HD);
        float acc[4][4] = {};
        if (u0 >= 8) {
#pragma unroll
          for (int j = 0; j < 2; j++) { const uint4 t = lds128(s3a + j * 512); acc[2 * j][0] = uf(t.x); acc[2 * j][1] = uf(t.y); acc[2 * j][2] = uf(t.z); acc[2 * j][3] = uf(t.w); }
        }
        FARL();
#pragma unroll
        for (int j = 0; j < 2; j++)
          sts128(s3a + j * 512, fu(acc[2 * j][0] + acc[2 * j + 1][0]), fu(acc[2 * j][1] + acc[2 * j + 1][1]), fu(acc[2 * j][2] + acc[2 * j + 1][2]), fu(acc[2 * j][3] + acc[2 * j + 1][3]));
        asm volatile("bar.arrive %0,64;" ::"r"(hb) : "memory");
        TS(16);
      }
      if (PFW == 3 && w == 9) {
#pragma unroll 1
        for (int j = 0; j < 12; j++) { if (lane < 27) l2_line(p.wd + (b * WSH + (27 * j + lane) * 128)); wait_clk(clk(), PFP); }
      }
      if (TG | TU | TW) {
        if (tid == 352) {
          if (TG) { wait_clk(t0, TG); GATE(); }
          if (TW < TU) { wait_clk(t0, TW); l2_pre<WSH>(p.wd + b * WSH); }
          if (TU) { wait_clk(t0, TU); UP(); }
          if (TW >= TU) { wait_clk(t0, TW); l2_pre<WSH>(p.wd + b * WSH); }
        }
      } else if (PFW < 2 && tid == 352) { mb_wait(SM_MB + 8); if (PFW) mb_wait(SM_MB + 16); l2_pre<WSH>(p.wd + b * WSH); }
      if (D0C && tid == 352 && b < 108) {
        mb_wait(SM_MB + 16);
        PROXY_FENCE();
        mb_expect(SM_MB + 24, 49152);
        tma3d(SM_TAP, &tm_down, SM_MB + 24, 64 * (b % 9), 4 * (b / 9));
      }
      TS(17);
    }
  }
  post_conv(p, &tm_down, tid2 + p.zero, b, b3);
  TSD();
}

typedef CUresult (*EncFn)(CUtensorMap*, CUtensorMapDataType, cuuint32_t, void*, const cuuint64_t*, const cuuint64_t*, const cuuint32_t*, const cuuint32_t*,
                          CUtensorMapInterleave, CUtensorMapSwizzle, CUtensorMapL2promotion, CUtensorMapFloatOOBfill);
static void make_map(EncFn enc, CUtensorMap* tm, void* ptr, int cols, int rows, int bw, int nb, CUtensorMapSwizzle sw, int gr = 192, int prom = 0) {
  cuuint64_t gd[3] = {(cuuint64_t)cols, (cuuint64_t)gr, (cuuint64_t)(rows / gr)}, gs[2] = {(cuuint64_t)cols * 2, (cuuint64_t)cols * 2 * gr};
  cuuint32_t bd[3] = {(cuuint32_t)bw, (cuuint32_t)gr, (cuuint32_t)nb}, es[3] = {1, 1, 1};
  enc(tm, CU_TENSOR_MAP_DATA_TYPE_BFLOAT16, 3, ptr, gd, gs, bd, es, CU_TENSOR_MAP_INTERLEAVE_NONE, sw, (CUtensorMapL2promotion)prom, CU_TENSOR_MAP_FLOAT_OOB_FILL_NONE);
}
extern "C" void kernel_launch(void* const* d_in, const int* in_sizes, int n_in, void* d_out, int out_size) {
  static EncFn enc = nullptr;
  static void* scratch = nullptr;
  if (!enc) {
    cudaGetSymbolAddress(&scratch, g_s);
    const uintptr_t last = (uintptr_t)scratch + G_END;
    if ((u32)last < G_END) scratch = (void*)(last - (u32)last);
    cudaDriverEntryPointQueryResult qr;
    cudaGetDriverEntryPoint("cuTensorMapEncodeTiled", (void**)&enc, cudaEnableDefault, &qr);
    cudaFuncSetAttribute(fused_kernel, cudaFuncAttributeMaxDynamicSharedMemorySize, SM_TOTAL);
  }
  CUtensorMap tm_mod, tm_gate, tm_gs, tm_up, tm_us, tm_down;
  make_map(enc, &tm_mod, d_in[13], 3456, 576, 32, 3, CU_TENSOR_MAP_SWIZZLE_64B, 192, PRM);
  make_map(enc, &tm_gate, d_in[9], 4608, 576, 32, 1, CU_TENSOR_MAP_SWIZZLE_64B, 192, PRG);
  make_map(enc, &tm_gs, d_in[9], 4608, 576, 8, 3, CU_TENSOR_MAP_SWIZZLE_NONE);
  make_map(enc, &tm_up, d_in[10], 4608, 576, 32, 3, CU_TENSOR_MAP_SWIZZLE_64B, 192, PRU);
  make_map(enc, &tm_us, d_in[10], 4608, 576, 8, 3, CU_TENSOR_MAP_SWIZZLE_NONE, 192, PRS);
  make_map(enc, &tm_down, d_in[11], 576, 4608, 64, 1, CU_TENSOR_MAP_SWIZZLE_128B, 96);
  Prm p;
  p.x = (const char*)d_in[0]; p.la = (const char*)d_in[1]; p.ai = (const char*)d_in[2]; p.cr = (const char*)d_in[3];
  p.ci = (const char*)d_in[4]; p.ldt = (const char*)d_in[5]; p.dsk = (const char*)d_in[6]; p.wr = (const char*)d_in[8];
  p.wg = (const char*)d_in[9]; p.wu = (const char*)d_in[10]; p.wd = (const char*)d_in[11];
  p.c = (const char*)d_in[12]; p.out = (char*)d_out; p.zero = 0; p.gs = (char*)scratch; p.glo = (u32)(uintptr_t)scratch; p.ghi = (u32)((uintptr_t)scratch >> 32);
  fused_kernel<<<128, 384, SM_TOTAL>>>(p, tm_mod, tm_gate, tm_gs, tm_up, tm_us, tm_down);
}
```

```cpp
#include <cuda_runtime.h>
#include <cuda.h>
#include <cuda_bf16.h>
#include <cuda_fp16.h>
#include <stdint.h>
#define FUSED 1
#define DEV __device__ __forceinline__
typedef uint32_t u32;

constexpr u32 BLK = 18432, G_Z = 0, G_Y = 128 * BLK, G_MOD = 2 * G_Y, G_KEY = G_MOD + 128 * 128, G_ACT = G_KEY + 128 * 128;
constexpr u32 G_PART = G_ACT + 576 * 128, G_EP = G_PART + 128 * 2048, G_END = G_EP + 128;
__device__ __align__(128) unsigned char g_s[2 * G_END];
#define TS(i)
#define TSJ(j)
#define TS0()
#define TSE()
#define TSD()
#define TSX 0
#define TSRND()
#define TSN(code, n)
#define ERRF(code)

constexpr int SM0 = 1024;
constexpr int ROW = 1168, SLV = 36864;
constexpr int SM_GATE = SM0, SM_UP = SM_GATE + 46080, SM_XST = SM_UP + 46080, SM_MODS = SM_XST + 16 * ROW, SM_W = SM_MODS + 11008;
constexpr int KTAB = 9216, WSL = 12544, W5O = 128, W3O = 3328, V2O = 6400, W9O = 8448, W7O = 10496;
constexpr int ZPS = 2192, ZSS = 2 * ZPS, ZP4 = 2368;
constexpr int SM_ZS = SM_W + 5 * WSL, SM_Z4 = SM_ZS + 4 * ZSS, SM_TAP = SM_Z4 + 2 * ZP4, TAPS = 3328;
constexpr int SM_MB = SM_TAP + 5 * TAPS;
constexpr int SM_SC = SM_MB + 48;
constexpr int SM_KV = SM_SC + 80;
constexpr int SM_THR = SM_KV + 32;
constexpr int SM_SLOT = SM_THR + 48;
constexpr int SM_KEY = SM_SLOT + 32;
constexpr int SM_ST = SM_KEY + 64;
constexpr int SM_ST2 = SM_ST + 256;
constexpr int SM_RC = SM_ST2 + 256;
constexpr int SM_SP = SM_RC + 192;
constexpr int SM_AF = SM_SP + 1152, SM_SIL = SM_AF + 1152, SM_INV = SM_SIL + 1152, SM_END = SM_SP + 5760;
constexpr int SM_ONE = SM_MODS + 9 * 1152;
constexpr int SM_WD = SM_W, SM_XS = SM_W + 36864, SM_AC = SM_ZS, SM_RED = SM_AC + 6144;
constexpr int SM_TSB = SM_END, SM_TOTAL = SM_END + TSX - SM0;
static_assert(SM_W % 1024 == 0 && SM_TAP % 1024 == 0 && SM_MODS + 8 * KTAB <= SM_ZS && SM_ZS + 2 * KTAB <= SM_TAP && SM_RED + 10240 <= SM_TAP && SM_XS + 8 * ROW <= SM_ZS, "smem map");
static_assert(SM_MB % 16 == 0 && SM_THR % 16 == 0 && SM_ST % 16 == 0 && SM_SP % 16 == 0 && SM_TOTAL <= 232448, "smem map");
constexpr int TE = 4, TO = 276, T5 = 560, T3 = 624, T9E = 680, T7E = 760, TEO = 40;
#define MT 10
#define MKT 1
#define KST 32
#define DE1 1
#define DE2 4
#define DE3 5
#define OUTB 7
#define PFW 1
#define PFU 0
#define KD 700
#define D0C 0
#define YE 104
#define YL 104
#define YD 250
#define OPTM 1
#define Y8 104
#define FH 0
#define FO 0
#define DB1 1
#define KD1 50
#define AD 0
#define PD 900
#define ZD 0
#define DD 1000
#define INCV 1
#define TPIN 0
#define A5P 1
#define TG 0
#define TU 0
#define TW 0
#define KDB 520
#define PRM 0
#define PRG 0
#define PRU 0
#define PRS 0
#define KE 64
#define PFP 200
#define GE 0
#define NB8 8
#define DX 0
#define DMOD 1000
#define RW 3
#define AW 7
#define HLP 1
#define SMD 1
#define CVG 1
#define SPL 1
#define GX 15
#define HD 0
#define KF 96
#define KDC 520
#define AFP 1
#define AFM 0
#define PFG 1
constexpr int N1 = 320 + 32 * DB1, N12 = 288 + 32 * !DB1;
constexpr int SPIN = 1 << 16, NEARLY = 4;
constexpr u32 TAGM = 0x40004000u, TAGR = 0x40000000u, INVAL = 0x00004801u;

DEV u32 s2u(const void* p) { return (u32)__cvta_generic_to_shared(p); }
DEV void mma_bf(float (&c)[4], u32 a0, u32 a1, u32 a2, u32 a3, u32 b0, u32 b1) {
  asm("mma.sync.aligned.m16n8k16.row.col.f32.bf16.bf16.f32 {%0,%1,%2,%3},{%4,%5,%6,%7},{%8,%9},{%0,%1,%2,%3};"
      : "+f"(c[0]), "+f"(c[1]), "+f"(c[2]), "+f"(c[3]) : "r"(a0), "r"(a1), "r"(a2), "r"(a3), "r"(b0), "r"(b1));
}
DEV void mma_hf(float (&c)[4], u32 a0, u32 a1, u32 a2, u32 a3, u32 b0, u32 b1) {
  asm("mma.sync.aligned.m16n8k16.row.col.f32.f16.f16.f32 {%0,%1,%2,%3},{%4,%5,%6,%7},{%8,%9},{%0,%1,%2,%3};"
      : "+f"(c[0]), "+f"(c[1]), "+f"(c[2]), "+f"(c[3]) : "r"(a0), "r"(a1), "r"(a2), "r"(a3), "r"(b0), "r"(b1));
}
DEV void mma8_bf(float (&c)[4], u32 a0, u32 a1, u32 b0) {
  asm("mma.sync.aligned.m16n8k8.row.col.f32.bf16.bf16.f32 {%0,%1,%2,%3},{%4,%5},{%6},{%0,%1,%2,%3};"
      : "+f"(c[0]), "+f"(c[1]), "+f"(c[2]), "+f"(c[3]) : "r"(a0), "r"(a1), "r"(b0));
}
DEV void mma8_hf(float (&c)[4], u32 a0, u32 a1, u32 b0) {
  asm("mma.sync.aligned.m16n8k8.row.col.f32.f16.f16.f32 {%0,%1,%2,%3},{%4,%5},{%6},{%0,%1,%2,%3};"
      : "+f"(c[0]), "+f"(c[1]), "+f"(c[2]), "+f"(c[3]) : "r"(a0), "r"(a1), "r"(b0));
}
DEV u32 movm(u32 x) { u32 r; asm("movmatrix.sync.aligned.m8n8.trans.b16 %0,%1;" : "=r"(r) : "r"(x)); return r; }
DEV void conv() { if (CVG) asm volatile("{.reg .u32 t; mov.u32 t,0; movmatrix.sync.aligned.m8n8.trans.b16 t,t;}"); }
DEV uint4 ldsm4(u32 a) { uint4 r; asm volatile("ldmatrix.sync.aligned.m8n8.x4.shared.b16 {%0,%1,%2,%3},[%4];" : "=r"(r.x), "=r"(r.y), "=r"(r.z), "=r"(r.w) : "r"(a)); return r; }
DEV uint4 ldsm4t(u32 a) { uint4 r; asm volatile("ldmatrix.sync.aligned.m8n8.x4.trans.shared.b16 {%0,%1,%2,%3},[%4];" : "=r"(r.x), "=r"(r.y), "=r"(r.z), "=r"(r.w) : "r"(a)); return r; }
DEV u32 lds32(u32 a) { u32 r; asm volatile("ld.volatile.shared.u32 %0,[%1];" : "=r"(r) : "r"(a)); return r; }
DEV uint2 lds64(u32 a) { uint2 r; asm volatile("ld.shared.v2.u32 {%0,%1},[%2];" : "=r"(r.x), "=r"(r.y) : "r"(a)); return r; }
DEV uint4 lds128(u32 a) { uint4 r; asm volatile("ld.shared.v4.u32 {%0,%1,%2,%3},[%4];" : "=r"(r.x), "=r"(r.y), "=r"(r.z), "=r"(r.w) : "r"(a)); return r; }
DEV void sts16(u32 a, u32 v) { asm volatile("st.shared.u16 [%0],%1;" ::"r"(a), "h"((unsigned short)v) : "memory"); }
DEV void sts32(u32 a, u32 v) { asm volatile("st.shared.u32 [%0],%1;" ::"r"(a), "r"(v) : "memory"); }
DEV void sts64(u32 a, u32 x, u32 y) { asm volatile("st.shared.v2.u32 [%0],{%1,%2};" ::"r"(a), "r"(x), "r"(y) : "memory"); }
DEV void sts128(u32 a, u32 x, u32 y, u32 z, u32 w) { asm volatile("st.shared.v4.u32 [%0],{%1,%2,%3,%4};" ::"r"(a), "r"(x), "r"(y), "r"(z), "r"(w) : "memory"); }
DEV uint4 ldr128(const void* p) { uint4 v; asm volatile("ld.relaxed.gpu.global.v4.u32 {%0,%1,%2,%3},[%4];" : "=r"(v.x), "=r"(v.y), "=r"(v.z), "=r"(v.w) : "l"(p) : "memory"); return v; }
DEV uint2 ldr64(const void* p) { uint2 v; asm volatile("ld.relaxed.gpu.global.v2.u32 {%0,%1},[%2];" : "=r"(v.x), "=r"(v.y) : "l"(p) : "memory"); return v; }
DEV u32 ldr32(const void* p) { u32 v; asm volatile("ld.relaxed.gpu.global.u32 %0,[%1];" : "=r"(v) : "l"(p) : "memory"); return v; }
template <u32 M> DEV void rld128(uint4& v, const void* p, u32 tag) {
  asm volatile("{.reg .pred p; .reg .u32 t; lop3.b32 t,%0,%5,%6,0x28; setp.ne.u32 p,t,0; @p ld.relaxed.gpu.global.v4.u32 {%0,%1,%2,%3},[%4];}"
               : "+r"(v.x), "+r"(v.y), "+r"(v.z), "+r"(v.w) : "l"(p), "r"(tag), "n"(M) : "memory");
}
template <u32 M> DEV void rld64(uint64_t& v, const void* p, u32 tag) {
  asm volatile("{.reg .pred p; .reg .u32 t, h; mov.b64 {t,h},%0; lop3.b32 t,t,%2,%3,0x28; setp.ne.u32 p,t,0; @p ld.relaxed.gpu.global.u64 %0,[%1];}" : "+l"(v) : "l"(p), "r"(tag), "n"(M) : "memory");
}
template <int L> DEV u32 lop3(u32 a, u32 b, u32 c) { u32 r; asm("lop3.b32 %0,%1,%2,%3,%4;" : "=r"(r) : "r"(a), "r"(b), "r"(c), "n"(L)); return r; }
DEV u32 ne3(u32 a, u32 b, u32 c) { u32 r; asm("lop3.b32 %0,%1,%2,%3,0x7e;" : "=r"(r) : "r"(a), "r"(b), "r"(c)); return r; }
DEV void pin(u32 zr, u32 a, u32 b = 0, u32 c = 0, u32 d = 0) { asm volatile("{.reg .pred p; setp.ne.u32 p,%0,0; @p st.shared.v4.u32 [%0],{%1,%2,%3,%4};}" ::"r"(zr), "r"(a), "r"(b), "r"(c), "r"(d) : "memory"); }
DEV void pin2(u32 zr, const void* a, const void* b) { asm volatile("{.reg .pred p; setp.ne.u32 p,%0,0; @p st.shared.v2.u64 [%0],{%1,%2};}" ::"r"(zr), "l"(a), "l"(b) : "memory"); }
DEV const char* rowa(const char* base, u32 key) { const char* r; asm("mad.wide.u32 %0,%1,288,%2;" : "=l"(r) : "r"(~key & 0x1ffc), "l"(base)); return r; }
DEV void str128(void* p, u32 x, u32 y, u32 z, u32 w) { asm volatile("st.relaxed.gpu.global.v4.u32 [%0],{%1,%2,%3,%4};" ::"l"(p), "r"(x), "r"(y), "r"(z), "r"(w) : "memory"); }
DEV void str64(void* p, u32 x, u32 y) { asm volatile("{.reg .u64 d; mov.b64 d,{%1,%2}; st.relaxed.gpu.global.u64 [%0],d;}" ::"l"(p), "r"(x), "r"(y) : "memory"); }
DEV void str32(void* p, u32 x) { asm volatile("st.relaxed.gpu.global.u32 [%0],%1;" ::"l"(p), "r"(x) : "memory"); }
DEV void str16(void* p, u32 x) { asm volatile("st.relaxed.gpu.global.u16 [%0],%1;" ::"l"(p), "h"((unsigned short)x) : "memory"); }
DEV uint4 ldg128(const void* p) { uint4 v; asm volatile("ld.global.nc.v4.u32 {%0,%1,%2,%3},[%4];" : "=r"(v.x), "=r"(v.y), "=r"(v.z), "=r"(v.w) : "l"(p)); return v; }
DEV uint2 ldg64(const void* p) { uint2 v; asm volatile("ld.global.nc.v2.u32 {%0,%1},[%2];" : "=r"(v.x), "=r"(v.y) : "l"(p)); return v; }
DEV u32 ldg32(const void* p) { u32 v; asm volatile("ld.global.nc.u32 %0,[%1];" : "=r"(v) : "l"(p)); return v; }
DEV u32 ldg16(const void* p) { unsigned short v; asm volatile("ld.global.nc.u16 %0,[%1];" : "=h"(v) : "l"(p)); return v; }
#define bsync(id, n) asm volatile("bar.sync %0,%1;" ::"n"(id), "n"(n) : "memory")
#define barrive(id, n) asm volatile("bar.arrive %0,%1;" ::"n"(id), "n"(n) : "memory")
DEV void bsyncr(u32 id) { asm volatile("bar.sync %0,96;" ::"r"(id) : "memory"); }
DEV void barriver(u32 id) { asm volatile("bar.arrive %0,96;" ::"r"(id) : "memory"); }
constexpr u32 BW = 0x0FEA, BS = 0x6532;
DEV void mb_init(u32 a, u32 n) { asm volatile("mbarrier.init.shared.b64 [%0],%1;" ::"r"(a), "r"(n) : "memory"); }
DEV void mb_arrive(u32 a) { asm volatile("mbarrier.arrive.shared.b64 _,[%0];" ::"r"(a) : "memory"); }
DEV void mb_expect(u32 a, u32 bytes) { asm volatile("mbarrier.arrive.expect_tx.shared.b64 _,[%0],%1;" ::"r"(a), "r"(bytes) : "memory"); }
DEV void mb_wait(u32 a, u32 ph = 0) {
  u32 ok; int it = 0;
  do { asm volatile("{.reg .pred p; mbarrier.try_wait.parity.shared.b64 p,[%1],%2; selp.u32 %0,1,0,p;}" : "=r"(ok) : "r"(a), "r"(ph) : "memory"); } while (!ok && ++it < SPIN);
}
template <int N> DEV void bulk_out(void* dst, u32 src) { asm volatile("cp.async.bulk.global.shared::cta.bulk_group [%0],[%1],%2;" ::"l"(dst), "r"(src), "n"(N) : "memory"); }
constexpr u32 WSH = 41472;
DEV void l2_line(const void* p) { asm volatile("prefetch.global.L2 [%0];" ::"l"(p) : "memory"); }
template <int N> DEV void l2_pre(const void* p) { asm volatile("cp.async.bulk.prefetch.L2.global [%0],%1;" ::"l"(p), "n"(N) : "memory"); }
DEV void tma3d(u32 dst, const CUtensorMap* tm, u32 mb, int c0, int c2) {
  asm volatile("cp.async.bulk.tensor.3d.shared::cluster.global.mbarrier::complete_tx::bytes [%0],[%1,{%3,0,%4}],[%2];"
               ::"r"(dst), "l"((uint64_t)tm), "r"(mb), "r"(c0), "r"(c2) : "memory");
}
DEV float blo(u32 w) { return __uint_as_float(w << 16); }
DEV float bhi(u32 w) { return __uint_as_float(w & 0xffff0000u); }
DEV u32 pk_bf(float lo, float hi) { u32 r; asm("cvt.rn.bf16x2.f32 %0,%1,%2;" : "=r"(r) : "f"(hi), "f"(lo)); return r; }
DEV u32 pk_hf(float lo, float hi) { u32 r; asm("cvt.rn.f16x2.f32 %0,%1,%2;" : "=r"(r) : "f"(hi), "f"(lo)); return r; }
DEV float rbf(float x) { return __uint_as_float(pk_bf(0.f, x) & 0xffff0000u); }
DEV u32 bfma(u32 a, u32 b, u32 c) { u32 r; asm("fma.rn.bf16x2 %0,%1,%2,%3;" : "=r"(r) : "r"(a), "r"(b), "r"(c)); return r; }
DEV u32 bmul(u32 a, u32 b) { u32 r; asm("mul.rn.bf16x2 %0,%1,%2;" : "=r"(r) : "r"(a), "r"(b)); return r; }
DEV u32 badd(u32 a, u32 b) { u32 r; asm("add.rn.bf16x2 %0,%1,%2;" : "=r"(r) : "r"(a), "r"(b)); return r; }
DEV u32 hadd(u32 a, u32 b) { u32 r; asm("add.rn.f16x2 %0,%1,%2;" : "=r"(r) : "r"(a), "r"(b)); return r; }
DEV u32 hfma(u32 a, u32 b, u32 c) { u32 r; asm("fma.rn.f16x2 %0,%1,%2,%3;" : "=r"(r) : "r"(a), "r"(b), "r"(c)); return r; }
struct C2 { u32 re, im; };
DEV C2 cm2(C2 a, C2 b) {
  const __half2 ar = *reinterpret_cast<__half2*>(&a.re), ai = *reinterpret_cast<__half2*>(&a.im), br = *reinterpret_cast<__half2*>(&b.re), bi = *reinterpret_cast<__half2*>(&b.im);
  __half2 re = __hfma2(ar, br, __hneg2(__hmul2(ai, bi))), im = __hfma2(ar, bi, __hmul2(ai, br));
  return {*reinterpret_cast<u32*>(&re), *reinterpret_cast<u32*>(&im)};
}
DEV C2 pk2(const float2 (&a)[2]) { return {pk_hf(a[0].x, a[1].x), pk_hf(a[0].y, a[1].y)}; }
DEV C2 pk2c(const float2 (&a)[2]) { return {pk_hf(a[0].x, a[1].x), pk_hf(-a[0].y, -a[1].y)}; }
DEV u32 cpy(u32 x, u32 zr, int alt) {
  u32 r;
  if (alt) asm volatile("xor.b32 %0,%1,%2;" : "=r"(r) : "r"(x), "r"(zr)); else asm volatile("mad.lo.u32 %0,%2,%2,%1;" : "=r"(r) : "r"(x), "r"(zr));
  return r;
}
template <int N> DEV void inc(u32& x) { asm volatile("add.u32 %0,%0,%1;" : "+r"(x) : "n"(N)); }
DEV u32 opq(u32 x) { u32 r; asm volatile("mov.u32 %0,%1;" : "=r"(r) : "r"(x)); return r; }
DEV u32 chan(u32 b, u32 i) { return 16 * (b >> 2) + 2 * (b & 3) + (i & 1) + 4 * (i & 2); }
DEV u32 row16(u32 lane) { const u32 r0 = (lane & 7) + ((lane >> 3) & 1) + 8 * (lane >> 4) - 1; return (r0 ^ ((r0 >> 3) & 3)) * 16; }
DEV u32 clk() { u32 r; asm volatile("mov.u32 %0,%%clock;" : "=r"(r)::"memory"); return r; }
DEV void wait_clk(u32 t, int d) { while ((int)(clk() - t) < d); }
DEV float ex2(float x) { float r; asm("ex2.approx.ftz.f32 %0,%1;" : "=f"(r) : "f"(x)); return r; }
DEV float rcpf(float x) { float r; asm("rcp.approx.ftz.f32 %0,%1;" : "=f"(r) : "f"(x)); return r; }
DEV float2 cmul(float2 a, float2 b) { return make_float2(fmaf(a.x, b.x, -a.y * b.y), fmaf(a.x, b.y, a.y * b.x)); }
DEV float2 csq(float2 a) { return make_float2(fmaf(a.x, a.x, -a.y * a.y), (a.x + a.x) * a.y); }
DEV float2 cexp(float lr2, float th) {
  const float m = ex2(lr2);
  return make_float2(m * __cosf(th), m * __sinf(th));
}
DEV float silu_f(float v) { return v * rcpf(1.f + ex2(-1.4426950408889634f * v)); }
constexpr u32 B2P64 = 0x5F805F80u, B2M64 = 0x1F801F80u, BONE = 0x3F803F80u;
constexpr u32 MODJ = 18 * 128;
DEV float sqrta(float x) { float r; asm("sqrt.approx.ftz.f32 %0,%1;" : "=f"(r) : "f"(x)); return r; }
DEV u32 fu(float x) { return __float_as_uint(x); }
DEV float uf(u32 x) { return __uint_as_float(x); }
DEV void mma_hf_o(float (&d)[4], const float (&c)[4], const u32 (&a)[4], u32 b0, u32 b1) {
  asm("mma.sync.aligned.m16n8k16.row.col.f32.f16.f16.f32 {%0,%1,%2,%3},{%4,%5,%6,%7},{%8,%9},{%10,%11,%12,%13};"
      : "=f"(d[0]), "=f"(d[1]), "=f"(d[2]), "=f"(d[3]) : "r"(a[0]), "r"(a[1]), "r"(a[2]), "r"(a[3]), "r"(b0), "r"(b1), "f"(c[0]), "f"(c[1]), "f"(c[2]), "f"(c[3]));
}

DEV void mma_hf_t(float (&c)[4], const u32 (&a)[4], u32 b0, u32 b1) { mma_hf(c, a[0], a[1], a[2], a[3], b0, b1); }
DEV void cpa16(u32 dst, const void* src) { asm volatile("cp.async.cg.shared.global [%0],[%1],16;" ::"r"(dst), "l"(src) : "memory"); }
DEV void tm_pre(const CUtensorMap* tm) { asm volatile("prefetch.tensormap [%0];" ::"l"((uint64_t)tm) : "memory"); }
#define PROXY_FENCE() asm volatile("fence.proxy.async.shared::cta;" ::: "memory")
struct Prm {
  const char *la, *ai, *cr, *ci, *ldt;
  u32 zero, glo, ghi;
  const char *x, *c;
  char* gs;
  const char *dsk, *wr, *wg, *wu, *wd;
  char* out;
};
DEV char* gptr(const Prm& p, u32 lo) { char* r; asm("mov.b64 %0,{%1,%2};" : "=l"(r) : "r"(lo), "r"(p.ghi)); return r; }
DEV u32 uni(const Prm& p, u32 x) { return x >> p.zero; }
DEV u32 rowo(u32 base, u32 key) { return (~key & 0x1ffc) * 288 + base; }
constexpr float LOG2E = 1.4426950408889634f, F2P64 = 1.8446744073709552e19f, F2M64 = 5.421010862427522e-20f;

template <int S> DEV void y_store(float c0, float c1, float c2, float c3, u32 F, u32 pml, char* yp) {
  str32(yp, bmul(pk_bf(c0, c2), F) | pml);
  str32(yp + S, bmul(pk_bf(c1, c3), F) | pml);
}
DEV u32 sgn2(u32 a, u32 x, u32 y) { return opq(((a - x) >> 31) + ((a - y) >> 31)); }
DEV void merge4(u32 (&h)[8], uint4 a, uint4 b) {
  const u32 e1 = min(a.x, b.x), e2 = max(a.z, b.z), o1 = min(a.y, b.y), o2 = max(a.w, b.w), o0 = max(a.y, b.y), e3 = min(a.z, b.z);
  const u32 f1 = max(e1, e2), f2 = min(e1, e2), p1 = max(o1, o2), p2 = min(o1, o2);
  h[0] = max(a.x, b.x); h[1] = max(o0, f1); h[2] = min(o0, f1); h[3] = max(p1, f2); h[4] = min(p1, f2); h[5] = max(p2, e3); h[6] = min(p2, e3); h[7] = min(a.w, b.w);
}
DEV void top8(u32 (&a)[8], uint4 l, uint4 m) {
  u32 b[8];
  merge4(b, l, m);
#pragma unroll
  for (int i = 0; i < 8; i++) a[i] = max(a[i], b[7 - i]);
#pragma unroll
  for (int s = 4; s; s >>= 1)
#pragma unroll
    for (int i = 0; i < 8; i++) if (!(i & s)) { const u32 x = a[i], y = a[i + s]; a[i] = max(x, y); a[i + s] = min(x, y); }
}
#define POLL(load, cond_bad, code) { int it_ = 0; do { load; } while (__any_sync(~0u, (cond_bad)) & (++it_ <= SPIN)); if (it_ > SPIN) { ERRF(code); } TSN(code, it_); }
DEV u32 tmask(u32 it, u32 m) { u32 r; asm volatile("{.reg .pred p; setp.ne.u32 p,%1,0; selp.u32 %0,%2,0,p;}" : "=r"(r) : "r"(it), "r"(m)); return r; }
#define POLLM(load, bad, M, code) { u32 it_ = SPIN + (tid >> 16), m_; do { m_ = tmask(--it_, M); load; } while (__any_sync(~0u, (bad) & m_)); if (!it_) { ERRF(code); } TSN(code, SPIN - it_); }
#define POLLS(use, load, bad, M, code) { u32 it_ = SPIN + (tid >> 16); for (;;) { const u32 m_ = tmask(--it_, M); use; if (!__any_sync(~0u, (bad) & m_)) break; load; } if (!it_) { ERRF(code); } TSN(code, SPIN - it_); }
#define POLLW(load, cond_bad, code) { int it_ = 0; while (__any_sync(~0u, (cond_bad))) { if (++it_ > SPIN) { ERRF(code); break; } load; } TSN(code, it_); }

#define DOWN(E) if (tid == (b < 108 ? 288 : ~0u)) { const u32 c0 = 64 * (b % 9), c2 = 4 * (b / 9); \
    if (!D0C && E == 1) { mb_expect(SM_MB + 24, 49152); tma3d(SM_TAP, tm_down, SM_MB + 24, c0, c2); } \
    if (DE1 == E) tma3d(SM_WD, tm_down, SM_MB + 24, c0, c2 + 1); \
    if (DE2 == E) tma3d(SM_WD + 12288, tm_down, SM_MB + 24, c0, c2 + 2); \
    if (DE3 == E) tma3d(SM_WD + 24576, tm_down, SM_MB + 24, c0, c2 + 3); }
#define OUTR() { const u32 tl = 4 * ((lane >> 1) & 1) + ((lane >> 2) & 3) + 8 * (lane & 1); \
    bulk_out<1152>(p.out + (uni(p, b * BLK) + tl * 1152), SM_XST + ((lane & 2) + 4 * (lane & 1) + ((lane >> 2) & 1) + (lane & 8)) * ROW); \
    asm volatile("cp.async.bulk.commit_group;" ::: "memory"); }
struct FA { u32 tid, ba, ra, sa, ad, as; };
DEV FA ffn_addr(const Prm& p, u32 tid, u32 b) {
  const u32 w = tid >> 5, lane = tid & 31, kq = w & 3, tg = w >> 2, t = 7 - w;
  FA f = {tid, SM_XS + (lane & 7) * ROW + (18 * kq + (lane >> 3)) * 16, SM_RED + (8 * tg + kq) * 512 + lane * 16, w >= uni(p, 3 + (b & 1)) && w < 8 ? SM_RED + t * 2048 + lane * 16 : 0,
          (t < 4 ? uni(p, p.glo + G_ACT + 512 * b) + 128 * t : uni(p, p.glo + G_ACT + (512 + (b >> 1)) * 128)) + lane * 4, uni(p, p.glo + G_ACT + (b / 9) * 6144) + tid * 16};
  if (AW & 2) { pin(tid >> 16, f.ba, f.ra, f.sa, tid); pin(tid >> 16, f.ad, f.as); }
  return f;
}
DEV void ffn_tail(const Prm& p, const CUtensorMap* tm_down, uint4 (&A)[24], const FA f, const u32 b, const u32 par, const u32 okl) {
  const u32 tid = f.tid, w = tid >> 5, lane = tid & 31, g = lane >> 2, q = lane & 3, tg = w >> 2, zr = tid >> 16;
  const u32 pm = par ? TAGM : 0, kt = par * 3, ba = f.ba, ra = f.ra;
  char* const gs = p.gs;
  __syncthreads();
  TS(25);
  {
    float c0[2][4] = {}, c1[2][4] = {};
    uint4 bb[5];
#pragma unroll
    for (int s = 0; s < 5; s++) bb[s] = ldsm4(ba + s * 64);
#define BX(s) (s & 1 ? bb[s >> 1].z : bb[s >> 1].x), (s & 1 ? bb[s >> 1].w : bb[s >> 1].y)
    if (!(GX & 2)) {
      DOWN(5);
#pragma unroll
      for (int s = 0; s < 9; s++) mma_bf(c0[s & 1], A[s].x, A[s].y, A[s].z, A[s].w, BX(s));
      if (tg < 2) {
#pragma unroll
        for (int s = 0; s < 9; s++) mma_bf(c1[s & 1], A[9 + s].x, A[9 + s].y, A[9 + s].z, A[9 + s].w, BX(s));
        sts128(ra + 2048, fu(c1[0][0] + c1[1][0]), fu(c1[0][1] + c1[1][1]), fu(c1[0][2] + c1[1][2]), fu(c1[0][3] + c1[1][3]));
      }
    } else if (tg < 2) {
#pragma unroll
      for (int s = 0; s < 9; s++) {
        mma_bf(c0[s & 1], A[s].x, A[s].y, A[s].z, A[s].w, BX(s));
        mma_bf(c1[s & 1], A[9 + s].x, A[9 + s].y, A[9 + s].z, A[9 + s].w, BX(s));
      }
      sts128(ra + 2048, fu(c1[0][0] + c1[1][0]), fu(c1[0][1] + c1[1][1]), fu(c1[0][2] + c1[1][2]), fu(c1[0][3] + c1[1][3]));
    } else {
      DOWN(5);
#pragma unroll
      for (int s = 0; s < 9; s++) mma_bf(s & 2 ? c1[s & 1] : c0[s & 1], A[s].x, A[s].y, A[s].z, A[s].w, BX(s));
#pragma unroll
      for (int i = 0; i < 4; i++) c0[1][i] += c1[0][i] + c1[1][i];
    }
    sts128(ra, fu(c0[0][0] + c0[1][0]), fu(c0[0][1] + c0[1][1]), fu(c0[0][2] + c0[1][2]), fu(c0[0][3] + c0[1][3]));
  }
  const u32 atag = q ? 0 : pm, acs = SM_AC + tid * 16, acl = SM_AC + lane * 16;
  if (GX & 4) pin(zr, atag, acs, acl, kt);
  TS(39);
  if (!(GX & 1)) __syncthreads();
  if (!f.sa) { if (GX & 1) bsync(0, 384); }
  else {
    if (GX & 1) bsync(0, 384);
    float s[4];
    const uint4 u0 = lds128(f.sa), u1 = lds128(f.sa + 512), u2 = lds128(f.sa + 1024), u3 = lds128(f.sa + 1536);
    s[0] = (uf(u0.x) + uf(u1.x)) + (uf(u2.x) + uf(u3.x)); s[1] = (uf(u0.y) + uf(u1.y)) + (uf(u2.y) + uf(u3.y));
    s[2] = (uf(u0.z) + uf(u1.z)) + (uf(u2.z) + uf(u3.z)); s[3] = (uf(u0.w) + uf(u1.w)) + (uf(u2.w) + uf(u3.w));
    const u32 sg = pk_bf(silu_f(rbf(s[0])), silu_f(rbf(s[1])));
    str32(gptr(p, f.ad), bmul(sg, bmul(pk_bf(s[2], s[3]), B2M64)) | atag);
  }
  TS(26);
  const bool fin = w == (b < 72 ? 8 : ~0u);
  u32 kg;
  uint4 xt;
  const char* xs;
  if (fin) { kg = lds32(SM_SLOT + 4 * g); xs = gptr(p, rowo(uni(p, p.glo + G_Y + 16 * b), kg)); xt = ldr128(xs); }
  if (b < 108) {
    const char* const as = gptr(p, f.as);
    uint4 a = ldr128(as);
    char* const dst = gptr(p, uni(p, p.glo + G_PART + b * 2048) + w * 512 + lane * 8);
    if (w < 4) {
      const u32 aa = SM_WD + (8 * (lane >> 4) + (lane & 7)) * 128 + (((2 * w + ((lane >> 3) & 1)) ^ (lane & 7)) << 4);
      mb_wait(SM_MB + 24);
#pragma unroll
      for (int s = 0; s < 24; s++) A[s] = ldsm4t(aa + (s < 6 ? SM_TAP - SM_WD : -12288) + s * 2048);
      if (AW & 2) pin2(zr, dst, as);
    }
    conv();
    TS(28);
    if (!(GX & 16)) {
      POLLW(rld128<TAGM>(a, as, pm), (a.x ^ pm) & TAGM, 9);
      sts128(acs, a.x, a.y, a.z, a.w); sts32(acs, a.x & ~TAGM);
    } else
    POLLS({ sts128(acs, a.x, a.y, a.z, a.w); sts32(acs, a.x & ~TAGM); }, rld128<TAGM>(a, as, pm), a.x ^ pm, TAGM, 9);
    TS(27);
    if (w < 4) {
      bsync(8, 384);
      float c[4][4] = {};
#pragma unroll
      for (int s = 0; s < 12; s++) {
        const uint4 bb = ldsm4t(acl + s * 512);
        mma_bf(c[2 * (s & 1)], A[2 * s].x, A[2 * s].y, A[2 * s].z, A[2 * s].w, bb.x, bb.y);
        mma_bf(c[2 * (s & 1) + 1], A[2 * s + 1].x, A[2 * s + 1].y, A[2 * s + 1].z, A[2 * s + 1].w, bb.z, bb.w);
      }
      u32 o[4];
#pragma unroll
      for (int i = 0; i < 4; i++) o[i] = fu((c[0][i] + c[1][i]) + (c[2][i] + c[3][i]));
      str64(dst, (o[0] & ~3u) | kt, o[1]); str64(dst + 256, (o[2] & ~3u) | kt, o[3]);
      TS(29);
    } else barrive(8, 384);
  }
  if (OUTB == 7 && w == 10 && okl < lds32(SM_SLOT + 28)) OUTR();
  if (fin) {
    const u32 ta = clk();
    const char* src = gptr(p, uni(p, p.glo + G_PART + b * 256) + lane * 8);
    const u32 co = uni(p, 16 * b) + 4 * q, gw = lds32(SM_MODS + 5760 + co), hw = lds32(SM_XS + g * ROW + co);
    const float sgm = rcpf(1.f + ex2(-LOG2E * bhi(kg ^ (~((int)kg >> 31) | 0x80000000))));
    char* const dst = p.out + rowo(co, kg);
    conv();
    POLLW(rld128<TAGM>(xt, xs, TAGR), (xt.x ^ TAGR) & TAGM, 10);
    const u32 x1w = (q & 2) ? ((q & 1) ? xt.w : xt.z) : ((q & 1) ? xt.y : bmul(xt.x ^ TAGR, B2P64));
    const u32 sg2 = bmul(pk_bf(sgm, sgm), B2P64);
    pin(zr, x1w, gw, hw, sg2); pin2(zr, dst, src);
    uint64_t v[12];
#pragma unroll
    for (int j = 0; j < 12; j++) v[j] = 1;
    float s0, s1;
    if (PD) wait_clk(ta, PD);
    conv();
    TS(13);
#define VL(j) (u32)v[j]
#define VS(j, s) ((uf((u32)(v[j] >> s)) + uf((u32)(v[j + 1] >> s))) + (uf((u32)(v[j + 2] >> s)) + uf((u32)(v[j + 3] >> s))))
    u32 res;
    POLLM({ _Pragma("unroll") for (int j = 0; j < 12; j++) rld64<3>(v[j], src + j * 9 * 2048, kt);
            s0 = VS(0, 0) + VS(4, 0) + VS(8, 0); s1 = VS(0, 32) + VS(4, 32) + VS(8, 32);
            res = opq(badd(x1w, bmul(gw, badd(hw, bmul(movm(pk_bf(s0, s1)), sg2))))); TSRND(); },
          lop3<0xfe>(ne3(VL(0), VL(1), kt), ne3(VL(2), VL(3), kt), ne3(VL(4), VL(5), kt)) |
          lop3<0xfe>(ne3(VL(6), VL(7), kt), ne3(VL(8), VL(9), kt), ne3(VL(10), VL(11), kt)), 3, 11);
    asm volatile("st.global.u32 [%0],%1;" ::"l"(dst), "r"(res) : "memory");
    if (b == 0 && lane == 0) str32(gs + G_EP, par);
    TS(30); TSE();
  }
  if (w == 10) asm volatile("cp.async.bulk.wait_group.read 0;" ::: "memory");
}

DEV u32 y_lo(const Prm& p, u32 tid, u32 b) {
  const u32 ua = uni(p, p.glo + G_Y + b * 128), ub = uni(p, p.glo + 16384 + (b & ~3) * BLK + (b & 3) * 512);
  return (tid < 256 ? ua : ub) + (((tid & 2) * 4) | ((tid >> 2) & 4)) * (tid < 256 ? BLK : 32) + (tid >> 5) * (16 * BLK) + ((tid >> 2) & 3) * 32 + (tid & 1) * 16;
}
DEV void post_conv(const Prm& p, const CUtensorMap* tm_down, const u32 tid, const u32 b, const u32 b3) {
  const u32 w = tid >> 5, lane = tid & 31;
  const u32 g = lane >> 2, q = lane & 3, e = g >> 2, h = (g >> 1) & 1, hi = g & 1;
  const u32 pm = lds32(SM_THR + 4), par = pm >> 30;
  char* const gs = p.gs;
  const u32 cho = 128 * w + 64 * e + 16 * q;
  u32 x1[4][4], h2[4][4], key[4], lt;
  u32 okl = ~0u;
  FA fa;
  uint4 A[24];
#define AROW(t) const u32 arow = 144 * ((t >> 5) & 3) + ((t >> 1) & 8) + (t & 7), ab = (t & 8) ? SM_UP : SM_GATE;
#define AFRAG9() { _Pragma("unroll") for (int s = 0; s < 9; s++) A[s] = ldsm4t(ab + SLV + arow * 16 + s * 256); }
#define AFRAG18() { const u32 t3 = opq(tid); AROW(t3); if (t3 < 256) { const u32 aa = ab + arow * 64 + ((((t3 >> 6) & 2) ^ ((t3 & 7) >> 1)) << 4); \
      _Pragma("unroll") for (int s = 0; s < 9; s++) { A[s] = ldsm4t(aa + s * 1024); A[9 + s] = ldsm4t((aa ^ 16) + s * 1024); } } else AFRAG9(); }
  if (w < 9) {
    const char* const ys = gptr(p, y_lo(p, tid, b));
    uint4 yv[4];
#pragma unroll
    for (int v = 0; v < 4; v++) yv[v].x = INVAL;
    const u32 tg0 = b < YL ? pm : INVAL;
    if (w >= 4) { pin2(tid >> 16, ys, ys); bsync(12, N12); TS(18); }
#pragma unroll
    for (int v = 0; v < 4; v++) rld128<TAGM>(yv[v], ys + v * BLK, tg0);
    const u32 tc = clk();
    const u32 ma = SM_MODS + cho, xa = SM_XST + (2 * h + 4 * hi) * ROW + cho;
    const uint4 sa = lds128(ma), ca = lds128(ma + 1152), ga = lds128(ma + 2304);
    const uint4 rb = lds128((g & 2) ? SM_ONE + 16 * hi : (ma ^ 64) + 8064 + 1152 * hi);
    const u32 saw[4] = {sa.x, sa.y, sa.z, sa.w}, caw[4] = {ca.x, ca.y, ca.z, ca.w}, gaw[4] = {ga.x, ga.y, ga.z, ga.w};
#pragma unroll
    for (int k = 0; k < 4; k++) {
      const uint2 st = lds64(SM_ST + 16 * (2 * h + 4 * hi + (k & 1) + 8 * (k >> 1)));
      const uint4 xv = lds128(xa + ((k & 1) + 8 * (k >> 1)) * ROW);
      x1[k][0] = xv.x; x1[k][1] = xv.y; x1[k][2] = xv.z; x1[k][3] = xv.w;
#pragma unroll
      for (int v = 0; v < 4; v++) x1[k][v] = badd(x1[k][v], bfma(bmul(badd(x1[k][v], st.x), st.y), caw[v], saw[v]));
    }
    const bool own = (q >> 1) == e;
    const u32 spw = SM_SP + (2 * w + e) * 320 + (g & 3) * 16 + (own ? ((q & 1) == h ? 4 : 12) : 8 - 8 * (q & 1));
    if (SMD && w < 4) asm volatile("setmaxnreg.dec.sync.aligned.u32 168;");
    if (b >= YL) wait_clk(tc, YD);
    conv();
    TS(13);
    POLLW(_Pragma("unroll") for (int v = 0; v < 4; v++) rld128<TAGM>(yv[v], ys + v * BLK, pm), lop3<0xa8>(ne3(yv[0].x, yv[1].x, pm), ne3(yv[2].x, yv[3].x, pm), TAGM), 5);
    TS(19);
    if (!SMD && w < 4) asm volatile("setmaxnreg.dec.sync.aligned.u32 168;");
#pragma unroll
    for (int k = 0; k < 4; k += 2) {
      float X[4] = {}, Y[4] = {}, R[4] = {};
#pragma unroll
      for (int v = 0; v < 4; v++) {
        const u32 y0 = k ? yv[v].z : yv[v].x & ~TAGM, y1 = k ? yv[v].w : yv[v].y;
        x1[k][v] = bfma(movm(y0), gaw[v], x1[k][v]);
        x1[k + 1][v] = bfma(movm(y1), gaw[v], x1[k + 1][v]);
        mma8_bf(X, x1[k][v], x1[k + 1][v], x1[k][v]); mma8_bf(Y, x1[k][v], x1[k + 1][v], x1[k + 1][v]);
        if (v & 1) mma_bf(R, x1[k][v - 1], x1[k + 1][v - 1], x1[k][v], x1[k + 1][v], v & 2 ? rb.z : rb.x, v & 2 ? rb.w : rb.y);
      }
      sts32(spw + k * 64, fu(own ? (hi ? X[1] : X[0]) : R[0] + R[1]));
      sts32(spw + k * 64 + 64, fu(own ? (hi ? Y[3] : Y[2]) : R[2] + R[3]));
    }
    barrive(1, N1);
    TS(36);
    if (AFP) { asm volatile("setmaxnreg.inc.sync.aligned.u32 168;"); mb_wait(SM_MB + 8); mb_wait(SM_MB + 16); }
    const uint4 sb = lds128(ma + 3456), cb = lds128(ma + 4608), gb = lds128(ma + 5760);
    const u32 sbw[4] = {sb.x, sb.y, sb.z, sb.w}, cbw[4] = {cb.x, cb.y, cb.z, cb.w}, gbw[4] = {gb.x, gb.y, gb.z, gb.w};
    const u32 t3 = opq(tid), zr = t3 >> 16;
    AROW(t3);
    const u32 aa = ab + arow * 64 + ((((t3 >> 6) & 2) ^ ((t3 & 7) >> 1)) << 4), sta = SM_ST2 + 16 * (g & 3);
    const u32 rowl = uni(p, p.glo + b * BLK) + (4 * h + 8 * hi) * 1152 + cho;
    char* const rowp = gptr(p, rowl);
    if (AFP) { pin(zr, aa, sta, xa); pin2(zr, rowp, rowp); }
    bsync(2, 320);
    TS(37);
    uint4 st[4];
#pragma unroll
    for (int k = 0; k < 4; k++) st[k] = lds128(sta + 64 * k);
    lt = lds32(SM_THR);
#define AFL() { _Pragma("unroll") for (int s = 0; s < 9; s++) { A[s] = ldsm4t(aa + s * 1024); A[9 + s] = ldsm4t((aa ^ 16) + s * 1024); } }
    if (AFP && (AFM >> w & 1)) { if (w < 8) AFL() else AFRAG9(); }
#pragma unroll
    for (int k = 0; k < 4; k++) {
      key[k] = st[k].w;
      u32 o[4];
#pragma unroll
      for (int v = 0; v < 4; v++) {
        const u32 d = badd(x1[k][v], st[k].x), z = bfma(d, st[k].y, bmul(d, st[k].z));
        h2[k][v] = FH ? bfma(z, cbw[v], sbw[v]) : badd(bmul(z, cbw[v]), sbw[v]);
        o[v] = FO ? bfma(gbw[v], h2[k][v], x1[k][v]) : badd(x1[k][v], bmul(gbw[v], h2[k][v]));
      }
      h2[k][0] = bmul(h2[k][0], B2M64) | TAGR; x1[k][0] = bmul(x1[k][0], B2M64) | TAGR;
      if (key[k] >= lt) str128(rowp + k * 1152, h2[k][0], h2[k][1], h2[k][2], h2[k][3]);
      sts128(xa + ((k & 1) + 8 * (k >> 1)) * ROW, o[0], o[1], o[2], o[3]);
    }
    barrive(3, 320);
    TS(21);
    if (!AFP) { asm volatile("setmaxnreg.inc.sync.aligned.u32 168;"); mb_wait(SM_MB + 8); mb_wait(SM_MB + 16); AFRAG18(); }
    else if (!(AFM >> w & 1)) { if (w < 8) AFL() else AFRAG9(); }
    TS(22);
    const u32 rr = tid * 57 >> 12, rc = tid * 16 - rr * 1152, sl = SM_SLOT + 8 * rr;
    const u32 rb_ = p.glo + rc;
    const u32 km = max(max(key[0], key[1]), max(key[2], key[3])), xd = SM_XS + rr * (2 * ROW) + rc;
    if (RW & 2) { pin(tid >> 16, sl, km, xd); pin(tid >> 16, rb_, rowl); }
    fa = ffn_addr(p, tid | p.zero, b);
    bsync(6, 320);
    TS(24);
    const uint2 sk = lds64(sl);
    const char *r0 = gptr(p, rowo(rb_, sk.x)), *r1 = gptr(p, rowo(rb_, sk.y));
    uint4 rv[2] = {ldr128(r0), ldr128(r1)};
    barrive(15, 320);
    const u32 g8 = lds32(SM_SLOT + 28);
    if (__any_sync(~0u, km >= g8 && lt > g8)) {
      char* const rowq = gptr(p, opq(rowl));
#pragma unroll
      for (int k = 0; k < 4; k++) if (key[k] >= g8 && key[k] < lt) str128(rowq + k * 1152, h2[k][0], h2[k][1], h2[k][2], h2[k][3]);
    }
    bsync(5, 320);
    const uint2 sf = lds64(sl);
    const u32 f8 = lds32(SM_SLOT + 28);
    if (__any_sync(~0u, km >= f8)) {
      char* const rowq = gptr(p, opq(rowl));
#pragma unroll
      for (int k = 0; k < 4; k++) if (key[k] >= f8) str128(rowq + (G_Y + k * 1152), x1[k][0], x1[k][1], x1[k][2], x1[k][3]);
    }
    if (__any_sync(~0u, sf.x != sk.x || sf.y != sk.y)) {
      r0 = gptr(p, rowo(rb_, sf.x)); r1 = gptr(p, rowo(rb_, sf.y));
      rv[0].x = rv[1].x = INVAL;
    }
    if (!(GX & 8)) {
      POLLW({ rld128<TAGM>(rv[0], r0, TAGR); rld128<TAGM>(rv[1], r1, TAGR); }, ne3(rv[0].x, rv[1].x, TAGR) & TAGM, 8);
#pragma unroll
      for (int j = 0; j < 2; j++) sts128(xd + j * ROW, bmul(rv[j].x ^ TAGR, B2P64), rv[j].y, rv[j].z, rv[j].w);
    } else
    POLLS(_Pragma("unroll") for (int j = 0; j < 2; j++) { sts128(xd + j * ROW, rv[j].x, rv[j].y, rv[j].z, rv[j].w); sts32(xd + j * ROW, bmul(rv[j].x ^ TAGR, B2P64)); },
          { rld128<TAGM>(rv[0], r0, TAGR); rld128<TAGM>(rv[1], r1, TAGR); }, ne3(rv[0].x, rv[1].x, TAGR), TAGM, 8);
    TS(38);
  } else {
    u32 ok, lr;
    if (w == 10) {
      uint2 rc = lds64(SM_RC + 8 * min(lane, 17u));
      float r1 = lane < 18 ? uf(rc.x) : 0.f, r2 = lane < 18 ? uf(rc.y) : 0.f;
#pragma unroll 1
      for (int o = 16; o; o >>= 1) { r1 += __shfl_xor_sync(~0u, r1, o); r2 += __shfl_xor_sync(~0u, r2, o); }
      const u32 tl = 4 * ((lane >> 1) & 1) + ((lane >> 2) & 3) + 8 * (lane & 1), kl = (2047 - 16 * b - tl) << 2 | par * 3;
      const u32 kp = uni(p, p.glo + G_KEY + b * KST) + (tid >> 16);
      const u32 spr = SM_SP + (lane >> 4) * 9 * 320 + (lane & 15) * 16;
      TS(31);
      r2 += 0.f;
      const u32 nth = b < NB8 ? 7 : NEARLY - 1, ka = SM_KEY + 4 * (lane & 15), kb = SM_KEY + 2 * (lane & 16), lim = lane < 16 ? 8 : 0;
      pin(tid >> 16, kl, ka, kb, lim); pin(tid >> 16, kp);
      conv();
      bsync(1, N1);
      uint4 t = lds128(spr);
      float S1 = uf(t.x), S2 = uf(t.y), S3 = uf(t.z);
#pragma unroll
      for (int i = 1; i < 9; i++) { t = lds128(spr + i * 320); S1 += uf(t.x); S2 += uf(t.y); S3 += uf(t.z); }
      S1 += __shfl_xor_sync(~0u, S1, 16); S2 += __shfl_xor_sync(~0u, S2, 16); S3 += __shfl_xor_sync(~0u, S3, 16);
      const float mu = S1 * (1.f / 576.f), var = fmaxf(fmaf(-mu, mu, S2 * (1.f / 576.f)), 0.f);
      const float m = rbf(mu), rs = rcpf(rbf(sqrta(rbf(rbf(var) + 1e-5f))));
      const u32 rb = pk_bf(0.f, fmaf(fmaf(-m, r1, S3), rs, r2));
      ok = ((rb ^ (((int)rb >> 31) | 0x80000000)) & 0xffff0000u) | kl;
      const float rh = rbf(rs);
      const u32 oh = ok >> 1;
      sts32(ka, oh);
      __syncwarp();
      const uint4 o0 = lds128(kb), o1 = lds128(kb + 16);
      sts128(SM_ST2 + 16 * (lane & 15), pk_bf(-m, -m), pk_bf(rh, rh), pk_bf(rs - rh, rs - rh), ok);
      lr = opq(sgn2(oh, o0.x, o0.y) + sgn2(oh, o0.z, o0.w)) +
           opq(sgn2(oh, o1.x, o1.y) + sgn2(oh, o1.z, o1.w));
      lr += __shfl_xor_sync(~0u, lr, 16);
      asm volatile("{.reg .pred p; setp.lt.u32 p,%0,%1; @p st.relaxed.gpu.global.u32 [%2],%3;}" ::"r"(lr), "r"(lim), "l"(gptr(p, kp + 4 * lr)), "r"(ok) : "memory");
      if (lr == nth) sts32(SM_THR, ok);
      barrive(2, 320);
      barrive(13, 64);
      TS(20);
    } else if (w == 9) {
      if (DB1) bsync(1, N1); else { bsync(12, N12); wait_clk(clk(), DD); }
      PROXY_FENCE();
      DOWN(1);
    } else {
      const char* ks = gs + (G_KEY + (lane >> 1) * KST + (lane & 1) * 16);
      const u32 kt = par * 3;
      uint4 L[8];
      u32 H[8];
#define KBAD(j) ((L[j].x ^ kt) & 3)
#define KLD(j) L[j] = ldr128(ks + j * 16 * KST)
#pragma unroll
      for (int j = 0; j < 8; j++) L[j].x = INVAL;
      bsync(13, 64);
      wait_clk(clk(), b < KE ? KD : b < KF ? KDB : b < YL ? KDC : KD1);
      TS(34);
      POLL({ _Pragma("unroll") for (int j = 0; j < 8; j++) if (KBAD(j)) KLD(j);
             merge4(H, L[0], L[1]); top8(H, L[2], L[3]);
             asm volatile("" : "+r"(H[0]), "+r"(H[1]), "+r"(H[2]), "+r"(H[3]), "+r"(H[4]), "+r"(H[5]), "+r"(H[6]), "+r"(H[7])); TS(32); },
           KBAD(0) | KBAD(1) | KBAD(2) | KBAD(3) | KBAD(4) | KBAD(5), 6);
      u32 u = __reduce_max_sync(~0u, max(H[0], max(L[4].x, L[5].x)));
      top8(H, L[4], L[5]);
      TS(35);
      u32 m[8], x0 = H[0], x1 = H[1];
#pragma unroll
      for (int r = 0; r < 8; r++) {
        const u32 ur = u;
        const bool win = x0 == ur;
        if (r < 7) { x0 = max(x0 - ur, x1 - ur); u = __reduce_max_sync(~0u, x0); }
        m[r] = r ? m[r - 1] + ur : ur;
        if (r == 0) { if (KBAD(6)) KLD(6); if (KBAD(7)) KLD(7); }
#pragma unroll
        for (int i = 1; i < 7 - r; i++) H[i] = win ? H[i + 1] : H[i];
        x1 = H[1] - m[r];
        if ((r & 3) == 3) sts128(SM_SLOT + 4 * r - 12, m[r - 3], m[r - 2], m[r - 1], m[r]);
      }
      barrive(6, 320);
      TS(23);
      conv();
      POLLW({ if (KBAD(6)) KLD(6); if (KBAD(7)) KLD(7); }, KBAD(6) | KBAD(7), 7);
      conv();
      u = __reduce_max_sync(~0u, max(L[6].x, L[7].x));
      if (u > m[7]) {
        do {
          const u32 x = u;
          if (L[6].x == x) L[6] = make_uint4(L[6].y, L[6].z, L[6].w, 0);
          if (L[7].x == x) L[7] = make_uint4(L[7].y, L[7].z, L[7].w, 0);
          u = __reduce_max_sync(~0u, max(L[6].x, L[7].x));
#pragma unroll
          for (int i = 7; i; i--) m[i] = max(min(m[i - 1], x), m[i]);
          m[0] = max(m[0], x);
        } while (u > m[7]);
        sts128(SM_SLOT, m[0], m[1], m[2], m[3]); sts128(SM_SLOT + 16, m[4], m[5], m[6], m[7]);
      }
      barrive(5, 320);
      TS(33);
    }
    asm volatile("setmaxnreg.inc.sync.aligned.u32 168;");
    mb_wait(SM_MB + 8); mb_wait(SM_MB + 16);
    AROW(tid);
    AFRAG9();
    fa = ffn_addr(p, tid | p.zero, b);
    TS(22);
    if (w == 10) {
      bsync(3, 320);
      PROXY_FENCE();
      if (lane < 16 && lr >= 8) OUTR();
      if (lane < 16 && lr < 8) okl = ok;
    } else if (w == 9) {
      bsync(15, 320);
      DOWN(4);
      TS(13);
    }
  }
  ffn_tail(p, tm_down, A, fa, b3, par, okl);
}

__global__ void __launch_bounds__(384, 1)
fused_kernel(const Prm p, const __grid_constant__ CUtensorMap tm_mod, const __grid_constant__ CUtensorMap tm_gate, const __grid_constant__ CUtensorMap tm_gs,
             const __grid_constant__ CUtensorMap tm_up, const __grid_constant__ CUtensorMap tm_us, const __grid_constant__ CUtensorMap tm_down) {
  extern __shared__ __align__(1024) unsigned char smem[];
  u32 la, ai, ldt; uint2 cr, ci;
  {
    const u32 t = threadIdx.x, d = t < 256 ? chan(blockIdx.x, t >> 5) : 512 + (blockIdx.x >> 1), o = d * 256 + 8 * (t & 31), o4 = o + ((t < 256 ? t >> 5 : t >> 3) & 4);
    asm volatile("{.reg .pred p; .reg .u16 h; setp.ne.u32 p,%7,0; @p ld.global.nc.u32 %0,[%8]; @p ld.global.nc.u32 %1,[%9]; @p ld.global.nc.v2.u32 {%2,%3},[%10];"
                 "@p ld.global.nc.v2.u32 {%4,%5},[%11]; @p ld.global.nc.u16 h,[%12]; cvt.u32.u16 %6,h;}"
                 : "=r"(la), "=r"(ai), "=r"(cr.x), "=r"(cr.y), "=r"(ci.x), "=r"(ci.y), "=r"(ldt)
                 : "r"(0x6ffu >> (t >> 5) & 1), "l"(p.la + o4), "l"(p.ai + o4), "l"(p.cr + o), "l"(p.ci + o), "l"(p.ldt + 2 * d));
  }
  const u32 t0 = clk();
  const u32 tid = __shfl_sync(~0u, threadIdx.x, threadIdx.x & 31), b = blockIdx.x + p.zero;
  const u32 w = tid >> 5, lane = tid & 31;
  const u32 g = lane >> 2, q = lane & 3, hi = g & 1;
  const u32 rho = b & 1, Ps = 512 + (b >> 1);
  char* const gs = p.gs;
  TS0();
  const bool kw = w != 8 && w != 11;
  const u32 ksig = w < 8 ? (w & 3) : 4, khf = w < 8 ? (w >> 2) : (w & 1);
  if (!kw) {
    if (tid == 352) {
#pragma unroll
      for (int i = 0; i < 5; i++) mb_init(SM_MB + 8 * i, i < 4 ? 1 : 64);
      asm volatile("fence.mbarrier_init.release.cluster;" ::: "memory");
      tm_pre(&tm_mod);
    }
    const char* cp = p.c + (576 * (w & 1) + 24 * min(lane, 23u));
    const uint2 c0 = ldg64(cp);
    la = c0.x; ai = c0.y; cr = ldg64(cp + 8); ci = ldg64(cp + 16);
  }
  u32 b3;
  asm volatile("shr.u32 %0,%1,%2;" : "=r"(b3) : "r"(blockIdx.x), "r"(p.zero));
  const u32 zr = tid >> 16;
  const u32 epv = ldr32(gs + (G_EP + zr));
  const u32 tp = SM_TAP + ksig * TAPS;
  if (kw && !khf) {
#pragma unroll 1
    for (u32 i = lane * 16; i < TAPS; i += 512) sts128(tp + i, 0, 0, 0, 0);
  }
  if (tid < 128) sts128(SM_INV + 16 * tid, INVAL, 0, 1, 0);
  if (tid >= 124) str128(gs + (tid >= 380 ? G_MOD + b * 128 + q * 16 : b * BLK + 16384 - 252 * 16 + tid * 16 + (tid < 252 ? G_Y + 2048 : 0)), INVAL, 0, 1, 0);
  if (tid == (b < 36 ? 352 : ~0u)) { while (clk() - t0 < DMOD); mb_expect(SM_MB, 36864); tma3d(SM_UP, &tm_mod, SM_MB, 32 * b, 0); }
  if (w < 9) {
    while ((int)(clk() - t0) < DX);
    const char* xp = p.x + (b * BLK + (lane >> 3) * 1152 + 128 * w + 16 * (lane & 7));
    const u32 xd = SM_XST + (((lane >> 3) & 1) + 8 * (lane >> 4)) * ROW + 128 * w + 16 * (lane & 7);
#pragma unroll
    for (int i = 0; i < 4; i++) cpa16(xd + 2 * ROW * i, xp + 4608 * i);
  }
  const u32 ktab = w < 8 ? SM_MODS + w * KTAB : SM_ZS + (w - 9) * KTAB;
  float k2048 = 0.f;
  if (kw) {
    u32 mx = __vmaxu2(__vmaxu2(cr.x & 0x7fff7fff, cr.y & 0x7fff7fff), __vmaxu2(ci.x & 0x7fff7fff, ci.y & 0x7fff7fff));
    const u32 E = max(__reduce_max_sync(~0u, max(mx & 0xffff, mx >> 16)) >> 7, 8u);
    TS(1);
    const float dt = rbf(ex2(blo(ldt) * LOG2E)), csc = uf((257 - E) << 23 | (fu(dt) & 0x7fffff));
    sts32(SM_SC + 16 * ksig + 12, fu(uf(fu(dt) & 0x7f800000) * uf((E - 2) << 23)));
    const u32 crw = khf ? cr.y : cr.x, ciw = khf ? ci.y : ci.x;
    float2 C[2], w4[2], w8[2], w16[2], w32[2], w64[2], w128[2], w256[2], w512[2], a1[2], a2[2], a3[2], t0[2], t1[2], s3[2];
#pragma unroll
    for (int m = 0; m < 2; m++) {
      const float lr2 = rbf(ex2((m ? bhi(la) : blo(la)) * LOG2E)) * dt * -LOG2E, th = (m ? bhi(ai) : blo(ai)) * dt;
      C[m] = make_float2((m ? bhi(crw) : blo(crw)) * csc, (m ? bhi(ciw) : blo(ciw)) * csc);
      const float2 w1 = cexp(lr2, th), w2 = csq(w1);
      w64[m] = cexp(64.f * lr2, 64.f * th);
      w4[m] = csq(w2); w8[m] = csq(w4[m]); w16[m] = csq(w8[m]); w32[m] = csq(w16[m]);
      w128[m] = csq(w64[m]); w256[m] = csq(w128[m]); w512[m] = csq(w256[m]);
      const float2 w1024 = csq(w512[m]);
      a1[m] = cmul(C[m], w1); a2[m] = cmul(C[m], w2); a3[m] = cmul(a1[m], w2);
      t0[m] = cmul(C[m], w1024); t1[m] = cmul(t0[m], w128[m]); s3[m] = cmul(w8[m], w16[m]);
      k2048 += fmaf(t0[m].x, w1024.x, -t0[m].y * w1024.y);
    }
    C2 B0[8], B1[8], B2[8], S[8];
    B0[0] = pk2(C); B0[1] = pk2(a1); B0[2] = pk2(a2); B0[3] = pk2(a3);
    const C2 h4 = pk2(w4), h256 = pk2(w256), h512 = pk2(w512);
#pragma unroll
    for (int i = 0; i < 4; i++) B0[4 + i] = cm2(B0[i], h4);
#pragma unroll
    for (int i = 0; i < 4; i++) B1[i] = cm2(B0[2 * i], h256);
    B1[4] = cm2(B0[0], h512); B1[5] = cm2(B0[4], h512);
    B1[6] = cm2(B1[4], h256); B1[7] = cm2(B1[5], h256);
    const u32 ta = ktab + lane * 128, f = ((lane & 3) << 5) | ((lane & 4) << 2);
#pragma unroll
    for (int i = 0; i < 8; i++) sts128(ta + ((i << 4) ^ f), B0[i].re, B0[i].im, B1[i].re, B1[i].im);
    B2[0] = pk2(t0); B2[1] = pk2(t1);
    B2[2] = cm2(B2[0], h256); B2[3] = cm2(B2[1], h256);
#pragma unroll
    for (int i = 0; i < 4; i++) B2[4 + i] = cm2(B2[i], h512);
    S[0] = {0x3C003C00u, 0u}; S[1] = pk2c(w8); S[2] = pk2c(w16); S[3] = pk2c(s3); S[4] = pk2c(w32);
#pragma unroll
    for (int i = 1; i < 4; i++) S[4 + i] = cm2(S[i], S[4]);
#pragma unroll
    for (int i = 0; i < 8; i++) sts128(ta + 4096 + ((i << 4) ^ f), B2[i].re, B2[i].im, S[i].re, S[i].im);
    const C2 m64 = pk2c(w64), m128 = pk2c(w128);
    sts128(ktab + 8192 + lane * 16, m64.re, m64.im, m128.re, m128.im);
    __syncwarp();
  } else {
    u32 sa = SM_SIL + 576 * (w & 1) + 24 * min(lane, 23u);
#pragma unroll 1
    for (int j = 0; j < 6; j++) {
      sts32(sa, pk_bf(silu_f(blo(la)), silu_f(bhi(la))));
      la = ai; ai = cr.x; cr.x = cr.y; cr.y = ci.x; ci.x = ci.y; sa += 4;
    }
    bsync(7, 64);
  }
  TS(2);
  const u32 pm = (__reduce_or_sync(~0u, epv) & 1) ? 0 : TAGM;
  sts32(SM_THR + 4, pm);
  if (w < 9) {
    asm volatile("cp.async.wait_all;" ::: "memory");
    __syncwarp();
    TS(4);
    if (tid == (b - 36 < 72 ? 256 : ~0u)) { mb_expect(SM_MB, 36864); tma3d(SM_UP, &tm_mod, SM_MB, 32 * b, 0); }
    const u32 xa = SM_XST + (lane & 15) * ROW + 128 * w + 16 * (lane >> 4);
    float s[4] = {}, X[2][4] = {}, Y[2][4] = {};
#pragma unroll
    for (int j = 0; j < 4; j++) {
      const uint4 a = ldsm4(xa + 32 * j);
      mma8_bf(X[0], a.x, a.y, a.x); mma8_bf(Y[0], a.x, a.y, a.y);
      mma8_bf(X[1], a.z, a.w, a.z); mma8_bf(Y[1], a.z, a.w, a.w);
      mma_bf(s, a.x, a.y, a.z, a.w, BONE, BONE);
    }
    uint4 t[4];
#pragma unroll
    for (int j = 0; j < 4; j++) t[j] = ldsm4t(xa + 32 * j);
    const float u0 = hi ? X[0][1] + X[1][1] : X[0][0] + X[1][0], u1 = hi ? Y[0][3] + Y[1][3] : Y[0][2] + Y[1][2];
    if (q == g >> 1) sts128(SM_SP + w * 128 + g * 16, fu(s[0]), fu(u0), fu(s[2]), fu(u1));
    bsync(1, 288);
    TS(7);
    const u32 spr = SM_SP + (lane & 7) * 16 + (lane & 8);
    const uint2 t8 = lds64(spr + 1024);
    const float f8 = lane < 16 ? 1.f : 0.f;
    float S1 = uf(t8.x) * f8, S2 = uf(t8.y) * f8;
#pragma unroll
    for (int i = 0; i < 4; i++) { const uint2 u = lds64(spr + (lane & 16) * 32 + i * 128); S1 += uf(u.x); S2 += uf(u.y); }
    S1 += __shfl_xor_sync(~0u, S1, 16); S2 += __shfl_xor_sync(~0u, S2, 16);
    const float mu = S1 * (1.f / 576.f), var = fmaxf(fmaf(-mu, mu, S2 * (1.f / 576.f)), 0.f);
    const float m = rbf(mu), rs = rcpf(rbf(sqrta(rbf(rbf(var) + 1e-5f))));
    const float ra = rs * 0.0625f;
    sts64(SM_AF + w * 128 + (lane & 15) * 8, fu(ra), fu(-m * ra));
    __syncwarp();
    TS(55);
    const uint4 f0 = lds128(SM_AF + w * 128 + q * 16), f1 = lds128(SM_AF + w * 128 + 64 + q * 16);
    const u32 zdst = SM_GATE + w * 2048 + (g >> 1) * 128 + (lane & 15) * 8;
    const u32 pz = (q & 1) ? 0 : pm;
#pragma unroll
    for (int j = 0; j < 8; j++) {
      const u32 x0 = j & 1 ? t[j >> 1].z : t[j >> 1].x, x1 = j & 1 ? t[j >> 1].w : t[j >> 1].y;
      sts64((j & 1 ? zdst ^ 64 : zdst) + 512 * (j >> 1), pk_hf(fmaf(blo(x0), uf(f0.x), uf(f0.y)), fmaf(bhi(x0), uf(f0.z), uf(f0.w))) | pz,
            pk_hf(fmaf(blo(x1), uf(f1.x), uf(f1.y)), fmaf(bhi(x1), uf(f1.z), uf(f1.w))));
    }
    TS(53);
    if (w < 8) barrive(15, 288);
    else {
      bsync(15, 288);
      TS(54);
      if (lane == 0) {
        PROXY_FENCE();
        bulk_out<BLK>(gs + b * BLK, SM_GATE);
        asm volatile("cp.async.bulk.commit_group;" ::: "memory");
        if (PFG & 1) l2_pre<WSH / 2>(p.wg + b * WSH);
      }
      const float rh = rbf(rs);
      sts128(SM_ST + 16 * (lane & 15), pk_bf(-m, -m), pk_bf(rh, rh), pk_bf(rs - rh, rs - rh), 0);
    }
    TS(5);
  }
  if (kw) {
    float D[5][4] = {};
    u32 ta = ktab + q * 128 + ((g ^ (q << 1)) << 4), tm = ktab + 8192 + q * 16;
#pragma unroll 2
    for (int s = 0; s < 8; s++) {
      const uint4 ca = lds128(ta), cb = lds128(ta + 4096), ma = lds128(tm);
      ta = (ta + 512) ^ 16; tm += 64;
      k2048 += __shfl_xor_sync(~0u, k2048, 16 >> s);
      const C2 s0 = {cb.z, cb.w}, s1 = cm2(s0, {ma.x, ma.y}), s2 = cm2(s0, {ma.z, ma.w}), s3 = cm2(s1, {ma.z, ma.w});
      mma_hf(D[0], s0.re, s1.re, s0.im, s1.im, ca.x, ca.y);
      mma_hf(D[2], s0.re, s1.re, s0.im, s1.im, ca.z, ca.w);
      mma_hf(D[4], s0.re, s1.re, s0.im, s1.im, cb.x, cb.y);
      mma_hf(D[1], s2.re, s3.re, s2.im, s3.im, ca.x, ca.y);
      mma_hf(D[3], s2.re, s3.re, s2.im, s3.im, ca.z, ca.w);
    }
    TS(3);
    const u32 xa = (w < 8 ? SM_MODS + (4 + ksig) * KTAB : SM_ZS) + lane * 16;
    if (khf) {
      __syncwarp();
#pragma unroll
      for (int j = 0; j < 5; j++) sts128(xa + 512 * j, fu(D[j][0]), fu(D[j][1]), fu(D[j][2]), fu(D[j][3]));
      if (lane == 0) sts32(xa + 2560, fu(k2048));
      asm volatile("bar.arrive %0,64;" ::"r"(2 + ksig) : "memory");
    } else {
      const u32 t1 = tp + (q < 2 ? (128 + 4 * g + 2 * q) * 4 : T3 * 4 + ((32 * q - 64 + g) ^ 1) * 2);
      const u32 x = 16 * q + (g >> 1) + hi + 1, tb = tp + (hi ? T7E : T9E) * 4 - 4;
      const u32 te = tb + (x + 2 * (x & 1)) * 2, to = tb + TEO * 4 + (x ^ 1) * 2;
      asm volatile("bar.sync %0,64;" ::"r"(2 + ksig) : "memory");
#pragma unroll
      for (int j = 0; j < 5; j++) { const uint4 t = lds128(xa + 512 * j); D[j][0] += uf(t.x); D[j][1] += uf(t.y); D[j][2] += uf(t.z); D[j][3] += uf(t.w); }
      k2048 = (k2048 + uf(lds32(xa + 2560))) * 0.125f;
#pragma unroll
      for (int r = 0; r < 4; r++) {
        const u32 v = pk_hf(D[2 + (r >> 1)][2 * (r & 1)], D[2 + (r >> 1)][2 * (r & 1) + 1]);
        if (q < 2) {
          const u32 vv = __byte_perm(v, v, 0x1010);
          sts32(t1 + (TO + 32 * r) * 4, vv); sts16(t1 + (TO + 32 * r + 1) * 4 + 2, v >> 16); sts16(t1 + (TO + 32 * r - 1) * 4, v);
          sts64(t1 + (TE + 32 * r) * 4, vv, __byte_perm(v, v, 0x1032));
        } else {
          sts16(t1 + 16 * r, v >> 16);
          if (r == 0 && lane == 2) {
            const u32 vv = __byte_perm(v, v, 0x1010);
            sts32(tp + (TO + 256) * 4, vv); sts16(tp + (TO + 257) * 4 + 2, v); sts16(tp + (TO + 255) * 4, v); sts64(tp + (TE + 256) * 4, vv, vv);
          } else sts16(t1 + 16 * r - ((T3 - T5) * 4 + 6) + 8 * hi, v);
        }
      }
#pragma unroll
      for (int r = 0; r < 2; r++) {
        const u32 v = pk_hf(D[4][2 * r], D[4][2 * r + 1]);
        if (r == 0 && lane == 0) { sts16(tp + T5 * 4 + 62 * 2, v); sts32(SM_KV + 4 * ksig, v & 0xffff); sts16(tp + (T9E + TEO) * 4 + 62 * 2, pk_hf(k2048, 0.f)); }
        else { sts16(te + 8 * r, v); sts16(to + 8 * r, v); }
        sts16(te + 8 * r + 16, v >> 16); sts16(to + 8 * r + 16, v >> 16);
      }
      __syncwarp();
#pragma unroll
      for (int r = 0; r < 4; r++) {
        const u32 v = pk_hf(D[r >> 1][2 * (r & 1) + 1], D[r >> 1][2 * (r & 1)]), t2 = tp + lane * 4 + 128 * r;
        sts32(t2 + TO * 4, v); sts16(t2 + TE * 4, v >> 16); sts16(t2 + (TE + 1) * 4 + 2, v);
      }
      __syncwarp();
    }
  } else if (w == (b < 108 ? 11 : ~0u)) {
    float c[4][4] = {};
    u32 aa = SM_UP + ((lane & 7) + 8 * (lane >> 4)) * 64 + ((((lane >> 3) & 1) ^ ((lane & 7) >> 1)) << 4);
    u32 ba = SM_SIL + (lane >> 3) * 16;
    uint4 a[2][10];
#define GLD(n) { _Pragma("unroll") for (int i = 0; i < 2; i++) { a[n][5 * i] = ldsm4(ba + i * 64); \
      _Pragma("unroll") for (int k = 0; k < 4; k++) a[n][5 * i + 1 + k] = ldsm4t((k & 2 ? aa ^ 32 : aa) + i * 2048 + (k & 1) * 1024); } aa += 4096; ba += 128; }
#define GMM(n) { _Pragma("unroll") for (int i = 0; i < 2; i++) _Pragma("unroll") for (int k = 0; k < 4; k++) { const uint4 f = a[n][5 * i + 1 + k], bb = a[n][5 * i]; \
      mma_bf(c[k], f.x, f.y, f.z, f.w, k & 1 ? bb.z : bb.x, k & 1 ? bb.w : bb.y); } }
    mb_wait(SM_MB);
    TS(56);
    GLD(0);
#pragma unroll 1
    for (int s = 0; s < 4; s++) { GLD(1); GMM(0); GLD(0); GMM(1); }
    GMM(0);
    const float v0 = (q & 1) ? c[0][2] + c[1][2] : c[0][0] + c[1][0], v1 = (q & 1) ? c[2][2] + c[3][2] : c[2][0] + c[3][0];
    str16(gs + (G_MOD + b * 128 + 2 * g + 16 * q), pk_bf(rbf((q & 2) ? v1 : v0) * F2M64, 0.f) | (g < 2 ? pm : 0));
    TS(57);
  }
  TS(6);
  u32 tid2 = tid;
  if (w < 4) {
    asm volatile("setmaxnreg.inc.sync.aligned.u32 232;");
    const u32 tid = tid2 + p.zero, w = tid >> 5, lane = tid & 31, g = lane >> 2, q = lane & 3, hi = g & 1, zr = tid >> 16, tp = SM_TAP + w * TAPS;
    const u32 pml = opq((g & 3) ? 0 : pm);
    const u32 tr = tp + ((hi ? TO : TE) + (g >> 1) - q) * 4;
    u32 T[33][4], B5[5][2], B3[5][2];
#pragma unroll
    for (int d = 0; d < 33; d++) {
      T[d][0] = lds32(tr + 32 * d); T[d][1] = lds32(tr + 32 * d + 16);
      T[d][2] = cpy(d ? T[d - 1][1] : zr, zr, 0); T[d][3] = cpy(T[d][0], zr, 1);
    }
    const u32 t33 = cpy(T[32][1], zr, 0), z33 = cpy(zr, zr, 0);
    if (TPIN) {
#pragma unroll
      for (int d = 0; d < 33; d++) asm volatile("{.reg .pred p; setp.ne.u32 p,%2,0; @p st.shared.v2.u32 [%2],{%0,%1};}" ::"r"(T[d][2]), "r"(T[d][3]), "r"(zr) : "memory");
    }
    const u32 bt = tp + (T5 + g - q) * 4;
#pragma unroll
    for (int d = 0; d < 5; d++) {
      B5[d][0] = lds32(bt + 32 * d); B5[d][1] = lds32(bt + 32 * d - 16);
      B3[d][0] = lds32(bt + 32 * d + (T3 - T5) * 4); B3[d][1] = lds32(bt + 32 * d - 16 + (T3 - T5) * 4);
    }
    u32 za = opq(SM_ZS + 16 + w * ZSS + ((lane >> 3) & 1) * ZPS + ((lane & 7) + (lane >> 4)) * 16);
    u32 wa = opq(SM_W + W5O + w * WSL + row16(lane));
    u32 sa = opq(SM_W + W9O - (SPL ? 0 : 2048) + w * WSL + lane * 16);
    const u32 yo = opq(p.glo + G_Y - 1024 + b * BLK + 256 * q + w * 32 + 4 * g);
    char* yp = gptr(p, yo);
#define YINC() asm volatile("{.reg .u32 l, h; mov.b64 {l,h},%0; add.u32 l,l,1024; mov.b64 %0,{l,h};}" : "+l"(yp))
    const u32 fa = opq(SM_SC + 16 * w + 8), bw = opq((BW >> 4 * w) & 15), bs = opq((BS >> 4 * w) & 15);
    if (TPIN) asm volatile("{.reg .pred p; setp.ne.u32 p,%8,0; @p st.shared.v4.u32 [%8],{%0,%1,%2,%3}; @p st.shared.v4.u32 [%8],{%4,%5,%6,%7};}"
                           ::"r"(za), "r"(wa), "r"(sa), "r"(yo), "r"(fa), "r"(bw), "r"(bs), "r"(pml), "r"(zr) : "memory");
    TS(8);
    u32 F;
    bsync(9, 384);
    TS(11);
    float A[4][4] = {};
    uint4 Z[4];
    Z[0] = ldsm4(za); Z[1] = ldsm4(za + 32);
#define STEP(s, b0, b1) { _Pragma("unroll") for (int i = 0; i < 4; i++) mma_hf_t(A[i], T[8 * i + 7 - (s)], b0, b1); }
#define PAIR(n) { Z[(n + 2) & 3] = ldsm4(za + 32 * (n + 2)); STEP(2 * n, Z[n].x, Z[n].y); STEP(2 * n + 1, Z[n].z, Z[n].w); }
#define LAST(N) mma8_hf(N, t33, z33, Z[3].y); float O[4]; mma_hf_o(O, A[0], T[0], Z[3].z, Z[3].w); \
    _Pragma("unroll") for (int i = 0; i < 3; i++) mma_hf_o(A[i], A[i + 1], T[8 * i + 8], Z[3].z, Z[3].w); \
    mma_hf_o(A[3], N, T[32], Z[3].z, Z[3].w);
#pragma unroll 1
    for (int j = 0; j < 4; j++) {
      PAIR(0);
      uint2 fc;
      asm volatile("ld.volatile.shared.v2.u32 {%0,%1},[%2];" : "=r"(fc.x), "=r"(fc.y) : "r"(fa));
      PAIR(1);
      F = __byte_perm(fu(uf(fc.x) * uf(fc.y)), 0, 0x3232);
      PAIR(2);
      Z[1] = ldsm4(za + 160); STEP(6, Z[3].x, Z[3].y);
      float N[4] = {};
      LAST(N);
      if (INCV) inc<128>(za);
      YINC();
      y_store<128>(O[0], O[1], O[2], O[3], F, pml, yp);
      if (!INCV) za += 128;
      TSJ(j);
    }
    bsyncr(bw);
    uint4 a5;
    if (A5P) a5 = ldsm4t(wa);
#pragma unroll
    for (int half = 0; half < (SPL ? 2 : 1); half++) {
    if (half) bsyncr(bs);
#pragma unroll 1
    for (int j = half ? 8 : 4; j < (SPL && !half ? 8 : 13); j++) {
      if (!SPL && j == 8) bsyncr(bs);
      if (!A5P) a5 = ldsm4t(wa);
      const uint4 a3 = ldsm4t(wa + (W3O - W5O));
      uint4 s3 = {0, 0, 0, 0};
      if (SPL ? half : j >= 8) s3 = lds128(sa);
      PAIR(0);
      float N[4] = {};
#pragma unroll
      for (int i = 0; i < 4; i++) mma_hf(A[i], a5.x, a5.y, a5.z, a5.w, B5[i][0], B5[i][1]);
      mma_hf(N, a5.x, a5.y, a5.z, a5.w, B5[4][0], B5[4][1]);
      if (INCV) asm volatile("{add.u32 %0,%0,256; xor.b32 %0,%0,32;}" : "+r"(wa)); else wa = (wa + 256) ^ 32;
      if (A5P) a5 = ldsm4t(wa);
      PAIR(1);
#pragma unroll
      for (int i = 0; i < 4; i++) mma_hf(A[i], a3.x, a3.y, a3.z, a3.w, B3[i][0], B3[i][1]);
      mma_hf(N, a3.x, a3.y, a3.z, a3.w, B3[4][0], B3[4][1]);
      PAIR(2);
      Z[1] = ldsm4(za + 160); STEP(6, Z[3].x, Z[3].y);
      LAST(N);
      if (INCV) { inc<128>(za); if (!SPL || half) inc<512>(sa); }
      YINC();
      if (SPL && !half) y_store<128>(O[0], O[1], O[2], O[3], F, pml, yp);
      else y_store<128>(O[0] + uf(s3.x), O[1] + uf(s3.y), O[2] + uf(s3.z), O[3] + uf(s3.w), F, pml, yp);
      if (!INCV) { za += 128; if (!SPL || half) sa += 512; }
      TSJ(j);
    }
    }
    {
      asm volatile("mov.u32 %0,%%tid.x;" : "=r"(tid2));
      const uint4 s3 = lds128(sa), s4 = lds128(sa + 512), s5 = lds128(sa + 1024);
      float X[3][4] = {{uf(s4.x), uf(s4.y), uf(s4.z), uf(s4.w)}, {}, {uf(s5.x), uf(s5.y), uf(s5.z), uf(s5.w)}};
#pragma unroll
      for (int ty = 0; ty < 2; ty++) {
        const uint4 a = A5P && !ty ? a5 : ldsm4t(wa + ty * (W3O - W5O)), c = ldsm4t((wa ^ 32) + 256 + ty * (W3O - W5O)), d = ldsm4t(wa + 512 + ty * (W3O - W5O));
#pragma unroll
        for (int i = 0; i < 3; i++) mma_hf(A[i], a.x, a.y, a.z, a.w, ty ? B3[i][0] : B5[i][0], ty ? B3[i][1] : B5[i][1]);
#pragma unroll
        for (int i = 0; i < 2; i++) mma_hf(X[i], c.x, c.y, c.z, c.w, ty ? B3[i][0] : B5[i][0], ty ? B3[i][1] : B5[i][1]);
        mma_hf(X[2], d.x, d.y, d.z, d.w, ty ? B3[0][0] : B5[0][0], ty ? B3[0][1] : B5[0][1]);
      }
#pragma unroll
      for (int n = 0; n < 4; n++) {
        const uint4 f0 = n < 2 ? Z[n] : ldsm4(za + 32 * n), f1 = ldsm4(za + 32 * n + 128), f2 = ldsm4(za + 32 * n + 256);
#pragma unroll
        for (int s = 2 * n; s < 2 * n + 2; s++) {
#pragma unroll
          for (int i = 0; i < 3; i++) mma_hf_t(A[i], T[8 * i + 7 - s], s & 1 ? f0.z : f0.x, s & 1 ? f0.w : f0.y);
          mma_hf_t(X[0], T[7 - s], s & 1 ? f1.z : f1.x, s & 1 ? f1.w : f1.y); mma_hf_t(X[1], T[15 - s], s & 1 ? f1.z : f1.x, s & 1 ? f1.w : f1.y);
          mma_hf_t(X[2], T[7 - s], s & 1 ? f2.z : f2.x, s & 1 ? f2.w : f2.y);
        }
      }
      y_store<128>(A[0][0] + uf(s3.x), A[0][1] + uf(s3.y), A[0][2] + uf(s3.z), A[0][3] + uf(s3.w), F, pml, yp + 1024);
      y_store<128>(A[1][0] + X[0][0], A[1][1] + X[0][1], A[1][2] + X[0][2], A[1][3] + X[0][3], F, pml, yp + 2048);
      y_store<128>(A[2][0] + X[1][0] + X[2][0], A[2][1] + X[1][1] + X[2][1], A[2][2] + X[1][2] + X[2][2], A[2][3] + X[1][3] + X[2][3], F, pml, yp + 3072);
    }
    barrive(12, N12);
    TS(15);
  } else {
    asm volatile("setmaxnreg.dec.sync.aligned.u32 136;");
    const u32 t8 = tid - 128, pml = (g & 3) ? 0 : pm;
    {
      TS(12);
      if (PFG == 1 && tid == 288) l2_pre<WSH / 2>(p.wg + (b * WSH + WSH / 2));
      const char* zs = gs + ((16 * w - 64 + (lane >> 3)) * BLK + b * 128 + ((lane & 7) * 16 ^ rho * 64));
      const char* zs4 = gs + ((t8 >> 1) * BLK + (Ps >> 4) * 512 + (Ps & 6) * 64 + ((Ps >> 2 ^ Ps) & 2) * 32 + (Ps & 1) * 32 + (t8 & 1) * 16);
      uint4 v[5];
      v[4].x = INVAL;
      if (ZD) wait_clk(t0, ZD);
      const u32 d = lane < 4 ? chan(b, lane) : Ps;
      const char* mp = gs + (G_MOD + (d >> 5) * 128 + (d & 24) * 2);
      uint4 ta, tc;
      ta.x = tc.x = INVAL;
      const u32 t9 = w == 9 ? pm : INVAL;
      pin2(zr, zs, zs4);
      conv();
      POLLM({ rld128<TAGM>(ta, mp, t9); rld128<TAGM>(tc, mp + MODJ, t9); rld128<TAGM>(v[4], zs4, pm); }, lop3<0xbe>(v[4].x, pm, ne3(ta.x, tc.x, t9)), TAGM, 1);
      TS(58);
#pragma unroll
      for (int j = 0; j < 4; j++) v[j] = ldr128(zs + j * 4 * BLK);
      if (w == 9) {
        const u32 aw = (d & 4) ? ((d & 2) ? ta.w : ta.z) : ((d & 2) ? ta.y : ta.x & ~TAGM);
        const u32 cw = (d & 4) ? ((d & 2) ? tc.w : tc.z) : ((d & 2) ? tc.y : tc.x & ~TAGM);
        const float sa = ((d & 1) ? bhi(aw) : blo(aw)) * F2P64, c1 = rbf(fmaf((d & 1) ? bhi(cw) : blo(cw), F2P64, 1.f));
        const u32 EM = min(max(fu(fmaxf(32.f * fabsf(c1), fabsf(sa))) >> 23, 80u), 250u);
        const float inv = uf((264 - EM) << 23);
        if (lane < 5) { sts64(SM_SC + 16 * lane, pk_hf(16.f * c1 * inv, 16.f * c1 * inv), pk_hf(sa * inv, sa * inv)); sts32(SM_SC + 16 * lane + 8, (EM - 74) << 23); }
        TS(10);
      }
#define MARKERS() if (tid == 256) { \
        _Pragma("unroll") for (int i = MT / 2; i < 8; i++) bulk_out<2048>(gs + (G_Y + 2048 * i + b * BLK), SM_INV); \
        bulk_out<2048>(gs + (G_PART + b * 2048), SM_INV); bulk_out<512>(gs + (G_ACT + b * 512), SM_INV); \
        bulk_out<32>(gs + (G_KEY + b * KST), SM_INV); if (!rho) bulk_out<128>(gs + (G_ACT + Ps * 128), SM_INV); \
        asm volatile("cp.async.bulk.commit_group;" ::: "memory"); }
#define GATE() { mb_expect(SM_MB + 8, rho ? SLV : 46080); \
        _Pragma("unroll") for (int i = GE; i < 3; i++) tma3d(SM_GATE + 12288 * i, &tm_gate, SM_MB + 8, 32 * b, i); \
        if (!rho) tma3d(SM_GATE + SLV, &tm_gs, SM_MB + 8, 4096 + 4 * b, 0); }
#define UP() { mb_expect(SM_MB + 16, rho ? SLV : 46080); tma3d(SM_UP, &tm_up, SM_MB + 16, 32 * b, 0); \
        if (!rho) tma3d(SM_UP + SLV, &tm_us, SM_MB + 16, 4096 + 4 * b, 0); }
      if (PFU == 2 && tid == 256) l2_pre<WSH>(p.wu + b * WSH);
      if (GE && tid == 256) {
        asm volatile("cp.async.bulk.wait_group.read 0;" ::: "memory");
#pragma unroll
        for (int i = 0; i < GE; i++) tma3d(SM_GATE + 12288 * i, &tm_gate, SM_MB + 8, 32 * b, i);
      }
      if (PFG == 2 && tid == 256) l2_pre<WSH>(p.wg + b * WSH);
      if (PFG == 3 && tid == 256) l2_pre<WSH / 2>(p.wg + (b * WSH + WSH / 2));
      bsync(8, 256);
      const uint2 cc = lds64(SM_SC + 8 * (t8 & 6)), c4 = lds64(SM_SC + 64);
      sts128(SM_Z4 + 256 + (t8 & 1) * ZP4 + (t8 >> 1) * 16, hfma(v[4].x & ~TAGM, c4.x, c4.y), hfma(v[4].y, c4.x, c4.y), hfma(v[4].z, c4.x, c4.y), hfma(v[4].w, c4.x, c4.y));
      if (t8 < 96) sts128(t8 < 64 ? SM_ZS + (t8 & 7) * ZPS + (t8 >> 3) * 16 : SM_Z4 + (t8 & 1) * ZP4 + (t8 & 30) * 8, 0, 0, 0, 0);
      asm volatile("cp.async.bulk.wait_group.read 0;" ::: "memory");
      const u32 dst = SM_ZS + 128 + (t8 & 7) * ZPS + (16 * w - 64 + (lane >> 3)) * 16;
      pin(zr, dst);
      conv();
      POLLS(_Pragma("unroll") for (int j = 0; j < 4; j++) sts128(dst + j * 64, hfma(v[j].x & ~TAGM, cc.x, cc.y), hfma(v[j].y, cc.x, cc.y), hfma(v[j].z, cc.x, cc.y), hfma(v[j].w, cc.x, cc.y)),
            _Pragma("unroll") for (int j = 0; j < 4; j++) rld128<TAGM>(v[j], zs + j * 4 * BLK, pm), ne3(v[0].x, v[1].x, pm) | ne3(v[2].x, v[3].x, pm), TAGM, 1);
      TS(9);
      bsync(9, 384);
      TS(11);
      if (MKT == 1) MARKERS();
      if (w == 10 && s2u(smem) != SM0) __trap();
      const bool lng = w < 8 || w == 9;
      const u32 ts = lane + 32 * (w == 8 ? 0 : w - 9), c = min(ts, 71u), ma = SM_MODS + 16 * c;
      const u32 sig = lng ? ksig : ts >> 4, l2 = lng ? lane : 32 + (ts & 15);
      const char* mq = gs + (G_MOD + (c >> 2) * 128 + (c & 3) * 16);
      if (!lng) {
#pragma unroll
        for (int j = 0; j < 6; j++) cpa16(ma + 1152 * j, mq + j * MODJ);
        cpa16(ma + 1152 * 6, p.dsk + 16 * c); cpa16(ma + 1152 * 7, p.wr + 16 * c);
        if (PFU == 3) {
#pragma unroll
          for (int j = 0; j < 4; j++) if (ts < 81) l2_line(p.wu + (b * WSH + (81 * j + ts) * 128));
        }
        if (tid == 352) {
          PROXY_FENCE();
          if (PFU == 1) l2_pre<WSH>(p.wu + b * WSH);
          if (!TG) GATE();
          if (!TU) UP();
        }
      }
      const u32 wb = SM_W + sig * WSL;
      if (sig < 5) {
        const u32 za = (sig < 4 ? SM_ZS + 128 + sig * ZSS : SM_Z4 + 256) + l2 * 32, zb = za + (sig < 4 ? ZPS : ZP4);
        const uint4 c0 = lds128(zb - 32), c1 = lds128(za - 16), c2 = lds128(zb - 16), c3 = lds128(za), c4 = lds128(zb), c5 = lds128(za + 16), c6 = lds128(zb + 16);
        const u32 P[25] = {c0.z, c0.w, c1.x, c1.y, c1.z, c1.w, c2.x, c2.y, c2.z, c2.w, c3.x, c3.y, c3.z, c3.w, c4.x, c4.y, c4.z, c4.w, c5.x, c5.y, c5.z, c5.w, c6.x, c6.y, c6.z};
        u32 Q[25], D1[24], F4[23], W5[21], W3[17];
#pragma unroll
        for (int j = 1; j < 25; j++) Q[j] = __byte_perm(P[j - 1], P[j], 0x5432);
#pragma unroll
        for (int j = 1; j < 24; j++) D1[j] = hadd(P[j], Q[j]);
#pragma unroll
        for (int j = 2; j < 23; j++) F4[j] = hadd(D1[j], D1[j - 1]);
#pragma unroll
        for (int n = 0; n < 21; n++) W5[n] = hadd(F4[n + 2], P[n]);
#pragma unroll
        for (int n = 0; n < 17; n++) W3[n] = hadd(Q[n + 8], D1[n + 7]);
        const u32 a0 = wb + W5O + 64 * l2 + 16 * ((l2 >> 1) & 3);
#pragma unroll
        for (int i = 0; i < 4; i++) {
          sts128(a0 ^ (16 * i), W5[4 * i + 5], W5[4 * i + 6], W5[4 * i + 7], W5[4 * i + 8]);
          sts128((a0 ^ (16 * i)) + (W3O - W5O), W3[4 * i + 1], W3[4 * i + 2], W3[4 * i + 3], W3[4 * i + 4]);
        }
        if (lng) {
          if (lane < 16) sts128(wb + (lane & 7) * 16 + (lane & 8) * 400, 0, 0, 0, 0);
          const u32 a1 = wb + 32 * lane + 16 * ((lane >> 2) & 1);
#pragma unroll
          for (int i = 0; i < 4; i++) {
            const u32 a = (a1 ^ (16 * (i >> 1))) + 1024 * (i & 1), n = 4 * i;
            sts128(a + V2O, hadd(Q[n + 9], P[n + 8]), hadd(Q[n + 10], P[n + 9]), hadd(Q[n + 11], P[n + 10]), hadd(Q[n + 12], P[n + 11]));
            sts128(a + W9O, hadd(F4[n + 4], W5[n]), hadd(F4[n + 5], W5[n + 1]), hadd(F4[n + 6], W5[n + 2]), hadd(F4[n + 7], W5[n + 3]));
            sts128(a + W7O, hadd(F4[n + 6], W3[n]), hadd(F4[n + 7], W3[n + 1]), hadd(F4[n + 8], W3[n + 2]), hadd(F4[n + 9], W3[n + 3]));
          }
        }
      }
      if (w < 8) barriver((BW >> (4 * w - 16)) & 15);
      else if (!(w & 1)) { barriver((BW >> (4 * w - 32)) & 15); barriver((BW >> (4 * w - 28)) & 15); }
      __syncwarp();
      TS(32);
      if (lng) {
        const u32 wa = wb + ((lane >> 3) & 1) * 1024 + (((lane & 7) ^ (lane >> 4)) + 8 * (lane >> 4)) * 16;
        const u32 kv = lds32(SM_KV + 4 * sig), bi = (g >> 1) == q ? (hi ? kv << 16 : kv) : 0u;
        float acc[8][4] = {};
#pragma unroll
        for (int j = 0; j < 4; j++) { const uint4 a = ldsm4t(wa + V2O + j * 256); mma8_hf(acc[2 * j], a.x, a.y, bi); mma8_hf(acc[2 * j + 1], a.z, a.w, bi); }
        u32 bt = tp + (T9E + hi * TEO + (g >> 1) - q) * 4, wt = wa + W9O;
#pragma unroll 1
        for (int ty = 0; ty < 2; ty++) {
          uint4 a[4];
#pragma unroll
          for (int be = 0; be < 4; be++) a[be] = ldsm4t(wt + be * 256);
          u32 b1 = lds32(bt - 16);
#pragma unroll
          for (int d = 0; d < 8; d++) {
            const u32 b0 = lds32(bt + 16 * d);
#pragma unroll
            for (int be = 0; be < 4; be++) if (d + 2 * be < 8) mma_hf(acc[d + 2 * be], a[be].x, a[be].y, a[be].z, a[be].w, b0, b1);
            b1 = b0;
          }
          bt += (T7E - T9E) * 4; wt += W7O - W9O;
        }
        __syncwarp();
#pragma unroll
        for (int j = 0; j < 8; j++) sts128(wb + W9O + j * 512 + lane * 16, fu(acc[j][0]), fu(acc[j][1]), fu(acc[j][2]), fu(acc[j][3]));
        if (w != 9) barriver((BS >> (4 * w - 16)) & 15);
        TS(34);
      }
      if (!lng) {
        asm volatile("cp.async.wait_all;" ::: "memory");
        uint4 md[6];
#pragma unroll
        for (int j = 0; j < 6; j++) md[j] = lds128(ma + 1152 * j);
        const uint4 dk = lds128(ma + 1152 * 6), wr = lds128(ma + 1152 * 7);
        POLLW(_Pragma("unroll") for (int j = 0; j < 6; j++) md[j] = ldr128(mq + j * MODJ),
              ((md[0].x ^ pm) | (md[1].x ^ pm) | (md[2].x ^ pm) | (md[3].x ^ pm) | (md[4].x ^ pm) | (md[5].x ^ pm)) & TAGM, 4);
#pragma unroll
        for (int j = 0; j < 6; j++) {
          const u32 o = (j % 3 == 1) ? BONE : 0x80008000u;
          md[j] = make_uint4(bfma(md[j].x & ~TAGM, B2P64, o), bfma(md[j].y, B2P64, o), bfma(md[j].z, B2P64, o), bfma(md[j].w, B2P64, o));
          if (j > 2) sts128(ma + 1152 * j, md[j].x, md[j].y, md[j].z, md[j].w);
        }
        const uint4 gd = make_uint4(bmul(md[2].x, dk.x), bmul(md[2].y, dk.y), bmul(md[2].z, dk.z), bmul(md[2].w, dk.w));
#pragma unroll
        for (int j = 0; j < 2; j++) sts128(ma + 1152 * j, bmul(md[j].x, gd.x), bmul(md[j].y, gd.y), bmul(md[j].z, gd.z), bmul(md[j].w, gd.w));
        sts128(ma + 2304, bmul(md[2].x, B2P64), bmul(md[2].y, B2P64), bmul(md[2].z, B2P64), bmul(md[2].w, B2P64));
        const uint4 H = make_uint4(bmul(md[4].x, wr.x), bmul(md[4].y, wr.y), bmul(md[4].z, wr.z), bmul(md[4].w, wr.w));
        sts128(ma + 1152 * 7, H.x, H.y, H.z, H.w);
        sts128(ma + 1152 * 8, bfma(md[4].x, wr.x, H.x ^ 0x80008000u), bfma(md[4].y, wr.y, H.y ^ 0x80008000u), bfma(md[4].z, wr.z, H.z ^ 0x80008000u), bfma(md[4].w, wr.w, H.w ^ 0x80008000u));
        float c4[4] = {};
        mma_bf(c4, md[4].x, md[3].x, md[4].y, md[3].y, wr.x, wr.y); mma_bf(c4, md[4].z, md[3].z, md[4].w, md[3].w, wr.z, wr.w);
        if (q == g >> 1) sts64(SM_RC + (ts >> 2) * 8, fu(hi ? c4[1] : c4[0]), fu(hi ? c4[3] : c4[2]));
        if (ts < 2) sts128(SM_ONE + 16 * ts, ts ? 0 : BONE, ts ? 0 : BONE, ts ? 0 : BONE, ts ? 0 : BONE);
        TS(14);
        if (MKT == 2) MARKERS();
        if (w == 8) asm volatile("cp.async.bulk.wait_group 0;" ::: "memory");
        if (PFW == 2) {
#pragma unroll
          for (int j = 0; j < 4; j++) if (ts < 81) l2_line(p.wd + (b * WSH + (81 * j + ts) * 128));
        }
        bsync(13, 96);
        if (w == 8) { barriver(2); barriver(3); barriver(5); barriver(6); if (HLP) barrive(7, 64); }
      }
      if (!HLP) { if (w >= 8) barrive(11, 256); }
      else if (w == 9) barrive(11, 128);
    }
    const u32 jw = w < 6 ? w ^ 1 : w < 8 ? w : max(w - 4, 5u);
    const int u0 = 4 * (jw - 4) + 2 * rho;
    const u32 t4 = SM_TAP + 4 * TAPS, s3a = SM_W + 4 * WSL + (u0 >= 8 ? W9O + (u0 - 8) * 512 : V2O) + lane * 16, hb = (0x4987 >> (4 * jw - 16)) & 15;
#define FARL() { u32 wa = (SM_W + 4 * WSL + W5O + row16(lane) + (u0 - 3) * 256) ^ 32, bt = t4 + (T5 + g - q) * 4; \
      _Pragma("unroll 1") for (int al = min(u0 - 2, 6); al > 0; al--) { \
        _Pragma("unroll") for (int ty = 0; ty < 2; ty++) { \
          const uint4 a = ldsm4t(wa + ty * (W3O - W5O)); \
          const u32 bb = bt + ty * (T3 - T5) * 4; \
          mma_hf(acc[ty], a.x, a.y, a.z, a.w, lds32(bb - 32), lds32(bb - 48)); \
          mma_hf(acc[2 + ty], a.x, a.y, a.z, a.w, lds32(bb), lds32(bb - 16)); \
        } \
        wa = (wa - 256) ^ 32; bt += 32; } }
    if (w < 8) {
      u32 tr = t4 + ((hi ? TO : TE) + (g >> 1) - q) * 4;
      u32 zb = SM_Z4 + 256 + ((lane >> 3) & 1) * ZP4 + u0 * 128 + (lane & 7) * 16 + (lane >> 4) * 128;
      float acc[4][4] = {};
      u32 prev = 0;
#pragma unroll 1
      for (int it = min(u0 + 2, 4); it; it--) {
#pragma unroll
        for (int s = 0; s < 8; s++) {
          const uint4 z = ldsm4(zb - 16 * s);
          const u32 t0 = lds32(tr + 32 * s), t1 = lds32(tr + 32 * s + 16);
          mma_hf(acc[s & 1], t0, t1, prev, t0, z.x, z.y);
          mma_hf(acc[2 + (s & 1)], t0, t1, prev, t0, z.z, z.w);
          prev = t1;
        }
        zb -= 128; tr += 256;
      }
      {
        const uint4 z = ldsm4(zb); const u32 t0 = lds32(tr), t1 = lds32(tr + 16);
        mma_hf(acc[0], t0, t1, prev, t0, z.x, z.y); mma_hf(acc[2], t0, t1, prev, t0, z.z, z.w);
        if (jw > 4) { const uint4 y = ldsm4(zb - 16); mma8_hf(acc[1], t1, zr, y.y); mma8_hf(acc[3], t1, zr, y.w); }
      }
      if (!HLP) { bsync(11, 256); FARL(); }
      else asm volatile("bar.sync %0,64;" ::"r"(hb) : "memory");
      TS(35);
      const uint2 fc = lds64(SM_SC + 16 * 4 + 8);
      const u32 F = __byte_perm(fu(uf(fc.x) * uf(fc.y)), 0, 0x3232);
      char* yp = gs + (G_Y + 16384 + (32 * jw - 128 + 16 * rho + 4 * (q >> 1) + ((b >> 2) & 3)) * BLK + (q & 1) * 1024 + (b & 112) * 4 + (b & 2) * 16 + 4 * g);
#pragma unroll
      for (int j = 0; j < 2; j++) {
        uint4 s3 = {0, 0, 0, 0};
        if (u0 >= (HLP ? 4 : 8)) s3 = lds128(s3a + j * 512);
        y_store<512>(acc[2 * j][0] + acc[2 * j + 1][0] + uf(s3.x), acc[2 * j][1] + acc[2 * j + 1][1] + uf(s3.y), acc[2 * j][2] + acc[2 * j + 1][2] + uf(s3.z),
                acc[2 * j][3] + acc[2 * j + 1][3] + uf(s3.w), F, pml, yp + j * 8 * BLK);
      }
      TS(16);
    } else {
      if (HLP && w != 9) {
        bsync(11, 128);
        if (HD) wait_clk(clk(), HD);
        float acc[4][4] = {};
        if (u0 >= 8) {
#pragma unroll
          for (int j = 0; j < 2; j++) { const uint4 t = lds128(s3a + j * 512); acc[2 * j][0] = uf(t.x); acc[2 * j][1] = uf(t.y); acc[2 * j][2] = uf(t.z); acc[2 * j][3] = uf(t.w); }
        }
        FARL();
#pragma unroll
        for (int j = 0; j < 2; j++)
          sts128(s3a + j * 512, fu(acc[2 * j][0] + acc[2 * j + 1][0]), fu(acc[2 * j][1] + acc[2 * j + 1][1]), fu(acc[2 * j][2] + acc[2 * j + 1][2]), fu(acc[2 * j][3] + acc[2 * j + 1][3]));
        asm volatile("bar.arrive %0,64;" ::"r"(hb) : "memory");
        TS(16);
      }
      if (PFW == 3 && w == 9) {
#pragma unroll 1
        for (int j = 0; j < 12; j++) { if (lane < 27) l2_line(p.wd + (b * WSH + (27 * j + lane) * 128)); wait_clk(clk(), PFP); }
      }
      if (TG | TU | TW) {
        if (tid == 352) {
          if (TG) { wait_clk(t0, TG); GATE(); }
          if (TW < TU) { wait_clk(t0, TW); l2_pre<WSH>(p.wd + b * WSH); }
          if (TU) { wait_clk(t0, TU); UP(); }
          if (TW >= TU) { wait_clk(t0, TW); l2_pre<WSH>(p.wd + b * WSH); }
        }
      } else if (PFW < 2 && tid == 352) { mb_wait(SM_MB + 8); if (PFW) mb_wait(SM_MB + 16); l2_pre<WSH>(p.wd + b * WSH); }
      if (D0C && tid == 352 && b < 108) {
        mb_wait(SM_MB + 16);
        PROXY_FENCE();
        mb_expect(SM_MB + 24, 49152);
        tma3d(SM_TAP, &tm_down, SM_MB + 24, 64 * (b % 9), 4 * (b / 9));
      }
      TS(17);
    }
  }
  post_conv(p, &tm_down, tid2 + p.zero, b, b3);
  TSD();
}

typedef CUresult (*EncFn)(CUtensorMap*, CUtensorMapDataType, cuuint32_t, void*, const cuuint64_t*, const cuuint64_t*, const cuuint32_t*, const cuuint32_t*,
                          CUtensorMapInterleave, CUtensorMapSwizzle, CUtensorMapL2promotion, CUtensorMapFloatOOBfill);
static void make_map(EncFn enc, CUtensorMap* tm, void* ptr, int cols, int rows, int bw, int nb, CUtensorMapSwizzle sw, int gr = 192, int prom = 0) {
  cuuint64_t gd[3] = {(cuuint64_t)cols, (cuuint64_t)gr, (cuuint64_t)(rows / gr)}, gs[2] = {(cuuint64_t)cols * 2, (cuuint64_t)cols * 2 * gr};
  cuuint32_t bd[3] = {(cuuint32_t)bw, (cuuint32_t)gr, (cuuint32_t)nb}, es[3] = {1, 1, 1};
  enc(tm, CU_TENSOR_MAP_DATA_TYPE_BFLOAT16, 3, ptr, gd, gs, bd, es, CU_TENSOR_MAP_INTERLEAVE_NONE, sw, (CUtensorMapL2promotion)prom, CU_TENSOR_MAP_FLOAT_OOB_FILL_NONE);
}
extern "C" void kernel_launch(void* const* d_in, const int* in_sizes, int n_in, void* d_out, int out_size) {
  static EncFn enc = nullptr;
  static void* scratch = nullptr;
  if (!enc) {
    cudaGetSymbolAddress(&scratch, g_s);
    const uintptr_t last = (uintptr_t)scratch + G_END;
    if ((u32)last < G_END) scratch = (void*)(last - (u32)last);
    cudaDriverEntryPointQueryResult qr;
    cudaGetDriverEntryPoint("cuTensorMapEncodeTiled", (void**)&enc, cudaEnableDefault, &qr);
    cudaFuncSetAttribute(fused_kernel, cudaFuncAttributeMaxDynamicSharedMemorySize, SM_TOTAL);
  }
  CUtensorMap tm_mod, tm_gate, tm_gs, tm_up, tm_us, tm_down;
  make_map(enc, &tm_mod, d_in[13], 3456, 576, 32, 3, CU_TENSOR_MAP_SWIZZLE_64B, 192, PRM);
  make_map(enc, &tm_gate, d_in[9], 4608, 576, 32, 1, CU_TENSOR_MAP_SWIZZLE_64B, 192, PRG);
  make_map(enc, &tm_gs, d_in[9], 4608, 576, 8, 3, CU_TENSOR_MAP_SWIZZLE_NONE);
  make_map(enc, &tm_up, d_in[10], 4608, 576, 32, 3, CU_TENSOR_MAP_SWIZZLE_64B, 192, PRU);
  make_map(enc, &tm_us, d_in[10], 4608, 576, 8, 3, CU_TENSOR_MAP_SWIZZLE_NONE, 192, PRS);
  make_map(enc, &tm_down, d_in[11], 576, 4608, 64, 1, CU_TENSOR_MAP_SWIZZLE_128B, 96);
  Prm p;
  p.x = (const char*)d_in[0]; p.la = (const char*)d_in[1]; p.ai = (const char*)d_in[2]; p.cr = (const char*)d_in[3];
  p.ci = (const char*)d_in[4]; p.ldt = (const char*)d_in[5]; p.dsk = (const char*)d_in[6]; p.wr = (const char*)d_in[8];
  p.wg = (const char*)d_in[9]; p.wu = (const char*)d_in[10]; p.wd = (const char*)d_in[11];
  p.c = (const char*)d_in[12]; p.out = (char*)d_out; p.zero = 0; p.gs = (char*)scratch; p.glo = (u32)(uintptr_t)scratch; p.ghi = (u32)((uintptr_t)scratch >> 32);
  fused_kernel<<<128, 384, SM_TOTAL>>>(p, tm_mod, tm_gate, tm_gs, tm_up, tm_us, tm_down);
}
```

```cpp
#include <cuda_runtime.h>
#include <cuda.h>
#include <cuda_bf16.h>
#include <cuda_fp16.h>
#include <stdint.h>
#define FUSED 1
#define DEV __device__ __forceinline__
typedef uint32_t u32;

constexpr u32 BLK = 18432, G_Z = 0, G_Y = 128 * BLK, G_MOD = 2 * G_Y, G_KEY = G_MOD + 128 * 128, G_ACT = G_KEY + 128 * 128;
constexpr u32 G_PART = G_ACT + 576 * 128, G_EP = G_PART + 128 * 2048, G_END = G_EP + 128;
__device__ __align__(128) unsigned char g_s[2 * G_END];
#define TS(i)
#define TSJ(j)
#define TS0()
#define TSE()
#define TSD()
#define TSX 0
#define TSN(code, n)
#define ERRF(code)

constexpr int SM0 = 1024;
constexpr int ROW = 1168, SLV = 36864;
constexpr int SM_GATE = SM0, SM_UP = SM_GATE + 46080, SM_XST = SM_UP + 46080, SM_MODS = SM_XST + 16 * ROW, SM_W = SM_MODS + 11008;
constexpr int KTAB = 9216, WSL = 12544, W5O = 128, W3O = 3328, V2O = 6400, W9O = 8448, W7O = 10496;
constexpr int ZPS = 2192, ZSS = 2 * ZPS, ZP4 = 2368;
constexpr int SM_ZS = SM_W + 5 * WSL, SM_Z4 = SM_ZS + 4 * ZSS, SM_TAP = SM_Z4 + 2 * ZP4, TAPS = 3328;
constexpr int SM_MB = SM_TAP + 5 * TAPS;
constexpr int SM_SC = SM_MB + 48;
constexpr int SM_KV = SM_SC + 80;
constexpr int SM_THR = SM_KV + 32;
constexpr int SM_SLOT = SM_THR + 48;
constexpr int SM_KEY = SM_SLOT + 32;
constexpr int SM_ST = SM_KEY + 64;
constexpr int SM_ST2 = SM_ST + 256;
constexpr int SM_RC = SM_ST2 + 256;
constexpr int SM_SP = SM_RC + 192;
constexpr int SM_AF = SM_SP + 1152, SM_SIL = SM_AF + 1152, SM_INV = SM_SIL + 1152, SM_END = SM_SP + 5760;
constexpr int SM_ONE = SM_MODS + 9 * 1152;
constexpr int SM_WD = SM_W, SM_XS = SM_W + 36864, SM_AC = SM_ZS, SM_RED = SM_AC + 6144;
constexpr int SM_TSB = SM_END, SM_TOTAL = SM_END + TSX - SM0;
static_assert(SM_W % 1024 == 0 && SM_TAP % 1024 == 0 && SM_MODS + 8 * KTAB <= SM_ZS && SM_ZS + 2 * KTAB <= SM_TAP && SM_RED + 10240 <= SM_TAP && SM_XS + 8 * ROW <= SM_ZS, "smem map");
static_assert(SM_MB % 16 == 0 && SM_THR % 16 == 0 && SM_ST % 16 == 0 && SM_SP % 16 == 0 && SM_TOTAL <= 232448, "smem map");
constexpr int TE = 4, TO = 276, T5 = 560, T3 = 624, T9E = 680, T7E = 760, TEO = 40;
constexpr int DMOD = 1000, YD = 250, KD = 700, KDB = 520, KD1 = 50, PD = 900;
constexpr u32 MT = 10, KST = 32, KE = 64, YL = 104, NB8 = 8;
constexpr int N1 = 352, N12 = 288;
constexpr int SPIN = 1 << 16, NEARLY = 4;
constexpr u32 TAGM = 0x40004000u, TAGR = 0x40000000u, INVAL = 0x00004801u;

DEV u32 s2u(const void* p) { return (u32)__cvta_generic_to_shared(p); }
DEV void mma_bf(float (&c)[4], u32 a0, u32 a1, u32 a2, u32 a3, u32 b0, u32 b1) {
  asm("mma.sync.aligned.m16n8k16.row.col.f32.bf16.bf16.f32 {%0,%1,%2,%3},{%4,%5,%6,%7},{%8,%9},{%0,%1,%2,%3};"
      : "+f"(c[0]), "+f"(c[1]), "+f"(c[2]), "+f"(c[3]) : "r"(a0), "r"(a1), "r"(a2), "r"(a3), "r"(b0), "r"(b1));
}
DEV void mma_hf(float (&c)[4], u32 a0, u32 a1, u32 a2, u32 a3, u32 b0, u32 b1) {
  asm("mma.sync.aligned.m16n8k16.row.col.f32.f16.f16.f32 {%0,%1,%2,%3},{%4,%5,%6,%7},{%8,%9},{%0,%1,%2,%3};"
      : "+f"(c[0]), "+f"(c[1]), "+f"(c[2]), "+f"(c[3]) : "r"(a0), "r"(a1), "r"(a2), "r"(a3), "r"(b0), "r"(b1));
}
DEV void mma8_bf(float (&c)[4], u32 a0, u32 a1, u32 b0) {
  asm("mma.sync.aligned.m16n8k8.row.col.f32.bf16.bf16.f32 {%0,%1,%2,%3},{%4,%5},{%6},{%0,%1,%2,%3};"
      : "+f"(c[0]), "+f"(c[1]), "+f"(c[2]), "+f"(c[3]) : "r"(a0), "r"(a1), "r"(b0));
}
DEV void mma8_hf(float (&c)[4], u32 a0, u32 a1, u32 b0) {
  asm("mma.sync.aligned.m16n8k8.row.col.f32.f16.f16.f32 {%0,%1,%2,%3},{%4,%5},{%6},{%0,%1,%2,%3};"
      : "+f"(c[0]), "+f"(c[1]), "+f"(c[2]), "+f"(c[3]) : "r"(a0), "r"(a1), "r"(b0));
}
DEV u32 movm(u32 x) { u32 r; asm("movmatrix.sync.aligned.m8n8.trans.b16 %0,%1;" : "=r"(r) : "r"(x)); return r; }
DEV void conv() { asm volatile("{.reg .u32 t; mov.u32 t,0; movmatrix.sync.aligned.m8n8.trans.b16 t,t;}"); }
DEV uint4 ldsm4(u32 a) { uint4 r; asm volatile("ldmatrix.sync.aligned.m8n8.x4.shared.b16 {%0,%1,%2,%3},[%4];" : "=r"(r.x), "=r"(r.y), "=r"(r.z), "=r"(r.w) : "r"(a)); return r; }
DEV uint4 ldsm4t(u32 a) { uint4 r; asm volatile("ldmatrix.sync.aligned.m8n8.x4.trans.shared.b16 {%0,%1,%2,%3},[%4];" : "=r"(r.x), "=r"(r.y), "=r"(r.z), "=r"(r.w) : "r"(a)); return r; }
DEV u32 lds32(u32 a) { u32 r; asm volatile("ld.volatile.shared.u32 %0,[%1];" : "=r"(r) : "r"(a)); return r; }
DEV uint2 lds64(u32 a) { uint2 r; asm volatile("ld.shared.v2.u32 {%0,%1},[%2];" : "=r"(r.x), "=r"(r.y) : "r"(a)); return r; }
DEV uint4 lds128(u32 a) { uint4 r; asm volatile("ld.shared.v4.u32 {%0,%1,%2,%3},[%4];" : "=r"(r.x), "=r"(r.y), "=r"(r.z), "=r"(r.w) : "r"(a)); return r; }
DEV void sts16(u32 a, u32 v) { asm volatile("st.shared.u16 [%0],%1;" ::"r"(a), "h"((unsigned short)v) : "memory"); }
DEV void sts32(u32 a, u32 v) { asm volatile("st.shared.u32 [%0],%1;" ::"r"(a), "r"(v) : "memory"); }
DEV void sts64(u32 a, u32 x, u32 y) { asm volatile("st.shared.v2.u32 [%0],{%1,%2};" ::"r"(a), "r"(x), "r"(y) : "memory"); }
DEV void sts128(u32 a, u32 x, u32 y, u32 z, u32 w) { asm volatile("st.shared.v4.u32 [%0],{%1,%2,%3,%4};" ::"r"(a), "r"(x), "r"(y), "r"(z), "r"(w) : "memory"); }
DEV uint4 ldr128(const void* p) { uint4 v; asm volatile("ld.relaxed.gpu.global.v4.u32 {%0,%1,%2,%3},[%4];" : "=r"(v.x), "=r"(v.y), "=r"(v.z), "=r"(v.w) : "l"(p) : "memory"); return v; }
DEV uint2 ldr64(const void* p) { uint2 v; asm volatile("ld.relaxed.gpu.global.v2.u32 {%0,%1},[%2];" : "=r"(v.x), "=r"(v.y) : "l"(p) : "memory"); return v; }
DEV u32 ldr32(const void* p) { u32 v; asm volatile("ld.relaxed.gpu.global.u32 %0,[%1];" : "=r"(v) : "l"(p) : "memory"); return v; }
template <u32 M> DEV void rld128(uint4& v, const void* p, u32 tag) {
  asm volatile("{.reg .pred p; .reg .u32 t; lop3.b32 t,%0,%5,%6,0x28; setp.ne.u32 p,t,0; @p ld.relaxed.gpu.global.v4.u32 {%0,%1,%2,%3},[%4];}"
               : "+r"(v.x), "+r"(v.y), "+r"(v.z), "+r"(v.w) : "l"(p), "r"(tag), "n"(M) : "memory");
}
template <u32 M> DEV void rld64(uint64_t& v, const void* p, u32 tag) {
  asm volatile("{.reg .pred p; .reg .u32 t, h; mov.b64 {t,h},%0; lop3.b32 t,t,%2,%3,0x28; setp.ne.u32 p,t,0; @p ld.relaxed.gpu.global.u64 %0,[%1];}" : "+l"(v) : "l"(p), "r"(tag), "n"(M) : "memory");
}
template <int L> DEV u32 lop3(u32 a, u32 b, u32 c) { u32 r; asm("lop3.b32 %0,%1,%2,%3,%4;" : "=r"(r) : "r"(a), "r"(b), "r"(c), "n"(L)); return r; }
DEV u32 ne3(u32 a, u32 b, u32 c) { u32 r; asm("lop3.b32 %0,%1,%2,%3,0x7e;" : "=r"(r) : "r"(a), "r"(b), "r"(c)); return r; }
DEV void pin(u32 zr, u32 a, u32 b = 0, u32 c = 0, u32 d = 0) { asm volatile("{.reg .pred p; setp.ne.u32 p,%0,0; @p st.shared.v4.u32 [%0],{%1,%2,%3,%4};}" ::"r"(zr), "r"(a), "r"(b), "r"(c), "r"(d) : "memory"); }
DEV void pin2(u32 zr, const void* a, const void* b) { asm volatile("{.reg .pred p; setp.ne.u32 p,%0,0; @p st.shared.v2.u64 [%0],{%1,%2};}" ::"r"(zr), "l"(a), "l"(b) : "memory"); }
DEV void str128(void* p, u32 x, u32 y, u32 z, u32 w) { asm volatile("st.relaxed.gpu.global.v4.u32 [%0],{%1,%2,%3,%4};" ::"l"(p), "r"(x), "r"(y), "r"(z), "r"(w) : "memory"); }
DEV void str64(void* p, u32 x, u32 y) { asm volatile("{.reg .u64 d; mov.b64 d,{%1,%2}; st.relaxed.gpu.global.u64 [%0],d;}" ::"l"(p), "r"(x), "r"(y) : "memory"); }
DEV void str32(void* p, u32 x) { asm volatile("st.relaxed.gpu.global.u32 [%0],%1;" ::"l"(p), "r"(x) : "memory"); }
DEV void str16(void* p, u32 x) { asm volatile("st.relaxed.gpu.global.u16 [%0],%1;" ::"l"(p), "h"((unsigned short)x) : "memory"); }
DEV uint4 ldg128(const void* p) { uint4 v; asm volatile("ld.global.nc.v4.u32 {%0,%1,%2,%3},[%4];" : "=r"(v.x), "=r"(v.y), "=r"(v.z), "=r"(v.w) : "l"(p)); return v; }
DEV uint2 ldg64(const void* p) { uint2 v; asm volatile("ld.global.nc.v2.u32 {%0,%1},[%2];" : "=r"(v.x), "=r"(v.y) : "l"(p)); return v; }
DEV u32 ldg32(const void* p) { u32 v; asm volatile("ld.global.nc.u32 %0,[%1];" : "=r"(v) : "l"(p)); return v; }
DEV u32 ldg16(const void* p) { unsigned short v; asm volatile("ld.global.nc.u16 %0,[%1];" : "=h"(v) : "l"(p)); return v; }
#define bsync(id, n) asm volatile("bar.sync %0,%1;" ::"n"(id), "n"(n) : "memory")
#define barrive(id, n) asm volatile("bar.arrive %0,%1;" ::"n"(id), "n"(n) : "memory")
DEV void bsyncr(u32 id) { asm volatile("bar.sync %0,96;" ::"r"(id) : "memory"); }
DEV void barriver(u32 id) { asm volatile("bar.arrive %0,96;" ::"r"(id) : "memory"); }
constexpr u32 BW = 0x0FEA, BS = 0x6532;
DEV void mb_init(u32 a, u32 n) { asm volatile("mbarrier.init.shared.b64 [%0],%1;" ::"r"(a), "r"(n) : "memory"); }
DEV void mb_arrive(u32 a) { asm volatile("mbarrier.arrive.shared.b64 _,[%0];" ::"r"(a) : "memory"); }
DEV void mb_expect(u32 a, u32 bytes) { asm volatile("mbarrier.arrive.expect_tx.shared.b64 _,[%0],%1;" ::"r"(a), "r"(bytes) : "memory"); }
DEV void mb_wait(u32 a, u32 ph = 0) {
  u32 ok; int it = 0;
  do { asm volatile("{.reg .pred p; mbarrier.try_wait.parity.shared.b64 p,[%1],%2; selp.u32 %0,1,0,p;}" : "=r"(ok) : "r"(a), "r"(ph) : "memory"); } while (!ok && ++it < SPIN);
}
template <int N> DEV void bulk_out(void* dst, u32 src) { asm volatile("cp.async.bulk.global.shared::cta.bulk_group [%0],[%1],%2;" ::"l"(dst), "r"(src), "n"(N) : "memory"); }
constexpr u32 WSH = 41472;
template <int N> DEV void l2_pre(const void* p) { asm volatile("cp.async.bulk.prefetch.L2.global [%0],%1;" ::"l"(p), "n"(N) : "memory"); }
DEV void tma3d(u32 dst, const CUtensorMap* tm, u32 mb, int c0, int c2) {
  asm volatile("cp.async.bulk.tensor.3d.shared::cluster.global.mbarrier::complete_tx::bytes [%0],[%1,{%3,0,%4}],[%2];"
               ::"r"(dst), "l"((uint64_t)tm), "r"(mb), "r"(c0), "r"(c2) : "memory");
}
DEV float blo(u32 w) { return __uint_as_float(w << 16); }
DEV float bhi(u32 w) { return __uint_as_float(w & 0xffff0000u); }
DEV u32 pk_bf(float lo, float hi) { u32 r; asm("cvt.rn.bf16x2.f32 %0,%1,%2;" : "=r"(r) : "f"(hi), "f"(lo)); return r; }
DEV u32 pk_hf(float lo, float hi) { u32 r; asm("cvt.rn.f16x2.f32 %0,%1,%2;" : "=r"(r) : "f"(hi), "f"(lo)); return r; }
DEV float rbf(float x) { return __uint_as_float(pk_bf(0.f, x) & 0xffff0000u); }
DEV u32 bfma(u32 a, u32 b, u32 c) { u32 r; asm("fma.rn.bf16x2 %0,%1,%2,%3;" : "=r"(r) : "r"(a), "r"(b), "r"(c)); return r; }
DEV u32 bmul(u32 a, u32 b) { u32 r; asm("mul.rn.bf16x2 %0,%1,%2;" : "=r"(r) : "r"(a), "r"(b)); return r; }
DEV u32 badd(u32 a, u32 b) { u32 r; asm("add.rn.bf16x2 %0,%1,%2;" : "=r"(r) : "r"(a), "r"(b)); return r; }
DEV u32 hadd(u32 a, u32 b) { u32 r; asm("add.rn.f16x2 %0,%1,%2;" : "=r"(r) : "r"(a), "r"(b)); return r; }
DEV u32 hfma(u32 a, u32 b, u32 c) { u32 r; asm("fma.rn.f16x2 %0,%1,%2,%3;" : "=r"(r) : "r"(a), "r"(b), "r"(c)); return r; }
struct C2 { u32 re, im; };
DEV C2 cm2(C2 a, C2 b) {
  const __half2 ar = *reinterpret_cast<__half2*>(&a.re), ai = *reinterpret_cast<__half2*>(&a.im), br = *reinterpret_cast<__half2*>(&b.re), bi = *reinterpret_cast<__half2*>(&b.im);
  __half2 re = __hfma2(ar, br, __hneg2(__hmul2(ai, bi))), im = __hfma2(ar, bi, __hmul2(ai, br));
  return {*reinterpret_cast<u32*>(&re), *reinterpret_cast<u32*>(&im)};
}
DEV C2 pk2(const float2 (&a)[2]) { return {pk_hf(a[0].x, a[1].x), pk_hf(a[0].y, a[1].y)}; }
DEV C2 pk2c(const float2 (&a)[2]) { return {pk_hf(a[0].x, a[1].x), pk_hf(-a[0].y, -a[1].y)}; }
DEV u32 cpy(u32 x, u32 zr, int alt) {
  u32 r;
  if (alt) asm volatile("xor.b32 %0,%1,%2;" : "=r"(r) : "r"(x), "r"(zr)); else asm volatile("mad.lo.u32 %0,%2,%2,%1;" : "=r"(r) : "r"(x), "r"(zr));
  return r;
}
template <int N> DEV void inc(u32& x) { asm volatile("add.u32 %0,%0,%1;" : "+r"(x) : "n"(N)); }
DEV u32 opq(u32 x) { u32 r; asm volatile("mov.u32 %0,%1;" : "=r"(r) : "r"(x)); return r; }
DEV u32 chan(u32 b, u32 i) { return 16 * (b >> 2) + 2 * (b & 3) + (i & 1) + 4 * (i & 2); }
DEV u32 row16(u32 lane) { const u32 r0 = (lane & 7) + ((lane >> 3) & 1) + 8 * (lane >> 4) - 1; return (r0 ^ ((r0 >> 3) & 3)) * 16; }
DEV u32 clk() { u32 r; asm volatile("mov.u32 %0,%%clock;" : "=r"(r)::"memory"); return r; }
DEV void wait_clk(u32 t, int d) { while ((int)(clk() - t) < d); }
DEV float ex2(float x) { float r; asm("ex2.approx.ftz.f32 %0,%1;" : "=f"(r) : "f"(x)); return r; }
DEV float rcpf(float x) { float r; asm("rcp.approx.ftz.f32 %0,%1;" : "=f"(r) : "f"(x)); return r; }
DEV float2 cmul(float2 a, float2 b) { return make_float2(fmaf(a.x, b.x, -a.y * b.y), fmaf(a.x, b.y, a.y * b.x)); }
DEV float2 csq(float2 a) { return make_float2(fmaf(a.x, a.x, -a.y * a.y), (a.x + a.x) * a.y); }
DEV float2 cexp(float lr2, float th) {
  const float m = ex2(lr2);
  return make_float2(m * __cosf(th), m * __sinf(th));
}
DEV float silu_f(float v) { return v * rcpf(1.f + ex2(-1.4426950408889634f * v)); }
constexpr u32 B2P64 = 0x5F805F80u, B2M64 = 0x1F801F80u, BONE = 0x3F803F80u;
constexpr u32 MODJ = 18 * 128;
DEV float sqrta(float x) { float r; asm("sqrt.approx.ftz.f32 %0,%1;" : "=f"(r) : "f"(x)); return r; }
DEV u32 fu(float x) { return __float_as_uint(x); }
DEV float uf(u32 x) { return __uint_as_float(x); }
DEV void mma_hf_o(float (&d)[4], const float (&c)[4], const u32 (&a)[4], u32 b0, u32 b1) {
  asm("mma.sync.aligned.m16n8k16.row.col.f32.f16.f16.f32 {%0,%1,%2,%3},{%4,%5,%6,%7},{%8,%9},{%10,%11,%12,%13};"
      : "=f"(d[0]), "=f"(d[1]), "=f"(d[2]), "=f"(d[3]) : "r"(a[0]), "r"(a[1]), "r"(a[2]), "r"(a[3]), "r"(b0), "r"(b1), "f"(c[0]), "f"(c[1]), "f"(c[2]), "f"(c[3]));
}

DEV void mma_hf_t(float (&c)[4], const u32 (&a)[4], u32 b0, u32 b1) { mma_hf(c, a[0], a[1], a[2], a[3], b0, b1); }
DEV void cpa16(u32 dst, const void* src) { asm volatile("cp.async.cg.shared.global [%0],[%1],16;" ::"r"(dst), "l"(src) : "memory"); }
DEV void tm_pre(const CUtensorMap* tm) { asm volatile("prefetch.tensormap [%0];" ::"l"((uint64_t)tm) : "memory"); }
#define PROXY_FENCE() asm volatile("fence.proxy.async.shared::cta;" ::: "memory")
struct Prm {
  const char *la, *ai, *cr, *ci, *ldt;
  u32 zero, glo, ghi;
  const char *x, *c;
  char* gs;
  const char *dsk, *wr, *wg, *wu, *wd;
  char* out;
};
DEV char* gptr(const Prm& p, u32 lo) { char* r; asm("mov.b64 %0,{%1,%2};" : "=l"(r) : "r"(lo), "r"(p.ghi)); return r; }
DEV u32 uni(const Prm& p, u32 x) { return x >> p.zero; }
DEV u32 rowo(u32 base, u32 key) { return (~key & 0x1ffc) * 288 + base; }
constexpr float LOG2E = 1.4426950408889634f, F2P64 = 1.8446744073709552e19f, F2M64 = 5.421010862427522e-20f;

template <int S> DEV void y_store(float c0, float c1, float c2, float c3, u32 F, u32 pml, char* yp) {
  str32(yp, bmul(pk_bf(c0, c2), F) | pml);
  str32(yp + S, bmul(pk_bf(c1, c3), F) | pml);
}
DEV u32 sgn2(u32 a, u32 x, u32 y) { return opq(((a - x) >> 31) + ((a - y) >> 31)); }
DEV void merge4(u32 (&h)[8], uint4 a, uint4 b) {
  const u32 e1 = min(a.x, b.x), e2 = max(a.z, b.z), o1 = min(a.y, b.y), o2 = max(a.w, b.w), o0 = max(a.y, b.y), e3 = min(a.z, b.z);
  const u32 f1 = max(e1, e2), f2 = min(e1, e2), p1 = max(o1, o2), p2 = min(o1, o2);
  h[0] = max(a.x, b.x); h[1] = max(o0, f1); h[2] = min(o0, f1); h[3] = max(p1, f2); h[4] = min(p1, f2); h[5] = max(p2, e3); h[6] = min(p2, e3); h[7] = min(a.w, b.w);
}
DEV void top8(u32 (&a)[8], uint4 l, uint4 m) {
  u32 b[8];
  merge4(b, l, m);
#pragma unroll
  for (int i = 0; i < 8; i++) a[i] = max(a[i], b[7 - i]);
#pragma unroll
  for (int s = 4; s; s >>= 1)
#pragma unroll
    for (int i = 0; i < 8; i++) if (!(i & s)) { const u32 x = a[i], y = a[i + s]; a[i] = max(x, y); a[i + s] = min(x, y); }
}
#define POLL(load, cond_bad, code) { int it_ = 0; do { load; } while (__any_sync(~0u, (cond_bad)) & (++it_ <= SPIN)); if (it_ > SPIN) { ERRF(code); } TSN(code, it_); }
DEV u32 tmask(u32 it, u32 m) { u32 r; asm volatile("{.reg .pred p; setp.ne.u32 p,%1,0; selp.u32 %0,%2,0,p;}" : "=r"(r) : "r"(it), "r"(m)); return r; }
#define POLLM(load, bad, M, code) { u32 it_ = SPIN + (tid >> 16), m_; do { m_ = tmask(--it_, M); load; } while (__any_sync(~0u, (bad) & m_)); if (!it_) { ERRF(code); } TSN(code, SPIN - it_); }
#define POLLS(use, load, bad, M, code) { u32 it_ = SPIN + (tid >> 16); for (;;) { const u32 m_ = tmask(--it_, M); use; if (!__any_sync(~0u, (bad) & m_)) break; load; } if (!it_) { ERRF(code); } TSN(code, SPIN - it_); }
#define POLLW(load, cond_bad, code) { int it_ = 0; while (__any_sync(~0u, (cond_bad))) { if (++it_ > SPIN) { ERRF(code); break; } load; } TSN(code, it_); }

#define DOWN(E) if (tid == (b < 108 ? 288 : ~0u)) { const u32 c0 = 64 * (b % 9), c2 = 4 * (b / 9); \
    if (E == 1) { mb_expect(SM_MB + 24, 49152); tma3d(SM_TAP, tm_down, SM_MB + 24, c0, c2); } \
    tma3d(SM_WD + (E - 1) * 12288, tm_down, SM_MB + 24, c0, c2 + E); }
#define OUTR() { const u32 tl = 4 * ((lane >> 1) & 1) + ((lane >> 2) & 3) + 8 * (lane & 1); \
    bulk_out<1152>(p.out + (uni(p, b * BLK) + tl * 1152), SM_XST + ((lane & 2) + 4 * (lane & 1) + ((lane >> 2) & 1) + (lane & 8)) * ROW); \
    asm volatile("cp.async.bulk.commit_group;" ::: "memory"); }
struct FA { u32 tid, ba, ra, sa, ad, as; };
DEV FA ffn_addr(const Prm& p, u32 tid, u32 b) {
  const u32 w = tid >> 5, lane = tid & 31, kq = w & 3, tg = w >> 2, t = 7 - w;
  FA f = {tid, SM_XS + (lane & 7) * ROW + (18 * kq + (lane >> 3)) * 16, SM_RED + (8 * tg + kq) * 512 + lane * 16, w >= uni(p, 3 + (b & 1)) && w < 8 ? SM_RED + t * 2048 + lane * 16 : 0,
          (t < 4 ? uni(p, p.glo + G_ACT + 512 * b) + 128 * t : uni(p, p.glo + G_ACT + (512 + (b >> 1)) * 128)) + lane * 4, uni(p, p.glo + G_ACT + (b / 9) * 6144) + tid * 16};
  pin(tid >> 16, f.ba, f.ra, f.sa, tid); pin(tid >> 16, f.ad, f.as);
  return f;
}
DEV void ffn_tail(const Prm& p, const CUtensorMap* tm_down, uint4 (&A)[24], const FA f, const u32 b, const u32 par, const u32 okl) {
  const u32 tid = f.tid, w = tid >> 5, lane = tid & 31, g = lane >> 2, q = lane & 3, tg = w >> 2, zr = tid >> 16;
  const u32 pm = par ? TAGM : 0, kt = par * 3, ba = f.ba, ra = f.ra;
  char* const gs = p.gs;
  __syncthreads();
  TS(25);
  {
    float c0[2][4] = {}, c1[2][4] = {};
    uint4 bb[5];
#pragma unroll
    for (int s = 0; s < 5; s++) bb[s] = ldsm4(ba + s * 64);
#define BX(s) (s & 1 ? bb[s >> 1].z : bb[s >> 1].x), (s & 1 ? bb[s >> 1].w : bb[s >> 1].y)
    if (tg < 2) {
#pragma unroll
      for (int s = 0; s < 9; s++) {
        mma_bf(c0[s & 1], A[s].x, A[s].y, A[s].z, A[s].w, BX(s));
        mma_bf(c1[s & 1], A[9 + s].x, A[9 + s].y, A[9 + s].z, A[9 + s].w, BX(s));
      }
      sts128(ra + 2048, fu(c1[0][0] + c1[1][0]), fu(c1[0][1] + c1[1][1]), fu(c1[0][2] + c1[1][2]), fu(c1[0][3] + c1[1][3]));
    } else {
      DOWN(3);
#pragma unroll
      for (int s = 0; s < 9; s++) mma_bf(s & 2 ? c1[s & 1] : c0[s & 1], A[s].x, A[s].y, A[s].z, A[s].w, BX(s));
#pragma unroll
      for (int i = 0; i < 4; i++) c0[1][i] += c1[0][i] + c1[1][i];
    }
    sts128(ra, fu(c0[0][0] + c0[1][0]), fu(c0[0][1] + c0[1][1]), fu(c0[0][2] + c0[1][2]), fu(c0[0][3] + c0[1][3]));
  }
  const u32 atag = q ? 0 : pm, acs = SM_AC + tid * 16, acl = SM_AC + lane * 16;
  pin(zr, atag, acs, acl, kt);
  TS(39);
  if (!f.sa) bsync(0, 384);
  else {
    bsync(0, 384);
    float s[4];
    const uint4 u0 = lds128(f.sa), u1 = lds128(f.sa + 512), u2 = lds128(f.sa + 1024), u3 = lds128(f.sa + 1536);
    s[0] = (uf(u0.x) + uf(u1.x)) + (uf(u2.x) + uf(u3.x)); s[1] = (uf(u0.y) + uf(u1.y)) + (uf(u2.y) + uf(u3.y));
    s[2] = (uf(u0.z) + uf(u1.z)) + (uf(u2.z) + uf(u3.z)); s[3] = (uf(u0.w) + uf(u1.w)) + (uf(u2.w) + uf(u3.w));
    const u32 sg = pk_bf(silu_f(rbf(s[0])), silu_f(rbf(s[1])));
    str32(gptr(p, f.ad), bmul(sg, bmul(pk_bf(s[2], s[3]), B2M64)) | atag);
  }
  TS(26);
  const bool fin = w == (b < 72 ? 8 : ~0u);
  u32 kg;
  uint4 xt;
  const char* xs;
  if (fin) { kg = lds32(SM_SLOT + 4 * g); xs = gptr(p, rowo(uni(p, p.glo + G_Y + 16 * b), kg)); xt = ldr128(xs); }
  if (b < 108) {
    const char* const as = gptr(p, f.as);
    uint4 a = ldr128(as);
    char* const dst = gptr(p, uni(p, p.glo + G_PART + b * 2048) + w * 512 + lane * 8);
    if (w < 4) {
      const u32 aa = SM_WD + (8 * (lane >> 4) + (lane & 7)) * 128 + (((2 * w + ((lane >> 3) & 1)) ^ (lane & 7)) << 4);
      mb_wait(SM_MB + 24);
#pragma unroll
      for (int s = 0; s < 24; s++) A[s] = ldsm4t(aa + (s < 6 ? SM_TAP - SM_WD : -12288) + s * 2048);
      pin2(zr, dst, as);
    }
    conv();
    TS(28);
    POLLW(rld128<TAGM>(a, as, pm), (a.x ^ pm) & TAGM, 9);
    sts128(acs, a.x, a.y, a.z, a.w); sts32(acs, a.x & ~TAGM);
    TS(27);
    if (w < 4) {
      bsync(8, 384);
      float c[4][4] = {};
#pragma unroll
      for (int s = 0; s < 12; s++) {
        const uint4 bb = ldsm4t(acl + s * 512);
        mma_bf(c[2 * (s & 1)], A[2 * s].x, A[2 * s].y, A[2 * s].z, A[2 * s].w, bb.x, bb.y);
        mma_bf(c[2 * (s & 1) + 1], A[2 * s + 1].x, A[2 * s + 1].y, A[2 * s + 1].z, A[2 * s + 1].w, bb.z, bb.w);
      }
      u32 o[4];
#pragma unroll
      for (int i = 0; i < 4; i++) o[i] = fu((c[0][i] + c[1][i]) + (c[2][i] + c[3][i]));
      str64(dst, (o[0] & ~3u) | kt, o[1]); str64(dst + 256, (o[2] & ~3u) | kt, o[3]);
      TS(29);
    } else barrive(8, 384);
  }
  if (w == 10 && okl < lds32(SM_SLOT + 28)) OUTR();
  if (fin) {
    const u32 ta = clk();
    const char* src = gptr(p, uni(p, p.glo + G_PART + b * 256) + lane * 8);
    const u32 co = uni(p, 16 * b) + 4 * q, gw = lds32(SM_MODS + 5760 + co), hw = lds32(SM_XS + g * ROW + co);
    const float sgm = rcpf(1.f + ex2(-LOG2E * bhi(kg ^ (~((int)kg >> 31) | 0x80000000))));
    char* const dst = p.out + rowo(co, kg);
    conv();
    POLLW(rld128<TAGM>(xt, xs, TAGR), (xt.x ^ TAGR) & TAGM, 10);
    const u32 x1w = (q & 2) ? ((q & 1) ? xt.w : xt.z) : ((q & 1) ? xt.y : bmul(xt.x ^ TAGR, B2P64));
    const u32 sg2 = bmul(pk_bf(sgm, sgm), B2P64);
    pin(zr, x1w, gw, hw, sg2); pin2(zr, dst, src);
    uint64_t v[12];
#pragma unroll
    for (int j = 0; j < 12; j++) v[j] = 1;
    float s0, s1;
    wait_clk(ta, PD);
    conv();
    TS(13);
#define VL(j) (u32)v[j]
#define VS(j, s) ((uf((u32)(v[j] >> s)) + uf((u32)(v[j + 1] >> s))) + (uf((u32)(v[j + 2] >> s)) + uf((u32)(v[j + 3] >> s))))
    u32 res;
    POLLM({ _Pragma("unroll") for (int j = 0; j < 12; j++) rld64<3>(v[j], src + j * 9 * 2048, kt);
            s0 = VS(0, 0) + VS(4, 0) + VS(8, 0); s1 = VS(0, 32) + VS(4, 32) + VS(8, 32);
            res = opq(badd(x1w, bmul(gw, badd(hw, bmul(movm(pk_bf(s0, s1)), sg2))))); },
          lop3<0xfe>(ne3(VL(0), VL(1), kt), ne3(VL(2), VL(3), kt), ne3(VL(4), VL(5), kt)) |
          lop3<0xfe>(ne3(VL(6), VL(7), kt), ne3(VL(8), VL(9), kt), ne3(VL(10), VL(11), kt)), 3, 11);
    asm volatile("st.global.u32 [%0],%1;" ::"l"(dst), "r"(res) : "memory");
    if (b == 0 && lane == 0) str32(gs + G_EP, par);
    TS(30); TSE();
  }
  if (w == 10) asm volatile("cp.async.bulk.wait_group.read 0;" ::: "memory");
}

DEV u32 y_lo(const Prm& p, u32 tid, u32 b) {
  const u32 ua = uni(p, p.glo + G_Y + b * 128), ub = uni(p, p.glo + 16384 + (b & ~3) * BLK + (b & 3) * 512);
  return (tid < 256 ? ua : ub) + (((tid & 2) * 4) | ((tid >> 2) & 4)) * (tid < 256 ? BLK : 32) + (tid >> 5) * (16 * BLK) + ((tid >> 2) & 3) * 32 + (tid & 1) * 16;
}
DEV void post_conv(const Prm& p, const CUtensorMap* tm_down, const u32 tid, const u32 b, const u32 b3) {
  const u32 w = tid >> 5, lane = tid & 31;
  const u32 g = lane >> 2, q = lane & 3, e = g >> 2, h = (g >> 1) & 1, hi = g & 1;
  const u32 pm = lds32(SM_THR + 4), par = pm >> 30;
  char* const gs = p.gs;
  const u32 cho = 128 * w + 64 * e + 16 * q;
  u32 x1[4][4], h2[4][4], key[4], lt;
  u32 okl = ~0u;
  FA fa;
  uint4 A[24];
#define AROW(t) const u32 arow = 144 * ((t >> 5) & 3) + ((t >> 1) & 8) + (t & 7), ab = (t & 8) ? SM_UP : SM_GATE;
#define AFRAG9() { _Pragma("unroll") for (int s = 0; s < 9; s++) A[s] = ldsm4t(ab + SLV + arow * 16 + s * 256); }
  if (w < 9) {
    const char* const ys = gptr(p, y_lo(p, tid, b));
    uint4 yv[4];
#pragma unroll
    for (int v = 0; v < 4; v++) yv[v].x = INVAL;
    const u32 tg0 = b < YL ? pm : INVAL;
    if (w >= 4) { pin2(tid >> 16, ys, ys); bsync(12, N12); TS(18); }
#pragma unroll
    for (int v = 0; v < 4; v++) rld128<TAGM>(yv[v], ys + v * BLK, tg0);
    const u32 tc = clk();
    const u32 ma = SM_MODS + cho, xa = SM_XST + (2 * h + 4 * hi) * ROW + cho;
    const uint4 sa = lds128(ma), ca = lds128(ma + 1152), ga = lds128(ma + 2304);
    const uint4 rb = lds128((g & 2) ? SM_ONE + 16 * hi : (ma ^ 64) + 8064 + 1152 * hi);
    const u32 saw[4] = {sa.x, sa.y, sa.z, sa.w}, caw[4] = {ca.x, ca.y, ca.z, ca.w}, gaw[4] = {ga.x, ga.y, ga.z, ga.w};
#pragma unroll
    for (int k = 0; k < 4; k++) {
      const uint2 st = lds64(SM_ST + 16 * (2 * h + 4 * hi + (k & 1) + 8 * (k >> 1)));
      const uint4 xv = lds128(xa + ((k & 1) + 8 * (k >> 1)) * ROW);
      x1[k][0] = xv.x; x1[k][1] = xv.y; x1[k][2] = xv.z; x1[k][3] = xv.w;
#pragma unroll
      for (int v = 0; v < 4; v++) x1[k][v] = badd(x1[k][v], bfma(bmul(badd(x1[k][v], st.x), st.y), caw[v], saw[v]));
    }
    const bool own = (q >> 1) == e;
    const u32 spw = SM_SP + (2 * w + e) * 320 + (g & 3) * 16 + (own ? ((q & 1) == h ? 4 : 12) : 8 - 8 * (q & 1));
    if (w < 4) asm volatile("setmaxnreg.dec.sync.aligned.u32 168;");
    if (b >= YL) wait_clk(tc, YD);
    conv();
    TS(13);
    POLLW(_Pragma("unroll") for (int v = 0; v < 4; v++) rld128<TAGM>(yv[v], ys + v * BLK, pm), lop3<0xa8>(ne3(yv[0].x, yv[1].x, pm), ne3(yv[2].x, yv[3].x, pm), TAGM), 5);
    TS(19);
#pragma unroll
    for (int k = 0; k < 4; k += 2) {
      float X[4] = {}, Y[4] = {}, R[4] = {};
#pragma unroll
      for (int v = 0; v < 4; v++) {
        const u32 y0 = k ? yv[v].z : yv[v].x & ~TAGM, y1 = k ? yv[v].w : yv[v].y;
        x1[k][v] = bfma(movm(y0), gaw[v], x1[k][v]);
        x1[k + 1][v] = bfma(movm(y1), gaw[v], x1[k + 1][v]);
        mma8_bf(X, x1[k][v], x1[k + 1][v], x1[k][v]); mma8_bf(Y, x1[k][v], x1[k + 1][v], x1[k + 1][v]);
        if (v & 1) mma_bf(R, x1[k][v - 1], x1[k + 1][v - 1], x1[k][v], x1[k + 1][v], v & 2 ? rb.z : rb.x, v & 2 ? rb.w : rb.y);
      }
      sts32(spw + k * 64, fu(own ? (hi ? X[1] : X[0]) : R[0] + R[1]));
      sts32(spw + k * 64 + 64, fu(own ? (hi ? Y[3] : Y[2]) : R[2] + R[3]));
    }
    barrive(1, N1);
    TS(36);
    asm volatile("setmaxnreg.inc.sync.aligned.u32 168;");
    mb_wait(SM_MB + 8); mb_wait(SM_MB + 16);
    const uint4 sb = lds128(ma + 3456), cb = lds128(ma + 4608), gb = lds128(ma + 5760);
    const u32 sbw[4] = {sb.x, sb.y, sb.z, sb.w}, cbw[4] = {cb.x, cb.y, cb.z, cb.w}, gbw[4] = {gb.x, gb.y, gb.z, gb.w};
    const u32 t3 = opq(tid), zr = t3 >> 16;
    AROW(t3);
    const u32 aa = ab + arow * 64 + ((((t3 >> 6) & 2) ^ ((t3 & 7) >> 1)) << 4), sta = SM_ST2 + 16 * (g & 3);
    const u32 rowl = uni(p, p.glo + b * BLK) + (4 * h + 8 * hi) * 1152 + cho;
    char* const rowp = gptr(p, rowl);
    pin(zr, aa, sta, xa); pin2(zr, rowp, rowp);
    bsync(2, 320);
    TS(37);
    uint4 st[4];
#pragma unroll
    for (int k = 0; k < 4; k++) st[k] = lds128(sta + 64 * k);
    lt = lds32(SM_THR);
#define AFL() { _Pragma("unroll") for (int s = 0; s < 9; s++) { A[s] = ldsm4t(aa + s * 1024); A[9 + s] = ldsm4t((aa ^ 16) + s * 1024); } }
#pragma unroll
    for (int k = 0; k < 4; k++) {
      key[k] = st[k].w;
      u32 o[4];
#pragma unroll
      for (int v = 0; v < 4; v++) {
        const u32 d = badd(x1[k][v], st[k].x), z = bfma(d, st[k].y, bmul(d, st[k].z));
        h2[k][v] = badd(bmul(z, cbw[v]), sbw[v]);
        o[v] = badd(x1[k][v], bmul(gbw[v], h2[k][v]));
      }
      h2[k][0] = bmul(h2[k][0], B2M64) | TAGR; x1[k][0] = bmul(x1[k][0], B2M64) | TAGR;
      if (key[k] >= lt) str128(rowp + k * 1152, h2[k][0], h2[k][1], h2[k][2], h2[k][3]);
      sts128(xa + ((k & 1) + 8 * (k >> 1)) * ROW, o[0], o[1], o[2], o[3]);
    }
    barrive(3, 320);
    TS(21);
    if (w < 8) AFL() else AFRAG9();
    TS(22);
    const u32 rr = tid * 57 >> 12, rc = tid * 16 - rr * 1152, sl = SM_SLOT + 8 * rr;
    const u32 rb_ = p.glo + rc;
    const u32 km = max(max(key[0], key[1]), max(key[2], key[3])), xd = SM_XS + rr * (2 * ROW) + rc;
    pin(tid >> 16, sl, km, xd); pin(tid >> 16, rb_, rowl);
    fa = ffn_addr(p, tid | p.zero, b);
    bsync(6, 320);
    TS(24);
    const uint2 sk = lds64(sl);
    const char *r0 = gptr(p, rowo(rb_, sk.x)), *r1 = gptr(p, rowo(rb_, sk.y));
    uint4 rv[2] = {ldr128(r0), ldr128(r1)};
    barrive(15, 320);
    const u32 g8 = lds32(SM_SLOT + 28);
    if (__any_sync(~0u, km >= g8 && lt > g8)) {
      char* const rowq = gptr(p, opq(rowl));
#pragma unroll
      for (int k = 0; k < 4; k++) if (key[k] >= g8 && key[k] < lt) str128(rowq + k * 1152, h2[k][0], h2[k][1], h2[k][2], h2[k][3]);
    }
    bsync(5, 320);
    const uint2 sf = lds64(sl);
    const u32 f8 = lds32(SM_SLOT + 28);
    if (__any_sync(~0u, km >= f8)) {
      char* const rowq = gptr(p, opq(rowl));
#pragma unroll
      for (int k = 0; k < 4; k++) if (key[k] >= f8) str128(rowq + (G_Y + k * 1152), x1[k][0], x1[k][1], x1[k][2], x1[k][3]);
    }
    if (__any_sync(~0u, sf.x != sk.x || sf.y != sk.y)) {
      r0 = gptr(p, rowo(rb_, sf.x)); r1 = gptr(p, rowo(rb_, sf.y));
      rv[0].x = rv[1].x = INVAL;
    }
    POLLS(_Pragma("unroll") for (int j = 0; j < 2; j++) { sts128(xd + j * ROW, rv[j].x, rv[j].y, rv[j].z, rv[j].w); sts32(xd + j * ROW, bmul(rv[j].x ^ TAGR, B2P64)); },
          { rld128<TAGM>(rv[0], r0, TAGR); rld128<TAGM>(rv[1], r1, TAGR); }, ne3(rv[0].x, rv[1].x, TAGR), TAGM, 8);
    TS(38);
  } else {
    u32 ok, lr;
    if (w == 10) {
      uint2 rc = lds64(SM_RC + 8 * min(lane, 17u));
      float r1 = lane < 18 ? uf(rc.x) : 0.f, r2 = lane < 18 ? uf(rc.y) : 0.f;
#pragma unroll 1
      for (int o = 16; o; o >>= 1) { r1 += __shfl_xor_sync(~0u, r1, o); r2 += __shfl_xor_sync(~0u, r2, o); }
      const u32 tl = 4 * ((lane >> 1) & 1) + ((lane >> 2) & 3) + 8 * (lane & 1), kl = (2047 - 16 * b - tl) << 2 | par * 3;
      const u32 kp = uni(p, p.glo + G_KEY + b * KST) + (tid >> 16);
      const u32 spr = SM_SP + (lane >> 4) * 9 * 320 + (lane & 15) * 16;
      TS(31);
      r2 += 0.f;
      const u32 nth = b < NB8 ? 7 : NEARLY - 1, ka = SM_KEY + 4 * (lane & 15), kb = SM_KEY + 2 * (lane & 16), lim = lane < 16 ? 8 : 0;
      pin(tid >> 16, kl, ka, kb, lim); pin(tid >> 16, kp);
      conv();
      bsync(1, N1);
      uint4 t = lds128(spr);
      float S1 = uf(t.x), S2 = uf(t.y), S3 = uf(t.z);
#pragma unroll
      for (int i = 1; i < 9; i++) { t = lds128(spr + i * 320); S1 += uf(t.x); S2 += uf(t.y); S3 += uf(t.z); }
      S1 += __shfl_xor_sync(~0u, S1, 16); S2 += __shfl_xor_sync(~0u, S2, 16); S3 += __shfl_xor_sync(~0u, S3, 16);
      const float mu = S1 * (1.f / 576.f), var = fmaxf(fmaf(-mu, mu, S2 * (1.f / 576.f)), 0.f);
      const float m = rbf(mu), rs = rcpf(rbf(sqrta(rbf(rbf(var) + 1e-5f))));
      const u32 rb = pk_bf(0.f, fmaf(fmaf(-m, r1, S3), rs, r2));
      ok = ((rb ^ (((int)rb >> 31) | 0x80000000)) & 0xffff0000u) | kl;
      const float rh = rbf(rs);
      const u32 oh = ok >> 1;
      sts32(ka, oh);
      __syncwarp();
      const uint4 o0 = lds128(kb), o1 = lds128(kb + 16);
      sts128(SM_ST2 + 16 * (lane & 15), pk_bf(-m, -m), pk_bf(rh, rh), pk_bf(rs - rh, rs - rh), ok);
      lr = opq(sgn2(oh, o0.x, o0.y) + sgn2(oh, o0.z, o0.w)) +
           opq(sgn2(oh, o1.x, o1.y) + sgn2(oh, o1.z, o1.w));
      lr += __shfl_xor_sync(~0u, lr, 16);
      asm volatile("{.reg .pred p; setp.lt.u32 p,%0,%1; @p st.relaxed.gpu.global.u32 [%2],%3;}" ::"r"(lr), "r"(lim), "l"(gptr(p, kp + 4 * lr)), "r"(ok) : "memory");
      if (lr == nth) sts32(SM_THR, ok);
      barrive(2, 320);
      barrive(13, 64);
      TS(20);
    } else if (w == 9) {
      bsync(1, N1);
      PROXY_FENCE();
      DOWN(1);
    } else {
      const char* ks = gs + (G_KEY + (lane >> 1) * KST + (lane & 1) * 16);
      const u32 kt = par * 3;
      uint4 L[8];
      u32 H[8];
#define KBAD(j) ((L[j].x ^ kt) & 3)
#define KLD(j) L[j] = ldr128(ks + j * 16 * KST)
#pragma unroll
      for (int j = 0; j < 8; j++) L[j].x = INVAL;
      bsync(13, 64);
      wait_clk(clk(), b < KE ? KD : b < YL ? KDB : KD1);
      TS(34);
      POLL({ _Pragma("unroll") for (int j = 0; j < 8; j++) if (KBAD(j)) KLD(j);
             merge4(H, L[0], L[1]); top8(H, L[2], L[3]);
             asm volatile("" : "+r"(H[0]), "+r"(H[1]), "+r"(H[2]), "+r"(H[3]), "+r"(H[4]), "+r"(H[5]), "+r"(H[6]), "+r"(H[7])); TS(32); },
           KBAD(0) | KBAD(1) | KBAD(2) | KBAD(3) | KBAD(4) | KBAD(5), 6);
      u32 u = __reduce_max_sync(~0u, max(H[0], max(L[4].x, L[5].x)));
      top8(H, L[4], L[5]);
      TS(35);
      u32 m[8], x0 = H[0], x1 = H[1];
#pragma unroll
      for (int r = 0; r < 8; r++) {
        const u32 ur = u;
        const bool win = x0 == ur;
        if (r < 7) { x0 = max(x0 - ur, x1 - ur); u = __reduce_max_sync(~0u, x0); }
        m[r] = r ? m[r - 1] + ur : ur;
        if (r == 0) { if (KBAD(6)) KLD(6); if (KBAD(7)) KLD(7); }
#pragma unroll
        for (int i = 1; i < 7 - r; i++) H[i] = win ? H[i + 1] : H[i];
        x1 = H[1] - m[r];
        if ((r & 3) == 3) sts128(SM_SLOT + 4 * r - 12, m[r - 3], m[r - 2], m[r - 1], m[r]);
      }
      barrive(6, 320);
      TS(23);
      conv();
      POLLW({ if (KBAD(6)) KLD(6); if (KBAD(7)) KLD(7); }, KBAD(6) | KBAD(7), 7);
      conv();
      u = __reduce_max_sync(~0u, max(L[6].x, L[7].x));
      if (u > m[7]) {
        do {
          const u32 x = u;
          if (L[6].x == x) L[6] = make_uint4(L[6].y, L[6].z, L[6].w, 0);
          if (L[7].x == x) L[7] = make_uint4(L[7].y, L[7].z, L[7].w, 0);
          u = __reduce_max_sync(~0u, max(L[6].x, L[7].x));
#pragma unroll
          for (int i = 7; i; i--) m[i] = max(min(m[i - 1], x), m[i]);
          m[0] = max(m[0], x);
        } while (u > m[7]);
        sts128(SM_SLOT, m[0], m[1], m[2], m[3]); sts128(SM_SLOT + 16, m[4], m[5], m[6], m[7]);
      }
      barrive(5, 320);
      TS(33);
    }
    asm volatile("setmaxnreg.inc.sync.aligned.u32 168;");
    mb_wait(SM_MB + 8); mb_wait(SM_MB + 16);
    AROW(tid);
    AFRAG9();
    fa = ffn_addr(p, tid | p.zero, b);
    TS(22);
    if (w == 10) {
      bsync(3, 320);
      PROXY_FENCE();
      if (lane < 16 && lr >= 8) OUTR();
      if (lane < 16 && lr < 8) okl = ok;
    } else if (w == 9) {
      bsync(15, 320);
      DOWN(2);
      TS(13);
    }
  }
  ffn_tail(p, tm_down, A, fa, b3, par, okl);
}

__global__ void __launch_bounds__(384, 1)
fused_kernel(const Prm p, const __grid_constant__ CUtensorMap tm_mod, const __grid_constant__ CUtensorMap tm_gate, const __grid_constant__ CUtensorMap tm_gs,
             const __grid_constant__ CUtensorMap tm_up, const __grid_constant__ CUtensorMap tm_us, const __grid_constant__ CUtensorMap tm_down) {
  extern __shared__ __align__(1024) unsigned char smem[];
  u32 la, ai, ldt; uint2 cr, ci;
  {
    const u32 t = threadIdx.x, d = t < 256 ? chan(blockIdx.x, t >> 5) : 512 + (blockIdx.x >> 1), o = d * 256 + 8 * (t & 31), o4 = o + ((t < 256 ? t >> 5 : t >> 3) & 4);
    asm volatile("{.reg .pred p; .reg .u16 h; setp.ne.u32 p,%7,0; @p ld.global.nc.u32 %0,[%8]; @p ld.global.nc.u32 %1,[%9]; @p ld.global.nc.v2.u32 {%2,%3},[%10];"
                 "@p ld.global.nc.v2.u32 {%4,%5},[%11]; @p ld.global.nc.u16 h,[%12]; cvt.u32.u16 %6,h;}"
                 : "=r"(la), "=r"(ai), "=r"(cr.x), "=r"(cr.y), "=r"(ci.x), "=r"(ci.y), "=r"(ldt)
                 : "r"(0x6ffu >> (t >> 5) & 1), "l"(p.la + o4), "l"(p.ai + o4), "l"(p.cr + o), "l"(p.ci + o), "l"(p.ldt + 2 * d));
  }
  const u32 t0 = clk();
  const u32 tid = __shfl_sync(~0u, threadIdx.x, threadIdx.x & 31), b = blockIdx.x + p.zero;
  const u32 w = tid >> 5, lane = tid & 31;
  const u32 g = lane >> 2, q = lane & 3, hi = g & 1;
  const u32 rho = b & 1, Ps = 512 + (b >> 1);
  char* const gs = p.gs;
  TS0();
  const bool kw = w != 8 && w != 11;
  const u32 ksig = w < 8 ? (w & 3) : 4, khf = w < 8 ? (w >> 2) : (w & 1);
  if (!kw) {
    if (tid == 352) {
#pragma unroll
      for (int i = 0; i < 5; i++) mb_init(SM_MB + 8 * i, i < 4 ? 1 : 64);
      asm volatile("fence.mbarrier_init.release.cluster;" ::: "memory");
      tm_pre(&tm_mod);
    }
    const char* cp = p.c + (576 * (w & 1) + 24 * min(lane, 23u));
    const uint2 c0 = ldg64(cp);
    la = c0.x; ai = c0.y; cr = ldg64(cp + 8); ci = ldg64(cp + 16);
  }
  u32 b3;
  asm volatile("shr.u32 %0,%1,%2;" : "=r"(b3) : "r"(blockIdx.x), "r"(p.zero));
  const u32 zr = tid >> 16;
  const u32 epv = ldr32(gs + (G_EP + zr));
  const u32 tp = SM_TAP + ksig * TAPS;
  if (kw && !khf) {
#pragma unroll 1
    for (u32 i = lane * 16; i < TAPS; i += 512) sts128(tp + i, 0, 0, 0, 0);
  }
  if (tid < 128) sts128(SM_INV + 16 * tid, INVAL, 0, 1, 0);
  if (tid >= 124) str128(gs + (tid >= 380 ? G_MOD + b * 128 + q * 16 : b * BLK + 16384 - 252 * 16 + tid * 16 + (tid < 252 ? G_Y + 2048 : 0)), INVAL, 0, 1, 0);
  if (tid == (b < 36 ? 352 : ~0u)) { while (clk() - t0 < DMOD); mb_expect(SM_MB, 36864); tma3d(SM_UP, &tm_mod, SM_MB, 32 * b, 0); }
  if (w < 9) {
    while ((int)(clk() - t0) < 0);
    const char* xp = p.x + (b * BLK + (lane >> 3) * 1152 + 128 * w + 16 * (lane & 7));
    const u32 xd = SM_XST + (((lane >> 3) & 1) + 8 * (lane >> 4)) * ROW + 128 * w + 16 * (lane & 7);
#pragma unroll
    for (int i = 0; i < 4; i++) cpa16(xd + 2 * ROW * i, xp + 4608 * i);
  }
  const u32 ktab = w < 8 ? SM_MODS + w * KTAB : SM_ZS + (w - 9) * KTAB;
  float k2048 = 0.f;
  if (kw) {
    u32 mx = __vmaxu2(__vmaxu2(cr.x & 0x7fff7fff, cr.y & 0x7fff7fff), __vmaxu2(ci.x & 0x7fff7fff, ci.y & 0x7fff7fff));
    const u32 E = max(__reduce_max_sync(~0u, max(mx & 0xffff, mx >> 16)) >> 7, 8u);
    TS(1);
    const float dt = rbf(ex2(blo(ldt) * LOG2E)), csc = uf((257 - E) << 23 | (fu(dt) & 0x7fffff));
    sts32(SM_SC + 16 * ksig + 12, fu(uf(fu(dt) & 0x7f800000) * uf((E - 2) << 23)));
    const u32 crw = khf ? cr.y : cr.x, ciw = khf ? ci.y : ci.x;
    float2 C[2], w4[2], w8[2], w16[2], w32[2], w64[2], w128[2], w256[2], w512[2], a1[2], a2[2], a3[2], t0[2], t1[2], s3[2];
#pragma unroll
    for (int m = 0; m < 2; m++) {
      const float lr2 = rbf(ex2((m ? bhi(la) : blo(la)) * LOG2E)) * dt * -LOG2E, th = (m ? bhi(ai) : blo(ai)) * dt;
      C[m] = make_float2((m ? bhi(crw) : blo(crw)) * csc, (m ? bhi(ciw) : blo(ciw)) * csc);
      const float2 w1 = cexp(lr2, th), w2 = csq(w1);
      w64[m] = cexp(64.f * lr2, 64.f * th);
      w4[m] = csq(w2); w8[m] = csq(w4[m]); w16[m] = csq(w8[m]); w32[m] = csq(w16[m]);
      w128[m] = csq(w64[m]); w256[m] = csq(w128[m]); w512[m] = csq(w256[m]);
      const float2 w1024 = csq(w512[m]);
      a1[m] = cmul(C[m], w1); a2[m] = cmul(C[m], w2); a3[m] = cmul(a1[m], w2);
      t0[m] = cmul(C[m], w1024); t1[m] = cmul(t0[m], w128[m]); s3[m] = cmul(w8[m], w16[m]);
      k2048 += fmaf(t0[m].x, w1024.x, -t0[m].y * w1024.y);
    }
    C2 B0[8], B1[8], B2[8], S[8];
    B0[0] = pk2(C); B0[1] = pk2(a1); B0[2] = pk2(a2); B0[3] = pk2(a3);
    const C2 h4 = pk2(w4), h256 = pk2(w256), h512 = pk2(w512);
#pragma unroll
    for (int i = 0; i < 4; i++) B0[4 + i] = cm2(B0[i], h4);
#pragma unroll
    for (int i = 0; i < 4; i++) B1[i] = cm2(B0[2 * i], h256);
    B1[4] = cm2(B0[0], h512); B1[5] = cm2(B0[4], h512);
    B1[6] = cm2(B1[4], h256); B1[7] = cm2(B1[5], h256);
    const u32 ta = ktab + lane * 128, f = ((lane & 3) << 5) | ((lane & 4) << 2);
#pragma unroll
    for (int i = 0; i < 8; i++) sts128(ta + ((i << 4) ^ f), B0[i].re, B0[i].im, B1[i].re, B1[i].im);
    B2[0] = pk2(t0); B2[1] = pk2(t1);
    B2[2] = cm2(B2[0], h256); B2[3] = cm2(B2[1], h256);
#pragma unroll
    for (int i = 0; i < 4; i++) B2[4 + i] = cm2(B2[i], h512);
    S[0] = {0x3C003C00u, 0u}; S[1] = pk2c(w8); S[2] = pk2c(w16); S[3] = pk2c(s3); S[4] = pk2c(w32);
#pragma unroll
    for (int i = 1; i < 4; i++) S[4 + i] = cm2(S[i], S[4]);
#pragma unroll
    for (int i = 0; i < 8; i++) sts128(ta + 4096 + ((i << 4) ^ f), B2[i].re, B2[i].im, S[i].re, S[i].im);
    const C2 m64 = pk2c(w64), m128 = pk2c(w128);
    sts128(ktab + 8192 + lane * 16, m64.re, m64.im, m128.re, m128.im);
    __syncwarp();
  } else {
    u32 sa = SM_SIL + 576 * (w & 1) + 24 * min(lane, 23u);
#pragma unroll 1
    for (int j = 0; j < 6; j++) {
      sts32(sa, pk_bf(silu_f(blo(la)), silu_f(bhi(la))));
      la = ai; ai = cr.x; cr.x = cr.y; cr.y = ci.x; ci.x = ci.y; sa += 4;
    }
    bsync(7, 64);
  }
  TS(2);
  const u32 pm = (__reduce_or_sync(~0u, epv) & 1) ? 0 : TAGM;
  sts32(SM_THR + 4, pm);
  if (w < 9) {
    asm volatile("cp.async.wait_all;" ::: "memory");
    __syncwarp();
    TS(4);
    if (tid == (b - 36 < 72 ? 256 : ~0u)) { mb_expect(SM_MB, 36864); tma3d(SM_UP, &tm_mod, SM_MB, 32 * b, 0); }
    const u32 xa = SM_XST + (lane & 15) * ROW + 128 * w + 16 * (lane >> 4);
    float s[4] = {}, X[2][4] = {}, Y[2][4] = {};
#pragma unroll
    for (int j = 0; j < 4; j++) {
      const uint4 a = ldsm4(xa + 32 * j);
      mma8_bf(X[0], a.x, a.y, a.x); mma8_bf(Y[0], a.x, a.y, a.y);
      mma8_bf(X[1], a.z, a.w, a.z); mma8_bf(Y[1], a.z, a.w, a.w);
      mma_bf(s, a.x, a.y, a.z, a.w, BONE, BONE);
    }
    uint4 t[4];
#pragma unroll
    for (int j = 0; j < 4; j++) t[j] = ldsm4t(xa + 32 * j);
    const float u0 = hi ? X[0][1] + X[1][1] : X[0][0] + X[1][0], u1 = hi ? Y[0][3] + Y[1][3] : Y[0][2] + Y[1][2];
    if (q == g >> 1) sts128(SM_SP + w * 128 + g * 16, fu(s[0]), fu(u0), fu(s[2]), fu(u1));
    bsync(1, 288);
    TS(7);
    const u32 spr = SM_SP + (lane & 7) * 16 + (lane & 8);
    const uint2 t8 = lds64(spr + 1024);
    const float f8 = lane < 16 ? 1.f : 0.f;
    float S1 = uf(t8.x) * f8, S2 = uf(t8.y) * f8;
#pragma unroll
    for (int i = 0; i < 4; i++) { const uint2 u = lds64(spr + (lane & 16) * 32 + i * 128); S1 += uf(u.x); S2 += uf(u.y); }
    S1 += __shfl_xor_sync(~0u, S1, 16); S2 += __shfl_xor_sync(~0u, S2, 16);
    const float mu = S1 * (1.f / 576.f), var = fmaxf(fmaf(-mu, mu, S2 * (1.f / 576.f)), 0.f);
    const float m = rbf(mu), rs = rcpf(rbf(sqrta(rbf(rbf(var) + 1e-5f))));
    const float ra = rs * 0.0625f;
    sts64(SM_AF + w * 128 + (lane & 15) * 8, fu(ra), fu(-m * ra));
    __syncwarp();
    TS(55);
    const uint4 f0 = lds128(SM_AF + w * 128 + q * 16), f1 = lds128(SM_AF + w * 128 + 64 + q * 16);
    const u32 zdst = SM_GATE + w * 2048 + (g >> 1) * 128 + (lane & 15) * 8;
    const u32 pz = (q & 1) ? 0 : pm;
#pragma unroll
    for (int j = 0; j < 8; j++) {
      const u32 x0 = j & 1 ? t[j >> 1].z : t[j >> 1].x, x1 = j & 1 ? t[j >> 1].w : t[j >> 1].y;
      sts64((j & 1 ? zdst ^ 64 : zdst) + 512 * (j >> 1), pk_hf(fmaf(blo(x0), uf(f0.x), uf(f0.y)), fmaf(bhi(x0), uf(f0.z), uf(f0.w))) | pz,
            pk_hf(fmaf(blo(x1), uf(f1.x), uf(f1.y)), fmaf(bhi(x1), uf(f1.z), uf(f1.w))));
    }
    TS(53);
    if (w < 8) barrive(15, 288);
    else {
      bsync(15, 288);
      TS(54);
      if (lane == 0) {
        PROXY_FENCE();
        bulk_out<BLK>(gs + b * BLK, SM_GATE);
        asm volatile("cp.async.bulk.commit_group;" ::: "memory");
        l2_pre<WSH / 2>(p.wg + b * WSH);
      }
      const float rh = rbf(rs);
      sts128(SM_ST + 16 * (lane & 15), pk_bf(-m, -m), pk_bf(rh, rh), pk_bf(rs - rh, rs - rh), 0);
    }
    TS(5);
  }
  if (kw) {
    float D[5][4] = {};
    u32 ta = ktab + q * 128 + ((g ^ (q << 1)) << 4), tm = ktab + 8192 + q * 16;
#pragma unroll 2
    for (int s = 0; s < 8; s++) {
      const uint4 ca = lds128(ta), cb = lds128(ta + 4096), ma = lds128(tm);
      ta = (ta + 512) ^ 16; tm += 64;
      k2048 += __shfl_xor_sync(~0u, k2048, 16 >> s);
      const C2 s0 = {cb.z, cb.w}, s1 = cm2(s0, {ma.x, ma.y}), s2 = cm2(s0, {ma.z, ma.w}), s3 = cm2(s1, {ma.z, ma.w});
      mma_hf(D[0], s0.re, s1.re, s0.im, s1.im, ca.x, ca.y);
      mma_hf(D[2], s0.re, s1.re, s0.im, s1.im, ca.z, ca.w);
      mma_hf(D[4], s0.re, s1.re, s0.im, s1.im, cb.x, cb.y);
      mma_hf(D[1], s2.re, s3.re, s2.im, s3.im, ca.x, ca.y);
      mma_hf(D[3], s2.re, s3.re, s2.im, s3.im, ca.z, ca.w);
    }
    TS(3);
    const u32 xa = (w < 8 ? SM_MODS + (4 + ksig) * KTAB : SM_ZS) + lane * 16;
    if (khf) {
      __syncwarp();
#pragma unroll
      for (int j = 0; j < 5; j++) sts128(xa + 512 * j, fu(D[j][0]), fu(D[j][1]), fu(D[j][2]), fu(D[j][3]));
      if (lane == 0) sts32(xa + 2560, fu(k2048));
      asm volatile("bar.arrive %0,64;" ::"r"(2 + ksig) : "memory");
    } else {
      const u32 t1 = tp + (q < 2 ? (128 + 4 * g + 2 * q) * 4 : T3 * 4 + ((32 * q - 64 + g) ^ 1) * 2);
      const u32 x = 16 * q + (g >> 1) + hi + 1, tb = tp + (hi ? T7E : T9E) * 4 - 4;
      const u32 te = tb + (x + 2 * (x & 1)) * 2, to = tb + TEO * 4 + (x ^ 1) * 2;
      asm volatile("bar.sync %0,64;" ::"r"(2 + ksig) : "memory");
#pragma unroll
      for (int j = 0; j < 5; j++) { const uint4 t = lds128(xa + 512 * j); D[j][0] += uf(t.x); D[j][1] += uf(t.y); D[j][2] += uf(t.z); D[j][3] += uf(t.w); }
      k2048 = (k2048 + uf(lds32(xa + 2560))) * 0.125f;
#pragma unroll
      for (int r = 0; r < 4; r++) {
        const u32 v = pk_hf(D[2 + (r >> 1)][2 * (r & 1)], D[2 + (r >> 1)][2 * (r & 1) + 1]);
        if (q < 2) {
          const u32 vv = __byte_perm(v, v, 0x1010);
          sts32(t1 + (TO + 32 * r) * 4, vv); sts16(t1 + (TO + 32 * r + 1) * 4 + 2, v >> 16); sts16(t1 + (TO + 32 * r - 1) * 4, v);
          sts64(t1 + (TE + 32 * r) * 4, vv, __byte_perm(v, v, 0x1032));
        } else {
          sts16(t1 + 16 * r, v >> 16);
          if (r == 0 && lane == 2) {
            const u32 vv = __byte_perm(v, v, 0x1010);
            sts32(tp + (TO + 256) * 4, vv); sts16(tp + (TO + 257) * 4 + 2, v); sts16(tp + (TO + 255) * 4, v); sts64(tp + (TE + 256) * 4, vv, vv);
          } else sts16(t1 + 16 * r - ((T3 - T5) * 4 + 6) + 8 * hi, v);
        }
      }
#pragma unroll
      for (int r = 0; r < 2; r++) {
        const u32 v = pk_hf(D[4][2 * r], D[4][2 * r + 1]);
        if (r == 0 && lane == 0) { sts16(tp + T5 * 4 + 62 * 2, v); sts32(SM_KV + 4 * ksig, v & 0xffff); sts16(tp + (T9E + TEO) * 4 + 62 * 2, pk_hf(k2048, 0.f)); }
        else { sts16(te + 8 * r, v); sts16(to + 8 * r, v); }
        sts16(te + 8 * r + 16, v >> 16); sts16(to + 8 * r + 16, v >> 16);
      }
      __syncwarp();
#pragma unroll
      for (int r = 0; r < 4; r++) {
        const u32 v = pk_hf(D[r >> 1][2 * (r & 1) + 1], D[r >> 1][2 * (r & 1)]), t2 = tp + lane * 4 + 128 * r;
        sts32(t2 + TO * 4, v); sts16(t2 + TE * 4, v >> 16); sts16(t2 + (TE + 1) * 4 + 2, v);
      }
      __syncwarp();
    }
  } else if (w == (b < 108 ? 11 : ~0u)) {
    float c[4][4] = {};
    u32 aa = SM_UP + ((lane & 7) + 8 * (lane >> 4)) * 64 + ((((lane >> 3) & 1) ^ ((lane & 7) >> 1)) << 4);
    u32 ba = SM_SIL + (lane >> 3) * 16;
    uint4 a[2][10];
#define GLD(n) { _Pragma("unroll") for (int i = 0; i < 2; i++) { a[n][5 * i] = ldsm4(ba + i * 64); \
      _Pragma("unroll") for (int k = 0; k < 4; k++) a[n][5 * i + 1 + k] = ldsm4t((k & 2 ? aa ^ 32 : aa) + i * 2048 + (k & 1) * 1024); } aa += 4096; ba += 128; }
#define GMM(n) { _Pragma("unroll") for (int i = 0; i < 2; i++) _Pragma("unroll") for (int k = 0; k < 4; k++) { const uint4 f = a[n][5 * i + 1 + k], bb = a[n][5 * i]; \
      mma_bf(c[k], f.x, f.y, f.z, f.w, k & 1 ? bb.z : bb.x, k & 1 ? bb.w : bb.y); } }
    mb_wait(SM_MB);
    TS(56);
    GLD(0);
#pragma unroll 1
    for (int s = 0; s < 4; s++) { GLD(1); GMM(0); GLD(0); GMM(1); }
    GMM(0);
    const float v0 = (q & 1) ? c[0][2] + c[1][2] : c[0][0] + c[1][0], v1 = (q & 1) ? c[2][2] + c[3][2] : c[2][0] + c[3][0];
    str16(gs + (G_MOD + b * 128 + 2 * g + 16 * q), pk_bf(rbf((q & 2) ? v1 : v0) * F2M64, 0.f) | (g < 2 ? pm : 0));
    TS(57);
  }
  TS(6);
  u32 tid2 = tid;
  if (w < 4) {
    asm volatile("setmaxnreg.inc.sync.aligned.u32 232;");
    const u32 tid = tid2 + p.zero, w = tid >> 5, lane = tid & 31, g = lane >> 2, q = lane & 3, hi = g & 1, zr = tid >> 16, tp = SM_TAP + w * TAPS;
    const u32 pml = opq((g & 3) ? 0 : pm);
    const u32 tr = tp + ((hi ? TO : TE) + (g >> 1) - q) * 4;
    u32 T[33][4], B5[5][2], B3[5][2];
#pragma unroll
    for (int d = 0; d < 33; d++) {
      T[d][0] = lds32(tr + 32 * d); T[d][1] = lds32(tr + 32 * d + 16);
      T[d][2] = cpy(d ? T[d - 1][1] : zr, zr, 0); T[d][3] = cpy(T[d][0], zr, 1);
    }
    const u32 t33 = cpy(T[32][1], zr, 0), z33 = cpy(zr, zr, 0);
    const u32 bt = tp + (T5 + g - q) * 4;
#pragma unroll
    for (int d = 0; d < 5; d++) {
      B5[d][0] = lds32(bt + 32 * d); B5[d][1] = lds32(bt + 32 * d - 16);
      B3[d][0] = lds32(bt + 32 * d + (T3 - T5) * 4); B3[d][1] = lds32(bt + 32 * d - 16 + (T3 - T5) * 4);
    }
    u32 za = opq(SM_ZS + 16 + w * ZSS + ((lane >> 3) & 1) * ZPS + ((lane & 7) + (lane >> 4)) * 16);
    u32 wa = opq(SM_W + W5O + w * WSL + row16(lane));
    u32 sa = opq(SM_W + W9O + w * WSL + lane * 16);
    const u32 yo = opq(p.glo + G_Y - 1024 + b * BLK + 256 * q + w * 32 + 4 * g);
    char* yp = gptr(p, yo);
#define YINC() asm volatile("{.reg .u32 l, h; mov.b64 {l,h},%0; add.u32 l,l,1024; mov.b64 %0,{l,h};}" : "+l"(yp))
    const u32 fa = opq(SM_SC + 16 * w + 8), bw = opq((BW >> 4 * w) & 15), bs = opq((BS >> 4 * w) & 15);
    TS(8);
    u32 F;
    bsync(9, 384);
    TS(11);
    float A[4][4] = {};
    uint4 Z[4];
    Z[0] = ldsm4(za); Z[1] = ldsm4(za + 32);
#define STEP(s, b0, b1) { _Pragma("unroll") for (int i = 0; i < 4; i++) mma_hf_t(A[i], T[8 * i + 7 - (s)], b0, b1); }
#define PAIR(n) { Z[(n + 2) & 3] = ldsm4(za + 32 * (n + 2)); STEP(2 * n, Z[n].x, Z[n].y); STEP(2 * n + 1, Z[n].z, Z[n].w); }
#define LAST(N) mma8_hf(N, t33, z33, Z[3].y); float O[4]; mma_hf_o(O, A[0], T[0], Z[3].z, Z[3].w); \
    _Pragma("unroll") for (int i = 0; i < 3; i++) mma_hf_o(A[i], A[i + 1], T[8 * i + 8], Z[3].z, Z[3].w); \
    mma_hf_o(A[3], N, T[32], Z[3].z, Z[3].w);
#pragma unroll 1
    for (int j = 0; j < 4; j++) {
      PAIR(0);
      uint2 fc;
      asm volatile("ld.volatile.shared.v2.u32 {%0,%1},[%2];" : "=r"(fc.x), "=r"(fc.y) : "r"(fa));
      PAIR(1);
      F = __byte_perm(fu(uf(fc.x) * uf(fc.y)), 0, 0x3232);
      PAIR(2);
      Z[1] = ldsm4(za + 160); STEP(6, Z[3].x, Z[3].y);
      float N[4] = {};
      LAST(N);
      inc<128>(za);
      YINC();
      y_store<128>(O[0], O[1], O[2], O[3], F, pml, yp);
      TSJ(j);
    }
    bsyncr(bw);
    uint4 a5 = ldsm4t(wa);
#pragma unroll
    for (int half = 0; half < 2; half++) {
    if (half) bsyncr(bs);
#pragma unroll 1
    for (int j = half ? 8 : 4; j < (half ? 13 : 8); j++) {
      const uint4 a3 = ldsm4t(wa + (W3O - W5O));
      uint4 s3 = {0, 0, 0, 0};
      if (half) s3 = lds128(sa);
      PAIR(0);
      float N[4] = {};
#pragma unroll
      for (int i = 0; i < 4; i++) mma_hf(A[i], a5.x, a5.y, a5.z, a5.w, B5[i][0], B5[i][1]);
      mma_hf(N, a5.x, a5.y, a5.z, a5.w, B5[4][0], B5[4][1]);
      asm volatile("{add.u32 %0,%0,256; xor.b32 %0,%0,32;}" : "+r"(wa));
      a5 = ldsm4t(wa);
      PAIR(1);
#pragma unroll
      for (int i = 0; i < 4; i++) mma_hf(A[i], a3.x, a3.y, a3.z, a3.w, B3[i][0], B3[i][1]);
      mma_hf(N, a3.x, a3.y, a3.z, a3.w, B3[4][0], B3[4][1]);
      PAIR(2);
      Z[1] = ldsm4(za + 160); STEP(6, Z[3].x, Z[3].y);
      LAST(N);
      inc<128>(za);
      if (half) inc<512>(sa);
      YINC();
      if (!half) y_store<128>(O[0], O[1], O[2], O[3], F, pml, yp);
      else y_store<128>(O[0] + uf(s3.x), O[1] + uf(s3.y), O[2] + uf(s3.z), O[3] + uf(s3.w), F, pml, yp);
      TSJ(j);
    }
    }
    {
      asm volatile("mov.u32 %0,%%tid.x;" : "=r"(tid2));
      const uint4 s3 = lds128(sa), s4 = lds128(sa + 512), s5 = lds128(sa + 1024);
      float X[3][4] = {{uf(s4.x), uf(s4.y), uf(s4.z), uf(s4.w)}, {}, {uf(s5.x), uf(s5.y), uf(s5.z), uf(s5.w)}};
#pragma unroll
      for (int ty = 0; ty < 2; ty++) {
        const uint4 a = !ty ? a5 : ldsm4t(wa + ty * (W3O - W5O)), c = ldsm4t((wa ^ 32) + 256 + ty * (W3O - W5O)), d = ldsm4t(wa + 512 + ty * (W3O - W5O));
#pragma unroll
        for (int i = 0; i < 3; i++) mma_hf(A[i], a.x, a.y, a.z, a.w, ty ? B3[i][0] : B5[i][0], ty ? B3[i][1] : B5[i][1]);
#pragma unroll
        for (int i = 0; i < 2; i++) mma_hf(X[i], c.x, c.y, c.z, c.w, ty ? B3[i][0] : B5[i][0], ty ? B3[i][1] : B5[i][1]);
        mma_hf(X[2], d.x, d.y, d.z, d.w, ty ? B3[0][0] : B5[0][0], ty ? B3[0][1] : B5[0][1]);
      }
#pragma unroll
      for (int n = 0; n < 4; n++) {
        const uint4 f0 = n < 2 ? Z[n] : ldsm4(za + 32 * n), f1 = ldsm4(za + 32 * n + 128), f2 = ldsm4(za + 32 * n + 256);
#pragma unroll
        for (int s = 2 * n; s < 2 * n + 2; s++) {
#pragma unroll
          for (int i = 0; i < 3; i++) mma_hf_t(A[i], T[8 * i + 7 - s], s & 1 ? f0.z : f0.x, s & 1 ? f0.w : f0.y);
          mma_hf_t(X[0], T[7 - s], s & 1 ? f1.z : f1.x, s & 1 ? f1.w : f1.y); mma_hf_t(X[1], T[15 - s], s & 1 ? f1.z : f1.x, s & 1 ? f1.w : f1.y);
          mma_hf_t(X[2], T[7 - s], s & 1 ? f2.z : f2.x, s & 1 ? f2.w : f2.y);
        }
      }
      y_store<128>(A[0][0] + uf(s3.x), A[0][1] + uf(s3.y), A[0][2] + uf(s3.z), A[0][3] + uf(s3.w), F, pml, yp + 1024);
      y_store<128>(A[1][0] + X[0][0], A[1][1] + X[0][1], A[1][2] + X[0][2], A[1][3] + X[0][3], F, pml, yp + 2048);
      y_store<128>(A[2][0] + X[1][0] + X[2][0], A[2][1] + X[1][1] + X[2][1], A[2][2] + X[1][2] + X[2][2], A[2][3] + X[1][3] + X[2][3], F, pml, yp + 3072);
    }
    barrive(12, N12);
    TS(15);
  } else {
    asm volatile("setmaxnreg.dec.sync.aligned.u32 136;");
    const u32 t8 = tid - 128, pml = (g & 3) ? 0 : pm;
    {
      TS(12);
      if (tid == 288) l2_pre<WSH / 2>(p.wg + (b * WSH + WSH / 2));
      const char* zs = gs + ((16 * w - 64 + (lane >> 3)) * BLK + b * 128 + ((lane & 7) * 16 ^ rho * 64));
      const char* zs4 = gs + ((t8 >> 1) * BLK + (Ps >> 4) * 512 + (Ps & 6) * 64 + ((Ps >> 2 ^ Ps) & 2) * 32 + (Ps & 1) * 32 + (t8 & 1) * 16);
      uint4 v[5];
      v[4].x = INVAL;
      const u32 d = lane < 4 ? chan(b, lane) : Ps;
      const char* mp = gs + (G_MOD + (d >> 5) * 128 + (d & 24) * 2);
      uint4 ta, tc;
      ta.x = tc.x = INVAL;
      const u32 t9 = w == 9 ? pm : INVAL;
      pin2(zr, zs, zs4);
      conv();
      POLLM({ rld128<TAGM>(ta, mp, t9); rld128<TAGM>(tc, mp + MODJ, t9); rld128<TAGM>(v[4], zs4, pm); }, lop3<0xbe>(v[4].x, pm, ne3(ta.x, tc.x, t9)), TAGM, 1);
      TS(58);
#pragma unroll
      for (int j = 0; j < 4; j++) v[j] = ldr128(zs + j * 4 * BLK);
      if (w == 9) {
        const u32 aw = (d & 4) ? ((d & 2) ? ta.w : ta.z) : ((d & 2) ? ta.y : ta.x & ~TAGM);
        const u32 cw = (d & 4) ? ((d & 2) ? tc.w : tc.z) : ((d & 2) ? tc.y : tc.x & ~TAGM);
        const float sa = ((d & 1) ? bhi(aw) : blo(aw)) * F2P64, c1 = rbf(fmaf((d & 1) ? bhi(cw) : blo(cw), F2P64, 1.f));
        const u32 EM = min(max(fu(fmaxf(32.f * fabsf(c1), fabsf(sa))) >> 23, 80u), 250u);
        const float inv = uf((264 - EM) << 23);
        if (lane < 5) { sts64(SM_SC + 16 * lane, pk_hf(16.f * c1 * inv, 16.f * c1 * inv), pk_hf(sa * inv, sa * inv)); sts32(SM_SC + 16 * lane + 8, (EM - 74) << 23); }
        TS(10);
      }
#define MARKERS() if (tid == 256) { \
        _Pragma("unroll") for (int i = MT / 2; i < 8; i++) bulk_out<2048>(gs + (G_Y + 2048 * i + b * BLK), SM_INV); \
        bulk_out<2048>(gs + (G_PART + b * 2048), SM_INV); bulk_out<512>(gs + (G_ACT + b * 512), SM_INV); \
        bulk_out<32>(gs + (G_KEY + b * KST), SM_INV); if (!rho) bulk_out<128>(gs + (G_ACT + Ps * 128), SM_INV); \
        asm volatile("cp.async.bulk.commit_group;" ::: "memory"); }
#define GATE() { mb_expect(SM_MB + 8, rho ? SLV : 46080); \
        _Pragma("unroll") for (int i = 0; i < 3; i++) tma3d(SM_GATE + 12288 * i, &tm_gate, SM_MB + 8, 32 * b, i); \
        if (!rho) tma3d(SM_GATE + SLV, &tm_gs, SM_MB + 8, 4096 + 4 * b, 0); }
#define UP() { mb_expect(SM_MB + 16, rho ? SLV : 46080); tma3d(SM_UP, &tm_up, SM_MB + 16, 32 * b, 0); \
        if (!rho) tma3d(SM_UP + SLV, &tm_us, SM_MB + 16, 4096 + 4 * b, 0); }
      bsync(8, 256);
      const uint2 cc = lds64(SM_SC + 8 * (t8 & 6)), c4 = lds64(SM_SC + 64);
      sts128(SM_Z4 + 256 + (t8 & 1) * ZP4 + (t8 >> 1) * 16, hfma(v[4].x & ~TAGM, c4.x, c4.y), hfma(v[4].y, c4.x, c4.y), hfma(v[4].z, c4.x, c4.y), hfma(v[4].w, c4.x, c4.y));
      if (t8 < 96) sts128(t8 < 64 ? SM_ZS + (t8 & 7) * ZPS + (t8 >> 3) * 16 : SM_Z4 + (t8 & 1) * ZP4 + (t8 & 30) * 8, 0, 0, 0, 0);
      asm volatile("cp.async.bulk.wait_group.read 0;" ::: "memory");
      const u32 dst = SM_ZS + 128 + (t8 & 7) * ZPS + (16 * w - 64 + (lane >> 3)) * 16;
      pin(zr, dst);
      conv();
      POLLS(_Pragma("unroll") for (int j = 0; j < 4; j++) sts128(dst + j * 64, hfma(v[j].x & ~TAGM, cc.x, cc.y), hfma(v[j].y, cc.x, cc.y), hfma(v[j].z, cc.x, cc.y), hfma(v[j].w, cc.x, cc.y)),
            _Pragma("unroll") for (int j = 0; j < 4; j++) rld128<TAGM>(v[j], zs + j * 4 * BLK, pm), ne3(v[0].x, v[1].x, pm) | ne3(v[2].x, v[3].x, pm), TAGM, 1);
      TS(9);
      bsync(9, 384);
      TS(11);
      MARKERS();
      if (w == 10 && s2u(smem) != SM0) __trap();
      const bool lng = w < 8 || w == 9;
      const u32 ts = lane + 32 * (w == 8 ? 0 : w - 9), c = min(ts, 71u), ma = SM_MODS + 16 * c;
      const u32 sig = lng ? ksig : ts >> 4, l2 = lng ? lane : 32 + (ts & 15);
      const char* mq = gs + (G_MOD + (c >> 2) * 128 + (c & 3) * 16);
      if (!lng) {
#pragma unroll
        for (int j = 0; j < 6; j++) cpa16(ma + 1152 * j, mq + j * MODJ);
        cpa16(ma + 1152 * 6, p.dsk + 16 * c); cpa16(ma + 1152 * 7, p.wr + 16 * c);
        if (tid == 352) {
          PROXY_FENCE();
          GATE();
          UP();
        }
      }
      const u32 wb = SM_W + sig * WSL;
      if (sig < 5) {
        const u32 za = (sig < 4 ? SM_ZS + 128 + sig * ZSS : SM_Z4 + 256) + l2 * 32, zb = za + (sig < 4 ? ZPS : ZP4);
        const uint4 c0 = lds128(zb - 32), c1 = lds128(za - 16), c2 = lds128(zb - 16), c3 = lds128(za), c4 = lds128(zb), c5 = lds128(za + 16), c6 = lds128(zb + 16);
        const u32 P[25] = {c0.z, c0.w, c1.x, c1.y, c1.z, c1.w, c2.x, c2.y, c2.z, c2.w, c3.x, c3.y, c3.z, c3.w, c4.x, c4.y, c4.z, c4.w, c5.x, c5.y, c5.z, c5.w, c6.x, c6.y, c6.z};
        u32 Q[25], D1[24], F4[23], W5[21], W3[17];
#pragma unroll
        for (int j = 1; j < 25; j++) Q[j] = __byte_perm(P[j - 1], P[j], 0x5432);
#pragma unroll
        for (int j = 1; j < 24; j++) D1[j] = hadd(P[j], Q[j]);
#pragma unroll
        for (int j = 2; j < 23; j++) F4[j] = hadd(D1[j], D1[j - 1]);
#pragma unroll
        for (int n = 0; n < 21; n++) W5[n] = hadd(F4[n + 2], P[n]);
#pragma unroll
        for (int n = 0; n < 17; n++) W3[n] = hadd(Q[n + 8], D1[n + 7]);
        const u32 a0 = wb + W5O + 64 * l2 + 16 * ((l2 >> 1) & 3);
#pragma unroll
        for (int i = 0; i < 4; i++) {
          sts128(a0 ^ (16 * i), W5[4 * i + 5], W5[4 * i + 6], W5[4 * i + 7], W5[4 * i + 8]);
          sts128((a0 ^ (16 * i)) + (W3O - W5O), W3[4 * i + 1], W3[4 * i + 2], W3[4 * i + 3], W3[4 * i + 4]);
        }
        if (lng) {
          if (lane < 16) sts128(wb + (lane & 7) * 16 + (lane & 8) * 400, 0, 0, 0, 0);
          const u32 a1 = wb + 32 * lane + 16 * ((lane >> 2) & 1);
#pragma unroll
          for (int i = 0; i < 4; i++) {
            const u32 a = (a1 ^ (16 * (i >> 1))) + 1024 * (i & 1), n = 4 * i;
            sts128(a + V2O, hadd(Q[n + 9], P[n + 8]), hadd(Q[n + 10], P[n + 9]), hadd(Q[n + 11], P[n + 10]), hadd(Q[n + 12], P[n + 11]));
            sts128(a + W9O, hadd(F4[n + 4], W5[n]), hadd(F4[n + 5], W5[n + 1]), hadd(F4[n + 6], W5[n + 2]), hadd(F4[n + 7], W5[n + 3]));
            sts128(a + W7O, hadd(F4[n + 6], W3[n]), hadd(F4[n + 7], W3[n + 1]), hadd(F4[n + 8], W3[n + 2]), hadd(F4[n + 9], W3[n + 3]));
          }
        }
      }
      if (w < 8) barriver((BW >> (4 * w - 16)) & 15);
      else if (!(w & 1)) { barriver((BW >> (4 * w - 32)) & 15); barriver((BW >> (4 * w - 28)) & 15); }
      __syncwarp();
      TS(32);
      if (lng) {
        const u32 wa = wb + ((lane >> 3) & 1) * 1024 + (((lane & 7) ^ (lane >> 4)) + 8 * (lane >> 4)) * 16;
        const u32 kv = lds32(SM_KV + 4 * sig), bi = (g >> 1) == q ? (hi ? kv << 16 : kv) : 0u;
        float acc[8][4] = {};
#pragma unroll
        for (int j = 0; j < 4; j++) { const uint4 a = ldsm4t(wa + V2O + j * 256); mma8_hf(acc[2 * j], a.x, a.y, bi); mma8_hf(acc[2 * j + 1], a.z, a.w, bi); }
        u32 bt = tp + (T9E + hi * TEO + (g >> 1) - q) * 4, wt = wa + W9O;
#pragma unroll 1
        for (int ty = 0; ty < 2; ty++) {
          uint4 a[4];
#pragma unroll
          for (int be = 0; be < 4; be++) a[be] = ldsm4t(wt + be * 256);
          u32 b1 = lds32(bt - 16);
#pragma unroll
          for (int d = 0; d < 8; d++) {
            const u32 b0 = lds32(bt + 16 * d);
#pragma unroll
            for (int be = 0; be < 4; be++) if (d + 2 * be < 8) mma_hf(acc[d + 2 * be], a[be].x, a[be].y, a[be].z, a[be].w, b0, b1);
            b1 = b0;
          }
          bt += (T7E - T9E) * 4; wt += W7O - W9O;
        }
        __syncwarp();
#pragma unroll
        for (int j = 0; j < 8; j++) sts128(wb + W9O + j * 512 + lane * 16, fu(acc[j][0]), fu(acc[j][1]), fu(acc[j][2]), fu(acc[j][3]));
        if (w != 9) barriver((BS >> (4 * w - 16)) & 15);
        TS(34);
      }
      if (!lng) {
        asm volatile("cp.async.wait_all;" ::: "memory");
        uint4 md[6];
#pragma unroll
        for (int j = 0; j < 6; j++) md[j] = lds128(ma + 1152 * j);
        const uint4 dk = lds128(ma + 1152 * 6), wr = lds128(ma + 1152 * 7);
        POLLW(_Pragma("unroll") for (int j = 0; j < 6; j++) md[j] = ldr128(mq + j * MODJ),
              ((md[0].x ^ pm) | (md[1].x ^ pm) | (md[2].x ^ pm) | (md[3].x ^ pm) | (md[4].x ^ pm) | (md[5].x ^ pm)) & TAGM, 4);
#pragma unroll
        for (int j = 0; j < 6; j++) {
          const u32 o = (j % 3 == 1) ? BONE : 0x80008000u;
          md[j] = make_uint4(bfma(md[j].x & ~TAGM, B2P64, o), bfma(md[j].y, B2P64, o), bfma(md[j].z, B2P64, o), bfma(md[j].w, B2P64, o));
          if (j > 2) sts128(ma + 1152 * j, md[j].x, md[j].y, md[j].z, md[j].w);
        }
        const uint4 gd = make_uint4(bmul(md[2].x, dk.x), bmul(md[2].y, dk.y), bmul(md[2].z, dk.z), bmul(md[2].w, dk.w));
#pragma unroll
        for (int j = 0; j < 2; j++) sts128(ma + 1152 * j, bmul(md[j].x, gd.x), bmul(md[j].y, gd.y), bmul(md[j].z, gd.z), bmul(md[j].w, gd.w));
        sts128(ma + 2304, bmul(md[2].x, B2P64), bmul(md[2].y, B2P64), bmul(md[2].z, B2P64), bmul(md[2].w, B2P64));
        const uint4 H = make_uint4(bmul(md[4].x, wr.x), bmul(md[4].y, wr.y), bmul(md[4].z, wr.z), bmul(md[4].w, wr.w));
        sts128(ma + 1152 * 7, H.x, H.y, H.z, H.w);
        sts128(ma + 1152 * 8, bfma(md[4].x, wr.x, H.x ^ 0x80008000u), bfma(md[4].y, wr.y, H.y ^ 0x80008000u), bfma(md[4].z, wr.z, H.z ^ 0x80008000u), bfma(md[4].w, wr.w, H.w ^ 0x80008000u));
        float c4[4] = {};
        mma_bf(c4, md[4].x, md[3].x, md[4].y, md[3].y, wr.x, wr.y); mma_bf(c4, md[4].z, md[3].z, md[4].w, md[3].w, wr.z, wr.w);
        if (q == g >> 1) sts64(SM_RC + (ts >> 2) * 8, fu(hi ? c4[1] : c4[0]), fu(hi ? c4[3] : c4[2]));
        if (ts < 2) sts128(SM_ONE + 16 * ts, ts ? 0 : BONE, ts ? 0 : BONE, ts ? 0 : BONE, ts ? 0 : BONE);
        TS(14);
        if (w == 8) asm volatile("cp.async.bulk.wait_group 0;" ::: "memory");
        bsync(13, 96);
        if (w == 8) { barriver(2); barriver(3); barriver(5); barriver(6); barrive(7, 64); }
      }
      if (w == 9) barrive(11, 128);
    }
    const u32 jw = w < 6 ? w ^ 1 : w < 8 ? w : max(w - 4, 5u);
    const int u0 = 4 * (jw - 4) + 2 * rho;
    const u32 t4 = SM_TAP + 4 * TAPS, s3a = SM_W + 4 * WSL + (u0 >= 8 ? W9O + (u0 - 8) * 512 : V2O) + lane * 16, hb = (0x4987 >> (4 * jw - 16)) & 15;
#define FARL() { u32 wa = (SM_W + 4 * WSL + W5O + row16(lane) + (u0 - 3) * 256) ^ 32, bt = t4 + (T5 + g - q) * 4; \
      _Pragma("unroll 1") for (int al = min(u0 - 2, 6); al > 0; al--) { \
        _Pragma("unroll") for (int ty = 0; ty < 2; ty++) { \
          const uint4 a = ldsm4t(wa + ty * (W3O - W5O)); \
          const u32 bb = bt + ty * (T3 - T5) * 4; \
          mma_hf(acc[ty], a.x, a.y, a.z, a.w, lds32(bb - 32), lds32(bb - 48)); \
          mma_hf(acc[2 + ty], a.x, a.y, a.z, a.w, lds32(bb), lds32(bb - 16)); \
        } \
        wa = (wa - 256) ^ 32; bt += 32; } }
    if (w < 8) {
      u32 tr = t4 + ((hi ? TO : TE) + (g >> 1) - q) * 4;
      u32 zb = SM_Z4 + 256 + ((lane >> 3) & 1) * ZP4 + u0 * 128 + (lane & 7) * 16 + (lane >> 4) * 128;
      float acc[4][4] = {};
      u32 prev = 0;
#pragma unroll 1
      for (int it = min(u0 + 2, 4); it; it--) {
#pragma unroll
        for (int s = 0; s < 8; s++) {
          const uint4 z = ldsm4(zb - 16 * s);
          const u32 t0 = lds32(tr + 32 * s), t1 = lds32(tr + 32 * s + 16);
          mma_hf(acc[s & 1], t0, t1, prev, t0, z.x, z.y);
          mma_hf(acc[2 + (s & 1)], t0, t1, prev, t0, z.z, z.w);
          prev = t1;
        }
        zb -= 128; tr += 256;
      }
      {
        const uint4 z = ldsm4(zb); const u32 t0 = lds32(tr), t1 = lds32(tr + 16);
        mma_hf(acc[0], t0, t1, prev, t0, z.x, z.y); mma_hf(acc[2], t0, t1, prev, t0, z.z, z.w);
        if (jw > 4) { const uint4 y = ldsm4(zb - 16); mma8_hf(acc[1], t1, zr, y.y); mma8_hf(acc[3], t1, zr, y.w); }
      }
      asm volatile("bar.sync %0,64;" ::"r"(hb) : "memory");
      TS(35);
      const uint2 fc = lds64(SM_SC + 16 * 4 + 8);
      const u32 F = __byte_perm(fu(uf(fc.x) * uf(fc.y)), 0, 0x3232);
      char* yp = gs + (G_Y + 16384 + (32 * jw - 128 + 16 * rho + 4 * (q >> 1) + ((b >> 2) & 3)) * BLK + (q & 1) * 1024 + (b & 112) * 4 + (b & 2) * 16 + 4 * g);
#pragma unroll
      for (int j = 0; j < 2; j++) {
        uint4 s3 = {0, 0, 0, 0};
        if (u0 >= 4) s3 = lds128(s3a + j * 512);
        y_store<512>(acc[2 * j][0] + acc[2 * j + 1][0] + uf(s3.x), acc[2 * j][1] + acc[2 * j + 1][1] + uf(s3.y), acc[2 * j][2] + acc[2 * j + 1][2] + uf(s3.z),
                acc[2 * j][3] + acc[2 * j + 1][3] + uf(s3.w), F, pml, yp + j * 8 * BLK);
      }
      TS(16);
    } else {
      if (w != 9) {
        bsync(11, 128);
        float acc[4][4] = {};
        if (u0 >= 8) {
#pragma unroll
          for (int j = 0; j < 2; j++) { const uint4 t = lds128(s3a + j * 512); acc[2 * j][0] = uf(t.x); acc[2 * j][1] = uf(t.y); acc[2 * j][2] = uf(t.z); acc[2 * j][3] = uf(t.w); }
        }
        FARL();
#pragma unroll
        for (int j = 0; j < 2; j++)
          sts128(s3a + j * 512, fu(acc[2 * j][0] + acc[2 * j + 1][0]), fu(acc[2 * j][1] + acc[2 * j + 1][1]), fu(acc[2 * j][2] + acc[2 * j + 1][2]), fu(acc[2 * j][3] + acc[2 * j + 1][3]));
        asm volatile("bar.arrive %0,64;" ::"r"(hb) : "memory");
        TS(16);
      }
      if (tid == 352) { mb_wait(SM_MB + 8); mb_wait(SM_MB + 16); l2_pre<WSH>(p.wd + b * WSH); }
      TS(17);
    }
  }
  post_conv(p, &tm_down, tid2 + p.zero, b, b3);
  TSD();
}

typedef CUresult (*EncFn)(CUtensorMap*, CUtensorMapDataType, cuuint32_t, void*, const cuuint64_t*, const cuuint64_t*, const cuuint32_t*, const cuuint32_t*,
                          CUtensorMapInterleave, CUtensorMapSwizzle, CUtensorMapL2promotion, CUtensorMapFloatOOBfill);
static void make_map(EncFn enc, CUtensorMap* tm, void* ptr, int cols, int rows, int bw, int nb, CUtensorMapSwizzle sw, int gr = 192, int prom = 0) {
  cuuint64_t gd[3] = {(cuuint64_t)cols, (cuuint64_t)gr, (cuuint64_t)(rows / gr)}, gs[2] = {(cuuint64_t)cols * 2, (cuuint64_t)cols * 2 * gr};
  cuuint32_t bd[3] = {(cuuint32_t)bw, (cuuint32_t)gr, (cuuint32_t)nb}, es[3] = {1, 1, 1};
  enc(tm, CU_TENSOR_MAP_DATA_TYPE_BFLOAT16, 3, ptr, gd, gs, bd, es, CU_TENSOR_MAP_INTERLEAVE_NONE, sw, (CUtensorMapL2promotion)prom, CU_TENSOR_MAP_FLOAT_OOB_FILL_NONE);
}
extern "C" void kernel_launch(void* const* d_in, const int* in_sizes, int n_in, void* d_out, int out_size) {
  static EncFn enc = nullptr;
  static void* scratch = nullptr;
  if (!enc) {
    cudaGetSymbolAddress(&scratch, g_s);
    const uintptr_t last = (uintptr_t)scratch + G_END;
    if ((u32)last < G_END) scratch = (void*)(last - (u32)last);
    cudaDriverEntryPointQueryResult qr;
    cudaGetDriverEntryPoint("cuTensorMapEncodeTiled", (void**)&enc, cudaEnableDefault, &qr);
    cudaFuncSetAttribute(fused_kernel, cudaFuncAttributeMaxDynamicSharedMemorySize, SM_TOTAL);
  }
  CUtensorMap tm_mod, tm_gate, tm_gs, tm_up, tm_us, tm_down;
  make_map(enc, &tm_mod, d_in[13], 3456, 576, 32, 3, CU_TENSOR_MAP_SWIZZLE_64B, 192, 0);
  make_map(enc, &tm_gate, d_in[9], 4608, 576, 32, 1, CU_TENSOR_MAP_SWIZZLE_64B, 192, 0);
  make_map(enc, &tm_gs, d_in[9], 4608, 576, 8, 3, CU_TENSOR_MAP_SWIZZLE_NONE);
  make_map(enc, &tm_up, d_in[10], 4608, 576, 32, 3, CU_TENSOR_MAP_SWIZZLE_64B, 192, 0);
  make_map(enc, &tm_us, d_in[10], 4608, 576, 8, 3, CU_TENSOR_MAP_SWIZZLE_NONE, 192, 0);
  make_map(enc, &tm_down, d_in[11], 576, 4608, 64, 1, CU_TENSOR_MAP_SWIZZLE_128B, 96);
  Prm p;
  p.x = (const char*)d_in[0]; p.la = (const char*)d_in[1]; p.ai = (const char*)d_in[2]; p.cr = (const char*)d_in[3];
  p.ci = (const char*)d_in[4]; p.ldt = (const char*)d_in[5]; p.dsk = (const char*)d_in[6]; p.wr = (const char*)d_in[8];
  p.wg = (const char*)d_in[9]; p.wu = (const char*)d_in[10]; p.wd = (const char*)d_in[11];
  p.c = (const char*)d_in[12]; p.out = (char*)d_out; p.zero = 0; p.gs = (char*)scratch; p.glo = (u32)(uintptr_t)scratch; p.ghi = (u32)((uintptr_t)scratch >> 32);
  fused_kernel<<<128, 384, SM_TOTAL>>>(p, tm_mod, tm_gate, tm_gs, tm_up, tm_us, tm_down);
}
```

```cpp
#include <cuda_runtime.h>
#include <cuda.h>
#include <cuda_bf16.h>
#include <cuda_fp16.h>
#include <stdint.h>
#define FUSED 1
#define DEV __device__ __forceinline__
typedef uint32_t u32;

constexpr u32 BLK = 18432, G_Z = 0, G_Y = 128 * BLK, G_MOD = 2 * G_Y, G_KEY = G_MOD + 128 * 128, G_ACT = G_KEY + 128 * 128;
constexpr u32 G_PART = G_ACT + 576 * 128, G_EP = G_PART + 128 * 2048, G_END = G_EP + 128;
__device__ __align__(128) unsigned char g_s[2 * G_END];
#define TS(i)
#define TSJ(j)
#define TS0()
#define TSE()
#define TSD()
#define TSX 0
#define TSN(code, n)
#define ERRF(code)

constexpr int SM0 = 1024;
constexpr int ROW = 1168, SLV = 36864;
constexpr int SM_GATE = SM0, SM_UP = SM_GATE + 46080, SM_XST = SM_UP + 46080, SM_MODS = SM_XST + 16 * ROW, SM_W = SM_MODS + 11008;
constexpr int KTAB = 9216, WSL = 12544, W5O = 128, W3O = 3328, V2O = 6400, W9O = 8448, W7O = 10496;
constexpr int ZPS = 2192, ZSS = 2 * ZPS, ZP4 = 2368;
constexpr int SM_ZS = SM_W + 5 * WSL, SM_Z4 = SM_ZS + 4 * ZSS, SM_TAP = SM_Z4 + 2 * ZP4, TAPS = 3328;
constexpr int SM_MB = SM_TAP + 5 * TAPS;
constexpr int SM_SC = SM_MB + 48;
constexpr int SM_KV = SM_SC + 80;
constexpr int SM_THR = SM_KV + 32;
constexpr int SM_SLOT = SM_THR + 48;
constexpr int SM_KEY = SM_SLOT + 32;
constexpr int SM_ST = SM_KEY + 64;
constexpr int SM_ST2 = SM_ST + 256;
constexpr int SM_RC = SM_ST2 + 256;
constexpr int SM_SP = SM_RC + 192;
constexpr int SM_AF = SM_SP + 1152, SM_SIL = SM_AF + 1152, SM_INV = SM_SIL + 1152, SM_END = SM_SP + 5760;
constexpr int SM_ONE = SM_MODS + 9 * 1152;
constexpr int SM_WD = SM_W, SM_XS = SM_W + 36864, SM_AC = SM_ZS, SM_RED = SM_AC + 6144;
constexpr int SM_TSB = SM_END, SM_TOTAL = SM_END + TSX - SM0;
static_assert(SM_W % 1024 == 0 && SM_TAP % 1024 == 0 && SM_MODS + 8 * KTAB <= SM_ZS && SM_ZS + 2 * KTAB <= SM_TAP && SM_RED + 10240 <= SM_TAP && SM_XS + 8 * ROW <= SM_ZS, "smem map");
static_assert(SM_MB % 16 == 0 && SM_THR % 16 == 0 && SM_ST % 16 == 0 && SM_SP % 16 == 0 && SM_TOTAL <= 232448, "smem map");
constexpr int TE = 4, TO = 276, T5 = 560, T3 = 624, T9E = 680, T7E = 760, TEO = 40;
constexpr int DMOD = 1000, DMOD2 = 2200, YD = 250, KD = 800, KDB = 600, KD1 = 50, PD = 900;
constexpr u32 MT = 10, KST = 32, KE = 64, YL = 104, NB8 = 8;
constexpr int N1 = 352, N12 = 288;
constexpr int SPIN = 1 << 16, NEARLY = 4;
constexpr u32 TAGM = 0x40004000u, TAGR = 0x40000000u, INVAL = 0x00004801u;

DEV u32 s2u(const void* p) { return (u32)__cvta_generic_to_shared(p); }
DEV void mma_bf(float (&c)[4], u32 a0, u32 a1, u32 a2, u32 a3, u32 b0, u32 b1) {
  asm("mma.sync.aligned.m16n8k16.row.col.f32.bf16.bf16.f32 {%0,%1,%2,%3},{%4,%5,%6,%7},{%8,%9},{%0,%1,%2,%3};"
      : "+f"(c[0]), "+f"(c[1]), "+f"(c[2]), "+f"(c[3]) : "r"(a0), "r"(a1), "r"(a2), "r"(a3), "r"(b0), "r"(b1));
}
DEV void mma_hf(float (&c)[4], u32 a0, u32 a1, u32 a2, u32 a3, u32 b0, u32 b1) {
  asm("mma.sync.aligned.m16n8k16.row.col.f32.f16.f16.f32 {%0,%1,%2,%3},{%4,%5,%6,%7},{%8,%9},{%0,%1,%2,%3};"
      : "+f"(c[0]), "+f"(c[1]), "+f"(c[2]), "+f"(c[3]) : "r"(a0), "r"(a1), "r"(a2), "r"(a3), "r"(b0), "r"(b1));
}
DEV void mma8_bf(float (&c)[4], u32 a0, u32 a1, u32 b0) {
  asm("mma.sync.aligned.m16n8k8.row.col.f32.bf16.bf16.f32 {%0,%1,%2,%3},{%4,%5},{%6},{%0,%1,%2,%3};"
      : "+f"(c[0]), "+f"(c[1]), "+f"(c[2]), "+f"(c[3]) : "r"(a0), "r"(a1), "r"(b0));
}
DEV void mma8_hf(float (&c)[4], u32 a0, u32 a1, u32 b0) {
  asm("mma.sync.aligned.m16n8k8.row.col.f32.f16.f16.f32 {%0,%1,%2,%3},{%4,%5},{%6},{%0,%1,%2,%3};"
      : "+f"(c[0]), "+f"(c[1]), "+f"(c[2]), "+f"(c[3]) : "r"(a0), "r"(a1), "r"(b0));
}
DEV u32 movm(u32 x) { u32 r; asm("movmatrix.sync.aligned.m8n8.trans.b16 %0,%1;" : "=r"(r) : "r"(x)); return r; }
DEV void conv() { asm volatile("{.reg .u32 t; mov.u32 t,0; movmatrix.sync.aligned.m8n8.trans.b16 t,t;}"); }
DEV uint4 ldsm4(u32 a) { uint4 r; asm volatile("ldmatrix.sync.aligned.m8n8.x4.shared.b16 {%0,%1,%2,%3},[%4];" : "=r"(r.x), "=r"(r.y), "=r"(r.z), "=r"(r.w) : "r"(a)); return r; }
DEV uint4 ldsm4t(u32 a) { uint4 r; asm volatile("ldmatrix.sync.aligned.m8n8.x4.trans.shared.b16 {%0,%1,%2,%3},[%4];" : "=r"(r.x), "=r"(r.y), "=r"(r.z), "=r"(r.w) : "r"(a)); return r; }
DEV u32 lds32(u32 a) { u32 r; asm volatile("ld.volatile.shared.u32 %0,[%1];" : "=r"(r) : "r"(a)); return r; }
DEV uint2 lds64(u32 a) { uint2 r; asm volatile("ld.shared.v2.u32 {%0,%1},[%2];" : "=r"(r.x), "=r"(r.y) : "r"(a)); return r; }
DEV uint4 lds128(u32 a) { uint4 r; asm volatile("ld.shared.v4.u32 {%0,%1,%2,%3},[%4];" : "=r"(r.x), "=r"(r.y), "=r"(r.z), "=r"(r.w) : "r"(a)); return r; }
DEV void sts16(u32 a, u32 v) { asm volatile("st.shared.u16 [%0],%1;" ::"r"(a), "h"((unsigned short)v) : "memory"); }
DEV void sts32(u32 a, u32 v) { asm volatile("st.shared.u32 [%0],%1;" ::"r"(a), "r"(v) : "memory"); }
DEV void sts64(u32 a, u32 x, u32 y) { asm volatile("st.shared.v2.u32 [%0],{%1,%2};" ::"r"(a), "r"(x), "r"(y) : "memory"); }
DEV void sts128(u32 a, u32 x, u32 y, u32 z, u32 w) { asm volatile("st.shared.v4.u32 [%0],{%1,%2,%3,%4};" ::"r"(a), "r"(x), "r"(y), "r"(z), "r"(w) : "memory"); }
DEV uint4 ldr128(const void* p) { uint4 v; asm volatile("ld.relaxed.gpu.global.v4.u32 {%0,%1,%2,%3},[%4];" : "=r"(v.x), "=r"(v.y), "=r"(v.z), "=r"(v.w) : "l"(p) : "memory"); return v; }
DEV uint2 ldr64(const void* p) { uint2 v; asm volatile("ld.relaxed.gpu.global.v2.u32 {%0,%1},[%2];" : "=r"(v.x), "=r"(v.y) : "l"(p) : "memory"); return v; }
DEV u32 ldr32(const void* p) { u32 v; asm volatile("ld.relaxed.gpu.global.u32 %0,[%1];" : "=r"(v) : "l"(p) : "memory"); return v; }
template <u32 M> DEV void rld128(uint4& v, const void* p, u32 tag) {
  asm volatile("{.reg .pred p; .reg .u32 t; lop3.b32 t,%0,%5,%6,0x28; setp.ne.u32 p,t,0; @p ld.relaxed.gpu.global.v4.u32 {%0,%1,%2,%3},[%4];}"
               : "+r"(v.x), "+r"(v.y), "+r"(v.z), "+r"(v.w) : "l"(p), "r"(tag), "n"(M) : "memory");
}
template <u32 M> DEV void rld64(uint64_t& v, const void* p, u32 tag) {
  asm volatile("{.reg .pred p; .reg .u32 t, h; mov.b64 {t,h},%0; lop3.b32 t,t,%2,%3,0x28; setp.ne.u32 p,t,0; @p ld.relaxed.gpu.global.u64 %0,[%1];}" : "+l"(v) : "l"(p), "r"(tag), "n"(M) : "memory");
}
template <int L> DEV u32 lop3(u32 a, u32 b, u32 c) { u32 r; asm("lop3.b32 %0,%1,%2,%3,%4;" : "=r"(r) : "r"(a), "r"(b), "r"(c), "n"(L)); return r; }
DEV u32 ne3(u32 a, u32 b, u32 c) { u32 r; asm("lop3.b32 %0,%1,%2,%3,0x7e;" : "=r"(r) : "r"(a), "r"(b), "r"(c)); return r; }
DEV void pin(u32 zr, u32 a, u32 b = 0, u32 c = 0, u32 d = 0) { asm volatile("{.reg .pred p; setp.ne.u32 p,%0,0; @p st.shared.v4.u32 [%0],{%1,%2,%3,%4};}" ::"r"(zr), "r"(a), "r"(b), "r"(c), "r"(d) : "memory"); }
DEV void pin2(u32 zr, const void* a, const void* b) { asm volatile("{.reg .pred p; setp.ne.u32 p,%0,0; @p st.shared.v2.u64 [%0],{%1,%2};}" ::"r"(zr), "l"(a), "l"(b) : "memory"); }
DEV void str128(void* p, u32 x, u32 y, u32 z, u32 w) { asm volatile("st.relaxed.gpu.global.v4.u32 [%0],{%1,%2,%3,%4};" ::"l"(p), "r"(x), "r"(y), "r"(z), "r"(w) : "memory"); }
DEV void str64(void* p, u32 x, u32 y) { asm volatile("{.reg .u64 d; mov.b64 d,{%1,%2}; st.relaxed.gpu.global.u64 [%0],d;}" ::"l"(p), "r"(x), "r"(y) : "memory"); }
DEV void str32(void* p, u32 x) { asm volatile("st.relaxed.gpu.global.u32 [%0],%1;" ::"l"(p), "r"(x) : "memory"); }
DEV void str16(void* p, u32 x) { asm volatile("st.relaxed.gpu.global.u16 [%0],%1;" ::"l"(p), "h"((unsigned short)x) : "memory"); }
DEV uint4 ldg128(const void* p) { uint4 v; asm volatile("ld.global.nc.v4.u32 {%0,%1,%2,%3},[%4];" : "=r"(v.x), "=r"(v.y), "=r"(v.z), "=r"(v.w) : "l"(p)); return v; }
DEV uint2 ldg64(const void* p) { uint2 v; asm volatile("ld.global.nc.v2.u32 {%0,%1},[%2];" : "=r"(v.x), "=r"(v.y) : "l"(p)); return v; }
DEV u32 ldg32(const void* p) { u32 v; asm volatile("ld.global.nc.u32 %0,[%1];" : "=r"(v) : "l"(p)); return v; }
DEV u32 ldg16(const void* p) { unsigned short v; asm volatile("ld.global.nc.u16 %0,[%1];" : "=h"(v) : "l"(p)); return v; }
#define bsync(id, n) asm volatile("bar.sync %0,%1;" ::"n"(id), "n"(n) : "memory")
#define barrive(id, n) asm volatile("bar.arrive %0,%1;" ::"n"(id), "n"(n) : "memory")
DEV void bsyncr(u32 id) { asm volatile("bar.sync %0,96;" ::"r"(id) : "memory"); }
DEV void barriver(u32 id) { asm volatile("bar.arrive %0,96;" ::"r"(id) : "memory"); }
constexpr u32 BW = 0x0FEA, BS = 0x6532;
DEV void mb_init(u32 a, u32 n) { asm volatile("mbarrier.init.shared.b64 [%0],%1;" ::"r"(a), "r"(n) : "memory"); }
DEV void mb_arrive(u32 a) { asm volatile("mbarrier.arrive.shared.b64 _,[%0];" ::"r"(a) : "memory"); }
DEV void mb_expect(u32 a, u32 bytes) { asm volatile("mbarrier.arrive.expect_tx.shared.b64 _,[%0],%1;" ::"r"(a), "r"(bytes) : "memory"); }
DEV void mb_wait(u32 a, u32 ph = 0) {
  u32 ok; int it = 0;
  do { asm volatile("{.reg .pred p; mbarrier.try_wait.parity.shared.b64 p,[%1],%2; selp.u32 %0,1,0,p;}" : "=r"(ok) : "r"(a), "r"(ph) : "memory"); } while (!ok && ++it < SPIN);
}
template <int N> DEV void bulk_out(void* dst, u32 src) { asm volatile("cp.async.bulk.global.shared::cta.bulk_group [%0],[%1],%2;" ::"l"(dst), "r"(src), "n"(N) : "memory"); }
constexpr u32 WSH = 41472;
template <int N> DEV void l2_pre(const void* p) { asm volatile("cp.async.bulk.prefetch.L2.global [%0],%1;" ::"l"(p), "n"(N) : "memory"); }
DEV void tma3d(u32 dst, const CUtensorMap* tm, u32 mb, int c0, int c2) {
  asm volatile("cp.async.bulk.tensor.3d.shared::cluster.global.mbarrier::complete_tx::bytes [%0],[%1,{%3,0,%4}],[%2];"
               ::"r"(dst), "l"((uint64_t)tm), "r"(mb), "r"(c0), "r"(c2) : "memory");
}
DEV float blo(u32 w) { return __uint_as_float(w << 16); }
DEV float bhi(u32 w) { return __uint_as_float(w & 0xffff0000u); }
DEV u32 pk_bf(float lo, float hi) { u32 r; asm("cvt.rn.bf16x2.f32 %0,%1,%2;" : "=r"(r) : "f"(hi), "f"(lo)); return r; }
DEV u32 pk_hf(float lo, float hi) { u32 r; asm("cvt.rn.f16x2.f32 %0,%1,%2;" : "=r"(r) : "f"(hi), "f"(lo)); return r; }
DEV float rbf(float x) { return __uint_as_float(pk_bf(0.f, x) & 0xffff0000u); }
DEV u32 bfma(u32 a, u32 b, u32 c) { u32 r; asm("fma.rn.bf16x2 %0,%1,%2,%3;" : "=r"(r) : "r"(a), "r"(b), "r"(c)); return r; }
DEV u32 bmul(u32 a, u32 b) { u32 r; asm("mul.rn.bf16x2 %0,%1,%2;" : "=r"(r) : "r"(a), "r"(b)); return r; }
DEV u32 badd(u32 a, u32 b) { u32 r; asm("add.rn.bf16x2 %0,%1,%2;" : "=r"(r) : "r"(a), "r"(b)); return r; }
DEV u32 hadd(u32 a, u32 b) { u32 r; asm("add.rn.f16x2 %0,%1,%2;" : "=r"(r) : "r"(a), "r"(b)); return r; }
DEV u32 hfma(u32 a, u32 b, u32 c) { u32 r; asm("fma.rn.f16x2 %0,%1,%2,%3;" : "=r"(r) : "r"(a), "r"(b), "r"(c)); return r; }
struct C2 { u32 re, im; };
DEV C2 cm2(C2 a, C2 b) {
  const __half2 ar = *reinterpret_cast<__half2*>(&a.re), ai = *reinterpret_cast<__half2*>(&a.im), br = *reinterpret_cast<__half2*>(&b.re), bi = *reinterpret_cast<__half2*>(&b.im);
  __half2 re = __hfma2(ar, br, __hneg2(__hmul2(ai, bi))), im = __hfma2(ar, bi, __hmul2(ai, br));
  return {*reinterpret_cast<u32*>(&re), *reinterpret_cast<u32*>(&im)};
}
DEV C2 pk2(const float2 (&a)[2]) { return {pk_hf(a[0].x, a[1].x), pk_hf(a[0].y, a[1].y)}; }
DEV C2 pk2c(const float2 (&a)[2]) { return {pk_hf(a[0].x, a[1].x), pk_hf(-a[0].y, -a[1].y)}; }
DEV u32 cpy(u32 x, u32 zr, int alt) {
  u32 r;
  if (alt) asm volatile("xor.b32 %0,%1,%2;" : "=r"(r) : "r"(x), "r"(zr)); else asm volatile("mad.lo.u32 %0,%2,%2,%1;" : "=r"(r) : "r"(x), "r"(zr));
  return r;
}
template <int N> DEV void inc(u32& x) { asm volatile("add.u32 %0,%0,%1;" : "+r"(x) : "n"(N)); }
DEV u32 opq(u32 x) { u32 r; asm volatile("mov.u32 %0,%1;" : "=r"(r) : "r"(x)); return r; }
DEV u32 chan(u32 b, u32 i) { return 16 * (b >> 2) + 2 * (b & 3) + (i & 1) + 4 * (i & 2); }
DEV u32 row16(u32 lane) { const u32 r0 = (lane & 7) + ((lane >> 3) & 1) + 8 * (lane >> 4) - 1; return (r0 ^ ((r0 >> 3) & 3)) * 16; }
DEV u32 clk() { u32 r; asm volatile("mov.u32 %0,%%clock;" : "=r"(r)::"memory"); return r; }
DEV void wait_clk(u32 t, int d) { while ((int)(clk() - t) < d); }
DEV float ex2(float x) { float r; asm("ex2.approx.ftz.f32 %0,%1;" : "=f"(r) : "f"(x)); return r; }
DEV float rcpf(float x) { float r; asm("rcp.approx.ftz.f32 %0,%1;" : "=f"(r) : "f"(x)); return r; }
DEV float2 cmul(float2 a, float2 b) { return make_float2(fmaf(a.x, b.x, -a.y * b.y), fmaf(a.x, b.y, a.y * b.x)); }
DEV float2 csq(float2 a) { return make_float2(fmaf(a.x, a.x, -a.y * a.y), (a.x + a.x) * a.y); }
DEV float2 cexp(float lr2, float th) {
  const float m = ex2(lr2);
  return make_float2(m * __cosf(th), m * __sinf(th));
}
DEV float silu_f(float v) { return v * rcpf(1.f + ex2(-1.4426950408889634f * v)); }
constexpr u32 B2P64 = 0x5F805F80u, B2M64 = 0x1F801F80u, BONE = 0x3F803F80u;
constexpr u32 MODJ = 18 * 128;
DEV float sqrta(float x) { float r; asm("sqrt.approx.ftz.f32 %0,%1;" : "=f"(r) : "f"(x)); return r; }
DEV u32 fu(float x) { return __float_as_uint(x); }
DEV float uf(u32 x) { return __uint_as_float(x); }
DEV void mma_hf_o(float (&d)[4], const float (&c)[4], const u32 (&a)[4], u32 b0, u32 b1) {
  asm("mma.sync.aligned.m16n8k16.row.col.f32.f16.f16.f32 {%0,%1,%2,%3},{%4,%5,%6,%7},{%8,%9},{%10,%11,%12,%13};"
      : "=f"(d[0]), "=f"(d[1]), "=f"(d[2]), "=f"(d[3]) : "r"(a[0]), "r"(a[1]), "r"(a[2]), "r"(a[3]), "r"(b0), "r"(b1), "f"(c[0]), "f"(c[1]), "f"(c[2]), "f"(c[3]));
}

DEV void mma_hf_t(float (&c)[4], const u32 (&a)[4], u32 b0, u32 b1) { mma_hf(c, a[0], a[1], a[2], a[3], b0, b1); }
DEV void cpa16(u32 dst, const void* src) { asm volatile("cp.async.cg.shared.global [%0],[%1],16;" ::"r"(dst), "l"(src) : "memory"); }
DEV void tm_pre(const CUtensorMap* tm) { asm volatile("prefetch.tensormap [%0];" ::"l"((uint64_t)tm) : "memory"); }
#define PROXY_FENCE() asm volatile("fence.proxy.async.shared::cta;" ::: "memory")
struct Prm {
  const char *la, *ai, *cr, *ci, *ldt;
  u32 zero, glo, ghi;
  const char *x, *c;
  char* gs;
  const char *dsk, *wr, *wg, *wu, *wd;
  char* out;
};
DEV char* gptr(const Prm& p, u32 lo) { char* r; asm("mov.b64 %0,{%1,%2};" : "=l"(r) : "r"(lo), "r"(p.ghi)); return r; }
DEV u32 uni(const Prm& p, u32 x) { return x >> p.zero; }
DEV u32 rowo(u32 base, u32 key) { return (~key & 0x1ffc) * 288 + base; }
constexpr float LOG2E = 1.4426950408889634f, F2P64 = 1.8446744073709552e19f, F2M64 = 5.421010862427522e-20f;

template <int S> DEV void y_store(float c0, float c1, float c2, float c3, u32 F, u32 pml, char* yp) {
  str32(yp, bmul(pk_bf(c0, c2), F) | pml);
  str32(yp + S, bmul(pk_bf(c1, c3), F) | pml);
}
DEV u32 sgn2(u32 a, u32 x, u32 y) { return opq(((a - x) >> 31) + ((a - y) >> 31)); }
DEV void merge4(u32 (&h)[8], uint4 a, uint4 b) {
  const u32 e1 = min(a.x, b.x), e2 = max(a.z, b.z), o1 = min(a.y, b.y), o2 = max(a.w, b.w), o0 = max(a.y, b.y), e3 = min(a.z, b.z);
  const u32 f1 = max(e1, e2), f2 = min(e1, e2), p1 = max(o1, o2), p2 = min(o1, o2);
  h[0] = max(a.x, b.x); h[1] = max(o0, f1); h[2] = min(o0, f1); h[3] = max(p1, f2); h[4] = min(p1, f2); h[5] = max(p2, e3); h[6] = min(p2, e3); h[7] = min(a.w, b.w);
}
DEV void top8(u32 (&a)[8], uint4 l, uint4 m) {
  u32 b[8];
  merge4(b, l, m);
#pragma unroll
  for (int i = 0; i < 8; i++) a[i] = max(a[i], b[7 - i]);
#pragma unroll
  for (int s = 4; s; s >>= 1)
#pragma unroll
    for (int i = 0; i < 8; i++) if (!(i & s)) { const u32 x = a[i], y = a[i + s]; a[i] = max(x, y); a[i + s] = min(x, y); }
}
#define POLL(load, cond_bad, code) { int it_ = 0; do { load; } while (__any_sync(~0u, (cond_bad)) & (++it_ <= SPIN)); if (it_ > SPIN) { ERRF(code); } TSN(code, it_); }
DEV u32 tmask(u32 it, u32 m) { u32 r; asm volatile("{.reg .pred p; setp.ne.u32 p,%1,0; selp.u32 %0,%2,0,p;}" : "=r"(r) : "r"(it), "r"(m)); return r; }
#define POLLM(load, bad, M, code) { u32 it_ = SPIN + (tid >> 16), m_; do { m_ = tmask(--it_, M); load; } while (__any_sync(~0u, (bad) & m_)); if (!it_) { ERRF(code); } TSN(code, SPIN - it_); }
#define POLLS(use, load, bad, M, code) { u32 it_ = SPIN + (tid >> 16); for (;;) { const u32 m_ = tmask(--it_, M); use; if (!__any_sync(~0u, (bad) & m_)) break; load; } if (!it_) { ERRF(code); } TSN(code, SPIN - it_); }
#define POLLW(load, cond_bad, code) { int it_ = 0; while (__any_sync(~0u, (cond_bad))) { if (++it_ > SPIN) { ERRF(code); break; } load; } TSN(code, it_); }

#define DOWN(E) if (tid == (b < 108 ? 288 : ~0u)) { const u32 c0 = 64 * (b % 9), c2 = 4 * (b / 9); \
    if (E == 1) { mb_expect(SM_MB + 24, 49152); tma3d(SM_TAP, tm_down, SM_MB + 24, c0, c2); } \
    tma3d(SM_WD + (E - 1) * 12288, tm_down, SM_MB + 24, c0, c2 + E); }
#define OUTR() { const u32 tl = 4 * ((lane >> 1) & 1) + ((lane >> 2) & 3) + 8 * (lane & 1); \
    bulk_out<1152>(p.out + (uni(p, b * BLK) + tl * 1152), SM_XST + ((lane & 2) + 4 * (lane & 1) + ((lane >> 2) & 1) + (lane & 8)) * ROW); \
    asm volatile("cp.async.bulk.commit_group;" ::: "memory"); }
struct FA { u32 tid, ba, ra, sa, ad, as; };
DEV FA ffn_addr(const Prm& p, u32 tid, u32 b) {
  const u32 w = tid >> 5, lane = tid & 31, kq = w & 3, tg = w >> 2, t = 7 - w;
  FA f = {tid, SM_XS + (lane & 7) * ROW + (18 * kq + (lane >> 3)) * 16, SM_RED + (8 * tg + kq) * 512 + lane * 16, w >= uni(p, 3 + (b & 1)) && w < 8 ? SM_RED + t * 2048 + lane * 16 : 0,
          (t < 4 ? uni(p, p.glo + G_ACT + 512 * b) + 128 * t : uni(p, p.glo + G_ACT + (512 + (b >> 1)) * 128)) + lane * 4, uni(p, p.glo + G_ACT + (b / 9) * 6144) + tid * 16};
  pin(tid >> 16, f.ba, f.ra, f.sa, tid); pin(tid >> 16, f.ad, f.as);
  return f;
}
DEV void ffn_tail(const Prm& p, const CUtensorMap* tm_down, uint4 (&A)[24], const FA f, const u32 b, const u32 par, const u32 okl) {
  const u32 tid = f.tid, w = tid >> 5, lane = tid & 31, g = lane >> 2, q = lane & 3, tg = w >> 2, zr = tid >> 16;
  const u32 pm = par ? TAGM : 0, kt = par * 3, ba = f.ba, ra = f.ra;
  char* const gs = p.gs;
  __syncthreads();
  TS(25);
  {
    float c0[2][4] = {}, c1[2][4] = {};
    uint4 bb[5];
#pragma unroll
    for (int s = 0; s < 5; s++) bb[s] = ldsm4(ba + s * 64);
#define BX(s) (s & 1 ? bb[s >> 1].z : bb[s >> 1].x), (s & 1 ? bb[s >> 1].w : bb[s >> 1].y)
    if (tg < 2) {
#pragma unroll
      for (int s = 0; s < 9; s++) {
        mma_bf(c0[s & 1], A[s].x, A[s].y, A[s].z, A[s].w, BX(s));
        mma_bf(c1[s & 1], A[9 + s].x, A[9 + s].y, A[9 + s].z, A[9 + s].w, BX(s));
      }
      sts128(ra + 2048, fu(c1[0][0] + c1[1][0]), fu(c1[0][1] + c1[1][1]), fu(c1[0][2] + c1[1][2]), fu(c1[0][3] + c1[1][3]));
    } else {
      DOWN(3);
#pragma unroll
      for (int s = 0; s < 9; s++) mma_bf(s & 2 ? c1[s & 1] : c0[s & 1], A[s].x, A[s].y, A[s].z, A[s].w, BX(s));
#pragma unroll
      for (int i = 0; i < 4; i++) c0[1][i] += c1[0][i] + c1[1][i];
    }
    sts128(ra, fu(c0[0][0] + c0[1][0]), fu(c0[0][1] + c0[1][1]), fu(c0[0][2] + c0[1][2]), fu(c0[0][3] + c0[1][3]));
  }
  const u32 atag = q ? 0 : pm, acs = SM_AC + tid * 16, acl = SM_AC + lane * 16;
  pin(zr, atag, acs, acl, kt);
  TS(39);
  if (!f.sa) bsync(0, 384);
  else {
    bsync(0, 384);
    float s[4];
    const uint4 u0 = lds128(f.sa), u1 = lds128(f.sa + 512), u2 = lds128(f.sa + 1024), u3 = lds128(f.sa + 1536);
    s[0] = (uf(u0.x) + uf(u1.x)) + (uf(u2.x) + uf(u3.x)); s[1] = (uf(u0.y) + uf(u1.y)) + (uf(u2.y) + uf(u3.y));
    s[2] = (uf(u0.z) + uf(u1.z)) + (uf(u2.z) + uf(u3.z)); s[3] = (uf(u0.w) + uf(u1.w)) + (uf(u2.w) + uf(u3.w));
    const u32 sg = pk_bf(silu_f(rbf(s[0])), silu_f(rbf(s[1])));
    str32(gptr(p, f.ad), bmul(sg, bmul(pk_bf(s[2], s[3]), B2M64)) | atag);
  }
  TS(26);
  const bool fin = w == (b < 72 ? 8 : ~0u);
  u32 kg;
  uint4 xt;
  const char* xs;
  if (fin) { kg = lds32(SM_SLOT + 4 * g); xs = gptr(p, rowo(uni(p, p.glo + G_Y + 16 * b), kg)); xt = ldr128(xs); }
  if (b < 108) {
    const char* const as = gptr(p, f.as);
    uint4 a = ldr128(as);
    char* const dst = gptr(p, uni(p, p.glo + G_PART + b * 2048) + w * 512 + lane * 8);
    if (w < 4) {
      const u32 aa = SM_WD + (8 * (lane >> 4) + (lane & 7)) * 128 + (((2 * w + ((lane >> 3) & 1)) ^ (lane & 7)) << 4);
      mb_wait(SM_MB + 24);
#pragma unroll
      for (int s = 0; s < 24; s++) A[s] = ldsm4t(aa + (s < 6 ? SM_TAP - SM_WD : -12288) + s * 2048);
      pin2(zr, dst, as);
    }
    conv();
    TS(28);
    POLLW(rld128<TAGM>(a, as, pm), (a.x ^ pm) & TAGM, 9);
    sts128(acs, a.x, a.y, a.z, a.w); sts32(acs, a.x & ~TAGM);
    TS(27);
    if (w < 4) {
      bsync(8, 384);
      float c[4][4] = {};
#pragma unroll
      for (int s = 0; s < 12; s++) {
        const uint4 bb = ldsm4t(acl + s * 512);
        mma_bf(c[2 * (s & 1)], A[2 * s].x, A[2 * s].y, A[2 * s].z, A[2 * s].w, bb.x, bb.y);
        mma_bf(c[2 * (s & 1) + 1], A[2 * s + 1].x, A[2 * s + 1].y, A[2 * s + 1].z, A[2 * s + 1].w, bb.z, bb.w);
      }
      u32 o[4];
#pragma unroll
      for (int i = 0; i < 4; i++) o[i] = fu((c[0][i] + c[1][i]) + (c[2][i] + c[3][i]));
      str64(dst, (o[0] & ~3u) | kt, o[1]); str64(dst + 256, (o[2] & ~3u) | kt, o[3]);
      TS(29);
    } else barrive(8, 384);
  }
  if (w == 10 && okl < lds32(SM_SLOT + 28)) OUTR();
  if (fin) {
    const u32 ta = clk();
    const char* src = gptr(p, uni(p, p.glo + G_PART + b * 256) + lane * 8);
    const u32 co = uni(p, 16 * b) + 4 * q, gw = lds32(SM_MODS + 5760 + co), hw = lds32(SM_XS + g * ROW + co);
    const float sgm = rcpf(1.f + ex2(-LOG2E * bhi(kg ^ (~((int)kg >> 31) | 0x80000000))));
    char* const dst = p.out + rowo(co, kg);
    conv();
    POLLW(rld128<TAGM>(xt, xs, TAGR), (xt.x ^ TAGR) & TAGM, 10);
    const u32 x1w = (q & 2) ? ((q & 1) ? xt.w : xt.z) : ((q & 1) ? xt.y : bmul(xt.x ^ TAGR, B2P64));
    const u32 sg2 = bmul(pk_bf(sgm, sgm), B2P64);
    pin(zr, x1w, gw, hw, sg2); pin2(zr, dst, src);
    uint64_t v[12];
#pragma unroll
    for (int j = 0; j < 12; j++) v[j] = 1;
    float s0, s1;
    wait_clk(ta, PD);
    conv();
    TS(13);
#define VL(j) (u32)v[j]
#define VS(j, s) ((uf((u32)(v[j] >> s)) + uf((u32)(v[j + 1] >> s))) + (uf((u32)(v[j + 2] >> s)) + uf((u32)(v[j + 3] >> s))))
    u32 res;
    POLLM({ _Pragma("unroll") for (int j = 0; j < 12; j++) rld64<3>(v[j], src + j * 9 * 2048, kt);
            s0 = VS(0, 0) + VS(4, 0) + VS(8, 0); s1 = VS(0, 32) + VS(4, 32) + VS(8, 32);
            res = opq(badd(x1w, bmul(gw, badd(hw, bmul(movm(pk_bf(s0, s1)), sg2))))); },
          lop3<0xfe>(ne3(VL(0), VL(1), kt), ne3(VL(2), VL(3), kt), ne3(VL(4), VL(5), kt)) |
          lop3<0xfe>(ne3(VL(6), VL(7), kt), ne3(VL(8), VL(9), kt), ne3(VL(10), VL(11), kt)), 3, 11);
    asm volatile("st.global.u32 [%0],%1;" ::"l"(dst), "r"(res) : "memory");
    if (b == 0 && lane == 0) str32(gs + G_EP, par);
    TS(30); TSE();
  }
  if (w == 10) asm volatile("cp.async.bulk.wait_group.read 0;" ::: "memory");
}

DEV u32 y_lo(const Prm& p, u32 tid, u32 b) {
  const u32 ua = uni(p, p.glo + G_Y + b * 128), ub = uni(p, p.glo + 16384 + (b & ~3) * BLK + (b & 3) * 512);
  return (tid < 256 ? ua : ub) + (((tid & 2) * 4) | ((tid >> 2) & 4)) * (tid < 256 ? BLK : 32) + (tid >> 5) * (16 * BLK) + ((tid >> 2) & 3) * 32 + (tid & 1) * 16;
}
DEV void post_conv(const Prm& p, const CUtensorMap* tm_down, const u32 tid, const u32 b, const u32 b3) {
  const u32 w = tid >> 5, lane = tid & 31;
  const u32 g = lane >> 2, q = lane & 3, e = g >> 2, h = (g >> 1) & 1, hi = g & 1;
  const u32 pm = lds32(SM_THR + 4), par = pm >> 30;
  char* const gs = p.gs;
  const u32 cho = 128 * w + 64 * e + 16 * q;
  u32 x1[4][4], h2[4][4], key[4], lt;
  u32 okl = ~0u;
  FA fa;
  uint4 A[24];
#define AROW(t) const u32 arow = 144 * ((t >> 5) & 3) + ((t >> 1) & 8) + (t & 7), ab = (t & 8) ? SM_UP : SM_GATE;
#define AFRAG9() { _Pragma("unroll") for (int s = 0; s < 9; s++) A[s] = ldsm4t(ab + SLV + arow * 16 + s * 256); }
  if (w < 9) {
    const char* const ys = gptr(p, y_lo(p, tid, b));
    uint4 yv[4];
#pragma unroll
    for (int v = 0; v < 4; v++) yv[v].x = INVAL;
    const u32 tg0 = b < YL ? pm : INVAL;
    if (w >= 4) { pin2(tid >> 16, ys, ys); bsync(12, N12); TS(18); }
#pragma unroll
    for (int v = 0; v < 4; v++) rld128<TAGM>(yv[v], ys + v * BLK, tg0);
    const u32 tc = clk();
    const u32 ma = SM_MODS + cho, xa = SM_XST + (2 * h + 4 * hi) * ROW + cho;
    const uint4 sa = lds128(ma), ca = lds128(ma + 1152), ga = lds128(ma + 2304);
    const uint4 rb = lds128((g & 2) ? SM_ONE + 16 * hi : (ma ^ 64) + 8064 + 1152 * hi);
    const u32 saw[4] = {sa.x, sa.y, sa.z, sa.w}, caw[4] = {ca.x, ca.y, ca.z, ca.w}, gaw[4] = {ga.x, ga.y, ga.z, ga.w};
#pragma unroll
    for (int k = 0; k < 4; k++) {
      const uint2 st = lds64(SM_ST + 16 * (2 * h + 4 * hi + (k & 1) + 8 * (k >> 1)));
      const uint4 xv = lds128(xa + ((k & 1) + 8 * (k >> 1)) * ROW);
      x1[k][0] = xv.x; x1[k][1] = xv.y; x1[k][2] = xv.z; x1[k][3] = xv.w;
#pragma unroll
      for (int v = 0; v < 4; v++) x1[k][v] = badd(x1[k][v], bfma(bmul(badd(x1[k][v], st.x), st.y), caw[v], saw[v]));
    }
    const bool own = (q >> 1) == e;
    const u32 spw = SM_SP + (2 * w + e) * 320 + (g & 3) * 16 + (own ? ((q & 1) == h ? 4 : 12) : 8 - 8 * (q & 1));
    if (w < 4) asm volatile("setmaxnreg.dec.sync.aligned.u32 168;");
    if (b >= YL) wait_clk(tc, YD);
    conv();
    TS(13);
    POLLW(_Pragma("unroll") for (int v = 0; v < 4; v++) rld128<TAGM>(yv[v], ys + v * BLK, pm), lop3<0xa8>(ne3(yv[0].x, yv[1].x, pm), ne3(yv[2].x, yv[3].x, pm), TAGM), 5);
    TS(19);
#pragma unroll
    for (int k = 0; k < 4; k += 2) {
      float X[4] = {}, Y[4] = {}, R[4] = {};
#pragma unroll
      for (int v = 0; v < 4; v++) {
        const u32 y0 = k ? yv[v].z : yv[v].x & ~TAGM, y1 = k ? yv[v].w : yv[v].y;
        x1[k][v] = bfma(movm(y0), gaw[v], x1[k][v]);
        x1[k + 1][v] = bfma(movm(y1), gaw[v], x1[k + 1][v]);
        mma8_bf(X, x1[k][v], x1[k + 1][v], x1[k][v]); mma8_bf(Y, x1[k][v], x1[k + 1][v], x1[k + 1][v]);
        if (v & 1) mma_bf(R, x1[k][v - 1], x1[k + 1][v - 1], x1[k][v], x1[k + 1][v], v & 2 ? rb.z : rb.x, v & 2 ? rb.w : rb.y);
      }
      sts32(spw + k * 64, fu(own ? (hi ? X[1] : X[0]) : R[0] + R[1]));
      sts32(spw + k * 64 + 64, fu(own ? (hi ? Y[3] : Y[2]) : R[2] + R[3]));
    }
    barrive(1, N1);
    TS(36);
    asm volatile("setmaxnreg.inc.sync.aligned.u32 168;");
    mb_wait(SM_MB + 8); mb_wait(SM_MB + 16);
    const uint4 sb = lds128(ma + 3456), cb = lds128(ma + 4608), gb = lds128(ma + 5760);
    const u32 sbw[4] = {sb.x, sb.y, sb.z, sb.w}, cbw[4] = {cb.x, cb.y, cb.z, cb.w}, gbw[4] = {gb.x, gb.y, gb.z, gb.w};
    const u32 t3 = opq(tid), zr = t3 >> 16;
    AROW(t3);
    const u32 aa = ab + arow * 64 + ((((t3 >> 6) & 2) ^ ((t3 & 7) >> 1)) << 4), sta = SM_ST2 + 16 * (g & 3);
    const u32 rowl = uni(p, p.glo + b * BLK) + (4 * h + 8 * hi) * 1152 + cho;
    char* const rowp = gptr(p, rowl);
    pin(zr, aa, sta, xa); pin2(zr, rowp, rowp);
    bsync(2, 320);
    TS(37);
    uint4 st[4];
#pragma unroll
    for (int k = 0; k < 4; k++) st[k] = lds128(sta + 64 * k);
    lt = lds32(SM_THR);
#define AFL() { _Pragma("unroll") for (int s = 0; s < 9; s++) { A[s] = ldsm4t(aa + s * 1024); A[9 + s] = ldsm4t((aa ^ 16) + s * 1024); } }
#pragma unroll
    for (int k = 0; k < 4; k++) {
      key[k] = st[k].w;
      u32 o[4];
#pragma unroll
      for (int v = 0; v < 4; v++) {
        const u32 d = badd(x1[k][v], st[k].x), z = bfma(d, st[k].y, bmul(d, st[k].z));
        h2[k][v] = badd(bmul(z, cbw[v]), sbw[v]);
        o[v] = badd(x1[k][v], bmul(gbw[v], h2[k][v]));
      }
      h2[k][0] = bmul(h2[k][0], B2M64) | TAGR; x1[k][0] = bmul(x1[k][0], B2M64) | TAGR;
      if (key[k] >= lt) str128(rowp + k * 1152, h2[k][0], h2[k][1], h2[k][2], h2[k][3]);
      sts128(xa + ((k & 1) + 8 * (k >> 1)) * ROW, o[0], o[1], o[2], o[3]);
    }
    barrive(3, 320);
    TS(21);
    if (w < 8) AFL() else AFRAG9();
    TS(22);
    const u32 rr = tid * 57 >> 12, rc = tid * 16 - rr * 1152, sl = SM_SLOT + 8 * rr;
    const u32 rb_ = p.glo + rc;
    const u32 km = max(max(key[0], key[1]), max(key[2], key[3])), xd = SM_XS + rr * (2 * ROW) + rc;
    pin(tid >> 16, sl, km, xd); pin(tid >> 16, rb_, rowl);
    fa = ffn_addr(p, tid | p.zero, b);
    bsync(6, 320);
    TS(24);
    const uint2 sk = lds64(sl);
    const char *r0 = gptr(p, rowo(rb_, sk.x)), *r1 = gptr(p, rowo(rb_, sk.y));
    uint4 rv[2] = {ldr128(r0), ldr128(r1)};
    barrive(15, 320);
    const u32 g8 = lds32(SM_SLOT + 28);
    if (__any_sync(~0u, km >= g8 && lt > g8)) {
      char* const rowq = gptr(p, opq(rowl));
#pragma unroll
      for (int k = 0; k < 4; k++) if (key[k] >= g8 && key[k] < lt) str128(rowq + k * 1152, h2[k][0], h2[k][1], h2[k][2], h2[k][3]);
    }
    bsync(5, 320);
    const uint2 sf = lds64(sl);
    const u32 f8 = lds32(SM_SLOT + 28);
    if (__any_sync(~0u, km >= f8)) {
      char* const rowq = gptr(p, opq(rowl));
#pragma unroll
      for (int k = 0; k < 4; k++) if (key[k] >= f8) str128(rowq + (G_Y + k * 1152), x1[k][0], x1[k][1], x1[k][2], x1[k][3]);
    }
    if (__any_sync(~0u, sf.x != sk.x || sf.y != sk.y)) {
      r0 = gptr(p, rowo(rb_, sf.x)); r1 = gptr(p, rowo(rb_, sf.y));
      rv[0].x = rv[1].x = INVAL;
    }
    POLLS(_Pragma("unroll") for (int j = 0; j < 2; j++) { sts128(xd + j * ROW, rv[j].x, rv[j].y, rv[j].z, rv[j].w); sts32(xd + j * ROW, bmul(rv[j].x ^ TAGR, B2P64)); },
          { rld128<TAGM>(rv[0], r0, TAGR); rld128<TAGM>(rv[1], r1, TAGR); }, ne3(rv[0].x, rv[1].x, TAGR), TAGM, 8);
    TS(38);
  } else {
    u32 ok, lr;
    if (w == 10) {
      uint2 rc = lds64(SM_RC + 8 * min(lane, 17u));
      float r1 = lane < 18 ? uf(rc.x) : 0.f, r2 = lane < 18 ? uf(rc.y) : 0.f;
#pragma unroll 1
      for (int o = 16; o; o >>= 1) { r1 += __shfl_xor_sync(~0u, r1, o); r2 += __shfl_xor_sync(~0u, r2, o); }
      const u32 tl = 4 * ((lane >> 1) & 1) + ((lane >> 2) & 3) + 8 * (lane & 1), kl = (2047 - 16 * b - tl) << 2 | par * 3;
      const u32 kp = uni(p, p.glo + G_KEY + b * KST) + (tid >> 16);
      const u32 spr = SM_SP + (lane >> 4) * 9 * 320 + (lane & 15) * 16;
      TS(31);
      r2 += 0.f;
      const u32 nth = b < NB8 ? 7 : NEARLY - 1, ka = SM_KEY + 4 * (lane & 15), kb = SM_KEY + 2 * (lane & 16), lim = lane < 16 ? 8 : 0;
      pin(tid >> 16, kl, ka, kb, lim); pin(tid >> 16, kp);
      conv();
      bsync(1, N1);
      uint4 t = lds128(spr);
      float S1 = uf(t.x), S2 = uf(t.y), S3 = uf(t.z);
#pragma unroll
      for (int i = 1; i < 9; i++) { t = lds128(spr + i * 320); S1 += uf(t.x); S2 += uf(t.y); S3 += uf(t.z); }
      S1 += __shfl_xor_sync(~0u, S1, 16); S2 += __shfl_xor_sync(~0u, S2, 16); S3 += __shfl_xor_sync(~0u, S3, 16);
      const float mu = S1 * (1.f / 576.f), var = fmaxf(fmaf(-mu, mu, S2 * (1.f / 576.f)), 0.f);
      const float m = rbf(mu), rs = rcpf(rbf(sqrta(rbf(rbf(var) + 1e-5f))));
      const u32 rb = pk_bf(0.f, fmaf(fmaf(-m, r1, S3), rs, r2));
      ok = ((rb ^ (((int)rb >> 31) | 0x80000000)) & 0xffff0000u) | kl;
      const float rh = rbf(rs);
      const u32 oh = ok >> 1;
      sts32(ka, oh);
      __syncwarp();
      const uint4 o0 = lds128(kb), o1 = lds128(kb + 16);
      sts128(SM_ST2 + 16 * (lane & 15), pk_bf(-m, -m), pk_bf(rh, rh), pk_bf(rs - rh, rs - rh), ok);
      lr = opq(sgn2(oh, o0.x, o0.y) + sgn2(oh, o0.z, o0.w)) +
           opq(sgn2(oh, o1.x, o1.y) + sgn2(oh, o1.z, o1.w));
      lr += __shfl_xor_sync(~0u, lr, 16);
      asm volatile("{.reg .pred p; setp.lt.u32 p,%0,%1; @p st.relaxed.gpu.global.u32 [%2],%3;}" ::"r"(lr), "r"(lim), "l"(gptr(p, kp + 4 * lr)), "r"(ok) : "memory");
      if (lr == nth) sts32(SM_THR, ok);
      barrive(2, 320);
      barrive(13, 64);
      TS(20);
    } else if (w == 9) {
      bsync(1, N1);
      PROXY_FENCE();
      DOWN(1);
    } else {
      const char* ks = gs + (G_KEY + (lane >> 1) * KST + (lane & 1) * 16);
      const u32 kt = par * 3;
      uint4 L[8];
      u32 H[8];
#define KBAD(j) ((L[j].x ^ kt) & 3)
#define KLD(j) L[j] = ldr128(ks + j * 16 * KST)
#pragma unroll
      for (int j = 0; j < 8; j++) L[j].x = INVAL;
      bsync(13, 64);
      wait_clk(clk(), b < KE ? KD : b < YL ? KDB : KD1);
      TS(34);
      POLL({ _Pragma("unroll") for (int j = 0; j < 8; j++) if (KBAD(j)) KLD(j);
             merge4(H, L[0], L[1]); top8(H, L[2], L[3]);
             asm volatile("" : "+r"(H[0]), "+r"(H[1]), "+r"(H[2]), "+r"(H[3]), "+r"(H[4]), "+r"(H[5]), "+r"(H[6]), "+r"(H[7])); TS(32); },
           KBAD(0) | KBAD(1) | KBAD(2) | KBAD(3) | KBAD(4) | KBAD(5), 6);
      u32 u = __reduce_max_sync(~0u, max(H[0], max(L[4].x, L[5].x)));
      top8(H, L[4], L[5]);
      TS(35);
      u32 m[8], x0 = H[0], x1 = H[1];
#pragma unroll
      for (int r = 0; r < 8; r++) {
        const u32 ur = u;
        const bool win = x0 == ur;
        if (r < 7) { x0 = max(x0 - ur, x1 - ur); u = __reduce_max_sync(~0u, x0); }
        m[r] = r ? m[r - 1] + ur : ur;
        if (r == 0) { if (KBAD(6)) KLD(6); if (KBAD(7)) KLD(7); }
#pragma unroll
        for (int i = 1; i < 7 - r; i++) H[i] = win ? H[i + 1] : H[i];
        x1 = H[1] - m[r];
        if ((r & 3) == 3) sts128(SM_SLOT + 4 * r - 12, m[r - 3], m[r - 2], m[r - 1], m[r]);
      }
      barrive(6, 320);
      TS(23);
      conv();
      POLLW({ if (KBAD(6)) KLD(6); if (KBAD(7)) KLD(7); }, KBAD(6) | KBAD(7), 7);
      conv();
      u = __reduce_max_sync(~0u, max(L[6].x, L[7].x));
      if (u > m[7]) {
        do {
          const u32 x = u;
          if (L[6].x == x) L[6] = make_uint4(L[6].y, L[6].z, L[6].w, 0);
          if (L[7].x == x) L[7] = make_uint4(L[7].y, L[7].z, L[7].w, 0);
          u = __reduce_max_sync(~0u, max(L[6].x, L[7].x));
#pragma unroll
          for (int i = 7; i; i--) m[i] = max(min(m[i - 1], x), m[i]);
          m[0] = max(m[0], x);
        } while (u > m[7]);
        sts128(SM_SLOT, m[0], m[1], m[2], m[3]); sts128(SM_SLOT + 16, m[4], m[5], m[6], m[7]);
      }
      barrive(5, 320);
      TS(33);
    }
    asm volatile("setmaxnreg.inc.sync.aligned.u32 168;");
    mb_wait(SM_MB + 8); mb_wait(SM_MB + 16);
    AROW(tid);
    AFRAG9();
    fa = ffn_addr(p, tid | p.zero, b);
    TS(22);
    if (w == 10) {
      bsync(3, 320);
      PROXY_FENCE();
      if (lane < 16 && lr >= 8) OUTR();
      if (lane < 16 && lr < 8) okl = ok;
    } else if (w == 9) {
      bsync(15, 320);
      DOWN(2);
      TS(13);
    }
  }
  ffn_tail(p, tm_down, A, fa, b3, par, okl);
}

__global__ void __launch_bounds__(384, 1)
fused_kernel(const Prm p, const __grid_constant__ CUtensorMap tm_mod, const __grid_constant__ CUtensorMap tm_gate, const __grid_constant__ CUtensorMap tm_gs,
             const __grid_constant__ CUtensorMap tm_up, const __grid_constant__ CUtensorMap tm_us, const __grid_constant__ CUtensorMap tm_down) {
  extern __shared__ __align__(1024) unsigned char smem[];
  u32 la, ai, ldt; uint2 cr, ci;
  {
    const u32 t = threadIdx.x, d = t < 256 ? chan(blockIdx.x, t >> 5) : 512 + (blockIdx.x >> 1), o = d * 256 + 8 * (t & 31), o4 = o + ((t < 256 ? t >> 5 : t >> 3) & 4);
    asm volatile("{.reg .pred p; .reg .u16 h; setp.ne.u32 p,%7,0; @p ld.global.nc.u32 %0,[%8]; @p ld.global.nc.u32 %1,[%9]; @p ld.global.nc.v2.u32 {%2,%3},[%10];"
                 "@p ld.global.nc.v2.u32 {%4,%5},[%11]; @p ld.global.nc.u16 h,[%12]; cvt.u32.u16 %6,h;}"
                 : "=r"(la), "=r"(ai), "=r"(cr.x), "=r"(cr.y), "=r"(ci.x), "=r"(ci.y), "=r"(ldt)
                 : "r"(0x6ffu >> (t >> 5) & 1), "l"(p.la + o4), "l"(p.ai + o4), "l"(p.cr + o), "l"(p.ci + o), "l"(p.ldt + 2 * d));
  }
  const u32 t0 = clk();
  const u32 tid = __shfl_sync(~0u, threadIdx.x, threadIdx.x & 31), b = blockIdx.x + p.zero;
  const u32 w = tid >> 5, lane = tid & 31;
  const u32 g = lane >> 2, q = lane & 3, hi = g & 1;
  const u32 rho = b & 1, Ps = 512 + (b >> 1);
  char* const gs = p.gs;
  TS0();
  const bool kw = w != 8 && w != 11;
  const u32 ksig = w < 8 ? (w & 3) : 4, khf = w < 8 ? (w >> 2) : (w & 1);
  if (!kw) {
    if (tid == 352) {
#pragma unroll
      for (int i = 0; i < 5; i++) mb_init(SM_MB + 8 * i, i < 4 ? 1 : 64);
      asm volatile("fence.mbarrier_init.release.cluster;" ::: "memory");
      tm_pre(&tm_mod);
    }
    const char* cp = p.c + (576 * (w & 1) + 24 * min(lane, 23u));
    const uint2 c0 = ldg64(cp);
    la = c0.x; ai = c0.y; cr = ldg64(cp + 8); ci = ldg64(cp + 16);
  }
  u32 b3;
  asm volatile("shr.u32 %0,%1,%2;" : "=r"(b3) : "r"(blockIdx.x), "r"(p.zero));
  const u32 zr = tid >> 16;
  const u32 epv = ldr32(gs + (G_EP + zr));
  const u32 tp = SM_TAP + ksig * TAPS;
  if (kw && !khf) {
#pragma unroll 1
    for (u32 i = lane * 16; i < TAPS; i += 512) sts128(tp + i, 0, 0, 0, 0);
  }
  if (tid < 128) sts128(SM_INV + 16 * tid, INVAL, 0, 1, 0);
  if (tid >= 124) str128(gs + (tid >= 380 ? G_MOD + b * 128 + q * 16 : b * BLK + 16384 - 252 * 16 + tid * 16 + (tid < 252 ? G_Y + 2048 : 0)), INVAL, 0, 1, 0);
  if (tid == (b < 36 ? 352 : ~0u)) { while (clk() - t0 < DMOD); mb_expect(SM_MB, 36864); tma3d(SM_UP, &tm_mod, SM_MB, 32 * b, 0); }
  if (w < 9) {
    while ((int)(clk() - t0) < 0);
    const char* xp = p.x + (b * BLK + (lane >> 3) * 1152 + 128 * w + 16 * (lane & 7));
    const u32 xd = SM_XST + (((lane >> 3) & 1) + 8 * (lane >> 4)) * ROW + 128 * w + 16 * (lane & 7);
#pragma unroll
    for (int i = 0; i < 4; i++) cpa16(xd + 2 * ROW * i, xp + 4608 * i);
  }
  const u32 ktab = w < 8 ? SM_MODS + w * KTAB : SM_ZS + (w - 9) * KTAB;
  float k2048 = 0.f;
  if (kw) {
    u32 mx = __vmaxu2(__vmaxu2(cr.x & 0x7fff7fff, cr.y & 0x7fff7fff), __vmaxu2(ci.x & 0x7fff7fff, ci.y & 0x7fff7fff));
    const u32 E = max(__reduce_max_sync(~0u, max(mx & 0xffff, mx >> 16)) >> 7, 8u);
    TS(1);
    const float dt = rbf(ex2(blo(ldt) * LOG2E)), csc = uf((257 - E) << 23 | (fu(dt) & 0x7fffff));
    sts32(SM_SC + 16 * ksig + 12, fu(uf(fu(dt) & 0x7f800000) * uf((E - 2) << 23)));
    const u32 crw = khf ? cr.y : cr.x, ciw = khf ? ci.y : ci.x;
    float2 C[2], w4[2], w8[2], w16[2], w32[2], w64[2], w128[2], w256[2], w512[2], a1[2], a2[2], a3[2], t0[2], t1[2], s3[2];
#pragma unroll
    for (int m = 0; m < 2; m++) {
      const float lr2 = rbf(ex2((m ? bhi(la) : blo(la)) * LOG2E)) * dt * -LOG2E, th = (m ? bhi(ai) : blo(ai)) * dt;
      C[m] = make_float2((m ? bhi(crw) : blo(crw)) * csc, (m ? bhi(ciw) : blo(ciw)) * csc);
      const float2 w1 = cexp(lr2, th), w2 = csq(w1);
      w64[m] = cexp(64.f * lr2, 64.f * th);
      w4[m] = csq(w2); w8[m] = csq(w4[m]); w16[m] = csq(w8[m]); w32[m] = csq(w16[m]);
      w128[m] = csq(w64[m]); w256[m] = csq(w128[m]); w512[m] = csq(w256[m]);
      const float2 w1024 = csq(w512[m]);
      a1[m] = cmul(C[m], w1); a2[m] = cmul(C[m], w2); a3[m] = cmul(a1[m], w2);
      t0[m] = cmul(C[m], w1024); t1[m] = cmul(t0[m], w128[m]); s3[m] = cmul(w8[m], w16[m]);
      k2048 += fmaf(t0[m].x, w1024.x, -t0[m].y * w1024.y);
    }
    C2 B0[8], B1[8], B2[8], S[8];
    B0[0] = pk2(C); B0[1] = pk2(a1); B0[2] = pk2(a2); B0[3] = pk2(a3);
    const C2 h4 = pk2(w4), h256 = pk2(w256), h512 = pk2(w512);
#pragma unroll
    for (int i = 0; i < 4; i++) B0[4 + i] = cm2(B0[i], h4);
#pragma unroll
    for (int i = 0; i < 4; i++) B1[i] = cm2(B0[2 * i], h256);
    B1[4] = cm2(B0[0], h512); B1[5] = cm2(B0[4], h512);
    B1[6] = cm2(B1[4], h256); B1[7] = cm2(B1[5], h256);
    const u32 ta = ktab + lane * 128, f = ((lane & 3) << 5) | ((lane & 4) << 2);
#pragma unroll
    for (int i = 0; i < 8; i++) sts128(ta + ((i << 4) ^ f), B0[i].re, B0[i].im, B1[i].re, B1[i].im);
    B2[0] = pk2(t0); B2[1] = pk2(t1);
    B2[2] = cm2(B2[0], h256); B2[3] = cm2(B2[1], h256);
#pragma unroll
    for (int i = 0; i < 4; i++) B2[4 + i] = cm2(B2[i], h512);
    S[0] = {0x3C003C00u, 0u}; S[1] = pk2c(w8); S[2] = pk2c(w16); S[3] = pk2c(s3); S[4] = pk2c(w32);
#pragma unroll
    for (int i = 1; i < 4; i++) S[4 + i] = cm2(S[i], S[4]);
#pragma unroll
    for (int i = 0; i < 8; i++) sts128(ta + 4096 + ((i << 4) ^ f), B2[i].re, B2[i].im, S[i].re, S[i].im);
    const C2 m64 = pk2c(w64), m128 = pk2c(w128);
    sts128(ktab + 8192 + lane * 16, m64.re, m64.im, m128.re, m128.im);
    __syncwarp();
  } else {
    u32 sa = SM_SIL + 576 * (w & 1) + 24 * min(lane, 23u);
#pragma unroll 1
    for (int j = 0; j < 6; j++) {
      sts32(sa, pk_bf(silu_f(blo(la)), silu_f(bhi(la))));
      la = ai; ai = cr.x; cr.x = cr.y; cr.y = ci.x; ci.x = ci.y; sa += 4;
    }
    bsync(7, 64);
  }
  TS(2);
  const u32 pm = (__reduce_or_sync(~0u, epv) & 1) ? 0 : TAGM;
  sts32(SM_THR + 4, pm);
  if (w >= 9) {
    if (tid == (b - 36 < 72 ? 352 : ~0u)) { while (clk() - t0 < DMOD2); mb_expect(SM_MB, 36864); tma3d(SM_UP, &tm_mod, SM_MB, 32 * b, 0); }
    __syncwarp();
  } else {
    const u32 xa = SM_XST + (lane & 15) * ROW + 128 * w + 16 * (lane >> 4);
    pin(zr, xa);
    asm volatile("cp.async.wait_all;" ::: "memory");
    __syncwarp();
    TS(4);
    float s[4] = {}, X[2][4] = {}, Y[2][4] = {};
#pragma unroll
    for (int j = 0; j < 4; j++) {
      const uint4 a = ldsm4(xa + 32 * j);
      mma8_bf(X[0], a.x, a.y, a.x); mma8_bf(Y[0], a.x, a.y, a.y);
      mma8_bf(X[1], a.z, a.w, a.z); mma8_bf(Y[1], a.z, a.w, a.w);
      mma_bf(s, a.x, a.y, a.z, a.w, BONE, BONE);
    }
    uint4 t[4];
#pragma unroll
    for (int j = 0; j < 4; j++) t[j] = ldsm4t(xa + 32 * j);
    const float u0 = hi ? X[0][1] + X[1][1] : X[0][0] + X[1][0], u1 = hi ? Y[0][3] + Y[1][3] : Y[0][2] + Y[1][2];
    if (q == g >> 1) sts128(SM_SP + w * 128 + g * 16, fu(s[0]), fu(u0), fu(s[2]), fu(u1));
    bsync(1, 288);
    TS(7);
    const u32 spr = SM_SP + (lane & 7) * 16 + (lane & 8);
    const uint2 t8 = lds64(spr + 1024);
    const float f8 = lane < 16 ? 1.f : 0.f;
    float S1 = uf(t8.x) * f8, S2 = uf(t8.y) * f8;
#pragma unroll
    for (int i = 0; i < 4; i++) { const uint2 u = lds64(spr + (lane & 16) * 32 + i * 128); S1 += uf(u.x); S2 += uf(u.y); }
    S1 += __shfl_xor_sync(~0u, S1, 16); S2 += __shfl_xor_sync(~0u, S2, 16);
    const float mu = S1 * (1.f / 576.f), var = fmaxf(fmaf(-mu, mu, S2 * (1.f / 576.f)), 0.f);
    const float m = rbf(mu), rs = rcpf(rbf(sqrta(rbf(rbf(var) + 1e-5f))));
    const float ra = rs * 0.0625f;
    sts64(SM_AF + w * 128 + (lane & 15) * 8, fu(ra), fu(-m * ra));
    __syncwarp();
    TS(55);
    const uint4 f0 = lds128(SM_AF + w * 128 + q * 16), f1 = lds128(SM_AF + w * 128 + 64 + q * 16);
    const u32 zdst = SM_GATE + w * 2048 + (g >> 1) * 128 + (lane & 15) * 8;
    const u32 pz = (q & 1) ? 0 : pm;
#pragma unroll
    for (int j = 0; j < 8; j++) {
      const u32 x0 = j & 1 ? t[j >> 1].z : t[j >> 1].x, x1 = j & 1 ? t[j >> 1].w : t[j >> 1].y;
      sts64((j & 1 ? zdst ^ 64 : zdst) + 512 * (j >> 1), pk_hf(fmaf(blo(x0), uf(f0.x), uf(f0.y)), fmaf(bhi(x0), uf(f0.z), uf(f0.w))) | pz,
            pk_hf(fmaf(blo(x1), uf(f1.x), uf(f1.y)), fmaf(bhi(x1), uf(f1.z), uf(f1.w))));
    }
    TS(53);
    if (w < 8) barrive(15, 288);
    else {
      bsync(15, 288);
      TS(54);
      if (lane == 0) {
        PROXY_FENCE();
        bulk_out<BLK>(gs + b * BLK, SM_GATE);
        asm volatile("cp.async.bulk.commit_group;" ::: "memory");
        l2_pre<WSH / 2>(p.wg + b * WSH);
      }
      const float rh = rbf(rs);
      sts128(SM_ST + 16 * (lane & 15), pk_bf(-m, -m), pk_bf(rh, rh), pk_bf(rs - rh, rs - rh), 0);
    }
    TS(5);
  }
  if (kw) {
    float D[5][4] = {};
    u32 ta = ktab + q * 128 + ((g ^ (q << 1)) << 4), tm = ktab + 8192 + q * 16;
#pragma unroll 2
    for (int s = 0; s < 8; s++) {
      const uint4 ca = lds128(ta), cb = lds128(ta + 4096), ma = lds128(tm);
      ta = (ta + 512) ^ 16; tm += 64;
      k2048 += __shfl_xor_sync(~0u, k2048, 16 >> s);
      const C2 s0 = {cb.z, cb.w}, s1 = cm2(s0, {ma.x, ma.y}), s2 = cm2(s0, {ma.z, ma.w}), s3 = cm2(s1, {ma.z, ma.w});
      mma_hf(D[0], s0.re, s1.re, s0.im, s1.im, ca.x, ca.y);
      mma_hf(D[2], s0.re, s1.re, s0.im, s1.im, ca.z, ca.w);
      mma_hf(D[4], s0.re, s1.re, s0.im, s1.im, cb.x, cb.y);
      mma_hf(D[1], s2.re, s3.re, s2.im, s3.im, ca.x, ca.y);
      mma_hf(D[3], s2.re, s3.re, s2.im, s3.im, ca.z, ca.w);
    }
    TS(3);
    const u32 xa = (w < 8 ? SM_MODS + (4 + ksig) * KTAB : SM_ZS) + lane * 16;
    if (khf) {
      __syncwarp();
#pragma unroll
      for (int j = 0; j < 5; j++) sts128(xa + 512 * j, fu(D[j][0]), fu(D[j][1]), fu(D[j][2]), fu(D[j][3]));
      if (lane == 0) sts32(xa + 2560, fu(k2048));
      asm volatile("bar.arrive %0,64;" ::"r"(2 + ksig) : "memory");
    } else {
      const u32 t1 = tp + (q < 2 ? (128 + 4 * g + 2 * q) * 4 : T3 * 4 + ((32 * q - 64 + g) ^ 1) * 2);
      const u32 x = 16 * q + (g >> 1) + hi + 1, tb = tp + (hi ? T7E : T9E) * 4 - 4;
      const u32 te = tb + (x + 2 * (x & 1)) * 2, to = tb + TEO * 4 + (x ^ 1) * 2;
      asm volatile("bar.sync %0,64;" ::"r"(2 + ksig) : "memory");
#pragma unroll
      for (int j = 0; j < 5; j++) { const uint4 t = lds128(xa + 512 * j); D[j][0] += uf(t.x); D[j][1] += uf(t.y); D[j][2] += uf(t.z); D[j][3] += uf(t.w); }
      k2048 = (k2048 + uf(lds32(xa + 2560))) * 0.125f;
#pragma unroll
      for (int r = 0; r < 4; r++) {
        const u32 v = pk_hf(D[2 + (r >> 1)][2 * (r & 1)], D[2 + (r >> 1)][2 * (r & 1) + 1]);
        if (q < 2) {
          const u32 vv = __byte_perm(v, v, 0x1010);
          sts32(t1 + (TO + 32 * r) * 4, vv); sts16(t1 + (TO + 32 * r + 1) * 4 + 2, v >> 16); sts16(t1 + (TO + 32 * r - 1) * 4, v);
          sts64(t1 + (TE + 32 * r) * 4, vv, __byte_perm(v, v, 0x1032));
        } else {
          sts16(t1 + 16 * r, v >> 16);
          if (r == 0 && lane == 2) {
            const u32 vv = __byte_perm(v, v, 0x1010);
            sts32(tp + (TO + 256) * 4, vv); sts16(tp + (TO + 257) * 4 + 2, v); sts16(tp + (TO + 255) * 4, v); sts64(tp + (TE + 256) * 4, vv, vv);
          } else sts16(t1 + 16 * r - ((T3 - T5) * 4 + 6) + 8 * hi, v);
        }
      }
#pragma unroll
      for (int r = 0; r < 2; r++) {
        const u32 v = pk_hf(D[4][2 * r], D[4][2 * r + 1]);
        if (r == 0 && lane == 0) { sts16(tp + T5 * 4 + 62 * 2, v); sts32(SM_KV + 4 * ksig, v & 0xffff); sts16(tp + (T9E + TEO) * 4 + 62 * 2, pk_hf(k2048, 0.f)); }
        else { sts16(te + 8 * r, v); sts16(to + 8 * r, v); }
        sts16(te + 8 * r + 16, v >> 16); sts16(to + 8 * r + 16, v >> 16);
      }
      __syncwarp();
#pragma unroll
      for (int r = 0; r < 4; r++) {
        const u32 v = pk_hf(D[r >> 1][2 * (r & 1) + 1], D[r >> 1][2 * (r & 1)]), t2 = tp + lane * 4 + 128 * r;
        sts32(t2 + TO * 4, v); sts16(t2 + TE * 4, v >> 16); sts16(t2 + (TE + 1) * 4 + 2, v);
      }
      __syncwarp();
    }
  } else if (w == (b < 108 ? 11 : ~0u)) {
    float c[4][4] = {};
    u32 aa = SM_UP + ((lane & 7) + 8 * (lane >> 4)) * 64 + ((((lane >> 3) & 1) ^ ((lane & 7) >> 1)) << 4);
    u32 ba = SM_SIL + (lane >> 3) * 16;
    uint4 a[2][10];
#define GLD(n) { _Pragma("unroll") for (int i = 0; i < 2; i++) { a[n][5 * i] = ldsm4(ba + i * 64); \
      _Pragma("unroll") for (int k = 0; k < 4; k++) a[n][5 * i + 1 + k] = ldsm4t((k & 2 ? aa ^ 32 : aa) + i * 2048 + (k & 1) * 1024); } aa += 4096; ba += 128; }
#define GMM(n) { _Pragma("unroll") for (int i = 0; i < 2; i++) _Pragma("unroll") for (int k = 0; k < 4; k++) { const uint4 f = a[n][5 * i + 1 + k], bb = a[n][5 * i]; \
      mma_bf(c[k], f.x, f.y, f.z, f.w, k & 1 ? bb.z : bb.x, k & 1 ? bb.w : bb.y); } }
    mb_wait(SM_MB);
    TS(56);
    GLD(0);
#pragma unroll 1
    for (int s = 0; s < 4; s++) { GLD(1); GMM(0); GLD(0); GMM(1); }
    GMM(0);
    const float v0 = (q & 1) ? c[0][2] + c[1][2] : c[0][0] + c[1][0], v1 = (q & 1) ? c[2][2] + c[3][2] : c[2][0] + c[3][0];
    str16(gs + (G_MOD + b * 128 + 2 * g + 16 * q), pk_bf(rbf((q & 2) ? v1 : v0) * F2M64, 0.f) | (g < 2 ? pm : 0));
    TS(57);
  }
  TS(6);
  u32 tid2 = tid;
  if (w < 4) {
    asm volatile("setmaxnreg.inc.sync.aligned.u32 232;");
    const u32 tid = tid2 + p.zero, w = tid >> 5, lane = tid & 31, g = lane >> 2, q = lane & 3, hi = g & 1, zr = tid >> 16, tp = SM_TAP + w * TAPS;
    const u32 pml = opq((g & 3) ? 0 : pm);
    const u32 tr = tp + ((hi ? TO : TE) + (g >> 1) - q) * 4;
    u32 T[33][4], B5[5][2], B3[5][2];
#pragma unroll
    for (int d = 0; d < 33; d++) {
      T[d][0] = lds32(tr + 32 * d); T[d][1] = lds32(tr + 32 * d + 16);
      T[d][2] = cpy(d ? T[d - 1][1] : zr, zr, 0); T[d][3] = cpy(T[d][0], zr, 1);
    }
    const u32 t33 = cpy(T[32][1], zr, 0), z33 = cpy(zr, zr, 0);
    const u32 bt = tp + (T5 + g - q) * 4;
#pragma unroll
    for (int d = 0; d < 5; d++) {
      B5[d][0] = lds32(bt + 32 * d); B5[d][1] = lds32(bt + 32 * d - 16);
      B3[d][0] = lds32(bt + 32 * d + (T3 - T5) * 4); B3[d][1] = lds32(bt + 32 * d - 16 + (T3 - T5) * 4);
    }
    u32 za = opq(SM_ZS + 16 + w * ZSS + ((lane >> 3) & 1) * ZPS + ((lane & 7) + (lane >> 4)) * 16);
    u32 wa = opq(SM_W + W5O + w * WSL + row16(lane));
    u32 sa = opq(SM_W + W9O + w * WSL + lane * 16);
    const u32 yo = opq(p.glo + G_Y - 1024 + b * BLK + 256 * q + w * 32 + 4 * g);
    char* yp = gptr(p, yo);
#define YINC() asm volatile("{.reg .u32 l, h; mov.b64 {l,h},%0; add.u32 l,l,1024; mov.b64 %0,{l,h};}" : "+l"(yp))
    const u32 fa = opq(SM_SC + 16 * w + 8), bw = opq((BW >> 4 * w) & 15), bs = opq((BS >> 4 * w) & 15);
    TS(8);
    u32 F;
    bsync(9, 384);
    TS(11);
    float A[4][4] = {};
    uint4 Z[4];
    Z[0] = ldsm4(za); Z[1] = ldsm4(za + 32);
#define STEP(s, b0, b1) { _Pragma("unroll") for (int i = 0; i < 4; i++) mma_hf_t(A[i], T[8 * i + 7 - (s)], b0, b1); }
#define PAIR(n) { Z[(n + 2) & 3] = ldsm4(za + 32 * (n + 2)); STEP(2 * n, Z[n].x, Z[n].y); STEP(2 * n + 1, Z[n].z, Z[n].w); }
#define LAST(N) mma8_hf(N, t33, z33, Z[3].y); float O[4]; mma_hf_o(O, A[0], T[0], Z[3].z, Z[3].w); \
    _Pragma("unroll") for (int i = 0; i < 3; i++) mma_hf_o(A[i], A[i + 1], T[8 * i + 8], Z[3].z, Z[3].w); \
    mma_hf_o(A[3], N, T[32], Z[3].z, Z[3].w);
#pragma unroll 1
    for (int j = 0; j < 4; j++) {
      PAIR(0);
      uint2 fc;
      asm volatile("ld.volatile.shared.v2.u32 {%0,%1},[%2];" : "=r"(fc.x), "=r"(fc.y) : "r"(fa));
      PAIR(1);
      F = __byte_perm(fu(uf(fc.x) * uf(fc.y)), 0, 0x3232);
      PAIR(2);
      Z[1] = ldsm4(za + 160); STEP(6, Z[3].x, Z[3].y);
      float N[4] = {};
      LAST(N);
      inc<128>(za);
      YINC();
      y_store<128>(O[0], O[1], O[2], O[3], F, pml, yp);
      TSJ(j);
    }
    bsyncr(bw);
    uint4 a5 = ldsm4t(wa);
#pragma unroll
    for (int half = 0; half < 2; half++) {
    if (half) bsyncr(bs);
#pragma unroll 1
    for (int j = half ? 8 : 4; j < (half ? 13 : 8); j++) {
      const uint4 a3 = ldsm4t(wa + (W3O - W5O));
      uint4 s3 = {0, 0, 0, 0};
      if (half) s3 = lds128(sa);
      PAIR(0);
      float N[4] = {};
#pragma unroll
      for (int i = 0; i < 4; i++) mma_hf(A[i], a5.x, a5.y, a5.z, a5.w, B5[i][0], B5[i][1]);
      mma_hf(N, a5.x, a5.y, a5.z, a5.w, B5[4][0], B5[4][1]);
      asm volatile("{add.u32 %0,%0,256; xor.b32 %0,%0,32;}" : "+r"(wa));
      a5 = ldsm4t(wa);
      PAIR(1);
#pragma unroll
      for (int i = 0; i < 4; i++) mma_hf(A[i], a3.x, a3.y, a3.z, a3.w, B3[i][0], B3[i][1]);
      mma_hf(N, a3.x, a3.y, a3.z, a3.w, B3[4][0], B3[4][1]);
      PAIR(2);
      Z[1] = ldsm4(za + 160); STEP(6, Z[3].x, Z[3].y);
      LAST(N);
      inc<128>(za);
      if (half) inc<512>(sa);
      YINC();
      if (!half) y_store<128>(O[0], O[1], O[2], O[3], F, pml, yp);
      else y_store<128>(O[0] + uf(s3.x), O[1] + uf(s3.y), O[2] + uf(s3.z), O[3] + uf(s3.w), F, pml, yp);
      TSJ(j);
    }
    }
    {
      asm volatile("mov.u32 %0,%%tid.x;" : "=r"(tid2));
      const uint4 s3 = lds128(sa), s4 = lds128(sa + 512), s5 = lds128(sa + 1024);
      float X[3][4] = {{uf(s4.x), uf(s4.y), uf(s4.z), uf(s4.w)}, {}, {uf(s5.x), uf(s5.y), uf(s5.z), uf(s5.w)}};
#pragma unroll
      for (int ty = 0; ty < 2; ty++) {
        const uint4 a = !ty ? a5 : ldsm4t(wa + ty * (W3O - W5O)), c = ldsm4t((wa ^ 32) + 256 + ty * (W3O - W5O)), d = ldsm4t(wa + 512 + ty * (W3O - W5O));
#pragma unroll
        for (int i = 0; i < 3; i++) mma_hf(A[i], a.x, a.y, a.z, a.w, ty ? B3[i][0] : B5[i][0], ty ? B3[i][1] : B5[i][1]);
#pragma unroll
        for (int i = 0; i < 2; i++) mma_hf(X[i], c.x, c.y, c.z, c.w, ty ? B3[i][0] : B5[i][0], ty ? B3[i][1] : B5[i][1]);
        mma_hf(X[2], d.x, d.y, d.z, d.w, ty ? B3[0][0] : B5[0][0], ty ? B3[0][1] : B5[0][1]);
      }
#pragma unroll
      for (int n = 0; n < 4; n++) {
        const uint4 f0 = n < 2 ? Z[n] : ldsm4(za + 32 * n), f1 = ldsm4(za + 32 * n + 128), f2 = ldsm4(za + 32 * n + 256);
#pragma unroll
        for (int s = 2 * n; s < 2 * n + 2; s++) {
#pragma unroll
          for (int i = 0; i < 3; i++) mma_hf_t(A[i], T[8 * i + 7 - s], s & 1 ? f0.z : f0.x, s & 1 ? f0.w : f0.y);
          mma_hf_t(X[0], T[7 - s], s & 1 ? f1.z : f1.x, s & 1 ? f1.w : f1.y); mma_hf_t(X[1], T[15 - s], s & 1 ? f1.z : f1.x, s & 1 ? f1.w : f1.y);
          mma_hf_t(X[2], T[7 - s], s & 1 ? f2.z : f2.x, s & 1 ? f2.w : f2.y);
        }
      }
      y_store<128>(A[0][0] + uf(s3.x), A[0][1] + uf(s3.y), A[0][2] + uf(s3.z), A[0][3] + uf(s3.w), F, pml, yp + 1024);
      y_store<128>(A[1][0] + X[0][0], A[1][1] + X[0][1], A[1][2] + X[0][2], A[1][3] + X[0][3], F, pml, yp + 2048);
      y_store<128>(A[2][0] + X[1][0] + X[2][0], A[2][1] + X[1][1] + X[2][1], A[2][2] + X[1][2] + X[2][2], A[2][3] + X[1][3] + X[2][3], F, pml, yp + 3072);
    }
    barrive(12, N12);
    TS(15);
  } else {
    asm volatile("setmaxnreg.dec.sync.aligned.u32 136;");
    const u32 t8 = tid - 128, pml = (g & 3) ? 0 : pm;
    {
      TS(12);
      if (tid == 288) l2_pre<WSH / 2>(p.wg + (b * WSH + WSH / 2));
      const char* zs = gs + ((16 * w - 64 + (lane >> 3)) * BLK + b * 128 + ((lane & 7) * 16 ^ rho * 64));
      const char* zs4 = gs + ((t8 >> 1) * BLK + (Ps >> 4) * 512 + (Ps & 6) * 64 + ((Ps >> 2 ^ Ps) & 2) * 32 + (Ps & 1) * 32 + (t8 & 1) * 16);
      uint4 v[5];
      v[4].x = INVAL;
      const u32 d = lane < 4 ? chan(b, lane) : Ps;
      const char* mp = gs + (G_MOD + (d >> 5) * 128 + (d & 24) * 2);
      uint4 ta, tc;
      ta.x = tc.x = INVAL;
      const u32 t9 = w == 9 ? pm : INVAL;
      pin2(zr, zs, zs4);
      conv();
      POLLM({ rld128<TAGM>(ta, mp, t9); rld128<TAGM>(tc, mp + MODJ, t9); rld128<TAGM>(v[4], zs4, pm); }, lop3<0xbe>(v[4].x, pm, ne3(ta.x, tc.x, t9)), TAGM, 1);
      TS(58);
#pragma unroll
      for (int j = 0; j < 4; j++) v[j] = ldr128(zs + j * 4 * BLK);
      if (w == 9) {
        const u32 aw = (d & 4) ? ((d & 2) ? ta.w : ta.z) : ((d & 2) ? ta.y : ta.x & ~TAGM);
        const u32 cw = (d & 4) ? ((d & 2) ? tc.w : tc.z) : ((d & 2) ? tc.y : tc.x & ~TAGM);
        const float sa = ((d & 1) ? bhi(aw) : blo(aw)) * F2P64, c1 = rbf(fmaf((d & 1) ? bhi(cw) : blo(cw), F2P64, 1.f));
        const u32 EM = min(max(fu(fmaxf(32.f * fabsf(c1), fabsf(sa))) >> 23, 80u), 250u);
        const float inv = uf((264 - EM) << 23);
        if (lane < 5) { sts64(SM_SC + 16 * lane, pk_hf(16.f * c1 * inv, 16.f * c1 * inv), pk_hf(sa * inv, sa * inv)); sts32(SM_SC + 16 * lane + 8, (EM - 74) << 23); }
        TS(10);
      }
#define MARKERS() if (tid == 256) { \
        _Pragma("unroll") for (int i = MT / 2; i < 8; i++) bulk_out<2048>(gs + (G_Y + 2048 * i + b * BLK), SM_INV); \
        bulk_out<2048>(gs + (G_PART + b * 2048), SM_INV); bulk_out<512>(gs + (G_ACT + b * 512), SM_INV); \
        bulk_out<32>(gs + (G_KEY + b * KST), SM_INV); if (!rho) bulk_out<128>(gs + (G_ACT + Ps * 128), SM_INV); \
        asm volatile("cp.async.bulk.commit_group;" ::: "memory"); }
#define GATE() { mb_expect(SM_MB + 8, rho ? SLV : 46080); \
        _Pragma("unroll") for (int i = 0; i < 3; i++) tma3d(SM_GATE + 12288 * i, &tm_gate, SM_MB + 8, 32 * b, i); \
        if (!rho) tma3d(SM_GATE + SLV, &tm_gs, SM_MB + 8, 4096 + 4 * b, 0); }
#define UP() { mb_expect(SM_MB + 16, rho ? SLV : 46080); tma3d(SM_UP, &tm_up, SM_MB + 16, 32 * b, 0); \
        if (!rho) tma3d(SM_UP + SLV, &tm_us, SM_MB + 16, 4096 + 4 * b, 0); }
      bsync(8, 256);
      const uint2 cc = lds64(SM_SC + 8 * (t8 & 6)), c4 = lds64(SM_SC + 64);
      sts128(SM_Z4 + 256 + (t8 & 1) * ZP4 + (t8 >> 1) * 16, hfma(v[4].x & ~TAGM, c4.x, c4.y), hfma(v[4].y, c4.x, c4.y), hfma(v[4].z, c4.x, c4.y), hfma(v[4].w, c4.x, c4.y));
      if (t8 < 96) sts128(t8 < 64 ? SM_ZS + (t8 & 7) * ZPS + (t8 >> 3) * 16 : SM_Z4 + (t8 & 1) * ZP4 + (t8 & 30) * 8, 0, 0, 0, 0);
      asm volatile("cp.async.bulk.wait_group.read 0;" ::: "memory");
      const u32 dst = SM_ZS + 128 + (t8 & 7) * ZPS + (16 * w - 64 + (lane >> 3)) * 16;
      pin(zr, dst);
      conv();
      POLLS(_Pragma("unroll") for (int j = 0; j < 4; j++) sts128(dst + j * 64, hfma(v[j].x & ~TAGM, cc.x, cc.y), hfma(v[j].y, cc.x, cc.y), hfma(v[j].z, cc.x, cc.y), hfma(v[j].w, cc.x, cc.y)),
            _Pragma("unroll") for (int j = 0; j < 4; j++) rld128<TAGM>(v[j], zs + j * 4 * BLK, pm), ne3(v[0].x, v[1].x, pm) | ne3(v[2].x, v[3].x, pm), TAGM, 1);
      TS(9);
      bsync(9, 384);
      TS(11);
      MARKERS();
      if (w == 10 && s2u(smem) != SM0) __trap();
      const bool lng = w < 8 || w == 9;
      const u32 ts = lane + 32 * (w == 8 ? 0 : w - 9), c = min(ts, 71u), ma = SM_MODS + 16 * c;
      const u32 sig = lng ? ksig : ts >> 4, l2 = lng ? lane : 32 + (ts & 15);
      const char* mq = gs + (G_MOD + (c >> 2) * 128 + (c & 3) * 16);
      if (!lng) {
#pragma unroll
        for (int j = 0; j < 6; j++) cpa16(ma + 1152 * j, mq + j * MODJ);
        cpa16(ma + 1152 * 6, p.dsk + 16 * c); cpa16(ma + 1152 * 7, p.wr + 16 * c);
        if (tid == 352) {
          PROXY_FENCE();
          GATE();
          UP();
        }
      }
      const u32 wb = SM_W + sig * WSL;
      if (sig < 5) {
        const u32 za = (sig < 4 ? SM_ZS + 128 + sig * ZSS : SM_Z4 + 256) + l2 * 32, zb = za + (sig < 4 ? ZPS : ZP4);
        const uint4 c0 = lds128(zb - 32), c1 = lds128(za - 16), c2 = lds128(zb - 16), c3 = lds128(za), c4 = lds128(zb), c5 = lds128(za + 16), c6 = lds128(zb + 16);
        const u32 P[25] = {c0.z, c0.w, c1.x, c1.y, c1.z, c1.w, c2.x, c2.y, c2.z, c2.w, c3.x, c3.y, c3.z, c3.w, c4.x, c4.y, c4.z, c4.w, c5.x, c5.y, c5.z, c5.w, c6.x, c6.y, c6.z};
        u32 Q[25], D1[24], F4[23], W5[21], W3[17];
#pragma unroll
        for (int j = 1; j < 25; j++) Q[j] = __byte_perm(P[j - 1], P[j], 0x5432);
#pragma unroll
        for (int j = 1; j < 24; j++) D1[j] = hadd(P[j], Q[j]);
#pragma unroll
        for (int j = 2; j < 23; j++) F4[j] = hadd(D1[j], D1[j - 1]);
#pragma unroll
        for (int n = 0; n < 21; n++) W5[n] = hadd(F4[n + 2], P[n]);
#pragma unroll
        for (int n = 0; n < 17; n++) W3[n] = hadd(Q[n + 8], D1[n + 7]);
        const u32 a0 = wb + W5O + 64 * l2 + 16 * ((l2 >> 1) & 3);
#pragma unroll
        for (int i = 0; i < 4; i++) {
          sts128(a0 ^ (16 * i), W5[4 * i + 5], W5[4 * i + 6], W5[4 * i + 7], W5[4 * i + 8]);
          sts128((a0 ^ (16 * i)) + (W3O - W5O), W3[4 * i + 1], W3[4 * i + 2], W3[4 * i + 3], W3[4 * i + 4]);
        }
        if (lng) {
          if (lane < 16) sts128(wb + (lane & 7) * 16 + (lane & 8) * 400, 0, 0, 0, 0);
          const u32 a1 = wb + 32 * lane + 16 * ((lane >> 2) & 1);
#pragma unroll
          for (int i = 0; i < 4; i++) {
            const u32 a = (a1 ^ (16 * (i >> 1))) + 1024 * (i & 1), n = 4 * i;
            sts128(a + V2O, hadd(Q[n + 9], P[n + 8]), hadd(Q[n + 10], P[n + 9]), hadd(Q[n + 11], P[n + 10]), hadd(Q[n + 12], P[n + 11]));
            sts128(a + W9O, hadd(F4[n + 4], W5[n]), hadd(F4[n + 5], W5[n + 1]), hadd(F4[n + 6], W5[n + 2]), hadd(F4[n + 7], W5[n + 3]));
            sts128(a + W7O, hadd(F4[n + 6], W3[n]), hadd(F4[n + 7], W3[n + 1]), hadd(F4[n + 8], W3[n + 2]), hadd(F4[n + 9], W3[n + 3]));
          }
        }
      }
      if (w < 8) barriver((BW >> (4 * w - 16)) & 15);
      else if (!(w & 1)) { barriver((BW >> (4 * w - 32)) & 15); barriver((BW >> (4 * w - 28)) & 15); }
      __syncwarp();
      TS(32);
      if (lng) {
        const u32 wa = wb + ((lane >> 3) & 1) * 1024 + (((lane & 7) ^ (lane >> 4)) + 8 * (lane >> 4)) * 16;
        const u32 kv = lds32(SM_KV + 4 * sig), bi = (g >> 1) == q ? (hi ? kv << 16 : kv) : 0u;
        float acc[8][4] = {};
#pragma unroll
        for (int j = 0; j < 4; j++) { const uint4 a = ldsm4t(wa + V2O + j * 256); mma8_hf(acc[2 * j], a.x, a.y, bi); mma8_hf(acc[2 * j + 1], a.z, a.w, bi); }
        u32 bt = tp + (T9E + hi * TEO + (g >> 1) - q) * 4, wt = wa + W9O;
#pragma unroll 1
        for (int ty = 0; ty < 2; ty++) {
          uint4 a[4];
#pragma unroll
          for (int be = 0; be < 4; be++) a[be] = ldsm4t(wt + be * 256);
          u32 b1 = lds32(bt - 16);
#pragma unroll
          for (int d = 0; d < 8; d++) {
            const u32 b0 = lds32(bt + 16 * d);
#pragma unroll
            for (int be = 0; be < 4; be++) if (d + 2 * be < 8) mma_hf(acc[d + 2 * be], a[be].x, a[be].y, a[be].z, a[be].w, b0, b1);
            b1 = b0;
          }
          bt += (T7E - T9E) * 4; wt += W7O - W9O;
        }
        __syncwarp();
#pragma unroll
        for (int j = 0; j < 8; j++) sts128(wb + W9O + j * 512 + lane * 16, fu(acc[j][0]), fu(acc[j][1]), fu(acc[j][2]), fu(acc[j][3]));
        if (w != 9) barriver((BS >> (4 * w - 16)) & 15);
        TS(34);
      }
      if (!lng) {
        asm volatile("cp.async.wait_all;" ::: "memory");
        uint4 md[6];
#pragma unroll
        for (int j = 0; j < 6; j++) md[j] = lds128(ma + 1152 * j);
        const uint4 dk = lds128(ma + 1152 * 6), wr = lds128(ma + 1152 * 7);
        POLLW(_Pragma("unroll") for (int j = 0; j < 6; j++) md[j] = ldr128(mq + j * MODJ),
              ((md[0].x ^ pm) | (md[1].x ^ pm) | (md[2].x ^ pm) | (md[3].x ^ pm) | (md[4].x ^ pm) | (md[5].x ^ pm)) & TAGM, 4);
#pragma unroll
        for (int j = 0; j < 6; j++) {
          const u32 o = (j % 3 == 1) ? BONE : 0x80008000u;
          md[j] = make_uint4(bfma(md[j].x & ~TAGM, B2P64, o), bfma(md[j].y, B2P64, o), bfma(md[j].z, B2P64, o), bfma(md[j].w, B2P64, o));
          if (j > 2) sts128(ma + 1152 * j, md[j].x, md[j].y, md[j].z, md[j].w);
        }
        const uint4 gd = make_uint4(bmul(md[2].x, dk.x), bmul(md[2].y, dk.y), bmul(md[2].z, dk.z), bmul(md[2].w, dk.w));
#pragma unroll
        for (int j = 0; j < 2; j++) sts128(ma + 1152 * j, bmul(md[j].x, gd.x), bmul(md[j].y, gd.y), bmul(md[j].z, gd.z), bmul(md[j].w, gd.w));
        sts128(ma + 2304, bmul(md[2].x, B2P64), bmul(md[2].y, B2P64), bmul(md[2].z, B2P64), bmul(md[2].w, B2P64));
        const uint4 H = make_uint4(bmul(md[4].x, wr.x), bmul(md[4].y, wr.y), bmul(md[4].z, wr.z), bmul(md[4].w, wr.w));
        sts128(ma + 1152 * 7, H.x, H.y, H.z, H.w);
        sts128(ma + 1152 * 8, bfma(md[4].x, wr.x, H.x ^ 0x80008000u), bfma(md[4].y, wr.y, H.y ^ 0x80008000u), bfma(md[4].z, wr.z, H.z ^ 0x80008000u), bfma(md[4].w, wr.w, H.w ^ 0x80008000u));
        float c4[4] = {};
        mma_bf(c4, md[4].x, md[3].x, md[4].y, md[3].y, wr.x, wr.y); mma_bf(c4, md[4].z, md[3].z, md[4].w, md[3].w, wr.z, wr.w);
        if (q == g >> 1) sts64(SM_RC + (ts >> 2) * 8, fu(hi ? c4[1] : c4[0]), fu(hi ? c4[3] : c4[2]));
        if (ts < 2) sts128(SM_ONE + 16 * ts, ts ? 0 : BONE, ts ? 0 : BONE, ts ? 0 : BONE, ts ? 0 : BONE);
        TS(14);
        if (w == 8) asm volatile("cp.async.bulk.wait_group 0;" ::: "memory");
        bsync(13, 96);
        if (w == 8) { barriver(2); barriver(3); barriver(5); barriver(6); barrive(7, 64); }
      }
      if (w == 9) barrive(11, 128);
    }
    const u32 jw = w < 6 ? w ^ 1 : w < 8 ? w : max(w - 4, 5u);
    const int u0 = 4 * (jw - 4) + 2 * rho;
    const u32 t4 = SM_TAP + 4 * TAPS, s3a = SM_W + 4 * WSL + (u0 >= 8 ? W9O + (u0 - 8) * 512 : V2O) + lane * 16, hb = (0x4987 >> (4 * jw - 16)) & 15;
#define FARL() { u32 wa = (SM_W + 4 * WSL + W5O + row16(lane) + (u0 - 3) * 256) ^ 32, bt = t4 + (T5 + g - q) * 4; \
      _Pragma("unroll 1") for (int al = min(u0 - 2, 6); al > 0; al--) { \
        _Pragma("unroll") for (int ty = 0; ty < 2; ty++) { \
          const uint4 a = ldsm4t(wa + ty * (W3O - W5O)); \
          const u32 bb = bt + ty * (T3 - T5) * 4; \
          mma_hf(acc[ty], a.x, a.y, a.z, a.w, lds32(bb - 32), lds32(bb - 48)); \
          mma_hf(acc[2 + ty], a.x, a.y, a.z, a.w, lds32(bb), lds32(bb - 16)); \
        } \
        wa = (wa - 256) ^ 32; bt += 32; } }
    if (w < 8) {
      u32 tr = t4 + ((hi ? TO : TE) + (g >> 1) - q) * 4;
      u32 zb = SM_Z4 + 256 + ((lane >> 3) & 1) * ZP4 + u0 * 128 + (lane & 7) * 16 + (lane >> 4) * 128;
      float acc[4][4] = {};
      u32 prev = 0;
#pragma unroll 1
      for (int it = min(u0 + 2, 4); it; it--) {
#pragma unroll
        for (int s = 0; s < 8; s++) {
          const uint4 z = ldsm4(zb - 16 * s);
          const u32 t0 = lds32(tr + 32 * s), t1 = lds32(tr + 32 * s + 16);
          mma_hf(acc[s & 1], t0, t1, prev, t0, z.x, z.y);
          mma_hf(acc[2 + (s & 1)], t0, t1, prev, t0, z.z, z.w);
          prev = t1;
        }
        zb -= 128; tr += 256;
      }
      {
        const uint4 z = ldsm4(zb); const u32 t0 = lds32(tr), t1 = lds32(tr + 16);
        mma_hf(acc[0], t0, t1, prev, t0, z.x, z.y); mma_hf(acc[2], t0, t1, prev, t0, z.z, z.w);
        if (jw > 4) { const uint4 y = ldsm4(zb - 16); mma8_hf(acc[1], t1, zr, y.y); mma8_hf(acc[3], t1, zr, y.w); }
      }
      asm volatile("bar.sync %0,64;" ::"r"(hb) : "memory");
      TS(35);
      const uint2 fc = lds64(SM_SC + 16 * 4 + 8);
      const u32 F = __byte_perm(fu(uf(fc.x) * uf(fc.y)), 0, 0x3232);
      char* yp = gs + (G_Y + 16384 + (32 * jw - 128 + 16 * rho + 4 * (q >> 1) + ((b >> 2) & 3)) * BLK + (q & 1) * 1024 + (b & 112) * 4 + (b & 2) * 16 + 4 * g);
#pragma unroll
      for (int j = 0; j < 2; j++) {
        uint4 s3 = {0, 0, 0, 0};
        if (u0 >= 4) s3 = lds128(s3a + j * 512);
        y_store<512>(acc[2 * j][0] + acc[2 * j + 1][0] + uf(s3.x), acc[2 * j][1] + acc[2 * j + 1][1] + uf(s3.y), acc[2 * j][2] + acc[2 * j + 1][2] + uf(s3.z),
                acc[2 * j][3] + acc[2 * j + 1][3] + uf(s3.w), F, pml, yp + j * 8 * BLK);
      }
      TS(16);
    } else {
      if (w != 9) {
        bsync(11, 128);
        float acc[4][4] = {};
        if (u0 >= 8) {
#pragma unroll
          for (int j = 0; j < 2; j++) { const uint4 t = lds128(s3a + j * 512); acc[2 * j][0] = uf(t.x); acc[2 * j][1] = uf(t.y); acc[2 * j][2] = uf(t.z); acc[2 * j][3] = uf(t.w); }
        }
        FARL();
#pragma unroll
        for (int j = 0; j < 2; j++)
          sts128(s3a + j * 512, fu(acc[2 * j][0] + acc[2 * j + 1][0]), fu(acc[2 * j][1] + acc[2 * j + 1][1]), fu(acc[2 * j][2] + acc[2 * j + 1][2]), fu(acc[2 * j][3] + acc[2 * j + 1][3]));
        asm volatile("bar.arrive %0,64;" ::"r"(hb) : "memory");
        TS(16);
      }
      if (tid == 352) { mb_wait(SM_MB + 8); mb_wait(SM_MB + 16); l2_pre<WSH>(p.wd + b * WSH); }
      TS(17);
    }
  }
  post_conv(p, &tm_down, tid2 + p.zero, b, b3);
  TSD();
}

typedef CUresult (*EncFn)(CUtensorMap*, CUtensorMapDataType, cuuint32_t, void*, const cuuint64_t*, const cuuint64_t*, const cuuint32_t*, const cuuint32_t*,
                          CUtensorMapInterleave, CUtensorMapSwizzle, CUtensorMapL2promotion, CUtensorMapFloatOOBfill);
static void make_map(EncFn enc, CUtensorMap* tm, void* ptr, int cols, int rows, int bw, int nb, CUtensorMapSwizzle sw, int gr = 192, int prom = 0) {
  cuuint64_t gd[3] = {(cuuint64_t)cols, (cuuint64_t)gr, (cuuint64_t)(rows / gr)}, gs[2] = {(cuuint64_t)cols * 2, (cuuint64_t)cols * 2 * gr};
  cuuint32_t bd[3] = {(cuuint32_t)bw, (cuuint32_t)gr, (cuuint32_t)nb}, es[3] = {1, 1, 1};
  enc(tm, CU_TENSOR_MAP_DATA_TYPE_BFLOAT16, 3, ptr, gd, gs, bd, es, CU_TENSOR_MAP_INTERLEAVE_NONE, sw, (CUtensorMapL2promotion)prom, CU_TENSOR_MAP_FLOAT_OOB_FILL_NONE);
}
extern "C" void kernel_launch(void* const* d_in, const int* in_sizes, int n_in, void* d_out, int out_size) {
  static EncFn enc = nullptr;
  static void* scratch = nullptr;
  if (!enc) {
    cudaGetSymbolAddress(&scratch, g_s);
    const uintptr_t last = (uintptr_t)scratch + G_END;
    if ((u32)last < G_END) scratch = (void*)(last - (u32)last);
    cudaDriverEntryPointQueryResult qr;
    cudaGetDriverEntryPoint("cuTensorMapEncodeTiled", (void**)&enc, cudaEnableDefault, &qr);
    cudaFuncSetAttribute(fused_kernel, cudaFuncAttributeMaxDynamicSharedMemorySize, SM_TOTAL);
  }
  CUtensorMap tm_mod, tm_gate, tm_gs, tm_up, tm_us, tm_down;
  make_map(enc, &tm_mod, d_in[13], 3456, 576, 32, 3, CU_TENSOR_MAP_SWIZZLE_64B, 192, 0);
  make_map(enc, &tm_gate, d_in[9], 4608, 576, 32, 1, CU_TENSOR_MAP_SWIZZLE_64B, 192, 0);
  make_map(enc, &tm_gs, d_in[9], 4608, 576, 8, 3, CU_TENSOR_MAP_SWIZZLE_NONE);
  make_map(enc, &tm_up, d_in[10], 4608, 576, 32, 3, CU_TENSOR_MAP_SWIZZLE_64B, 192, 0);
  make_map(enc, &tm_us, d_in[10], 4608, 576, 8, 3, CU_TENSOR_MAP_SWIZZLE_NONE, 192, 0);
  make_map(enc, &tm_down, d_in[11], 576, 4608, 64, 1, CU_TENSOR_MAP_SWIZZLE_128B, 96);
  Prm p;
  p.x = (const char*)d_in[0]; p.la = (const char*)d_in[1]; p.ai = (const char*)d_in[2]; p.cr = (const char*)d_in[3];
  p.ci = (const char*)d_in[4]; p.ldt = (const char*)d_in[5]; p.dsk = (const char*)d_in[6]; p.wr = (const char*)d_in[8];
  p.wg = (const char*)d_in[9]; p.wu = (const char*)d_in[10]; p.wd = (const char*)d_in[11];
  p.c = (const char*)d_in[12]; p.out = (char*)d_out; p.zero = 0; p.gs = (char*)scratch; p.glo = (u32)(uintptr_t)scratch; p.ghi = (u32)((uintptr_t)scratch >> 32);
  fused_kernel<<<128, 384, SM_TOTAL>>>(p, tm_mod, tm_gate, tm_gs, tm_up, tm_us, tm_down);
}
```
